```python
import torch

def _softmax(x, axis=-1):
    return torch.softmax(x, dim=axis)

def _gelu(x):
    return torch.nn.functional.gelu(x, approximate='tanh')

def _silu(x):
    return torch.nn.functional.silu(x)

def _sigmoid(x):
    return torch.sigmoid(x)

def _layernorm(x, axis=-1, eps=1e-05):
    m = x.mean(dim=axis, keepdim=True)
    v = x.var(dim=axis, keepdim=True, unbiased=False)
    return (x - m) / torch.sqrt(v + eps)

def _scatter_add(tgt, idx, src, axis=0):
    return tgt.clone().index_add_(axis, idx, src)

def _segment_sum(src, seg, n):
    out = torch.zeros((n,) + src.shape[1:], dtype=src.dtype)
    return out.index_add_(0, seg, src)

def _pad(x, pw):
    flat = tuple((v for pair in reversed(pw) for v in pair))
    return torch.nn.functional.pad(x, flat)
kernel_name = 'concat_heads__memory_aug_recurrent_mem_tr__spectral_gfnet__prompt'

def setup_inputs():

    _w = lambda a: (lambda t: t.to(torch.bfloat16) if t.is_floating_point() else t)(torch.as_tensor(a))

    def _A_setup():
        B, S, Dm = (1, 2048, 1024)
        H, Dh = (32, 128)
        M, seg = (8, 32)
        seg = min(seg, S)
        S = S // seg * seg
        return {'x': _w((lambda *s: torch.randn(*s, dtype=torch.bfloat16) * 0.05)(B, S, Dm)), 'mem0': _w((lambda *s: torch.randn(*s, dtype=torch.bfloat16) * 0.4)(B, M, Dm)), 'Wq': _w((lambda *s: torch.randn(*s, dtype=torch.bfloat16) * 6.4)(Dm, H, Dh) * Dm ** (-0.5)), 'Wk': _w((lambda *s: torch.randn(*s, dtype=torch.bfloat16) * 6.4)(Dm, H, Dh) * Dm ** (-0.5)), 'Wv': _w((lambda *s: torch.randn(*s, dtype=torch.bfloat16) * 0.4)(Dm, H, Dh) * Dm ** (-0.5)), 'Wo': _w((lambda *s: torch.randn(*s, dtype=torch.bfloat16) * 0.4)(H, Dh, Dm) * (H * Dh) ** (-0.5)), 'seg_len': seg}
    _A_in = _A_setup()

    def _B_setup():
        B, S, D = (1, 2048, 1024)
        Df = D // 2 + 1
        return {'x': _w((lambda *s: torch.randn(*s, dtype=torch.bfloat16) * 0.05)(B, S, D)), 'w_r': _w((lambda *s: torch.randn(*s, dtype=torch.bfloat16) * 3.2)(S, Df) * 0.02), 'w_i': _w((lambda *s: torch.randn(*s, dtype=torch.bfloat16) * 3.2)(S, Df) * 0.02)}
    _B_in = _B_setup()
    return {'A_x': _A_in['x'], 'A_mem0': _A_in['mem0'], 'A_Wq': _A_in['Wq'], 'A_Wk': _A_in['Wk'], 'A_Wv': _A_in['Wv'], 'A_Wo': _A_in['Wo'], 'A_seg_len': _A_in['seg_len'], 'B_x': _B_in['x'], 'B_w_r': _B_in['w_r'], 'B_w_i': _B_in['w_i']}

def reference(A_x, A_mem0, A_Wq, A_Wk, A_Wv, A_Wo, A_seg_len, B_x, B_w_r, B_w_i):

    def _A_ref(x, mem0, Wq, Wk, Wv, Wo, seg_len):
        B, S, Dm = x.shape
        H, Dh = (Wq.shape[1], Wq.shape[2])
        M = mem0.shape[1]
        scale = Dh ** (-0.5)
        n_seg = S // seg_len
        L = M + seg_len
        idx = torch.arange(L)
        mask = (idx[:, None] < M) | (idx[:, None] >= idx[None, :])
        mem = mem0
        outs = []
        for s in range(n_seg):
            xs = x[:, s * seg_len:(s + 1) * seg_len, :].clone()
            h = torch.concatenate([mem, xs], axis=1)
            q = torch.einsum('btd,dhe->bhte', h, Wq)
            k = torch.einsum('btd,dhe->bhte', h, Wk)
            v = torch.einsum('btd,dhe->bhte', h, Wv)
            scores = torch.einsum('bhqe,bhke->bhqk', q, k) * scale
            scores = torch.where(mask[None, None], scores, -1000000000.0)
            p = _softmax(scores, axis=-1)
            o = torch.einsum('bhqk,bhke->bhqe', p, v)
            o = torch.einsum('bhte,hed->btd', o, Wo)
            mem = o[:, :M, :].clone()
            outs.append(o[:, M:, :])
        return torch.concatenate(outs, axis=1)

    def _B_ref(x, w_r, w_i):
        B, S, D = x.shape
        X = (lambda x, axes=(-2, -1): torch.fft.rfft2(x.float(), dim=axes))(x, axes=(-2, -1))
        W = w_r + 1j * w_i
        X = X * W
        y = (lambda x, s, axes=(-2, -1): torch.fft.irfft2(x, s=s, dim=axes).to(torch.bfloat16))(X, (S, D), axes=(-2, -1))
        return y
    a = _A_ref(A_x, A_mem0, A_Wq, A_Wk, A_Wv, A_Wo, A_seg_len)
    b = _B_ref(B_x, B_w_r, B_w_i)
    return torch.concatenate([a, b], axis=-1)
```

```cpp
#include <cuda_runtime.h>
#include <cuda_bf16.h>
#include <cuda.h>
#include <stdint.h>
#include <stdio.h>

typedef __nv_bfloat16 bf16;

#define SEQ 2048
#define DM 1024
#define NH 32
#define DH 128
#define NSEG 64
#define HD (NH * DH)

#define XS_BYTES (16u << 20)
__device__ uint4 g_xs[2 * XS_BYTES / 16];
#define XO_SLOT (1u << 23)
#define XO_HEAD (160u << 10)
#define XO_CQK 0u
#define XO_XF (16u << 10)
#define XO_XKV (32u << 10)
#define XO_XQ (96u << 10)
#define XO_CV (128u << 10)
#define XO_R (6u << 20)
#define XO_B (7u << 20)
__device__ bf16 g_ox[SEQ * HD];
__device__ float2 g_F[SEQ * 520];

#define DEVI __device__ __forceinline__

DEVI uint32_t smem_u32(const void* p) { return (uint32_t)__cvta_generic_to_shared(p); }
DEVI void mbar_init(uint32_t bar, uint32_t cnt) { asm volatile("mbarrier.init.shared::cta.b64 [%0], %1;" ::"r"(bar), "r"(cnt) : "memory"); }
DEVI void mbar_expect(uint32_t bar, uint32_t bytes) { asm volatile("mbarrier.arrive.expect_tx.shared::cta.b64 _, [%0], %1;" ::"r"(bar), "r"(bytes) : "memory"); }
DEVI void mbar_arrive(uint32_t bar) { asm volatile("mbarrier.arrive.shared::cta.b64 _, [%0];" ::"r"(bar) : "memory"); }
DEVI void mbar_wait(uint32_t bar, uint32_t parity) {
    uint32_t done;
    int it = 0;
    do {
        asm volatile("{\n.reg .pred p;\nmbarrier.try_wait.parity.shared::cta.b64 p, [%1], %2;\nselp.u32 %0, 1, 0, p;\n}\n"
                     : "=r"(done) : "r"(bar), "r"(parity) : "memory");
        if (++it > (1 << 22)) __trap();
    } while (!done);
}
DEVI void tma2d(uint32_t dst, const CUtensorMap* tm, uint32_t bar, int c0, int c1) {
    asm volatile("cp.async.bulk.tensor.2d.shared::cluster.global.mbarrier::complete_tx::bytes [%0], [%1, {%3, %4}], [%2];"
                 ::"r"(dst), "l"(tm), "r"(bar), "r"(c0), "r"(c1) : "memory");
}
DEVI void tma3d(uint32_t dst, const CUtensorMap* tm, uint32_t bar, int c0, int c1, int c2) {
    asm volatile("cp.async.bulk.tensor.3d.shared::cluster.global.mbarrier::complete_tx::bytes [%0], [%1, {%3, %4, %5}], [%2];"
                 ::"r"(dst), "l"(tm), "r"(bar), "r"(c0), "r"(c1), "r"(c2) : "memory");
}
DEVI void ldsm4(uint32_t (&r)[4], uint32_t a) {
    asm volatile("ldmatrix.sync.aligned.m8n8.x4.shared.b16 {%0,%1,%2,%3}, [%4];" : "=r"(r[0]), "=r"(r[1]), "=r"(r[2]), "=r"(r[3]) : "r"(a) : "memory");
}
DEVI void ldsm4t(uint32_t (&r)[4], uint32_t a) {
    asm volatile("ldmatrix.sync.aligned.m8n8.x4.trans.shared.b16 {%0,%1,%2,%3}, [%4];" : "=r"(r[0]), "=r"(r[1]), "=r"(r[2]), "=r"(r[3]) : "r"(a) : "memory");
}
DEVI uint32_t ldsm1(uint32_t a) {
    uint32_t r;
    asm volatile("ldmatrix.sync.aligned.m8n8.x1.shared.b16 {%0}, [%1];" : "=r"(r) : "r"(a) : "memory");
    return r;
}
DEVI void stsm4(uint32_t a, uint32_t r0, uint32_t r1, uint32_t r2, uint32_t r3) {
    asm volatile("stmatrix.sync.aligned.m8n8.x4.shared.b16 [%0], {%1,%2,%3,%4};" ::"r"(a), "r"(r0), "r"(r1), "r"(r2), "r"(r3) : "memory");
}
DEVI void stsm2(uint32_t a, uint32_t r0, uint32_t r1) {
    asm volatile("stmatrix.sync.aligned.m8n8.x2.shared.b16 [%0], {%1,%2};" ::"r"(a), "r"(r0), "r"(r1) : "memory");
}
DEVI uint32_t movm(uint32_t a) {
    uint32_t d;
    asm volatile("movmatrix.sync.aligned.m8n8.trans.b16 %0, %1;" : "=r"(d) : "r"(a));
    return d;
}
DEVI void mma16(float (&d)[4], uint32_t a0, uint32_t a1, uint32_t a2, uint32_t a3, uint32_t b0, uint32_t b1) {
    asm volatile("mma.sync.aligned.m16n8k16.row.col.f32.bf16.bf16.f32 {%0,%1,%2,%3}, {%4,%5,%6,%7}, {%8,%9}, {%0,%1,%2,%3};"
                 : "+f"(d[0]), "+f"(d[1]), "+f"(d[2]), "+f"(d[3]) : "r"(a0), "r"(a1), "r"(a2), "r"(a3), "r"(b0), "r"(b1));
}
DEVI void mma16z(float (&d)[4], uint32_t a0, uint32_t a1, uint32_t a2, uint32_t a3, uint32_t b0, uint32_t b1) {
    asm volatile("mma.sync.aligned.m16n8k16.row.col.f32.bf16.bf16.f32 {%0,%1,%2,%3}, {%4,%5,%6,%7}, {%8,%9}, {%10,%10,%10,%10};"
                 : "=f"(d[0]), "=f"(d[1]), "=f"(d[2]), "=f"(d[3]) : "r"(a0), "r"(a1), "r"(a2), "r"(a3), "r"(b0), "r"(b1), "f"(0.f));
}
DEVI void mma8(float (&d)[4], uint32_t a0, uint32_t a1, uint32_t b0) {
    asm volatile("mma.sync.aligned.m16n8k8.row.col.f32.bf16.bf16.f32 {%0,%1,%2,%3}, {%4,%5}, {%6}, {%0,%1,%2,%3};"
                 : "+f"(d[0]), "+f"(d[1]), "+f"(d[2]), "+f"(d[3]) : "r"(a0), "r"(a1), "r"(b0));
}
DEVI void mma8z(float (&d)[4], uint32_t a0, uint32_t a1, uint32_t b0) {
    asm volatile("mma.sync.aligned.m16n8k8.row.col.f32.bf16.bf16.f32 {%0,%1,%2,%3}, {%4,%5}, {%6}, {%7,%7,%7,%7};"
                 : "=f"(d[0]), "=f"(d[1]), "=f"(d[2]), "=f"(d[3]) : "r"(a0), "r"(a1), "r"(b0), "f"(0.f));
}
DEVI uint32_t pack2(float lo, float hi) {
    uint32_t r;
    asm("cvt.rn.bf16x2.f32 %0, %1, %2;" : "=r"(r) : "f"(hi), "f"(lo));
    return r;
}
DEVI uint32_t hadd2(uint32_t a, uint32_t b) {
    uint32_t r;
    asm("add.rn.bf16x2 %0, %1, %2;" : "=r"(r) : "r"(a), "r"(b));
    return r;
}
DEVI float lo_f(uint32_t x) { return __uint_as_float(x << 16); }
DEVI float hi_f(uint32_t x) { return __uint_as_float(x & 0xFFFF0000u); }
template <uint32_t OFF> DEVI uint4 ldg4(uint32_t lo, uint32_t hi) {
    uint4 v;
    asm volatile("{\n.reg .b64 a;\nmov.b64 a, {%4,%5};\nld.relaxed.gpu.global.v4.u32 {%0,%1,%2,%3}, [a+%6];\n}"
                 : "=r"(v.x), "=r"(v.y), "=r"(v.z), "=r"(v.w) : "r"(lo), "r"(hi), "n"(OFF) : "memory");
    return v;
}
template <uint32_t OFF> DEVI uint2 ldg2(uint32_t lo, uint32_t hi) {
    uint2 v;
    asm volatile("{\n.reg .b64 a;\nmov.b64 a, {%2,%3};\nld.relaxed.gpu.global.v2.u32 {%0,%1}, [a+%4];\n}"
                 : "=r"(v.x), "=r"(v.y) : "r"(lo), "r"(hi), "n"(OFF) : "memory");
    return v;
}
template <uint32_t OFF> DEVI void stg4(uint32_t lo, uint32_t hi, uint32_t a, uint32_t b, uint32_t c, uint32_t d) {
    asm volatile("{\n.reg .b64 a;\nmov.b64 a, {%0,%1};\nst.relaxed.gpu.global.v4.u32 [a+%6], {%2,%3,%4,%5};\n}"
                 ::"r"(lo), "r"(hi), "r"(a), "r"(b), "r"(c), "r"(d), "n"(OFF) : "memory");
}
template <uint32_t OFF> DEVI void stg2(uint32_t lo, uint32_t hi, uint32_t a, uint32_t b) {
    asm volatile("{\n.reg .b64 a;\nmov.b64 a, {%0,%1};\nst.relaxed.gpu.global.v2.u32 [a+%4], {%2,%3};\n}"
                 ::"r"(lo), "r"(hi), "r"(a), "r"(b), "n"(OFF) : "memory");
}
DEVI uint32_t tagx2(uint32_t a, uint32_t b, uint32_t t) { uint32_t r; asm("lop3.b32 %0, %1, %2, %3, 0x7E;" : "=r"(r) : "r"(a), "r"(b), "r"(t)); return r; }
DEVI uint32_t tagx1(uint32_t a, uint32_t b, uint32_t t) { uint32_t r; asm("lop3.b32 %0, %1, %2, %3, 0xF6;" : "=r"(r) : "r"(a), "r"(b), "r"(t)); return r; }
DEVI uint32_t or3(uint32_t a, uint32_t b, uint32_t c) { uint32_t r; asm("lop3.b32 %0, %1, %2, %3, 0xFE;" : "=r"(r) : "r"(a), "r"(b), "r"(c)); return r; }
DEVI bool any_bad(uint32_t x) { return __any_sync(0xFFFFFFFFu, (x & 1u) != 0); }
DEVI uint32_t settag(uint32_t x, uint32_t tag) { return (x & ~1u) | tag; }
DEVI void sts32f(uint32_t a, float v) { asm volatile("st.shared.f32 [%0], %1;" ::"r"(a), "f"(v) : "memory"); }
DEVI void sts16(uint32_t a, uint32_t v) { asm volatile("st.shared.u16 [%0], %1;" ::"r"(a), "h"((unsigned short)v) : "memory"); }
DEVI void sts64(uint32_t a, uint32_t x, uint32_t y) { asm volatile("st.shared.v2.u32 [%0], {%1,%2};" ::"r"(a), "r"(x), "r"(y) : "memory"); }
DEVI void sts128(uint32_t a, uint32_t x, uint32_t y, uint32_t z, uint32_t w) {
    asm volatile("st.shared.v4.u32 [%0], {%1,%2,%3,%4};" ::"r"(a), "r"(x), "r"(y), "r"(z), "r"(w) : "memory");
}
DEVI float4 lds128f(uint32_t a) {
    float4 v;
    asm volatile("ld.shared.v4.f32 {%0,%1,%2,%3}, [%4];" : "=f"(v.x), "=f"(v.y), "=f"(v.z), "=f"(v.w) : "r"(a) : "memory");
    return v;
}
DEVI uint4 lds128(uint32_t a) {
    uint4 v;
    asm volatile("ld.shared.v4.u32 {%0,%1,%2,%3}, [%4];" : "=r"(v.x), "=r"(v.y), "=r"(v.z), "=r"(v.w) : "r"(a) : "memory");
    return v;
}
DEVI uint2 lds64(uint32_t a) {
    uint2 v;
    asm volatile("ld.shared.v2.u32 {%0,%1}, [%2];" : "=r"(v.x), "=r"(v.y) : "r"(a) : "memory");
    return v;
}
template <int ID> DEVI void bar_s() { asm volatile("bar.sync %0, 256;" ::"n"(ID) : "memory"); }
template <int ID> DEVI void bar_a() { asm volatile("bar.arrive %0, 256;" ::"n"(ID) : "memory"); }
DEVI float ex2(float x) { float r; asm("ex2.approx.ftz.f32 %0, %1;" : "=f"(r) : "f"(x)); return r; }
DEVI float rcp(float x) { float r; asm("rcp.approx.ftz.f32 %0, %1;" : "=f"(r) : "f"(x)); return r; }
DEVI uint32_t clk() { uint32_t c; asm volatile("mov.u32 %0, %%clock;" : "=r"(c)::"memory"); return c; }

DEVI uint64_t mkdesc(uint32_t addr, uint32_t lbo, uint32_t sbo) {
    return (uint64_t)((addr & 0x3FFFF) >> 4) | ((uint64_t)(lbo >> 4) << 16) | ((uint64_t)(sbo >> 4) << 32) | ((uint64_t)1 << 62);
}
DEVI void wg_fence() { asm volatile("wgmma.fence.sync.aligned;" ::: "memory"); }
DEVI void wg_commit() { asm volatile("wgmma.commit_group.sync.aligned;" ::: "memory"); }
template <int N> DEVI void wg_wait() { asm volatile("wgmma.wait_group.sync.aligned %0;" ::"n"(N) : "memory"); }
template <int SC>
DEVI void wg_rs32(float (&d)[16], const uint32_t (&a)[4], uint64_t db) {
    if (SC) {
        asm volatile("wgmma.mma_async.sync.aligned.m64n32k16.f32.bf16.bf16 "
                     "{%0,%1,%2,%3,%4,%5,%6,%7,%8,%9,%10,%11,%12,%13,%14,%15}, {%16,%17,%18,%19}, %20, 1, 1, 1, 0;"
                     : "+f"(d[0]), "+f"(d[1]), "+f"(d[2]), "+f"(d[3]), "+f"(d[4]), "+f"(d[5]), "+f"(d[6]), "+f"(d[7]),
                       "+f"(d[8]), "+f"(d[9]), "+f"(d[10]), "+f"(d[11]), "+f"(d[12]), "+f"(d[13]), "+f"(d[14]), "+f"(d[15])
                     : "r"(a[0]), "r"(a[1]), "r"(a[2]), "r"(a[3]), "l"(db));
    } else {
        asm volatile("wgmma.mma_async.sync.aligned.m64n32k16.f32.bf16.bf16 "
                     "{%0,%1,%2,%3,%4,%5,%6,%7,%8,%9,%10,%11,%12,%13,%14,%15}, {%16,%17,%18,%19}, %20, 0, 1, 1, 0;"
                     : "=f"(d[0]), "=f"(d[1]), "=f"(d[2]), "=f"(d[3]), "=f"(d[4]), "=f"(d[5]), "=f"(d[6]), "=f"(d[7]),
                       "=f"(d[8]), "=f"(d[9]), "=f"(d[10]), "=f"(d[11]), "=f"(d[12]), "=f"(d[13]), "=f"(d[14]), "=f"(d[15])
                     : "r"(a[0]), "r"(a[1]), "r"(a[2]), "r"(a[3]), "l"(db));
    }
}

#define SM_WO 0
#define SM_STA 65536
#define SM_STB 131072
#define SM_X 196608
#define SM_BAR 229376
#define SM_TOTAL (229376 + 128)
#define SM_MEMT (SM_STB)
#define SM_OT (SM_STB + 4096)
#define SM_SPM (SM_STB + 6144)
#define SM_SPX (SM_SPM + 10368)
#define SM_PM (SM_SPX + 10368)
#define SM_PX (SM_PM + 640)
#define SM_VP (SM_PX + 640)
#define SM_QP (SM_VP + 10240)
#define SM_XP (SM_QP + 2048)

#define SPIN_LIMIT (1 << 20)
#define WO_PRE 0

#define PT(n)

template <bool MASK>
DEVI void softmax_row(uint32_t spA, uint32_t pA, bool lo8, bool masked) {
    float4 a = lds128f(spA), b = lds128f(spA ^ 16);
    float4 c = make_float4(0.f, 0.f, 0.f, 0.f), d = c;
    if (lo8) { c = lds128f(spA + 1024); d = lds128f((spA ^ 16) + 1024); }
    float s0 = ((a.x + a.y) + (a.z + a.w)) + ((b.x + b.y) + (b.z + b.w));
    float s1 = ((c.x + c.y) + (c.z + c.w)) + ((d.x + d.y) + (d.z + d.w));
    if (MASK) s0 = masked ? -1.0e9f * 11.313708499f : s0;
    s1 = lo8 ? s1 : s0;
    int mi = __float_as_int(fmaxf(s0, s1));
    mi ^= (mi >> 31) & 0x7FFFFFFF;
    mi = __reduce_max_sync(0xFFFFFFFFu, mi);
    mi ^= (mi >> 31) & 0x7FFFFFFF;
    const float c2 = 0.08838834764831845f * 1.4426950408889634f;
    float mc = __int_as_float(mi) * c2;
    float e0 = ex2(fmaf(s0, c2, -mc)), e1 = ex2(fmaf(s1, c2, -mc));
    uint32_t pk = pack2(e0, e1);
    sts16(pA, pk & 0xFFFF);
    if (lo8) sts16(pA + 64, pk >> 16);
}

struct Ctx {
    uint32_t sb, w, h, j, xlo, xhi, zero;
};
#define REFRESH() asm volatile("xor.b32 %0, %0, %1;" : "+r"(t16) : "r"(c.zero))

DEVI void pv_x(const Ctx& c, uint32_t t16, int sg) {
    const uint32_t ONES = 0x3F803F80u;
    const uint32_t sb = c.sb;
    const uint32_t l7 = (t16 >> 4) & 7;
    uint32_t p[4];
    ldsm4(p, sb + SM_PX + l7 * 80 + ((t16 >> 3) & 0x30));
    uint32_t p4 = ldsm1(sb + SM_PX + l7 * 80 + 64);
    uint4 va = lds128(sb + SM_VP + t16), vb = lds128(sb + SM_VP + 4096 + t16);
    uint2 vm = lds64(sb + SM_VP + 8192 + (t16 >> 1));
    float o[4], dn[4];
    mma16z(o, va.x, va.y, va.z, va.w, p[0], p[1]);
    mma16z(dn, ONES, ONES, ONES, ONES, p[0], p[1]);
    mma16(o, vb.x, vb.y, vb.z, vb.w, p[2], p[3]);
    mma16(dn, ONES, ONES, ONES, ONES, p[2], p[3]);
    mma8(o, vm.x, vm.y, p4);
    mma8(dn, ONES, ONES, p4);
    float r0 = rcp(dn[0]), r1 = rcp(dn[1]);
    uint32_t u0 = movm(pack2(o[0] * r0, o[1] * r1));
    uint32_t u1 = movm(pack2(o[2] * r0, o[3] * r1));
    const bool odd = (t16 & 16) != 0;
    uint32_t snd = odd ? u0 : u1;
    uint32_t rcv = __shfl_xor_sync(0xFFFFFFFFu, snd, 1);
    uint32_t lo = odd ? rcv : u0, hi = odd ? u1 : rcv;
    const uint32_t off = (uint32_t)(sg * 32 + 8 * c.j) * (HD * 2) + c.h * 256 + c.w * 32 + ((t16 >> 6) & 7) * (HD * 2) + (t16 & 16) + ((t16 >> 2) & 8);
    asm volatile("st.global.v2.u32 [%0], {%1,%2};" ::"l"((char*)g_ox + off), "r"(lo), "r"(hi) : "memory");
}

#define XDOFF(ks) ((((ks) >> 2) * 4096 + ((ks) & 3) * 32) >> 4)

template <bool MAIN>
DEVI void window(const Ctx& c, uint32_t& t16, int s, const uint32_t (&Wq)[16][4], const uint32_t (&Wk)[16][4], const uint32_t (&Wv)[16][4]) {
    const uint32_t sb = c.sb, w = c.w, h = c.h, j = c.j, xhi = c.xhi;
    float xa[16], xb[16];
    const bool doX1 = (s + 2 < NSEG), doX2 = (s >= -1 && s + 1 < NSEG);
    const uint64_t xd = mkdesc(sb + SM_X + (s & 1) * 16384, 16, 1024);
    const uint32_t hb = c.xlo + h * XO_HEAD + (s & 1) * XO_SLOT;
    const uint32_t x1tag = (((s + 2) >> 1) & 1) ^ 1;
    if (doX1) mbar_wait(sb + SM_BAR + 32 + (s & 1) * 8, ((s + 2) >> 1) & 1);
    wg_fence();
#pragma unroll
    for (int ks = 0; ks < 16; ks++) {
        if (ks == 0) wg_rs32<0>(xa, Wq[ks], xd + XDOFF(ks));
        else wg_rs32<1>(xa, Wq[ks], xd + XDOFF(ks));
    }
    wg_commit();
    if (doX2) {
        const uint32_t tag = (((s + 1) >> 1) & 1) ^ 1;
        const uint32_t a16 = (hb ^ XO_SLOT) + j * 16384 + t16, a8 = (hb ^ XO_SLOT) + j * 8192 + (t16 >> 1);
        uint2 q[4];
        uint4 kv[4];
        int it = 0;
        do {
            q[0] = ldg2<XO_XQ>(a8, xhi); q[1] = ldg2<XO_XQ + 2048>(a8, xhi); q[2] = ldg2<XO_XQ + 4096>(a8, xhi); q[3] = ldg2<XO_XQ + 6144>(a8, xhi);
            kv[0] = ldg4<XO_XKV>(a16, xhi); kv[1] = ldg4<XO_XKV + 4096>(a16, xhi); kv[2] = ldg4<XO_XKV + 8192>(a16, xhi); kv[3] = ldg4<XO_XKV + 12288>(a16, xhi);
            if (++it > SPIN_LIMIT) __trap();
        } while (any_bad(or3(tagx2(q[0].x, q[1].x, tag), tagx2(q[2].x, q[3].x, tag), tagx2(kv[0].x, kv[1].x, tag)) | tagx2(kv[2].x, kv[3].x, tag)));
#define SUM4(A, F) pack2((lo_f(A[0].F) + lo_f(A[1].F)) + (lo_f(A[2].F) + lo_f(A[3].F)), (hi_f(A[0].F) + hi_f(A[1].F)) + (hi_f(A[2].F) + hi_f(A[3].F)))
        sts64(sb + SM_QP + (t16 >> 1), movm(SUM4(q, x)), movm(SUM4(q, y)));
        const uint32_t kk0 = movm(SUM4(kv, x)), kk1 = movm(SUM4(kv, y));
        stg4<XO_XF>((hb ^ XO_SLOT) + j * 4096 + t16, xhi, settag(kk0, tag), kk1, SUM4(kv, z), SUM4(kv, w));
    }
    PT(11);
    REFRESH();
    wg_fence();
#pragma unroll
    for (int ks = 0; ks < 8; ks++) {
        if (ks == 0) wg_rs32<0>(xb, Wk[ks], xd + XDOFF(ks));
        else wg_rs32<1>(xb, Wk[ks], xd + XDOFF(ks));
    }
    wg_commit();
    if (MAIN) {
        const uint32_t lane = (t16 >> 4) & 31;
        softmax_row<true>(sb + SM_SPX + w * 1280 + (w >> 2) * 32 + lane * 32 + ((t16 >> 2) & 16), sb + SM_PX + w * 80 + lane * 2, lane < 8, lane > 8 * j + w);
    }
    wg_wait<1>();
    sts128(sb + SM_XP + t16, settag(pack2(xa[0], xa[1]), x1tag), pack2(xa[2], xa[3]), settag(pack2(xa[4], xa[5]), x1tag), pack2(xa[6], xa[7]));
    sts128(sb + SM_XP + 4096 + t16, settag(pack2(xa[8], xa[9]), x1tag), pack2(xa[10], xa[11]), settag(pack2(xa[12], xa[13]), x1tag), pack2(xa[14], xa[15]));
    wg_wait<0>();
    PT(12);
    REFRESH();
    if (MAIN && s < NSEG - 1) {
        if (w - 1 < 2) {
            const uint32_t rtag = (s & 1) ^ 1;
            const uint32_t g8 = (t16 >> 3) & 0x38, t = (t16 >> 4) & 3;
            const uint32_t a = c.xlo + XO_R + (j * 32 + h) * 4096 + (w - 1) * 64 + t * 128 + g8;
            const uint32_t sel = (t16 & 64) ? 0x3F800000u : 0x00003F80u;
            const uint32_t ab = c.xlo + XO_B + ((s + 1) * 4 + j) * 4096 + h * 128 + (w - 1) * 8 + g8 * 2;
            float r0[4], r1[4];
            int it = 0;
            uint32_t bad;
            do {
                uint2 v0 = ldg2<0>(a, xhi), v1 = ldg2<512>(a, xhi), v2 = ldg2<1024>(a, xhi), v3 = ldg2<1536>(a, xhi);
                uint2 v4 = ldg2<2048>(a, xhi), v5 = ldg2<2560>(a, xhi), v6 = ldg2<3072>(a, xhi), v7 = ldg2<3584>(a, xhi);
                bad = or3(tagx2(v0.x, v1.x, rtag), tagx2(v2.x, v3.x, rtag), tagx2(v4.x, v5.x, rtag)) | tagx2(v6.x, v7.x, rtag);
                mma16z(r0, v0.x, v0.y, v1.x, v1.y, sel, sel);
                mma16z(r1, v2.x, v2.y, v3.x, v3.y, sel, sel);
                mma16(r0, v4.x, v4.y, v5.x, v5.y, sel, sel);
                mma16(r1, v6.x, v6.y, v7.x, v7.y, sel, sel);
                if (++it > SPIN_LIMIT) __trap();
            } while (any_bad(bad));
            PT(13);
            bar_a<5>();
            const uint32_t m0 = pack2(r0[0] + r1[0], r0[1] + r1[1]);
            const uint32_t m1 = pack2(r0[2] + r1[2], r0[3] + r1[3]);
            if (t == 0) stg2<0>(ab, xhi, m0, m1);
        } else {
            bar_s<5>();
        }
    }
    PT(14);
    REFRESH();
    wg_fence();
#pragma unroll
    for (int ks = 8; ks < 16; ks++) wg_rs32<1>(xb, Wk[ks], xd + XDOFF(ks));
#pragma unroll
    for (int ks = 0; ks < 16; ks++) {
        if (ks == 0) wg_rs32<0>(xa, Wv[ks], xd + XDOFF(ks));
        else wg_rs32<1>(xa, Wv[ks], xd + XDOFF(ks));
    }
    wg_commit();
    if (doX1) {
        const uint32_t a8 = hb + j * 2048 + (t16 >> 1);
        const uint4 u0 = lds128(sb + SM_XP + t16), u1 = lds128(sb + SM_XP + 4096 + t16);
        stg2<XO_XQ>(a8, xhi, u0.x, u0.y);
        stg2<XO_XQ + 8192>(a8, xhi, u0.z, u0.w);
        stg2<XO_XQ + 16384>(a8, xhi, u1.x, u1.y);
        stg2<XO_XQ + 24576>(a8, xhi, u1.z, u1.w);
    }
    wg_wait<0>();
    if (doX1) {
        const uint32_t a16 = hb + j * 4096 + t16;
#define STKV(i) stg4<XO_XKV + (i) * 16384>(a16, xhi, settag(pack2(xb[4 * (i)], xb[4 * (i) + 1]), x1tag), pack2(xb[4 * (i) + 2], xb[4 * (i) + 3]), \
                                            pack2(xa[4 * (i)], xa[4 * (i) + 1]), pack2(xa[4 * (i) + 2], xa[4 * (i) + 3]))
        STKV(0); STKV(1); STKV(2); STKV(3);
    }
    PT(15);
    REFRESH();
    if (MAIN && s < NSEG - 1) {
        const uint32_t a = c.xlo + XO_B + ((s + 1) * 4 + j) * 4096 + t16;
        uint4 v;
        int it = 0;
        do {
            v = ldg4<0>(a, xhi);
            if (++it > SPIN_LIMIT) __trap();
        } while (__any_sync(0xFFFFFFFFu, v.x == 0xFFFFFFFFu || v.z == 0xFFFFFFFFu));
        stsm4(sb + SM_MEMT + t16, v.x, v.y, v.z, v.w);
    }
}

__global__ void __launch_bounds__(256, 1)
chain_kernel(const __grid_constant__ CUtensorMap tmq, const __grid_constant__ CUtensorMap tmk,
             const __grid_constant__ CUtensorMap tmv, const __grid_constant__ CUtensorMap tmo,
             const __grid_constant__ CUtensorMap tmx, const bf16* __restrict__ mem0, uint32_t xlo, uint32_t xhi, uint32_t zero) {
    extern __shared__ __align__(1024) uint8_t smem[];
    const uint32_t sb = smem_u32(smem);
    const uint32_t w = __reduce_max_sync(0xFFFFFFFFu, threadIdx.x >> 5);
    const uint32_t h = blockIdx.x >> 2, j = blockIdx.x & 3;
    const uint32_t bq = sb + SM_BAR, bk = bq + 8, bv = bq + 16, bo = bq + 24, bx = bq + 32;
    uint32_t Wq[16][4], Wk[16][4], Wv[16][4];
    uint32_t t16;
    {
        const int tid = threadIdx.x, lane = tid & 31;
        if (tid == 0) {
            mbar_init(bq, 1); mbar_init(bk, 1); mbar_init(bv, 1); mbar_init(bo, 1); mbar_init(bx, 1); mbar_init(bx + 8, 1);
            asm volatile("fence.mbarrier_init.release.cluster;" ::: "memory");
            asm volatile("fence.proxy.async.shared::cta;" ::: "memory");
            mbar_expect(bq, 65536);
            tma2d(sb + SM_STA, &tmq, bq, h * 128, j * 256);
            tma2d(sb + SM_STA + 32768, &tmq, bq, h * 128 + 64, j * 256);
            mbar_expect(bx, 16384);
            tma3d(sb + SM_X, &tmx, bx, 0, 0, j * 4);
            mbar_expect(bk, 65536);
            tma2d(sb + SM_STB, &tmk, bk, h * 128, j * 256);
            tma2d(sb + SM_STB + 32768, &tmk, bk, h * 128 + 64, j * 256);
            mbar_expect(bx + 8, 16384);
            tma3d(sb + SM_X + 16384, &tmx, bx + 8, 0, 32, j * 4);
            mbar_expect(bo, 65536);
            for (int i = 0; i < 4; i++) tma2d(sb + SM_WO + i * 16384, &tmo, bo, j * 256 + i * 64, h * 128);
        }
        __syncthreads();
        const uint32_t chunk = (uint32_t)((w & 3) * 2 + ((lane >> 3) & 1));
        const uint32_t off = (uint32_t)(w >> 2) * 32768u + (uint32_t)(((lane >> 4) & 1) * 8 + (lane & 7)) * 128u + ((chunk ^ (lane & 7)) << 4);
        mbar_wait(bq, 0);
#pragma unroll
        for (int ks = 0; ks < 16; ks++) ldsm4t(Wq[ks], sb + SM_STA + off + ks * 2048);
        __syncthreads();
        if (tid == 0) {
            asm volatile("fence.proxy.async.shared::cta;" ::: "memory");
            mbar_expect(bv, 65536);
            tma2d(sb + SM_STA, &tmv, bv, h * 128, j * 256);
            tma2d(sb + SM_STA + 32768, &tmv, bv, h * 128 + 64, j * 256);
        }
        mbar_wait(bk, 0);
#pragma unroll
        for (int ks = 0; ks < 16; ks++) ldsm4t(Wk[ks], sb + SM_STB + off + ks * 2048);
        __syncthreads();
        {
            const unsigned short* m0 = (const unsigned short*)mem0 + j * 256 + tid;
            uint32_t v[4];
#pragma unroll
            for (int i = 0; i < 4; i++) v[i] = (uint32_t)m0[(2 * i) * DM] | ((uint32_t)m0[(2 * i + 1) * DM] << 16);
            sts128(sb + SM_MEMT + tid * 16, v[0], v[1], v[2], v[3]);
        }
        t16 = __shfl_sync(0xFFFFFFFFu, tid * 16, lane);
        mbar_wait(bv, 0);
#pragma unroll
        for (int ks = 0; ks < 16; ks++) ldsm4t(Wv[ks], sb + SM_STA + off + ks * 2048);
        mbar_wait(bo, 0);
    }
    const Ctx c = {sb, w, h, j, xlo, xhi, zero};
    const uint32_t ONES = 0x3F803F80u;

#pragma unroll 1
    for (int s = -2; s < 0; s++) {
        PT(0);
        bar_s<1>();
        if (t16 == 0 && s == -1) {
            mbar_expect(bx, 16384);
            tma3d(sb + SM_X, &tmx, bx, 0, 64, j * 4);
        }
        window<false>(c, t16, s, Wq, Wk, Wv);
    }

#pragma unroll 1
    for (int s = 0; s < NSEG; s++) {
        const uint32_t ctag = ((s >> 1) & 1) ^ 1;
        const uint32_t hb = xlo + h * XO_HEAD + (s & 1) * XO_SLOT;
        PT(0);
        bar_s<1>();
        PT(1);
        uint32_t oq0, oq1, ok0, ok1, ov0, ov1;
        {
            uint32_t b[8][4];
#pragma unroll
            for (int p = 0; p < 8; p++) ldsm4t(b[p], sb + SM_MEMT + (t16 & 0x1F0) + p * 512);
            float q0[4], q1[4], k0[4], k1[4];
#pragma unroll
            for (int p = 0; p < 8; p++) {
                if (p == 0) {
                    mma16z(q0, Wq[0][0], Wq[0][1], Wq[0][2], Wq[0][3], b[p][0], b[p][1]);
                    mma16z(k0, Wk[0][0], Wk[0][1], Wk[0][2], Wk[0][3], b[p][0], b[p][1]);
                    mma16z(q1, Wq[1][0], Wq[1][1], Wq[1][2], Wq[1][3], b[p][2], b[p][3]);
                    mma16z(k1, Wk[1][0], Wk[1][1], Wk[1][2], Wk[1][3], b[p][2], b[p][3]);
                } else {
                    mma16(q0, Wq[2 * p][0], Wq[2 * p][1], Wq[2 * p][2], Wq[2 * p][3], b[p][0], b[p][1]);
                    mma16(k0, Wk[2 * p][0], Wk[2 * p][1], Wk[2 * p][2], Wk[2 * p][3], b[p][0], b[p][1]);
                    mma16(q1, Wq[2 * p + 1][0], Wq[2 * p + 1][1], Wq[2 * p + 1][2], Wq[2 * p + 1][3], b[p][2], b[p][3]);
                    mma16(k1, Wk[2 * p + 1][0], Wk[2 * p + 1][1], Wk[2 * p + 1][2], Wk[2 * p + 1][3], b[p][2], b[p][3]);
                }
            }
            oq0 = pack2(q0[0] + q1[0], q0[1] + q1[1]);
            oq1 = pack2(q0[2] + q1[2], q0[3] + q1[3]);
            ok0 = pack2(k0[0] + k1[0], k0[1] + k1[1]);
            ok1 = pack2(k0[2] + k1[2], k0[3] + k1[3]);
            stg4<XO_CQK>(hb + j * 4096 + t16, xhi, settag(oq0, ctag), oq1, ok0, ok1);
            PT(2);
            const float z = __uint_as_float(ok1 & zero);
#pragma unroll
            for (int i = 0; i < 4; i++) q0[i] = q1[i] = k0[i] = z;
#pragma unroll
            for (int ks = 0; ks < 16; ks++) {
                if (ks % 3 == 0) mma16(q0, Wv[ks][0], Wv[ks][1], Wv[ks][2], Wv[ks][3], b[ks >> 1][(ks & 1) * 2], b[ks >> 1][(ks & 1) * 2 + 1]);
                if (ks % 3 == 1) mma16(q1, Wv[ks][0], Wv[ks][1], Wv[ks][2], Wv[ks][3], b[ks >> 1][(ks & 1) * 2], b[ks >> 1][(ks & 1) * 2 + 1]);
                if (ks % 3 == 2) mma16(k0, Wv[ks][0], Wv[ks][1], Wv[ks][2], Wv[ks][3], b[ks >> 1][(ks & 1) * 2], b[ks >> 1][(ks & 1) * 2 + 1]);
            }
            ov0 = pack2((q1[0] + k0[0]) + q0[0], (q1[1] + k0[1]) + q0[1]);
            ov1 = pack2((q1[2] + k0[2]) + q0[2], (q1[3] + k0[3]) + q0[3]);
            stg2<XO_CV>(hb + j * 2048 + (t16 >> 1), xhi, settag(ov0, ctag), ov1);
        }
        PT(3);
    REFRESH();
        uint4 xf[4];
        xf[0] = ldg4<XO_XF>(hb + t16, xhi); xf[1] = ldg4<XO_XF + 4096>(hb + t16, xhi);
        xf[2] = ldg4<XO_XF + 8192>(hb + t16, xhi); xf[3] = ldg4<XO_XF + 12288>(hb + t16, xhi);
        if (t16 == 0 && s + 3 < NSEG) {
            const uint32_t b = (uint32_t)((s + 3) & 1);
            mbar_expect(bx + b * 8, 16384);
            tma3d(sb + SM_X + b * 16384, &tmx, bx + b * 8, 0, (s + 3) * 32, j * 4);
        }
        if (s >= 1) pv_x(c, t16, s - 1);
        PT(4);
    REFRESH();
        {
            const uint32_t lane = (t16 >> 4) & 31, g = lane >> 2, t = lane & 3;
            const uint32_t aWo = sb + SM_WO + (w >> 1) * 16384u + (((lane >> 4) & 1) * 8 + (lane & 7)) * 128u +
                                 ((((w & 1) * 4 + ((lane >> 3) & 1)) ^ (lane & 7)) << 4);
            const uint32_t aSpW = sb + SM_SPM + (g * 320 + (g >> 2) * 8 + 16 * t + (w ^ (((t >> 1) << 2) | (g & 3)))) * 4u;
            {
                int it = 0;
                while (any_bad(tagx2(xf[0].x, xf[1].x, ctag) | tagx2(xf[2].x, xf[3].x, ctag))) {
                    xf[0] = ldg4<XO_XF>(hb + t16, xhi); xf[1] = ldg4<XO_XF + 4096>(hb + t16, xhi);
                    xf[2] = ldg4<XO_XF + 8192>(hb + t16, xhi); xf[3] = ldg4<XO_XF + 12288>(hb + t16, xhi);
                    if (++it > SPIN_LIMIT) __trap();
                }
            }
            sts128(sb + SM_VP + t16, xf[0].z, xf[0].w, xf[1].z, xf[1].w);
            sts128(sb + SM_VP + 4096 + t16, xf[2].z, xf[2].w, xf[3].z, xf[3].w);
            const uint2 qx = lds64(sb + SM_QP + (t16 >> 1));
            uint32_t wo[16][4];
#pragma unroll
            for (int i = 0; i < WO_PRE; i++) ldsm4t(wo[i], (aWo ^ ((i & 1) << 5)) + (i >> 1) * 2048);
            PT(5);
            uint4 c1, c2, c3;
            {
                int it = 0;
                do {
                    c1 = ldg4<XO_CQK>(hb + (j ^ 1) * 4096 + t16, xhi);
                    c2 = ldg4<XO_CQK>(hb + (j ^ 2) * 4096 + t16, xhi);
                    c3 = ldg4<XO_CQK>(hb + (j ^ 3) * 4096 + t16, xhi);
                    if (++it > SPIN_LIMIT) __trap();
                } while (any_bad(tagx1(tagx2(c1.x, c2.x, ctag), c3.x, ctag)));
            }
            PT(6);
            uint2 d1 = ldg2<XO_CV>(hb + (j ^ 1) * 2048 + (t16 >> 1), xhi);
            uint2 d2 = ldg2<XO_CV>(hb + (j ^ 2) * 2048 + (t16 >> 1), xhi);
            uint2 d3 = ldg2<XO_CV>(hb + (j ^ 3) * 2048 + (t16 >> 1), xhi);
            const uint32_t qT0 = movm(hadd2(hadd2(oq0, c1.x), hadd2(c2.x, c3.x)));
            const uint32_t qT1 = movm(hadd2(hadd2(oq1, c1.y), hadd2(c2.y, c3.y)));
            const uint32_t kT0 = movm(hadd2(hadd2(ok0, c1.z), hadd2(c2.z, c3.z)));
            const uint32_t kT1 = movm(hadd2(hadd2(ok1, c1.w), hadd2(c2.w, c3.w)));
            float sc[5][4];
#pragma unroll
            for (int i = 0; i < 4; i++) mma16z(sc[i], qT0, qx.x, qT1, qx.y, xf[i].x, xf[i].y);
            mma16z(sc[4], qT0, qx.x, qT1, qx.y, kT0, kT1);
#pragma unroll
            for (int i = 0; i < 5; i++) { sts32f(aSpW + i * 256, sc[i][0]); sts32f(aSpW + i * 256 + 32, sc[i][1]); }
            bar_s<2>();
            PT(7);
            softmax_row<false>(sb + SM_SPM + w * 1280 + (w >> 2) * 32 + lane * 32 + ((t16 >> 2) & 16), sb + SM_PM + w * 80 + lane * 2, lane < 8, false);
#pragma unroll
            for (int i = 0; i < 5; i++) { sts32f(aSpW + (SM_SPX - SM_SPM) + i * 256, sc[i][2]); sts32f(aSpW + (SM_SPX - SM_SPM) + i * 256 + 32, sc[i][3]); }
            const uint4 va = lds128(sb + SM_VP + t16), vb = lds128(sb + SM_VP + 4096 + t16);
            {
                int it = 0;
                while (any_bad(tagx1(tagx2(d1.x, d2.x, ctag), d3.x, ctag))) {
                    d1 = ldg2<XO_CV>(hb + (j ^ 1) * 2048 + (t16 >> 1), xhi);
                    d2 = ldg2<XO_CV>(hb + (j ^ 2) * 2048 + (t16 >> 1), xhi);
                    d3 = ldg2<XO_CV>(hb + (j ^ 3) * 2048 + (t16 >> 1), xhi);
                    if (++it > SPIN_LIMIT) __trap();
                }
            }
            const uint32_t vm0 = hadd2(hadd2(ov0, d1.x), hadd2(d2.x, d3.x));
            const uint32_t vm1 = hadd2(hadd2(ov1, d1.y), hadd2(d2.y, d3.y));
            bar_s<3>();
            PT(8);
            uint32_t p[4];
            ldsm4(p, sb + SM_PM + (lane & 7) * 80 + (lane >> 3) * 16);
            uint32_t p4 = ldsm1(sb + SM_PM + (lane & 7) * 80 + 64);
            float oa[4], ob[4], dn[4];
            mma16z(oa, va.x, va.y, va.z, va.w, p[0], p[1]);
            mma16z(ob, vb.x, vb.y, vb.z, vb.w, p[2], p[3]);
            mma8(oa, vm0, vm1, p4);
            mma16z(dn, ONES, ONES, ONES, ONES, p[0], p[1]);
            mma16(dn, ONES, ONES, ONES, ONES, p[2], p[3]);
            mma8(dn, ONES, ONES, p4);
#pragma unroll
            for (int i = WO_PRE; i < 6; i++) ldsm4t(wo[i], (aWo ^ ((i & 1) << 5)) + (i >> 1) * 2048);
            stsm2(sb + SM_OT + w * 256 + (t16 & 0xF0), pack2(oa[0] + ob[0], oa[1] + ob[1]), pack2(oa[2] + ob[2], oa[3] + ob[3]));
            sts64(sb + SM_VP + 8192 + (t16 >> 1), vm0, vm1);
            bar_s<4>();
            PT(9);
            float r[2][2][4];
#pragma unroll
            for (int pp = 0; pp < 4; pp++) {
                uint32_t b[4];
                ldsm4t(b, sb + SM_OT + (t16 & 0x1F0) + pp * 512);
#pragma unroll
                for (int e = 0; e < 2; e++)
#pragma unroll
                    for (int mt = 0; mt < 2; mt++) {
                        const int i = (pp * 2 + e) * 2 + mt;
                        if (pp == 0) mma16z(r[mt][e], wo[i][0], wo[i][1], wo[i][2], wo[i][3], b[2 * e], b[2 * e + 1]);
                        else mma16(r[mt][e], wo[i][0], wo[i][1], wo[i][2], wo[i][3], b[2 * e], b[2 * e + 1]);
                        if (i + 6 < 16) ldsm4t(wo[i + 6], (aWo ^ ((i & 1) << 5)) + ((i + 6) >> 1) * 2048);
                    }
            }
            const float r0 = rcp(dn[0]), r1 = rcp(dn[1]);
            const uint32_t rtag = (s & 1) ^ 1;
            uint32_t y0 = pack2((r[0][0][0] + r[0][1][0]) * r0, (r[0][0][1] + r[0][1][1]) * r1);
            uint32_t y1 = pack2((r[0][0][2] + r[0][1][2]) * r0, (r[0][0][3] + r[0][1][3]) * r1);
            uint32_t y2 = pack2((r[1][0][0] + r[1][1][0]) * r0, (r[1][0][1] + r[1][1][1]) * r1);
            uint32_t y3 = pack2((r[1][0][2] + r[1][1][2]) * r0, (r[1][0][3] + r[1][1][3]) * r1);
            const uint32_t ar = xlo + XO_R + j * 131072 + h * 128 + (t16 >> 7) * 4096 + ((t16 >> 1) & 0x38);
            stg2<0>(ar, xhi, settag(y0, rtag), y1);
            stg2<64>(ar, xhi, settag(y2, rtag), y3);
        }
        PT(10);
    REFRESH();
        window<true>(c, t16, s, Wq, Wk, Wv);
    }
    bar_s<1>();
    pv_x(c, t16, NSEG - 1);
}

#define G2_STAGES 6
#define G2_STAGE_BYTES 32768
DEVI void wg_ss128t(float (&d)[64], uint64_t da, uint64_t db, int sc) {
    asm volatile("{\n.reg .pred p;\nsetp.ne.b32 p, %66, 0;\n"
                 "wgmma.mma_async.sync.aligned.m64n128k16.f32.bf16.bf16 "
                 "{%0,%1,%2,%3,%4,%5,%6,%7,%8,%9,%10,%11,%12,%13,%14,%15,%16,%17,%18,%19,%20,%21,%22,%23,%24,%25,%26,%27,%28,%29,%30,%31,"
                 "%32,%33,%34,%35,%36,%37,%38,%39,%40,%41,%42,%43,%44,%45,%46,%47,%48,%49,%50,%51,%52,%53,%54,%55,%56,%57,%58,%59,%60,%61,%62,%63}, "
                 "%64, %65, p, 1, 1, 0, 1;\n}\n"
                 : "+f"(d[0]), "+f"(d[1]), "+f"(d[2]), "+f"(d[3]), "+f"(d[4]), "+f"(d[5]), "+f"(d[6]), "+f"(d[7]),
                   "+f"(d[8]), "+f"(d[9]), "+f"(d[10]), "+f"(d[11]), "+f"(d[12]), "+f"(d[13]), "+f"(d[14]), "+f"(d[15]),
                   "+f"(d[16]), "+f"(d[17]), "+f"(d[18]), "+f"(d[19]), "+f"(d[20]), "+f"(d[21]), "+f"(d[22]), "+f"(d[23]),
                   "+f"(d[24]), "+f"(d[25]), "+f"(d[26]), "+f"(d[27]), "+f"(d[28]), "+f"(d[29]), "+f"(d[30]), "+f"(d[31]),
                   "+f"(d[32]), "+f"(d[33]), "+f"(d[34]), "+f"(d[35]), "+f"(d[36]), "+f"(d[37]), "+f"(d[38]), "+f"(d[39]),
                   "+f"(d[40]), "+f"(d[41]), "+f"(d[42]), "+f"(d[43]), "+f"(d[44]), "+f"(d[45]), "+f"(d[46]), "+f"(d[47]),
                   "+f"(d[48]), "+f"(d[49]), "+f"(d[50]), "+f"(d[51]), "+f"(d[52]), "+f"(d[53]), "+f"(d[54]), "+f"(d[55]),
                   "+f"(d[56]), "+f"(d[57]), "+f"(d[58]), "+f"(d[59]), "+f"(d[60]), "+f"(d[61]), "+f"(d[62]), "+f"(d[63])
                 : "l"(da), "l"(db), "r"(sc));
}

__global__ void __launch_bounds__(288, 1)
gemm2_kernel(const __grid_constant__ CUtensorMap tma, const __grid_constant__ CUtensorMap tmb, bf16* __restrict__ out) {
    extern __shared__ __align__(1024) uint8_t smem[];
    const uint32_t sb = smem_u32(smem);
    const uint32_t bars = sb + G2_STAGES * G2_STAGE_BYTES;
    const int tid = threadIdx.x, lane = tid & 31;
    const int w = __shfl_sync(0xFFFFFFFFu, tid >> 5, 0);
    const int bm = blockIdx.x >> 3, bn = blockIdx.x & 7;
    if (tid == 0) {
        for (int i = 0; i < G2_STAGES; i++) { mbar_init(bars + i * 8, 1); mbar_init(bars + (G2_STAGES + i) * 8, 2); }
        asm volatile("fence.mbarrier_init.release.cluster;" ::: "memory");
        asm volatile("fence.proxy.async.shared::cta;" ::: "memory");
    }
    __syncthreads();
    const int NK = HD / 64;
    if (w == 8) {
        if (lane == 0) {
            int st = 0, ph = 1;
            for (int kb = 0; kb < NK; kb++) {
                mbar_wait(bars + (G2_STAGES + st) * 8, ph);
                const uint32_t dst = sb + st * G2_STAGE_BYTES;
                mbar_expect(bars + st * 8, G2_STAGE_BYTES);
                tma2d(dst, &tma, bars + st * 8, kb * 64, bm * 128);
                tma2d(dst + 16384, &tmb, bars + st * 8, bn * 128, kb * 64);
                tma2d(dst + 24576, &tmb, bars + st * 8, bn * 128 + 64, kb * 64);
                if (++st == G2_STAGES) { st = 0; ph ^= 1; }
            }
        }
    } else {
        const int wg = w >> 2;
        float acc[64];
        int st = 0, ph = 0;
        for (int kb = 0; kb < NK; kb++) {
            mbar_wait(bars + st * 8, ph);
            const uint32_t base = sb + st * G2_STAGE_BYTES;
            const uint64_t da = mkdesc(base + wg * 8192, 16, 1024);
            const uint64_t db = mkdesc(base + 16384, 8192, 1024);
            wg_fence();
#pragma unroll
            for (int k = 0; k < 4; k++) wg_ss128t(acc, da + k * 2, db + k * 128, (kb | k) != 0);
            wg_commit();
            if (kb > 0) {
                wg_wait<1>();
                const int pst = st == 0 ? G2_STAGES - 1 : st - 1;
                if ((tid & 127) == 0) mbar_arrive(bars + (G2_STAGES + pst) * 8);
            }
            if (++st == G2_STAGES) { st = 0; ph ^= 1; }
        }
        wg_wait<0>();
        const int row = bm * 128 + wg * 64 + (w & 3) * 16 + (lane >> 2);
        bf16* o = out + (size_t)row * 2048 + bn * 128 + (lane & 3) * 2;
#pragma unroll
        for (int i = 0; i < 16; i++) {
            *(uint32_t*)(o + i * 8) = pack2(acc[4 * i], acc[4 * i + 1]);
            *(uint32_t*)(o + 8 * 2048 + i * 8) = pack2(acc[4 * i + 2], acc[4 * i + 3]);
        }
    }
}

template <int N, int LOGN, int NT>
DEVI void fft_smem(float2* x, int tid, float sgn) {
    for (int st = 0; st < LOGN; st++) {
        const int half = 1 << st;
        __syncthreads();
        for (int i = tid; i < N / 2; i += NT) {
            const int k = i & (half - 1), base = ((i >> st) << (st + 1)) + k;
            float sn, cs;
            sincospif(sgn * (float)k / (float)half, &sn, &cs);
            const float2 a = x[base], b = x[base + half];
            const float2 tw = make_float2(b.x * cs - b.y * sn, b.x * sn + b.y * cs);
            x[base] = make_float2(a.x + tw.x, a.y + tw.y);
            x[base + half] = make_float2(a.x - tw.x, a.y - tw.y);
        }
    }
    __syncthreads();
}
__global__ void __launch_bounds__(256) fft_rows_fwd(const bf16* __restrict__ x) {
    __shared__ float2 sm[1024];
    const int row = blockIdx.x, tid = threadIdx.x;
    for (int i = tid; i < 1024; i += 256) sm[__brev(i) >> 22] = make_float2(__bfloat162float(x[row * 1024 + i]), 0.f);
    fft_smem<1024, 10, 256>(sm, tid, -1.f);
    for (int i = tid; i < 513; i += 256) g_F[row * 520 + i] = sm[i];
}
__global__ void __launch_bounds__(256) fft_cols(const bf16* __restrict__ wr, const bf16* __restrict__ wi) {
    __shared__ float2 sm[2048], sm2[2048];
    const int col = blockIdx.x, tid = threadIdx.x;
    for (int i = tid; i < 2048; i += 256) sm[__brev(i) >> 21] = g_F[i * 520 + col];
    fft_smem<2048, 11, 256>(sm, tid, -1.f);
    for (int i = tid; i < 2048; i += 256) {
        const float a = __bfloat162float(wr[i * 513 + col]), b = __bfloat162float(wi[i * 513 + col]);
        const float2 v = sm[i];
        sm2[__brev(i) >> 21] = make_float2(v.x * a - v.y * b, v.x * b + v.y * a);
    }
    fft_smem<2048, 11, 256>(sm2, tid, 1.f);
    for (int i = tid; i < 2048; i += 256) g_F[i * 520 + col] = sm2[i];
}
__global__ void __launch_bounds__(256) fft_rows_inv(bf16* __restrict__ out) {
    __shared__ float2 sm[1024];
    const int row = blockIdx.x, tid = threadIdx.x;
    for (int i = tid; i < 1024; i += 256) {
        float2 v;
        if (i <= 512) { v = g_F[row * 520 + i]; if (i == 0 || i == 512) v.y = 0.f; }
        else { v = g_F[row * 520 + 1024 - i]; v.y = -v.y; }
        sm[__brev(i) >> 22] = v;
    }
    fft_smem<1024, 10, 256>(sm, tid, 1.f);
    const float sc = 1.f / (2048.f * 1024.f);
    for (int i = tid; i < 1024; i += 256) out[(size_t)row * 2048 + 1024 + i] = __float2bfloat16(sm[i].x * sc);
}

typedef CUresult (*EncodeFn)(CUtensorMap*, CUtensorMapDataType, cuuint32_t, void*, const cuuint64_t*, const cuuint64_t*,
                             const cuuint32_t*, const cuuint32_t*, CUtensorMapInterleave, CUtensorMapSwizzle,
                             CUtensorMapL2promotion, CUtensorMapFloatOOBfill);

static void make_map(EncodeFn enc, CUtensorMap* m, const void* ptr, int rank, const cuuint64_t* dims, const cuuint64_t* strides,
                     const cuuint32_t* box) {
    cuuint32_t es[3] = {1, 1, 1};
    CUresult r = enc(m, CU_TENSOR_MAP_DATA_TYPE_BFLOAT16, rank, (void*)ptr, dims, strides, box, es, CU_TENSOR_MAP_INTERLEAVE_NONE,
                     CU_TENSOR_MAP_SWIZZLE_128B, CU_TENSOR_MAP_L2_PROMOTION_L2_256B, CU_TENSOR_MAP_FLOAT_OOB_FILL_NONE);
    if (r != CUDA_SUCCESS) fprintf(stderr, "tensor map encode failed: %d\n", (int)r);
}

extern "C" void kernel_launch(void* const* d_in, const int* in_sizes, int n_in, void* d_out, int out_size) {
    const bf16* A_x = (const bf16*)d_in[0];
    const bf16* A_mem0 = (const bf16*)d_in[1];
    const bf16* A_Wq = (const bf16*)d_in[2];
    const bf16* A_Wk = (const bf16*)d_in[3];
    const bf16* A_Wv = (const bf16*)d_in[4];
    const bf16* A_Wo = (const bf16*)d_in[5];
    const bf16* B_x = (const bf16*)d_in[7];
    const bf16* B_wr = (const bf16*)d_in[8];
    const bf16* B_wi = (const bf16*)d_in[9];
    bf16* out = (bf16*)d_out;

    static EncodeFn enc = nullptr;
    static void *pxs = nullptr, *pox = nullptr;
    if (!enc) {
        cudaDriverEntryPointQueryResult qr;
        void* fn = nullptr;
        cudaGetDriverEntryPoint("cuTensorMapEncodeTiled", &fn, cudaEnableDefault, &qr);
        enc = (EncodeFn)fn;
        cudaFuncSetAttribute(chain_kernel, cudaFuncAttributeMaxDynamicSharedMemorySize, SM_TOTAL);
        cudaFuncSetAttribute(gemm2_kernel, cudaFuncAttributeMaxDynamicSharedMemorySize, G2_STAGES * G2_STAGE_BYTES + 128);
        cudaGetSymbolAddress(&pxs, g_xs);
        cudaGetSymbolAddress(&pox, g_ox);
    }
    CUtensorMap tmq, tmk, tmv, tmo, tmx, tma, tmb;
    {
        cuuint64_t d[2] = {HD, DM}, st[1] = {HD * 2};
        cuuint32_t bx[2] = {64, 256};
        make_map(enc, &tmq, A_Wq, 2, d, st, bx);
        make_map(enc, &tmk, A_Wk, 2, d, st, bx);
        make_map(enc, &tmv, A_Wv, 2, d, st, bx);
    }
    {
        cuuint64_t d[2] = {DM, HD}, st[1] = {DM * 2};
        cuuint32_t bx[2] = {64, 128}, bx2[2] = {64, 64};
        make_map(enc, &tmo, A_Wo, 2, d, st, bx);
        make_map(enc, &tmb, A_Wo, 2, d, st, bx2);
    }
    {
        cuuint64_t d[3] = {64, SEQ, DM / 64}, st[2] = {DM * 2, 128};
        cuuint32_t bx[3] = {64, 32, 4};
        make_map(enc, &tmx, A_x, 3, d, st, bx);
    }
    {
        cuuint64_t d[2] = {HD, SEQ}, st[1] = {HD * 2};
        cuuint32_t bx[2] = {64, 128};
        make_map(enc, &tma, pox, 2, d, st, bx);
    }
    cudaStream_t st = cudaStreamPerThread;
    const uint64_t xs = ((uint64_t)pxs + XS_BYTES - 1) & ~(uint64_t)(XS_BYTES - 1);
    cudaMemsetAsync((void*)(xs + XO_B), 0xFF, NSEG * 4 * 4096, st);
    chain_kernel<<<128, 256, SM_TOTAL, st>>>(tmq, tmk, tmv, tmo, tmx, A_mem0, (uint32_t)xs, (uint32_t)(xs >> 32), 0u);
    gemm2_kernel<<<128, 288, G2_STAGES * G2_STAGE_BYTES + 128, st>>>(tma, tmb, out);
    fft_rows_fwd<<<2048, 256, 0, st>>>(B_x);
    fft_cols<<<513, 256, 0, st>>>(B_wr, B_wi);
    fft_rows_inv<<<2048, 256, 0, st>>>(out);
}
```

```cpp
#include <cuda_runtime.h>
#include <cuda_bf16.h>
#include <cuda.h>
#include <stdint.h>
#include <stdio.h>

typedef __nv_bfloat16 bf16;

#define SEQ 2048
#define DM 1024
#define NH 32
#define DH 128
#define NSEG 64
#define HD (NH * DH)

#define XS_BYTES (16u << 20)
__device__ uint4 g_xs[2 * XS_BYTES / 16];
#define XO_SLOT (1u << 23)
#define XO_HEAD (128u << 10)
#define XO_CQK 0u
#define XO_XF (16u << 10)
#define XO_CV (32u << 10)
#define XO_XP (48u << 10)
#define XO_R (6u << 20)
#define XO_B (7u << 20)
__device__ bf16 g_ox[SEQ * HD];
__device__ float2 g_F[SEQ * 520];

#define DEVI __device__ __forceinline__

DEVI uint32_t smem_u32(const void* p) { return (uint32_t)__cvta_generic_to_shared(p); }
DEVI void mbar_init(uint32_t bar, uint32_t cnt) { asm volatile("mbarrier.init.shared::cta.b64 [%0], %1;" ::"r"(bar), "r"(cnt) : "memory"); }
DEVI void mbar_expect(uint32_t bar, uint32_t bytes) { asm volatile("mbarrier.arrive.expect_tx.shared::cta.b64 _, [%0], %1;" ::"r"(bar), "r"(bytes) : "memory"); }
DEVI void mbar_arrive(uint32_t bar) { asm volatile("mbarrier.arrive.shared::cta.b64 _, [%0];" ::"r"(bar) : "memory"); }
DEVI void mbar_wait(uint32_t bar, uint32_t parity) {
    uint32_t done;
    int it = 0;
    do {
        asm volatile("{\n.reg .pred p;\nmbarrier.try_wait.parity.shared::cta.b64 p, [%1], %2;\nselp.u32 %0, 1, 0, p;\n}\n"
                     : "=r"(done) : "r"(bar), "r"(parity) : "memory");
        if (++it > (1 << 22)) __trap();
    } while (!done);
}
DEVI void tma2d(uint32_t dst, const CUtensorMap* tm, uint32_t bar, int c0, int c1) {
    asm volatile("cp.async.bulk.tensor.2d.shared::cluster.global.mbarrier::complete_tx::bytes [%0], [%1, {%3, %4}], [%2];"
                 ::"r"(dst), "l"(tm), "r"(bar), "r"(c0), "r"(c1) : "memory");
}
DEVI void tma3d(uint32_t dst, const CUtensorMap* tm, uint32_t bar, int c0, int c1, int c2) {
    asm volatile("cp.async.bulk.tensor.3d.shared::cluster.global.mbarrier::complete_tx::bytes [%0], [%1, {%3, %4, %5}], [%2];"
                 ::"r"(dst), "l"(tm), "r"(bar), "r"(c0), "r"(c1), "r"(c2) : "memory");
}
DEVI void bulk_g2s(uint32_t dst, uint32_t lo, uint32_t hi, uint32_t bytes, uint32_t bar) {
    asm volatile("{\n.reg .b64 a;\nmov.b64 a, {%1,%2};\ncp.async.bulk.shared::cluster.global.mbarrier::complete_tx::bytes [%0], [a], %3, [%4];\n}"
                 ::"r"(dst), "r"(lo), "r"(hi), "r"(bytes), "r"(bar) : "memory");
}
DEVI void bulk_s2g(uint32_t lo, uint32_t hi, uint32_t src, uint32_t bytes) {
    asm volatile("{\n.reg .b64 a;\nmov.b64 a, {%0,%1};\ncp.async.bulk.global.shared::cta.bulk_group [a], [%2], %3;\ncp.async.bulk.commit_group;\n}"
                 ::"r"(lo), "r"(hi), "r"(src), "r"(bytes) : "memory");
}
DEVI bool elect() {
    uint32_t p;
    asm volatile("{\n.reg .pred P;\nelect.sync _|P, 0xFFFFFFFF;\nselp.u32 %0, 1, 0, P;\n}" : "=r"(p));
    return p != 0;
}
DEVI void ldsm4(uint32_t (&r)[4], uint32_t a) {
    asm volatile("ldmatrix.sync.aligned.m8n8.x4.shared.b16 {%0,%1,%2,%3}, [%4];" : "=r"(r[0]), "=r"(r[1]), "=r"(r[2]), "=r"(r[3]) : "r"(a) : "memory");
}
DEVI void ldsm4t(uint32_t (&r)[4], uint32_t a) {
    asm volatile("ldmatrix.sync.aligned.m8n8.x4.trans.shared.b16 {%0,%1,%2,%3}, [%4];" : "=r"(r[0]), "=r"(r[1]), "=r"(r[2]), "=r"(r[3]) : "r"(a) : "memory");
}
DEVI uint32_t ldsm1(uint32_t a) {
    uint32_t r;
    asm volatile("ldmatrix.sync.aligned.m8n8.x1.shared.b16 {%0}, [%1];" : "=r"(r) : "r"(a) : "memory");
    return r;
}
DEVI void stsm4(uint32_t a, uint32_t r0, uint32_t r1, uint32_t r2, uint32_t r3) {
    asm volatile("stmatrix.sync.aligned.m8n8.x4.shared.b16 [%0], {%1,%2,%3,%4};" ::"r"(a), "r"(r0), "r"(r1), "r"(r2), "r"(r3) : "memory");
}
DEVI void stsm2(uint32_t a, uint32_t r0, uint32_t r1) {
    asm volatile("stmatrix.sync.aligned.m8n8.x2.shared.b16 [%0], {%1,%2};" ::"r"(a), "r"(r0), "r"(r1) : "memory");
}
DEVI uint32_t movm(uint32_t a) {
    uint32_t d;
    asm volatile("movmatrix.sync.aligned.m8n8.trans.b16 %0, %1;" : "=r"(d) : "r"(a));
    return d;
}
DEVI void mma16(float (&d)[4], uint32_t a0, uint32_t a1, uint32_t a2, uint32_t a3, uint32_t b0, uint32_t b1) {
    asm volatile("mma.sync.aligned.m16n8k16.row.col.f32.bf16.bf16.f32 {%0,%1,%2,%3}, {%4,%5,%6,%7}, {%8,%9}, {%0,%1,%2,%3};"
                 : "+f"(d[0]), "+f"(d[1]), "+f"(d[2]), "+f"(d[3]) : "r"(a0), "r"(a1), "r"(a2), "r"(a3), "r"(b0), "r"(b1));
}
DEVI void mma16z(float (&d)[4], uint32_t a0, uint32_t a1, uint32_t a2, uint32_t a3, uint32_t b0, uint32_t b1) {
    asm volatile("mma.sync.aligned.m16n8k16.row.col.f32.bf16.bf16.f32 {%0,%1,%2,%3}, {%4,%5,%6,%7}, {%8,%9}, {%10,%10,%10,%10};"
                 : "=f"(d[0]), "=f"(d[1]), "=f"(d[2]), "=f"(d[3]) : "r"(a0), "r"(a1), "r"(a2), "r"(a3), "r"(b0), "r"(b1), "f"(0.f));
}
DEVI void mma8(float (&d)[4], uint32_t a0, uint32_t a1, uint32_t b0) {
    asm volatile("mma.sync.aligned.m16n8k8.row.col.f32.bf16.bf16.f32 {%0,%1,%2,%3}, {%4,%5}, {%6}, {%0,%1,%2,%3};"
                 : "+f"(d[0]), "+f"(d[1]), "+f"(d[2]), "+f"(d[3]) : "r"(a0), "r"(a1), "r"(b0));
}
DEVI void mma8z(float (&d)[4], uint32_t a0, uint32_t a1, uint32_t b0) {
    asm volatile("mma.sync.aligned.m16n8k8.row.col.f32.bf16.bf16.f32 {%0,%1,%2,%3}, {%4,%5}, {%6}, {%7,%7,%7,%7};"
                 : "=f"(d[0]), "=f"(d[1]), "=f"(d[2]), "=f"(d[3]) : "r"(a0), "r"(a1), "r"(b0), "f"(0.f));
}
DEVI uint32_t pack2(float lo, float hi) {
    uint32_t r;
    asm("cvt.rn.bf16x2.f32 %0, %1, %2;" : "=r"(r) : "f"(hi), "f"(lo));
    return r;
}
DEVI uint32_t hadd2(uint32_t a, uint32_t b) {
    uint32_t r;
    asm("add.rn.bf16x2 %0, %1, %2;" : "=r"(r) : "r"(a), "r"(b));
    return r;
}
DEVI float lo_f(uint32_t x) { return __uint_as_float(x << 16); }
DEVI float hi_f(uint32_t x) { return __uint_as_float(x & 0xFFFF0000u); }
template <uint32_t OFF> DEVI uint4 ldg4(uint32_t lo, uint32_t hi) {
    uint4 v;
    asm volatile("{\n.reg .b64 a;\nmov.b64 a, {%4,%5};\nld.relaxed.gpu.global.v4.u32 {%0,%1,%2,%3}, [a+%6];\n}"
                 : "=r"(v.x), "=r"(v.y), "=r"(v.z), "=r"(v.w) : "r"(lo), "r"(hi), "n"(OFF) : "memory");
    return v;
}
template <uint32_t OFF> DEVI uint2 ldg2(uint32_t lo, uint32_t hi) {
    uint2 v;
    asm volatile("{\n.reg .b64 a;\nmov.b64 a, {%2,%3};\nld.relaxed.gpu.global.v2.u32 {%0,%1}, [a+%4];\n}"
                 : "=r"(v.x), "=r"(v.y) : "r"(lo), "r"(hi), "n"(OFF) : "memory");
    return v;
}
template <uint32_t OFF> DEVI void stg4(uint32_t lo, uint32_t hi, uint32_t a, uint32_t b, uint32_t c, uint32_t d) {
    asm volatile("{\n.reg .b64 a;\nmov.b64 a, {%0,%1};\nst.relaxed.gpu.global.v4.u32 [a+%6], {%2,%3,%4,%5};\n}"
                 ::"r"(lo), "r"(hi), "r"(a), "r"(b), "r"(c), "r"(d), "n"(OFF) : "memory");
}
template <uint32_t OFF> DEVI void stg2(uint32_t lo, uint32_t hi, uint32_t a, uint32_t b) {
    asm volatile("{\n.reg .b64 a;\nmov.b64 a, {%0,%1};\nst.relaxed.gpu.global.v2.u32 [a+%4], {%2,%3};\n}"
                 ::"r"(lo), "r"(hi), "r"(a), "r"(b), "n"(OFF) : "memory");
}
DEVI uint32_t tagx2(uint32_t a, uint32_t b, uint32_t t) { uint32_t r; asm("lop3.b32 %0, %1, %2, %3, 0x7E;" : "=r"(r) : "r"(a), "r"(b), "r"(t)); return r; }
DEVI uint32_t tagx1(uint32_t a, uint32_t b, uint32_t t) { uint32_t r; asm("lop3.b32 %0, %1, %2, %3, 0xF6;" : "=r"(r) : "r"(a), "r"(b), "r"(t)); return r; }
DEVI uint32_t or3(uint32_t a, uint32_t b, uint32_t c) { uint32_t r; asm("lop3.b32 %0, %1, %2, %3, 0xFE;" : "=r"(r) : "r"(a), "r"(b), "r"(c)); return r; }
DEVI bool any_bad(uint32_t x) { return __any_sync(0xFFFFFFFFu, (x & 1u) != 0); }
DEVI uint32_t settag(uint32_t x, uint32_t tag) { return (x & ~1u) | tag; }
DEVI void sts32f(uint32_t a, float v) { asm volatile("st.shared.f32 [%0], %1;" ::"r"(a), "f"(v) : "memory"); }
DEVI void sts16(uint32_t a, uint32_t v) { asm volatile("st.shared.u16 [%0], %1;" ::"r"(a), "h"((unsigned short)v) : "memory"); }
DEVI void sts64(uint32_t a, uint32_t x, uint32_t y) { asm volatile("st.shared.v2.u32 [%0], {%1,%2};" ::"r"(a), "r"(x), "r"(y) : "memory"); }
DEVI void sts128(uint32_t a, uint32_t x, uint32_t y, uint32_t z, uint32_t w) {
    asm volatile("st.shared.v4.u32 [%0], {%1,%2,%3,%4};" ::"r"(a), "r"(x), "r"(y), "r"(z), "r"(w) : "memory");
}
DEVI float4 lds128f(uint32_t a) {
    float4 v;
    asm volatile("ld.shared.v4.f32 {%0,%1,%2,%3}, [%4];" : "=f"(v.x), "=f"(v.y), "=f"(v.z), "=f"(v.w) : "r"(a) : "memory");
    return v;
}
DEVI uint4 lds128(uint32_t a) {
    uint4 v;
    asm volatile("ld.shared.v4.u32 {%0,%1,%2,%3}, [%4];" : "=r"(v.x), "=r"(v.y), "=r"(v.z), "=r"(v.w) : "r"(a) : "memory");
    return v;
}
DEVI uint2 lds64(uint32_t a) {
    uint2 v;
    asm volatile("ld.shared.v2.u32 {%0,%1}, [%2];" : "=r"(v.x), "=r"(v.y) : "r"(a) : "memory");
    return v;
}
template <int ID> DEVI void bar_s() { asm volatile("bar.sync %0, 256;" ::"n"(ID) : "memory"); }
template <int ID> DEVI void bar_a() { asm volatile("bar.arrive %0, 256;" ::"n"(ID) : "memory"); }
DEVI float ex2(float x) { float r; asm("ex2.approx.ftz.f32 %0, %1;" : "=f"(r) : "f"(x)); return r; }
DEVI float rcp(float x) { float r; asm("rcp.approx.ftz.f32 %0, %1;" : "=f"(r) : "f"(x)); return r; }
DEVI uint32_t clk() { uint32_t c; asm volatile("mov.u32 %0, %%clock;" : "=r"(c)::"memory"); return c; }

DEVI uint64_t mkdesc(uint32_t addr, uint32_t lbo, uint32_t sbo) {
    return (uint64_t)((addr & 0x3FFFF) >> 4) | ((uint64_t)(lbo >> 4) << 16) | ((uint64_t)(sbo >> 4) << 32) | ((uint64_t)1 << 62);
}
DEVI void wg_fence() { asm volatile("wgmma.fence.sync.aligned;" ::: "memory"); }
DEVI void wg_commit() { asm volatile("wgmma.commit_group.sync.aligned;" ::: "memory"); }
template <int N> DEVI void wg_wait() { asm volatile("wgmma.wait_group.sync.aligned %0;" ::"n"(N) : "memory"); }
template <int SC>
DEVI void wg_rs32(float (&d)[16], const uint32_t (&a)[4], uint64_t db) {
    if (SC) {
        asm volatile("wgmma.mma_async.sync.aligned.m64n32k16.f32.bf16.bf16 "
                     "{%0,%1,%2,%3,%4,%5,%6,%7,%8,%9,%10,%11,%12,%13,%14,%15}, {%16,%17,%18,%19}, %20, 1, 1, 1, 0;"
                     : "+f"(d[0]), "+f"(d[1]), "+f"(d[2]), "+f"(d[3]), "+f"(d[4]), "+f"(d[5]), "+f"(d[6]), "+f"(d[7]),
                       "+f"(d[8]), "+f"(d[9]), "+f"(d[10]), "+f"(d[11]), "+f"(d[12]), "+f"(d[13]), "+f"(d[14]), "+f"(d[15])
                     : "r"(a[0]), "r"(a[1]), "r"(a[2]), "r"(a[3]), "l"(db));
    } else {
        asm volatile("wgmma.mma_async.sync.aligned.m64n32k16.f32.bf16.bf16 "
                     "{%0,%1,%2,%3,%4,%5,%6,%7,%8,%9,%10,%11,%12,%13,%14,%15}, {%16,%17,%18,%19}, %20, 0, 1, 1, 0;"
                     : "=f"(d[0]), "=f"(d[1]), "=f"(d[2]), "=f"(d[3]), "=f"(d[4]), "=f"(d[5]), "=f"(d[6]), "=f"(d[7]),
                       "=f"(d[8]), "=f"(d[9]), "=f"(d[10]), "=f"(d[11]), "=f"(d[12]), "=f"(d[13]), "=f"(d[14]), "=f"(d[15])
                     : "r"(a[0]), "r"(a[1]), "r"(a[2]), "r"(a[3]), "l"(db));
    }
}

#define SM_WO 0
#define SM_STA 65536
#define SM_STB 131072
#define SM_X 196608
#define SM_BAR 212992
#define SM_TOTAL (212992 + 128)
#define SM_MEMT (SM_STB)
#define SM_OT (SM_STB + 4096)
#define SM_SPM (SM_STB + 6144)
#define SM_SPX (SM_SPM + 10368)
#define SM_PM (SM_SPX + 10368)
#define SM_PX (SM_PM + 640)
#define SM_VM (SM_PX + 640)
#define SM_QP (SM_VM + 2048)
#define SM_XF (SM_STB + 32768)
#define SM_XO (SM_STA)
#define SM_XW (SM_STA + 18432)
#define SM_XI (SM_STA + 30720)
#define BAR_X 32
#define BAR_XF 40
#define BAR_XI 48

#define SPIN_LIMIT (1 << 20)

#define PT(n)
#define PC(n, v)

template <bool MASK>
DEVI void softmax_row(uint32_t spA, uint32_t pA, bool lo8, bool masked) {
    float4 a = lds128f(spA), b = lds128f(spA ^ 16);
    float4 c = make_float4(0.f, 0.f, 0.f, 0.f), d = c;
    if (lo8) { c = lds128f(spA + 1024); d = lds128f((spA ^ 16) + 1024); }
    float s0 = ((a.x + a.y) + (a.z + a.w)) + ((b.x + b.y) + (b.z + b.w));
    float s1 = ((c.x + c.y) + (c.z + c.w)) + ((d.x + d.y) + (d.z + d.w));
    if (MASK) s0 = masked ? -1.0e9f * 11.313708499f : s0;
    s1 = lo8 ? s1 : s0;
    int mi = __float_as_int(fmaxf(s0, s1));
    mi ^= (mi >> 31) & 0x7FFFFFFF;
    mi = __reduce_max_sync(0xFFFFFFFFu, mi);
    mi ^= (mi >> 31) & 0x7FFFFFFF;
    const float c2 = 0.08838834764831845f * 1.4426950408889634f;
    float mc = __int_as_float(mi) * c2;
    float e0 = ex2(fmaf(s0, c2, -mc)), e1 = ex2(fmaf(s1, c2, -mc));
    uint32_t pk = pack2(e0, e1);
    sts16(pA, pk & 0xFFFF);
    if (lo8) sts16(pA + 64, pk >> 16);
}

struct Ctx {
    uint32_t sb, w, h, j, xlo, xhi, zero;
};
#define REFRESH() asm volatile("xor.b32 %0, %0, %1;" : "+r"(t16) : "r"(c.zero))

DEVI void pv_x(const Ctx& c, uint32_t t16, int sg) {
    const uint32_t ONES = 0x3F803F80u;
    const uint32_t sb = c.sb;
    const uint32_t l7 = (t16 >> 4) & 7;
    uint32_t p[4];
    ldsm4(p, sb + SM_PX + l7 * 80 + ((t16 >> 3) & 0x30));
    uint32_t p4 = ldsm1(sb + SM_PX + l7 * 80 + 64);
    const uint32_t av = sb + SM_XF + (sg & 1) * 16384 + 2048 + (t16 >> 1);
    const uint2 v0 = lds64(av), v1 = lds64(av + 4096), v2 = lds64(av + 8192), v3 = lds64(av + 12288);
    const uint2 vm = lds64(sb + SM_VM + (t16 >> 1));
    float o[4], dn[4];
    mma16z(o, v0.x, v0.y, v1.x, v1.y, p[0], p[1]);
    mma16z(dn, ONES, ONES, ONES, ONES, p[0], p[1]);
    mma16(o, v2.x, v2.y, v3.x, v3.y, p[2], p[3]);
    mma16(dn, ONES, ONES, ONES, ONES, p[2], p[3]);
    mma8(o, vm.x, vm.y, p4);
    mma8(dn, ONES, ONES, p4);
    float r0 = rcp(dn[0]), r1 = rcp(dn[1]);
    uint32_t u0 = movm(pack2(o[0] * r0, o[1] * r1));
    uint32_t u1 = movm(pack2(o[2] * r0, o[3] * r1));
    const bool odd = (t16 & 16) != 0;
    uint32_t snd = odd ? u0 : u1;
    uint32_t rcv = __shfl_xor_sync(0xFFFFFFFFu, snd, 1);
    uint32_t lo = odd ? rcv : u0, hi = odd ? u1 : rcv;
    const uint32_t off = (uint32_t)(sg * 32 + 8 * c.j) * (HD * 2) + c.h * 256 + c.w * 32 + ((t16 >> 6) & 7) * (HD * 2) + (t16 & 16) + ((t16 >> 2) & 8);
    asm volatile("st.global.v2.u32 [%0], {%1,%2};" ::"l"((char*)g_ox + off), "r"(lo), "r"(hi) : "memory");
}

#define XDOFF(ks) ((((ks) >> 2) * 4096 + ((ks) & 3) * 32) >> 4)
#define NK1 8

DEVI void issue_in(const Ctx& c, int s) {
    const uint32_t w = c.w, j = c.j;
    if (w < 3) {
        if (s >= 0 && elect()) {
            const uint32_t a = (j + 1 + w) & 3;
            mbar_expect(c.sb + SM_BAR + BAR_XF, 4096);
            bulk_g2s(c.sb + SM_XF + (s & 1) * 16384 + a * 4096, c.xlo + c.h * XO_HEAD + (s & 1) * XO_SLOT + XO_XF + a * 4096, c.xhi, 4096, c.sb + SM_BAR + BAR_XF);
        }
    } else if (w < 6) {
        if (s >= -1 && s + 1 < NSEG && elect()) {
            const uint32_t a = (j + w - 2) & 3;
            mbar_expect(c.sb + SM_BAR + BAR_XI, 6144);
            bulk_g2s(c.sb + SM_XI + (w - 3) * 6144, c.xlo + c.h * XO_HEAD + ((s + 1) & 1) * XO_SLOT + XO_XP + a * 18432 + (5 - w) * 6144, c.xhi, 6144,
                     c.sb + SM_BAR + BAR_XI);
        }
    }
}
DEVI void issue_mid(const Ctx& c, int s, const CUtensorMap* tmx) {
    if (c.w == 6) {
        if (s >= -2 && s + 2 < NSEG && elect()) bulk_s2g(c.xlo + c.h * XO_HEAD + (s & 1) * XO_SLOT + XO_XP + c.j * 18432, c.xhi, c.sb + SM_XO, 18432);
    } else if (c.w == 7) {
        if (s + 3 < NSEG && elect()) {
            mbar_expect(c.sb + SM_BAR + BAR_X, 16384);
            tma3d(c.sb + SM_X, tmx, c.sb + SM_BAR + BAR_X, 0, (s + 3) * 32, c.j * 4);
        }
    }
}

template <bool MAIN>
DEVI void window(const Ctx& c, uint32_t& t16, int s, const uint32_t (&Wq)[16][4], const uint32_t (&Wk)[16][4], const uint32_t (&Wv)[16][4]) {
    const uint32_t sb = c.sb, w = c.w, h = c.h, j = c.j, xhi = c.xhi;
    float xa[16], xb[16];
    const bool doX1 = (s + 3 < NSEG), doX2 = (s >= -1 && s + 1 < NSEG);
    const uint64_t xd = mkdesc(sb + SM_X + (s & c.zero), 16, 1024);
    const uint32_t hb1 = c.xlo + h * XO_HEAD + ((s + 1) & 1) * XO_SLOT;
    const uint32_t x1tag = (((s + 3) >> 1) & 1) ^ 1, x2tag = (((s + 1) >> 1) & 1) ^ 1;
    const uint32_t own = sb + SM_XW + ((s + 1) & 1) * 6144;
#define PARK(i) ((i) == j ? own : sb + SM_XO + (((i) - j - 1) & 3) * 6144)
    if (doX1) mbar_wait(sb + SM_BAR + BAR_X, (s + 3) & 1);
    PT(16);
    wg_fence();
#pragma unroll
    for (int ks = 0; ks < 16; ks++) {
        if (ks == 0) wg_rs32<0>(xa, Wq[ks], xd + XDOFF(ks));
        else wg_rs32<1>(xa, Wq[ks], xd + XDOFF(ks));
    }
    wg_commit();
#pragma unroll
    for (int ks = 0; ks < NK1; ks++) {
        if (ks == 0) wg_rs32<0>(xb, Wk[ks], xd + XDOFF(ks));
        else wg_rs32<1>(xb, Wk[ks], xd + XDOFF(ks));
    }
    wg_commit();
    PT(17);
    if (MAIN) {
        const uint32_t lane = (t16 >> 4) & 31;
        softmax_row<true>(sb + SM_SPX + w * 1280 + (w >> 2) * 32 + lane * 32 + ((t16 >> 2) & 16), sb + SM_PX + w * 80 + lane * 2, lane < 8, lane > 8 * j + w);
    }
    REFRESH();
    if (doX2) {
        PT(18);
        mbar_wait(sb + SM_BAR + BAR_XI, (s + 1) & 1);
#define SUM4(A, F) pack2((lo_f(A[0].F) + lo_f(A[1].F)) + (lo_f(A[2].F) + lo_f(A[3].F)), (hi_f(A[0].F) + hi_f(A[1].F)) + (hi_f(A[2].F) + hi_f(A[3].F)))
        {
            uint2 q[4];
            q[0] = lds64(sb + SM_XI + 4096 + (t16 >> 1)); q[1] = lds64(sb + SM_XI + 6144 + 4096 + (t16 >> 1));
            q[2] = lds64(sb + SM_XI + 12288 + 4096 + (t16 >> 1)); q[3] = lds64(own + 4096 + (t16 >> 1));
            int it = 0;
            while (any_bad(tagx1(tagx2(q[0].x, q[1].x, x2tag), q[2].x, x2tag))) {
                q[0] = ldg2<XO_XP + 2 * 6144 + 4096>(hb1 + ((j + 1) & 3) * 18432 + (t16 >> 1), xhi);
                q[1] = ldg2<XO_XP + 1 * 6144 + 4096>(hb1 + ((j + 2) & 3) * 18432 + (t16 >> 1), xhi);
                q[2] = ldg2<XO_XP + 0 * 6144 + 4096>(hb1 + ((j + 3) & 3) * 18432 + (t16 >> 1), xhi);
                if (++it > SPIN_LIMIT) __trap();
            }
            PC(20, it);
            sts64(sb + SM_QP + (t16 >> 1), movm(SUM4(q, x)), movm(SUM4(q, y)));
        }
        REFRESH();
        {
            uint4 kv[4];
            kv[0] = lds128(sb + SM_XI + t16); kv[1] = lds128(sb + SM_XI + 6144 + t16);
            kv[2] = lds128(sb + SM_XI + 12288 + t16); kv[3] = lds128(own + t16);
            int it = 0;
            while (any_bad(tagx1(tagx2(kv[0].x, kv[1].x, x2tag), kv[2].x, x2tag))) {
                kv[0] = ldg4<XO_XP + 2 * 6144>(hb1 + ((j + 1) & 3) * 18432 + t16, xhi);
                kv[1] = ldg4<XO_XP + 1 * 6144>(hb1 + ((j + 2) & 3) * 18432 + t16, xhi);
                kv[2] = ldg4<XO_XP + 0 * 6144>(hb1 + ((j + 3) & 3) * 18432 + t16, xhi);
                if (++it > SPIN_LIMIT) __trap();
            }
            PC(21, it);
            const uint32_t af = sb + SM_XF + ((s + 1) & 1) * 16384 + j * 4096 + (t16 >> 1);
            sts64(af, settag(movm(SUM4(kv, x)), x2tag), movm(SUM4(kv, y)));
            sts64(af + 2048, settag(SUM4(kv, z), x2tag), SUM4(kv, w));
        }
    }
    PT(11);
    REFRESH();
    wg_wait<1>();
#pragma unroll
    for (int i = 0; i < 4; i++) sts64(PARK(i) + 4096 + (t16 >> 1), settag(pack2(xa[4 * i], xa[4 * i + 1]), x1tag), pack2(xa[4 * i + 2], xa[4 * i + 3]));
    PT(12);
    REFRESH();
    if (MAIN && s < NSEG - 1) {
        if (w - 1 < 2) {
            const uint32_t rtag = (s & 1) ^ 1;
            const uint32_t g8 = (t16 >> 3) & 0x38, t = (t16 >> 4) & 3;
            const uint32_t a = c.xlo + XO_R + (j * 32 + h) * 4096 + (w - 1) * 64 + t * 128 + g8;
            const uint32_t sel = (t16 & 64) ? 0x3F800000u : 0x00003F80u;
            const uint32_t ab = c.xlo + XO_B + ((s + 1) * 4 + j) * 4096 + h * 128 + (w - 1) * 8 + g8 * 2;
            float r0[4], r1[4];
            int it = 0;
            uint32_t bad;
            do {
                uint2 v0 = ldg2<0>(a, xhi), v1 = ldg2<512>(a, xhi), v2 = ldg2<1024>(a, xhi), v3 = ldg2<1536>(a, xhi);
                uint2 v4 = ldg2<2048>(a, xhi), v5 = ldg2<2560>(a, xhi), v6 = ldg2<3072>(a, xhi), v7 = ldg2<3584>(a, xhi);
                bad = or3(tagx2(v0.x, v1.x, rtag), tagx2(v2.x, v3.x, rtag), tagx2(v4.x, v5.x, rtag)) | tagx2(v6.x, v7.x, rtag);
                mma16z(r0, v0.x, v0.y, v1.x, v1.y, sel, sel);
                mma16z(r1, v2.x, v2.y, v3.x, v3.y, sel, sel);
                mma16(r0, v4.x, v4.y, v5.x, v5.y, sel, sel);
                mma16(r1, v6.x, v6.y, v7.x, v7.y, sel, sel);
                if (++it > SPIN_LIMIT) __trap();
            } while (any_bad(bad));
            PT(13);
            PC(22, it);
            bar_a<5>();
            const uint32_t m0 = pack2(r0[0] + r1[0], r0[1] + r1[1]);
            const uint32_t m1 = pack2(r0[2] + r1[2], r0[3] + r1[3]);
            if (t == 0) stg2<0>(ab, xhi, m0, m1);
        } else {
            bar_s<5>();
        }
    }
    PT(14);
    REFRESH();
    wg_wait<0>();
    wg_fence();
#pragma unroll
    for (int ks = NK1; ks < 16; ks++) {
        if (ks == 0) wg_rs32<0>(xb, Wk[ks], xd + XDOFF(ks));
        else wg_rs32<1>(xb, Wk[ks], xd + XDOFF(ks));
    }
#pragma unroll
    for (int ks = 0; ks < 16; ks++) {
        if (ks == 0) wg_rs32<0>(xa, Wv[ks], xd + XDOFF(ks));
        else wg_rs32<1>(xa, Wv[ks], xd + XDOFF(ks));
    }
    wg_commit();
    if (doX2) {
        const uint32_t af = sb + SM_XF + ((s + 1) & 1) * 16384 + j * 4096 + (t16 >> 1);
        const uint2 k = lds64(af), v = lds64(af + 2048);
        stg2<XO_XF>(hb1 + j * 4096 + (t16 >> 1), xhi, k.x, k.y);
        stg2<XO_XF + 2048>(hb1 + j * 4096 + (t16 >> 1), xhi, v.x, v.y);
    }
    uint4 mv;
    const uint32_t ab = c.xlo + XO_B + ((s + 1) * 4 + j) * 4096 + t16;
    wg_wait<0>();
    if (MAIN && s < NSEG - 1) mv = ldg4<0>(ab, xhi);
    else mv = make_uint4(0, 0, 0, 0);
#pragma unroll
    for (int i = 0; i < 4; i++)
        sts128(PARK(i) + t16, settag(pack2(xb[4 * i], xb[4 * i + 1]), x1tag), pack2(xb[4 * i + 2], xb[4 * i + 3]),
               pack2(xa[4 * i], xa[4 * i + 1]), pack2(xa[4 * i + 2], xa[4 * i + 3]));
    PT(15);
    if (MAIN && s < NSEG - 1) {
        int it = 0;
        while (__any_sync(0xFFFFFFFFu, mv.x == 0xFFFFFFFFu || mv.z == 0xFFFFFFFFu)) {
            mv = ldg4<0>(ab, xhi);
            if (++it > SPIN_LIMIT) __trap();
        }
        stsm4(sb + SM_MEMT + t16, mv.x, mv.y, mv.z, mv.w);
        PC(23, it);
    }
    REFRESH();
}

__global__ void __launch_bounds__(256, 1)
chain_kernel(const __grid_constant__ CUtensorMap tmq, const __grid_constant__ CUtensorMap tmk,
             const __grid_constant__ CUtensorMap tmv, const __grid_constant__ CUtensorMap tmo,
             const __grid_constant__ CUtensorMap tmx, const bf16* __restrict__ mem0, const bf16* __restrict__ xg,
             uint32_t xlo, uint32_t xhi, uint32_t zero) {
    extern __shared__ __align__(1024) uint8_t smem[];
    const uint32_t sb = smem_u32(smem);
    const uint32_t w = __reduce_max_sync(0xFFFFFFFFu, threadIdx.x >> 5);
    const uint32_t h = blockIdx.x >> 2, j = blockIdx.x & 3;
    const uint32_t bq = sb + SM_BAR, bk = bq + 8, bv = bq + 16, bo = bq + 24;
    uint32_t Wq[16][4], Wk[16][4], Wv[16][4];
    uint32_t t16;
    {
        const int tid = threadIdx.x, lane = tid & 31;
        if (tid == 0) {
            mbar_init(bq, 1); mbar_init(bk, 1); mbar_init(bv, 1); mbar_init(bo, 1);
            mbar_init(bq + BAR_X, 1); mbar_init(bq + BAR_XF, 3); mbar_init(bq + BAR_XI, 3);
            asm volatile("fence.mbarrier_init.release.cluster;" ::: "memory");
            asm volatile("fence.proxy.async.shared::cta;" ::: "memory");
            mbar_expect(bq, 65536);
            tma2d(sb + SM_STA, &tmq, bq, h * 128, j * 256);
            tma2d(sb + SM_STA + 32768, &tmq, bq, h * 128 + 64, j * 256);
            mbar_expect(bk, 65536);
            tma2d(sb + SM_STB, &tmk, bk, h * 128, j * 256);
            tma2d(sb + SM_STB + 32768, &tmk, bk, h * 128 + 64, j * 256);
            mbar_expect(bo, 65536);
            for (int i = 0; i < 4; i++) tma2d(sb + SM_WO + i * 16384, &tmo, bo, j * 256 + i * 64, h * 128);
        }
        __syncthreads();
        const uint32_t chunk = (uint32_t)((w & 3) * 2 + ((lane >> 3) & 1));
        const uint32_t off = (uint32_t)(w >> 2) * 32768u + (uint32_t)(((lane >> 4) & 1) * 8 + (lane & 7)) * 128u + ((chunk ^ (lane & 7)) << 4);
        mbar_wait(bq, 0);
#pragma unroll
        for (int ks = 0; ks < 16; ks++) ldsm4t(Wq[ks], sb + SM_STA + off + ks * 2048);
        __syncthreads();
        if (tid == 0) {
            asm volatile("fence.proxy.async.shared::cta;" ::: "memory");
            mbar_expect(bv, 65536);
            tma2d(sb + SM_STA, &tmv, bv, h * 128, j * 256);
            tma2d(sb + SM_STA + 32768, &tmv, bv, h * 128 + 64, j * 256);
            asm volatile("cp.async.bulk.prefetch.L2.global [%0], %1;" ::"l"((const char*)xg + blockIdx.x * 32768), "r"(32768) : "memory");
        }
        mbar_wait(bk, 0);
#pragma unroll
        for (int ks = 0; ks < 16; ks++) ldsm4t(Wk[ks], sb + SM_STB + off + ks * 2048);
        __syncthreads();
        {
            const unsigned short* m0 = (const unsigned short*)mem0 + j * 256 + tid;
            uint32_t v[4];
#pragma unroll
            for (int i = 0; i < 4; i++) v[i] = (uint32_t)m0[(2 * i) * DM] | ((uint32_t)m0[(2 * i + 1) * DM] << 16);
            sts128(sb + SM_MEMT + tid * 16, v[0], v[1], v[2], v[3]);
        }
        t16 = __shfl_sync(0xFFFFFFFFu, tid * 16, lane);
        mbar_wait(bv, 0);
#pragma unroll
        for (int ks = 0; ks < 16; ks++) ldsm4t(Wv[ks], sb + SM_STA + off + ks * 2048);
        mbar_wait(bo, 0);
    }
    const Ctx c = {sb, w, h, j, xlo, xhi, zero};
    const uint32_t ONES = 0x3F803F80u;

#pragma unroll 1
    for (int s = -3; s < 0; s++) {
        bar_s<1>();
        asm volatile("fence.proxy.async.shared::cta;" ::: "memory");
        issue_in(c, s);
        issue_mid(c, s, &tmx);
        if (w == 6) asm volatile("cp.async.bulk.wait_group.read 0;" ::: "memory");
        bar_s<1>();
        window<false>(c, t16, s, Wq, Wk, Wv);
    }

#pragma unroll 1
    for (int s = 0; s < NSEG; s++) {
        const uint32_t ctag = ((s >> 1) & 1) ^ 1;
        const uint32_t hb = xlo + h * XO_HEAD + (s & 1) * XO_SLOT;
        PT(0);
        bar_s<1>();
        PT(1);
        uint32_t oq0, oq1, ok0, ok1, ov0, ov1;
        {
            uint32_t b[8][4];
#pragma unroll
            for (int p = 0; p < 8; p++) ldsm4t(b[p], sb + SM_MEMT + (t16 & 0x1F0) + p * 512);
            issue_in(c, s);
            float q0[4], q1[4], k0[4], k1[4];
#pragma unroll
            for (int p = 0; p < 8; p++) {
                if (p == 0) {
                    mma16z(q0, Wq[0][0], Wq[0][1], Wq[0][2], Wq[0][3], b[p][0], b[p][1]);
                    mma16z(k0, Wk[0][0], Wk[0][1], Wk[0][2], Wk[0][3], b[p][0], b[p][1]);
                    mma16z(q1, Wq[1][0], Wq[1][1], Wq[1][2], Wq[1][3], b[p][2], b[p][3]);
                    mma16z(k1, Wk[1][0], Wk[1][1], Wk[1][2], Wk[1][3], b[p][2], b[p][3]);
                } else {
                    mma16(q0, Wq[2 * p][0], Wq[2 * p][1], Wq[2 * p][2], Wq[2 * p][3], b[p][0], b[p][1]);
                    mma16(k0, Wk[2 * p][0], Wk[2 * p][1], Wk[2 * p][2], Wk[2 * p][3], b[p][0], b[p][1]);
                    mma16(q1, Wq[2 * p + 1][0], Wq[2 * p + 1][1], Wq[2 * p + 1][2], Wq[2 * p + 1][3], b[p][2], b[p][3]);
                    mma16(k1, Wk[2 * p + 1][0], Wk[2 * p + 1][1], Wk[2 * p + 1][2], Wk[2 * p + 1][3], b[p][2], b[p][3]);
                }
            }
            oq0 = pack2(q0[0] + q1[0], q0[1] + q1[1]);
            oq1 = pack2(q0[2] + q1[2], q0[3] + q1[3]);
            ok0 = pack2(k0[0] + k1[0], k0[1] + k1[1]);
            ok1 = pack2(k0[2] + k1[2], k0[3] + k1[3]);
            stg4<XO_CQK>(hb + j * 4096 + t16, xhi, settag(oq0, ctag), oq1, ok0, ok1);
            PT(2);
            const float z = __uint_as_float(ok1 & zero);
#pragma unroll
            for (int i = 0; i < 4; i++) q0[i] = q1[i] = k0[i] = z;
#pragma unroll
            for (int ks = 0; ks < 16; ks++) {
                if (ks % 3 == 0) mma16(q0, Wv[ks][0], Wv[ks][1], Wv[ks][2], Wv[ks][3], b[ks >> 1][(ks & 1) * 2], b[ks >> 1][(ks & 1) * 2 + 1]);
                if (ks % 3 == 1) mma16(q1, Wv[ks][0], Wv[ks][1], Wv[ks][2], Wv[ks][3], b[ks >> 1][(ks & 1) * 2], b[ks >> 1][(ks & 1) * 2 + 1]);
                if (ks % 3 == 2) mma16(k0, Wv[ks][0], Wv[ks][1], Wv[ks][2], Wv[ks][3], b[ks >> 1][(ks & 1) * 2], b[ks >> 1][(ks & 1) * 2 + 1]);
            }
            ov0 = pack2((q1[0] + k0[0]) + q0[0], (q1[1] + k0[1]) + q0[1]);
            ov1 = pack2((q1[2] + k0[2]) + q0[2], (q1[3] + k0[3]) + q0[3]);
            stg2<XO_CV>(hb + j * 2048 + (t16 >> 1), xhi, settag(ov0, ctag), ov1);
        }
        PT(3);
        REFRESH();
        uint4 c1 = ldg4<XO_CQK>(hb + (j ^ 1) * 4096 + t16, xhi);
        uint4 c2 = ldg4<XO_CQK>(hb + (j ^ 2) * 4096 + t16, xhi);
        uint4 c3 = ldg4<XO_CQK>(hb + (j ^ 3) * 4096 + t16, xhi);
        if (s >= 1) pv_x(c, t16, s - 1);
        PT(4);
        REFRESH();
        {
            uint2 d1 = ldg2<XO_CV>(hb + (j ^ 1) * 2048 + (t16 >> 1), xhi);
            uint2 d2 = ldg2<XO_CV>(hb + (j ^ 2) * 2048 + (t16 >> 1), xhi);
            uint2 d3 = ldg2<XO_CV>(hb + (j ^ 3) * 2048 + (t16 >> 1), xhi);
            const uint32_t lane = (t16 >> 4) & 31, g = lane >> 2, t = lane & 3;
            const uint32_t aSpW = sb + SM_SPM + (g * 320 + (g >> 2) * 8 + 16 * t + (w ^ (((t >> 1) << 2) | (g & 3)))) * 4u;
            const uint32_t af = sb + SM_XF + (s & 1) * 16384 + (t16 >> 1);
            mbar_wait(bq + BAR_XF, s & 1);
            PT(19);
            uint2 kx[4];
            {
                uint32_t vt[4];
#pragma unroll
                for (int i = 0; i < 4; i++) { kx[i] = lds64(af + i * 4096); vt[i] = lds64(af + i * 4096 + 2048).x; }
                int it = 0;
                while (any_bad(or3(tagx2(kx[0].x, kx[1].x, ctag), tagx2(kx[2].x, kx[3].x, ctag), tagx2(vt[0], vt[1], ctag)) | tagx2(vt[2], vt[3], ctag))) {
#define RELD(i) { kx[i] = ldg2<XO_XF + (i) * 4096>(hb + (t16 >> 1), xhi); const uint2 vv = ldg2<XO_XF + (i) * 4096 + 2048>(hb + (t16 >> 1), xhi); \
                  vt[i] = vv.x; sts64(af + (i) * 4096 + 2048, vv.x, vv.y); }
                    RELD(0) RELD(1) RELD(2) RELD(3)
                    if (++it > SPIN_LIMIT) __trap();
                }
                PC(24, it);
            }
            const uint2 qx = lds64(sb + SM_QP + (t16 >> 1));
            if (w == 6) asm volatile("fence.proxy.async.shared::cta;" ::: "memory");
            PT(5);
            {
                int it = 0;
                while (any_bad(tagx1(tagx2(c1.x, c2.x, ctag), c3.x, ctag))) {
                    c1 = ldg4<XO_CQK>(hb + (j ^ 1) * 4096 + t16, xhi);
                    c2 = ldg4<XO_CQK>(hb + (j ^ 2) * 4096 + t16, xhi);
                    c3 = ldg4<XO_CQK>(hb + (j ^ 3) * 4096 + t16, xhi);
                    if (++it > SPIN_LIMIT) __trap();
                }
                PC(25, it);
            }
            PT(6);
            const uint32_t qT0 = movm(hadd2(hadd2(oq0, c1.x), hadd2(c2.x, c3.x)));
            const uint32_t qT1 = movm(hadd2(hadd2(oq1, c1.y), hadd2(c2.y, c3.y)));
            const uint32_t kT0 = movm(hadd2(hadd2(ok0, c1.z), hadd2(c2.z, c3.z)));
            const uint32_t kT1 = movm(hadd2(hadd2(ok1, c1.w), hadd2(c2.w, c3.w)));
            float sc[5][4];
#pragma unroll
            for (int i = 0; i < 4; i++) mma16z(sc[i], qT0, qx.x, qT1, qx.y, kx[i].x, kx[i].y);
            mma16z(sc[4], qT0, qx.x, qT1, qx.y, kT0, kT1);
#pragma unroll
            for (int i = 0; i < 5; i++) { sts32f(aSpW + i * 256, sc[i][0]); sts32f(aSpW + i * 256 + 32, sc[i][1]); }
            issue_mid(c, s, &tmx);
            bar_s<2>();
            PT(7);
            softmax_row<false>(sb + SM_SPM + w * 1280 + (w >> 2) * 32 + lane * 32 + ((t16 >> 2) & 16), sb + SM_PM + w * 80 + lane * 2, lane < 8, false);
#pragma unroll
            for (int i = 0; i < 5; i++) { sts32f(aSpW + (SM_SPX - SM_SPM) + i * 256, sc[i][2]); sts32f(aSpW + (SM_SPX - SM_SPM) + i * 256 + 32, sc[i][3]); }
            const uint2 v0 = lds64(af + 2048), v1 = lds64(af + 4096 + 2048), v2 = lds64(af + 8192 + 2048), v3 = lds64(af + 12288 + 2048);
            {
                int it = 0;
                while (any_bad(tagx1(tagx2(d1.x, d2.x, ctag), d3.x, ctag))) {
                    d1 = ldg2<XO_CV>(hb + (j ^ 1) * 2048 + (t16 >> 1), xhi);
                    d2 = ldg2<XO_CV>(hb + (j ^ 2) * 2048 + (t16 >> 1), xhi);
                    d3 = ldg2<XO_CV>(hb + (j ^ 3) * 2048 + (t16 >> 1), xhi);
                    if (++it > SPIN_LIMIT) __trap();
                }
                PC(26, it);
            }
            const uint32_t vm0 = hadd2(hadd2(ov0, d1.x), hadd2(d2.x, d3.x));
            const uint32_t vm1 = hadd2(hadd2(ov1, d1.y), hadd2(d2.y, d3.y));
            const uint32_t aWo = sb + SM_WO + (w >> 1) * 16384u + (((lane >> 4) & 1) * 8 + (lane & 7)) * 128u +
                                 ((((w & 1) * 4 + ((lane >> 3) & 1)) ^ (lane & 7)) << 4);
            uint32_t wo[16][4];
            bar_s<3>();
            PT(8);
            uint32_t p[4];
            ldsm4(p, sb + SM_PM + (lane & 7) * 80 + (lane >> 3) * 16);
            uint32_t p4 = ldsm1(sb + SM_PM + (lane & 7) * 80 + 64);
            float oa[4], ob[4], dn[4];
            mma16z(oa, v0.x, v0.y, v1.x, v1.y, p[0], p[1]);
            mma16z(ob, v2.x, v2.y, v3.x, v3.y, p[2], p[3]);
            mma8(oa, vm0, vm1, p4);
            mma16z(dn, ONES, ONES, ONES, ONES, p[0], p[1]);
            mma16(dn, ONES, ONES, ONES, ONES, p[2], p[3]);
            mma8(dn, ONES, ONES, p4);
#pragma unroll
            for (int i = 0; i < 6; i++) ldsm4t(wo[i], (aWo ^ ((i & 1) << 5)) + (i >> 1) * 2048);
            stsm2(sb + SM_OT + w * 256 + (t16 & 0xF0), pack2(oa[0] + ob[0], oa[1] + ob[1]), pack2(oa[2] + ob[2], oa[3] + ob[3]));
            sts64(sb + SM_VM + (t16 >> 1), vm0, vm1);
            if (w == 6) asm volatile("cp.async.bulk.wait_group.read 0;" ::: "memory");
            bar_s<4>();
            PT(9);
            float r[2][2][4];
#pragma unroll
            for (int pp = 0; pp < 4; pp++) {
                uint32_t b[4];
                ldsm4t(b, sb + SM_OT + (t16 & 0x1F0) + pp * 512);
#pragma unroll
                for (int e = 0; e < 2; e++)
#pragma unroll
                    for (int mt = 0; mt < 2; mt++) {
                        const int i = (pp * 2 + e) * 2 + mt;
                        if (pp == 0) mma16z(r[mt][e], wo[i][0], wo[i][1], wo[i][2], wo[i][3], b[2 * e], b[2 * e + 1]);
                        else mma16(r[mt][e], wo[i][0], wo[i][1], wo[i][2], wo[i][3], b[2 * e], b[2 * e + 1]);
                        if (i + 6 < 16) ldsm4t(wo[i + 6], (aWo ^ ((i & 1) << 5)) + ((i + 6) >> 1) * 2048);
                    }
            }
            const float r0 = rcp(dn[0]), r1 = rcp(dn[1]);
            const uint32_t rtag = (s & 1) ^ 1;
            uint32_t y0 = pack2((r[0][0][0] + r[0][1][0]) * r0, (r[0][0][1] + r[0][1][1]) * r1);
            uint32_t y1 = pack2((r[0][0][2] + r[0][1][2]) * r0, (r[0][0][3] + r[0][1][3]) * r1);
            uint32_t y2 = pack2((r[1][0][0] + r[1][1][0]) * r0, (r[1][0][1] + r[1][1][1]) * r1);
            uint32_t y3 = pack2((r[1][0][2] + r[1][1][2]) * r0, (r[1][0][3] + r[1][1][3]) * r1);
            const uint32_t ar = xlo + XO_R + j * 131072 + h * 128 + (t16 >> 7) * 4096 + ((t16 >> 1) & 0x38);
            stg2<0>(ar, xhi, settag(y0, rtag), y1);
            stg2<64>(ar, xhi, settag(y2, rtag), y3);
        }
        PT(10);
        REFRESH();
        window<true>(c, t16, s, Wq, Wk, Wv);
    }
    bar_s<1>();
    pv_x(c, t16, NSEG - 1);
}

#define G2_STAGES 6
#define G2_STAGE_BYTES 32768
DEVI void wg_ss128t(float (&d)[64], uint64_t da, uint64_t db, int sc) {
    asm volatile("{\n.reg .pred p;\nsetp.ne.b32 p, %66, 0;\n"
                 "wgmma.mma_async.sync.aligned.m64n128k16.f32.bf16.bf16 "
                 "{%0,%1,%2,%3,%4,%5,%6,%7,%8,%9,%10,%11,%12,%13,%14,%15,%16,%17,%18,%19,%20,%21,%22,%23,%24,%25,%26,%27,%28,%29,%30,%31,"
                 "%32,%33,%34,%35,%36,%37,%38,%39,%40,%41,%42,%43,%44,%45,%46,%47,%48,%49,%50,%51,%52,%53,%54,%55,%56,%57,%58,%59,%60,%61,%62,%63}, "
                 "%64, %65, p, 1, 1, 0, 1;\n}\n"
                 : "+f"(d[0]), "+f"(d[1]), "+f"(d[2]), "+f"(d[3]), "+f"(d[4]), "+f"(d[5]), "+f"(d[6]), "+f"(d[7]),
                   "+f"(d[8]), "+f"(d[9]), "+f"(d[10]), "+f"(d[11]), "+f"(d[12]), "+f"(d[13]), "+f"(d[14]), "+f"(d[15]),
                   "+f"(d[16]), "+f"(d[17]), "+f"(d[18]), "+f"(d[19]), "+f"(d[20]), "+f"(d[21]), "+f"(d[22]), "+f"(d[23]),
                   "+f"(d[24]), "+f"(d[25]), "+f"(d[26]), "+f"(d[27]), "+f"(d[28]), "+f"(d[29]), "+f"(d[30]), "+f"(d[31]),
                   "+f"(d[32]), "+f"(d[33]), "+f"(d[34]), "+f"(d[35]), "+f"(d[36]), "+f"(d[37]), "+f"(d[38]), "+f"(d[39]),
                   "+f"(d[40]), "+f"(d[41]), "+f"(d[42]), "+f"(d[43]), "+f"(d[44]), "+f"(d[45]), "+f"(d[46]), "+f"(d[47]),
                   "+f"(d[48]), "+f"(d[49]), "+f"(d[50]), "+f"(d[51]), "+f"(d[52]), "+f"(d[53]), "+f"(d[54]), "+f"(d[55]),
                   "+f"(d[56]), "+f"(d[57]), "+f"(d[58]), "+f"(d[59]), "+f"(d[60]), "+f"(d[61]), "+f"(d[62]), "+f"(d[63])
                 : "l"(da), "l"(db), "r"(sc));
}

__global__ void __launch_bounds__(288, 1)
gemm2_kernel(const __grid_constant__ CUtensorMap tma, const __grid_constant__ CUtensorMap tmb, bf16* __restrict__ out) {
    extern __shared__ __align__(1024) uint8_t smem[];
    const uint32_t sb = smem_u32(smem);
    const uint32_t bars = sb + G2_STAGES * G2_STAGE_BYTES;
    const int tid = threadIdx.x, lane = tid & 31;
    const int w = __shfl_sync(0xFFFFFFFFu, tid >> 5, 0);
    const int bm = blockIdx.x >> 3, bn = blockIdx.x & 7;
    if (tid == 0) {
        for (int i = 0; i < G2_STAGES; i++) { mbar_init(bars + i * 8, 1); mbar_init(bars + (G2_STAGES + i) * 8, 2); }
        asm volatile("fence.mbarrier_init.release.cluster;" ::: "memory");
        asm volatile("fence.proxy.async.shared::cta;" ::: "memory");
    }
    __syncthreads();
    const int NK = HD / 64;
    if (w == 8) {
        if (lane == 0) {
            int st = 0, ph = 1;
            for (int kb = 0; kb < NK; kb++) {
                mbar_wait(bars + (G2_STAGES + st) * 8, ph);
                const uint32_t dst = sb + st * G2_STAGE_BYTES;
                mbar_expect(bars + st * 8, G2_STAGE_BYTES);
                tma2d(dst, &tma, bars + st * 8, kb * 64, bm * 128);
                tma2d(dst + 16384, &tmb, bars + st * 8, bn * 128, kb * 64);
                tma2d(dst + 24576, &tmb, bars + st * 8, bn * 128 + 64, kb * 64);
                if (++st == G2_STAGES) { st = 0; ph ^= 1; }
            }
        }
    } else {
        const int wg = w >> 2;
        float acc[64];
        int st = 0, ph = 0;
        for (int kb = 0; kb < NK; kb++) {
            mbar_wait(bars + st * 8, ph);
            const uint32_t base = sb + st * G2_STAGE_BYTES;
            const uint64_t da = mkdesc(base + wg * 8192, 16, 1024);
            const uint64_t db = mkdesc(base + 16384, 8192, 1024);
            wg_fence();
#pragma unroll
            for (int k = 0; k < 4; k++) wg_ss128t(acc, da + k * 2, db + k * 128, (kb | k) != 0);
            wg_commit();
            if (kb > 0) {
                wg_wait<1>();
                const int pst = st == 0 ? G2_STAGES - 1 : st - 1;
                if ((tid & 127) == 0) mbar_arrive(bars + (G2_STAGES + pst) * 8);
            }
            if (++st == G2_STAGES) { st = 0; ph ^= 1; }
        }
        wg_wait<0>();
        const int row = bm * 128 + wg * 64 + (w & 3) * 16 + (lane >> 2);
        bf16* o = out + (size_t)row * 2048 + bn * 128 + (lane & 3) * 2;
#pragma unroll
        for (int i = 0; i < 16; i++) {
            *(uint32_t*)(o + i * 8) = pack2(acc[4 * i], acc[4 * i + 1]);
            *(uint32_t*)(o + 8 * 2048 + i * 8) = pack2(acc[4 * i + 2], acc[4 * i + 3]);
        }
    }
}

template <int N, int LOGN, int NT>
DEVI void fft_smem(float2* x, int tid, float sgn) {
    for (int st = 0; st < LOGN; st++) {
        const int half = 1 << st;
        __syncthreads();
        for (int i = tid; i < N / 2; i += NT) {
            const int k = i & (half - 1), base = ((i >> st) << (st + 1)) + k;
            float sn, cs;
            sincospif(sgn * (float)k / (float)half, &sn, &cs);
            const float2 a = x[base], b = x[base + half];
            const float2 tw = make_float2(b.x * cs - b.y * sn, b.x * sn + b.y * cs);
            x[base] = make_float2(a.x + tw.x, a.y + tw.y);
            x[base + half] = make_float2(a.x - tw.x, a.y - tw.y);
        }
    }
    __syncthreads();
}
__global__ void __launch_bounds__(256) fft_rows_fwd(const bf16* __restrict__ x) {
    __shared__ float2 sm[1024];
    const int row = blockIdx.x, tid = threadIdx.x;
    for (int i = tid; i < 1024; i += 256) sm[__brev(i) >> 22] = make_float2(__bfloat162float(x[row * 1024 + i]), 0.f);
    fft_smem<1024, 10, 256>(sm, tid, -1.f);
    for (int i = tid; i < 513; i += 256) g_F[row * 520 + i] = sm[i];
}
__global__ void __launch_bounds__(256) fft_cols(const bf16* __restrict__ wr, const bf16* __restrict__ wi) {
    __shared__ float2 sm[2048], sm2[2048];
    const int col = blockIdx.x, tid = threadIdx.x;
    for (int i = tid; i < 2048; i += 256) sm[__brev(i) >> 21] = g_F[i * 520 + col];
    fft_smem<2048, 11, 256>(sm, tid, -1.f);
    for (int i = tid; i < 2048; i += 256) {
        const float a = __bfloat162float(wr[i * 513 + col]), b = __bfloat162float(wi[i * 513 + col]);
        const float2 v = sm[i];
        sm2[__brev(i) >> 21] = make_float2(v.x * a - v.y * b, v.x * b + v.y * a);
    }
    fft_smem<2048, 11, 256>(sm2, tid, 1.f);
    for (int i = tid; i < 2048; i += 256) g_F[i * 520 + col] = sm2[i];
}
__global__ void __launch_bounds__(256) fft_rows_inv(bf16* __restrict__ out) {
    __shared__ float2 sm[1024];
    const int row = blockIdx.x, tid = threadIdx.x;
    for (int i = tid; i < 1024; i += 256) {
        float2 v;
        if (i <= 512) { v = g_F[row * 520 + i]; if (i == 0 || i == 512) v.y = 0.f; }
        else { v = g_F[row * 520 + 1024 - i]; v.y = -v.y; }
        sm[__brev(i) >> 22] = v;
    }
    fft_smem<1024, 10, 256>(sm, tid, 1.f);
    const float sc = 1.f / (2048.f * 1024.f);
    for (int i = tid; i < 1024; i += 256) out[(size_t)row * 2048 + 1024 + i] = __float2bfloat16(sm[i].x * sc);
}

typedef CUresult (*EncodeFn)(CUtensorMap*, CUtensorMapDataType, cuuint32_t, void*, const cuuint64_t*, const cuuint64_t*,
                             const cuuint32_t*, const cuuint32_t*, CUtensorMapInterleave, CUtensorMapSwizzle,
                             CUtensorMapL2promotion, CUtensorMapFloatOOBfill);

static void make_map(EncodeFn enc, CUtensorMap* m, const void* ptr, int rank, const cuuint64_t* dims, const cuuint64_t* strides,
                     const cuuint32_t* box) {
    cuuint32_t es[3] = {1, 1, 1};
    CUresult r = enc(m, CU_TENSOR_MAP_DATA_TYPE_BFLOAT16, rank, (void*)ptr, dims, strides, box, es, CU_TENSOR_MAP_INTERLEAVE_NONE,
                     CU_TENSOR_MAP_SWIZZLE_128B, CU_TENSOR_MAP_L2_PROMOTION_L2_256B, CU_TENSOR_MAP_FLOAT_OOB_FILL_NONE);
    if (r != CUDA_SUCCESS) fprintf(stderr, "tensor map encode failed: %d\n", (int)r);
}

extern "C" void kernel_launch(void* const* d_in, const int* in_sizes, int n_in, void* d_out, int out_size) {
    const bf16* A_x = (const bf16*)d_in[0];
    const bf16* A_mem0 = (const bf16*)d_in[1];
    const bf16* A_Wq = (const bf16*)d_in[2];
    const bf16* A_Wk = (const bf16*)d_in[3];
    const bf16* A_Wv = (const bf16*)d_in[4];
    const bf16* A_Wo = (const bf16*)d_in[5];
    const bf16* B_x = (const bf16*)d_in[7];
    const bf16* B_wr = (const bf16*)d_in[8];
    const bf16* B_wi = (const bf16*)d_in[9];
    bf16* out = (bf16*)d_out;

    static EncodeFn enc = nullptr;
    static void *pxs = nullptr, *pox = nullptr;
    if (!enc) {
        cudaDriverEntryPointQueryResult qr;
        void* fn = nullptr;
        cudaGetDriverEntryPoint("cuTensorMapEncodeTiled", &fn, cudaEnableDefault, &qr);
        enc = (EncodeFn)fn;
        cudaFuncSetAttribute(chain_kernel, cudaFuncAttributeMaxDynamicSharedMemorySize, SM_TOTAL);
        cudaFuncSetAttribute(gemm2_kernel, cudaFuncAttributeMaxDynamicSharedMemorySize, G2_STAGES * G2_STAGE_BYTES + 128);
        cudaGetSymbolAddress(&pxs, g_xs);
        cudaGetSymbolAddress(&pox, g_ox);
    }
    CUtensorMap tmq, tmk, tmv, tmo, tmx, tma, tmb;
    {
        cuuint64_t d[2] = {HD, DM}, st[1] = {HD * 2};
        cuuint32_t bx[2] = {64, 256};
        make_map(enc, &tmq, A_Wq, 2, d, st, bx);
        make_map(enc, &tmk, A_Wk, 2, d, st, bx);
        make_map(enc, &tmv, A_Wv, 2, d, st, bx);
    }
    {
        cuuint64_t d[2] = {DM, HD}, st[1] = {DM * 2};
        cuuint32_t bx[2] = {64, 128}, bx2[2] = {64, 64};
        make_map(enc, &tmo, A_Wo, 2, d, st, bx);
        make_map(enc, &tmb, A_Wo, 2, d, st, bx2);
    }
    {
        cuuint64_t d[3] = {64, SEQ, DM / 64}, st[2] = {DM * 2, 128};
        cuuint32_t bx[3] = {64, 32, 4};
        make_map(enc, &tmx, A_x, 3, d, st, bx);
    }
    {
        cuuint64_t d[2] = {HD, SEQ}, st[1] = {HD * 2};
        cuuint32_t bx[2] = {64, 128};
        make_map(enc, &tma, pox, 2, d, st, bx);
    }
    cudaStream_t st = cudaStreamPerThread;
    const uint64_t xs = ((uint64_t)pxs + XS_BYTES - 1) & ~(uint64_t)(XS_BYTES - 1);
    cudaMemsetAsync((void*)(xs + XO_B), 0xFF, NSEG * 4 * 4096, st);
    chain_kernel<<<128, 256, SM_TOTAL, st>>>(tmq, tmk, tmv, tmo, tmx, A_mem0, A_x, (uint32_t)xs, (uint32_t)(xs >> 32), 0u);
    gemm2_kernel<<<128, 288, G2_STAGES * G2_STAGE_BYTES + 128, st>>>(tma, tmb, out);
    fft_rows_fwd<<<2048, 256, 0, st>>>(B_x);
    fft_cols<<<513, 256, 0, st>>>(B_wr, B_wi);
    fft_rows_inv<<<2048, 256, 0, st>>>(out);
}
```

```cpp
#include <cuda_runtime.h>
#include <cuda_bf16.h>
#include <cuda.h>
#include <stdint.h>
#include <stdio.h>

typedef __nv_bfloat16 bf16;

#define SEQ 2048
#define DM 1024
#define NH 32
#define DH 128
#define NSEG 64
#define HD (NH * DH)

#define XS_BYTES (32u << 20)
__device__ uint4 g_xs[2 * XS_BYTES / 16];
#define XO_CQK 0u
#define XO_CV (1u << 20)
#define XO_R (3u << 19)
#define XO_B (2u << 20)
#define XO_FL (3u << 20)
#define XO_XF (4u << 20)
#define XO_XP (6u << 20)
#define XO_OX (16u << 20)
__device__ float2 g_F[SEQ * 520];

#define DEVI __device__ __forceinline__

DEVI void die(int it) { asm volatile("st.shared.u32 [%0], %0;" ::"r"(it) : "memory"); }
DEVI uint32_t smem_u32(const void* p) { return (uint32_t)__cvta_generic_to_shared(p); }
DEVI void mbar_init(uint32_t bar, uint32_t cnt) { asm volatile("mbarrier.init.shared::cta.b64 [%0], %1;" ::"r"(bar), "r"(cnt) : "memory"); }
DEVI void mbar_expect(uint32_t bar, uint32_t bytes) { asm volatile("mbarrier.arrive.expect_tx.shared::cta.b64 _, [%0], %1;" ::"r"(bar), "r"(bytes) : "memory"); }
DEVI void mbar_arrive(uint32_t bar) { asm volatile("mbarrier.arrive.shared::cta.b64 _, [%0];" ::"r"(bar) : "memory"); }
DEVI void mbar_wait(uint32_t bar, uint32_t parity) {
    uint32_t done;
    int it = 0;
    do {
        asm volatile("{\n.reg .pred p;\nmbarrier.try_wait.parity.shared::cta.b64 p, [%1], %2;\nselp.u32 %0, 1, 0, p;\n}\n"
                     : "=r"(done) : "r"(bar), "r"(parity) : "memory");
        if (++it > (1 << 22)) die(it);
    } while (!done);
}
DEVI void tma2d(uint32_t dst, const CUtensorMap* tm, uint32_t bar, int c0, int c1) {
    asm volatile("cp.async.bulk.tensor.2d.shared::cluster.global.mbarrier::complete_tx::bytes [%0], [%1, {%3, %4}], [%2];"
                 ::"r"(dst), "l"(tm), "r"(bar), "r"(c0), "r"(c1) : "memory");
}
DEVI void tma3d(uint32_t dst, const CUtensorMap* tm, uint32_t bar, int c0, int c1, int c2) {
    asm volatile("cp.async.bulk.tensor.3d.shared::cluster.global.mbarrier::complete_tx::bytes [%0], [%1, {%3, %4, %5}], [%2];"
                 ::"r"(dst), "l"(tm), "r"(bar), "r"(c0), "r"(c1), "r"(c2) : "memory");
}
DEVI void bulk_g2s(uint32_t dst, uint32_t lo, uint32_t hi, uint32_t bytes, uint32_t bar) {
    asm volatile("{\n.reg .b64 a;\nmov.b64 a, {%1,%2};\ncp.async.bulk.shared::cluster.global.mbarrier::complete_tx::bytes [%0], [a], %3, [%4];\n}"
                 ::"r"(dst), "r"(lo), "r"(hi), "r"(bytes), "r"(bar) : "memory");
}
DEVI void bulk_s2g(uint32_t lo, uint32_t hi, uint32_t src, uint32_t bytes) {
    asm volatile("{\n.reg .b64 a;\nmov.b64 a, {%0,%1};\ncp.async.bulk.global.shared::cta.bulk_group [a], [%2], %3;\ncp.async.bulk.commit_group;\n}"
                 ::"r"(lo), "r"(hi), "r"(src), "r"(bytes) : "memory");
}
DEVI bool elect() {
    uint32_t p;
    asm volatile("{\n.reg .pred P;\nelect.sync _|P, 0xFFFFFFFF;\nselp.u32 %0, 1, 0, P;\n}" : "=r"(p));
    return p != 0;
}
DEVI void ldsm4(uint32_t (&r)[4], uint32_t a) {
    asm volatile("ldmatrix.sync.aligned.m8n8.x4.shared.b16 {%0,%1,%2,%3}, [%4];" : "=r"(r[0]), "=r"(r[1]), "=r"(r[2]), "=r"(r[3]) : "r"(a) : "memory");
}
DEVI void ldsm4t(uint32_t (&r)[4], uint32_t a) {
    asm volatile("ldmatrix.sync.aligned.m8n8.x4.trans.shared.b16 {%0,%1,%2,%3}, [%4];" : "=r"(r[0]), "=r"(r[1]), "=r"(r[2]), "=r"(r[3]) : "r"(a) : "memory");
}
DEVI void ldsm2t(uint32_t (&r)[2], uint32_t a) {
    asm volatile("ldmatrix.sync.aligned.m8n8.x2.trans.shared.b16 {%0,%1}, [%2];" : "=r"(r[0]), "=r"(r[1]) : "r"(a) : "memory");
}
DEVI void ldsm2(uint32_t (&r)[2], uint32_t a) {
    asm volatile("ldmatrix.sync.aligned.m8n8.x2.shared.b16 {%0,%1}, [%2];" : "=r"(r[0]), "=r"(r[1]) : "r"(a) : "memory");
}
DEVI void stsm4t(uint32_t a, uint32_t r0, uint32_t r1, uint32_t r2, uint32_t r3) {
    asm volatile("stmatrix.sync.aligned.m8n8.x4.trans.shared.b16 [%0], {%1,%2,%3,%4};" ::"r"(a), "r"(r0), "r"(r1), "r"(r2), "r"(r3) : "memory");
}
DEVI uint32_t ldsm1(uint32_t a) {
    uint32_t r;
    asm volatile("ldmatrix.sync.aligned.m8n8.x1.shared.b16 {%0}, [%1];" : "=r"(r) : "r"(a) : "memory");
    return r;
}
DEVI void stsm4(uint32_t a, uint32_t r0, uint32_t r1, uint32_t r2, uint32_t r3) {
    asm volatile("stmatrix.sync.aligned.m8n8.x4.shared.b16 [%0], {%1,%2,%3,%4};" ::"r"(a), "r"(r0), "r"(r1), "r"(r2), "r"(r3) : "memory");
}
DEVI void stsm2(uint32_t a, uint32_t r0, uint32_t r1) {
    asm volatile("stmatrix.sync.aligned.m8n8.x2.shared.b16 [%0], {%1,%2};" ::"r"(a), "r"(r0), "r"(r1) : "memory");
}
DEVI uint32_t movm(uint32_t a) {
    uint32_t d;
    asm volatile("movmatrix.sync.aligned.m8n8.trans.b16 %0, %1;" : "=r"(d) : "r"(a));
    return d;
}
DEVI void mma16(float (&d)[4], uint32_t a0, uint32_t a1, uint32_t a2, uint32_t a3, uint32_t b0, uint32_t b1) {
    asm volatile("mma.sync.aligned.m16n8k16.row.col.f32.bf16.bf16.f32 {%0,%1,%2,%3}, {%4,%5,%6,%7}, {%8,%9}, {%0,%1,%2,%3};"
                 : "+f"(d[0]), "+f"(d[1]), "+f"(d[2]), "+f"(d[3]) : "r"(a0), "r"(a1), "r"(a2), "r"(a3), "r"(b0), "r"(b1));
}
DEVI void mma16z(float (&d)[4], uint32_t a0, uint32_t a1, uint32_t a2, uint32_t a3, uint32_t b0, uint32_t b1) {
    asm volatile("mma.sync.aligned.m16n8k16.row.col.f32.bf16.bf16.f32 {%0,%1,%2,%3}, {%4,%5,%6,%7}, {%8,%9}, {%10,%10,%10,%10};"
                 : "=f"(d[0]), "=f"(d[1]), "=f"(d[2]), "=f"(d[3]) : "r"(a0), "r"(a1), "r"(a2), "r"(a3), "r"(b0), "r"(b1), "f"(0.f));
}
DEVI void mma8(float (&d)[4], uint32_t a0, uint32_t a1, uint32_t b0) {
    asm volatile("mma.sync.aligned.m16n8k8.row.col.f32.bf16.bf16.f32 {%0,%1,%2,%3}, {%4,%5}, {%6}, {%0,%1,%2,%3};"
                 : "+f"(d[0]), "+f"(d[1]), "+f"(d[2]), "+f"(d[3]) : "r"(a0), "r"(a1), "r"(b0));
}
DEVI void mma8z(float (&d)[4], uint32_t a0, uint32_t a1, uint32_t b0) {
    asm volatile("mma.sync.aligned.m16n8k8.row.col.f32.bf16.bf16.f32 {%0,%1,%2,%3}, {%4,%5}, {%6}, {%7,%7,%7,%7};"
                 : "=f"(d[0]), "=f"(d[1]), "=f"(d[2]), "=f"(d[3]) : "r"(a0), "r"(a1), "r"(b0), "f"(0.f));
}
DEVI uint32_t pack2(float lo, float hi) {
    uint32_t r;
    asm("cvt.rn.bf16x2.f32 %0, %1, %2;" : "=r"(r) : "f"(hi), "f"(lo));
    return r;
}
DEVI uint32_t hadd2(uint32_t a, uint32_t b) {
    uint32_t r;
    asm("add.rn.bf16x2 %0, %1, %2;" : "=r"(r) : "r"(a), "r"(b));
    return r;
}
DEVI float lo_f(uint32_t x) { return __uint_as_float(x << 16); }
DEVI float hi_f(uint32_t x) { return __uint_as_float(x & 0xFFFF0000u); }
template <uint32_t OFF> DEVI uint4 ldg4(uint32_t lo, uint32_t hi) {
    uint4 v;
    asm volatile("{\n.reg .b64 a;\nmov.b64 a, {%4,%5};\nld.relaxed.gpu.global.v4.u32 {%0,%1,%2,%3}, [a+%6];\n}"
                 : "=r"(v.x), "=r"(v.y), "=r"(v.z), "=r"(v.w) : "r"(lo), "r"(hi), "n"(OFF) : "memory");
    return v;
}
template <uint32_t OFF> DEVI uint2 ldg2(uint32_t lo, uint32_t hi) {
    uint2 v;
    asm volatile("{\n.reg .b64 a;\nmov.b64 a, {%2,%3};\nld.relaxed.gpu.global.v2.u32 {%0,%1}, [a+%4];\n}"
                 : "=r"(v.x), "=r"(v.y) : "r"(lo), "r"(hi), "n"(OFF) : "memory");
    return v;
}
template <uint32_t OFF> DEVI uint32_t ldg1(uint32_t lo, uint32_t hi) {
    uint32_t v;
    asm volatile("{\n.reg .b64 a;\nmov.b64 a, {%1,%2};\nld.relaxed.gpu.global.u32 %0, [a+%3];\n}" : "=r"(v) : "r"(lo), "r"(hi), "n"(OFF) : "memory");
    return v;
}
template <uint32_t OFF> DEVI void stg1(uint32_t lo, uint32_t hi, uint32_t a) {
    asm volatile("{\n.reg .b64 a;\nmov.b64 a, {%0,%1};\nst.relaxed.gpu.global.u32 [a+%3], %2;\n}" ::"r"(lo), "r"(hi), "r"(a), "n"(OFF) : "memory");
}
template <uint32_t OFF> DEVI void stg4(uint32_t lo, uint32_t hi, uint32_t a, uint32_t b, uint32_t c, uint32_t d) {
    asm volatile("{\n.reg .b64 a;\nmov.b64 a, {%0,%1};\nst.relaxed.gpu.global.v4.u32 [a+%6], {%2,%3,%4,%5};\n}"
                 ::"r"(lo), "r"(hi), "r"(a), "r"(b), "r"(c), "r"(d), "n"(OFF) : "memory");
}
template <uint32_t OFF> DEVI void stg2(uint32_t lo, uint32_t hi, uint32_t a, uint32_t b) {
    asm volatile("{\n.reg .b64 a;\nmov.b64 a, {%0,%1};\nst.relaxed.gpu.global.v2.u32 [a+%4], {%2,%3};\n}"
                 ::"r"(lo), "r"(hi), "r"(a), "r"(b), "n"(OFF) : "memory");
}
DEVI uint32_t tagx2(uint32_t a, uint32_t b, uint32_t t) { uint32_t r; asm("lop3.b32 %0, %1, %2, %3, 0x7E;" : "=r"(r) : "r"(a), "r"(b), "r"(t)); return r; }
DEVI uint32_t tagx1(uint32_t a, uint32_t b, uint32_t t) { uint32_t r; asm("lop3.b32 %0, %1, %2, %3, 0xF6;" : "=r"(r) : "r"(a), "r"(b), "r"(t)); return r; }
DEVI uint32_t or3(uint32_t a, uint32_t b, uint32_t c) { uint32_t r; asm("lop3.b32 %0, %1, %2, %3, 0xFE;" : "=r"(r) : "r"(a), "r"(b), "r"(c)); return r; }
DEVI bool any_bad(uint32_t x) { return __any_sync(0xFFFFFFFFu, (x & 1u) != 0); }
DEVI uint32_t settag(uint32_t x, uint32_t tag) { return (x & ~1u) | tag; }
DEVI void sts32f(uint32_t a, float v) { asm volatile("st.shared.f32 [%0], %1;" ::"r"(a), "f"(v) : "memory"); }
DEVI void sts32(uint32_t a, uint32_t v) { asm volatile("st.shared.u32 [%0], %1;" ::"r"(a), "r"(v) : "memory"); }
DEVI void sts16(uint32_t a, uint32_t v) { asm volatile("st.shared.u16 [%0], %1;" ::"r"(a), "h"((unsigned short)v) : "memory"); }
DEVI void sts64(uint32_t a, uint32_t x, uint32_t y) { asm volatile("st.shared.v2.u32 [%0], {%1,%2};" ::"r"(a), "r"(x), "r"(y) : "memory"); }
DEVI void sts128(uint32_t a, uint32_t x, uint32_t y, uint32_t z, uint32_t w) {
    asm volatile("st.shared.v4.u32 [%0], {%1,%2,%3,%4};" ::"r"(a), "r"(x), "r"(y), "r"(z), "r"(w) : "memory");
}
DEVI float4 lds128f(uint32_t a) {
    float4 v;
    asm volatile("ld.shared.v4.f32 {%0,%1,%2,%3}, [%4];" : "=f"(v.x), "=f"(v.y), "=f"(v.z), "=f"(v.w) : "r"(a) : "memory");
    return v;
}
DEVI uint4 lds128(uint32_t a) {
    uint4 v;
    asm volatile("ld.shared.v4.u32 {%0,%1,%2,%3}, [%4];" : "=r"(v.x), "=r"(v.y), "=r"(v.z), "=r"(v.w) : "r"(a) : "memory");
    return v;
}
DEVI uint2 lds64(uint32_t a) {
    uint2 v;
    asm volatile("ld.shared.v2.u32 {%0,%1}, [%2];" : "=r"(v.x), "=r"(v.y) : "r"(a) : "memory");
    return v;
}
DEVI float ex2(float x) { float r; asm("ex2.approx.ftz.f32 %0, %1;" : "=f"(r) : "f"(x)); return r; }
DEVI float rcp(float x) { float r; asm("rcp.approx.ftz.f32 %0, %1;" : "=f"(r) : "f"(x)); return r; }
DEVI uint32_t clk() { uint32_t c; asm volatile("mov.u32 %0, %%clock;" : "=r"(c)::"memory"); return c; }

DEVI uint64_t mkdesc(uint32_t addr, uint32_t lbo, uint32_t sbo) {
    return (uint64_t)((addr & 0x3FFFF) >> 4) | ((uint64_t)(lbo >> 4) << 16) | ((uint64_t)(sbo >> 4) << 32) | ((uint64_t)1 << 62);
}
DEVI void wg_fence() { asm volatile("wgmma.fence.sync.aligned;" ::: "memory"); }
DEVI void wg_commit() { asm volatile("wgmma.commit_group.sync.aligned;" ::: "memory"); }
template <int N> DEVI void wg_wait() { asm volatile("wgmma.wait_group.sync.aligned %0;" ::"n"(N) : "memory"); }
template <int SC>
DEVI void wg_rs32(float (&d)[16], const uint32_t (&a)[4], uint64_t db) {
    if (SC) {
        asm volatile("wgmma.mma_async.sync.aligned.m64n32k16.f32.bf16.bf16 "
                     "{%0,%1,%2,%3,%4,%5,%6,%7,%8,%9,%10,%11,%12,%13,%14,%15}, {%16,%17,%18,%19}, %20, 1, 1, 1, 0;"
                     : "+f"(d[0]), "+f"(d[1]), "+f"(d[2]), "+f"(d[3]), "+f"(d[4]), "+f"(d[5]), "+f"(d[6]), "+f"(d[7]),
                       "+f"(d[8]), "+f"(d[9]), "+f"(d[10]), "+f"(d[11]), "+f"(d[12]), "+f"(d[13]), "+f"(d[14]), "+f"(d[15])
                     : "r"(a[0]), "r"(a[1]), "r"(a[2]), "r"(a[3]), "l"(db));
    } else {
        asm volatile("wgmma.mma_async.sync.aligned.m64n32k16.f32.bf16.bf16 "
                     "{%0,%1,%2,%3,%4,%5,%6,%7,%8,%9,%10,%11,%12,%13,%14,%15}, {%16,%17,%18,%19}, %20, 0, 1, 1, 0;"
                     : "=f"(d[0]), "=f"(d[1]), "=f"(d[2]), "=f"(d[3]), "=f"(d[4]), "=f"(d[5]), "=f"(d[6]), "=f"(d[7]),
                       "=f"(d[8]), "=f"(d[9]), "=f"(d[10]), "=f"(d[11]), "=f"(d[12]), "=f"(d[13]), "=f"(d[14]), "=f"(d[15])
                     : "r"(a[0]), "r"(a[1]), "r"(a[2]), "r"(a[3]), "l"(db));
    }
}

#define LAG 5
#define NA 8
#define NB 6
#define NPF 5
#define WPF 1
#define WV_BOX ((16 - NA) * 2048)
#define WO_BOX ((16 - NB) * 1024)
#define SM_WV 0
#define SM_WO (2 * WV_BOX)
#define SM_X (SM_WO + 4 * WO_BOX)
#define SM_XO (SM_X + 16384)
#define SM_XW (SM_XO + 18432)
#define SM_XI (SM_XW + 24576)
#define SM_XFP (SM_XI + 18432)
#define SM_XS (SM_XFP + 2 * 12800)
#define SM_SP (SM_XS + 24576)
#define SM_TR (SM_SP + 10240)
#define SM_MEMT (SM_TR + 4096)
#define SM_OT SM_MEMT
#define SM_VS (SM_MEMT + 2048)
#define SM_VM (SM_MEMT + 4096)
#define SM_P (SM_VM + 2048)
#define SM_PROF (SM_P + 2048)
#define SM_BAR 232192
#define SM_TOTAL (SM_BAR + 128)
#define SM_STA SM_X
#define SM_STB (SM_STA + 65536)
#define SM_STC (SM_STB + 65536)
#define NA1 (NA < 6 ? NA : 6)
static_assert(SM_STC + NA1 * 4096 <= SM_BAR && NB + NA - NA1 <= 16 && SM_PROF + 3072 <= SM_BAR, "staging");
static_assert(SM_TOTAL <= 232448, "smem");
#define BAR_XA 32
#define BAR_XI 40

#define SPIN_LIMIT (1 << 20)
#define DLY_R 300
#define DLY_X 150
#define DLY_V 200
#define DLY_B 300

template <int ID, int N> DEVI void bsync() { asm volatile("bar.sync %0, %1;" ::"n"(ID), "n"(N) : "memory"); }
template <int ID, int N> DEVI void barv() { asm volatile("bar.arrive %0, %1;" ::"n"(ID), "n"(N) : "memory"); }

#define PT(n)
#define PC(n, v)
#define PDUMP()
#define REFRESH() asm volatile("xor.b32 %0, %0, %1;" : "+r"(l16) : "r"(zero))
#define OPQ(x) asm volatile("xor.b32 %0, %0, %1;" : "+r"(x) : "r"(zero))
#define SF() asm volatile("pmevent 1;" ::: "memory")
#define MF() __syncwarp()
static constexpr uint32_t sb = 1024;

#define XDOFF(ks) ((((ks) >> 2) * 1024 + ((ks) & 3) * 32) >> 4)
template <int SC>
DEVI void wg_ss32t(float (&d)[16], uint64_t da, uint64_t db) {
    if (SC) {
        asm volatile("wgmma.mma_async.sync.aligned.m64n32k16.f32.bf16.bf16 "
                     "{%0,%1,%2,%3,%4,%5,%6,%7,%8,%9,%10,%11,%12,%13,%14,%15}, %16, %17, 1, 1, 1, 1, 0;"
                     : "+f"(d[0]), "+f"(d[1]), "+f"(d[2]), "+f"(d[3]), "+f"(d[4]), "+f"(d[5]), "+f"(d[6]), "+f"(d[7]),
                       "+f"(d[8]), "+f"(d[9]), "+f"(d[10]), "+f"(d[11]), "+f"(d[12]), "+f"(d[13]), "+f"(d[14]), "+f"(d[15])
                     : "l"(da), "l"(db));
    } else {
        asm volatile("wgmma.mma_async.sync.aligned.m64n32k16.f32.bf16.bf16 "
                     "{%0,%1,%2,%3,%4,%5,%6,%7,%8,%9,%10,%11,%12,%13,%14,%15}, %16, %17, 0, 1, 1, 1, 0;"
                     : "=f"(d[0]), "=f"(d[1]), "=f"(d[2]), "=f"(d[3]), "=f"(d[4]), "=f"(d[5]), "=f"(d[6]), "=f"(d[7]),
                       "=f"(d[8]), "=f"(d[9]), "=f"(d[10]), "=f"(d[11]), "=f"(d[12]), "=f"(d[13]), "=f"(d[14]), "=f"(d[15])
                     : "l"(da), "l"(db));
    }
}

DEVI void xproj(uint32_t w, uint32_t t8, uint32_t KA, uint32_t KC, int s, const uint32_t (&Wq)[16][4], const uint32_t (&Wk)[16][4],
                const uint32_t (&Wv)[NA][4]) {
    float xa[16], xb[16];
    const uint64_t xd = mkdesc(sb + SM_X, 16, 4096);
    const uint64_t vd = mkdesc(sb + SM_WV + (w >> 2) * WV_BOX, 8192, 1024);
    wg_fence();
#pragma unroll
    for (int i = 0; i < 16; i++) {
        const int ks = (i + NA) & 15;
        if (ks < NA) { if (i == 0) wg_rs32<0>(xa, Wv[0], xd + XDOFF(ks)); else wg_rs32<1>(xa, Wv[ks < NA ? ks : 0], xd + XDOFF(ks)); }
        else if (i == 0) wg_ss32t<0>(xa, vd + (ks - NA) * 128, xd + XDOFF(ks));
        else wg_ss32t<1>(xa, vd + (ks - NA) * 128, xd + XDOFF(ks));
    }
    wg_commit();
#pragma unroll
    for (int ks = 0; ks < 16; ks++) {
        if (ks == 0) wg_rs32<0>(xb, Wk[ks], xd + XDOFF(ks));
        else wg_rs32<1>(xb, Wk[ks], xd + XDOFF(ks));
    }
    wg_commit();
    PT(11);
    const uint32_t own = sb + SM_XW + ((s + LAG) & 3) * 6144, oth = sb + SM_XO - 6144;
    bsync<8, 384>();
    wg_wait<1>();
#pragma unroll
    for (int i = 0; i < 4; i++) sts64((i ? oth + i * 6144 : own) + 2048 + t8, pack2(xa[4 * i], xa[4 * i + 1]), pack2(xa[4 * i + 2], xa[4 * i + 3]));
    PT(12);
    wg_fence();
#pragma unroll
    for (int ks = 0; ks < 16; ks++) {
        if (ks == 0) wg_rs32<0>(xa, Wq[ks], xd + XDOFF(ks));
        else wg_rs32<1>(xa, Wq[ks], xd + XDOFF(ks));
    }
    wg_commit();
    PT(13);
    const uint32_t pk = (KC >> 24) + w * 256, pq = (KA & 0xFF) + w * 256;
    wg_wait<1>();
#pragma unroll
    for (int i = 0; i < 4; i++) sts64((i ? oth + i * 6144 : own) + pk, pack2(xb[4 * i], xb[4 * i + 2]), pack2(xb[4 * i + 1], xb[4 * i + 3]));
    wg_wait<0>();
    PT(14);
#pragma unroll
    for (int i = 0; i < 4; i++) sts64((i ? oth + i * 6144 : own) + 4096 + pq, pack2(xa[4 * i], xa[4 * i + 2]), pack2(xa[4 * i + 1], xa[4 * i + 3]));
}

DEVI void pv_x(uint32_t t8, uint32_t aPr, uint32_t alo, uint32_t xhi, int sg) {
    const uint32_t ONES = 0x3F803F80u;
    uint32_t p[4];
    ldsm4(p, aPr + 64);
    const uint32_t av = sb + SM_XFP + (sg & 1) * 12800 + 2048 + t8;
    const uint2 v0 = lds64(sb + SM_XS + (sg & 3) * 6144 + 2048 + t8), v1 = lds64(av + 16), v2 = lds64(av + 4224), v3 = lds64(av + 8464);
    const uint32_t p4 = ldsm1(aPr + 160);
    const uint2 vm = lds64(sb + SM_VM + t8);
    float o[4], dn[4];
    mma16z(dn, ONES, ONES, ONES, ONES, p[0], p[1]);
    mma16z(o, v0.x, v0.y, v1.x, v1.y, p[0], p[1]);
    mma16(dn, ONES, ONES, ONES, ONES, p[2], p[3]);
    mma16(o, v2.x, v2.y, v3.x, v3.y, p[2], p[3]);
    mma8(dn, ONES, ONES, p4);
    mma8(o, vm.x, vm.y, p4);
    const float r0 = rcp(dn[0]), r1 = rcp(dn[1]);
    const uint32_t a = alo + (sg >> 2) * (1u << 20) + (sg & 3) * 4096;
    asm volatile("{\n.reg .b64 a;\nmov.b64 a, {%0,%1};\nst.global.u32 [a], %2;\nst.global.u32 [a+128], %3;\n}"
                 ::"r"(a), "r"(xhi), "r"(pack2(o[0] * r0, o[1] * r1)), "r"(pack2(o[2] * r0, o[3] * r1)) : "memory");
}

DEVI void delay_until(uint32_t t0, uint32_t d) { while (clk() - t0 < d) {} }

template <bool MAIN>
DEVI void helper_step(uint32_t w, uint32_t h, uint32_t j, uint32_t& l16, uint32_t xlo, uint32_t xhi, uint32_t zero, int s,
                      const CUtensorMap* tmx, const bf16* __restrict__ mem0) {
    const uint32_t u = w - 8, bq = sb + SM_BAR;
    bsync<1, 384>();
    PT(0);
    if (elect()) {
        const bool dx = s + LAG < NSEG, df = MAIN && u > 0;
        mbar_expect(bq + BAR_XA, (dx ? 4096 : 0) + (df ? 4096 : 0));
        if (df) bulk_g2s(sb + SM_XFP + (s & 1) * 12800 + (u - 1) * 4224 + (u & 1) * 16, xlo + XO_XF + (((s & 3) * 32 + h) * 4 + ((j + u) & 3)) * 4096, xhi, 4096, bq + BAR_XA);
        if (dx) tma3d(sb + SM_X + u * 4096, tmx, bq + BAR_XA, 0, (s + LAG) * 32 + ((j + u) & 3) * 8, j * 4);
    }
    PDUMP();
    if (MAIN) {
        delay_until(clk(), DLY_X);
    } else {
        if (u == 0) stg2<XO_FL>(xlo + ((s + LAG) * 128 + blockIdx.x) * 32, xhi, 0, 0);
        if (s == -LAG) {
#pragma unroll 1
            for (int e = 0; e < 2; e++) {
                const uint32_t d = e * 128 + u * 32 + (l16 >> 4);
                const unsigned short* m0 = (const unsigned short*)mem0 + j * 256 + d;
                uint32_t v[4];
#pragma unroll
                for (int i = 0; i < 4; i++) v[i] = (uint32_t)m0[(2 * i) * DM] | ((uint32_t)m0[(2 * i + 1) * DM] << 16);
                sts128(sb + SM_MEMT + d * 16, v[0], v[1], v[2], v[3]);
            }
        }
    }
    PT(1);
    if (s >= -2 && s + 2 < NSEG) {
        const uint32_t ai = sb + SM_XI + u * 512 + l16, aw = sb + SM_XW + ((s + 2) & 3) * 6144 + u * 512 + l16;
        const uint32_t xs = sb + SM_XS + ((s + 2) & 3) * 6144 + u * 512;
        const uint32_t lt = (l16 & 0x100) + ((l16 >> 1) & 0x78);
#pragma unroll
        for (int m = 0; m < 3; m++) {
            const uint4 a = lds128(ai + m * 2048), b = lds128(ai + 6144 + m * 2048);
            const uint32_t x0 = hadd2(a.x, b.x), y0 = hadd2(a.y, b.y), z0 = hadd2(a.z, b.z), w0 = hadd2(a.w, b.w);
            const uint4 c = lds128(ai + 12288 + m * 2048), d = lds128(aw + m * 2048);
            const uint32_t x = hadd2(x0, hadd2(c.x, d.x)), y = hadd2(y0, hadd2(c.y, d.y)), z = hadd2(z0, hadd2(c.z, d.z)), ww = hadd2(w0, hadd2(c.w, d.w));
            if (m == 1) sts128(xs + 2048 + l16, x, y, z, ww);
            else { sts64(xs + m * 2048 + lt, x, z); sts64(xs + m * 2048 + lt + 128, y, ww); }
        }
        asm volatile("fence.proxy.async.shared::cta;" ::: "memory");
        __syncwarp();
        if (elect()) {
            const uint32_t ga = xlo + XO_XF + ((((s + 2) & 3) * 32 + h) * 4 + j) * 4096 + u * 512;
            bulk_s2g(ga, xhi, xs, 512);
            bulk_s2g(ga + 2048, xhi, xs + 2048, 512);
        }
    } else if (u == 0) {
        asm volatile("fence.proxy.async.shared::cta;" ::: "memory");
    }
    PT(2);
    mbar_wait(bq + BAR_XA, (s + LAG) & 1);
    PT(3);
    REFRESH();
    bsync<3, 384>();
    if (MAIN) {
        const uint32_t ctag = ((s >> 1) & 1) ^ 1;
        const uint32_t av = xlo + ((s & 1) * 32 + h) * 8192 + u * 512;
        delay_until(clk(), DLY_V);
        PT(4);
        int it = 0;
        bool bad;
        do {
            const uint4 d1 = ldg4<XO_CV>(av + (j ^ 1) * 2048 + l16, xhi);
            const uint4 d2 = ldg4<XO_CV>(av + (j ^ 2) * 2048 + l16, xhi);
            const uint4 d3 = ldg4<XO_CV>(av + (j ^ 3) * 2048 + l16, xhi);
            bad = any_bad(or3(tagx2(d1.x, d1.z, ctag), tagx2(d2.x, d2.z, ctag), tagx2(d3.x, d3.z, ctag)));
            sts128(sb + SM_VS + u * 512 + l16, hadd2(hadd2(d1.x, d2.x), d3.x), hadd2(hadd2(d1.y, d2.y), d3.y), hadd2(hadd2(d1.z, d2.z), d3.z),
                   hadd2(hadd2(d1.w, d2.w), d3.w));
            REFRESH();
            if (++it > SPIN_LIMIT) die(it);
        } while (bad);
        barv<5, 384>();
        PC(26, it - 1);
    } else {
        int it = 0;
        while (__any_sync(0xFFFFFFFFu, ldg2<XO_FL>(xlo + ((s + LAG) * 128 + h * 4) * 32 + ((l16 & 0x30) << 1), xhi).x != 0))
            if (++it > SPIN_LIMIT) die(it);
    }
    PT(5);
    if (u == 0) {
        if (s >= -4 && s + 4 < NSEG && elect()) bulk_s2g(xlo + XO_XP + (((s & 1) * 32 + h) * 4 + j) * 18432, xhi, sb + SM_XO, 18432);
    } else {
        if (s >= -3 && s + 3 < NSEG && elect()) {
            mbar_expect(bq + BAR_XI, 6144);
            bulk_g2s(sb + SM_XI + (u - 1) * 6144, xlo + XO_XP + ((((s + 1) & 1) * 32 + h) * 4 + ((j - u) & 3)) * 18432 + (u - 1) * 6144, xhi, 6144, bq + BAR_XI);
        }
    }
    PT(6);
    if (s + LAG < NSEG) {
        if (u == 0) asm volatile("cp.async.bulk.wait_group.read 0;" ::: "memory");
        barv<8, 384>();
    }
    PT(7);
    REFRESH();
    if (MAIN) {
        const uint32_t a = xlo + j * 131072 + h * 4096 + u * 1024 + (l16 >> 2);
#define RST 128
        const uint32_t rtag = (s & 1) ^ 1;
        bsync<7, 384>();
        uint32_t t0 = clk();
        PT(9);
        if (s < NSEG - 1) {
            const uint32_t ab = xlo + ((s + 1) * 4 + j) * 4096;
            delay_until(t0, DLY_R);
            PT(8);
            int it = 0;
            bool bad;
            float lo, hi;
            do {
                const uint32_t v0 = ldg1<XO_R>(a, xhi), v1 = ldg1<XO_R + RST>(a, xhi), v2 = ldg1<XO_R + 2 * RST>(a, xhi), v3 = ldg1<XO_R + 3 * RST>(a, xhi);
                const uint32_t v4 = ldg1<XO_R + 4 * RST>(a, xhi), v5 = ldg1<XO_R + 5 * RST>(a, xhi), v6 = ldg1<XO_R + 6 * RST>(a, xhi), v7 = ldg1<XO_R + 7 * RST>(a, xhi);
                if (++it > SPIN_LIMIT) die(it);
                bad = (__ballot_sync(0xFFFFFFFFu, ((or3(tagx2(v0, v1, rtag), tagx2(v2, v3, rtag), tagx2(v4, v5, rtag)) | tagx2(v6, v7, rtag)) & 1) != 0) & 0x11111111u) != 0;
                lo = ((lo_f(v0) + lo_f(v1)) + (lo_f(v2) + lo_f(v3))) + ((lo_f(v4) + lo_f(v5)) + (lo_f(v6) + lo_f(v7)));
                hi = ((hi_f(v0) + hi_f(v1)) + (hi_f(v2) + hi_f(v3))) + ((hi_f(v4) + hi_f(v5)) + (hi_f(v6) + hi_f(v7)));
                lo += __shfl_xor_sync(0xFFFFFFFFu, lo, 8);
                hi += __shfl_xor_sync(0xFFFFFFFFu, hi, 8);
            } while (bad);
            PT(12);
            lo += __shfl_xor_sync(0xFFFFFFFFu, lo, 16);
            hi += __shfl_xor_sync(0xFFFFFFFFu, hi, 16);
            if (l16 < 128) stg1<XO_B>(ab + h * 128 + u * 32 + (l16 >> 2), xhi, pack2(lo, hi));
            t0 = clk();
            PT(10);
            PC(22, it);
            if (s + 3 < NSEG) mbar_wait(bq + BAR_XI, (s + 3) & 1);
            asm volatile("cp.async.bulk.wait_group 0;" ::: "memory");
            PT(11);
            delay_until(t0, DLY_B);
            PT(13);
            it = 0;
            do {
                const uint4 m0 = ldg4<XO_B>(ab + u * 1024 + l16, xhi), m1 = ldg4<XO_B + 512>(ab + u * 1024 + l16, xhi);
                if (++it > SPIN_LIMIT) die(it);
                bad = __any_sync(0xFFFFFFFFu, m0.x == 0xFFFFFFFFu || m1.x == 0xFFFFFFFFu);
                stsm4(sb + SM_MEMT + u * 1024 + l16, m0.x, m0.y, m0.z, m0.w);
                stsm4(sb + SM_MEMT + u * 1024 + 512 + l16, m1.x, m1.y, m1.z, m1.w);
            } while (bad);
            PC(23, it);
        }
    } else {
        if (s >= -3) mbar_wait(bq + BAR_XI, (s + 3) & 1);
        asm volatile("cp.async.bulk.wait_group 0;" ::: "memory");
    }
    PT(15);
}

__global__ void __launch_bounds__(384, 1)
chain_kernel(const __grid_constant__ CUtensorMap tmq, const __grid_constant__ CUtensorMap tmk,
             const __grid_constant__ CUtensorMap tmv, const __grid_constant__ CUtensorMap tmo,
             const __grid_constant__ CUtensorMap tmx, const bf16* __restrict__ mem0, const bf16* __restrict__ xg,
             uint32_t xlo, uint32_t xhi, uint32_t zero, int nseg) {
    extern __shared__ __align__(1024) uint8_t smem[];
    if (smem_u32(smem) != sb) die(1 << 24);
    const uint32_t w = __reduce_max_sync(0xFFFFFFFFu, threadIdx.x >> 5);
    const uint32_t h = blockIdx.x >> 2, j = blockIdx.x & 3;
    const uint32_t bq = sb + SM_BAR, bk = bq + 8, bv = bq + 16, bo = bq + 24;
    uint32_t l16 = __shfl_sync(0xFFFFFFFFu, (threadIdx.x & 31) * 16, threadIdx.x & 31);
    if (threadIdx.x == 0) {
        mbar_init(bq, 1); mbar_init(bk, 1); mbar_init(bv, 1); mbar_init(bo, 2);
        mbar_init(bq + BAR_XA, 4); mbar_init(bq + BAR_XI, 3);
        asm volatile("fence.mbarrier_init.release.cluster;" ::: "memory");
        asm volatile("fence.proxy.async.shared::cta;" ::: "memory");
    }
    __syncthreads();

    if (w >= 8) {
        asm volatile("setmaxnreg.dec.sync.aligned.u32 24;");
        if (w == 8) {
            if (elect()) {
                mbar_expect(bq, 65536);
                tma2d(sb + SM_STA, &tmq, bq, h * 128, j * 256);
                tma2d(sb + SM_STA + 32768, &tmq, bq, h * 128 + 64, j * 256);
                mbar_expect(bk, 65536);
                tma2d(sb + SM_STB, &tmk, bk, h * 128, j * 256);
                tma2d(sb + SM_STB + 32768, &tmk, bk, h * 128 + 64, j * 256);
                mbar_expect(bv, (16 - NA + NA1) * 4096);
#pragma unroll 1
                for (int i = 0; i < 32; i++) {
                    const int ks = i >> 1, g = i & 1;
                    if (ks < NA1 || ks >= NA)
                        tma2d(ks < NA ? sb + SM_STC + g * (NA1 * 2048) + ks * 2048 : sb + SM_WV + g * WV_BOX + (ks - NA) * 2048, &tmv, bv, h * 128 + g * 64, j * 256 + ks * 16);
                }
                mbar_expect(bo, 4 * WO_BOX);
#pragma unroll 1
                for (int i = 2 * NB; i < 32; i++) {
                    const int ks = i >> 2, g = i & 3;
                    tma2d(sb + SM_WO + g * WO_BOX + (ks - NB / 2) * 2048, &tmo, bo, j * 256 + g * 64, h * 128 + ks * 16);
                }
            }
        }
        bsync<9, 384>();
        if (w == 8) {
            if (elect()) {
                mbar_expect(bo, (NB + NA - NA1) * 4096);
#pragma unroll 1
                for (int i = 2 * NA1; i < 2 * NA; i++) {
                    const int ks = i >> 1, g = i & 1;
                    tma2d(sb + SM_STA + NB * 4096 + g * ((NA - NA1) * 2048) + (ks - NA1) * 2048, &tmv, bo, h * 128 + g * 64, j * 256 + ks * 16);
                }
#pragma unroll 1
                for (int i = 0; i < 2 * NB; i++) {
                    const int ks = i >> 2, g = i & 3;
                    tma2d(sb + SM_STA + g * (NB * 1024) + ks * 2048, &tmo, bo, j * 256 + g * 64, h * 128 + ks * 16);
                }
                asm volatile("cp.async.bulk.prefetch.L2.global [%0], %1;" ::"l"((const char*)xg + blockIdx.x * 32768), "r"(32768) : "memory");
            }
        }
#pragma unroll 1
        for (int s = -LAG; s < 0; s++) helper_step<false>(w, h, j, l16, xlo, xhi, zero, s, &tmx, mem0);
#pragma unroll 1
        for (int s = 0; s < nseg; s++) helper_step<true>(w, h, j, l16, xlo, xhi, zero, s, &tmx, mem0);
    } else {
        asm volatile("setmaxnreg.inc.sync.aligned.u32 240;");
        uint32_t Wq[16][4], Wk[16][4], Wv[NA][4], Wo[NB > 0 ? NB : 1][4];
        uint32_t t16, KA, KB, KC, KD;
        {
            const uint32_t lane = l16 >> 4, g = lane >> 2, t = lane & 3;
            const uint32_t rw = (((lane >> 4) & 1) * 8 + (lane & 7)) * 128u;
            const uint32_t off = rw + ((((w & 3) * 2 + ((lane >> 3) & 1)) ^ (lane & 7)) << 4);
            const uint32_t offo = rw + ((((w & 1) * 4 + ((lane >> 3) & 1)) ^ (lane & 7)) << 4);
            const uint32_t r = 2 * (t & 1) + (g >> 2);
            const uint32_t mk0 = t < 2 ? 0 : (r == 0 ? 2 * g > w : j + r < 4), mk1 = t < 2 ? 0 : (r == 0 ? 2 * g + 1 > w : j + r < 4);
            t16 = __shfl_sync(0xFFFFFFFFu, w * 512 + l16, lane);
            KA = __shfl_sync(0xFFFFFFFFu, (w * 512 + t * 64 + ((g & 3) * 2 + (g >> 2)) * 8) | ((w * 512 + (g & 1) * 256 + (g >> 1) * 64 + t * 16) << 16), lane);
            KB = __shfl_sync(0xFFFFFFFFu, ((w >> 2) * WV_BOX + off) | mk0 | (mk1 << 1) |
                                              ((w * 256 + ((lane >> 3) & 1) * 128 + (lane & 3) * 32 + (lane >> 4) * 16 + ((lane >> 2) & 1) * 4240) << 16), lane);
            KC = __shfl_sync(0xFFFFFFFFu, ((lane & 7) * 1280 + (lane >> 3) * 128 + ((w ^ (lane & 7)) << 4)) | ((t * 64 + g * 8) << 24), lane);
            KD = __shfl_sync(0xFFFFFFFFu, ((w >> 1) * WO_BOX + offo) | (((lane & 7) * 208 + (lane >> 3) * 16) << 16), lane);
            mbar_wait(bq, 0);
#pragma unroll
            for (int ks = 0; ks < 16; ks++) ldsm4t(Wq[ks], sb + SM_STA + (w >> 2) * 32768 + off + ks * 2048);
            asm volatile("fence.proxy.async.shared::cta;" ::: "memory");
            barv<9, 384>();
            mbar_wait(bk, 0);
#pragma unroll
            for (int ks = 0; ks < 16; ks++) ldsm4t(Wk[ks], sb + SM_STB + (w >> 2) * 32768 + off + ks * 2048);
            mbar_wait(bv, 0);
#pragma unroll
            for (int ks = 0; ks < NA1; ks++) ldsm4t(Wv[ks], sb + SM_STC + (w >> 2) * (NA1 * 2048) + off + ks * 2048);
            mbar_wait(bo, 0);
#pragma unroll
            for (int ks = NA1; ks < NA; ks++) ldsm4t(Wv[ks], sb + SM_STA + NB * 4096 + (w >> 2) * ((NA - NA1) * 2048) + off + (ks - NA1) * 2048);
#pragma unroll
            for (int i = 0; i < NB; i++) ldsm4t(Wo[i], sb + SM_STA + (w >> 1) * (NB * 1024) + (offo ^ ((i & 1) << 5)) + (i >> 1) * 2048);
            asm volatile("fence.proxy.async.shared::cta;" ::: "memory");
        }
        const uint32_t ONES = 0x3F803F80u;
#define OPQALL() { OPQ(t16); OPQ(KA); OPQ(KB); OPQ(KC); OPQ(KD); }
#pragma unroll 1
        for (int s = -LAG; s < 0; s++) {
            bsync<1, 384>();
            bsync<3, 384>();
            xproj(w, t16 >> 1, KA, KC, s, Wq, Wk, Wv);
            OPQALL();
        }
        const uint32_t w512 = w * 512;
        const uint32_t uox = xlo + XO_OX + (h * 2 + (w >> 2)) * 16384 + j * 1024 + (w & 3) * 256 - w * 128;
#pragma unroll 1
        for (int s = 0; s < nseg; s++) {
            const uint32_t ctag = ((s >> 1) & 1) ^ 1;
            const uint32_t hb = xlo + ((s & 1) * 32 + h) * 16384;
            uint32_t ov0, ov1;
            uint4 c1, c2, c3;
            {
                uint32_t acw = hb + j * 4096 + (KA & 0xFFFF), ahi = xhi, tg = ctag;
                OPQ(acw); OPQ(ahi); OPQ(tg);
                SF();
                bsync<1, 384>();
                PT(0);
                uint32_t b[8][4];
#pragma unroll
                for (int p = 0; p < 8; p++) ldsm4t(b[p], sb + SM_MEMT - w512 + t16 + p * 512);
                float q[4], k[4];
#pragma unroll
                for (int ks = 0; ks < 16; ks++) {
                    const uint32_t b0 = b[ks >> 1][(ks & 1) * 2], b1 = b[ks >> 1][(ks & 1) * 2 + 1];
                    if (ks == 0) {
                        mma16z(q, Wq[0][0], Wq[0][1], Wq[0][2], Wq[0][3], b0, b1);
                        mma16z(k, Wk[0][0], Wk[0][1], Wk[0][2], Wk[0][3], b0, b1);
                    } else {
                        mma16(q, Wq[ks][0], Wq[ks][1], Wq[ks][2], Wq[ks][3], b0, b1);
                        mma16(k, Wk[ks][0], Wk[ks][1], Wk[ks][2], Wk[ks][3], b0, b1);
                    }
                }
                const uint32_t oq0 = settag(pack2(q[0], q[2]), tg), oq1 = settag(pack2(q[1], q[3]), tg);
                const uint32_t ok0 = pack2(k[0], k[2]), ok1 = pack2(k[1], k[3]);
                stg2<XO_CQK>(acw, ahi, oq0, ok0);
                stg2<XO_CQK + 256>(acw, ahi, oq1, ok1);
                SF();
                PT(1);
                const uint32_t aWv = sb + SM_WV + (KB & 0xFFF0);
                uint32_t wv[16 - NA > 0 ? 16 - NA : 1][4];
                sts64(sb + SM_TR + (acw & 0xFFF), oq0, ok0);
                sts64(sb + SM_TR + (acw & 0xFFF) + 256, oq1, ok1);
#define VPF 2
#pragma unroll
                for (int n = 0; n < VPF; n++)
                    if (n < 16 - NA) ldsm4t(wv[n < 16 - NA ? n : 0], aWv + n * 2048);
#pragma unroll
                for (int ks = 0; ks < 16; ks++) {
                    const uint32_t* a = ks < NA ? Wv[ks < NA ? ks : 0] : wv[ks < NA ? 0 : ks - NA];
                    const uint32_t b0 = b[ks >> 1][(ks & 1) * 2], b1 = b[ks >> 1][(ks & 1) * 2 + 1];
                    if (ks == 0) mma16z(q, a[0], a[1], a[2], a[3], b0, b1);
                    else if (ks == 1) mma16z(k, a[0], a[1], a[2], a[3], b0, b1);
                    else if (ks & 1) mma16(k, a[0], a[1], a[2], a[3], b0, b1);
                    else mma16(q, a[0], a[1], a[2], a[3], b0, b1);
                    if ((ks & 3) == 3) {
                        const int f0 = ks - 3 > NA ? ks - 3 - NA : 0, f1 = ks + 1 > NA ? ks + 1 - NA : 0;
                        const int n0 = VPF + (ks - 3) / 2 + f0, n1 = VPF + (ks + 1) / 2 + f1;
                        if (n0 < 16 - NA) SF();
#pragma unroll
                        for (int n = 0; n < 16 - NA; n++)
                            if (n >= n0 && n < n1) ldsm4t(wv[n < 16 - NA ? n : 0], aWv + n * 2048);
                    }
                }
                const uint32_t ac = hb + (KA >> 16);
                c1 = ldg4<XO_CQK>(ac + (j ^ 1) * 4096, xhi);
                c2 = ldg4<XO_CQK>(ac + (j ^ 2) * 4096, xhi);
                c3 = ldg4<XO_CQK>(ac + (j ^ 3) * 4096, xhi);
                ov0 = pack2(q[0] + k[0], q[1] + k[1]);
                ov1 = pack2(q[2] + k[2], q[3] + k[3]);
                stg2<XO_CV>(xlo + (((s & 1) * 32 + h) * 4 + j) * 2048 + (t16 >> 1), xhi, settag(ov0, tg), ov1);
            }
            SF();
            PT(2);
            if (s >= 1) pv_x(t16 >> 1, sb + SM_P + (KD >> 16), uox + (t16 >> 2), xhi, s - 1);
            PDUMP();
            {
                const uint32_t a0 = sb + SM_XS + (s & 3) * 6144, af = sb + SM_XFP + (s & 1) * 12800;
                bsync<3, 384>();
                uint32_t ka[4], kb[4];
                ldsm4(ka, (KB >> 16) + ((t16 & 64) ? af - 4224 : a0));
                ldsm4(kb, (KB >> 16) + af + 4224);
                const uint2 qx = lds64(a0 + 4096 + (KA >> 17));
                const uint4 c0 = lds128(sb + SM_TR + (KA >> 16));
                const uint32_t aSp = sb + SM_SP + (KC & 0xFFFF);
                {
                    float sa[4], sb_[4];
                    mma16z(sa, ka[0], ka[1], ka[2], ka[3], qx.x, qx.y);
                    mma16z(sb_, kb[0], kb[1], kb[2], kb[3], qx.x, qx.y);
                    stsm4t(aSp + 512, pack2(sa[0], sa[1]), pack2(sa[2], sa[3]), pack2(sb_[0], sb_[1]), pack2(sb_[2], sb_[3]));
                }
                uint32_t qx0 = qx.x, qx1 = qx.y;
                OPQ(qx0); OPQ(qx1);
                PT(3);
                SF();
                int it = 0;
                while (true) {
                    const uint32_t qA = hadd2(hadd2(c0.x, c1.x), hadd2(c2.x, c3.x)), qB = hadd2(hadd2(c0.z, c1.z), hadd2(c2.z, c3.z));
                    float sa[4], sb_[4], sc[4];
                    mma16z(sa, ka[0], ka[1], ka[2], ka[3], qA, qB);
                    mma16z(sb_, kb[0], kb[1], kb[2], kb[3], qA, qB);
                    const uint32_t kA = hadd2(hadd2(c0.y, c1.y), hadd2(c2.y, c3.y)), kB = hadd2(hadd2(c0.w, c1.w), hadd2(c2.w, c3.w));
                    mma16z(sc, qA, qx0, qB, qx1, kA, kB);
                    const bool bad = any_bad(or3(tagx2(c1.x, c1.z, ctag), tagx2(c2.x, c2.z, ctag), tagx2(c3.x, c3.z, ctag)));
                    stsm4t(aSp, pack2(sa[0], sa[1]), pack2(sa[2], sa[3]), pack2(sb_[0], sb_[1]), pack2(sb_[2], sb_[3]));
                    stsm2(aSp + 1024, pack2(sc[0], sc[1]), pack2(sc[2], sc[3]));
                    if (__builtin_expect(!bad, 1)) break;
                    OPQ(KA);
                    const uint32_t ac = hb + (KA >> 16);
                    c1 = ldg4<XO_CQK>(ac + (j ^ 1) * 4096, xhi);
                    c2 = ldg4<XO_CQK>(ac + (j ^ 2) * 4096, xhi);
                    c3 = ldg4<XO_CQK>(ac + (j ^ 3) * 4096, xhi);
                    if (++it > SPIN_LIMIT) die(it);
                }
                PC(25, it);
                PT(4);
                bsync<4, 256>();
                uint2 v0, v1, v2, v3;
                uint32_t wo[16 - NB][4];
                const uint32_t t8 = t16 >> 1;
                const uint32_t aWo = sb + SM_WO + (KD & 0xFFFF), aWo1 = sb + SM_WO + ((KD & 0xFFFF) ^ 32);
                {
                    uint32_t am[4], ax[4], a4[2];
                    ldsm4t(am, sb + SM_SP + w * 768 + t16);
                    ldsm4t(ax, sb + SM_SP + w * 768 + 512 + t16);
                    ldsm2t(a4, sb + SM_SP + w * 768 + 1024 + t16);
                    MF();
                    v0 = lds64(a0 + 2048 + t8); v1 = lds64(af + 16 + 2048 + t8);
                    v2 = lds64(af + 4224 + 2048 + t8); v3 = lds64(af + 8464 + 2048 + t8);
                    const uint32_t se = (t16 & 128) ? 0u : ONES, so = se ^ ONES;
                    float hm[4], hx[4], h4[4];
                    mma16z(hm, am[0], am[1], am[2], am[3], se, so);
                    mma16z(hx, ax[0], ax[1], ax[2], ax[3], se, so);
                    mma8z(h4, a4[0], a4[1], ONES);
                    const bool hi = (t16 & 32) != 0;
                    float s0 = hi ? hx[0] : hm[0], s1 = hi ? hx[2] : hm[2];
                    const float s2 = hi ? h4[2] : h4[0];
                    s0 = (KB & 1) ? -1.0e9f * 11.313708499f : s0;
                    s1 = (KB & 2) ? -1.0e9f * 11.313708499f : s1;
                    int mi = __float_as_int(fmaxf(fmaxf(s0, s2), s1));
                    mi ^= (mi >> 31) & 0x7FFFFFFF;
                    const int mm = __reduce_max_sync(0xFFFFFFFFu, hi ? (int)0x80000000 : mi), mx = __reduce_max_sync(0xFFFFFFFFu, hi ? mi : (int)0x80000000);
#pragma unroll
                    for (int i = 0; i < NPF; i++) ldsm4t(wo[i], ((i & 1) ? aWo1 : aWo) + (i >> 1) * 2048);
                    MF();
                    mi = hi ? mx : mm;
                    mi ^= (mi >> 31) & 0x7FFFFFFF;
                    const float c2_ = 0.08838834764831845f * 1.4426950408889634f;
                    const float mc = __int_as_float(mi) * c2_;
                    const float e0 = ex2(fmaf(s0, c2_, -mc)), e1 = ex2(fmaf(s1, c2_, -mc)), e2 = ex2(fmaf(s2, c2_, -mc));
                    sts32(sb + SM_P + w * 208 + (KC >> 25), pack2(e0, e1));
                    sts16(sb + SM_P + w * 208 + 128 + (KC >> 26), pack2(e2, e2));
                }
                const uint32_t aPr = sb + SM_P + (KD >> 16);
                PT(5);
                bsync<5, 384>();
                uint32_t pm[4];
                ldsm4(pm, aPr);
                const uint2 vs = lds64(sb + SM_VS + t8);
                const uint32_t p4 = ldsm1(aPr + 128);
                const uint32_t vm0 = hadd2(ov0, vs.x), vm1 = hadd2(ov1, vs.y);
                float oa[4], ob[4], dn[4];
                mma16z(oa, v0.x, v0.y, v1.x, v1.y, pm[0], pm[1]);
                mma16z(ob, v2.x, v2.y, v3.x, v3.y, pm[2], pm[3]);
                mma8(oa, vm0, vm1, p4);
                stsm2(sb + SM_OT - w * 256 + t16, pack2(oa[0] + ob[0], oa[1] + ob[1]), pack2(oa[2] + ob[2], oa[3] + ob[3]));
                PT(6);
                bsync<6, 256>();
                SF();
                uint32_t b[4][4];
                mma16z(dn, ONES, ONES, ONES, ONES, pm[0], pm[1]);
                ldsm4t(b[0], sb + SM_OT - w512 + t16);
                ldsm4t(b[1], sb + SM_OT - w512 + t16 + 512);
                MF();
                sts64(sb + SM_VM + t8, vm0, vm1);
                mma16(dn, ONES, ONES, ONES, ONES, pm[2], pm[3]);
                mma8(dn, ONES, ONES, p4);
                SF();
                const float r0 = rcp(dn[0]), r1 = rcp(dn[1]);
                uint32_t ar = xlo + j * 131072 + h * 32 + (t16 >> 5) * 992 + t16, ahi = xhi, tg = (s & 1) ^ 1;
                float r[2][4];
#pragma unroll
                for (int pp = 0; pp < 4; pp++) {
                    const int f0 = 4 * pp - NB > 0 ? 4 * pp - NB : 0, fp = 4 * (pp - 1) - NB > 0 ? 4 * (pp - 1) - NB : 0;
                    const int n0 = pp == 0 ? NPF : NPF + WPF + fp, n1 = NPF + WPF + f0;
                    if (pp >= 1 && pp <= 2) ldsm4t(b[pp + 1], sb + SM_OT - w512 + t16 + (pp + 1) * 512);
#pragma unroll
                    for (int n = 0; n < 16 - NB; n++)
                        if (n >= n0 && (pp == 3 || n < n1)) ldsm4t(wo[n < 16 - NB ? n : 0], ((n & 1) ? aWo1 : aWo) + (n >> 1) * 2048);
                    if (pp == 2) { OPQ(ar); OPQ(ahi); OPQ(tg); }
#pragma unroll
                    for (int e = 0; e < 2; e++)
#pragma unroll
                        for (int mt = 0; mt < 2; mt++) {
                            const int i = (pp * 2 + e) * 2 + mt;
                            const uint32_t* a = i < NB ? Wo[i < NB ? i : 0] : wo[i < NB ? 0 : i - NB];
                            if (i < 2) mma16z(r[mt], a[0], a[1], a[2], a[3], b[pp][2 * e], b[pp][2 * e + 1]);
                            else mma16(r[mt], a[0], a[1], a[2], a[3], b[pp][2 * e], b[pp][2 * e + 1]);
                        }
                    if (pp < 3) SF();
                }
                stg4<XO_R>(ar, ahi, settag(pack2(r[0][0] * r0, r[0][1] * r1), tg),
                           pack2(r[0][2] * r0, r[0][3] * r1), pack2(r[1][0] * r0, r[1][1] * r1), pack2(r[1][2] * r0, r[1][3] * r1));
                barv<7, 384>();
            }
            PT(10);
            if (s + LAG < NSEG) xproj(w, t16 >> 1, KA, KC, s, Wq, Wk, Wv);
            OPQALL();
            PT(15);
        }
        pv_x(t16 >> 1, sb + SM_P + (KD >> 16), uox + (t16 >> 2), xhi, NSEG - 1);
    }
}

#define G2_STAGES 6
#define G2_STAGE_BYTES 32768
DEVI void wg_ss128t(float (&d)[64], uint64_t da, uint64_t db, int sc) {
    asm volatile("{\n.reg .pred p;\nsetp.ne.b32 p, %66, 0;\n"
                 "wgmma.mma_async.sync.aligned.m64n128k16.f32.bf16.bf16 "
                 "{%0,%1,%2,%3,%4,%5,%6,%7,%8,%9,%10,%11,%12,%13,%14,%15,%16,%17,%18,%19,%20,%21,%22,%23,%24,%25,%26,%27,%28,%29,%30,%31,"
                 "%32,%33,%34,%35,%36,%37,%38,%39,%40,%41,%42,%43,%44,%45,%46,%47,%48,%49,%50,%51,%52,%53,%54,%55,%56,%57,%58,%59,%60,%61,%62,%63}, "
                 "%64, %65, p, 1, 1, 1, 1;\n}\n"
                 : "+f"(d[0]), "+f"(d[1]), "+f"(d[2]), "+f"(d[3]), "+f"(d[4]), "+f"(d[5]), "+f"(d[6]), "+f"(d[7]),
                   "+f"(d[8]), "+f"(d[9]), "+f"(d[10]), "+f"(d[11]), "+f"(d[12]), "+f"(d[13]), "+f"(d[14]), "+f"(d[15]),
                   "+f"(d[16]), "+f"(d[17]), "+f"(d[18]), "+f"(d[19]), "+f"(d[20]), "+f"(d[21]), "+f"(d[22]), "+f"(d[23]),
                   "+f"(d[24]), "+f"(d[25]), "+f"(d[26]), "+f"(d[27]), "+f"(d[28]), "+f"(d[29]), "+f"(d[30]), "+f"(d[31]),
                   "+f"(d[32]), "+f"(d[33]), "+f"(d[34]), "+f"(d[35]), "+f"(d[36]), "+f"(d[37]), "+f"(d[38]), "+f"(d[39]),
                   "+f"(d[40]), "+f"(d[41]), "+f"(d[42]), "+f"(d[43]), "+f"(d[44]), "+f"(d[45]), "+f"(d[46]), "+f"(d[47]),
                   "+f"(d[48]), "+f"(d[49]), "+f"(d[50]), "+f"(d[51]), "+f"(d[52]), "+f"(d[53]), "+f"(d[54]), "+f"(d[55]),
                   "+f"(d[56]), "+f"(d[57]), "+f"(d[58]), "+f"(d[59]), "+f"(d[60]), "+f"(d[61]), "+f"(d[62]), "+f"(d[63])
                 : "l"(da), "l"(db), "r"(sc));
}

__global__ void __launch_bounds__(288, 1)
gemm2_kernel(uint32_t xlo, uint32_t xhi, const __grid_constant__ CUtensorMap tmb, bf16* __restrict__ out) {
    extern __shared__ __align__(1024) uint8_t smem[];
    if (smem_u32(smem) != sb) die(1 << 24);
    const uint32_t bars = sb + G2_STAGES * G2_STAGE_BYTES;
    const int tid = threadIdx.x, lane = tid & 31;
    const int w = __shfl_sync(0xFFFFFFFFu, tid >> 5, 0);
    const int bm = blockIdx.x >> 3, bn = blockIdx.x & 7;
    if (tid == 0) {
        for (int i = 0; i < G2_STAGES; i++) { mbar_init(bars + i * 8, 1); mbar_init(bars + (G2_STAGES + i) * 8, 2); }
        asm volatile("fence.mbarrier_init.release.cluster;" ::: "memory");
        asm volatile("fence.proxy.async.shared::cta;" ::: "memory");
    }
    __syncthreads();
    const int NK = HD / 64;
    if (w == 8) {
        if (lane == 0) {
            int st = 0, ph = 1;
            for (int kb = 0; kb < NK; kb++) {
                mbar_wait(bars + (G2_STAGES + st) * 8, ph);
                const uint32_t dst = sb + st * G2_STAGE_BYTES;
                mbar_expect(bars + st * 8, G2_STAGE_BYTES);
                bulk_g2s(dst, xlo + XO_OX + (bm * 64 + kb) * 16384, xhi, 16384, bars + st * 8);
                tma2d(dst + 16384, &tmb, bars + st * 8, bn * 128, kb * 64);
                tma2d(dst + 24576, &tmb, bars + st * 8, bn * 128 + 64, kb * 64);
                if (++st == G2_STAGES) { st = 0; ph ^= 1; }
            }
        }
    } else {
        const int wg = w >> 2;
        float acc[64];
        int st = 0, ph = 0;
        for (int kb = 0; kb < NK; kb++) {
            mbar_wait(bars + st * 8, ph);
            const uint32_t base = sb + st * G2_STAGE_BYTES;
            const uint64_t da = mkdesc(base + wg * 8192, 128, 1024) & ~((uint64_t)3 << 62);
            const uint64_t db = mkdesc(base + 16384, 8192, 1024);
            wg_fence();
#pragma unroll
            for (int k = 0; k < 4; k++) wg_ss128t(acc, da + k * 16, db + k * 128, (kb | k) != 0);
            wg_commit();
            if (kb > 0) {
                wg_wait<1>();
                const int pst = st == 0 ? G2_STAGES - 1 : st - 1;
                if ((tid & 127) == 0) mbar_arrive(bars + (G2_STAGES + pst) * 8);
            }
            if (++st == G2_STAGES) { st = 0; ph ^= 1; }
        }
        wg_wait<0>();
        const int row = bm * 128 + wg * 64 + (w & 3) * 16 + (lane >> 2);
        bf16* o = out + (size_t)row * 2048 + bn * 128 + (lane & 3) * 2;
#pragma unroll
        for (int i = 0; i < 16; i++) {
            *(uint32_t*)(o + i * 8) = pack2(acc[4 * i], acc[4 * i + 1]);
            *(uint32_t*)(o + 8 * 2048 + i * 8) = pack2(acc[4 * i + 2], acc[4 * i + 3]);
        }
    }
}

template <int N, int LOGN, int NT>
DEVI void fft_smem(float2* x, int tid, float sgn) {
    for (int st = 0; st < LOGN; st++) {
        const int half = 1 << st;
        __syncthreads();
        for (int i = tid; i < N / 2; i += NT) {
            const int k = i & (half - 1), base = ((i >> st) << (st + 1)) + k;
            float sn, cs;
            sincospif(sgn * (float)k / (float)half, &sn, &cs);
            const float2 a = x[base], b = x[base + half];
            const float2 tw = make_float2(b.x * cs - b.y * sn, b.x * sn + b.y * cs);
            x[base] = make_float2(a.x + tw.x, a.y + tw.y);
            x[base + half] = make_float2(a.x - tw.x, a.y - tw.y);
        }
    }
    __syncthreads();
}
__global__ void __launch_bounds__(256) fft_rows_fwd(const bf16* __restrict__ x) {
    __shared__ float2 sm[1024];
    const int row = blockIdx.x, tid = threadIdx.x;
    for (int i = tid; i < 1024; i += 256) sm[__brev(i) >> 22] = make_float2(__bfloat162float(x[row * 1024 + i]), 0.f);
    fft_smem<1024, 10, 256>(sm, tid, -1.f);
    for (int i = tid; i < 513; i += 256) g_F[row * 520 + i] = sm[i];
}
__global__ void __launch_bounds__(256) fft_cols(const bf16* __restrict__ wr, const bf16* __restrict__ wi) {
    __shared__ float2 sm[2048], sm2[2048];
    const int col = blockIdx.x, tid = threadIdx.x;
    for (int i = tid; i < 2048; i += 256) sm[__brev(i) >> 21] = g_F[i * 520 + col];
    fft_smem<2048, 11, 256>(sm, tid, -1.f);
    for (int i = tid; i < 2048; i += 256) {
        const float a = __bfloat162float(wr[i * 513 + col]), b = __bfloat162float(wi[i * 513 + col]);
        const float2 v = sm[i];
        sm2[__brev(i) >> 21] = make_float2(v.x * a - v.y * b, v.x * b + v.y * a);
    }
    fft_smem<2048, 11, 256>(sm2, tid, 1.f);
    for (int i = tid; i < 2048; i += 256) g_F[i * 520 + col] = sm2[i];
}
__global__ void __launch_bounds__(256) fft_rows_inv(bf16* __restrict__ out) {
    __shared__ float2 sm[1024];
    const int row = blockIdx.x, tid = threadIdx.x;
    for (int i = tid; i < 1024; i += 256) {
        float2 v;
        if (i <= 512) { v = g_F[row * 520 + i]; if (i == 0 || i == 512) v.y = 0.f; }
        else { v = g_F[row * 520 + 1024 - i]; v.y = -v.y; }
        sm[__brev(i) >> 22] = v;
    }
    fft_smem<1024, 10, 256>(sm, tid, 1.f);
    const float sc = 1.f / (2048.f * 1024.f);
    for (int i = tid; i < 1024; i += 256) out[(size_t)row * 2048 + 1024 + i] = __float2bfloat16(sm[i].x * sc);
}

typedef CUresult (*EncodeFn)(CUtensorMap*, CUtensorMapDataType, cuuint32_t, void*, const cuuint64_t*, const cuuint64_t*,
                             const cuuint32_t*, const cuuint32_t*, CUtensorMapInterleave, CUtensorMapSwizzle,
                             CUtensorMapL2promotion, CUtensorMapFloatOOBfill);

static void make_map(EncodeFn enc, CUtensorMap* m, const void* ptr, int rank, const cuuint64_t* dims, const cuuint64_t* strides,
                     const cuuint32_t* box) {
    cuuint32_t es[3] = {1, 1, 1};
    CUresult r = enc(m, CU_TENSOR_MAP_DATA_TYPE_BFLOAT16, rank, (void*)ptr, dims, strides, box, es, CU_TENSOR_MAP_INTERLEAVE_NONE,
                     CU_TENSOR_MAP_SWIZZLE_128B, CU_TENSOR_MAP_L2_PROMOTION_L2_256B, CU_TENSOR_MAP_FLOAT_OOB_FILL_NONE);
    if (r != CUDA_SUCCESS) fprintf(stderr, "tensor map encode failed: %d\n", (int)r);
}

extern "C" void kernel_launch(void* const* d_in, const int* in_sizes, int n_in, void* d_out, int out_size) {
    const bf16* A_x = (const bf16*)d_in[0];
    const bf16* A_mem0 = (const bf16*)d_in[1];
    const bf16* A_Wq = (const bf16*)d_in[2];
    const bf16* A_Wk = (const bf16*)d_in[3];
    const bf16* A_Wv = (const bf16*)d_in[4];
    const bf16* A_Wo = (const bf16*)d_in[5];
    const bf16* B_x = (const bf16*)d_in[7];
    const bf16* B_wr = (const bf16*)d_in[8];
    const bf16* B_wi = (const bf16*)d_in[9];
    bf16* out = (bf16*)d_out;

    static EncodeFn enc = nullptr;
    static void* pxs = nullptr;
    if (!enc) {
        cudaDriverEntryPointQueryResult qr;
        void* fn = nullptr;
        cudaGetDriverEntryPoint("cuTensorMapEncodeTiled", &fn, cudaEnableDefault, &qr);
        enc = (EncodeFn)fn;
        cudaFuncSetAttribute(chain_kernel, cudaFuncAttributeMaxDynamicSharedMemorySize, SM_TOTAL);
        cudaFuncSetAttribute(gemm2_kernel, cudaFuncAttributeMaxDynamicSharedMemorySize, G2_STAGES * G2_STAGE_BYTES + 128);
        cudaGetSymbolAddress(&pxs, g_xs);
    }
    CUtensorMap tmq, tmk, tmv, tmo, tmx, tmb;
    {
        cuuint64_t d[2] = {HD, DM}, st[1] = {HD * 2};
        cuuint32_t bx[2] = {64, 256};
        make_map(enc, &tmq, A_Wq, 2, d, st, bx);
        make_map(enc, &tmk, A_Wk, 2, d, st, bx);
        cuuint32_t bx2[2] = {64, 16};
        make_map(enc, &tmv, A_Wv, 2, d, st, bx2);
    }
    {
        cuuint64_t d[2] = {DM, HD}, st[1] = {DM * 2};
        cuuint32_t bx[2] = {64, 16}, bx2[2] = {64, 64};
        make_map(enc, &tmo, A_Wo, 2, d, st, bx);
        make_map(enc, &tmb, A_Wo, 2, d, st, bx2);
    }
    {
        cuuint64_t d[3] = {64, SEQ, DM / 64}, st[2] = {DM * 2, 128};
        cuuint32_t bx[3] = {64, 8, 4};
        make_map(enc, &tmx, A_x, 3, d, st, bx);
    }
    cudaStream_t st = cudaStreamPerThread;
    const uint64_t xs = ((uint64_t)pxs + XS_BYTES - 1) & ~(uint64_t)(XS_BYTES - 1);
    cudaMemsetAsync((void*)(xs + XO_B), 0xFF, XO_FL - XO_B + 8 * 128 * 32, st);
    chain_kernel<<<128, 384, SM_TOTAL, st>>>(tmq, tmk, tmv, tmo, tmx, A_mem0, A_x, (uint32_t)xs, (uint32_t)(xs >> 32), 0u, NSEG);
    gemm2_kernel<<<128, 288, G2_STAGES * G2_STAGE_BYTES + 128, st>>>((uint32_t)xs, (uint32_t)(xs >> 32), tmb, out);
    fft_rows_fwd<<<2048, 256, 0, st>>>(B_x);
    fft_cols<<<513, 256, 0, st>>>(B_wr, B_wi);
    fft_rows_inv<<<2048, 256, 0, st>>>(out);
}
```

```cpp
#include <cuda_runtime.h>
#include <cuda_bf16.h>
#include <cuda.h>
#include <stdint.h>
#include <stdio.h>

typedef __nv_bfloat16 bf16;

#define SEQ 2048
#define DM 1024
#define NH 32
#define DH 128
#define NSEG 64
#define HD (NH * DH)

#define XS_BYTES (32u << 20)
__device__ uint4 g_xs[2 * XS_BYTES / 16];
#define XO_R 0u
#define XO_B (1u << 19)
#define XO_PB (XO_B + 16384u)
#define XO_FL (XO_B + 32768u)
#define XO_TK (XO_FL + 32768u)
#define XO_CQK (1u << 20)
#define XO_CV (2u << 20)
#define XO_XG (4u << 20)
#define XO_OX (16u << 20)

#define DEVI __device__ __forceinline__

DEVI void die(int it) { asm volatile("st.shared.u32 [%0], %0;" ::"r"(it) : "memory"); }
DEVI uint32_t smem_u32(const void* p) { return (uint32_t)__cvta_generic_to_shared(p); }
DEVI void mbar_init(uint32_t bar, uint32_t cnt) { asm volatile("mbarrier.init.shared::cta.b64 [%0], %1;" ::"r"(bar), "r"(cnt) : "memory"); }
DEVI void mbar_expect(uint32_t bar, uint32_t bytes) { asm volatile("mbarrier.arrive.expect_tx.shared::cta.b64 _, [%0], %1;" ::"r"(bar), "r"(bytes) : "memory"); }
DEVI void mbar_arrive(uint32_t bar) { asm volatile("mbarrier.arrive.shared::cta.b64 _, [%0];" ::"r"(bar) : "memory"); }
DEVI void mbar_wait(uint32_t bar, uint32_t parity) {
    uint32_t done;
    int it = 0;
    do {
        asm volatile("{\n.reg .pred p;\nmbarrier.try_wait.parity.shared::cta.b64 p, [%1], %2;\nselp.u32 %0, 1, 0, p;\n}\n"
                     : "=r"(done) : "r"(bar), "r"(parity) : "memory");
        if (++it > (1 << 22)) die(it);
    } while (!done);
}
DEVI void tma2d(uint32_t dst, const CUtensorMap* tm, uint32_t bar, int c0, int c1) {
    asm volatile("cp.async.bulk.tensor.2d.shared::cluster.global.mbarrier::complete_tx::bytes [%0], [%1, {%3, %4}], [%2];"
                 ::"r"(dst), "l"(tm), "r"(bar), "r"(c0), "r"(c1) : "memory");
}
DEVI void tma3d(uint32_t dst, const CUtensorMap* tm, uint32_t bar, int c0, int c1, int c2) {
    asm volatile("cp.async.bulk.tensor.3d.shared::cluster.global.mbarrier::complete_tx::bytes [%0], [%1, {%3, %4, %5}], [%2];"
                 ::"r"(dst), "l"(tm), "r"(bar), "r"(c0), "r"(c1), "r"(c2) : "memory");
}
DEVI void bulk_g2s(uint32_t dst, uint32_t lo, uint32_t hi, uint32_t bytes, uint32_t bar) {
    asm volatile("{\n.reg .b64 a;\nmov.b64 a, {%1,%2};\ncp.async.bulk.shared::cluster.global.mbarrier::complete_tx::bytes [%0], [a], %3, [%4];\n}"
                 ::"r"(dst), "r"(lo), "r"(hi), "r"(bytes), "r"(bar) : "memory");
}
DEVI void bulk_s2g(uint32_t lo, uint32_t hi, uint32_t src, uint32_t bytes) {
    asm volatile("{\n.reg .b64 a;\nmov.b64 a, {%0,%1};\ncp.async.bulk.global.shared::cta.bulk_group [a], [%2], %3;\ncp.async.bulk.commit_group;\n}"
                 ::"r"(lo), "r"(hi), "r"(src), "r"(bytes) : "memory");
}
DEVI void bulk_red(uint32_t lo, uint32_t hi, uint32_t src, uint32_t bytes) {
    asm volatile("{\n.reg .b64 a;\nmov.b64 a, {%0,%1};\ncp.reduce.async.bulk.global.shared::cta.bulk_group.add.noftz.bf16 [a], [%2], %3;\ncp.async.bulk.commit_group;\n}"
                 ::"r"(lo), "r"(hi), "r"(src), "r"(bytes) : "memory");
}
DEVI bool elect() {
    uint32_t p;
    asm volatile("{\n.reg .pred P;\nelect.sync _|P, 0xFFFFFFFF;\nselp.u32 %0, 1, 0, P;\n}" : "=r"(p));
    return p != 0;
}
DEVI void ldsm4(uint32_t (&r)[4], uint32_t a) {
    asm volatile("ldmatrix.sync.aligned.m8n8.x4.shared.b16 {%0,%1,%2,%3}, [%4];" : "=r"(r[0]), "=r"(r[1]), "=r"(r[2]), "=r"(r[3]) : "r"(a) : "memory");
}
DEVI void ldsm4t(uint32_t (&r)[4], uint32_t a) {
    asm volatile("ldmatrix.sync.aligned.m8n8.x4.trans.shared.b16 {%0,%1,%2,%3}, [%4];" : "=r"(r[0]), "=r"(r[1]), "=r"(r[2]), "=r"(r[3]) : "r"(a) : "memory");
}
DEVI void ldsm2t(uint32_t (&r)[2], uint32_t a) {
    asm volatile("ldmatrix.sync.aligned.m8n8.x2.trans.shared.b16 {%0,%1}, [%2];" : "=r"(r[0]), "=r"(r[1]) : "r"(a) : "memory");
}
DEVI void ldsm2(uint32_t (&r)[2], uint32_t a) {
    asm volatile("ldmatrix.sync.aligned.m8n8.x2.shared.b16 {%0,%1}, [%2];" : "=r"(r[0]), "=r"(r[1]) : "r"(a) : "memory");
}
DEVI void stsm4t(uint32_t a, uint32_t r0, uint32_t r1, uint32_t r2, uint32_t r3) {
    asm volatile("stmatrix.sync.aligned.m8n8.x4.trans.shared.b16 [%0], {%1,%2,%3,%4};" ::"r"(a), "r"(r0), "r"(r1), "r"(r2), "r"(r3) : "memory");
}
DEVI uint32_t ldsm1(uint32_t a) {
    uint32_t r;
    asm volatile("ldmatrix.sync.aligned.m8n8.x1.shared.b16 {%0}, [%1];" : "=r"(r) : "r"(a) : "memory");
    return r;
}
DEVI void stsm4(uint32_t a, uint32_t r0, uint32_t r1, uint32_t r2, uint32_t r3) {
    asm volatile("stmatrix.sync.aligned.m8n8.x4.shared.b16 [%0], {%1,%2,%3,%4};" ::"r"(a), "r"(r0), "r"(r1), "r"(r2), "r"(r3) : "memory");
}
DEVI void stsm2(uint32_t a, uint32_t r0, uint32_t r1) {
    asm volatile("stmatrix.sync.aligned.m8n8.x2.shared.b16 [%0], {%1,%2};" ::"r"(a), "r"(r0), "r"(r1) : "memory");
}
DEVI uint32_t movm(uint32_t a) {
    uint32_t d;
    asm volatile("movmatrix.sync.aligned.m8n8.trans.b16 %0, %1;" : "=r"(d) : "r"(a));
    return d;
}
DEVI void mma16(float (&d)[4], uint32_t a0, uint32_t a1, uint32_t a2, uint32_t a3, uint32_t b0, uint32_t b1) {
    asm volatile("mma.sync.aligned.m16n8k16.row.col.f32.bf16.bf16.f32 {%0,%1,%2,%3}, {%4,%5,%6,%7}, {%8,%9}, {%0,%1,%2,%3};"
                 : "+f"(d[0]), "+f"(d[1]), "+f"(d[2]), "+f"(d[3]) : "r"(a0), "r"(a1), "r"(a2), "r"(a3), "r"(b0), "r"(b1));
}
DEVI void mma16z(float (&d)[4], uint32_t a0, uint32_t a1, uint32_t a2, uint32_t a3, uint32_t b0, uint32_t b1) {
    asm volatile("mma.sync.aligned.m16n8k16.row.col.f32.bf16.bf16.f32 {%0,%1,%2,%3}, {%4,%5,%6,%7}, {%8,%9}, {%10,%10,%10,%10};"
                 : "=f"(d[0]), "=f"(d[1]), "=f"(d[2]), "=f"(d[3]) : "r"(a0), "r"(a1), "r"(a2), "r"(a3), "r"(b0), "r"(b1), "f"(0.f));
}
DEVI void mma8(float (&d)[4], uint32_t a0, uint32_t a1, uint32_t b0) {
    asm volatile("mma.sync.aligned.m16n8k8.row.col.f32.bf16.bf16.f32 {%0,%1,%2,%3}, {%4,%5}, {%6}, {%0,%1,%2,%3};"
                 : "+f"(d[0]), "+f"(d[1]), "+f"(d[2]), "+f"(d[3]) : "r"(a0), "r"(a1), "r"(b0));
}
DEVI void mma8z(float (&d)[4], uint32_t a0, uint32_t a1, uint32_t b0) {
    asm volatile("mma.sync.aligned.m16n8k8.row.col.f32.bf16.bf16.f32 {%0,%1,%2,%3}, {%4,%5}, {%6}, {%7,%7,%7,%7};"
                 : "=f"(d[0]), "=f"(d[1]), "=f"(d[2]), "=f"(d[3]) : "r"(a0), "r"(a1), "r"(b0), "f"(0.f));
}
DEVI uint32_t pack2(float lo, float hi) {
    uint32_t r;
    asm("cvt.rn.bf16x2.f32 %0, %1, %2;" : "=r"(r) : "f"(hi), "f"(lo));
    return r;
}
DEVI uint32_t hadd2(uint32_t a, uint32_t b) {
    uint32_t r;
    asm("add.rn.bf16x2 %0, %1, %2;" : "=r"(r) : "r"(a), "r"(b));
    return r;
}
DEVI float lo_f(uint32_t x) { return __uint_as_float(x << 16); }
DEVI float hi_f(uint32_t x) { return __uint_as_float(x & 0xFFFF0000u); }
template <uint32_t OFF> DEVI uint4 ldg4(uint32_t lo, uint32_t hi) {
    uint4 v;
    asm volatile("{\n.reg .b64 a;\nmov.b64 a, {%4,%5};\nld.relaxed.gpu.global.v4.u32 {%0,%1,%2,%3}, [a+%6];\n}"
                 : "=r"(v.x), "=r"(v.y), "=r"(v.z), "=r"(v.w) : "r"(lo), "r"(hi), "n"(OFF) : "memory");
    return v;
}
template <uint32_t OFF> DEVI uint2 ldg2(uint32_t lo, uint32_t hi) {
    uint2 v;
    asm volatile("{\n.reg .b64 a;\nmov.b64 a, {%2,%3};\nld.relaxed.gpu.global.v2.u32 {%0,%1}, [a+%4];\n}"
                 : "=r"(v.x), "=r"(v.y) : "r"(lo), "r"(hi), "n"(OFF) : "memory");
    return v;
}
template <uint32_t OFF> DEVI uint32_t ldg1(uint32_t lo, uint32_t hi) {
    uint32_t v;
    asm volatile("{\n.reg .b64 a;\nmov.b64 a, {%1,%2};\nld.relaxed.gpu.global.u32 %0, [a+%3];\n}" : "=r"(v) : "r"(lo), "r"(hi), "n"(OFF) : "memory");
    return v;
}
template <uint32_t OFF> DEVI void stg1(uint32_t lo, uint32_t hi, uint32_t a) {
    asm volatile("{\n.reg .b64 a;\nmov.b64 a, {%0,%1};\nst.relaxed.gpu.global.u32 [a+%3], %2;\n}" ::"r"(lo), "r"(hi), "r"(a), "n"(OFF) : "memory");
}
template <uint32_t OFF> DEVI void stg4(uint32_t lo, uint32_t hi, uint32_t a, uint32_t b, uint32_t c, uint32_t d) {
    asm volatile("{\n.reg .b64 a;\nmov.b64 a, {%0,%1};\nst.relaxed.gpu.global.v4.u32 [a+%6], {%2,%3,%4,%5};\n}"
                 ::"r"(lo), "r"(hi), "r"(a), "r"(b), "r"(c), "r"(d), "n"(OFF) : "memory");
}
template <uint32_t OFF> DEVI void stg2(uint32_t lo, uint32_t hi, uint32_t a, uint32_t b) {
    asm volatile("{\n.reg .b64 a;\nmov.b64 a, {%0,%1};\nst.relaxed.gpu.global.v2.u32 [a+%4], {%2,%3};\n}"
                 ::"r"(lo), "r"(hi), "r"(a), "r"(b), "n"(OFF) : "memory");
}
DEVI uint32_t tagx2(uint32_t a, uint32_t b, uint32_t t) { uint32_t r; asm("lop3.b32 %0, %1, %2, %3, 0x7E;" : "=r"(r) : "r"(a), "r"(b), "r"(t)); return r; }
DEVI uint32_t tagx1(uint32_t a, uint32_t b, uint32_t t) { uint32_t r; asm("lop3.b32 %0, %1, %2, %3, 0xF6;" : "=r"(r) : "r"(a), "r"(b), "r"(t)); return r; }
DEVI uint32_t or3(uint32_t a, uint32_t b, uint32_t c) { uint32_t r; asm("lop3.b32 %0, %1, %2, %3, 0xFE;" : "=r"(r) : "r"(a), "r"(b), "r"(c)); return r; }
DEVI bool any_bad(uint32_t x) { return __any_sync(0xFFFFFFFFu, (x & 1u) != 0); }
DEVI uint32_t settag(uint32_t x, uint32_t tag) { return (x & ~1u) | tag; }
DEVI void sts32f(uint32_t a, float v) { asm volatile("st.shared.f32 [%0], %1;" ::"r"(a), "f"(v) : "memory"); }
DEVI void sts32(uint32_t a, uint32_t v) { asm volatile("st.shared.u32 [%0], %1;" ::"r"(a), "r"(v) : "memory"); }
DEVI void sts16(uint32_t a, uint32_t v) { asm volatile("st.shared.u16 [%0], %1;" ::"r"(a), "h"((unsigned short)v) : "memory"); }
DEVI void sts64(uint32_t a, uint32_t x, uint32_t y) { asm volatile("st.shared.v2.u32 [%0], {%1,%2};" ::"r"(a), "r"(x), "r"(y) : "memory"); }
DEVI void sts128(uint32_t a, uint32_t x, uint32_t y, uint32_t z, uint32_t w) {
    asm volatile("st.shared.v4.u32 [%0], {%1,%2,%3,%4};" ::"r"(a), "r"(x), "r"(y), "r"(z), "r"(w) : "memory");
}
DEVI float4 lds128f(uint32_t a) {
    float4 v;
    asm volatile("ld.shared.v4.f32 {%0,%1,%2,%3}, [%4];" : "=f"(v.x), "=f"(v.y), "=f"(v.z), "=f"(v.w) : "r"(a) : "memory");
    return v;
}
DEVI uint4 lds128(uint32_t a) {
    uint4 v;
    asm volatile("ld.shared.v4.u32 {%0,%1,%2,%3}, [%4];" : "=r"(v.x), "=r"(v.y), "=r"(v.z), "=r"(v.w) : "r"(a) : "memory");
    return v;
}
DEVI uint2 lds64(uint32_t a) {
    uint2 v;
    asm volatile("ld.shared.v2.u32 {%0,%1}, [%2];" : "=r"(v.x), "=r"(v.y) : "r"(a) : "memory");
    return v;
}
DEVI uint32_t lds32(uint32_t a) {
    uint32_t v;
    asm volatile("ld.shared.u32 %0, [%1];" : "=r"(v) : "r"(a) : "memory");
    return v;
}
DEVI float ex2(float x) { float r; asm("ex2.approx.ftz.f32 %0, %1;" : "=f"(r) : "f"(x)); return r; }
DEVI float rcp(float x) { float r; asm("rcp.approx.ftz.f32 %0, %1;" : "=f"(r) : "f"(x)); return r; }
DEVI uint32_t clk() { uint32_t c; asm volatile("mov.u32 %0, %%clock;" : "=r"(c)::"memory"); return c; }

DEVI uint64_t mkdesc(uint32_t addr, uint32_t lbo, uint32_t sbo) {
    return (uint64_t)((addr & 0x3FFFF) >> 4) | ((uint64_t)(lbo >> 4) << 16) | ((uint64_t)(sbo >> 4) << 32) | ((uint64_t)1 << 62);
}
DEVI void wg_fence() { asm volatile("wgmma.fence.sync.aligned;" ::: "memory"); }
DEVI void wg_commit() { asm volatile("wgmma.commit_group.sync.aligned;" ::: "memory"); }
template <int N> DEVI void wg_wait() { asm volatile("wgmma.wait_group.sync.aligned %0;" ::"n"(N) : "memory"); }
template <int SC>
DEVI void wg_rs32(float (&d)[16], const uint32_t (&a)[4], uint64_t db) {
    if (SC) {
        asm volatile("wgmma.mma_async.sync.aligned.m64n32k16.f32.bf16.bf16 "
                     "{%0,%1,%2,%3,%4,%5,%6,%7,%8,%9,%10,%11,%12,%13,%14,%15}, {%16,%17,%18,%19}, %20, 1, 1, 1, 0;"
                     : "+f"(d[0]), "+f"(d[1]), "+f"(d[2]), "+f"(d[3]), "+f"(d[4]), "+f"(d[5]), "+f"(d[6]), "+f"(d[7]),
                       "+f"(d[8]), "+f"(d[9]), "+f"(d[10]), "+f"(d[11]), "+f"(d[12]), "+f"(d[13]), "+f"(d[14]), "+f"(d[15])
                     : "r"(a[0]), "r"(a[1]), "r"(a[2]), "r"(a[3]), "l"(db));
    } else {
        asm volatile("wgmma.mma_async.sync.aligned.m64n32k16.f32.bf16.bf16 "
                     "{%0,%1,%2,%3,%4,%5,%6,%7,%8,%9,%10,%11,%12,%13,%14,%15}, {%16,%17,%18,%19}, %20, 0, 1, 1, 0;"
                     : "=f"(d[0]), "=f"(d[1]), "=f"(d[2]), "=f"(d[3]), "=f"(d[4]), "=f"(d[5]), "=f"(d[6]), "=f"(d[7]),
                       "=f"(d[8]), "=f"(d[9]), "=f"(d[10]), "=f"(d[11]), "=f"(d[12]), "=f"(d[13]), "=f"(d[14]), "=f"(d[15])
                     : "r"(a[0]), "r"(a[1]), "r"(a[2]), "r"(a[3]), "l"(db));
    }
}

#define LAG 3
#define NA 8
#define NB 6
#define NPF 5
#define WPF 1
#define WV_BOX ((16 - NA) * 2048)
#define WO_BOX ((16 - NB) * 1024)
#define SM_WV 0
#define SM_WO (2 * WV_BOX)
#define SM_X (SM_WO + 4 * WO_BOX)
#define SM_XO (SM_X + 16384)
#define SM_KV (SM_XO + 49152)
#define SM_SP (SM_KV + 2 * 18432)
#define SM_TR (SM_SP + 10240)
#define SM_MEMT (SM_TR + 12288)
#define SM_OT SM_MEMT
#define SM_VS (SM_MEMT + 2048)
#define SM_VM (SM_MEMT + 4096)
#define SM_P (SM_VM + 2048)
#define SM_RS (SM_P + 2048)
#define SM_PROF (SM_RS + 1024)
#define SM_BAR 232192
#define SM_TOTAL (SM_BAR + 128)
#define SM_STA SM_X
#define SM_STB (SM_STA + 65536)
#define SM_STC (SM_STB + 65536)
#define NA1 (NA < 6 ? NA : 6)
static_assert(SM_STC + NA1 * 4096 <= SM_BAR && NB + NA - NA1 <= 16 && SM_PROF + 3072 <= SM_BAR, "staging");
static_assert(SM_TOTAL <= 232448, "smem");
#define BAR_XA 32
#define BAR_KV 40
#define SM_ROLE (SM_BAR + 64)

#define SPIN_LIMIT (1 << 20)
#define DLY_R 200
#define DLY_W 100
#define CFAR 1
#define SWV 0x1221
#define SW(u) ((SWV >> (4 * (u))) & 15)
#define SD 0x3403
#define RLV 2
#define DLY_V 0
#define DLY_B 400

template <int ID, int N> DEVI void bsync() { asm volatile("bar.sync %0, %1;" ::"n"(ID), "n"(N) : "memory"); }
template <int ID, int N> DEVI void barv() { asm volatile("bar.arrive %0, %1;" ::"n"(ID), "n"(N) : "memory"); }

#define PT(n)
#define PC(n, v)
#define PDUMP()
#define REFRESH() asm volatile("xor.b32 %0, %0, %1;" : "+r"(l16) : "r"(zero))
#define OPQ(x) asm volatile("xor.b32 %0, %0, %1;" : "+r"(x) : "r"(zero))
#define SF() asm volatile("pmevent 1;" ::: "memory")
#define MF() __syncwarp()
#define SB0 1024u

#define XDOFF(ks) ((((ks) >> 2) * 1024 + ((ks) & 3) * 32) >> 4)
template <int SC>
DEVI void wg_ss32t(float (&d)[16], uint64_t da, uint64_t db) {
    if (SC) {
        asm volatile("wgmma.mma_async.sync.aligned.m64n32k16.f32.bf16.bf16 "
                     "{%0,%1,%2,%3,%4,%5,%6,%7,%8,%9,%10,%11,%12,%13,%14,%15}, %16, %17, 1, 1, 1, 1, 0;"
                     : "+f"(d[0]), "+f"(d[1]), "+f"(d[2]), "+f"(d[3]), "+f"(d[4]), "+f"(d[5]), "+f"(d[6]), "+f"(d[7]),
                       "+f"(d[8]), "+f"(d[9]), "+f"(d[10]), "+f"(d[11]), "+f"(d[12]), "+f"(d[13]), "+f"(d[14]), "+f"(d[15])
                     : "l"(da), "l"(db));
    } else {
        asm volatile("wgmma.mma_async.sync.aligned.m64n32k16.f32.bf16.bf16 "
                     "{%0,%1,%2,%3,%4,%5,%6,%7,%8,%9,%10,%11,%12,%13,%14,%15}, %16, %17, 0, 1, 1, 1, 0;"
                     : "=f"(d[0]), "=f"(d[1]), "=f"(d[2]), "=f"(d[3]), "=f"(d[4]), "=f"(d[5]), "=f"(d[6]), "=f"(d[7]),
                       "=f"(d[8]), "=f"(d[9]), "=f"(d[10]), "=f"(d[11]), "=f"(d[12]), "=f"(d[13]), "=f"(d[14]), "=f"(d[15])
                     : "l"(da), "l"(db));
    }
}

DEVI void delay_until(uint32_t t0, uint32_t d) { t0 += d; while (clk() < t0) {} }

DEVI void xproj(uint32_t sb, uint32_t w, uint32_t t8, uint32_t KA, uint32_t KB, int s, const uint32_t (&Wq)[16][4], const uint32_t (&Wk)[16][4],
                const uint32_t (&Wv)[NA][4]) {
    float xa[16];
    const uint64_t xd = mkdesc(SB0 + SM_X, 16, 4096);
    const uint32_t xo = sb + SM_XO + (s & 1) * 24576;
    const uint32_t pk = (KA & 0xFF) + w * 256 + xo;
    const uint64_t vd = mkdesc(SB0 + SM_WV + (w >> 2) * WV_BOX, 8192, 1024);
    if (w >= 4) delay_until(clk(), DLY_W);
    wg_fence();
#pragma unroll
    for (int ks = 0; ks < 16; ks++) {
        if (ks == 0) wg_rs32<0>(xa, Wk[ks], xd + XDOFF(ks));
        else wg_rs32<1>(xa, Wk[ks], xd + XDOFF(ks));
    }
    wg_commit();
    PT(11);
    wg_wait<0>();
#pragma unroll
    for (int i = 0; i < 4; i++) sts64(i * 6144 + 2048 + pk, pack2(xa[4 * i], xa[4 * i + 2]), pack2(xa[4 * i + 1], xa[4 * i + 3]));
    PT(12);
    wg_fence();
#pragma unroll
    for (int ks = 0; ks < 16; ks++) {
        if (ks == 0) wg_rs32<0>(xa, Wq[ks], xd + XDOFF(ks));
        else wg_rs32<1>(xa, Wq[ks], xd + XDOFF(ks));
    }
    wg_commit();
    wg_wait<0>();
#pragma unroll
    for (int i = 0; i < 4; i++) sts64(i * 6144 + pk, pack2(xa[4 * i], xa[4 * i + 2]), pack2(xa[4 * i + 1], xa[4 * i + 3]));
    PT(13);
    wg_fence();
#pragma unroll
    for (int ks = 0; ks < 16; ks++) {
        if (ks == 0) wg_rs32<0>(xa, Wv[0], xd + XDOFF(ks));
        else if (ks < NA) wg_rs32<1>(xa, Wv[ks < NA ? ks : 0], xd + XDOFF(ks));
        else wg_ss32t<1>(xa, vd + (ks - NA) * 128, xd + XDOFF(ks));
    }
    wg_commit();
    wg_wait<0>();
    PT(14);
#pragma unroll
    for (int i = 0; i < 4; i++) sts64(xo + i * 6144 + 4096 + t8, pack2(xa[4 * i], xa[4 * i + 1]), pack2(xa[4 * i + 2], xa[4 * i + 3]));
}

DEVI void pv_x(uint32_t sb, uint32_t t8, uint32_t aPr, uint32_t alo, uint32_t xhi, int sg) {
    const uint32_t ONES = 0x3F803F80u;
    uint32_t p[4];
    ldsm4(p, aPr + 64);
    const uint32_t av = sb + SM_KV + (sg & 1) * 18432 + 4096 + t8;
    const uint2 v0 = lds64(av), v1 = lds64(av + 4096), v2 = lds64(av + 8192), v3 = lds64(av + 12288);
    const uint32_t p4 = ldsm1(aPr + 160);
    const uint2 vm = lds64(sb + SM_VM + t8);
    float o[4], dn[4];
    mma16z(dn, ONES, ONES, ONES, ONES, p[0], p[1]);
    mma16z(o, v0.x, v0.y, v1.x, v1.y, p[0], p[1]);
    mma16(dn, ONES, ONES, ONES, ONES, p[2], p[3]);
    mma16(o, v2.x, v2.y, v3.x, v3.y, p[2], p[3]);
    mma8(dn, ONES, ONES, p4);
    mma8(o, vm.x, vm.y, p4);
    const float r0 = rcp(dn[0]), r1 = rcp(dn[1]);
    const uint32_t a = alo + (sg >> 2) * (1u << 20) + (sg & 3) * 4096;
    asm volatile("{\n.reg .b64 a;\nmov.b64 a, {%0,%1};\nst.global.u32 [a], %2;\nst.global.u32 [a+128], %3;\n}"
                 ::"r"(a), "r"(xhi), "r"(pack2(o[0] * r0, o[1] * r1)), "r"(pack2(o[2] * r0, o[3] * r1)) : "memory");
}

DEVI uint32_t par(uint32_t off) { return __popc(off & 0xB2000u) & 1; }
DEVI uint32_t probe(uint32_t lo, uint32_t hi) {
    uint32_t best = 0xFFFFFFFFu, x = 0;
    stg1<0>(lo, hi, 0);
#pragma unroll 1
    for (int r = 0; r < 4; r++) {
        const uint32_t t0 = clk();
        asm volatile("{\n.reg .b64 a;\nmov.b64 a, {%1,%2};\natom.relaxed.gpu.global.add.u32 %0, [a], 2;\n}" : "=r"(x) : "r"(lo), "r"(hi) : "memory");
        if (x == 0xFFFFFFFFu) die(1 << 23);
        best = min(best, clk() - t0);
    }
    return best;
}

DEVI void xsend(uint32_t u, uint32_t h, uint32_t j, uint32_t xlo, uint32_t xhi, int s, uint32_t off, uint32_t bytes) {
    const int sg = u == 0 ? s + LAG + 1 : s + LAG - 1;
    if (sg >= 0 && sg < NSEG && elect()) {
        const uint32_t ga = xlo + XO_XG + (((sg & 7) * 32 + h) * 4 + ((j + u) & 3)) * 6144 + off;
        const uint32_t sa = SB0 + (j << 24 & 0x1000000) + SM_XO + ((s + 1) & 1) * 24576 + u * 6144 + off;
        if (u == 0) bulk_s2g(ga, xhi, sa, bytes);
        else bulk_red(ga, xhi, sa, bytes);
    }
}

template <bool MAIN>
DEVI void helper_step(uint32_t w, uint32_t h, uint32_t j, uint32_t& l16, uint32_t xlo, uint32_t xhi, uint32_t zero, int s,
                      const CUtensorMap* tmx, const bf16* __restrict__ mem0) {
    const uint32_t sb = SB0 + (j << 24 & 0x1000000);
    const uint32_t u = w - 8, bq = sb + SM_BAR;
    bsync<1, 384>();
    PT(0);
#define XLOAD() if (elect()) { \
        const int sg = u == 0 ? s + LAG + 2 : s + LAG; \
        const bool dx = sg >= 0 && sg < NSEG; \
        mbar_expect(bq + BAR_XA, dx ? 4096 : 0); \
        if (dx) tma3d(sb + SM_X + u * 4096, tmx, bq + BAR_XA, 0, sg * 32 + ((j + u) & 3) * 8, j * 4); \
    }
    uint32_t t0;
    if (MAIN && SW(u) == 1 && s > 0) xsend(u, h, j, xlo, xhi, s - 1, 0, 6144);
    XLOAD();
    asm volatile("cp.async.bulk.wait_group 0;" ::: "memory");
    if (MAIN) barv<8, 384>();
    asm volatile("fence.proxy.async.shared::cta;" ::: "memory");
    PDUMP();
    PT(1);
    if (MAIN) {
        const uint32_t ctag = ((s >> 1) & 1) ^ 1;
        const uint32_t av = xlo + ((s & 1) * 32 + h) * 8192 + u * 512;
        bsync<3, 384>();
        delay_until(clk(), DLY_V);
        PT(4);
        int it = 0;
        bool bad;
        do {
            const uint4 d1 = ldg4<XO_CV>(av + (j ^ 1) * 2048 + l16, xhi);
            const uint4 d2 = ldg4<XO_CV>(av + (j ^ 2) * 2048 + l16, xhi);
            const uint4 d3 = ldg4<XO_CV>(av + (j ^ 3) * 2048 + l16, xhi);
            bad = any_bad(or3(tagx2(d1.x, d1.z, ctag), tagx2(d2.x, d2.z, ctag), tagx2(d3.x, d3.z, ctag)));
            sts128(sb + SM_VS + u * 512 + l16, hadd2(hadd2(d1.x, d2.x), d3.x), hadd2(hadd2(d1.y, d2.y), d3.y), hadd2(hadd2(d1.z, d2.z), d3.z),
                   hadd2(hadd2(d1.w, d2.w), d3.w));
            REFRESH();
            if (++it > SPIN_LIMIT) die(it);
        } while (bad);
        PC(26, it - 1);
    } else {
        if (u == 0) stg2<XO_FL>(xlo + ((s + LAG + 2) * 128 + h * 4 + j) * 32, xhi, 0, 0);
        if (s == -LAG - 2) {
#pragma unroll 1
            for (int e = 0; e < 4; e++) sts128(sb + SM_TR + 4096 + e * 2048 + u * 512 + l16, 0, 0, 0, 0);
        }
        if (s == -1) {
#pragma unroll 1
            for (int e = 0; e < 2; e++) {
                const uint32_t d = e * 128 + u * 32 + (l16 >> 4);
                const unsigned short* m0 = (const unsigned short*)mem0 + j * 256 + d;
                uint32_t v[4];
#pragma unroll
                for (int i = 0; i < 4; i++) v[i] = (uint32_t)m0[(2 * i) * DM] | ((uint32_t)m0[(2 * i + 1) * DM] << 16);
                sts128(sb + SM_MEMT + d * 16, v[0], v[1], v[2], v[3]);
            }
        }
        int it = 0;
        while (__any_sync(0xFFFFFFFFu, ldg2<XO_FL>(xlo + ((s + LAG + 2) * 128 + h * 4) * 32 + ((l16 & 0x30) << 1), xhi).x != 0))
            if (++it > SPIN_LIMIT) die(it);
    }
    PT(5);
    t0 = clk();
    mbar_wait(bq + BAR_XA, (s + LAG + 2) & 1);
    PT(6);
    barv<5, 384>();
    if (MAIN) {
        delay_until(t0, ((SD >> (4 * u)) & 15) * 100);
        if (SW(u) == 2) xsend(u, h, j, xlo, xhi, s, 0, 6144);
    } else xsend(u, h, j, xlo, xhi, s, 0, 6144);
    if (s >= -1 && s + 1 < NSEG && elect()) {
        const uint32_t o = u == 0 ? 0 : 2048;
        mbar_expect(bq + BAR_KV, 6144 - o);
        bulk_g2s(sb + SM_KV + ((s + 1) & 1) * 18432 + u * 4096 + o, xlo + XO_XG + ((((s + 1) & 7) * 32 + h) * 4 + ((j + u) & 3)) * 6144 + o, xhi, 6144 - o, bq + BAR_KV);
    }
    if (!MAIN) asm volatile("cp.async.bulk.wait_group 0;" ::: "memory");
    PT(7);
    REFRESH();
    if (MAIN) {
        const uint32_t rb = ((j & 1) * 32 + h) * 8192;
        const uint32_t a = xlo + rb + ((par(rb) ^ (j >> 1)) << 12) + u * 1024 + (l16 >> 2);
        const uint32_t rtag = (s & 1) ^ 1;
        bsync<7, 384>();
        t0 = clk();
        PT(9);
        if (s < NSEG - 1) {
            const uint32_t ab = xlo + (j & 1) * 8192 + ((par(XO_B + (j & 1) * 8192) ^ (j >> 1)) << 12);
            delay_until(t0, DLY_R);
            PT(8);
            int it = 0;
            bool bad;
            float lo, hi;
            do {
                const uint32_t v0 = ldg1<XO_R>(a, xhi), v1 = ldg1<XO_R + 128>(a, xhi), v2 = ldg1<XO_R + 256>(a, xhi), v3 = ldg1<XO_R + 384>(a, xhi);
                const uint32_t v4 = ldg1<XO_R + 512>(a, xhi), v5 = ldg1<XO_R + 640>(a, xhi), v6 = ldg1<XO_R + 768>(a, xhi), v7 = ldg1<XO_R + 896>(a, xhi);
                SF();
                if (it == 0 && SW(u) == 3) xsend(u, h, j, xlo, xhi, s, 0, 6144);
                if (++it > SPIN_LIMIT) die(it);
                const uint32_t a0 = hadd2(hadd2(v0, v1), hadd2(v2, v3)), a1 = hadd2(hadd2(v4, v5), hadd2(v6, v7));
                lo = lo_f(a0) + lo_f(a1);
                hi = hi_f(a0) + hi_f(a1);
                sts64(sb + SM_RS + u * 256 + (l16 >> 1), __float_as_uint(lo), __float_as_uint(hi));
                bad = (__ballot_sync(0xFFFFFFFFu, ((or3(tagx2(v0, v1, rtag), tagx2(v2, v3, rtag), tagx2(v4, v5, rtag)) | tagx2(v6, v7, rtag)) & 1) != 0) & 0x11111111u) != 0;
            } while (bad);
            PT(12);
            bsync<2, 128>();
            if (u == 0) {
                const uint2 p1 = lds64(sb + SM_RS + 256 + (l16 >> 1)), p2 = lds64(sb + SM_RS + 512 + (l16 >> 1)), p3 = lds64(sb + SM_RS + 768 + (l16 >> 1));
                const uint32_t m = (l16 & 0x30) ? 0u : 1u;
                lo = (lo + __uint_as_float(p1.x)) + (__uint_as_float(p2.x) + __uint_as_float(p3.x));
                hi = (hi + __uint_as_float(p1.y)) + (__uint_as_float(p2.y) + __uint_as_float(p3.y));
                stg1<XO_B>(ab + h * 128 + (l16 >> 2), xhi, (pack2(lo, hi) & ~m) | (s & m));
            }
            t0 = clk();
            PT(10);
            PC(22, it);
            mbar_wait(bq + BAR_KV, (s + 1) & 1);
            PT(11);
            delay_until(t0, u == 0 ? DLY_B - 50 : DLY_B);
            PT(13);
            it = 0;
            do {
                const uint4 m0 = ldg4<XO_B>(ab + u * 1024 + l16, xhi), m1 = ldg4<XO_B + 512>(ab + u * 1024 + l16, xhi);
                SF();
                if (it == 0 && SW(u) == 4) xsend(u, h, j, xlo, xhi, s, 0, 6144);
                if (++it > SPIN_LIMIT) die(it);
                bad = any_bad(tagx2(m0.x, m1.x, s));
                stsm4(sb + SM_MEMT + u * 1024 + l16, m0.x, m0.y, m0.z, m0.w);
                stsm4(sb + SM_MEMT + u * 1024 + 512 + l16, m1.x, m1.y, m1.z, m1.w);
            } while (bad);
            PC(23, it);
        }
    } else {
        if (s == -1) mbar_wait(bq + BAR_KV, 0);
    }
    PT(15);
}

__global__ void __cluster_dims__(2, 1, 1) __launch_bounds__(384, 1)
chain_kernel(const __grid_constant__ CUtensorMap tmq, const __grid_constant__ CUtensorMap tmk,
             const __grid_constant__ CUtensorMap tmv, const __grid_constant__ CUtensorMap tmo,
             const __grid_constant__ CUtensorMap tmx, const bf16* __restrict__ mem0, const bf16* __restrict__ xg,
             uint32_t xlo, uint32_t xhi, uint32_t zero, int nseg) {
    extern __shared__ __align__(1024) uint8_t smem[];
    if ((smem_u32(smem) & 0xFFFFFF) != SB0) die(1 << 23);
    asm volatile("griddepcontrol.launch_dependents;" ::: "memory");
    const uint32_t w = __reduce_max_sync(0xFFFFFFFFu, threadIdx.x >> 5);
    const uint32_t swin = (uint32_t)((uint64_t)smem >> 32);
    const uint32_t rk = smem_u32(smem) & 0x1000000;
    const uint32_t sb = __reduce_max_sync(0xFFFFFFFFu, smem_u32(smem));
    const uint32_t bq = sb + SM_BAR, bk = bq + 8, bv = bq + 16, bo = bq + 24;
    uint32_t l16 = __shfl_sync(0xFFFFFFFFu, (threadIdx.x & 31) * 16, threadIdx.x & 31);
    if (threadIdx.x == 0) {
        mbar_init(bq, 1); mbar_init(bk, 1); mbar_init(bv, 1); mbar_init(bo, 2);
        mbar_init(bq + BAR_XA, 4); mbar_init(bq + BAR_KV, 4);
        asm volatile("fence.mbarrier_init.release.cluster;" ::: "memory");
        asm volatile("fence.proxy.async.shared::cta;" ::: "memory");
    }
    if (rk == 0) {
        if (w < 2 && l16 == 0) sts32(sb + SM_ROLE + w * 4, probe(xlo + XO_PB + w * 4096 + blockIdx.x * 16, xhi));
        __syncthreads();
        if (threadIdx.x == 0) {
            uint32_t side = (lds32(sb + SM_ROLE) < lds32(sb + SM_ROLE + 4) ? 0u : 1u) ^ par(XO_PB);
            uint32_t* tk = (uint32_t*)(((uint64_t)xhi << 32) | (xlo + XO_TK));
            uint32_t t = atomicAdd(tk + side, 1u) + 1;
            if (t >= 32) {
                uint2 c;
                int it = 0;
                do {
                    c = ldg2<XO_TK>(xlo, xhi);
                    if (++it > SPIN_LIMIT) die(it);
                } while (c.x + c.y + 2 != gridDim.x / 2);
                t += (side ? c.x : c.y) + 1 - 32;
                side ^= 1;
            }
            sts32(sb + SM_ROLE + 8, t * 4 + side * 2);
        }
    }
    __syncthreads();
    asm volatile("barrier.cluster.arrive.release.aligned;\nbarrier.cluster.wait.acquire.aligned;" ::: "memory");
    uint32_t role;
    asm volatile("ld.shared::cluster.u32 %0, [%1];" : "=r"(role) : "r"(SB0 + SM_ROLE + 8) : "memory");
    role = __reduce_max_sync(0xFFFFFFFFu, role) + (rk >> 24);
    asm volatile("barrier.cluster.arrive.release.aligned;\nbarrier.cluster.wait.acquire.aligned;" ::: "memory");
    if (role >= 128) return;
    const uint32_t h = role >> 2, j = role & 3;

    if (w >= 8) {
        asm volatile("setmaxnreg.dec.sync.aligned.u32 24;");
        if (w == 8) {
            if (elect()) {
                mbar_expect(bq, 65536);
                tma2d(sb + SM_STA, &tmq, bq, h * 128, j * 256);
                tma2d(sb + SM_STA + 32768, &tmq, bq, h * 128 + 64, j * 256);
                mbar_expect(bk, 65536);
                tma2d(sb + SM_STB, &tmk, bk, h * 128, j * 256);
                tma2d(sb + SM_STB + 32768, &tmk, bk, h * 128 + 64, j * 256);
                mbar_expect(bv, (16 - NA + NA1) * 4096);
#pragma unroll 1
                for (int i = 0; i < 32; i++) {
                    const int ks = i >> 1, g = i & 1;
                    if (ks < NA1 || ks >= NA)
                        tma2d((ks < NA ? sb + SM_STC + g * (NA1 * 2048) + ks * 2048 : sb + SM_WV + g * WV_BOX + (ks - NA) * 2048), &tmv, bv, h * 128 + g * 64, j * 256 + ks * 16);
                }
                mbar_expect(bo, 4 * WO_BOX);
#pragma unroll 1
                for (int i = 2 * NB; i < 32; i++) {
                    const int ks = i >> 2, g = i & 3;
                    tma2d(sb + SM_WO + g * WO_BOX + (ks - NB / 2) * 2048, &tmo, bo, j * 256 + g * 64, h * 128 + ks * 16);
                }
            }
        }
        bsync<9, 384>();
        if (w == 8) {
            if (elect()) {
                mbar_expect(bo, (NB + NA - NA1) * 4096);
#pragma unroll 1
                for (int i = 2 * NA1; i < 2 * NA; i++) {
                    const int ks = i >> 1, g = i & 1;
                    tma2d(sb + SM_STA + NB * 4096 + g * ((NA - NA1) * 2048) + (ks - NA1) * 2048, &tmv, bo, h * 128 + g * 64, j * 256 + ks * 16);
                }
#pragma unroll 1
                for (int i = 0; i < 2 * NB; i++) {
                    const int ks = i >> 2, g = i & 3;
                    tma2d(sb + SM_STA + g * (NB * 1024) + ks * 2048, &tmo, bo, j * 256 + g * 64, h * 128 + ks * 16);
                }
                asm volatile("cp.async.bulk.prefetch.L2.global [%0], %1;" ::"l"((const char*)xg + role * 32768), "r"(32768) : "memory");
            }
        }
#pragma unroll 1
        for (int s = -LAG - 2; s < 0; s++) helper_step<false>(w, h, j, l16, xlo, xhi, zero, s, &tmx, mem0);
#pragma unroll 1
        for (int s = 0; s < nseg; s++) helper_step<true>(w, h, j, l16, xlo, xhi, zero, s, &tmx, mem0);
    } else {
        asm volatile("setmaxnreg.inc.sync.aligned.u32 240;");
        uint32_t Wq[16][4], Wk[16][4], Wv[NA][4], Wo[NB > 0 ? NB : 1][4];
        uint32_t t16, KA, KB, KC, KD;
        {
            const uint32_t lane = l16 >> 4, g = lane >> 2, t = lane & 3;
            const uint32_t rw = (((lane >> 4) & 1) * 8 + (lane & 7)) * 128u;
            const uint32_t off = rw + ((((w & 3) * 2 + ((lane >> 3) & 1)) ^ (lane & 7)) << 4);
            const uint32_t offo = rw + ((((w & 1) * 4 + ((lane >> 3) & 1)) ^ (lane & 7)) << 4);
            const uint32_t r = 2 * (t & 1) + (g >> 2);
            const uint32_t mk0 = t < 2 ? 0 : (r == 0 ? 2 * g > w : j + r < 4), mk1 = t < 2 ? 0 : (r == 0 ? 2 * g + 1 > w : j + r < 4);
            t16 = __shfl_sync(0xFFFFFFFFu, w * 512 + l16, lane);
            KA = __shfl_sync(0xFFFFFFFFu, (w * 512 + t * 64 + g * 8) | ((w * 512 + (g & 1) * 256 + (g >> 1) * 64 + t * 16) << 16), lane);
            KB = __shfl_sync(0xFFFFFFFFu, ((w >> 2) * WV_BOX + off) | mk0 | (mk1 << 1) |
                                              ((w * 256 + (g >> 2) * 4096 + (g & 3) * 64 + t * 16) << 16), lane);
            KC = __shfl_sync(0xFFFFFFFFu, ((lane & 7) * 1280 + (lane >> 3) * 128 + ((w ^ (lane & 7)) << 4)) | ((t * 64 + g * 8) << 24), lane);
            KD = __shfl_sync(0xFFFFFFFFu, ((w >> 1) * WO_BOX + offo) | (((lane & 7) * 208 + (lane >> 3) * 16) << 16), lane);
            const uint32_t rb = ((j & 1) * 32 + w * 4 + (lane >> 3)) * 8192;
            KC |= (par(rb) ^ (j >> 1)) << 16;
            mbar_wait(bq, 0);
#pragma unroll
            for (int ks = 0; ks < 16; ks++) ldsm4t(Wq[ks], sb + SM_STA + (w >> 2) * 32768 + off + ks * 2048);
            asm volatile("fence.proxy.async.shared::cta;" ::: "memory");
            barv<9, 384>();
            mbar_wait(bk, 0);
#pragma unroll
            for (int ks = 0; ks < 16; ks++) ldsm4t(Wk[ks], sb + SM_STB + (w >> 2) * 32768 + off + ks * 2048);
            mbar_wait(bv, 0);
#pragma unroll
            for (int ks = 0; ks < NA1; ks++) ldsm4t(Wv[ks], sb + SM_STC + (w >> 2) * (NA1 * 2048) + off + ks * 2048);
            mbar_wait(bo, 0);
#pragma unroll
            for (int ks = NA1; ks < NA; ks++) ldsm4t(Wv[ks], sb + SM_STA + NB * 4096 + (w >> 2) * ((NA - NA1) * 2048) + off + (ks - NA1) * 2048);
#pragma unroll
            for (int i = 0; i < NB; i++) ldsm4t(Wo[i], sb + SM_STA + (w >> 1) * (NB * 1024) + (offo ^ ((i & 1) << 5)) + (i >> 1) * 2048);
            asm volatile("fence.proxy.async.shared::cta;" ::: "memory");
        }
        const uint32_t ONES = 0x3F803F80u;
#define OPQALL() { OPQ(t16); OPQ(KA); OPQ(KB); OPQ(KC); OPQ(KD); }
#pragma unroll 1
        for (int s = -LAG - 2; s < 0; s++) {
            bsync<1, 384>();
            bsync<5, 384>();
            xproj(sb, w, t16 >> 1, KA, KB, s, Wq, Wk, Wv);
            OPQALL();
        }
        const uint32_t w512 = w * 512;
        const uint32_t cb0 = (h >> 1) * 32768 + (j & 1) * 16384 + (h & 1) * 8192;
        const uint32_t cb = xlo + cb0 + ((par(cb0) ^ (j >> 1) ^ CFAR) << 12);
        const uint32_t uox = xlo + XO_OX + (h * 2 + (w >> 2)) * 16384 + j * 1024 + (w & 3) * 256 - w * 128;
#pragma unroll 1
        for (int s = 0; s < nseg; s++) {
            const uint32_t ctag = ((s >> 1) & 1) ^ 1;
            const uint32_t hb = cb ^ ((s & 1) * 0x81000);
            uint32_t ov0, ov1;
            uint4 c1, c2, c3;
            {
                uint32_t acw = hb + (KA & 0xFFFF), ahi = xhi, tg = ctag;
                OPQ(acw); OPQ(ahi); OPQ(tg);
                SF();
                bsync<1, 384>();
                PT(0);
                uint32_t b[8][4];
#pragma unroll
                for (int p = 0; p < 8; p++) {
                    const int pp = p < 2 ? p : p ^ 1;
                    ldsm4t(b[pp], sb + SM_MEMT - w512 + t16 + pp * 512);
                    if (p < 7) MF();
                }
                float q[4], k[4];
#pragma unroll
                for (int ks = 0; ks < 16; ks++) {
                    const uint32_t b0 = b[ks >> 1][(ks & 1) * 2], b1 = b[ks >> 1][(ks & 1) * 2 + 1];
                    if (ks == 0) {
                        mma16z(q, Wq[0][0], Wq[0][1], Wq[0][2], Wq[0][3], b0, b1);
                        mma16z(k, Wk[0][0], Wk[0][1], Wk[0][2], Wk[0][3], b0, b1);
                    } else {
                        mma16(q, Wq[ks][0], Wq[ks][1], Wq[ks][2], Wq[ks][3], b0, b1);
                        mma16(k, Wk[ks][0], Wk[ks][1], Wk[ks][2], Wk[ks][3], b0, b1);
                    }
                }
                const uint32_t oq0 = settag(pack2(q[0], q[2]), tg), oq1 = settag(pack2(q[1], q[3]), tg);
                const uint32_t ok0 = pack2(k[0], k[2]), ok1 = pack2(k[1], k[3]);
                stg2<XO_CQK>(acw, ahi, oq0, ok0);
                stg2<XO_CQK + 256>(acw, ahi, oq1, ok1);
                SF();
                PT(1);
                const uint32_t aWv = sb + SM_WV + (KB & 0xFFF0);
                uint32_t wv[16 - NA > 0 ? 16 - NA : 1][4];
                asm volatile("{\n.reg .b64 a;\nmov.b64 a, {%0,%1};\nst.v2.u32 [a], {%2,%3};\nst.v2.u32 [a+256], {%4,%5};\n}"
                             ::"r"((acw & 0xFFF) + (sb ^ 0x1000000) + SM_TR + 4096 + (s & 1) * 4096), "r"(swin), "r"(oq0), "r"(ok0), "r"(oq1), "r"(ok1) : "memory");
                sts64(sb + SM_TR + (acw & 0xFFF), oq0, ok0);
                sts64(sb + SM_TR + (acw & 0xFFF) + 256, oq1, ok1);
#define VPF 2
#pragma unroll
                for (int n = 0; n < VPF; n++)
                    if (n < 16 - NA) ldsm4t(wv[n < 16 - NA ? n : 0], aWv + n * 2048);
#pragma unroll
                for (int ks = 0; ks < 16; ks++) {
                    const uint32_t* a = ks < NA ? Wv[ks < NA ? ks : 0] : wv[ks < NA ? 0 : ks - NA];
                    const uint32_t b0 = b[ks >> 1][(ks & 1) * 2], b1 = b[ks >> 1][(ks & 1) * 2 + 1];
                    if (ks == 0) mma16z(q, a[0], a[1], a[2], a[3], b0, b1);
                    else if (ks == 1) mma16z(k, a[0], a[1], a[2], a[3], b0, b1);
                    else if (ks & 1) mma16(k, a[0], a[1], a[2], a[3], b0, b1);
                    else mma16(q, a[0], a[1], a[2], a[3], b0, b1);
                    if ((ks & 3) == 3) {
                        const int f0 = ks - 3 > NA ? ks - 3 - NA : 0, f1 = ks + 1 > NA ? ks + 1 - NA : 0;
                        const int n0 = VPF + (ks - 3) / 2 + f0, n1 = VPF + (ks + 1) / 2 + f1;
                        if (n0 < 16 - NA) SF();
#pragma unroll
                        for (int n = 0; n < 16 - NA; n++)
                            if (n >= n0 && n < n1) ldsm4t(wv[n < 16 - NA ? n : 0], aWv + n * 2048);
                    }
                }
                c2 = ldg4<XO_CQK>((hb ^ 0x1000) + (KA >> 16), xhi);
                c3 = ldg4<XO_CQK>((hb ^ 0x5000) + (KA >> 16), xhi);
                ov0 = pack2(q[0] + k[0], q[1] + k[1]);
                ov1 = pack2(q[2] + k[2], q[3] + k[3]);
                bsync<8, 384>();
                stg2<XO_CV>(xlo + (((s & 1) * 32 + h) * 4 + j) * 2048 + (t16 >> 1), xhi, settag(ov0, tg), ov1);
            }
            SF();
            PT(2);
            if (s >= 1) pv_x(sb, t16 >> 1, sb + SM_P + (KD >> 16), uox + (t16 >> 2), xhi, s - 1);
            barv<3, 384>();
            PDUMP();
            {
                const uint32_t a0 = sb + SM_KV + (s & 1) * 18432;
                const uint4 qq = lds128(a0 + w * 256 + ((KA >> 16) & 0xFF));
                const uint4 k0 = lds128(a0 + 2048 + (KB >> 16)), k1 = lds128(a0 + 10240 + (KB >> 16));
                const uint32_t ka[4] = {k0.x, k0.y, k0.z, k0.w}, kb[4] = {k1.x, k1.y, k1.z, k1.w};
                const uint2 qx = (t16 & 64) ? make_uint2(qq.y, qq.w) : make_uint2(qq.x, qq.z);
                const uint4 c0 = lds128(sb + SM_TR + (KA >> 16));
                c1 = lds128(sb + SM_TR + 4096 + (s & 1) * 4096 + (KA >> 16));
                const uint32_t aSp = sb + SM_SP + (KC & 0xFFFF);
                {
                    float sa[4], sb_[4];
                    mma16z(sa, ka[0], ka[1], ka[2], ka[3], qx.x, qx.y);
                    mma16z(sb_, kb[0], kb[1], kb[2], kb[3], qx.x, qx.y);
                    stsm4t(aSp + 512, pack2(sa[0], sa[1]), pack2(sa[2], sa[3]), pack2(sb_[0], sb_[1]), pack2(sb_[2], sb_[3]));
                }
                uint32_t qx0 = qx.x, qx1 = qx.y;
                OPQ(qx0); OPQ(qx1);
                PT(3);
                SF();
                int it = 0;
                while (true) {
                    const uint32_t qA = hadd2(hadd2(c0.x, c1.x), hadd2(c2.x, c3.x)), qB = hadd2(hadd2(c0.z, c1.z), hadd2(c2.z, c3.z));
                    float sa[4], sb_[4], sc[4];
                    mma16z(sa, ka[0], ka[1], ka[2], ka[3], qA, qB);
                    mma16z(sb_, kb[0], kb[1], kb[2], kb[3], qA, qB);
                    const uint32_t kA = hadd2(hadd2(c0.y, c1.y), hadd2(c2.y, c3.y)), kB = hadd2(hadd2(c0.w, c1.w), hadd2(c2.w, c3.w));
                    mma16z(sc, qA, qx0, qB, qx1, kA, kB);
                    const bool bad = any_bad(or3(tagx2(c1.x, c1.z, ctag), tagx2(c2.x, c2.z, ctag), tagx2(c3.x, c3.z, ctag)));
                    stsm4t(aSp, pack2(sa[0], sa[1]), pack2(sa[2], sa[3]), pack2(sb_[0], sb_[1]), pack2(sb_[2], sb_[3]));
                    stsm2(aSp + 1024, pack2(sc[0], sc[1]), pack2(sc[2], sc[3]));
                    if (__builtin_expect(!bad, 1)) break;
                    OPQ(KA);
                    c1 = lds128(sb + SM_TR + 4096 + (s & 1) * 4096 + (KA >> 16));
                    c2 = ldg4<XO_CQK>((hb ^ 0x1000) + (KA >> 16), xhi);
                    c3 = ldg4<XO_CQK>((hb ^ 0x5000) + (KA >> 16), xhi);
                    if (++it > SPIN_LIMIT) die(it);
                }
                PC(25, it);
                PT(4);
                bsync<4, 256>();
                uint2 v0, v1, v2, v3;
                uint32_t wo[16 - NB][4];
                const uint32_t t8 = t16 >> 1;
                const uint32_t aWo = sb + SM_WO + (KD & 0xFFFF), aWo1 = sb + SM_WO + ((KD & 0xFFFF) ^ 32);
                {
                    uint32_t am[4], ax[4], a4[2];
                    const uint32_t aSr = sb + SM_SP + (t16 >> 9) * 768 + t16;
                    ldsm4t(am, aSr);
                    ldsm4t(ax, aSr + 512);
                    ldsm2t(a4, aSr + 1024);
                    MF();
                    v0 = lds64(a0 + 4096 + t8); v1 = lds64(a0 + 8192 + t8);
                    v2 = lds64(a0 + 12288 + t8); v3 = lds64(a0 + 16384 + t8);
                    const uint32_t se = (t16 & 128) ? 0u : ONES, so = se ^ ONES;
                    float hm[4], hx[4], h4[4];
                    mma16z(hm, am[0], am[1], am[2], am[3], se, so);
                    mma16z(hx, ax[0], ax[1], ax[2], ax[3], se, so);
                    mma8z(h4, a4[0], a4[1], ONES);
                    const bool hi = (t16 & 32) != 0;
                    float s0 = hi ? hx[0] : hm[0], s1 = hi ? hx[2] : hm[2];
                    const float s2 = hi ? h4[2] : h4[0];
                    s0 = (KB & 1) ? -1.0e9f * 11.313708499f : s0;
                    s1 = (KB & 2) ? -1.0e9f * 11.313708499f : s1;
                    int mi = __float_as_int(fmaxf(fmaxf(s0, s2), s1));
                    mi ^= (mi >> 31) & 0x7FFFFFFF;
                    const int mm = __reduce_max_sync(0xFFFFFFFFu, hi ? (int)0x80000000 : mi), mx = __reduce_max_sync(0xFFFFFFFFu, hi ? mi : (int)0x80000000);
#pragma unroll
                    for (int i = 0; i < NPF; i++) ldsm4t(wo[i], ((i & 1) ? aWo1 : aWo) + (i >> 1) * 2048);
                    MF();
                    mi = hi ? mx : mm;
                    mi ^= (mi >> 31) & 0x7FFFFFFF;
                    const float c2_ = 0.08838834764831845f * 1.4426950408889634f;
                    const float mc = __int_as_float(mi) * c2_;
                    const float e0 = ex2(fmaf(s0, c2_, -mc)), e1 = ex2(fmaf(s1, c2_, -mc)), e2 = ex2(fmaf(s2, c2_, -mc));
                    sts32(sb + SM_P + w * 208 + (KC >> 25), pack2(e0, e1));
                    sts16(sb + SM_P + w * 208 + 128 + (KC >> 26), pack2(e2, e2));
                }
                const uint32_t aPr = sb + SM_P + (KD >> 16);
                PT(5);
                bsync<5, 384>();
                uint32_t pm[4];
                ldsm4(pm, aPr);
                const uint2 vs = lds64(sb + SM_VS + t8);
                const uint32_t p4 = ldsm1(aPr + 128);
                const uint32_t vm0 = hadd2(ov0, vs.x), vm1 = hadd2(ov1, vs.y);
                float oa[4], ob[4], dn[4];
                mma16z(oa, v0.x, v0.y, v1.x, v1.y, pm[0], pm[1]);
                mma16z(ob, v2.x, v2.y, v3.x, v3.y, pm[2], pm[3]);
                mma8(oa, vm0, vm1, p4);
                stsm2(sb + SM_OT - w * 256 + t16, pack2(oa[0] + ob[0], oa[1] + ob[1]), pack2(oa[2] + ob[2], oa[3] + ob[3]));
                PT(6);
                bsync<6, 256>();
                SF();
                uint32_t b[4][4];
                mma16z(dn, ONES, ONES, ONES, ONES, pm[0], pm[1]);
                ldsm4t(b[0], sb + SM_OT - w512 + t16);
                ldsm4t(b[1], sb + SM_OT - w512 + t16 + 512);
                MF();
                sts64(sb + SM_VM + t8, vm0, vm1);
                mma16(dn, ONES, ONES, ONES, ONES, pm[2], pm[3]);
                mma8(dn, ONES, ONES, p4);
                SF();
                const float r0 = rcp(dn[0]), r1 = rcp(dn[1]);
                uint32_t ar = xlo + (j & 1) * 262144 + h * 128 + (t16 >> 7) * 8064 + t16 + ((KC >> 4) & 0x1000), ahi = xhi, tg = (s & 1) ^ 1;
                float r[2][4];
#pragma unroll
                for (int pp = 0; pp < 4; pp++) {
                    const int f0 = 4 * pp - NB > 0 ? 4 * pp - NB : 0, fp = 4 * (pp - 1) - NB > 0 ? 4 * (pp - 1) - NB : 0;
                    const int n0 = pp == 0 ? NPF : NPF + WPF + fp, n1 = NPF + WPF + f0;
                    if (pp >= 1 && pp <= 2) ldsm4t(b[pp + 1], sb + SM_OT - w512 + t16 + (pp + 1) * 512);
#pragma unroll
                    for (int n = 0; n < 16 - NB; n++)
                        if (n >= n0 && (pp == 3 || n < n1)) ldsm4t(wo[n < 16 - NB ? n : 0], ((n & 1) ? aWo1 : aWo) + (n >> 1) * 2048);
                    if (pp == 2) { OPQ(ar); OPQ(ahi); OPQ(tg); }
#pragma unroll
                    for (int e = 0; e < 2; e++)
#pragma unroll
                        for (int mt = 0; mt < 2; mt++) {
                            const int i = (pp * 2 + e) * 2 + mt;
                            const uint32_t* a = i < NB ? Wo[i < NB ? i : 0] : wo[i < NB ? 0 : i - NB];
                            if (i < 2) mma16z(r[mt], a[0], a[1], a[2], a[3], b[pp][2 * e], b[pp][2 * e + 1]);
                            else mma16(r[mt], a[0], a[1], a[2], a[3], b[pp][2 * e], b[pp][2 * e + 1]);
                        }
                    if (pp < 3) SF();
                }
                stg4<XO_R>(ar, ahi, settag(pack2(r[0][0] * r0, r[0][1] * r1), tg),
                           pack2(r[0][2] * r0, r[0][3] * r1), pack2(r[1][0] * r0, r[1][1] * r1), pack2(r[1][2] * r0, r[1][3] * r1));
                barv<7, 384>();
            }
            PT(10);
            if (s + LAG < NSEG) xproj(sb, w, t16 >> 1, KA, KB, s, Wq, Wk, Wv);
            OPQALL();
            PT(15);
        }
        pv_x(sb, t16 >> 1, sb + SM_P + (KD >> 16), uox + (t16 >> 2), xhi, NSEG - 1);
    }
}

#define G2_STAGES 6
#define G2_STAGE_BYTES 32768
DEVI void wg_ss128t(float (&d)[64], uint64_t da, uint64_t db, int sc) {
    asm volatile("{\n.reg .pred p;\nsetp.ne.b32 p, %66, 0;\n"
                 "wgmma.mma_async.sync.aligned.m64n128k16.f32.bf16.bf16 "
                 "{%0,%1,%2,%3,%4,%5,%6,%7,%8,%9,%10,%11,%12,%13,%14,%15,%16,%17,%18,%19,%20,%21,%22,%23,%24,%25,%26,%27,%28,%29,%30,%31,"
                 "%32,%33,%34,%35,%36,%37,%38,%39,%40,%41,%42,%43,%44,%45,%46,%47,%48,%49,%50,%51,%52,%53,%54,%55,%56,%57,%58,%59,%60,%61,%62,%63}, "
                 "%64, %65, p, 1, 1, 1, 1;\n}\n"
                 : "+f"(d[0]), "+f"(d[1]), "+f"(d[2]), "+f"(d[3]), "+f"(d[4]), "+f"(d[5]), "+f"(d[6]), "+f"(d[7]),
                   "+f"(d[8]), "+f"(d[9]), "+f"(d[10]), "+f"(d[11]), "+f"(d[12]), "+f"(d[13]), "+f"(d[14]), "+f"(d[15]),
                   "+f"(d[16]), "+f"(d[17]), "+f"(d[18]), "+f"(d[19]), "+f"(d[20]), "+f"(d[21]), "+f"(d[22]), "+f"(d[23]),
                   "+f"(d[24]), "+f"(d[25]), "+f"(d[26]), "+f"(d[27]), "+f"(d[28]), "+f"(d[29]), "+f"(d[30]), "+f"(d[31]),
                   "+f"(d[32]), "+f"(d[33]), "+f"(d[34]), "+f"(d[35]), "+f"(d[36]), "+f"(d[37]), "+f"(d[38]), "+f"(d[39]),
                   "+f"(d[40]), "+f"(d[41]), "+f"(d[42]), "+f"(d[43]), "+f"(d[44]), "+f"(d[45]), "+f"(d[46]), "+f"(d[47]),
                   "+f"(d[48]), "+f"(d[49]), "+f"(d[50]), "+f"(d[51]), "+f"(d[52]), "+f"(d[53]), "+f"(d[54]), "+f"(d[55]),
                   "+f"(d[56]), "+f"(d[57]), "+f"(d[58]), "+f"(d[59]), "+f"(d[60]), "+f"(d[61]), "+f"(d[62]), "+f"(d[63])
                 : "l"(da), "l"(db), "r"(sc));
}

DEVI void gemm2(int tile, uint32_t xlo, uint32_t xhi, const CUtensorMap& tmb, bf16* __restrict__ out) {
    const uint32_t sb = SB0;
    const uint32_t bars = sb + G2_STAGES * G2_STAGE_BYTES;
    const int tid = threadIdx.x, lane = tid & 31;
    const int w = __shfl_sync(0xFFFFFFFFu, tid >> 5, 0);
    const int bm = tile >> 3, bn = tile & 7;
    if (tid == 0) {
        for (int i = 0; i < G2_STAGES; i++) { mbar_init(bars + i * 8, 1); mbar_init(bars + (G2_STAGES + i) * 8, 2); }
        asm volatile("fence.mbarrier_init.release.cluster;" ::: "memory");
        asm volatile("fence.proxy.async.shared::cta;" ::: "memory");
    }
    __syncthreads();
    const int NK = HD / 64;
    if (w == 8) {
        if (lane == 0) {
            for (int kb = 0; kb < G2_STAGES; kb++) {
                const uint32_t dst = sb + kb * G2_STAGE_BYTES;
                mbar_expect(bars + kb * 8, G2_STAGE_BYTES);
                tma2d(dst + 16384, &tmb, bars + kb * 8, bn * 128, kb * 64);
                tma2d(dst + 24576, &tmb, bars + kb * 8, bn * 128 + 64, kb * 64);
            }
            asm volatile("griddepcontrol.wait;" ::: "memory");
            for (int kb = 0; kb < G2_STAGES; kb++)
                bulk_g2s(sb + kb * G2_STAGE_BYTES, xlo + XO_OX + (bm * 64 + kb) * 16384, xhi, 16384, bars + kb * 8);
            int st = 0, ph = 0;
            for (int kb = G2_STAGES; kb < NK; kb++) {
                mbar_wait(bars + (G2_STAGES + st) * 8, ph);
                const uint32_t dst = sb + st * G2_STAGE_BYTES;
                mbar_expect(bars + st * 8, G2_STAGE_BYTES);
                bulk_g2s(dst, xlo + XO_OX + (bm * 64 + kb) * 16384, xhi, 16384, bars + st * 8);
                tma2d(dst + 16384, &tmb, bars + st * 8, bn * 128, kb * 64);
                tma2d(dst + 24576, &tmb, bars + st * 8, bn * 128 + 64, kb * 64);
                if (++st == G2_STAGES) { st = 0; ph ^= 1; }
            }
        }
    } else if (w < 8) {
        const int wg = w >> 2;
        float acc[64];
        int st = 0, ph = 0;
        for (int kb = 0; kb < NK; kb++) {
            mbar_wait(bars + st * 8, ph);
            const uint32_t base = sb + st * G2_STAGE_BYTES;
            const uint64_t da = mkdesc(base + wg * 8192, 128, 1024) & ~((uint64_t)3 << 62);
            const uint64_t db = mkdesc(base + 16384, 8192, 1024);
            wg_fence();
#pragma unroll
            for (int k = 0; k < 4; k++) wg_ss128t(acc, da + k * 16, db + k * 128, (kb | k) != 0);
            wg_commit();
            if (kb > 0) {
                wg_wait<1>();
                const int pst = st == 0 ? G2_STAGES - 1 : st - 1;
                if ((tid & 127) == 0) mbar_arrive(bars + (G2_STAGES + pst) * 8);
            }
            if (++st == G2_STAGES) { st = 0; ph ^= 1; }
        }
        wg_wait<0>();
        const int row = bm * 128 + wg * 64 + (w & 3) * 16 + (lane >> 2);
        bf16* o = out + (size_t)row * 2048 + bn * 128 + (lane & 3) * 2;
#pragma unroll
        for (int i = 0; i < 16; i++) {
            *(uint32_t*)(o + i * 8) = pack2(acc[4 * i], acc[4 * i + 1]);
            *(uint32_t*)(o + 8 * 2048 + i * 8) = pack2(acc[4 * i + 2], acc[4 * i + 3]);
        }
    }
}

#define D4(c, i) #c "f"(d[i]), #c "f"(d[i + 1]), #c "f"(d[i + 2]), #c "f"(d[i + 3])
template <int SC> DEVI void wg_rs128t(float (&d)[64], const uint32_t (&a)[4], uint64_t db) {
    if (SC) asm volatile("wgmma.mma_async.sync.aligned.m64n128k16.f32.bf16.bf16 "
        "{%0,%1,%2,%3,%4,%5,%6,%7,%8,%9,%10,%11,%12,%13,%14,%15,%16,%17,%18,%19,%20,%21,%22,%23,%24,%25,%26,%27,%28,%29,%30,%31,%32,%33,%34,%35,%36,%37,%38,%39,%40,%41,%42,%43,%44,%45,%46,%47,%48,%49,%50,%51,%52,%53,%54,%55,%56,%57,%58,%59,%60,%61,%62,%63}, "
        "{%64,%65,%66,%67}, %68, 1, 1, 1, 1;"
        : D4(+, 0), D4(+, 4), D4(+, 8), D4(+, 12), D4(+, 16), D4(+, 20), D4(+, 24), D4(+, 28), D4(+, 32), D4(+, 36), D4(+, 40), D4(+, 44), D4(+, 48), D4(+, 52), D4(+, 56), D4(+, 60) : "r"(a[0]), "r"(a[1]), "r"(a[2]), "r"(a[3]), "l"(db));
    else asm volatile("wgmma.mma_async.sync.aligned.m64n128k16.f32.bf16.bf16 "
        "{%0,%1,%2,%3,%4,%5,%6,%7,%8,%9,%10,%11,%12,%13,%14,%15,%16,%17,%18,%19,%20,%21,%22,%23,%24,%25,%26,%27,%28,%29,%30,%31,%32,%33,%34,%35,%36,%37,%38,%39,%40,%41,%42,%43,%44,%45,%46,%47,%48,%49,%50,%51,%52,%53,%54,%55,%56,%57,%58,%59,%60,%61,%62,%63}, "
        "{%64,%65,%66,%67}, %68, 0, 1, 1, 1;"
        : D4(=, 0), D4(=, 4), D4(=, 8), D4(=, 12), D4(=, 16), D4(=, 20), D4(=, 24), D4(=, 28), D4(=, 32), D4(=, 36), D4(=, 40), D4(=, 44), D4(=, 48), D4(=, 52), D4(=, 56), D4(=, 60) : "r"(a[0]), "r"(a[1]), "r"(a[2]), "r"(a[3]), "l"(db));
}
template <int SC> DEVI void wg_rs64t(float (&d)[32], const uint32_t (&a)[4], uint64_t db) {
    if (SC) asm volatile("wgmma.mma_async.sync.aligned.m64n64k16.f32.bf16.bf16 "
        "{%0,%1,%2,%3,%4,%5,%6,%7,%8,%9,%10,%11,%12,%13,%14,%15,%16,%17,%18,%19,%20,%21,%22,%23,%24,%25,%26,%27,%28,%29,%30,%31}, "
        "{%32,%33,%34,%35}, %36, 1, 1, 1, 1;"
        : D4(+, 0), D4(+, 4), D4(+, 8), D4(+, 12), D4(+, 16), D4(+, 20), D4(+, 24), D4(+, 28) : "r"(a[0]), "r"(a[1]), "r"(a[2]), "r"(a[3]), "l"(db));
    else asm volatile("wgmma.mma_async.sync.aligned.m64n64k16.f32.bf16.bf16 "
        "{%0,%1,%2,%3,%4,%5,%6,%7,%8,%9,%10,%11,%12,%13,%14,%15,%16,%17,%18,%19,%20,%21,%22,%23,%24,%25,%26,%27,%28,%29,%30,%31}, "
        "{%32,%33,%34,%35}, %36, 0, 1, 1, 1;"
        : D4(=, 0), D4(=, 4), D4(=, 8), D4(=, 12), D4(=, 16), D4(=, 20), D4(=, 24), D4(=, 28) : "r"(a[0]), "r"(a[1]), "r"(a[2]), "r"(a[3]), "l"(db));
}
template <int SC> DEVI void wg_rs40(float (&d)[20], const uint32_t (&a)[4], uint64_t db) {
    if (SC) asm volatile("wgmma.mma_async.sync.aligned.m64n40k16.f32.bf16.bf16 "
        "{%0,%1,%2,%3,%4,%5,%6,%7,%8,%9,%10,%11,%12,%13,%14,%15,%16,%17,%18,%19}, "
        "{%20,%21,%22,%23}, %24, 1, 1, 1, 0;"
        : D4(+, 0), D4(+, 4), D4(+, 8), D4(+, 12), D4(+, 16) : "r"(a[0]), "r"(a[1]), "r"(a[2]), "r"(a[3]), "l"(db));
    else asm volatile("wgmma.mma_async.sync.aligned.m64n40k16.f32.bf16.bf16 "
        "{%0,%1,%2,%3,%4,%5,%6,%7,%8,%9,%10,%11,%12,%13,%14,%15,%16,%17,%18,%19}, "
        "{%20,%21,%22,%23}, %24, 0, 1, 1, 0;"
        : D4(=, 0), D4(=, 4), D4(=, 8), D4(=, 12), D4(=, 16) : "r"(a[0]), "r"(a[1]), "r"(a[2]), "r"(a[3]), "l"(db));
}
template <int SC> DEVI void wg_rs8(float (&d)[4], const uint32_t (&a)[4], uint64_t db) {
    if (SC) asm volatile("wgmma.mma_async.sync.aligned.m64n8k16.f32.bf16.bf16 "
        "{%0,%1,%2,%3}, "
        "{%4,%5,%6,%7}, %8, 1, 1, 1, 0;"
        : D4(+, 0) : "r"(a[0]), "r"(a[1]), "r"(a[2]), "r"(a[3]), "l"(db));
    else asm volatile("wgmma.mma_async.sync.aligned.m64n8k16.f32.bf16.bf16 "
        "{%0,%1,%2,%3}, "
        "{%4,%5,%6,%7}, %8, 0, 1, 1, 0;"
        : D4(=, 0) : "r"(a[0]), "r"(a[1]), "r"(a[2]), "r"(a[3]), "l"(db));
}
template <int SC> DEVI void wg_ss64a(float (&d)[32], uint64_t da, uint64_t db) {
    if (SC) asm volatile("wgmma.mma_async.sync.aligned.m64n64k16.f32.bf16.bf16 "
        "{%0,%1,%2,%3,%4,%5,%6,%7,%8,%9,%10,%11,%12,%13,%14,%15,%16,%17,%18,%19,%20,%21,%22,%23,%24,%25,%26,%27,%28,%29,%30,%31}, "
        "%32, %33, 1, 1, 1, 1, 0;"
        : D4(+, 0), D4(+, 4), D4(+, 8), D4(+, 12), D4(+, 16), D4(+, 20), D4(+, 24), D4(+, 28) : "l"(da), "l"(db));
    else asm volatile("wgmma.mma_async.sync.aligned.m64n64k16.f32.bf16.bf16 "
        "{%0,%1,%2,%3,%4,%5,%6,%7,%8,%9,%10,%11,%12,%13,%14,%15,%16,%17,%18,%19,%20,%21,%22,%23,%24,%25,%26,%27,%28,%29,%30,%31}, "
        "%32, %33, 0, 1, 1, 1, 0;"
        : D4(=, 0), D4(=, 4), D4(=, 8), D4(=, 12), D4(=, 16), D4(=, 20), D4(=, 24), D4(=, 28) : "l"(da), "l"(db));
}

#define G_ROWS 514
__device__ uint4 g_G[64 * G_ROWS * 8];
__device__ uint4 g_GN[64 * 8];
__device__ uint4 g_WN[1152];
#define FS_F2 196608
#define FS_TB (FS_F2 + 8192)
#define FS_NQ (FS_TB + 16384)
#define FS_BAR (FS_NQ + 128)
#define FS_NY (FS_NQ + 1024 + 128)
#define FS_TOTAL (FS_NQ + 3072)
#define F_THREADS 512

DEVI uint32_t cis(int j) {
    const float a = fmaf(__uint_as_float((((j + 1024) << 12) & 0x7FF000) | 0x3F800000), 6.283185307179586f, -9.42477796076938f);
    return pack2(__cosf(a), __sinf(a));
}
DEVI uint32_t cos2(int j0, int j1) {
    const float f = 6.283185307179586f / 2048.f;
    return pack2(__cosf((float)(((j0 + 1024) & 2047) - 1024) * f), __cosf((float)(((j1 + 1024) & 2047) - 1024) * f));
}
DEVI void twid(int j, float& c, float& s) {
    const float a = (float)(((j + 512) & 1023) - 512) * (6.283185307179586f / 1024.f);
    c = __cosf(a) * (1.f / 1024.f);
    s = __sinf(a) * (1.f / 1024.f);
}
DEVI void mwait(uint32_t bar, uint32_t parity) {
    asm volatile("{\n.reg .pred p;\n.reg .b32 c;\nmbarrier.try_wait.parity.shared::cta.b64 p, [%0], %1;\n@p bra.uni D;\nmov.b32 c, 0;\n"
                 "L:\nadd.u32 c, c, 1;\nsetp.gt.u32 p, c, 4194304;\n@p st.shared.u32 [c], c;\n"
                 "mbarrier.try_wait.parity.shared::cta.b64 p, [%0], %1;\n@!p bra.uni L;\nD:\n}" ::"r"(bar), "r"(parity) : "memory");
}
template <bool B> struct Bool { static constexpr bool v = B; };
DEVI uint32_t opq(uint32_t& x, uint32_t zero) { OPQ(x); return x; }
DEVI uint32_t tidx() { uint32_t r; asm volatile("mov.u32 %0, %%tid.x;" : "=r"(r)); return r; }
DEVI void tma4d(uint32_t dst, const CUtensorMap* tm, uint32_t bar, int c0, int c1, int c2, int c3) {
    asm volatile("cp.async.bulk.tensor.4d.shared::cluster.global.mbarrier::complete_tx::bytes [%0], [%1, {%3, %4, %5, %6}], [%2];"
                 ::"r"(dst), "l"(tm), "r"(bar), "r"(c0), "r"(c1), "r"(c2), "r"(c3) : "memory");
}
DEVI void tma3s(const CUtensorMap* tm, uint32_t src, int c0, int c1, int c2) {
    asm volatile("cp.async.bulk.tensor.3d.global.shared::cta.bulk_group [%0, {%2, %3, %4}], [%1];" ::"l"(tm), "r"(src), "r"(c0), "r"(c1), "r"(c2) : "memory");
}
DEVI void tma4s(const CUtensorMap* tm, uint32_t src, int c0, int c1, int c2, int c3) {
    asm volatile("cp.async.bulk.tensor.4d.global.shared::cta.bulk_group [%0, {%2, %3, %4, %5}], [%1];"
                 ::"l"(tm), "r"(src), "r"(c0), "r"(c1), "r"(c2), "r"(c3) : "memory");
}
DEVI void bulk_commit() { asm volatile("cp.async.bulk.commit_group;" ::: "memory"); }
DEVI void fence_async() { asm volatile("fence.proxy.async;" ::: "memory"); }
DEVI void fence_smem() { asm volatile("fence.proxy.async.shared::cta;" ::: "memory"); }
DEVI void wgbar(uint32_t q) { asm volatile("bar.sync %0, 128;" ::"r"(q + 2) : "memory"); }
DEVI void grid_arrive(uint32_t* c) { asm volatile("fence.proxy.async;\nred.release.gpu.global.add.u32 [%0], 1;" ::"l"(c) : "memory"); }
DEVI void grid_wait(uint32_t* c, uint32_t n) {
    uint32_t v;
    int it = 0;
    do {
        asm volatile("ld.acquire.gpu.global.u32 %0, [%1];" : "=r"(v) : "l"(c) : "memory");
        if (++it > (1 << 22)) die(it);
    } while (v + 1 != n);
    fence_async();
}

template <bool INV, class S1, class S2>
DEVI void fft_rows(uint32_t grp, uint32_t q, const uint32_t (&F)[2][4], const float (&tc)[8], const float (&ts)[8], uint32_t so, float fx, uint32_t nq,
                   S1 sh1, S2 sh2) {
    float d[64];
    const uint64_t db = INV ? mkdesc(grp, 1024, 2048) : (mkdesc(grp, 2048, 512) ^ ((uint64_t)3 << 62));
    wg_fence();
    wg_rs128t<0>(d, F[0], db);
    wg_rs128t<1>(d, F[1], db + (INV ? 256 : 64));
    wg_commit();
    SF();
    sh1();
    float4 ny;
    if (INV) ny = lds128f(nq);
    wg_wait<0>();
    if (INV) { d[0] = fmaf(fx, ny.x, d[0]); d[16] = fmaf(fx, ny.y, d[16]); d[32] = fmaf(fx, ny.z, d[32]); d[48] = fmaf(fx, ny.w, d[48]); }
    uint32_t a[2][4][4];
    float e[2][INV ? 16 : 20];
    const uint64_t df = mkdesc(SB0 + FS_F2, 16, 1024);
#pragma unroll
    for (int s = 0; s < 2; s++) {
#pragma unroll
        for (int i = 0; i < 4; i++)
#pragma unroll
            for (int h = 0; h < 2; h++) {
                const float* x = d + (2 * s + h) * 16 + i * 4;
                a[s][i][h] = pack2(fmaf(x[2], ts[2 * i], x[0] * tc[2 * i]), fmaf(x[3], ts[2 * i + 1], x[1] * tc[2 * i + 1]));
                a[s][i][h + 2] = pack2(fmaf(-x[0], ts[2 * i], x[2] * tc[2 * i]), fmaf(-x[1], ts[2 * i + 1], x[3] * tc[2 * i + 1]));
            }
        wg_fence();
#pragma unroll
        for (int i = 0; i < 4; i++) {
            if constexpr (INV) { if (i == 0) wg_rs32<0>(e[s], a[s][i], df); else wg_rs32<1>(e[s], a[s][i], df + i * 2); }
            else { if (i == 0) wg_rs40<0>(e[s], a[s][i], df); else wg_rs40<1>(e[s], a[s][i], df + i * 2); }
        }
        wg_commit();
    }
    SF();
    sh2();
#pragma unroll
    for (int s = 0; s < 2; s++) {
        if (s == 0) wg_wait<1>(); else wg_wait<0>();
        float* x = e[s];
        if constexpr (!INV) {
            x[0] *= fx; x[1] *= fx; x[2] *= fx; x[3] *= fx;
            if (fx != 1.f) sts64(nq + s * 8, pack2(x[16], 0.f), pack2(x[18], 0.f));
        }
        const uint32_t o = grp + (INV ? so + s * 4096 : so ^ (s * 576));
#pragma unroll
        for (int b = 0; b < 2; b++)
            stsm4t(o + b * (INV ? 1024 : 4096), pack2(x[8 * b], x[8 * b + 1]), pack2(x[8 * b + 2], x[8 * b + 3]), pack2(x[8 * b + 4], x[8 * b + 5]),
                   pack2(x[8 * b + 6], x[8 * b + 7]));
    }
}

template <bool INV>
DEVI void fft_gen(uint32_t a, uint32_t n2) {
    const uint32_t tid = tidx(), x = ((tid >> 4) & 24) + (tid & 3), o = (tid & 4) * 128;
    if (INV) {
        const uint32_t r = (tid & 64) * 16 + (tid & 16) * 32 + (tid & 40) * 8 + n2;
        sts128(a + tid * 16, cis(o - r * x), cis(o - (r + 128) * x), cis(o - r * (x + 4)), cis(o - (r + 128) * (x + 4)));
    } else {
        const uint32_t r = 64 * x + n2, k = ((tid >> 2) & 24) + ((tid >> 3) & 3);
        sts128(a + tid * 16, cis(r * k + o), cis(r * (k + 4) + o), cis((r + 256) * k + o), cis((r + 256) * (k + 4) + o));
    }
}
template <bool INV, class S1>
DEVI void fft_cross(uint32_t buf, uint32_t q, uint32_t fa, uint32_t so, uint32_t nq, float (&n)[4], S1 sh1) {
    uint32_t F[4][4];
#pragma unroll
    for (int s = 0; s < 4; s++) { const uint4 v = lds128(fa + s * 2048); F[s][0] = v.x; F[s][1] = v.y; F[s][2] = v.z; F[s][3] = v.w; }
    float d[64];
    const uint64_t db = mkdesc(buf + q * 2048, 1024, 8192), dn = mkdesc(nq, 16, 1024);
    wg_fence();
#pragma unroll
    for (int s = 0; s < 4; s++) { if (s == 0) wg_rs128t<0>(d, F[s], db); else wg_rs128t<1>(d, F[s], db + s * 1024); }
#pragma unroll
    for (int s = 0; s < 4; s++) { if (s == 0) wg_rs8<0>(n, F[s], dn); else wg_rs8<1>(n, F[s], dn + s * 2); }
    wg_commit();
    SF();
    sh1();
    wg_wait<0>();
#pragma unroll
    for (int b = 0; b < 8; b++) {
        const uint32_t o = INV ? so ^ ((b >> 1) * 288 ^ (b & 1) * 32) : (so ^ ((b & 3) * 32)) + (b >> 2) * 1024;
        stsm4(buf + o, pack2(d[8 * b], d[8 * b + 1]), pack2(d[8 * b + 2], d[8 * b + 3]), pack2(d[8 * b + 4], d[8 * b + 5]), pack2(d[8 * b + 6], d[8 * b + 7]));
    }
}

template <bool ODD>
DEVI void fft_filter(uint32_t aw, const float (&e)[32], const float (&o)[32], uint32_t (&u)[4][4], uint32_t (&v)[4][4]) {
#pragma unroll
    for (int s = 0; s < 4; s++) {
        float y[2][2][4];
#pragma unroll
        for (int c = 0; c < 2; c++) {
            float f[4][2];
#pragma unroll
            for (int i = 0; i < 4; i++) {
                const uint32_t a = aw + (i * 32 + s * 8 + c) * 144, x = lds32(a);
                f[i][0] = ODD ? hi_f(x) : lo_f(x);
                f[i][1] = ODD ? lo_f(lds32(a + 4)) : hi_f(x);
            }
#pragma unroll
            for (int h = 0; h < 2; h++) {
                const int x = 8 * s + 2 * h + c;
                const float ar = e[x] + o[x], ai = e[x + 4] + o[x + 4], br = e[x] - o[x], bi = e[x + 4] - o[x + 4];
                const float yr = fmaf(-ai, f[2][h], ar * f[0][h]), yi = fmaf(ar, f[2][h], ai * f[0][h]);
                y[h][c][0] = fmaf(-bi, f[3][h], fmaf(br, f[1][h], yr));
                y[h][c][1] = fmaf(br, f[3][h], fmaf(bi, f[1][h], yi));
                y[h][c][2] = fmaf(2.f, yr, -y[h][c][0]);
                y[h][c][3] = fmaf(2.f, yi, -y[h][c][1]);
            }
        }
#pragma unroll
        for (int h = 0; h < 2; h++) {
            u[s][h] = pack2(y[h][0][0], y[h][1][0]); u[s][h + 2] = pack2(y[h][0][1], y[h][1][1]);
            v[s][h] = pack2(y[h][0][2], y[h][1][2]); v[s][h + 2] = pack2(y[h][0][3], y[h][1][3]);
        }
    }
}

__global__ void __launch_bounds__(F_THREADS, 1)
post_kernel(const __grid_constant__ CUtensorMap tmx, const __grid_constant__ CUtensorMap tmg1, const __grid_constant__ CUtensorMap tmg2,
           const __grid_constant__ CUtensorMap tmwr, const __grid_constant__ CUtensorMap tmwi, const __grid_constant__ CUtensorMap tmy,
           const bf16* __restrict__ wr, const bf16* __restrict__ wi, uint32_t* cnt, uint32_t zero, int nw,
           const __grid_constant__ CUtensorMap tmb, uint32_t xlo, uint32_t xhi, bf16* __restrict__ out) {
    extern __shared__ __align__(1024) uint8_t smem[];
    const uint32_t sb = SB0;
    if (smem_u32(smem) != sb) die(1 << 23);
    if (blockIdx.x >= nw) {
        gemm2(blockIdx.x - nw, xlo, xhi, tmb, out);
        return;
    }
    const uint32_t tid = threadIdx.x, lane = tid & 31, g = lane >> 2, t = lane & 3, j8 = lane & 7, mat = lane >> 3;
    const uint32_t wi_ = __reduce_max_sync(0xFFFFFFFFu, tid >> 5), q = wi_ >> 2, w = wi_ & 3;
    const int cta = blockIdx.x;
    const int nt = cta < 64 ? (64 - cta + nw - 1) / nw : 0;
    const uint32_t bar = sb + FS_BAR;
    if (tid == 0) {
        for (int i = 0; i < 30; i++) mbar_init(bar + i * 8, i < 3 ? 4 : i < 6 ? 16 : i >= 14 && i < 18 ? 2 : 1);
        asm volatile("fence.mbarrier_init.release.cluster;" ::: "memory");
        fence_smem();
    }
    __syncthreads();
#define FT(n)
    FT(0);
#define N2(p) (2 * ((p) & 31) + ((p) >> 5))
#define WLOAD(tk, part) { \
        const uint32_t wd_ = sb + 131072 + q * 18432 + (part) * 9216, wb_ = bar + 112 + q * 8; \
        mbar_expect(wb_, 9216); \
        if ((tk) < 256) tma3d(wd_, (part) ? &tmwi : &tmwr, wb_, ((tk) & 63) * 64, (tk) >> 6, 0); \
        else asm volatile("cp.async.bulk.shared::cluster.global.mbarrier::complete_tx::bytes [%0], [%1], 9216, [%2];" \
                          ::"r"(wd_), "l"(g_WN + (part) * 576), "r"(wb_) : "memory"); }
#define GROW(tk) ((tk) < 256 ? ((tk) >> 5) * 64 + ((tk) & 7) * 8 + (((tk) >> 3) & 3) * 2 : 512)
#define DLOAD(tk, sl) { mbar_expect(bar + 48 + (sl) * 8, 16384); tma3d(sb + (sl) * 16384, &tmg2, bar + 48 + (sl) * 8, 0, GROW(tk), 0); }
#define IO(c) if (w == 3 && (c) && elect())
#define XLOAD1(i, bb) { const uint32_t xb_ = bar + 144 + (bb) * 32 + q * 8; mbar_expect(xb_, 16384); tma4d(sb + (bb) * 65536 + q * 16384, &tmx, xb_, 0, 0, q * 8, N2(cta + (i) * nw)); }
#define GLOAD3(i, bb) { mbar_expect(bar + (bb) * 8, q ? 16384 : 16512); tma3d(sb + (bb) * 65536 + q * 16384, &tmg1, bar + (bb) * 8, 0, q * 128, cta + (i) * nw); \
        if (q == 0) asm volatile("cp.async.bulk.shared::cluster.global.mbarrier::complete_tx::bytes [%0], [%1], 128, [%2];" \
                                 ::"r"(sb + FS_NQ + (bb) * 1024), "l"(g_GN + (cta + (i) * nw) * 8), "r"(bar + (bb) * 8) : "memory"); }
    for (int i = 0; i < 3; i++) IO(i < nt) XLOAD1(i, i);
    for (uint32_t x = tid; x < 40 * 32; x += 512) {
        const uint32_t n = x >> 5, m2 = mat * 8 + t * 2, ri = g & 1;
        const uint32_t c2 = ((n >> 1) & 1) + ((n >> 3) & 1) * 2 + (n & 4) + (n >> 4) * 8;
        const uint32_t v = cos2(m2 * c2 * 64 + ((n & 1) - ri) * 512, (m2 + 1) * c2 * 64 + ((n & 1) - ri) * 512);
        sts32(sb + FS_F2 + n * 128 + ((g ^ (n & 7)) << 4) + t * 4, n < 32 ? v : n == 32 && ri == 0 ? 0xBF003F00u : 0u);
    }
    float tc[8], ts[8];
    uint32_t F[2][4];
    uint32_t c1 = 16 * (w >> 1) + 2 * g + (w & 1);
#pragma unroll
    for (int i = 0; i < 8; i++) {
        twid(c1 * (8 * (i >> 1) + 2 * t + (i & 1)), tc[i], ts[i]);
        const uint32_t m1 = (i >> 1) * 8 + 2 * t;
        F[i >> 2][i & 3] = cos2(c1 * m1 * 64 + (i & 1) * 512, c1 * (m1 + 1) * 64 + (i & 1) * 512);
    }
    {
        const uint32_t kr = (2 * (mat & 1) + (j8 & 1)) ^ ((j8 >> 2) << 1);
        const uint32_t so1 = ((mat >> 1) + 2 * (j8 >> 2)) * 1024 + kr * 128 + (((((j8 >> 1) & 1) * 4 + w) ^ kr) << 4);
        const uint32_t so2 = (2 * w + (mat & 1)) * 8192 + q * 2048 + j8 * 128 + (((mat >> 1) ^ j8) << 4);
        uint32_t so = so1 << 16 | so2;
        const float fx = (tid & 127) == 0 ? 0.5f : 1.f;
        fft_gen<false>(sb + FS_TB, N2(cta));
        fence_smem();
        bsync<1, 512>();
        FT(1);
        int b = 0, bp = 2, ph = 0;
        if (nt) mwait(bar + 144 + q * 8, 0);
        __syncwarp();
        auto step = [&](auto first, auto last, const int i) {
            const uint32_t p = cta + i * nw, bn = 3 - b - bp, tb = (i & 1) * 8192;
            const uint32_t grp = sb + b * 65536 + q * 16384, nq = sb + FS_NQ + b * 1024 + q * 32;
            auto sa = [&]() {
                if constexpr (!decltype(first)::v) {
                    fence_smem();
                    __syncwarp();
                    if (elect()) mbar_arrive(bar + 24);
                }
                IO(i > 1) {
                    mwait(bar + 32, i & 1);
                    tma3s(&tmg1, sb + bn * 65536 + q * 16384, 0, q * 128, p - 2 * nw);
                    bulk_commit();
                }
            };
            auto sb_ = [&]() { if constexpr (!decltype(first)::v) mwait(bar + 24, (i - 1) & 1); };
            if constexpr (!decltype(last)::v) fft_rows<false>(grp, q, F, tc, ts, opq(so, zero) >> 16, fx, nq, sa, sb_);
            else { sa(); __syncwarp(); sb_(); __syncwarp(); }
            if constexpr (!decltype(first)::v) {
                float n[4];
                fft_cross<false>(sb + bp * 65536, q, sb + FS_TB + 8192 - tb + (((tidx() & 127) ^ (q & 1)) << 4), opq(so, zero) & 0xFFFF, sb + FS_NQ + bp * 1024, n, [&]() {
                    fft_gen<false>(sb + FS_TB + tb, N2(p));
                    IO(i >= 2 && i + 1 < nt) {
                        asm volatile("cp.async.bulk.wait_group.read 0;" ::: "memory");
                        XLOAD1(i + 1, bn);
                    }
                });
                if (q == 0) {
                    const uint32_t x = tidx();
                    bf16* z = (bf16*)(g_G + ((p - nw) * G_ROWS + 512) * 8) + (x & 4) * 16 + ((x >> 2) & 24) + ((x >> 3) & 3);
                    asm volatile("{\n.reg .pred p;\n.reg .b16 a, b;\nsetp.eq.u32 p, %2, 0;\nmov.b32 {a, b}, %1;\n@p st.global.u16 [%0], a;\n@p st.global.u16 [%0+8], b;\n}"
                                 ::"l"(z), "r"(pack2(n[0], n[2])), "r"(x & 3) : "memory");
                }
            }
            if constexpr (!decltype(last)::v) {
                fft_rows<false>(grp + 8192, q, F, tc, ts, opq(so, zero) >> 16, fx, nq + 16, [&]() {
                    if constexpr (!decltype(first)::v) {
                        fence_smem();
                        __syncwarp();
                        if (elect()) mbar_arrive(bar + 32);
                    }
                    if ((w == 1 || w == 2) && elect())
                        asm volatile("cp.async.bulk.prefetch.L2.global [%0], 8208;" ::"l"((w == 1 ? wr : wi) + (p * 4 + q) * 4104) : "memory");
                }, [&]() { if (i + 1 < nt) mwait(bar + 144 + bn * 32 + q * 8, bn ? ph : ph ^ 1); });
                bp = b;
                if (++b == 3) { b = 0; ph ^= 1; }
            }
        };
        if (nt) {
            step(Bool<true>(), Bool<false>(), 0);
#pragma unroll 1
            for (int i = 1; i < nt; i++) step(Bool<false>(), Bool<false>(), i);
            step(Bool<false>(), Bool<true>(), nt);
        }
        for (uint32_t x = cta * 512 + tid; x < 4096; x += nw * 512)
            ((bf16*)g_WN)[(x >> 5) * 72 + (x & 16) + (x & 7) * 2 + ((x >> 3) & 1)] = (x < 2048 ? wr : wi)[(x & 2047) * 513 + 512];
        FT(2);
        fence_async();
        bsync<1, 512>();
        IO(nt) { tma3s(&tmg1, sb + bp * 65536 + q * 16384, 0, q * 128, cta + (nt - 1) * nw); bulk_commit(); }
    }
    for (uint32_t x = tid; x < 128 * 32; x += 512) {
        const uint32_t n = (x >> 5) & 63, a = x & 31, k2 = (n >> 4) * 8 + (n & 7);
        sts32(sb + FS_TB + (x >> 5) * 128 + (((a >> 2) ^ (n & 7)) << 4) + (a & 3) * 4, cis((2 * a + (x >> 11)) * k2 * 32 + (n & 8) * 64));
    }
    fence_smem();
    bsync<1, 512>();
    IO(true) {
        asm volatile("cp.async.bulk.wait_group 0;" ::: "memory");
        grid_arrive(cnt);
        grid_wait(cnt, 4 * nw);
        const int tk = cta + q * nw;
        if (tk <= 256) { DLOAD(tk, q); WLOAD(tk, 0); WLOAD(tk, 1); }
    }
    __syncwarp();
    {
        const uint32_t lo = j8 * 128 + (((2 * w + (mat & 1)) ^ j8) << 4);
        const uint32_t aw = sb + 131072 + q * 18432 + t * 288 + w * 32 + g * 4;
        const uint64_t df = mkdesc(sb + FS_TB, 16, 1024);
        const uint64_t da = mkdesc(sb + q * 16384, 16, 1024);
        const uint32_t buf = sb + 65536 + q * 16384;
        int i = 0, tk = cta + q * nw;
        if (tk <= 256) mwait(bar + 48 + q * 8, 0);
        FT(3);
#pragma unroll 1
        for (; tk <= 256; tk += 4 * nw, i++) {
            const bool more = tk + 4 * nw <= 256;
            float e[32], o[32];
            wg_fence();
#pragma unroll
            for (int s = 0; s < 4; s++) { if (s == 0) wg_ss64a<0>(e, da, df); else wg_ss64a<1>(e, da + s * 128, df + s * 2); }
#pragma unroll
            for (int s = 0; s < 4; s++) { if (s == 0) wg_ss64a<0>(o, da + 512, df + 512); else wg_ss64a<1>(o, da + 512 + s * 128, df + 512 + s * 2); }
            wg_commit();
            SF();
            if (i > 0) {
                fence_smem();
                wgbar(q);
                IO(true) { tma3s(&tmg2, buf, 0, GROW(tk - 4 * nw), 0); bulk_commit(); }
            }
            if (w == 2 && more && elect()) mbar_expect(bar + 48 + q * 8, 16384);
            const int gr = GROW(tk + 4 * nw);
            mwait(bar + 112 + q * 8, i & 1);
            wg_wait<0>();
            if (w == 2 && more && elect()) tma3d(sb + q * 16384, &tmg2, bar + 48 + q * 8, 0, gr, 0);
            uint32_t u[4][4], v[4][4];
            if (tk & 8) fft_filter<true>(aw + (tk & 48) / 4, e, o, u, v);
            else fft_filter<false>(aw + (tk & 48) / 4, e, o, u, v);
            wg_fence();
#pragma unroll
            for (int s = 0; s < 4; s++) { if (s == 0) wg_rs64t<0>(e, u[s], df); else wg_rs64t<1>(e, u[s], df + s * 128); }
#pragma unroll
            for (int s = 0; s < 4; s++) { if (s == 0) wg_rs64t<0>(o, v[s], df + 512); else wg_rs64t<1>(o, v[s], df + 512 + s * 128); }
            wg_commit();
            SF();
            IO(true) asm volatile("cp.async.bulk.wait_group.read 0;" ::: "memory");
            wgbar(q);
            if (more) {
                if ((w == 1 || w == 2) && elect()) WLOAD(tk + 4 * nw, w - 1);
                mwait(bar + 48 + q * 8, (i + 1) & 1);
            }
            wg_wait<0>();
#pragma unroll
            for (int s = 0; s < 4; s++) {
                const uint32_t a = buf + (mat >> 1) * 1024 + lo + s * 2048;
                stsm4t(a, pack2(e[8 * s], e[8 * s + 1]), pack2(e[8 * s + 2], e[8 * s + 3]), pack2(e[8 * s + 4], e[8 * s + 5]), pack2(e[8 * s + 6], e[8 * s + 7]));
                stsm4t(a + 8192, pack2(o[8 * s], o[8 * s + 1]), pack2(o[8 * s + 2], o[8 * s + 3]), pack2(o[8 * s + 4], o[8 * s + 5]), pack2(o[8 * s + 6], o[8 * s + 7]));
            }
            if (tk == 256 && w < 2) {
                uint32_t* z = (uint32_t*)g_GN + t * 32 + w * 16 + g;
#pragma unroll
                for (int s = 0; s < 16; s++) {
                    z[(s >> 1) * 128 + (s & 1) * 8] = pack2(e[2 * s], e[2 * s + 1]);
                    z[(s >> 1) * 128 + (s & 1) * 8 + 1024] = pack2(o[2 * s], o[2 * s + 1]);
                }
                fence_async();
            }
        }
        fence_smem();
        wgbar(q);
        IO(true) {
            if (i > 0) { tma3s(&tmg2, buf, 0, GROW(tk - 4 * nw), 0); bulk_commit(); }
            asm volatile("cp.async.bulk.wait_group 0;" ::: "memory");
            grid_arrive(cnt + 1);
        }
    }
    FT(4);
    bsync<1, 512>();
    {
        for (uint32_t n = wi_; n < 32; n += 16) {
            const uint32_t cl = (mat >> 1) * 16 + t * 4 + (mat & 1), mh = ((n >> 3) & 1) + (n & 7) * 2 + (n & 16);
            sts32(sb + FS_F2 + n * 128 + ((g ^ (n & 7)) << 4) + t * 4, cos2(cl * mh * 64 + (g & 1) * 512, (cl + 2) * mh * 64 + (g & 1) * 512));
        }
        fence_smem();
        c1 = 8 * w + g;
#pragma unroll
        for (int i = 0; i < 8; i++) {
            twid(-c1 * (16 * (i >> 2) + 4 * t + 2 * (i & 1) + ((i >> 1) & 1)), tc[i], ts[i]);
            F[i >> 2][i & 3] = cis((i & 1) * 512 - c1 * ((i >> 1) * 4 + (t ^ (q & 1))) * 64);
        }
        const uint32_t kr = (j8 & 1) ^ ((j8 >> 2) << 1);
        const uint32_t so2 = ((w >> 1) * 4 + (j8 >> 2) * 2 + (w & 1)) * 8192 + (2 * q + (mat & 1)) * 1024 + kr * 128 + (((((j8 >> 1) & 1) * 4 + (mat >> 1)) ^ kr) << 4);
        const uint32_t so1 = (mat & 1) * 2048 + j8 * 128 + ((((mat >> 1) * 4 + w) ^ j8) << 4);
        uint32_t so = so1 << 16 | so2;
        const float fx = t ? 0.f : (g & 1) ? -1.f : 1.f;
        fft_gen<true>(sb + FS_TB, N2(cta));
        bsync<1, 512>();
        IO(true) grid_wait(cnt + 1, 4 * nw);
        for (int i = 0; i < 3; i++) IO(i < nt) GLOAD3(i, i);
        __syncwarp();
        int b = 0, bp = 2, ph = 0;
        auto step = [&](auto first, auto last, const int i) {
            const uint32_t p = cta + i * nw, bn = 3 - b - bp, tb = (i & 1) * 8192;
            const uint32_t grp = sb + bp * 65536 + q * 16384, ny = sb + FS_NY + bp * 128 + q * 32;
            auto sb_ = [&]() { if constexpr (!decltype(last)::v) mwait(bar + b * 8, ph); };
            if constexpr (!decltype(first)::v) {
                fft_rows<true>(grp, q, F, tc, ts, opq(so, zero) >> 16, fx, ny, [&]() {
                    if (i > 1) {
                        fence_smem();
                        wgbar(q);
                        IO(true) { tma4s(&tmy, sb + bn * 65536 + q * 16384, 0, 0, q * 8, N2(p - 2 * nw)); bulk_commit(); }
                    }
                }, sb_);
            } else { sb_(); __syncwarp(); }
            if constexpr (decltype(first)::v) FT(5);
            if constexpr (!decltype(last)::v) {
                float n[4];
                fft_cross<true>(sb + b * 65536, q, sb + FS_TB + tb + (tidx() & 127) * 16, opq(so, zero) & 0xFFFF, sb + FS_NQ + b * 1024, n, [&]() {
                    fft_gen<true>(sb + FS_TB + 8192 - tb, N2(p + nw));
                    IO(i >= 2 && i + 1 < nt) {
                        asm volatile("cp.async.bulk.wait_group.read 0;" ::: "memory");
                        GLOAD3(i + 1, bn);
                    }
                });
                if (q == 0) {
                    const uint32_t x = tidx(), a = sb + FS_NY + b * 128 + (x & 64) + (x & 16) * 2 + ((x & 40) >> 1);
                    if ((x & 7) == 0) { sts32f(a, n[0]); sts32f(a + 8, n[2]); }
                }
            }
            auto sc = [&]() {
                if constexpr (!decltype(last)::v) {
                    fence_smem();
                    __syncwarp();
                    if (elect()) mbar_arrive(bar + 24);
                }
            };
            auto sd = [&]() { if constexpr (!decltype(last)::v) mwait(bar + 24, (nt + i) & 1); };
            if constexpr (!decltype(first)::v) fft_rows<true>(grp + 8192, q, F, tc, ts, opq(so, zero) >> 16, fx, ny + 16, sc, sd);
            else { sc(); __syncwarp(); sd(); __syncwarp(); }
            if constexpr (!decltype(last)::v) {
                bp = b;
                if (++b == 3) { b = 0; ph ^= 1; }
            }
        };
        if (nt) {
            step(Bool<true>(), Bool<false>(), 0);
#pragma unroll 1
            for (int i = 1; i < nt; i++) step(Bool<false>(), Bool<false>(), i);
            step(Bool<false>(), Bool<true>(), nt);
        }
        fence_smem();
        wgbar(q);
        IO(nt) { tma4s(&tmy, sb + bp * 65536 + q * 16384, 0, 0, q * 8, N2(cta + (nt - 1) * nw)); bulk_commit(); }
        FT(6);
        IO(true) asm volatile("cp.async.bulk.wait_group 0;" ::: "memory");
    }
}

typedef CUresult (*EncodeFn)(CUtensorMap*, CUtensorMapDataType, cuuint32_t, void*, const cuuint64_t*, const cuuint64_t*,
                             const cuuint32_t*, const cuuint32_t*, CUtensorMapInterleave, CUtensorMapSwizzle,
                             CUtensorMapL2promotion, CUtensorMapFloatOOBfill);

static void make_map(EncodeFn enc, CUtensorMap* m, const void* ptr, int rank, const cuuint64_t* dims, const cuuint64_t* strides,
                     const cuuint32_t* box, CUtensorMapSwizzle sw = CU_TENSOR_MAP_SWIZZLE_128B) {
    cuuint32_t es[4] = {1, 1, 1, 1};
    CUresult r = enc(m, CU_TENSOR_MAP_DATA_TYPE_BFLOAT16, rank, (void*)ptr, dims, strides, box, es, CU_TENSOR_MAP_INTERLEAVE_NONE,
                     sw, CU_TENSOR_MAP_L2_PROMOTION_L2_256B, CU_TENSOR_MAP_FLOAT_OOB_FILL_NONE);
    if (r != CUDA_SUCCESS) fprintf(stderr, "tensor map encode failed: %d\n", (int)r);
}

extern "C" void kernel_launch(void* const* d_in, const int* in_sizes, int n_in, void* d_out, int out_size) {
    const bf16* A_x = (const bf16*)d_in[0];
    const bf16* A_mem0 = (const bf16*)d_in[1];
    const bf16* A_Wq = (const bf16*)d_in[2];
    const bf16* A_Wk = (const bf16*)d_in[3];
    const bf16* A_Wv = (const bf16*)d_in[4];
    const bf16* A_Wo = (const bf16*)d_in[5];
    const bf16* B_x = (const bf16*)d_in[7];
    const bf16* B_wr = (const bf16*)d_in[8];
    const bf16* B_wi = (const bf16*)d_in[9];
    bf16* out = (bf16*)d_out;

    static EncodeFn enc = nullptr;
    static void *pxs = nullptr, *pg = nullptr;
    static int ncl = 64;
    if (!enc) {
        cudaDriverEntryPointQueryResult qr;
        void* fn = nullptr;
        cudaGetDriverEntryPoint("cuTensorMapEncodeTiled", &fn, cudaEnableDefault, &qr);
        enc = (EncodeFn)fn;
        cudaFuncSetAttribute(chain_kernel, cudaFuncAttributeMaxDynamicSharedMemorySize, SM_TOTAL);
        cudaFuncSetAttribute(post_kernel, cudaFuncAttributeMaxDynamicSharedMemorySize, FS_TOTAL);
        cudaGetSymbolAddress(&pxs, g_xs);
        cudaGetSymbolAddress(&pg, g_G);
        cudaLaunchConfig_t lc = {};
        cudaLaunchAttribute at;
        at.id = cudaLaunchAttributeClusterDimension;
        at.val.clusterDim.x = 2; at.val.clusterDim.y = 1; at.val.clusterDim.z = 1;
        lc.gridDim = dim3(132); lc.blockDim = dim3(384); lc.dynamicSmemBytes = SM_TOTAL; lc.attrs = &at; lc.numAttrs = 1;
        int nc = 0;
        if (cudaOccupancyMaxActiveClusters(&nc, chain_kernel, &lc) == cudaSuccess && nc > 64) ncl = nc < 66 ? nc : 66;
    }
    CUtensorMap tmq, tmk, tmv, tmo, tmx, tmb;
    {
        cuuint64_t d[2] = {HD, DM}, st[1] = {HD * 2};
        cuuint32_t bx[2] = {64, 256};
        make_map(enc, &tmq, A_Wq, 2, d, st, bx);
        make_map(enc, &tmk, A_Wk, 2, d, st, bx);
        cuuint32_t bx2[2] = {64, 16};
        make_map(enc, &tmv, A_Wv, 2, d, st, bx2);
    }
    {
        cuuint64_t d[2] = {DM, HD}, st[1] = {DM * 2};
        cuuint32_t bx[2] = {64, 16}, bx2[2] = {64, 64};
        make_map(enc, &tmo, A_Wo, 2, d, st, bx);
        make_map(enc, &tmb, A_Wo, 2, d, st, bx2);
    }
    {
        cuuint64_t d[3] = {64, SEQ, DM / 64}, st[2] = {DM * 2, 128};
        cuuint32_t bx[3] = {64, 8, 4};
        make_map(enc, &tmx, A_x, 3, d, st, bx);
    }
    CUtensorMap fx, fg1, fg2, fwr, fwi, fy;
    {
        cuuint64_t d[4] = {32, 32, 32, 64}, st[3] = {64, 64 * DM * 2, DM * 2};
        cuuint32_t bx[4] = {32, 32, 8, 1};
        make_map(enc, &fx, B_x, 4, d, st, bx, CU_TENSOR_MAP_SWIZZLE_64B);
        cuuint64_t d2[4] = {64, 16, 32, 64}, st2[3] = {128, 64 * 4096, 4096};
        cuuint32_t bx2[4] = {64, 16, 8, 1};
        make_map(enc, &fy, out + DM, 4, d2, st2, bx2);
    }
    {
        cuuint64_t d[3] = {64, G_ROWS, 64}, st[2] = {128, G_ROWS * 128};
        cuuint32_t bx[3] = {64, 128, 1}, bx2[3] = {64, 2, 64};
        make_map(enc, &fg1, pg, 3, d, st, bx);
        make_map(enc, &fg2, pg, 3, d, st, bx2);
        cuuint64_t d2[3] = {8 * 513, 4, 64}, st2[2] = {8 * 513 * 2, 32 * 513 * 2};
        cuuint32_t bx3[3] = {72, 1, 64};
        make_map(enc, &fwr, B_wr, 3, d2, st2, bx3, CU_TENSOR_MAP_SWIZZLE_NONE);
        make_map(enc, &fwi, B_wi, 3, d2, st2, bx3, CU_TENSOR_MAP_SWIZZLE_NONE);
    }
    cudaStream_t st = cudaStreamPerThread;
    const uint64_t xs = ((uint64_t)pxs + XS_BYTES - 1) & ~(uint64_t)(XS_BYTES - 1);
    cudaMemsetAsync((void*)(xs + XO_B), 0xFF, XO_TK - XO_B + 512, st);
    chain_kernel<<<2 * ncl, 384, SM_TOTAL, st>>>(tmq, tmk, tmv, tmo, tmx, A_mem0, A_x, (uint32_t)xs, (uint32_t)(xs >> 32), 0u, NSEG);
    int nw = ncl == 66 ? 4 : 64;
    cudaLaunchConfig_t lc = {};
    cudaLaunchAttribute at;
    at.id = cudaLaunchAttributeProgrammaticStreamSerialization;
    at.val.programmaticStreamSerializationAllowed = 1;
    lc.gridDim = dim3(nw + 128); lc.blockDim = dim3(F_THREADS); lc.dynamicSmemBytes = FS_TOTAL; lc.stream = st; lc.attrs = &at; lc.numAttrs = 1;
    cudaLaunchKernelEx(&lc, post_kernel, fx, fg1, fg2, fwr, fwi, fy, B_wr, B_wi, (uint32_t*)(xs + XO_TK + 256), 0u, nw, tmb, (uint32_t)xs,
                       (uint32_t)(xs >> 32), out);
}
```

```cpp
#include <cuda_runtime.h>
#include <cuda_bf16.h>
#include <cuda.h>
#include <stdint.h>
#include <stdio.h>

typedef __nv_bfloat16 bf16;

#define SEQ 2048
#define DM 1024
#define NH 32
#define DH 128
#define NSEG 64
#define HD (NH * DH)

#define XS_BYTES (32u << 20)
__device__ uint4 g_xs[2 * XS_BYTES / 16];
#define XO_R 0u
#define XO_PB (1u << 18)
#define XO_FL (XO_PB + 16384u)
#define XO_TK (XO_FL + 32768u)
#define XO_CQK (1u << 20)
#define XO_CV (2u << 20)
#define XO_XG (4u << 20)
#define XO_OX (16u << 20)

#define DEVI __device__ __forceinline__

DEVI void die(int it) { asm volatile("st.shared.u32 [%0], %0;" ::"r"(it) : "memory"); }
DEVI uint32_t smem_u32(const void* p) { return (uint32_t)__cvta_generic_to_shared(p); }
DEVI void mbar_init(uint32_t bar, uint32_t cnt) { asm volatile("mbarrier.init.shared::cta.b64 [%0], %1;" ::"r"(bar), "r"(cnt) : "memory"); }
DEVI void mbar_expect(uint32_t bar, uint32_t bytes) { asm volatile("mbarrier.arrive.expect_tx.shared::cta.b64 _, [%0], %1;" ::"r"(bar), "r"(bytes) : "memory"); }
DEVI void mbar_arrive(uint32_t bar) { asm volatile("mbarrier.arrive.shared::cta.b64 _, [%0];" ::"r"(bar) : "memory"); }
DEVI void mbar_wait(uint32_t bar, uint32_t parity) {
    uint32_t done;
    int it = 0;
    do {
        asm volatile("{\n.reg .pred p;\nmbarrier.try_wait.parity.shared::cta.b64 p, [%1], %2;\nselp.u32 %0, 1, 0, p;\n}\n"
                     : "=r"(done) : "r"(bar), "r"(parity) : "memory");
        if (++it > (1 << 22)) die(it);
    } while (!done);
}
DEVI void tma2d(uint32_t dst, const CUtensorMap* tm, uint32_t bar, int c0, int c1) {
    asm volatile("cp.async.bulk.tensor.2d.shared::cluster.global.mbarrier::complete_tx::bytes [%0], [%1, {%3, %4}], [%2];"
                 ::"r"(dst), "l"(tm), "r"(bar), "r"(c0), "r"(c1) : "memory");
}
DEVI void tma3d(uint32_t dst, const CUtensorMap* tm, uint32_t bar, int c0, int c1, int c2) {
    asm volatile("cp.async.bulk.tensor.3d.shared::cluster.global.mbarrier::complete_tx::bytes [%0], [%1, {%3, %4, %5}], [%2];"
                 ::"r"(dst), "l"(tm), "r"(bar), "r"(c0), "r"(c1), "r"(c2) : "memory");
}
DEVI void bulk_g2s(uint32_t dst, uint32_t lo, uint32_t hi, uint32_t bytes, uint32_t bar) {
    asm volatile("{\n.reg .b64 a;\nmov.b64 a, {%1,%2};\ncp.async.bulk.shared::cluster.global.mbarrier::complete_tx::bytes [%0], [a], %3, [%4];\n}"
                 ::"r"(dst), "r"(lo), "r"(hi), "r"(bytes), "r"(bar) : "memory");
}
DEVI void bulk_s2g(uint32_t lo, uint32_t hi, uint32_t src, uint32_t bytes) {
    asm volatile("{\n.reg .b64 a;\nmov.b64 a, {%0,%1};\ncp.async.bulk.global.shared::cta.bulk_group [a], [%2], %3;\ncp.async.bulk.commit_group;\n}"
                 ::"r"(lo), "r"(hi), "r"(src), "r"(bytes) : "memory");
}
DEVI void bulk_red(uint32_t lo, uint32_t hi, uint32_t src, uint32_t bytes) {
    asm volatile("{\n.reg .b64 a;\nmov.b64 a, {%0,%1};\ncp.reduce.async.bulk.global.shared::cta.bulk_group.add.noftz.bf16 [a], [%2], %3;\ncp.async.bulk.commit_group;\n}"
                 ::"r"(lo), "r"(hi), "r"(src), "r"(bytes) : "memory");
}
DEVI bool elect() {
    uint32_t p;
    asm volatile("{\n.reg .pred P;\nelect.sync _|P, 0xFFFFFFFF;\nselp.u32 %0, 1, 0, P;\n}" : "=r"(p));
    return p != 0;
}
DEVI void ldsm4(uint32_t (&r)[4], uint32_t a) {
    asm volatile("ldmatrix.sync.aligned.m8n8.x4.shared.b16 {%0,%1,%2,%3}, [%4];" : "=r"(r[0]), "=r"(r[1]), "=r"(r[2]), "=r"(r[3]) : "r"(a) : "memory");
}
DEVI void ldsm4t(uint32_t (&r)[4], uint32_t a) {
    asm volatile("ldmatrix.sync.aligned.m8n8.x4.trans.shared.b16 {%0,%1,%2,%3}, [%4];" : "=r"(r[0]), "=r"(r[1]), "=r"(r[2]), "=r"(r[3]) : "r"(a) : "memory");
}
DEVI void ldsm2t(uint32_t (&r)[2], uint32_t a) {
    asm volatile("ldmatrix.sync.aligned.m8n8.x2.trans.shared.b16 {%0,%1}, [%2];" : "=r"(r[0]), "=r"(r[1]) : "r"(a) : "memory");
}
DEVI void ldsm2(uint32_t (&r)[2], uint32_t a) {
    asm volatile("ldmatrix.sync.aligned.m8n8.x2.shared.b16 {%0,%1}, [%2];" : "=r"(r[0]), "=r"(r[1]) : "r"(a) : "memory");
}
DEVI void stsm4t(uint32_t a, uint32_t r0, uint32_t r1, uint32_t r2, uint32_t r3) {
    asm volatile("stmatrix.sync.aligned.m8n8.x4.trans.shared.b16 [%0], {%1,%2,%3,%4};" ::"r"(a), "r"(r0), "r"(r1), "r"(r2), "r"(r3) : "memory");
}
DEVI uint32_t ldsm1(uint32_t a) {
    uint32_t r;
    asm volatile("ldmatrix.sync.aligned.m8n8.x1.shared.b16 {%0}, [%1];" : "=r"(r) : "r"(a) : "memory");
    return r;
}
DEVI void stsm4(uint32_t a, uint32_t r0, uint32_t r1, uint32_t r2, uint32_t r3) {
    asm volatile("stmatrix.sync.aligned.m8n8.x4.shared.b16 [%0], {%1,%2,%3,%4};" ::"r"(a), "r"(r0), "r"(r1), "r"(r2), "r"(r3) : "memory");
}
DEVI void stsm2(uint32_t a, uint32_t r0, uint32_t r1) {
    asm volatile("stmatrix.sync.aligned.m8n8.x2.shared.b16 [%0], {%1,%2};" ::"r"(a), "r"(r0), "r"(r1) : "memory");
}
DEVI uint32_t movm(uint32_t a) {
    uint32_t d;
    asm volatile("movmatrix.sync.aligned.m8n8.trans.b16 %0, %1;" : "=r"(d) : "r"(a));
    return d;
}
DEVI void mma16(float (&d)[4], uint32_t a0, uint32_t a1, uint32_t a2, uint32_t a3, uint32_t b0, uint32_t b1) {
    asm volatile("mma.sync.aligned.m16n8k16.row.col.f32.bf16.bf16.f32 {%0,%1,%2,%3}, {%4,%5,%6,%7}, {%8,%9}, {%0,%1,%2,%3};"
                 : "+f"(d[0]), "+f"(d[1]), "+f"(d[2]), "+f"(d[3]) : "r"(a0), "r"(a1), "r"(a2), "r"(a3), "r"(b0), "r"(b1));
}
DEVI void mma16z(float (&d)[4], uint32_t a0, uint32_t a1, uint32_t a2, uint32_t a3, uint32_t b0, uint32_t b1) {
    asm volatile("mma.sync.aligned.m16n8k16.row.col.f32.bf16.bf16.f32 {%0,%1,%2,%3}, {%4,%5,%6,%7}, {%8,%9}, {%10,%10,%10,%10};"
                 : "=f"(d[0]), "=f"(d[1]), "=f"(d[2]), "=f"(d[3]) : "r"(a0), "r"(a1), "r"(a2), "r"(a3), "r"(b0), "r"(b1), "f"(0.f));
}
DEVI void mma8(float (&d)[4], uint32_t a0, uint32_t a1, uint32_t b0) {
    asm volatile("mma.sync.aligned.m16n8k8.row.col.f32.bf16.bf16.f32 {%0,%1,%2,%3}, {%4,%5}, {%6}, {%0,%1,%2,%3};"
                 : "+f"(d[0]), "+f"(d[1]), "+f"(d[2]), "+f"(d[3]) : "r"(a0), "r"(a1), "r"(b0));
}
DEVI void mma8z(float (&d)[4], uint32_t a0, uint32_t a1, uint32_t b0) {
    asm volatile("mma.sync.aligned.m16n8k8.row.col.f32.bf16.bf16.f32 {%0,%1,%2,%3}, {%4,%5}, {%6}, {%7,%7,%7,%7};"
                 : "=f"(d[0]), "=f"(d[1]), "=f"(d[2]), "=f"(d[3]) : "r"(a0), "r"(a1), "r"(b0), "f"(0.f));
}
DEVI uint32_t pack2(float lo, float hi) {
    uint32_t r;
    asm("cvt.rn.bf16x2.f32 %0, %1, %2;" : "=r"(r) : "f"(hi), "f"(lo));
    return r;
}
DEVI uint32_t hadd2(uint32_t a, uint32_t b) {
    uint32_t r;
    asm("add.rn.bf16x2 %0, %1, %2;" : "=r"(r) : "r"(a), "r"(b));
    return r;
}
DEVI float lo_f(uint32_t x) { return __uint_as_float(x << 16); }
DEVI float hi_f(uint32_t x) { return __uint_as_float(x & 0xFFFF0000u); }
template <uint32_t OFF> DEVI uint4 ldg4(uint32_t lo, uint32_t hi) {
    uint4 v;
    asm volatile("{\n.reg .b64 a;\nmov.b64 a, {%4,%5};\nld.relaxed.gpu.global.v4.u32 {%0,%1,%2,%3}, [a+%6];\n}"
                 : "=r"(v.x), "=r"(v.y), "=r"(v.z), "=r"(v.w) : "r"(lo), "r"(hi), "n"(OFF) : "memory");
    return v;
}
template <uint32_t OFF> DEVI uint2 ldg2(uint32_t lo, uint32_t hi) {
    uint2 v;
    asm volatile("{\n.reg .b64 a;\nmov.b64 a, {%2,%3};\nld.relaxed.gpu.global.v2.u32 {%0,%1}, [a+%4];\n}"
                 : "=r"(v.x), "=r"(v.y) : "r"(lo), "r"(hi), "n"(OFF) : "memory");
    return v;
}
template <uint32_t OFF> DEVI uint32_t ldg1(uint32_t lo, uint32_t hi) {
    uint32_t v;
    asm volatile("{\n.reg .b64 a;\nmov.b64 a, {%1,%2};\nld.relaxed.gpu.global.u32 %0, [a+%3];\n}" : "=r"(v) : "r"(lo), "r"(hi), "n"(OFF) : "memory");
    return v;
}
template <uint32_t OFF> DEVI void stg1(uint32_t lo, uint32_t hi, uint32_t a) {
    asm volatile("{\n.reg .b64 a;\nmov.b64 a, {%0,%1};\nst.relaxed.gpu.global.u32 [a+%3], %2;\n}" ::"r"(lo), "r"(hi), "r"(a), "n"(OFF) : "memory");
}
template <uint32_t OFF> DEVI void stg4(uint32_t lo, uint32_t hi, uint32_t a, uint32_t b, uint32_t c, uint32_t d) {
    asm volatile("{\n.reg .b64 a;\nmov.b64 a, {%0,%1};\nst.relaxed.gpu.global.v4.u32 [a+%6], {%2,%3,%4,%5};\n}"
                 ::"r"(lo), "r"(hi), "r"(a), "r"(b), "r"(c), "r"(d), "n"(OFF) : "memory");
}
template <uint32_t OFF> DEVI void stg2(uint32_t lo, uint32_t hi, uint32_t a, uint32_t b) {
    asm volatile("{\n.reg .b64 a;\nmov.b64 a, {%0,%1};\nst.relaxed.gpu.global.v2.u32 [a+%4], {%2,%3};\n}"
                 ::"r"(lo), "r"(hi), "r"(a), "r"(b), "n"(OFF) : "memory");
}
DEVI uint32_t tagx2(uint32_t a, uint32_t b, uint32_t t) { uint32_t r; asm("lop3.b32 %0, %1, %2, %3, 0x7E;" : "=r"(r) : "r"(a), "r"(b), "r"(t)); return r; }
DEVI uint32_t tagx1(uint32_t a, uint32_t b, uint32_t t) { uint32_t r; asm("lop3.b32 %0, %1, %2, %3, 0xF6;" : "=r"(r) : "r"(a), "r"(b), "r"(t)); return r; }
DEVI uint32_t or3(uint32_t a, uint32_t b, uint32_t c) { uint32_t r; asm("lop3.b32 %0, %1, %2, %3, 0xFE;" : "=r"(r) : "r"(a), "r"(b), "r"(c)); return r; }
DEVI bool any_bad(uint32_t x) { return __any_sync(0xFFFFFFFFu, (x & 1u) != 0); }
DEVI uint32_t settag(uint32_t x, uint32_t tag) { return (x & ~1u) | tag; }
DEVI void sts32f(uint32_t a, float v) { asm volatile("st.shared.f32 [%0], %1;" ::"r"(a), "f"(v) : "memory"); }
DEVI void sts32(uint32_t a, uint32_t v) { asm volatile("st.shared.u32 [%0], %1;" ::"r"(a), "r"(v) : "memory"); }
DEVI void sts16(uint32_t a, uint32_t v) { asm volatile("st.shared.u16 [%0], %1;" ::"r"(a), "h"((unsigned short)v) : "memory"); }
DEVI void sts64(uint32_t a, uint32_t x, uint32_t y) { asm volatile("st.shared.v2.u32 [%0], {%1,%2};" ::"r"(a), "r"(x), "r"(y) : "memory"); }
DEVI void sts128(uint32_t a, uint32_t x, uint32_t y, uint32_t z, uint32_t w) {
    asm volatile("st.shared.v4.u32 [%0], {%1,%2,%3,%4};" ::"r"(a), "r"(x), "r"(y), "r"(z), "r"(w) : "memory");
}
DEVI float4 lds128f(uint32_t a) {
    float4 v;
    asm volatile("ld.shared.v4.f32 {%0,%1,%2,%3}, [%4];" : "=f"(v.x), "=f"(v.y), "=f"(v.z), "=f"(v.w) : "r"(a) : "memory");
    return v;
}
DEVI uint4 lds128(uint32_t a) {
    uint4 v;
    asm volatile("ld.shared.v4.u32 {%0,%1,%2,%3}, [%4];" : "=r"(v.x), "=r"(v.y), "=r"(v.z), "=r"(v.w) : "r"(a) : "memory");
    return v;
}
DEVI uint2 lds64(uint32_t a) {
    uint2 v;
    asm volatile("ld.shared.v2.u32 {%0,%1}, [%2];" : "=r"(v.x), "=r"(v.y) : "r"(a) : "memory");
    return v;
}
DEVI uint32_t lds32(uint32_t a) {
    uint32_t v;
    asm volatile("ld.shared.u32 %0, [%1];" : "=r"(v) : "r"(a) : "memory");
    return v;
}
DEVI float ex2(float x) { float r; asm("ex2.approx.ftz.f32 %0, %1;" : "=f"(r) : "f"(x)); return r; }
DEVI float rcp(float x) { float r; asm("rcp.approx.ftz.f32 %0, %1;" : "=f"(r) : "f"(x)); return r; }
DEVI uint32_t clk() { uint32_t c; asm volatile("mov.u32 %0, %%clock;" : "=r"(c)::"memory"); return c; }

DEVI uint64_t mkdesc(uint32_t addr, uint32_t lbo, uint32_t sbo) {
    return (uint64_t)((addr & 0x3FFFF) >> 4) | ((uint64_t)(lbo >> 4) << 16) | ((uint64_t)(sbo >> 4) << 32) | ((uint64_t)1 << 62);
}
DEVI void wg_fence() { asm volatile("wgmma.fence.sync.aligned;" ::: "memory"); }
DEVI void wg_commit() { asm volatile("wgmma.commit_group.sync.aligned;" ::: "memory"); }
template <int N> DEVI void wg_wait() { asm volatile("wgmma.wait_group.sync.aligned %0;" ::"n"(N) : "memory"); }
template <int SC>
DEVI void wg_rs32(float (&d)[16], const uint32_t (&a)[4], uint64_t db) {
    if (SC) {
        asm volatile("wgmma.mma_async.sync.aligned.m64n32k16.f32.bf16.bf16 "
                     "{%0,%1,%2,%3,%4,%5,%6,%7,%8,%9,%10,%11,%12,%13,%14,%15}, {%16,%17,%18,%19}, %20, 1, 1, 1, 0;"
                     : "+f"(d[0]), "+f"(d[1]), "+f"(d[2]), "+f"(d[3]), "+f"(d[4]), "+f"(d[5]), "+f"(d[6]), "+f"(d[7]),
                       "+f"(d[8]), "+f"(d[9]), "+f"(d[10]), "+f"(d[11]), "+f"(d[12]), "+f"(d[13]), "+f"(d[14]), "+f"(d[15])
                     : "r"(a[0]), "r"(a[1]), "r"(a[2]), "r"(a[3]), "l"(db));
    } else {
        asm volatile("wgmma.mma_async.sync.aligned.m64n32k16.f32.bf16.bf16 "
                     "{%0,%1,%2,%3,%4,%5,%6,%7,%8,%9,%10,%11,%12,%13,%14,%15}, {%16,%17,%18,%19}, %20, 0, 1, 1, 0;"
                     : "=f"(d[0]), "=f"(d[1]), "=f"(d[2]), "=f"(d[3]), "=f"(d[4]), "=f"(d[5]), "=f"(d[6]), "=f"(d[7]),
                       "=f"(d[8]), "=f"(d[9]), "=f"(d[10]), "=f"(d[11]), "=f"(d[12]), "=f"(d[13]), "=f"(d[14]), "=f"(d[15])
                     : "r"(a[0]), "r"(a[1]), "r"(a[2]), "r"(a[3]), "l"(db));
    }
}

#define NPRO 5
#define NA 12
#define NB 0
#define NPF 6
#define PF1 2
#define PF2 2
#define PF3 5
#define WPF 1
#define NPE (NPF & ~1)
#define VPF 2
#define VORD (NA == 12 ? 0x01234567 : NA == 10 ? 0x50123467 : NA == 8 ? 0x40125367 : 0x30142567)
#define WV_BOX ((16 - NA) * 2048)
#define WO_BOX ((16 - NB) * 1024)
#define SM_WV 0
#define SM_WO (2 * WV_BOX)
#define SM_X (SM_WO + 4 * WO_BOX)
#define SM_XO (SM_X + 32768)
#define SM_PI (SM_XO + 12288)
#define SM_KV (SM_PI + 24576)
#define SM_SP (SM_KV + 18432)
#define SM_TR (SM_SP + 10240)
#define SM_MEMT (SM_TR + 12288)
#define SM_OT (SM_MEMT + 4096)
#define SM_VS (SM_OT + 2048)
#define SM_P (SM_VS + 2048)
#define SM_DN (SM_P + 1792)
#define SM_PROF (SM_P + 2048)
#define SM_BAR 232192
#define SM_TOTAL (SM_BAR + 128)
#define SM_STA SM_X
#define SM_STB (SM_STA + 65536)
#define SM_STC (SM_STB + 65536)
#define NA1_ ((SM_BAR - SM_STC) / 4096)
#define NA1 (NA < NA1_ ? NA : NA1_)
static_assert(SM_STC + NA1 * 4096 <= SM_BAR && NB + NA - NA1 <= 16 && SM_PROF + 3072 <= SM_BAR, "staging");
static_assert(SM_TOTAL <= 232448, "smem");
#define BAR_XA 32
#define BAR_KV 40
#define BAR_PI 48
#define SM_ROLE (SM_BAR + 64)

#define SPIN_LIMIT (1 << 20)
#define RPOS 20
#define VPOS 0
#define CPOS 4
#define DLY_V 400
#define XPOS 2
#define CFAR 1
#define SD 0x0000

template <int ID, int N> DEVI void bsync() { asm volatile("bar.sync %0, %1;" ::"n"(ID), "n"(N) : "memory"); }
template <int ID, int N> DEVI void barv() { asm volatile("bar.arrive %0, %1;" ::"n"(ID), "n"(N) : "memory"); }

#define PT(n)
#define PC(n, v)
#define PDUMP()
#define REFRESH() asm volatile("xor.b32 %0, %0, %1;" : "+r"(l16) : "r"(zero))
#define OPQ(x) asm volatile("xor.b32 %0, %0, %1;" : "+r"(x) : "r"(zero))
#define SF() asm volatile("pmevent 1;" ::: "memory")
#define MF() __syncwarp()
#define SB0 1024u

#define XDOFF(ks) ((((ks) >> 2) * 1024 + ((ks) & 3) * 32) >> 4)
template <int SC>
DEVI void wg_ss32t(float (&d)[16], uint64_t da, uint64_t db) {
    if (SC) {
        asm volatile("wgmma.mma_async.sync.aligned.m64n32k16.f32.bf16.bf16 "
                     "{%0,%1,%2,%3,%4,%5,%6,%7,%8,%9,%10,%11,%12,%13,%14,%15}, %16, %17, 1, 1, 1, 1, 0;"
                     : "+f"(d[0]), "+f"(d[1]), "+f"(d[2]), "+f"(d[3]), "+f"(d[4]), "+f"(d[5]), "+f"(d[6]), "+f"(d[7]),
                       "+f"(d[8]), "+f"(d[9]), "+f"(d[10]), "+f"(d[11]), "+f"(d[12]), "+f"(d[13]), "+f"(d[14]), "+f"(d[15])
                     : "l"(da), "l"(db));
    } else {
        asm volatile("wgmma.mma_async.sync.aligned.m64n32k16.f32.bf16.bf16 "
                     "{%0,%1,%2,%3,%4,%5,%6,%7,%8,%9,%10,%11,%12,%13,%14,%15}, %16, %17, 0, 1, 1, 1, 0;"
                     : "=f"(d[0]), "=f"(d[1]), "=f"(d[2]), "=f"(d[3]), "=f"(d[4]), "=f"(d[5]), "=f"(d[6]), "=f"(d[7]),
                       "=f"(d[8]), "=f"(d[9]), "=f"(d[10]), "=f"(d[11]), "=f"(d[12]), "=f"(d[13]), "=f"(d[14]), "=f"(d[15])
                     : "l"(da), "l"(db));
    }
}

DEVI void delay_until(uint32_t t0, uint32_t d) { t0 += d; while (clk() < t0) {} }

template <int I0, int I1>
DEVI void xmma(float (&xa)[16], float (&xb)[16], uint32_t w, int ps, uint32_t zero, const uint32_t (&Wq)[16][4], const uint32_t (&Wk)[16][4],
               const uint32_t (&Wv)[NA][4]) {
    const uint64_t xd = mkdesc(SB0 + SM_X, 16, 4096) + (ps & 1) * 1024, vd = mkdesc(SB0 + SM_WV, 8192, 1024);
    uint32_t vo = (w >> 2) * (WV_BOX / 16);
    if (I0 < 16 - NA) OPQ(vo);
#pragma unroll
    for (int i = I0; i < I1; i++) {
        if (i == 0) wg_ss32t<0>(xb, (vd & ~0xFFFFFFFFull) | ((uint32_t)vd + vo), xd + XDOFF(NA));
        else if (i < 16 - NA) wg_ss32t<1>(xb, (vd & ~0xFFFFFFFFull) | ((uint32_t)vd + i * 128 + vo), xd + XDOFF(NA + i));
        else if (i == 16 - NA) wg_rs32<0>(xa, Wq[0], xd);
        else if (i < 32 - NA) wg_rs32<1>(xa, Wq[(i + NA) & 15], xd + XDOFF((i + NA) & 15));
        else if (i < 32) wg_rs32<1>(xb, Wv[(i + NA) & 15], xd + XDOFF((i + NA) & 15));
        else if (i == 32) wg_rs32<0>(xa, Wk[0], xd);
        else wg_rs32<1>(xa, Wk[i & 15], xd + XDOFF(i & 15));
    }
    wg_commit();
}
#define XMMA(I0, I1) xmma<(I0), (I1)>(xa, xb, w, p ^ 1, zero, Wq, Wk, Wv)
DEVI void wg_done(float (&d)[16]) {
    asm volatile("" : "+f"(d[0]), "+f"(d[1]), "+f"(d[2]), "+f"(d[3]), "+f"(d[4]), "+f"(d[5]), "+f"(d[6]), "+f"(d[7]),
                      "+f"(d[8]), "+f"(d[9]), "+f"(d[10]), "+f"(d[11]), "+f"(d[12]), "+f"(d[13]), "+f"(d[14]), "+f"(d[15]) :: "memory");
}
template <int M>
DEVI void xpack(uint32_t (&xp)[8], float (&xa)[16]) {
    wg_done(xa);
#pragma unroll
    for (int i = 0; i < 4; i++) {
        xp[2 * i] = pack2(xa[4 * i], xa[4 * i + (M < 2 ? 2 : 1)]);
        xp[2 * i + 1] = pack2(xa[4 * i + (M < 2 ? 1 : 2)], xa[4 * i + 3]);
    }
}
template <int M>
DEVI uint4 xpeer(uint32_t sb, int ps, uint32_t t16) { return lds128(sb + SM_PI + ((ps & 1) ^ 1) * 12288 + M * 4096 + t16); }
template <int M>
DEVI void xpark(const uint32_t (&xp)[8], const uint4& pi, uint32_t sb, uint32_t sbw, int ps, uint32_t t16, uint32_t KA) {
    const uint32_t a = SM_XO + M * 2048 + (M < 2 ? (KA & 0xFF) + sbw : (t16 >> 1) + sb);
    sts64(a, hadd2(xp[0], pi.x), hadd2(xp[1], pi.y));
    sts64(a + 6144, hadd2(xp[2], pi.z), hadd2(xp[3], pi.w));
    asm volatile("st.async.weak.shared::cluster.mbarrier::complete_tx::bytes.v4.b32 [%0], {%1,%2,%3,%4}, [%5];"
                 ::"r"((sb ^ 0x1000000) + SM_PI + (ps & 1) * 12288 + M * 4096 + t16), "r"(xp[4]), "r"(xp[5]), "r"(xp[6]), "r"(xp[7]),
                   "r"((sb ^ 0x1000000) + SM_BAR + BAR_PI + (ps & 1) * 8) : "memory");
}
template <int M>
DEVI void xfinish(float (&xa)[16], uint32_t sb, uint32_t sbw, int ps, uint32_t t16, uint32_t KA) {
    uint32_t xp[8];
    const uint4 pi = xpeer<M>(sb, ps, t16);
    xpack<M>(xp, xa);
    xpark<M>(xp, pi, sb, sbw, ps, t16, KA);
}
DEVI void piwait(uint32_t sb, int p, int ps) { mbar_wait(sb + SM_BAR + BAR_PI + p * 8, ((ps + NPRO + 1) >> 1) & 1); }

DEVI uint32_t par(uint32_t off) { return __popc(off & 0xB2000u) & 1; }
DEVI uint32_t probe(uint32_t lo, uint32_t hi) {
    uint32_t best = 0xFFFFFFFFu, x = 0;
    stg1<0>(lo, hi, 0);
#pragma unroll 1
    for (int r = 0; r < 4; r++) {
        const uint32_t t0 = clk();
        asm volatile("{\n.reg .b64 a;\nmov.b64 a, {%1,%2};\natom.relaxed.gpu.global.add.u32 %0, [a], 2;\n}" : "=r"(x) : "r"(lo), "r"(hi) : "memory");
        if (x == 0xFFFFFFFFu) die(1 << 23);
        best = min(best, clk() - t0);
    }
    return best;
}

DEVI void xload(uint32_t sb, uint32_t u, uint32_t j, int ps, const CUtensorMap* tmx) {
    if (elect()) {
        const uint32_t sg = ps + 4 - (u & 1) + (u >> 1);
        mbar_expect(sb + SM_BAR + BAR_XA, sg < NSEG ? 4096 : 0);
        if (sg < NSEG) tma3d(sb + SM_X + (ps & 1) * 16384 + u * 4096, tmx, sb + SM_BAR + BAR_XA, 0, sg * 32 + (j ^ ((u & 1) * 2 + (u >> 1))) * 8, j * 4);
    }
}
DEVI uint32_t rpage(uint32_t j, int s) { return (s & 3) * 65536 + (j & 1) * 8192 + (((s ^ (s >> 1) ^ j ^ (j >> 1)) & 1) << 12); }

#define RLOAD(a) { m0 = ldg4<XO_R>(a, xhi); n0 = ldg4<XO_R + 16384>(a, xhi); \
                   e0 = ldg1<XO_R + 32768>(((a) & ~0xFFFu) + (((a) & 0xFFF) >> 2), xhi); f0 = ldg1<XO_R + 33792>(((a) & ~0xFFFu) + (((a) & 0xFFF) >> 2), xhi); }
DEVI bool ruse(uint32_t a, const uint4& m0, const uint4& n0, uint32_t e0, uint32_t f0) {
    const uint32_t a0 = hadd2(m0.w, n0.w), b0 = hadd2(e0, f0);
    stsm4(a, hadd2(m0.x, n0.x), hadd2(m0.y, n0.y), hadd2(m0.z, n0.z), __byte_perm(a0, b0, 0x5410));
    return __any_sync(0xFFFFFFFFu, (a0 & b0 & 0x42000000u) != 0x42000000u);
}

template <bool MAIN>
DEVI void helper_step(uint32_t sb, uint32_t w, uint32_t h, uint32_t j, uint32_t& l16, uint32_t xlo, uint32_t xhi, uint32_t zero, int s,
                      const CUtensorMap* tmx, const bf16* __restrict__ mem0) {
    const uint32_t u = w - 8, bq = sb + SM_BAR;
    bsync<1, 384>();
    PT(0);
    PDUMP();
    PT(1);
    if (MAIN) {
        const uint32_t ctag = ((s >> 1) & 1) ^ 1;
        const uint32_t av = xlo + ((s & 1) * 32 + h) * 8192 + u * 512;
        mbar_wait(bq + BAR_XA, (s + NPRO) & 1);
        bsync<8, 384>();
        delay_until(clk(), DLY_V);
        PT(4);
        int it = 0;
        bool bad;
        do {
            const uint4 d1 = ldg4<XO_CV>(av + (j ^ 1) * 2048 + l16, xhi);
            const uint4 d2 = ldg4<XO_CV>(av + (j ^ 2) * 2048 + l16, xhi);
            const uint4 d3 = ldg4<XO_CV>(av + (j ^ 3) * 2048 + l16, xhi);
            bad = any_bad(or3(tagx2(d1.x, d1.z, ctag), tagx2(d2.x, d2.z, ctag), tagx2(d3.x, d3.z, ctag)));
            sts128(sb + SM_VS + u * 512 + l16, hadd2(hadd2(d1.x, d2.x), d3.x), hadd2(hadd2(d1.y, d2.y), d3.y), hadd2(hadd2(d1.z, d2.z), d3.z),
                   hadd2(hadd2(d1.w, d2.w), d3.w));
            REFRESH();
            if (++it > SPIN_LIMIT) die(it);
        } while (bad);
        PC(26, it - 1);
    } else {
        if (u == 0) stg2<XO_FL>(xlo + ((s + NPRO) * 128 + h * 4 + j) * 32, xhi, 1, 1);
        if (s == -NPRO) {
            xload(sb, u, j, s, tmx);
#pragma unroll 1
            for (int e = 0; e < 4; e++) sts128(sb + SM_TR + 4096 + e * 2048 + u * 512 + l16, 0, 0, 0, 0);
        }
        if (s == -1) {
#pragma unroll 1
            for (int e = 0; e < 2; e++) {
                const uint32_t d = e * 128 + u * 32 + (l16 >> 4);
                const unsigned short* m0 = (const unsigned short*)mem0 + j * 256 + d;
                uint32_t v[4];
#pragma unroll
                for (int i = 0; i < 4; i++) v[i] = (uint32_t)m0[(2 * i) * DM] | ((uint32_t)m0[(2 * i + 1) * DM] << 16);
                sts128(sb + SM_MEMT + d * 16, v[0], v[1], v[2], v[3]);
            }
        }
        mbar_wait(bq + BAR_XA, (s + NPRO) & 1);
    }
    PT(5);
    barv<5, 384>();
    bsync<3, 384>();
    if (!MAIN) {
        int it = 0;
        while (__any_sync(0xFFFFFFFFu, ldg2<XO_FL>(xlo + ((s + NPRO) * 128 + h * 4) * 32 + ((l16 & 0x30) << 1), xhi).x == 0))
            if (++it > SPIN_LIMIT) die(it);
    }
    if (u < 2) {
        asm volatile("fence.proxy.async.shared::cta;" ::: "memory");
        if (MAIN && SD) delay_until(clk(), ((SD >> (4 * u)) & 15) * 100);
        if (elect()) {
            const uint32_t sg = s + 3 - u;
            if (sg < NSEG) {
                const uint32_t ga = xlo + XO_XG + (((sg & 7) * 32 + h) * 4 + (j ^ (2 * u))) * 6144, sa = sb + SM_XO + u * 6144;
                if (u == 0) bulk_s2g(ga, xhi, sa, 6144);
                else bulk_red(ga, xhi, sa, 6144);
            }
        }
    }
    PT(6);
    uint32_t old = 0;
    if (XPOS == 0) xload(sb, u, j, s + 1, tmx);
    if (MAIN && u > 0) asm volatile("{\n.reg .b64 a;\nmov.b64 a, {%1,%2};\natom.relaxed.gpu.global.exch.b32 %0, [a], 0;\n}"
                                    : "=r"(old) : "r"(xlo + XO_R + rpage(j, s + 2) + (u - 1) * 16384 + h * 128 + (l16 >> 2)), "r"(xhi) : "memory");
    PT(7);
    if (MAIN) bsync<7, 384>();
    if (s >= -1 && s + 1 < NSEG && elect()) {
        const uint32_t o = u == 0 ? 0 : 2048;
        mbar_expect(bq + BAR_KV, 6144 - o);
        bulk_g2s(sb + SM_KV + u * 4096 + o, xlo + XO_XG + ((((s + 1) & 7) * 32 + h) * 4 + ((j + u) & 3)) * 6144 + o, xhi, 6144 - o, bq + BAR_KV);
    }
    if (XPOS == 1) xload(sb, u, j, s + 1, tmx);
    if (u < 2) {
        asm volatile("cp.async.bulk.wait_group.read 0;" ::: "memory");
        if (elect()) mbar_expect(bq + BAR_PI + ((s & 1) ^ 1) * 8, !MAIN && s == -NPRO ? 0 : 6144);
    }
    PT(8);
    if (XPOS == 2) {
        if (MAIN && s + 1 < NSEG) bsync<10, 384>();
        xload(sb, u, j, s + 1, tmx);
    }
    asm volatile("cp.async.bulk.wait_group 0;" ::: "memory");
    if (s >= -1 && s + 1 < NSEG) mbar_wait(bq + BAR_KV, (s + 1) & 1);
    asm volatile("lop3.b32 %0, %0, %1, %2, 0x78;" : "+r"(l16) : "r"(old), "r"(zero));
    PT(15);
}

__global__ void __cluster_dims__(2, 1, 1) __launch_bounds__(384, 1)
chain_kernel(const __grid_constant__ CUtensorMap tmq, const __grid_constant__ CUtensorMap tmk,
             const __grid_constant__ CUtensorMap tmv, const __grid_constant__ CUtensorMap tmo,
             const __grid_constant__ CUtensorMap tmx, const bf16* __restrict__ mem0, const bf16* __restrict__ xg,
             uint32_t xlo, uint32_t xhi, uint32_t zero, int nseg) {
    extern __shared__ __align__(1024) uint8_t smem[];
    if ((smem_u32(smem) & 0xFFFFFF) != SB0) die(1 << 23);
    asm volatile("griddepcontrol.launch_dependents;" ::: "memory");
    const uint32_t w = __reduce_max_sync(0xFFFFFFFFu, threadIdx.x >> 5);
    const uint32_t rk = smem_u32(smem) & 0x1000000;
    const uint32_t sb = __reduce_max_sync(0xFFFFFFFFu, smem_u32(smem));
    const uint32_t bq = sb + SM_BAR, bk = bq + 8, bv = bq + 16, bo = bq + 24;
    uint32_t l16 = __shfl_sync(0xFFFFFFFFu, (threadIdx.x & 31) * 16, threadIdx.x & 31);
    if (threadIdx.x == 0) {
        mbar_init(bq, 1); mbar_init(bk, 1); mbar_init(bv, 1); mbar_init(bo, 2);
        mbar_init(bq + BAR_XA, 4); mbar_init(bq + BAR_KV, 4); mbar_init(bq + BAR_PI, 2); mbar_init(bq + BAR_PI + 8, 2);
        asm volatile("fence.mbarrier_init.release.cluster;" ::: "memory");
        asm volatile("fence.proxy.async.shared::cta;" ::: "memory");
    }
    if (rk == 0) {
        if (w < 2 && l16 == 0) sts32(sb + SM_ROLE + w * 4, probe(xlo + XO_PB + w * 4096 + blockIdx.x * 16, xhi));
        __syncthreads();
        if (threadIdx.x == 0) {
            uint32_t side = (lds32(sb + SM_ROLE) < lds32(sb + SM_ROLE + 4) ? 0u : 1u) ^ par(XO_PB);
            uint32_t* tk = (uint32_t*)(((uint64_t)xhi << 32) | (xlo + XO_TK));
            uint32_t t = atomicAdd(tk + side, 1u);
            if (t >= 32) {
                uint2 c;
                int it = 0;
                do {
                    c = ldg2<XO_TK>(xlo, xhi);
                    if (++it > SPIN_LIMIT) die(it);
                } while (c.x + c.y != gridDim.x / 2);
                t += (side ? c.x : c.y) - 32;
                side ^= 1;
            }
            sts32(sb + SM_ROLE + 8, t * 4 + side * 2);
        }
    }
    __syncthreads();
    asm volatile("barrier.cluster.arrive.release.aligned;\nbarrier.cluster.wait.acquire.aligned;" ::: "memory");
    uint32_t role;
    asm volatile("ld.shared::cluster.u32 %0, [%1];" : "=r"(role) : "r"(SB0 + SM_ROLE + 8) : "memory");
    role = __reduce_max_sync(0xFFFFFFFFu, role) + (rk >> 24);
    asm volatile("barrier.cluster.arrive.release.aligned;\nbarrier.cluster.wait.acquire.aligned;" ::: "memory");
    if (role >= 128) return;
    const uint32_t h = role >> 2, j = role & 3;

    if (w >= 8) {
        asm volatile("setmaxnreg.dec.sync.aligned.u32 24;");
        if (w == 8) {
            if (elect()) {
                mbar_expect(bq, 65536);
                tma2d(sb + SM_STA, &tmq, bq, h * 128, j * 256);
                tma2d(sb + SM_STA + 32768, &tmq, bq, h * 128 + 64, j * 256);
                mbar_expect(bk, 65536);
                tma2d(sb + SM_STB, &tmk, bk, h * 128, j * 256);
                tma2d(sb + SM_STB + 32768, &tmk, bk, h * 128 + 64, j * 256);
                mbar_expect(bv, (16 - NA + NA1) * 4096);
#pragma unroll 1
                for (int i = 0; i < 32; i++) {
                    const int ks = i >> 1, g = i & 1;
                    if (ks < NA1 || ks >= NA)
                        tma2d((ks < NA ? sb + SM_STC + g * (NA1 * 2048) + ks * 2048 : sb + SM_WV + g * WV_BOX + (ks - NA) * 2048), &tmv, bv, h * 128 + g * 64, j * 256 + ks * 16);
                }
                mbar_expect(bo, 4 * WO_BOX);
#pragma unroll 1
                for (int i = 0; i < 32 - 2 * NB; i++) {
                    const int ks = i >> 2, g = i & 3;
                    tma2d(sb + SM_WO + g * WO_BOX + ks * 2048, &tmo, bo, j * 256 + g * 64, h * 128 + (ks < NPE / 2 ? ks : ks + NB / 2) * 16);
                }
            }
        }
        bsync<9, 384>();
        if (w == 8) {
            if (elect()) {
                mbar_expect(bo, (NB + NA - NA1) * 4096);
#pragma unroll 1
                for (int i = 2 * NA1; i < 2 * NA; i++) {
                    const int ks = i >> 1, g = i & 1;
                    tma2d(sb + SM_STA + NB * 4096 + g * ((NA - NA1) * 2048) + (ks - NA1) * 2048, &tmv, bo, h * 128 + g * 64, j * 256 + ks * 16);
                }
#pragma unroll 1
                for (int i = 0; i < 2 * NB; i++) {
                    const int ks = i >> 2, g = i & 3;
                    tma2d(sb + SM_STA + g * (NB * 1024) + ks * 2048, &tmo, bo, j * 256 + g * 64, h * 128 + (ks + NPE / 2) * 16);
                }
                asm volatile("cp.async.bulk.prefetch.L2.global [%0], %1;" ::"l"((const char*)xg + role * 32768), "r"(32768) : "memory");
            }
        }
#pragma unroll 1
        for (int s = -NPRO; s < 0; s++) helper_step<false>(sb, w, h, j, l16, xlo, xhi, zero, s, &tmx, mem0);
#pragma unroll 1
        for (int s = 0; s < nseg; s++) helper_step<true>(sb, w, h, j, l16, xlo, xhi, zero, s, &tmx, mem0);
        piwait(sb, 0, nseg - 2);
    } else {
        asm volatile("setmaxnreg.inc.sync.aligned.u32 240;");
        uint32_t Wq[16][4], Wk[16][4], Wv[NA][4], Wo[NB > 0 ? NB : 1][4];
        uint32_t t16, KA, KB, KC, KD;
        {
            const uint32_t lane = l16 >> 4, g = lane >> 2, t = lane & 3;
            const uint32_t rw = (((lane >> 4) & 1) * 8 + (lane & 7)) * 128u;
            const uint32_t off = rw + ((((w & 3) * 2 + ((lane >> 3) & 1)) ^ (lane & 7)) << 4);
            const uint32_t offo = rw + ((((w & 1) * 4 + ((lane >> 3) & 1)) ^ (lane & 7)) << 4);
            const uint32_t r = 2 * (t & 1) + (g >> 2);
            const uint32_t mk0 = t < 2 ? 0 : (r == 0 ? 2 * g > w : j + r < 4), mk1 = t < 2 ? 0 : (r == 0 ? 2 * g + 1 > w : j + r < 4);
            t16 = __shfl_sync(0xFFFFFFFFu, w * 512 + l16, lane);
            KA = __shfl_sync(0xFFFFFFFFu, (w * 512 + t * 64 + g * 8) | ((w * 512 + (g & 1) * 256 + (g >> 1) * 64 + t * 16) << 16), lane);
            KB = __shfl_sync(0xFFFFFFFFu, ((w >> 2) * WV_BOX + off) | mk0 | (mk1 << 1) |
                                              ((w * 256 + (g >> 2) * 4096 + (g & 3) * 64 + t * 16) << 16), lane);
            KC = __shfl_sync(0xFFFFFFFFu, ((lane & 7) * 1280 + (lane >> 3) * 128 + ((w ^ (lane & 7)) << 4)) | (((t >> 1) * 16 + g * 2) << 16) | ((t * 64 + g * 8) << 24), lane);
            KD = __shfl_sync(0xFFFFFFFFu, ((w >> 1) * WO_BOX + offo) | (((lane & 7) * 208 + (lane >> 3) * 16) << 16), lane);
            mbar_wait(bq, 0);
#pragma unroll
            for (int ks = 0; ks < 16; ks++) ldsm4t(Wq[ks], sb + SM_STA + (w >> 2) * 32768 + off + ks * 2048);
            asm volatile("fence.proxy.async.shared::cta;" ::: "memory");
            barv<9, 384>();
            mbar_wait(bk, 0);
#pragma unroll
            for (int ks = 0; ks < 16; ks++) ldsm4t(Wk[ks], sb + SM_STB + (w >> 2) * 32768 + off + ks * 2048);
            mbar_wait(bv, 0);
#pragma unroll
            for (int ks = 0; ks < NA1; ks++) ldsm4t(Wv[ks], sb + SM_STC + (w >> 2) * (NA1 * 2048) + off + ks * 2048);
            mbar_wait(bo, 0);
#pragma unroll
            for (int ks = NA1; ks < NA; ks++) ldsm4t(Wv[ks], sb + SM_STA + NB * 4096 + (w >> 2) * ((NA - NA1) * 2048) + off + (ks - NA1) * 2048);
#pragma unroll
            for (int i = 0; i < NB; i++) ldsm4t(Wo[i], sb + SM_STA + (w >> 1) * (NB * 1024) + (offo ^ ((i & 1) << 5)) + (i >> 1) * 2048);
            asm volatile("fence.proxy.async.shared::cta;" ::: "memory");
        }
        const uint32_t ONES = 0x3F803F80u;
#define UNI(x) __reduce_max_sync(0xFFFFFFFFu, x)
        const uint32_t sbw = UNI(sb + w * 256), sbm = UNI(sb - w * 512), sbs = UNI(sb + w * 768), sbp = UNI(sb + w * 208);
#define OPQALL() { OPQ(t16); OPQ(KA); OPQ(KB); OPQ(KC); OPQ(KD); }
        bsync<1, 384>();
        barv<3, 384>();
        bsync<5, 384>();
#pragma unroll 1
        for (int s2 = 1 - NPRO; s2 < 0; s2 += 2)
#pragma unroll
        for (int p = 0; p < 2; p++) {
            const int s = s2 + p;
            float xa[16], xb[16];
            wg_fence();
            XMMA(0, 32 - NA);
            XMMA(32 - NA, 32);
            piwait(sb, p, s - 2);
            wg_wait<1>();
            xfinish<0>(xa, sb, sbw, p ^ 1, t16, KA);
            wg_fence();
            XMMA(32, 48);
            bsync<1, 384>();
            wg_wait<1>();
            xfinish<2>(xb, sb, sbw, p ^ 1, t16, KA);
            wg_wait<0>();
            xfinish<1>(xa, sb, sbw, p ^ 1, t16, KA);
            barv<3, 384>();
            bsync<5, 384>();
            OPQALL();
        }
        const uint32_t cb0 = (h >> 1) * 32768 + (j & 1) * 16384 + (h & 1) * 8192;
        const uint32_t cb = xlo + cb0 + ((par(cb0) ^ (j >> 1) ^ CFAR) << 12);
        const uint32_t uox = xlo + XO_OX + (h * 2 + (w >> 2)) * 16384 + j * 1024 + (w & 3) * 256 - w * 128;
        uint32_t ov0, ov1;
#define OXSTORE(s) asm volatile("{\n.reg .b64 a;\nmov.b64 a, {%0,%1};\nst.global.u32 [a], %2;\nst.global.u32 [a+128], %3;\n}" \
                                ::"r"(uox + (t16 >> 2) + ((s) >> 2) * (1u << 20) + ((s) & 3) * 4096), "r"(xhi), "r"(ov0), "r"(ov1) : "memory")
#pragma unroll 1
        for (int s2 = 0;; s2 += 2)
#pragma unroll
        for (int p = 0; p < 2; p++) {
            const int s = s2 + p;
            const uint32_t ctag = ((s2 >> 1) & 1) ^ 1;
            const uint32_t hb = cb ^ (p * 0x81000), rb = xlo + rpage(j, s);
            uint4 k0, k1, qq;
            {
                float xa[16], xb[16];
                uint4 m0, n0;
                uint32_t e0, f0, a = xlo + rpage(j, s - 1) + t16;
                uint32_t xp[8];
                wg_fence();
                XMMA(0, 6);
                SF();
                piwait(sb, p, s - 2);
                uint4 pi = xpeer<0>(sb, p ^ 1, t16);
                SF();
                wg_fence();
                XMMA(6, RPOS);
                XMMA(RPOS, RPOS + 4);
                wg_wait<1>();
                SF();
                PT(11);
                RLOAD(a);
                SF();
#define QPOS (RPOS >= 32 - NA ? RPOS : RPOS + 4 >= 32 - NA ? RPOS + 4 : 32 - NA)
                if (QPOS > RPOS) {
                    wg_fence();
                    if (QPOS > RPOS + 4) XMMA(RPOS + 4, QPOS);
                    XMMA(QPOS, QPOS + 4);
                    wg_wait<1>();
                    SF();
                }
                xpack<0>(xp, xa);
                xpark<0>(xp, pi, sb, sbw, p ^ 1, t16, KA);
                pi = xpeer<2>(sb, p ^ 1, t16);
                SF();
                if (QPOS + 4 < 32) {
                    wg_fence();
                    XMMA(QPOS + 4, 32);
                    SF();
                }
                if (VPOS == 0) {
                    wg_wait<0>();
                    xpack<2>(xp, xb);
                    xpark<2>(xp, pi, sb, sbw, p ^ 1, t16, KA);
                    SF();
                }
                PT(12);
                if (p == 1 || s2 > 0) {
                    int it = 0;
                    while (ruse(sb + SM_MEMT + t16, m0, n0, e0, f0)) {
                        OPQ(a);
                        RLOAD(a);
                        if (++it > SPIN_LIMIT) die(it);
                    }
                    PC(22, it + 1);
                }
                PT(13);
                OPQ(KA); OPQ(t16);
                uint32_t acw = hb + (KA & 0xFFFF), ahi = xhi, tg = ctag;
                OPQ(acw); OPQ(ahi); OPQ(tg);
                uint32_t swi;
                asm volatile("{\n.reg .b64 a;\n.reg .b32 l;\nmov.b64 a, 0;\ncvta.shared.u64 a, a;\nmov.b64 {l, %0}, a;\n}" : "=r"(swi));
                SF();
                bsync<1, 384>();
                PT(0);
                uint32_t b[8][4];
#pragma unroll
                for (int i = 0; i < 8; i++) {
                    const int pp = i < 2 ? i : i ^ 1;
                    ldsm4t(b[pp], sbm + SM_MEMT + t16 + pp * 512);
                    if (i < 7) MF();
                    if (i == 3 && VPOS == 1) {
                        wg_wait<0>();
                        xpack<2>(xp, xb);
                        xpark<2>(xp, pi, sb, sbw, p ^ 1, t16, KA);
                    }
                }
                float q[4], k[4];
                const uint32_t aWv = sb + SM_WV + (KB & 0xFFF0);
                uint32_t wv[16 - NA > 0 ? 16 - NA : 1][4];
#define WVLD(n0, n1) _Pragma("unroll") for (int n = (n0); n < (n1) && n < 16 - NA; n++) ldsm4t(wv[n], aWv + n * 2048)
#pragma unroll
                for (int ks = 0; ks < 16; ks++) {
                    const uint32_t b0 = b[ks >> 1][(ks & 1) * 2], b1 = b[ks >> 1][(ks & 1) * 2 + 1];
                    if (ks == 0) {
                        mma16z(q, Wq[0][0], Wq[0][1], Wq[0][2], Wq[0][3], b0, b1);
                        mma16z(k, Wk[0][0], Wk[0][1], Wk[0][2], Wk[0][3], b0, b1);
                    } else {
                        mma16(q, Wq[ks][0], Wq[ks][1], Wq[ks][2], Wq[ks][3], b0, b1);
                        mma16(k, Wk[ks][0], Wk[ks][1], Wk[ks][2], Wk[ks][3], b0, b1);
                    }
                    if (ks == 10 && VPF) { SF(); WVLD(0, VPF); }
                }
                const uint32_t oq0 = settag(pack2(q[0], q[2]), tg), oq1 = settag(pack2(q[1], q[3]), tg);
                const uint32_t ok0 = pack2(k[0], k[2]), ok1 = pack2(k[1], k[3]);
                stg2<XO_CQK>(acw, ahi, oq0, ok0);
                stg2<XO_CQK + 256>(acw, ahi, oq1, ok1);
                SF();
                PT(1);
                asm volatile("{\n.reg .b64 a;\nmov.b64 a, {%0,%1};\nst.v2.u32 [a], {%2,%3};\nst.v2.u32 [a+256], {%4,%5};\n}"
                             ::"r"((KA & 0xFFF) + (sb ^ 0x1000000) + SM_TR + 4096 + p * 4096), "r"(swi), "r"(oq0), "r"(ok0), "r"(oq1), "r"(ok1) : "memory");
                sts64(sb + SM_TR + (KA & 0xFFF), oq0, ok0);
                sts64(sb + SM_TR + (KA & 0xFFF) + 256, oq1, ok1);
                int nl = VPF;
#pragma unroll
                for (int rd = 0; rd < 8; rd++) {
                    const int pp = (VORD >> (28 - 4 * rd)) & 7;
                    const uint32_t* a = 2 * pp < NA ? Wv[2 * pp < NA ? 2 * pp : 0] : wv[2 * pp < NA ? 0 : 2 * pp - NA];
                    const uint32_t* c = 2 * pp < NA ? Wv[2 * pp < NA ? 2 * pp + 1 : 0] : wv[2 * pp < NA ? 0 : 2 * pp + 1 - NA];
                    if (rd == 0) {
                        mma16z(q, a[0], a[1], a[2], a[3], b[pp][0], b[pp][1]);
                        mma16z(k, c[0], c[1], c[2], c[3], b[pp][2], b[pp][3]);
                    } else {
                        mma16(q, a[0], a[1], a[2], a[3], b[pp][0], b[pp][1]);
                        mma16(k, c[0], c[1], c[2], c[3], b[pp][2], b[pp][3]);
                    }
                    if (nl < 16 - NA) {
                        SF();
                        WVLD(nl, nl + (2 * pp < NA ? 1 : 3));
                        nl += 2 * pp < NA ? 1 : 3;
                    } else if (nl < 32) {
                        SF();
                        asm volatile("" ::"r"(oq0), "r"(oq1), "r"(ok0), "r"(ok1));
                        k0 = lds128(sb + SM_KV + 2048 + (KB >> 16));
                        nl = 32;
                    } else if (nl == 32) {
                        SF();
                        k1 = lds128(sb + SM_KV + 10240 + (KB >> 16));
                        qq = lds128(sbw + SM_KV + ((KA >> 16) & 0xFF));
                        nl = 33;
                    }
                }
                ov0 = pack2(q[0] + k[0], q[1] + k[1]);
                ov1 = pack2(q[2] + k[2], q[3] + k[3]);
                stg2<XO_CV>(xlo + ((p * 32 + h) * 4 + j) * 2048 + (t16 >> 1), xhi, settag(ov0, tg), ov1);
                barv<8, 384>();
            }
            OPQ(t16);
            SF();
            PT(2);
            PDUMP();
            {
                const uint32_t a0 = sb + SM_KV;
#define CLOADG() { c2 = ldg4<XO_CQK>((hb ^ 0x1000) + (KA >> 16), xhi); c3 = ldg4<XO_CQK>((hb ^ 0x5000) + (KA >> 16), xhi); }
#define CLOADS() { c0 = lds128(sb + SM_TR + (KA >> 16)); c1 = lds128(sb + SM_TR + 4096 + p * 4096 + (KA >> 16)); }
                uint4 c0, c1, c2, c3;
                float xa[16], xb[16];
                wg_fence();
                XMMA(32, 32 + CPOS);
                SF();
                c0 = lds128(sb + SM_TR + (KA >> 16));
                const uint4 pi = xpeer<1>(sb, p ^ 1, t16);
                SF();
                wg_fence();
                XMMA(32 + CPOS, 36 + CPOS);
                wg_wait<1>();
                SF();
                CLOADG();
                SF();
                c1 = lds128(sb + SM_TR + 4096 + p * 4096 + (KA >> 16));
                SF();
                wg_fence();
                XMMA(36 + CPOS, 48);
                SF();
                const uint32_t ka[4] = {k0.x, k0.y, k0.z, k0.w}, kb[4] = {k1.x, k1.y, k1.z, k1.w};
                const uint2 qx = (t16 & 64) ? make_uint2(qq.y, qq.w) : make_uint2(qq.x, qq.z);
                const uint32_t aSp = sb + SM_SP + (KC & 0xFFFF);
                uint32_t qx0 = qx.x, qx1 = qx.y;
                wg_wait<0>();
                {
                    uint32_t xp[8];
                    float sd[4], se[4];
                    xpack<1>(xp, xa);
                    mma16z(sd, ka[0], ka[1], ka[2], ka[3], qx0, qx1);
                    mma16z(se, kb[0], kb[1], kb[2], kb[3], qx0, qx1);
                    xpark<1>(xp, pi, sb, sbw, p ^ 1, t16, KA);
                    barv<3, 384>();
                    stsm4t(aSp + 512, pack2(sd[0], sd[1]), pack2(sd[2], sd[3]), pack2(se[0], se[1]), pack2(se[2], se[3]));
                }
                SF();
                PT(3);
#define SCORES() { \
                    const uint32_t qA = hadd2(hadd2(c0.x, c1.x), hadd2(c2.x, c3.x)), qB = hadd2(hadd2(c0.z, c1.z), hadd2(c2.z, c3.z)); \
                    float sa[4], sb_[4], sc[4]; \
                    mma16z(sa, ka[0], ka[1], ka[2], ka[3], qA, qB); \
                    mma16z(sb_, kb[0], kb[1], kb[2], kb[3], qA, qB); \
                    const uint32_t kA = hadd2(hadd2(c0.y, c1.y), hadd2(c2.y, c3.y)), kB = hadd2(hadd2(c0.w, c1.w), hadd2(c2.w, c3.w)); \
                    mma16z(sc, qA, qx0, qB, qx1, kA, kB); \
                    bad = any_bad(or3(tagx2(c1.x, c1.z, ctag), tagx2(c2.x, c2.z, ctag), tagx2(c3.x, c3.z, ctag))); \
                    stsm4t(aSp, pack2(sa[0], sa[1]), pack2(sa[2], sa[3]), pack2(sb_[0], sb_[1]), pack2(sb_[2], sb_[3])); \
                    stsm2(aSp + 1024, pack2(sc[0], sc[1]), pack2(sc[2], sc[3])); }
                int it = 0;
                bool bad;
                SCORES();
                while (__builtin_expect(bad, 0)) {
                    OPQ(KA);
                    CLOADG();
                    CLOADS();
                    SCORES();
                    if (++it > SPIN_LIMIT) die(it);
                }
                PC(25, it);
                PT(4);
                bsync<4, 256>();
                uint32_t wo[16 - NB][4];
                const uint32_t aWo = sb + SM_WO + (KD & 0xFFFF), aWo1 = sb + SM_WO + ((KD & 0xFFFF) ^ 32);
#define WOLD(n0, n1) _Pragma("unroll") for (int n = (n0); n < (n1) && n < 16 - NB; n++) ldsm4t(wo[n], ((n & 1) ? aWo1 : aWo) + (n >> 1) * 2048)
                const bool hi = (t16 & 32) != 0;
                const uint32_t t8 = t16 >> 1;
                uint2 v0, v1, v2, v3;
                uint32_t es;
                {
                    uint32_t am[4], ax[4], a4[2];
                    const uint32_t aSr = sbs + SM_SP + t16;
                    ldsm4t(am, aSr);
                    ldsm4t(ax, aSr + 512);
                    ldsm2t(a4, aSr + 1024);
                    MF();
                    const uint32_t se = (t16 & 128) ? 0u : ONES, so = se ^ ONES;
                    float hm[4], hx[4], h4[4];
                    mma16z(hm, am[0], am[1], am[2], am[3], se, so);
                    mma16z(hx, ax[0], ax[1], ax[2], ax[3], se, so);
                    mma8z(h4, a4[0], a4[1], ONES);
                    SF();
                    v0 = lds64(a0 + 4096 + t8); v1 = lds64(a0 + 8192 + t8); v2 = lds64(a0 + 12288 + t8); v3 = lds64(a0 + 16384 + t8);
                    WOLD(0, PF2);
                    float s0 = hi ? hx[0] : hm[0], s1 = hi ? hx[2] : hm[2];
                    const float s2 = hi ? h4[2] : h4[0];
                    s0 = (KB & 1) ? -1.0e9f * 11.313708499f : s0;
                    s1 = (KB & 2) ? -1.0e9f * 11.313708499f : s1;
                    int mi = __float_as_int(fmaxf(fmaxf(s0, s2), s1));
                    mi ^= (mi >> 31) & 0x7FFFFFFF;
                    const int mm = __reduce_max_sync(0xFFFFFFFFu, hi ? (int)0x80000000 : mi), mx = __reduce_max_sync(0xFFFFFFFFu, hi ? mi : (int)0x80000000);
                    SF();
                    WOLD(PF2, PF3);
                    SF();
                    mi = hi ? mx : mm;
                    mi ^= (mi >> 31) & 0x7FFFFFFF;
                    const float c2_ = 0.08838834764831845f * 1.4426950408889634f;
                    const float mc = __int_as_float(mi) * c2_;
                    const float e0 = ex2(fmaf(s0, c2_, -mc)), e1 = ex2(fmaf(s1, c2_, -mc)), e2 = ex2(fmaf(s2, c2_, -mc));
                    sts32(sbp + SM_P + (KC >> 25), pack2(e0, e1));
                    sts16(sbp + SM_P + 128 + ((KC >> 16) & 0xFF), pack2(e2, e2));
                    es = __float_as_uint(fmaf(e2, 0.5f, e0 + e1) + 64.f);
                }
                const uint32_t aPr = sb + SM_P + (KD >> 16);
                PT(5);
                bsync<5, 384>();
                uint32_t pm[4], px[4], p4[2];
                ldsm4(pm, aPr);
                const uint2 vs = lds64(sb + SM_VS + t8);
                ldsm2(p4, aPr + 128);
                ldsm4(px, aPr + 64);
                SF();
                WOLD(PF3, NPF);
                const uint32_t sm = __reduce_add_sync(0xFFFFFFFFu, hi ? 0u : es), sx = __reduce_add_sync(0xFFFFFFFFu, hi ? es : 0u);
                SF();
                const uint32_t vm0 = hadd2(ov0, vs.x), vm1 = hadd2(ov1, vs.y);
                float oa[4], ob[4];
                mma16z(oa, v0.x, v0.y, v1.x, v1.y, pm[0], pm[1]);
                mma16z(ob, v2.x, v2.y, v3.x, v3.y, pm[2], pm[3]);
                sts32f(sb + SM_DN + w * 8 + ((t16 >> 3) & 4), rcp(__uint_as_float((hi ? sx : sm) - 15u * 0x42800000u) - 64.f));
                mma8(oa, vm0, vm1, p4[0]);
                stsm2(sbw + SM_OT + (t16 & 511), pack2(oa[0] + ob[0], oa[1] + ob[1]), pack2(oa[2] + ob[2], oa[3] + ob[3]));
                PT(6);
                SF();
                bsync<6, 256>();
                mma16z(oa, v0.x, v0.y, v1.x, v1.y, px[0], px[1]);
                uint32_t b[4][4];
#define OTLD(pp) ldsm4t(b[pp], sbm + SM_OT + t16 + (pp) * 512)
                const float4 dn = lds128f(sb + SM_DN + (t16 & 48));
                MF();
                OTLD(0);
                MF();
                OTLD(1);
                barv<7, 384>();
                mma16(oa, v2.x, v2.y, v3.x, v3.y, px[2], px[3]);
                mma8(oa, vm0, vm1, p4[1]);
                SF();
                const float r0 = dn.x, r1 = dn.z;
                uint32_t ar = rb + (h & 1) * 16384 + t16, ae = rb + (h & 1) * 1024 + (t16 >> 2), ahi = xhi;
                float r[2][4];
#pragma unroll
                for (int ks = 0; ks < 8; ks++) {
                    if (ks == 0) { OTLD(2); MF(); WOLD(NPF, NPF + WPF); }
                    else if (ks == 3) { OTLD(3); MF(); }
                    if (ks > 0) WOLD(NPF + WPF + 2 * (ks - 1), NPF + WPF + 2 * ks);
                    if (ks == 0) {
                        ov0 = pack2(oa[0] * dn.y, oa[1] * dn.w);
                        ov1 = pack2(oa[2] * dn.y, oa[3] * dn.w);
                    }
                    if (ks == 5) { OPQ(ar); OPQ(ahi); OPQ(ae); }
#pragma unroll
                    for (int mt = 0; mt < 2; mt++) {
                        const int i = ks * 2 + mt;
                        const uint32_t* a = i < NPE ? wo[i < NPE ? i : 0] : i < NPE + NB ? Wo[i < NPE + NB ? i - NPE : 0] : wo[i < NPE + NB ? 0 : i - NB];
                        if (i < 2) mma16z(r[mt], a[0], a[1], a[2], a[3], b[ks >> 1][2 * (ks & 1)], b[ks >> 1][2 * (ks & 1) + 1]);
                        else mma16(r[mt], a[0], a[1], a[2], a[3], b[ks >> 1][2 * (ks & 1)], b[ks >> 1][2 * (ks & 1) + 1]);
                    }
                    if (NPF + WPF + 2 * ks < 16 - NB || ks == 2) SF();
                }
                if (p == 1 && s + 1 == nseg) goto done;
                asm volatile("{\n.reg .b64 a;\nmov.b64 a, {%0,%2};\nred.relaxed.gpu.global.add.noftz.v4.bf16x2 [a], {%3,%4,%5,%6};\n"
                             "mov.b64 a, {%1,%2};\nred.relaxed.gpu.global.add.noftz.bf16x2 [a+32768], %7;\n}"
                             ::"r"(ar), "r"(ae), "r"(ahi), "r"(pack2(r[0][0] * r0, r[0][1] * r1)), "r"(pack2(r[0][2] * r0, r[0][3] * r1)),
                               "r"(pack2(r[1][0] * r0, r[1][1] * r1)), "r"(pack2(r[1][2] * r0, 1.f)), "r"(pack2(r[1][3] * r1, 1.f)) : "memory");
                if (XPOS == 2) barv<10, 384>();
            }
            SF();
            PT(10);
            OXSTORE(s);
            OPQALL();
        }
    done:
        OXSTORE(nseg - 1);
    }
}

#define G2_STAGES 6
#define G2_STAGE_BYTES 32768
DEVI void wg_ss128t(float (&d)[64], uint64_t da, uint64_t db, int sc) {
    asm volatile("{\n.reg .pred p;\nsetp.ne.b32 p, %66, 0;\n"
                 "wgmma.mma_async.sync.aligned.m64n128k16.f32.bf16.bf16 "
                 "{%0,%1,%2,%3,%4,%5,%6,%7,%8,%9,%10,%11,%12,%13,%14,%15,%16,%17,%18,%19,%20,%21,%22,%23,%24,%25,%26,%27,%28,%29,%30,%31,"
                 "%32,%33,%34,%35,%36,%37,%38,%39,%40,%41,%42,%43,%44,%45,%46,%47,%48,%49,%50,%51,%52,%53,%54,%55,%56,%57,%58,%59,%60,%61,%62,%63}, "
                 "%64, %65, p, 1, 1, 1, 1;\n}\n"
                 : "+f"(d[0]), "+f"(d[1]), "+f"(d[2]), "+f"(d[3]), "+f"(d[4]), "+f"(d[5]), "+f"(d[6]), "+f"(d[7]),
                   "+f"(d[8]), "+f"(d[9]), "+f"(d[10]), "+f"(d[11]), "+f"(d[12]), "+f"(d[13]), "+f"(d[14]), "+f"(d[15]),
                   "+f"(d[16]), "+f"(d[17]), "+f"(d[18]), "+f"(d[19]), "+f"(d[20]), "+f"(d[21]), "+f"(d[22]), "+f"(d[23]),
                   "+f"(d[24]), "+f"(d[25]), "+f"(d[26]), "+f"(d[27]), "+f"(d[28]), "+f"(d[29]), "+f"(d[30]), "+f"(d[31]),
                   "+f"(d[32]), "+f"(d[33]), "+f"(d[34]), "+f"(d[35]), "+f"(d[36]), "+f"(d[37]), "+f"(d[38]), "+f"(d[39]),
                   "+f"(d[40]), "+f"(d[41]), "+f"(d[42]), "+f"(d[43]), "+f"(d[44]), "+f"(d[45]), "+f"(d[46]), "+f"(d[47]),
                   "+f"(d[48]), "+f"(d[49]), "+f"(d[50]), "+f"(d[51]), "+f"(d[52]), "+f"(d[53]), "+f"(d[54]), "+f"(d[55]),
                   "+f"(d[56]), "+f"(d[57]), "+f"(d[58]), "+f"(d[59]), "+f"(d[60]), "+f"(d[61]), "+f"(d[62]), "+f"(d[63])
                 : "l"(da), "l"(db), "r"(sc));
}

DEVI void gemm2(int tile, uint32_t xlo, uint32_t xhi, const CUtensorMap& tmb, bf16* __restrict__ out) {
    const uint32_t sb = SB0;
    const uint32_t bars = sb + G2_STAGES * G2_STAGE_BYTES;
    const int tid = threadIdx.x, lane = tid & 31;
    const int w = __shfl_sync(0xFFFFFFFFu, tid >> 5, 0);
    const int bm = tile >> 3, bn = tile & 7;
    if (tid == 0) {
        for (int i = 0; i < G2_STAGES; i++) { mbar_init(bars + i * 8, 1); mbar_init(bars + (G2_STAGES + i) * 8, 2); }
        asm volatile("fence.mbarrier_init.release.cluster;" ::: "memory");
        asm volatile("fence.proxy.async.shared::cta;" ::: "memory");
    }
    __syncthreads();
    const int NK = HD / 64;
    if (w == 8) {
        if (lane == 0) {
            for (int kb = 0; kb < G2_STAGES; kb++) {
                const uint32_t dst = sb + kb * G2_STAGE_BYTES;
                mbar_expect(bars + kb * 8, G2_STAGE_BYTES);
                tma2d(dst + 16384, &tmb, bars + kb * 8, bn * 128, kb * 64);
                tma2d(dst + 24576, &tmb, bars + kb * 8, bn * 128 + 64, kb * 64);
            }
            asm volatile("griddepcontrol.wait;" ::: "memory");
            for (int kb = 0; kb < G2_STAGES; kb++)
                bulk_g2s(sb + kb * G2_STAGE_BYTES, xlo + XO_OX + (bm * 64 + kb) * 16384, xhi, 16384, bars + kb * 8);
            int st = 0, ph = 0;
            for (int kb = G2_STAGES; kb < NK; kb++) {
                mbar_wait(bars + (G2_STAGES + st) * 8, ph);
                const uint32_t dst = sb + st * G2_STAGE_BYTES;
                mbar_expect(bars + st * 8, G2_STAGE_BYTES);
                bulk_g2s(dst, xlo + XO_OX + (bm * 64 + kb) * 16384, xhi, 16384, bars + st * 8);
                tma2d(dst + 16384, &tmb, bars + st * 8, bn * 128, kb * 64);
                tma2d(dst + 24576, &tmb, bars + st * 8, bn * 128 + 64, kb * 64);
                if (++st == G2_STAGES) { st = 0; ph ^= 1; }
            }
        }
    } else if (w < 8) {
        const int wg = w >> 2;
        float acc[64];
        int st = 0, ph = 0;
        for (int kb = 0; kb < NK; kb++) {
            mbar_wait(bars + st * 8, ph);
            const uint32_t base = sb + st * G2_STAGE_BYTES;
            const uint64_t da = mkdesc(base + wg * 8192, 128, 1024) & ~((uint64_t)3 << 62);
            const uint64_t db = mkdesc(base + 16384, 8192, 1024);
            wg_fence();
#pragma unroll
            for (int k = 0; k < 4; k++) wg_ss128t(acc, da + k * 16, db + k * 128, (kb | k) != 0);
            wg_commit();
            if (kb > 0) {
                wg_wait<1>();
                const int pst = st == 0 ? G2_STAGES - 1 : st - 1;
                if ((tid & 127) == 0) mbar_arrive(bars + (G2_STAGES + pst) * 8);
            }
            if (++st == G2_STAGES) { st = 0; ph ^= 1; }
        }
        wg_wait<0>();
        const int row = bm * 128 + wg * 64 + (w & 3) * 16 + (lane >> 2);
        bf16* o = out + (size_t)row * 2048 + bn * 128 + (lane & 3) * 2;
#pragma unroll
        for (int i = 0; i < 16; i++) {
            *(uint32_t*)(o + i * 8) = pack2(acc[4 * i], acc[4 * i + 1]);
            *(uint32_t*)(o + 8 * 2048 + i * 8) = pack2(acc[4 * i + 2], acc[4 * i + 3]);
        }
    }
}

#define D4(c, i) #c "f"(d[i]), #c "f"(d[i + 1]), #c "f"(d[i + 2]), #c "f"(d[i + 3])
template <int SC> DEVI void wg_rs128t(float (&d)[64], const uint32_t (&a)[4], uint64_t db) {
    if (SC) asm volatile("wgmma.mma_async.sync.aligned.m64n128k16.f32.bf16.bf16 "
        "{%0,%1,%2,%3,%4,%5,%6,%7,%8,%9,%10,%11,%12,%13,%14,%15,%16,%17,%18,%19,%20,%21,%22,%23,%24,%25,%26,%27,%28,%29,%30,%31,%32,%33,%34,%35,%36,%37,%38,%39,%40,%41,%42,%43,%44,%45,%46,%47,%48,%49,%50,%51,%52,%53,%54,%55,%56,%57,%58,%59,%60,%61,%62,%63}, "
        "{%64,%65,%66,%67}, %68, 1, 1, 1, 1;"
        : D4(+, 0), D4(+, 4), D4(+, 8), D4(+, 12), D4(+, 16), D4(+, 20), D4(+, 24), D4(+, 28), D4(+, 32), D4(+, 36), D4(+, 40), D4(+, 44), D4(+, 48), D4(+, 52), D4(+, 56), D4(+, 60) : "r"(a[0]), "r"(a[1]), "r"(a[2]), "r"(a[3]), "l"(db));
    else asm volatile("wgmma.mma_async.sync.aligned.m64n128k16.f32.bf16.bf16 "
        "{%0,%1,%2,%3,%4,%5,%6,%7,%8,%9,%10,%11,%12,%13,%14,%15,%16,%17,%18,%19,%20,%21,%22,%23,%24,%25,%26,%27,%28,%29,%30,%31,%32,%33,%34,%35,%36,%37,%38,%39,%40,%41,%42,%43,%44,%45,%46,%47,%48,%49,%50,%51,%52,%53,%54,%55,%56,%57,%58,%59,%60,%61,%62,%63}, "
        "{%64,%65,%66,%67}, %68, 0, 1, 1, 1;"
        : D4(=, 0), D4(=, 4), D4(=, 8), D4(=, 12), D4(=, 16), D4(=, 20), D4(=, 24), D4(=, 28), D4(=, 32), D4(=, 36), D4(=, 40), D4(=, 44), D4(=, 48), D4(=, 52), D4(=, 56), D4(=, 60) : "r"(a[0]), "r"(a[1]), "r"(a[2]), "r"(a[3]), "l"(db));
}
template <int SC> DEVI void wg_rs64t(float (&d)[32], const uint32_t (&a)[4], uint64_t db) {
    if (SC) asm volatile("wgmma.mma_async.sync.aligned.m64n64k16.f32.bf16.bf16 "
        "{%0,%1,%2,%3,%4,%5,%6,%7,%8,%9,%10,%11,%12,%13,%14,%15,%16,%17,%18,%19,%20,%21,%22,%23,%24,%25,%26,%27,%28,%29,%30,%31}, "
        "{%32,%33,%34,%35}, %36, 1, 1, 1, 1;"
        : D4(+, 0), D4(+, 4), D4(+, 8), D4(+, 12), D4(+, 16), D4(+, 20), D4(+, 24), D4(+, 28) : "r"(a[0]), "r"(a[1]), "r"(a[2]), "r"(a[3]), "l"(db));
    else asm volatile("wgmma.mma_async.sync.aligned.m64n64k16.f32.bf16.bf16 "
        "{%0,%1,%2,%3,%4,%5,%6,%7,%8,%9,%10,%11,%12,%13,%14,%15,%16,%17,%18,%19,%20,%21,%22,%23,%24,%25,%26,%27,%28,%29,%30,%31}, "
        "{%32,%33,%34,%35}, %36, 0, 1, 1, 1;"
        : D4(=, 0), D4(=, 4), D4(=, 8), D4(=, 12), D4(=, 16), D4(=, 20), D4(=, 24), D4(=, 28) : "r"(a[0]), "r"(a[1]), "r"(a[2]), "r"(a[3]), "l"(db));
}
template <int SC> DEVI void wg_rs40(float (&d)[20], const uint32_t (&a)[4], uint64_t db) {
    if (SC) asm volatile("wgmma.mma_async.sync.aligned.m64n40k16.f32.bf16.bf16 "
        "{%0,%1,%2,%3,%4,%5,%6,%7,%8,%9,%10,%11,%12,%13,%14,%15,%16,%17,%18,%19}, "
        "{%20,%21,%22,%23}, %24, 1, 1, 1, 0;"
        : D4(+, 0), D4(+, 4), D4(+, 8), D4(+, 12), D4(+, 16) : "r"(a[0]), "r"(a[1]), "r"(a[2]), "r"(a[3]), "l"(db));
    else asm volatile("wgmma.mma_async.sync.aligned.m64n40k16.f32.bf16.bf16 "
        "{%0,%1,%2,%3,%4,%5,%6,%7,%8,%9,%10,%11,%12,%13,%14,%15,%16,%17,%18,%19}, "
        "{%20,%21,%22,%23}, %24, 0, 1, 1, 0;"
        : D4(=, 0), D4(=, 4), D4(=, 8), D4(=, 12), D4(=, 16) : "r"(a[0]), "r"(a[1]), "r"(a[2]), "r"(a[3]), "l"(db));
}
template <int SC> DEVI void wg_rs8(float (&d)[4], const uint32_t (&a)[4], uint64_t db) {
    if (SC) asm volatile("wgmma.mma_async.sync.aligned.m64n8k16.f32.bf16.bf16 "
        "{%0,%1,%2,%3}, "
        "{%4,%5,%6,%7}, %8, 1, 1, 1, 0;"
        : D4(+, 0) : "r"(a[0]), "r"(a[1]), "r"(a[2]), "r"(a[3]), "l"(db));
    else asm volatile("wgmma.mma_async.sync.aligned.m64n8k16.f32.bf16.bf16 "
        "{%0,%1,%2,%3}, "
        "{%4,%5,%6,%7}, %8, 0, 1, 1, 0;"
        : D4(=, 0) : "r"(a[0]), "r"(a[1]), "r"(a[2]), "r"(a[3]), "l"(db));
}
template <int SC> DEVI void wg_ss64a(float (&d)[32], uint64_t da, uint64_t db) {
    if (SC) asm volatile("wgmma.mma_async.sync.aligned.m64n64k16.f32.bf16.bf16 "
        "{%0,%1,%2,%3,%4,%5,%6,%7,%8,%9,%10,%11,%12,%13,%14,%15,%16,%17,%18,%19,%20,%21,%22,%23,%24,%25,%26,%27,%28,%29,%30,%31}, "
        "%32, %33, 1, 1, 1, 1, 0;"
        : D4(+, 0), D4(+, 4), D4(+, 8), D4(+, 12), D4(+, 16), D4(+, 20), D4(+, 24), D4(+, 28) : "l"(da), "l"(db));
    else asm volatile("wgmma.mma_async.sync.aligned.m64n64k16.f32.bf16.bf16 "
        "{%0,%1,%2,%3,%4,%5,%6,%7,%8,%9,%10,%11,%12,%13,%14,%15,%16,%17,%18,%19,%20,%21,%22,%23,%24,%25,%26,%27,%28,%29,%30,%31}, "
        "%32, %33, 0, 1, 1, 1, 0;"
        : D4(=, 0), D4(=, 4), D4(=, 8), D4(=, 12), D4(=, 16), D4(=, 20), D4(=, 24), D4(=, 28) : "l"(da), "l"(db));
}

#define G_ROWS 514
__device__ uint4 g_G[64 * G_ROWS * 8];
__device__ uint4 g_GN[64 * 8];
__device__ uint4 g_WN[1152];
#define FS_F2 196608
#define FS_TB (FS_F2 + 8192)
#define FS_NQ (FS_TB + 16384)
#define FS_BAR (FS_NQ + 128)
#define FS_NY (FS_NQ + 1024 + 128)
#define FS_TOTAL (FS_NQ + 3072)
#define F_THREADS 512

DEVI uint32_t cis(int j) {
    const float a = fmaf(__uint_as_float((((j + 1024) << 12) & 0x7FF000) | 0x3F800000), 6.283185307179586f, -9.42477796076938f);
    return pack2(__cosf(a), __sinf(a));
}
DEVI uint32_t cos2(int j0, int j1) {
    const float f = 6.283185307179586f / 2048.f;
    return pack2(__cosf((float)(((j0 + 1024) & 2047) - 1024) * f), __cosf((float)(((j1 + 1024) & 2047) - 1024) * f));
}
DEVI void twid(int j, float& c, float& s) {
    const float a = (float)(((j + 512) & 1023) - 512) * (6.283185307179586f / 1024.f);
    c = __cosf(a) * (1.f / 1024.f);
    s = __sinf(a) * (1.f / 1024.f);
}
DEVI void mwait(uint32_t bar, uint32_t parity) {
    asm volatile("{\n.reg .pred p;\n.reg .b32 c;\nmbarrier.try_wait.parity.shared::cta.b64 p, [%0], %1;\n@p bra.uni D;\nmov.b32 c, 0;\n"
                 "L:\nadd.u32 c, c, 1;\nsetp.gt.u32 p, c, 4194304;\n@p st.shared.u32 [c], c;\n"
                 "mbarrier.try_wait.parity.shared::cta.b64 p, [%0], %1;\n@!p bra.uni L;\nD:\n}" ::"r"(bar), "r"(parity) : "memory");
}
template <bool B> struct Bool { static constexpr bool v = B; };
DEVI uint32_t opq(uint32_t& x, uint32_t zero) { OPQ(x); return x; }
DEVI uint32_t tidx() { uint32_t r; asm volatile("mov.u32 %0, %%tid.x;" : "=r"(r)); return r; }
DEVI void tma4d(uint32_t dst, const CUtensorMap* tm, uint32_t bar, int c0, int c1, int c2, int c3) {
    asm volatile("cp.async.bulk.tensor.4d.shared::cluster.global.mbarrier::complete_tx::bytes [%0], [%1, {%3, %4, %5, %6}], [%2];"
                 ::"r"(dst), "l"(tm), "r"(bar), "r"(c0), "r"(c1), "r"(c2), "r"(c3) : "memory");
}
DEVI void tma3s(const CUtensorMap* tm, uint32_t src, int c0, int c1, int c2) {
    asm volatile("cp.async.bulk.tensor.3d.global.shared::cta.bulk_group [%0, {%2, %3, %4}], [%1];" ::"l"(tm), "r"(src), "r"(c0), "r"(c1), "r"(c2) : "memory");
}
DEVI void tma4s(const CUtensorMap* tm, uint32_t src, int c0, int c1, int c2, int c3) {
    asm volatile("cp.async.bulk.tensor.4d.global.shared::cta.bulk_group [%0, {%2, %3, %4, %5}], [%1];"
                 ::"l"(tm), "r"(src), "r"(c0), "r"(c1), "r"(c2), "r"(c3) : "memory");
}
DEVI void bulk_commit() { asm volatile("cp.async.bulk.commit_group;" ::: "memory"); }
DEVI void fence_async() { asm volatile("fence.proxy.async;" ::: "memory"); }
DEVI void fence_smem() { asm volatile("fence.proxy.async.shared::cta;" ::: "memory"); }
DEVI void wgbar(uint32_t q) { asm volatile("bar.sync %0, 128;" ::"r"(q + 2) : "memory"); }
DEVI void grid_arrive(uint32_t* c) { asm volatile("fence.proxy.async;\nred.release.gpu.global.add.u32 [%0], 1;" ::"l"(c) : "memory"); }
DEVI void grid_wait(uint32_t* c, uint32_t n) {
    uint32_t v;
    int it = 0;
    do {
        asm volatile("ld.acquire.gpu.global.u32 %0, [%1];" : "=r"(v) : "l"(c) : "memory");
        if (++it > (1 << 22)) die(it);
    } while (v != n);
    fence_async();
}

template <bool INV, class S1, class S2>
DEVI void fft_rows(uint32_t grp, uint32_t q, const uint32_t (&F)[2][4], const float (&tc)[8], const float (&ts)[8], uint32_t so, float fx, uint32_t nq,
                   S1 sh1, S2 sh2) {
    float d[64];
    const uint64_t db = INV ? mkdesc(grp, 1024, 2048) : (mkdesc(grp, 2048, 512) ^ ((uint64_t)3 << 62));
    wg_fence();
    wg_rs128t<0>(d, F[0], db);
    wg_rs128t<1>(d, F[1], db + (INV ? 256 : 64));
    wg_commit();
    SF();
    sh1();
    float4 ny;
    if (INV) ny = lds128f(nq);
    wg_wait<0>();
    if (INV) { d[0] = fmaf(fx, ny.x, d[0]); d[16] = fmaf(fx, ny.y, d[16]); d[32] = fmaf(fx, ny.z, d[32]); d[48] = fmaf(fx, ny.w, d[48]); }
    uint32_t a[2][4][4];
    float e[2][INV ? 16 : 20];
    const uint64_t df = mkdesc(SB0 + FS_F2, 16, 1024);
#pragma unroll
    for (int s = 0; s < 2; s++) {
#pragma unroll
        for (int i = 0; i < 4; i++)
#pragma unroll
            for (int h = 0; h < 2; h++) {
                const float* x = d + (2 * s + h) * 16 + i * 4;
                a[s][i][h] = pack2(fmaf(x[2], ts[2 * i], x[0] * tc[2 * i]), fmaf(x[3], ts[2 * i + 1], x[1] * tc[2 * i + 1]));
                a[s][i][h + 2] = pack2(fmaf(-x[0], ts[2 * i], x[2] * tc[2 * i]), fmaf(-x[1], ts[2 * i + 1], x[3] * tc[2 * i + 1]));
            }
        wg_fence();
#pragma unroll
        for (int i = 0; i < 4; i++) {
            if constexpr (INV) { if (i == 0) wg_rs32<0>(e[s], a[s][i], df); else wg_rs32<1>(e[s], a[s][i], df + i * 2); }
            else { if (i == 0) wg_rs40<0>(e[s], a[s][i], df); else wg_rs40<1>(e[s], a[s][i], df + i * 2); }
        }
        wg_commit();
    }
    SF();
    sh2();
#pragma unroll
    for (int s = 0; s < 2; s++) {
        if (s == 0) wg_wait<1>(); else wg_wait<0>();
        float* x = e[s];
        if constexpr (!INV) {
            x[0] *= fx; x[1] *= fx; x[2] *= fx; x[3] *= fx;
            if (fx != 1.f) sts64(nq + s * 8, pack2(x[16], 0.f), pack2(x[18], 0.f));
        }
        const uint32_t o = grp + (INV ? so + s * 4096 : so ^ (s * 576));
#pragma unroll
        for (int b = 0; b < 2; b++)
            stsm4t(o + b * (INV ? 1024 : 4096), pack2(x[8 * b], x[8 * b + 1]), pack2(x[8 * b + 2], x[8 * b + 3]), pack2(x[8 * b + 4], x[8 * b + 5]),
                   pack2(x[8 * b + 6], x[8 * b + 7]));
    }
}

template <bool INV>
DEVI void fft_gen(uint32_t a, uint32_t n2) {
    const uint32_t tid = tidx(), x = ((tid >> 4) & 24) + (tid & 3), o = (tid & 4) * 128;
    if (INV) {
        const uint32_t r = (tid & 64) * 16 + (tid & 16) * 32 + (tid & 40) * 8 + n2;
        sts128(a + tid * 16, cis(o - r * x), cis(o - (r + 128) * x), cis(o - r * (x + 4)), cis(o - (r + 128) * (x + 4)));
    } else {
        const uint32_t r = 64 * x + n2, k = ((tid >> 2) & 24) + ((tid >> 3) & 3);
        sts128(a + tid * 16, cis(r * k + o), cis(r * (k + 4) + o), cis((r + 256) * k + o), cis((r + 256) * (k + 4) + o));
    }
}
template <bool INV, class S1>
DEVI void fft_cross(uint32_t buf, uint32_t q, uint32_t fa, uint32_t so, uint32_t nq, float (&n)[4], S1 sh1) {
    uint32_t F[4][4];
#pragma unroll
    for (int s = 0; s < 4; s++) { const uint4 v = lds128(fa + s * 2048); F[s][0] = v.x; F[s][1] = v.y; F[s][2] = v.z; F[s][3] = v.w; }
    float d[64];
    const uint64_t db = mkdesc(buf + q * 2048, 1024, 8192), dn = mkdesc(nq, 16, 1024);
    wg_fence();
#pragma unroll
    for (int s = 0; s < 4; s++) { if (s == 0) wg_rs128t<0>(d, F[s], db); else wg_rs128t<1>(d, F[s], db + s * 1024); }
#pragma unroll
    for (int s = 0; s < 4; s++) { if (s == 0) wg_rs8<0>(n, F[s], dn); else wg_rs8<1>(n, F[s], dn + s * 2); }
    wg_commit();
    SF();
    sh1();
    wg_wait<0>();
#pragma unroll
    for (int b = 0; b < 8; b++) {
        const uint32_t o = INV ? so ^ ((b >> 1) * 288 ^ (b & 1) * 32) : (so ^ ((b & 3) * 32)) + (b >> 2) * 1024;
        stsm4(buf + o, pack2(d[8 * b], d[8 * b + 1]), pack2(d[8 * b + 2], d[8 * b + 3]), pack2(d[8 * b + 4], d[8 * b + 5]), pack2(d[8 * b + 6], d[8 * b + 7]));
    }
}

template <bool ODD>
DEVI void fft_filter(uint32_t aw, const float (&e)[32], const float (&o)[32], uint32_t (&u)[4][4], uint32_t (&v)[4][4]) {
#pragma unroll
    for (int s = 0; s < 4; s++) {
        float y[2][2][4];
#pragma unroll
        for (int c = 0; c < 2; c++) {
            float f[4][2];
#pragma unroll
            for (int i = 0; i < 4; i++) {
                const uint32_t a = aw + (i * 32 + s * 8 + c) * 144, x = lds32(a);
                f[i][0] = ODD ? hi_f(x) : lo_f(x);
                f[i][1] = ODD ? lo_f(lds32(a + 4)) : hi_f(x);
            }
#pragma unroll
            for (int h = 0; h < 2; h++) {
                const int x = 8 * s + 2 * h + c;
                const float ar = e[x] + o[x], ai = e[x + 4] + o[x + 4], br = e[x] - o[x], bi = e[x + 4] - o[x + 4];
                const float yr = fmaf(-ai, f[2][h], ar * f[0][h]), yi = fmaf(ar, f[2][h], ai * f[0][h]);
                y[h][c][0] = fmaf(-bi, f[3][h], fmaf(br, f[1][h], yr));
                y[h][c][1] = fmaf(br, f[3][h], fmaf(bi, f[1][h], yi));
                y[h][c][2] = fmaf(2.f, yr, -y[h][c][0]);
                y[h][c][3] = fmaf(2.f, yi, -y[h][c][1]);
            }
        }
#pragma unroll
        for (int h = 0; h < 2; h++) {
            u[s][h] = pack2(y[h][0][0], y[h][1][0]); u[s][h + 2] = pack2(y[h][0][1], y[h][1][1]);
            v[s][h] = pack2(y[h][0][2], y[h][1][2]); v[s][h + 2] = pack2(y[h][0][3], y[h][1][3]);
        }
    }
}

__global__ void __launch_bounds__(F_THREADS, 1)
post_kernel(const __grid_constant__ CUtensorMap tmx, const __grid_constant__ CUtensorMap tmg1, const __grid_constant__ CUtensorMap tmg2,
           const __grid_constant__ CUtensorMap tmwr, const __grid_constant__ CUtensorMap tmwi, const __grid_constant__ CUtensorMap tmy,
           const bf16* __restrict__ wr, const bf16* __restrict__ wi, uint32_t* cnt, uint32_t zero, int nw,
           const __grid_constant__ CUtensorMap tmb, uint32_t xlo, uint32_t xhi, bf16* __restrict__ out) {
    extern __shared__ __align__(1024) uint8_t smem[];
    const uint32_t sb = SB0;
    if (smem_u32(smem) != sb) die(1 << 23);
    if (blockIdx.x >= nw) {
        gemm2(blockIdx.x - nw, xlo, xhi, tmb, out);
        return;
    }
    const uint32_t tid = threadIdx.x, lane = tid & 31, g = lane >> 2, t = lane & 3, j8 = lane & 7, mat = lane >> 3;
    const uint32_t wi_ = __reduce_max_sync(0xFFFFFFFFu, tid >> 5), q = wi_ >> 2, w = wi_ & 3;
    const int cta = blockIdx.x;
    const int nt = cta < 64 ? (64 - cta + nw - 1) / nw : 0;
    const uint32_t bar = sb + FS_BAR;
    if (tid == 0) {
        for (int i = 0; i < 30; i++) mbar_init(bar + i * 8, i < 3 ? 4 : i < 6 ? 16 : i >= 14 && i < 18 ? 2 : 1);
        asm volatile("fence.mbarrier_init.release.cluster;" ::: "memory");
        fence_smem();
    }
    __syncthreads();
#define FT(n)
    FT(0);
#define N2(p) (2 * ((p) & 31) + ((p) >> 5))
#define WLOAD(tk, part) { \
        const uint32_t wd_ = sb + 131072 + q * 18432 + (part) * 9216, wb_ = bar + 112 + q * 8; \
        mbar_expect(wb_, 9216); \
        if ((tk) < 256) tma3d(wd_, (part) ? &tmwi : &tmwr, wb_, ((tk) & 63) * 64, (tk) >> 6, 0); \
        else asm volatile("cp.async.bulk.shared::cluster.global.mbarrier::complete_tx::bytes [%0], [%1], 9216, [%2];" \
                          ::"r"(wd_), "l"(g_WN + (part) * 576), "r"(wb_) : "memory"); }
#define GROW(tk) ((tk) < 256 ? ((tk) >> 5) * 64 + ((tk) & 7) * 8 + (((tk) >> 3) & 3) * 2 : 512)
#define DLOAD(tk, sl) { mbar_expect(bar + 48 + (sl) * 8, 16384); tma3d(sb + (sl) * 16384, &tmg2, bar + 48 + (sl) * 8, 0, GROW(tk), 0); }
#define IO(c) if (w == 3 && (c) && elect())
#define XLOAD1(i, bb) { const uint32_t xb_ = bar + 144 + (bb) * 32 + q * 8; mbar_expect(xb_, 16384); tma4d(sb + (bb) * 65536 + q * 16384, &tmx, xb_, 0, 0, q * 8, N2(cta + (i) * nw)); }
#define GLOAD3(i, bb) { mbar_expect(bar + (bb) * 8, q ? 16384 : 16512); tma3d(sb + (bb) * 65536 + q * 16384, &tmg1, bar + (bb) * 8, 0, q * 128, cta + (i) * nw); \
        if (q == 0) asm volatile("cp.async.bulk.shared::cluster.global.mbarrier::complete_tx::bytes [%0], [%1], 128, [%2];" \
                                 ::"r"(sb + FS_NQ + (bb) * 1024), "l"(g_GN + (cta + (i) * nw) * 8), "r"(bar + (bb) * 8) : "memory"); }
    for (int i = 0; i < 3; i++) IO(i < nt) XLOAD1(i, i);
    for (uint32_t x = tid; x < 40 * 32; x += 512) {
        const uint32_t n = x >> 5, m2 = mat * 8 + t * 2, ri = g & 1;
        const uint32_t c2 = ((n >> 1) & 1) + ((n >> 3) & 1) * 2 + (n & 4) + (n >> 4) * 8;
        const uint32_t v = cos2(m2 * c2 * 64 + ((n & 1) - ri) * 512, (m2 + 1) * c2 * 64 + ((n & 1) - ri) * 512);
        sts32(sb + FS_F2 + n * 128 + ((g ^ (n & 7)) << 4) + t * 4, n < 32 ? v : n == 32 && ri == 0 ? 0xBF003F00u : 0u);
    }
    float tc[8], ts[8];
    uint32_t F[2][4];
    uint32_t c1 = 16 * (w >> 1) + 2 * g + (w & 1);
#pragma unroll
    for (int i = 0; i < 8; i++) {
        twid(c1 * (8 * (i >> 1) + 2 * t + (i & 1)), tc[i], ts[i]);
        const uint32_t m1 = (i >> 1) * 8 + 2 * t;
        F[i >> 2][i & 3] = cos2(c1 * m1 * 64 + (i & 1) * 512, c1 * (m1 + 1) * 64 + (i & 1) * 512);
    }
    {
        const uint32_t kr = (2 * (mat & 1) + (j8 & 1)) ^ ((j8 >> 2) << 1);
        const uint32_t so1 = ((mat >> 1) + 2 * (j8 >> 2)) * 1024 + kr * 128 + (((((j8 >> 1) & 1) * 4 + w) ^ kr) << 4);
        const uint32_t so2 = (2 * w + (mat & 1)) * 8192 + q * 2048 + j8 * 128 + (((mat >> 1) ^ j8) << 4);
        uint32_t so = so1 << 16 | so2;
        const float fx = (tid & 127) == 0 ? 0.5f : 1.f;
        fft_gen<false>(sb + FS_TB, N2(cta));
        fence_smem();
        bsync<1, 512>();
        FT(1);
        int b = 0, bp = 2, ph = 0;
        if (nt) mwait(bar + 144 + q * 8, 0);
        __syncwarp();
        auto step = [&](auto first, auto last, const int i) {
            const uint32_t p = cta + i * nw, bn = 3 - b - bp, tb = (i & 1) * 8192;
            const uint32_t grp = sb + b * 65536 + q * 16384, nq = sb + FS_NQ + b * 1024 + q * 32;
            auto sa = [&]() {
                if constexpr (!decltype(first)::v) {
                    fence_smem();
                    __syncwarp();
                    if (elect()) mbar_arrive(bar + 24);
                }
                IO(i > 1) {
                    mwait(bar + 32, i & 1);
                    tma3s(&tmg1, sb + bn * 65536 + q * 16384, 0, q * 128, p - 2 * nw);
                    bulk_commit();
                }
            };
            auto sb_ = [&]() { if constexpr (!decltype(first)::v) mwait(bar + 24, (i - 1) & 1); };
            if constexpr (!decltype(last)::v) fft_rows<false>(grp, q, F, tc, ts, opq(so, zero) >> 16, fx, nq, sa, sb_);
            else { sa(); __syncwarp(); sb_(); __syncwarp(); }
            if constexpr (!decltype(first)::v) {
                float n[4];
                fft_cross<false>(sb + bp * 65536, q, sb + FS_TB + 8192 - tb + (((tidx() & 127) ^ (q & 1)) << 4), opq(so, zero) & 0xFFFF, sb + FS_NQ + bp * 1024, n, [&]() {
                    fft_gen<false>(sb + FS_TB + tb, N2(p));
                    IO(i >= 2 && i + 1 < nt) {
                        asm volatile("cp.async.bulk.wait_group.read 0;" ::: "memory");
                        XLOAD1(i + 1, bn);
                    }
                });
                if (q == 0) {
                    const uint32_t x = tidx();
                    bf16* z = (bf16*)(g_G + ((p - nw) * G_ROWS + 512) * 8) + (x & 4) * 16 + ((x >> 2) & 24) + ((x >> 3) & 3);
                    asm volatile("{\n.reg .pred p;\n.reg .b16 a, b;\nsetp.eq.u32 p, %2, 0;\nmov.b32 {a, b}, %1;\n@p st.global.u16 [%0], a;\n@p st.global.u16 [%0+8], b;\n}"
                                 ::"l"(z), "r"(pack2(n[0], n[2])), "r"(x & 3) : "memory");
                }
            }
            if constexpr (!decltype(last)::v) {
                fft_rows<false>(grp + 8192, q, F, tc, ts, opq(so, zero) >> 16, fx, nq + 16, [&]() {
                    if constexpr (!decltype(first)::v) {
                        fence_smem();
                        __syncwarp();
                        if (elect()) mbar_arrive(bar + 32);
                    }
                    if ((w == 1 || w == 2) && elect())
                        asm volatile("cp.async.bulk.prefetch.L2.global [%0], 8208;" ::"l"((w == 1 ? wr : wi) + (p * 4 + q) * 4104) : "memory");
                }, [&]() { if (i + 1 < nt) mwait(bar + 144 + bn * 32 + q * 8, bn ? ph : ph ^ 1); });
                bp = b;
                if (++b == 3) { b = 0; ph ^= 1; }
            }
        };
        if (nt) {
            step(Bool<true>(), Bool<false>(), 0);
#pragma unroll 1
            for (int i = 1; i < nt; i++) step(Bool<false>(), Bool<false>(), i);
            step(Bool<false>(), Bool<true>(), nt);
        }
        for (uint32_t x = cta * 512 + tid; x < 4096; x += nw * 512)
            ((bf16*)g_WN)[(x >> 5) * 72 + (x & 16) + (x & 7) * 2 + ((x >> 3) & 1)] = (x < 2048 ? wr : wi)[(x & 2047) * 513 + 512];
        FT(2);
        fence_async();
        bsync<1, 512>();
        IO(nt) { tma3s(&tmg1, sb + bp * 65536 + q * 16384, 0, q * 128, cta + (nt - 1) * nw); bulk_commit(); }
    }
    for (uint32_t x = tid; x < 128 * 32; x += 512) {
        const uint32_t n = (x >> 5) & 63, a = x & 31, k2 = (n >> 4) * 8 + (n & 7);
        sts32(sb + FS_TB + (x >> 5) * 128 + (((a >> 2) ^ (n & 7)) << 4) + (a & 3) * 4, cis((2 * a + (x >> 11)) * k2 * 32 + (n & 8) * 64));
    }
    fence_smem();
    bsync<1, 512>();
    IO(true) {
        asm volatile("cp.async.bulk.wait_group 0;" ::: "memory");
        grid_arrive(cnt);
        grid_wait(cnt, 4 * nw);
        const int tk = cta + q * nw;
        if (tk <= 256) { DLOAD(tk, q); WLOAD(tk, 0); WLOAD(tk, 1); }
    }
    __syncwarp();
    {
        const uint32_t lo = j8 * 128 + (((2 * w + (mat & 1)) ^ j8) << 4);
        const uint32_t aw = sb + 131072 + q * 18432 + t * 288 + w * 32 + g * 4;
        const uint64_t df = mkdesc(sb + FS_TB, 16, 1024);
        const uint64_t da = mkdesc(sb + q * 16384, 16, 1024);
        const uint32_t buf = sb + 65536 + q * 16384;
        int i = 0, tk = cta + q * nw;
        if (tk <= 256) mwait(bar + 48 + q * 8, 0);
        FT(3);
#pragma unroll 1
        for (; tk <= 256; tk += 4 * nw, i++) {
            const bool more = tk + 4 * nw <= 256;
            float e[32], o[32];
            wg_fence();
#pragma unroll
            for (int s = 0; s < 4; s++) { if (s == 0) wg_ss64a<0>(e, da, df); else wg_ss64a<1>(e, da + s * 128, df + s * 2); }
#pragma unroll
            for (int s = 0; s < 4; s++) { if (s == 0) wg_ss64a<0>(o, da + 512, df + 512); else wg_ss64a<1>(o, da + 512 + s * 128, df + 512 + s * 2); }
            wg_commit();
            SF();
            if (i > 0) {
                fence_smem();
                wgbar(q);
                IO(true) { tma3s(&tmg2, buf, 0, GROW(tk - 4 * nw), 0); bulk_commit(); }
            }
            if (w == 2 && more && elect()) mbar_expect(bar + 48 + q * 8, 16384);
            const int gr = GROW(tk + 4 * nw);
            mwait(bar + 112 + q * 8, i & 1);
            wg_wait<0>();
            if (w == 2 && more && elect()) tma3d(sb + q * 16384, &tmg2, bar + 48 + q * 8, 0, gr, 0);
            uint32_t u[4][4], v[4][4];
            if (tk & 8) fft_filter<true>(aw + (tk & 48) / 4, e, o, u, v);
            else fft_filter<false>(aw + (tk & 48) / 4, e, o, u, v);
            wg_fence();
#pragma unroll
            for (int s = 0; s < 4; s++) { if (s == 0) wg_rs64t<0>(e, u[s], df); else wg_rs64t<1>(e, u[s], df + s * 128); }
#pragma unroll
            for (int s = 0; s < 4; s++) { if (s == 0) wg_rs64t<0>(o, v[s], df + 512); else wg_rs64t<1>(o, v[s], df + 512 + s * 128); }
            wg_commit();
            SF();
            IO(true) asm volatile("cp.async.bulk.wait_group.read 0;" ::: "memory");
            wgbar(q);
            if (more) {
                if ((w == 1 || w == 2) && elect()) WLOAD(tk + 4 * nw, w - 1);
                mwait(bar + 48 + q * 8, (i + 1) & 1);
            }
            wg_wait<0>();
#pragma unroll
            for (int s = 0; s < 4; s++) {
                const uint32_t a = buf + (mat >> 1) * 1024 + lo + s * 2048;
                stsm4t(a, pack2(e[8 * s], e[8 * s + 1]), pack2(e[8 * s + 2], e[8 * s + 3]), pack2(e[8 * s + 4], e[8 * s + 5]), pack2(e[8 * s + 6], e[8 * s + 7]));
                stsm4t(a + 8192, pack2(o[8 * s], o[8 * s + 1]), pack2(o[8 * s + 2], o[8 * s + 3]), pack2(o[8 * s + 4], o[8 * s + 5]), pack2(o[8 * s + 6], o[8 * s + 7]));
            }
            if (tk == 256 && w < 2) {
                uint32_t* z = (uint32_t*)g_GN + t * 32 + w * 16 + g;
#pragma unroll
                for (int s = 0; s < 16; s++) {
                    z[(s >> 1) * 128 + (s & 1) * 8] = pack2(e[2 * s], e[2 * s + 1]);
                    z[(s >> 1) * 128 + (s & 1) * 8 + 1024] = pack2(o[2 * s], o[2 * s + 1]);
                }
                fence_async();
            }
        }
        fence_smem();
        wgbar(q);
        IO(true) {
            if (i > 0) { tma3s(&tmg2, buf, 0, GROW(tk - 4 * nw), 0); bulk_commit(); }
            asm volatile("cp.async.bulk.wait_group 0;" ::: "memory");
            grid_arrive(cnt + 1);
        }
    }
    FT(4);
    bsync<1, 512>();
    {
        for (uint32_t n = wi_; n < 32; n += 16) {
            const uint32_t cl = (mat >> 1) * 16 + t * 4 + (mat & 1), mh = ((n >> 3) & 1) + (n & 7) * 2 + (n & 16);
            sts32(sb + FS_F2 + n * 128 + ((g ^ (n & 7)) << 4) + t * 4, cos2(cl * mh * 64 + (g & 1) * 512, (cl + 2) * mh * 64 + (g & 1) * 512));
        }
        fence_smem();
        c1 = 8 * w + g;
#pragma unroll
        for (int i = 0; i < 8; i++) {
            twid(-c1 * (16 * (i >> 2) + 4 * t + 2 * (i & 1) + ((i >> 1) & 1)), tc[i], ts[i]);
            F[i >> 2][i & 3] = cis((i & 1) * 512 - c1 * ((i >> 1) * 4 + (t ^ (q & 1))) * 64);
        }
        const uint32_t kr = (j8 & 1) ^ ((j8 >> 2) << 1);
        const uint32_t so2 = ((w >> 1) * 4 + (j8 >> 2) * 2 + (w & 1)) * 8192 + (2 * q + (mat & 1)) * 1024 + kr * 128 + (((((j8 >> 1) & 1) * 4 + (mat >> 1)) ^ kr) << 4);
        const uint32_t so1 = (mat & 1) * 2048 + j8 * 128 + ((((mat >> 1) * 4 + w) ^ j8) << 4);
        uint32_t so = so1 << 16 | so2;
        const float fx = t ? 0.f : (g & 1) ? -1.f : 1.f;
        fft_gen<true>(sb + FS_TB, N2(cta));
        bsync<1, 512>();
        IO(true) grid_wait(cnt + 1, 4 * nw);
        for (int i = 0; i < 3; i++) IO(i < nt) GLOAD3(i, i);
        __syncwarp();
        int b = 0, bp = 2, ph = 0;
        auto step = [&](auto first, auto last, const int i) {
            const uint32_t p = cta + i * nw, bn = 3 - b - bp, tb = (i & 1) * 8192;
            const uint32_t grp = sb + bp * 65536 + q * 16384, ny = sb + FS_NY + bp * 128 + q * 32;
            auto sb_ = [&]() { if constexpr (!decltype(last)::v) mwait(bar + b * 8, ph); };
            if constexpr (!decltype(first)::v) {
                fft_rows<true>(grp, q, F, tc, ts, opq(so, zero) >> 16, fx, ny, [&]() {
                    if (i > 1) {
                        fence_smem();
                        wgbar(q);
                        IO(true) { tma4s(&tmy, sb + bn * 65536 + q * 16384, 0, 0, q * 8, N2(p - 2 * nw)); bulk_commit(); }
                    }
                }, sb_);
            } else { sb_(); __syncwarp(); }
            if constexpr (decltype(first)::v) FT(5);
            if constexpr (!decltype(last)::v) {
                float n[4];
                fft_cross<true>(sb + b * 65536, q, sb + FS_TB + tb + (tidx() & 127) * 16, opq(so, zero) & 0xFFFF, sb + FS_NQ + b * 1024, n, [&]() {
                    fft_gen<true>(sb + FS_TB + 8192 - tb, N2(p + nw));
                    IO(i >= 2 && i + 1 < nt) {
                        asm volatile("cp.async.bulk.wait_group.read 0;" ::: "memory");
                        GLOAD3(i + 1, bn);
                    }
                });
                if (q == 0) {
                    const uint32_t x = tidx(), a = sb + FS_NY + b * 128 + (x & 64) + (x & 16) * 2 + ((x & 40) >> 1);
                    if ((x & 7) == 0) { sts32f(a, n[0]); sts32f(a + 8, n[2]); }
                }
            }
            auto sc = [&]() {
                if constexpr (!decltype(last)::v) {
                    fence_smem();
                    __syncwarp();
                    if (elect()) mbar_arrive(bar + 24);
                }
            };
            auto sd = [&]() { if constexpr (!decltype(last)::v) mwait(bar + 24, (nt + i) & 1); };
            if constexpr (!decltype(first)::v) fft_rows<true>(grp + 8192, q, F, tc, ts, opq(so, zero) >> 16, fx, ny + 16, sc, sd);
            else { sc(); __syncwarp(); sd(); __syncwarp(); }
            if constexpr (!decltype(last)::v) {
                bp = b;
                if (++b == 3) { b = 0; ph ^= 1; }
            }
        };
        if (nt) {
            step(Bool<true>(), Bool<false>(), 0);
#pragma unroll 1
            for (int i = 1; i < nt; i++) step(Bool<false>(), Bool<false>(), i);
            step(Bool<false>(), Bool<true>(), nt);
        }
        fence_smem();
        wgbar(q);
        IO(nt) { tma4s(&tmy, sb + bp * 65536 + q * 16384, 0, 0, q * 8, N2(cta + (nt - 1) * nw)); bulk_commit(); }
        FT(6);
        IO(true) asm volatile("cp.async.bulk.wait_group 0;" ::: "memory");
    }
}

typedef CUresult (*EncodeFn)(CUtensorMap*, CUtensorMapDataType, cuuint32_t, void*, const cuuint64_t*, const cuuint64_t*,
                             const cuuint32_t*, const cuuint32_t*, CUtensorMapInterleave, CUtensorMapSwizzle,
                             CUtensorMapL2promotion, CUtensorMapFloatOOBfill);

static void make_map(EncodeFn enc, CUtensorMap* m, const void* ptr, int rank, const cuuint64_t* dims, const cuuint64_t* strides,
                     const cuuint32_t* box, CUtensorMapSwizzle sw = CU_TENSOR_MAP_SWIZZLE_128B) {
    cuuint32_t es[4] = {1, 1, 1, 1};
    CUresult r = enc(m, CU_TENSOR_MAP_DATA_TYPE_BFLOAT16, rank, (void*)ptr, dims, strides, box, es, CU_TENSOR_MAP_INTERLEAVE_NONE,
                     sw, CU_TENSOR_MAP_L2_PROMOTION_L2_256B, CU_TENSOR_MAP_FLOAT_OOB_FILL_NONE);
    if (r != CUDA_SUCCESS) fprintf(stderr, "tensor map encode failed: %d\n", (int)r);
}

extern "C" void kernel_launch(void* const* d_in, const int* in_sizes, int n_in, void* d_out, int out_size) {
    const bf16* A_x = (const bf16*)d_in[0];
    const bf16* A_mem0 = (const bf16*)d_in[1];
    const bf16* A_Wq = (const bf16*)d_in[2];
    const bf16* A_Wk = (const bf16*)d_in[3];
    const bf16* A_Wv = (const bf16*)d_in[4];
    const bf16* A_Wo = (const bf16*)d_in[5];
    const bf16* B_x = (const bf16*)d_in[7];
    const bf16* B_wr = (const bf16*)d_in[8];
    const bf16* B_wi = (const bf16*)d_in[9];
    bf16* out = (bf16*)d_out;

    static EncodeFn enc = nullptr;
    static void *pxs = nullptr, *pg = nullptr;
    static int ncl = 64;
    if (!enc) {
        cudaDriverEntryPointQueryResult qr;
        void* fn = nullptr;
        cudaGetDriverEntryPoint("cuTensorMapEncodeTiled", &fn, cudaEnableDefault, &qr);
        enc = (EncodeFn)fn;
        cudaFuncSetAttribute(chain_kernel, cudaFuncAttributeMaxDynamicSharedMemorySize, SM_TOTAL);
        cudaFuncSetAttribute(post_kernel, cudaFuncAttributeMaxDynamicSharedMemorySize, FS_TOTAL);
        cudaGetSymbolAddress(&pxs, g_xs);
        cudaGetSymbolAddress(&pg, g_G);
        cudaLaunchConfig_t lc = {};
        cudaLaunchAttribute at;
        at.id = cudaLaunchAttributeClusterDimension;
        at.val.clusterDim.x = 2; at.val.clusterDim.y = 1; at.val.clusterDim.z = 1;
        lc.gridDim = dim3(132); lc.blockDim = dim3(384); lc.dynamicSmemBytes = SM_TOTAL; lc.attrs = &at; lc.numAttrs = 1;
        int nc = 0;
        if (cudaOccupancyMaxActiveClusters(&nc, chain_kernel, &lc) == cudaSuccess && nc > 64) ncl = nc < 66 ? nc : 66;
    }
    CUtensorMap tmq, tmk, tmv, tmo, tmx, tmb;
    {
        cuuint64_t d[2] = {HD, DM}, st[1] = {HD * 2};
        cuuint32_t bx[2] = {64, 256};
        make_map(enc, &tmq, A_Wq, 2, d, st, bx);
        make_map(enc, &tmk, A_Wk, 2, d, st, bx);
        cuuint32_t bx2[2] = {64, 16};
        make_map(enc, &tmv, A_Wv, 2, d, st, bx2);
    }
    {
        cuuint64_t d[2] = {DM, HD}, st[1] = {DM * 2};
        cuuint32_t bx[2] = {64, 16}, bx2[2] = {64, 64};
        make_map(enc, &tmo, A_Wo, 2, d, st, bx);
        make_map(enc, &tmb, A_Wo, 2, d, st, bx2);
    }
    {
        cuuint64_t d[3] = {64, SEQ, DM / 64}, st[2] = {DM * 2, 128};
        cuuint32_t bx[3] = {64, 8, 4};
        make_map(enc, &tmx, A_x, 3, d, st, bx);
    }
    CUtensorMap fx, fg1, fg2, fwr, fwi, fy;
    {
        cuuint64_t d[4] = {32, 32, 32, 64}, st[3] = {64, 64 * DM * 2, DM * 2};
        cuuint32_t bx[4] = {32, 32, 8, 1};
        make_map(enc, &fx, B_x, 4, d, st, bx, CU_TENSOR_MAP_SWIZZLE_64B);
        cuuint64_t d2[4] = {64, 16, 32, 64}, st2[3] = {128, 64 * 4096, 4096};
        cuuint32_t bx2[4] = {64, 16, 8, 1};
        make_map(enc, &fy, out + DM, 4, d2, st2, bx2);
    }
    {
        cuuint64_t d[3] = {64, G_ROWS, 64}, st[2] = {128, G_ROWS * 128};
        cuuint32_t bx[3] = {64, 128, 1}, bx2[3] = {64, 2, 64};
        make_map(enc, &fg1, pg, 3, d, st, bx);
        make_map(enc, &fg2, pg, 3, d, st, bx2);
        cuuint64_t d2[3] = {8 * 513, 4, 64}, st2[2] = {8 * 513 * 2, 32 * 513 * 2};
        cuuint32_t bx3[3] = {72, 1, 64};
        make_map(enc, &fwr, B_wr, 3, d2, st2, bx3, CU_TENSOR_MAP_SWIZZLE_NONE);
        make_map(enc, &fwi, B_wi, 3, d2, st2, bx3, CU_TENSOR_MAP_SWIZZLE_NONE);
    }
    cudaStream_t st = cudaStreamPerThread;
    const uint64_t xs = ((uint64_t)pxs + XS_BYTES - 1) & ~(uint64_t)(XS_BYTES - 1);
    cudaMemsetAsync((void*)(xs + XO_R), 0, XO_TK + 512, st);
    chain_kernel<<<2 * ncl, 384, SM_TOTAL, st>>>(tmq, tmk, tmv, tmo, tmx, A_mem0, A_x, (uint32_t)xs, (uint32_t)(xs >> 32), 0u, NSEG);
    int nw = ncl == 66 ? 4 : 64;
    cudaLaunchConfig_t lc = {};
    cudaLaunchAttribute at;
    at.id = cudaLaunchAttributeProgrammaticStreamSerialization;
    at.val.programmaticStreamSerializationAllowed = 1;
    lc.gridDim = dim3(nw + 128); lc.blockDim = dim3(F_THREADS); lc.dynamicSmemBytes = FS_TOTAL; lc.stream = st; lc.attrs = &at; lc.numAttrs = 1;
    cudaLaunchKernelEx(&lc, post_kernel, fx, fg1, fg2, fwr, fwi, fy, B_wr, B_wi, (uint32_t*)(xs + XO_TK + 256), 0u, nw, tmb, (uint32_t)xs,
                       (uint32_t)(xs >> 32), out);
}
```

```cpp
#include <cuda_runtime.h>
#include <cuda_bf16.h>
#include <cuda.h>
#include <stdint.h>
#include <stdio.h>

typedef __nv_bfloat16 bf16;

#define SEQ 2048
#define DM 1024
#define NH 32
#define DH 128
#define NSEG 64
#define HD (NH * DH)

#define XS_BYTES (32u << 20)
__device__ uint4 g_xs[2 * XS_BYTES / 16];
#define XO_R 0u
#define XO_PB (1u << 18)
#define XO_FL (XO_PB + 16384u)
#define XO_TK (XO_FL + 32768u)
#define XO_CQK (1u << 20)
#define XO_CV (2u << 20)
#define XO_XG (4u << 20)
#define XO_OX (16u << 20)
#define GSYNC(n)

#define DEVI __device__ __forceinline__

DEVI void die(int it) { asm volatile("st.shared.u32 [%0], %0;" ::"r"(it) : "memory"); }
DEVI uint32_t smem_u32(const void* p) { return (uint32_t)__cvta_generic_to_shared(p); }
DEVI void mbar_init(uint32_t bar, uint32_t cnt) { asm volatile("mbarrier.init.shared::cta.b64 [%0], %1;" ::"r"(bar), "r"(cnt) : "memory"); }
DEVI void mbar_expect(uint32_t bar, uint32_t bytes) { asm volatile("mbarrier.arrive.expect_tx.shared::cta.b64 _, [%0], %1;" ::"r"(bar), "r"(bytes) : "memory"); }
DEVI void mbar_arrive(uint32_t bar) { asm volatile("mbarrier.arrive.shared::cta.b64 _, [%0];" ::"r"(bar) : "memory"); }
DEVI void mbar_wait(uint32_t bar, uint32_t parity) {
    uint32_t done;
    int it = 0;
    do {
        asm volatile("{\n.reg .pred p;\nmbarrier.try_wait.parity.shared::cta.b64 p, [%1], %2;\nselp.u32 %0, 1, 0, p;\n}\n"
                     : "=r"(done) : "r"(bar), "r"(parity) : "memory");
        if (++it > (1 << 22)) die(it);
    } while (!done);
}
DEVI void tma2d(uint32_t dst, const CUtensorMap* tm, uint32_t bar, int c0, int c1) {
    asm volatile("cp.async.bulk.tensor.2d.shared::cluster.global.mbarrier::complete_tx::bytes [%0], [%1, {%3, %4}], [%2];"
                 ::"r"(dst), "l"(tm), "r"(bar), "r"(c0), "r"(c1) : "memory");
}
DEVI void tma3d(uint32_t dst, const CUtensorMap* tm, uint32_t bar, int c0, int c1, int c2) {
    asm volatile("cp.async.bulk.tensor.3d.shared::cluster.global.mbarrier::complete_tx::bytes [%0], [%1, {%3, %4, %5}], [%2];"
                 ::"r"(dst), "l"(tm), "r"(bar), "r"(c0), "r"(c1), "r"(c2) : "memory");
}
DEVI void bulk_g2s(uint32_t dst, uint32_t lo, uint32_t hi, uint32_t bytes, uint32_t bar) {
    asm volatile("{\n.reg .b64 a;\nmov.b64 a, {%1,%2};\ncp.async.bulk.shared::cluster.global.mbarrier::complete_tx::bytes [%0], [a], %3, [%4];\n}"
                 ::"r"(dst), "r"(lo), "r"(hi), "r"(bytes), "r"(bar) : "memory");
}
DEVI void bulk_s2g(uint32_t lo, uint32_t hi, uint32_t src, uint32_t bytes) {
    asm volatile("{\n.reg .b64 a;\nmov.b64 a, {%0,%1};\ncp.async.bulk.global.shared::cta.bulk_group [a], [%2], %3;\ncp.async.bulk.commit_group;\n}"
                 ::"r"(lo), "r"(hi), "r"(src), "r"(bytes) : "memory");
}
DEVI void bulk_red(uint32_t lo, uint32_t hi, uint32_t src, uint32_t bytes) {
    asm volatile("{\n.reg .b64 a;\nmov.b64 a, {%0,%1};\ncp.reduce.async.bulk.global.shared::cta.bulk_group.add.noftz.bf16 [a], [%2], %3;\ncp.async.bulk.commit_group;\n}"
                 ::"r"(lo), "r"(hi), "r"(src), "r"(bytes) : "memory");
}
DEVI bool elect() {
    uint32_t p;
    asm volatile("{\n.reg .pred P;\nelect.sync _|P, 0xFFFFFFFF;\nselp.u32 %0, 1, 0, P;\n}" : "=r"(p));
    return p != 0;
}
DEVI void ldsm4(uint32_t (&r)[4], uint32_t a) {
    asm volatile("ldmatrix.sync.aligned.m8n8.x4.shared.b16 {%0,%1,%2,%3}, [%4];" : "=r"(r[0]), "=r"(r[1]), "=r"(r[2]), "=r"(r[3]) : "r"(a) : "memory");
}
DEVI void ldsm4t(uint32_t (&r)[4], uint32_t a) {
    asm volatile("ldmatrix.sync.aligned.m8n8.x4.trans.shared.b16 {%0,%1,%2,%3}, [%4];" : "=r"(r[0]), "=r"(r[1]), "=r"(r[2]), "=r"(r[3]) : "r"(a) : "memory");
}
DEVI void ldsm2t(uint32_t (&r)[2], uint32_t a) {
    asm volatile("ldmatrix.sync.aligned.m8n8.x2.trans.shared.b16 {%0,%1}, [%2];" : "=r"(r[0]), "=r"(r[1]) : "r"(a) : "memory");
}
DEVI void ldsm2(uint32_t (&r)[2], uint32_t a) {
    asm volatile("ldmatrix.sync.aligned.m8n8.x2.shared.b16 {%0,%1}, [%2];" : "=r"(r[0]), "=r"(r[1]) : "r"(a) : "memory");
}
DEVI void stsm4t(uint32_t a, uint32_t r0, uint32_t r1, uint32_t r2, uint32_t r3) {
    asm volatile("stmatrix.sync.aligned.m8n8.x4.trans.shared.b16 [%0], {%1,%2,%3,%4};" ::"r"(a), "r"(r0), "r"(r1), "r"(r2), "r"(r3) : "memory");
}
DEVI uint32_t ldsm1(uint32_t a) {
    uint32_t r;
    asm volatile("ldmatrix.sync.aligned.m8n8.x1.shared.b16 {%0}, [%1];" : "=r"(r) : "r"(a) : "memory");
    return r;
}
DEVI void stsm4(uint32_t a, uint32_t r0, uint32_t r1, uint32_t r2, uint32_t r3) {
    asm volatile("stmatrix.sync.aligned.m8n8.x4.shared.b16 [%0], {%1,%2,%3,%4};" ::"r"(a), "r"(r0), "r"(r1), "r"(r2), "r"(r3) : "memory");
}
DEVI void stsm2(uint32_t a, uint32_t r0, uint32_t r1) {
    asm volatile("stmatrix.sync.aligned.m8n8.x2.shared.b16 [%0], {%1,%2};" ::"r"(a), "r"(r0), "r"(r1) : "memory");
}
DEVI uint32_t movm(uint32_t a) {
    uint32_t d;
    asm volatile("movmatrix.sync.aligned.m8n8.trans.b16 %0, %1;" : "=r"(d) : "r"(a));
    return d;
}
DEVI void mma16(float (&d)[4], uint32_t a0, uint32_t a1, uint32_t a2, uint32_t a3, uint32_t b0, uint32_t b1) {
    asm volatile("mma.sync.aligned.m16n8k16.row.col.f32.bf16.bf16.f32 {%0,%1,%2,%3}, {%4,%5,%6,%7}, {%8,%9}, {%0,%1,%2,%3};"
                 : "+f"(d[0]), "+f"(d[1]), "+f"(d[2]), "+f"(d[3]) : "r"(a0), "r"(a1), "r"(a2), "r"(a3), "r"(b0), "r"(b1));
}
DEVI void mma16z(float (&d)[4], uint32_t a0, uint32_t a1, uint32_t a2, uint32_t a3, uint32_t b0, uint32_t b1) {
    asm volatile("mma.sync.aligned.m16n8k16.row.col.f32.bf16.bf16.f32 {%0,%1,%2,%3}, {%4,%5,%6,%7}, {%8,%9}, {%10,%10,%10,%10};"
                 : "=f"(d[0]), "=f"(d[1]), "=f"(d[2]), "=f"(d[3]) : "r"(a0), "r"(a1), "r"(a2), "r"(a3), "r"(b0), "r"(b1), "f"(0.f));
}
DEVI void mma8(float (&d)[4], uint32_t a0, uint32_t a1, uint32_t b0) {
    asm volatile("mma.sync.aligned.m16n8k8.row.col.f32.bf16.bf16.f32 {%0,%1,%2,%3}, {%4,%5}, {%6}, {%0,%1,%2,%3};"
                 : "+f"(d[0]), "+f"(d[1]), "+f"(d[2]), "+f"(d[3]) : "r"(a0), "r"(a1), "r"(b0));
}
DEVI void mma8z(float (&d)[4], uint32_t a0, uint32_t a1, uint32_t b0) {
    asm volatile("mma.sync.aligned.m16n8k8.row.col.f32.bf16.bf16.f32 {%0,%1,%2,%3}, {%4,%5}, {%6}, {%7,%7,%7,%7};"
                 : "=f"(d[0]), "=f"(d[1]), "=f"(d[2]), "=f"(d[3]) : "r"(a0), "r"(a1), "r"(b0), "f"(0.f));
}
DEVI uint32_t pack2(float lo, float hi) {
    uint32_t r;
    asm("cvt.rn.bf16x2.f32 %0, %1, %2;" : "=r"(r) : "f"(hi), "f"(lo));
    return r;
}
DEVI uint32_t hadd2(uint32_t a, uint32_t b) {
    uint32_t r;
    asm("add.rn.bf16x2 %0, %1, %2;" : "=r"(r) : "r"(a), "r"(b));
    return r;
}
DEVI float lo_f(uint32_t x) { return __uint_as_float(x << 16); }
DEVI float hi_f(uint32_t x) { return __uint_as_float(x & 0xFFFF0000u); }
template <uint32_t OFF> DEVI uint4 ldg4(uint32_t lo, uint32_t hi) {
    uint4 v;
    asm volatile("{\n.reg .b64 a;\nmov.b64 a, {%4,%5};\nld.relaxed.gpu.global.v4.u32 {%0,%1,%2,%3}, [a+%6];\n}"
                 : "=r"(v.x), "=r"(v.y), "=r"(v.z), "=r"(v.w) : "r"(lo), "r"(hi), "n"(OFF) : "memory");
    return v;
}
template <uint32_t OFF> DEVI uint2 ldg2(uint32_t lo, uint32_t hi) {
    uint2 v;
    asm volatile("{\n.reg .b64 a;\nmov.b64 a, {%2,%3};\nld.relaxed.gpu.global.v2.u32 {%0,%1}, [a+%4];\n}"
                 : "=r"(v.x), "=r"(v.y) : "r"(lo), "r"(hi), "n"(OFF) : "memory");
    return v;
}
template <uint32_t OFF> DEVI uint32_t ldg1(uint32_t lo, uint32_t hi) {
    uint32_t v;
    asm volatile("{\n.reg .b64 a;\nmov.b64 a, {%1,%2};\nld.relaxed.gpu.global.u32 %0, [a+%3];\n}" : "=r"(v) : "r"(lo), "r"(hi), "n"(OFF) : "memory");
    return v;
}
template <uint32_t OFF> DEVI void stg1(uint32_t lo, uint32_t hi, uint32_t a) {
    asm volatile("{\n.reg .b64 a;\nmov.b64 a, {%0,%1};\nst.relaxed.gpu.global.u32 [a+%3], %2;\n}" ::"r"(lo), "r"(hi), "r"(a), "n"(OFF) : "memory");
}
template <uint32_t OFF> DEVI void stg4(uint32_t lo, uint32_t hi, uint32_t a, uint32_t b, uint32_t c, uint32_t d) {
    asm volatile("{\n.reg .b64 a;\nmov.b64 a, {%0,%1};\nst.relaxed.gpu.global.v4.u32 [a+%6], {%2,%3,%4,%5};\n}"
                 ::"r"(lo), "r"(hi), "r"(a), "r"(b), "r"(c), "r"(d), "n"(OFF) : "memory");
}
template <uint32_t OFF> DEVI void stg2(uint32_t lo, uint32_t hi, uint32_t a, uint32_t b) {
    asm volatile("{\n.reg .b64 a;\nmov.b64 a, {%0,%1};\nst.relaxed.gpu.global.v2.u32 [a+%4], {%2,%3};\n}"
                 ::"r"(lo), "r"(hi), "r"(a), "r"(b), "n"(OFF) : "memory");
}
DEVI uint32_t tagx2(uint32_t a, uint32_t b, uint32_t t) { uint32_t r; asm("lop3.b32 %0, %1, %2, %3, 0x7E;" : "=r"(r) : "r"(a), "r"(b), "r"(t)); return r; }
DEVI uint32_t tagx1(uint32_t a, uint32_t b, uint32_t t) { uint32_t r; asm("lop3.b32 %0, %1, %2, %3, 0xF6;" : "=r"(r) : "r"(a), "r"(b), "r"(t)); return r; }
DEVI uint32_t or3(uint32_t a, uint32_t b, uint32_t c) { uint32_t r; asm("lop3.b32 %0, %1, %2, %3, 0xFE;" : "=r"(r) : "r"(a), "r"(b), "r"(c)); return r; }
DEVI bool any_bad(uint32_t x) { return __any_sync(0xFFFFFFFFu, (x & 1u) != 0); }
DEVI uint32_t settag(uint32_t x, uint32_t tag) { return (x & ~1u) | tag; }
DEVI void sts32f(uint32_t a, float v) { asm volatile("st.shared.f32 [%0], %1;" ::"r"(a), "f"(v) : "memory"); }
DEVI void sts32(uint32_t a, uint32_t v) { asm volatile("st.shared.u32 [%0], %1;" ::"r"(a), "r"(v) : "memory"); }
DEVI void sts16(uint32_t a, uint32_t v) { asm volatile("st.shared.u16 [%0], %1;" ::"r"(a), "h"((unsigned short)v) : "memory"); }
DEVI void sts64(uint32_t a, uint32_t x, uint32_t y) { asm volatile("st.shared.v2.u32 [%0], {%1,%2};" ::"r"(a), "r"(x), "r"(y) : "memory"); }
DEVI void sts128(uint32_t a, uint32_t x, uint32_t y, uint32_t z, uint32_t w) {
    asm volatile("st.shared.v4.u32 [%0], {%1,%2,%3,%4};" ::"r"(a), "r"(x), "r"(y), "r"(z), "r"(w) : "memory");
}
DEVI float4 lds128f(uint32_t a) {
    float4 v;
    asm volatile("ld.shared.v4.f32 {%0,%1,%2,%3}, [%4];" : "=f"(v.x), "=f"(v.y), "=f"(v.z), "=f"(v.w) : "r"(a) : "memory");
    return v;
}
DEVI uint4 lds128(uint32_t a) {
    uint4 v;
    asm volatile("ld.shared.v4.u32 {%0,%1,%2,%3}, [%4];" : "=r"(v.x), "=r"(v.y), "=r"(v.z), "=r"(v.w) : "r"(a) : "memory");
    return v;
}
DEVI uint2 lds64(uint32_t a) {
    uint2 v;
    asm volatile("ld.shared.v2.u32 {%0,%1}, [%2];" : "=r"(v.x), "=r"(v.y) : "r"(a) : "memory");
    return v;
}
DEVI uint32_t lds32(uint32_t a) {
    uint32_t v;
    asm volatile("ld.shared.u32 %0, [%1];" : "=r"(v) : "r"(a) : "memory");
    return v;
}
DEVI float ex2(float x) { float r; asm("ex2.approx.ftz.f32 %0, %1;" : "=f"(r) : "f"(x)); return r; }
DEVI float rcp(float x) { float r; asm("rcp.approx.ftz.f32 %0, %1;" : "=f"(r) : "f"(x)); return r; }
DEVI uint32_t clk() { uint32_t c; asm volatile("mov.u32 %0, %%clock;" : "=r"(c)::"memory"); return c; }

DEVI uint64_t mkdesc(uint32_t addr, uint32_t lbo, uint32_t sbo) {
    return (uint64_t)((addr & 0x3FFFF) >> 4) | ((uint64_t)(lbo >> 4) << 16) | ((uint64_t)(sbo >> 4) << 32) | ((uint64_t)1 << 62);
}
DEVI void wg_fence() { asm volatile("wgmma.fence.sync.aligned;" ::: "memory"); }
DEVI void wg_commit() { asm volatile("wgmma.commit_group.sync.aligned;" ::: "memory"); }
template <int N> DEVI void wg_wait() { asm volatile("wgmma.wait_group.sync.aligned %0;" ::"n"(N) : "memory"); }
template <int SC>
DEVI void wg_rs32(float (&d)[16], const uint32_t (&a)[4], uint64_t db) {
    if (SC) {
        asm volatile("wgmma.mma_async.sync.aligned.m64n32k16.f32.bf16.bf16 "
                     "{%0,%1,%2,%3,%4,%5,%6,%7,%8,%9,%10,%11,%12,%13,%14,%15}, {%16,%17,%18,%19}, %20, 1, 1, 1, 0;"
                     : "+f"(d[0]), "+f"(d[1]), "+f"(d[2]), "+f"(d[3]), "+f"(d[4]), "+f"(d[5]), "+f"(d[6]), "+f"(d[7]),
                       "+f"(d[8]), "+f"(d[9]), "+f"(d[10]), "+f"(d[11]), "+f"(d[12]), "+f"(d[13]), "+f"(d[14]), "+f"(d[15])
                     : "r"(a[0]), "r"(a[1]), "r"(a[2]), "r"(a[3]), "l"(db));
    } else {
        asm volatile("wgmma.mma_async.sync.aligned.m64n32k16.f32.bf16.bf16 "
                     "{%0,%1,%2,%3,%4,%5,%6,%7,%8,%9,%10,%11,%12,%13,%14,%15}, {%16,%17,%18,%19}, %20, 0, 1, 1, 0;"
                     : "=f"(d[0]), "=f"(d[1]), "=f"(d[2]), "=f"(d[3]), "=f"(d[4]), "=f"(d[5]), "=f"(d[6]), "=f"(d[7]),
                       "=f"(d[8]), "=f"(d[9]), "=f"(d[10]), "=f"(d[11]), "=f"(d[12]), "=f"(d[13]), "=f"(d[14]), "=f"(d[15])
                     : "r"(a[0]), "r"(a[1]), "r"(a[2]), "r"(a[3]), "l"(db));
    }
}

#define NPRO 5
#define NA 12
#define NB 0
#define NPF 6
#define PF1 2
#define PF2 2
#define PF3 5
#define WPF 2
#define NPE (NPF & ~1)
#define VPF 2
#define VORD (NA == 12 ? 0x01234567 : NA == 10 ? 0x50123467 : NA == 8 ? 0x40125367 : 0x30142567)
#define WV_BOX ((16 - NA) * 2048)
#define WO_BOX ((16 - NB) * 1024)
#define SM_WV 0
#define SM_WO (2 * WV_BOX)
#define SM_X (SM_WO + 4 * WO_BOX)
#define SM_XO (SM_X + 32768)
#define SM_PI (SM_XO + 12288)
#define SM_KV (SM_PI + 24576)
#define SM_SP (SM_KV + 18432)
#define SM_TR (SM_SP + 10240)
#define SM_MEMT (SM_TR + 12288)
#define SM_OT (SM_MEMT + 4096)
#define SM_VS (SM_OT + 2048)
#define SM_P (SM_VS + 2048)
#define SM_DN (SM_P + 1792)
#define SM_PROF (SM_P + 2048)
#define SM_BAR 232192
#define SM_TOTAL (SM_BAR + 128)
#define SM_STA SM_X
#define SM_STB (SM_STA + 65536)
#define SM_STC (SM_STB + 65536)
#define NA1_ ((SM_BAR - SM_STC) / 4096)
#define NA1 (NA < NA1_ ? NA : NA1_)
static_assert(SM_STC + NA1 * 4096 <= SM_BAR && NB + NA - NA1 <= 16 && SM_PROF + 3072 <= SM_BAR, "staging");
static_assert(SM_TOTAL <= 232448, "smem");
#define BAR_XA 32
#define BAR_KV 40
#define BAR_PI 48
#define SM_ROLE (SM_BAR + 64)

#define SPIN_LIMIT (1 << 20)
#define DLY_R 0
#define RPOS 20
#define OPOS 2
#define ASF 0
#define KPOS 0
#define CPOS 1
#define DLY_V 400
#define XPOS 2
#define CFAR 1
#define SD 0x0000

template <int ID, int N> DEVI void bsync() { asm volatile("bar.sync %0, %1;" ::"n"(ID), "n"(N) : "memory"); }
template <int ID, int N> DEVI void barv() { asm volatile("bar.arrive %0, %1;" ::"n"(ID), "n"(N) : "memory"); }

#define PT(n)
#define PC(n, v)
#define PDUMP()
#define REFRESH() asm volatile("xor.b32 %0, %0, %1;" : "+r"(l16) : "r"(zero))
#define OPQ(x) asm volatile("xor.b32 %0, %0, %1;" : "+r"(x) : "r"(zero))
#define KEEP(x, a, b, c, d) asm volatile("{\n.reg .b32 t;\nlop3.b32 t, %1, %2, %3, 0x80;\nlop3.b32 t, t, %4, %5, 0x80;\nxor.b32 %0, %0, t;\n}" \
                                         : "+r"(x) : "r"(a), "r"(b), "r"(c), "r"(d), "r"(zero))
#define SF() asm volatile("pmevent 1;" ::: "memory")
#define MF() __syncwarp()
#define SB0 1024u

#define XDOFF(ks) ((((ks) >> 2) * 1024 + ((ks) & 3) * 32) >> 4)
template <int SC>
DEVI void wg_ss32t(float (&d)[16], uint64_t da, uint64_t db) {
    if (SC) {
        asm volatile("wgmma.mma_async.sync.aligned.m64n32k16.f32.bf16.bf16 "
                     "{%0,%1,%2,%3,%4,%5,%6,%7,%8,%9,%10,%11,%12,%13,%14,%15}, %16, %17, 1, 1, 1, 1, 0;"
                     : "+f"(d[0]), "+f"(d[1]), "+f"(d[2]), "+f"(d[3]), "+f"(d[4]), "+f"(d[5]), "+f"(d[6]), "+f"(d[7]),
                       "+f"(d[8]), "+f"(d[9]), "+f"(d[10]), "+f"(d[11]), "+f"(d[12]), "+f"(d[13]), "+f"(d[14]), "+f"(d[15])
                     : "l"(da), "l"(db));
    } else {
        asm volatile("wgmma.mma_async.sync.aligned.m64n32k16.f32.bf16.bf16 "
                     "{%0,%1,%2,%3,%4,%5,%6,%7,%8,%9,%10,%11,%12,%13,%14,%15}, %16, %17, 0, 1, 1, 1, 0;"
                     : "=f"(d[0]), "=f"(d[1]), "=f"(d[2]), "=f"(d[3]), "=f"(d[4]), "=f"(d[5]), "=f"(d[6]), "=f"(d[7]),
                       "=f"(d[8]), "=f"(d[9]), "=f"(d[10]), "=f"(d[11]), "=f"(d[12]), "=f"(d[13]), "=f"(d[14]), "=f"(d[15])
                     : "l"(da), "l"(db));
    }
}

DEVI void delay_until(uint32_t t0, uint32_t d) { t0 += d; while (clk() < t0) {} }

template <int I0, int I1>
DEVI void xmma(float (&xa)[16], float (&xb)[16], uint32_t w, int ps, uint32_t zero, const uint32_t (&Wq)[16][4], const uint32_t (&Wk)[16][4],
               const uint32_t (&Wv)[NA][4]) {
    const uint64_t xd = mkdesc(SB0 + SM_X, 16, 4096) + (ps & 1) * 1024, vd = mkdesc(SB0 + SM_WV, 8192, 1024);
    uint32_t vo = (w >> 2) * (WV_BOX / 16);
    if (I0 < 16 - NA) OPQ(vo);
#pragma unroll
    for (int i = I0; i < I1; i++) {
        if (i == 0) wg_ss32t<0>(xb, (vd & ~0xFFFFFFFFull) | ((uint32_t)vd + vo), xd + XDOFF(NA));
        else if (i < 16 - NA) wg_ss32t<1>(xb, (vd & ~0xFFFFFFFFull) | ((uint32_t)vd + i * 128 + vo), xd + XDOFF(NA + i));
        else if (i == 16 - NA) wg_rs32<0>(xa, Wq[0], xd);
        else if (i < 32 - NA) wg_rs32<1>(xa, Wq[(i + NA) & 15], xd + XDOFF((i + NA) & 15));
        else if (i < 32) wg_rs32<1>(xb, Wv[(i + NA) & 15], xd + XDOFF((i + NA) & 15));
        else if (i == 32) wg_rs32<0>(xa, Wk[0], xd);
        else wg_rs32<1>(xa, Wk[i & 15], xd + XDOFF(i & 15));
    }
    wg_commit();
}
#define XMMA(I0, I1) xmma<(I0), (I1)>(xa, xb, w, p ^ 1, zero, Wq, Wk, Wv)
DEVI void wg_done(float (&d)[16]) {
    asm volatile("" : "+f"(d[0]), "+f"(d[1]), "+f"(d[2]), "+f"(d[3]), "+f"(d[4]), "+f"(d[5]), "+f"(d[6]), "+f"(d[7]),
                      "+f"(d[8]), "+f"(d[9]), "+f"(d[10]), "+f"(d[11]), "+f"(d[12]), "+f"(d[13]), "+f"(d[14]), "+f"(d[15]) :: "memory");
}
template <int M>
DEVI void xpack(uint32_t (&xp)[8], float (&xa)[16]) {
    wg_done(xa);
#pragma unroll
    for (int i = 0; i < 4; i++) {
        xp[2 * i] = pack2(xa[4 * i], xa[4 * i + (M < 2 ? 2 : 1)]);
        xp[2 * i + 1] = pack2(xa[4 * i + (M < 2 ? 1 : 2)], xa[4 * i + 3]);
    }
}
template <int M>
DEVI uint4 xpeer(uint32_t sb, int ps, uint32_t t16) { return lds128(sb + SM_PI + ((ps & 1) ^ 1) * 12288 + M * 4096 + t16); }
DEVI void xadd(uint32_t (&xp)[8], const uint4& pi) {
    xp[0] = hadd2(xp[0], pi.x); xp[1] = hadd2(xp[1], pi.y); xp[2] = hadd2(xp[2], pi.z); xp[3] = hadd2(xp[3], pi.w);
}
template <int M>
DEVI void xstore(const uint32_t (&xp)[8], uint32_t sb, uint32_t sbw, int ps, uint32_t t16, uint32_t KA) {
    const uint32_t a = SM_XO + M * 2048 + (M < 2 ? (KA & 0xFF) + sbw : (t16 >> 1) + sb);
    sts64(a, xp[0], xp[1]);
    sts64(a + 6144, xp[2], xp[3]);
    asm volatile("st.async.weak.shared::cluster.mbarrier::complete_tx::bytes.v4.b32 [%0], {%1,%2,%3,%4}, [%5];"
                 ::"r"((sb ^ 0x1000000) + SM_PI + (ps & 1) * 12288 + M * 4096 + t16), "r"(xp[4]), "r"(xp[5]), "r"(xp[6]), "r"(xp[7]),
                   "r"((sb ^ 0x1000000) + SM_BAR + BAR_PI + (ps & 1) * 8) : "memory");
}
template <int M>
DEVI void xpark(uint32_t (&xp)[8], const uint4& pi, uint32_t sb, uint32_t sbw, int ps, uint32_t t16, uint32_t KA) {
    xadd(xp, pi);
    xstore<M>(xp, sb, sbw, ps, t16, KA);
}
template <int M>
DEVI void xfinish(float (&xa)[16], uint32_t sb, uint32_t sbw, int ps, uint32_t t16, uint32_t KA) {
    uint32_t xp[8];
    const uint4 pi = xpeer<M>(sb, ps, t16);
    xpack<M>(xp, xa);
    xpark<M>(xp, pi, sb, sbw, ps, t16, KA);
}
DEVI void piwait(uint32_t sb, int p, int ps) { mbar_wait(sb + SM_BAR + BAR_PI + p * 8, ((ps + NPRO + 1) >> 1) & 1); }

DEVI uint32_t par(uint32_t off) { return __popc(off & 0xB2000u) & 1; }
DEVI uint32_t probe(uint32_t lo, uint32_t hi) {
    uint32_t best = 0xFFFFFFFFu, x = 0;
    stg1<0>(lo, hi, 0);
#pragma unroll 1
    for (int r = 0; r < 4; r++) {
        const uint32_t t0 = clk();
        asm volatile("{\n.reg .b64 a;\nmov.b64 a, {%1,%2};\natom.relaxed.gpu.global.add.u32 %0, [a], 2;\n}" : "=r"(x) : "r"(lo), "r"(hi) : "memory");
        if (x == 0xFFFFFFFFu) die(1 << 23);
        best = min(best, clk() - t0);
    }
    return best;
}

DEVI void xload(uint32_t sb, uint32_t u, uint32_t j, int ps, const CUtensorMap* tmx) {
    if (elect()) {
        const uint32_t sg = ps + 4 - (u & 1) + (u >> 1);
        mbar_expect(sb + SM_BAR + BAR_XA, sg < NSEG ? 4096 : 0);
        if (sg < NSEG) tma3d(sb + SM_X + (ps & 1) * 16384 + u * 4096, tmx, sb + SM_BAR + BAR_XA, 0, sg * 32 + (j ^ ((u & 1) * 2 + (u >> 1))) * 8, j * 4);
    }
}
DEVI uint32_t rpage(uint32_t j, int s) { return (s & 3) * 65536 + (j & 1) * 8192 + (((s ^ (s >> 1) ^ j ^ (j >> 1)) & 1) << 12); }

#define RLOAD(a) { m0 = ldg4<XO_R>(a, xhi); n0 = ldg4<XO_R + 16384>(a, xhi); \
                   e0 = ldg1<XO_R + 32768>(((a) & ~0xFFFu) + (((a) & 0xFFF) >> 2), xhi); f0 = ldg1<XO_R + 33792>(((a) & ~0xFFFu) + (((a) & 0xFFF) >> 2), xhi); }
DEVI bool ruse(uint32_t a, const uint4& m0, const uint4& n0, uint32_t e0, uint32_t f0) {
    const uint32_t a0 = hadd2(m0.w, n0.w), b0 = hadd2(e0, f0);
    stsm4(a, hadd2(m0.x, n0.x), hadd2(m0.y, n0.y), hadd2(m0.z, n0.z), __byte_perm(a0, b0, 0x5410));
    return __any_sync(0xFFFFFFFFu, (a0 & b0 & 0x42000000u) != 0x42000000u);
}

template <bool MAIN>
DEVI void helper_step(uint32_t sb, uint32_t w, uint32_t h, uint32_t j, uint32_t& l16, uint32_t xlo, uint32_t xhi, uint32_t zero, int s,
                      const CUtensorMap* tmx, const bf16* __restrict__ mem0) {
    const uint32_t u = w - 8, bq = sb + SM_BAR;
    bsync<1, 384>();
    PT(0);
    PDUMP();
    PT(1);
    if (MAIN) {
        const uint32_t ctag = ((s >> 1) & 1) ^ 1;
        const uint32_t av = xlo + ((s & 1) * 32 + h) * 8192 + u * 512;
        mbar_wait(bq + BAR_XA, (s + NPRO) & 1);
        bsync<8, 384>();
        delay_until(clk(), DLY_V);
        PT(4);
        int it = 0;
        bool bad;
        do {
            const uint4 d1 = ldg4<XO_CV>(av + (j ^ 1) * 2048 + l16, xhi);
            const uint4 d2 = ldg4<XO_CV>(av + (j ^ 2) * 2048 + l16, xhi);
            const uint4 d3 = ldg4<XO_CV>(av + (j ^ 3) * 2048 + l16, xhi);
            bad = any_bad(or3(tagx2(d1.x, d1.z, ctag), tagx2(d2.x, d2.z, ctag), tagx2(d3.x, d3.z, ctag)));
            sts128(sb + SM_VS + u * 512 + l16, hadd2(hadd2(d1.x, d2.x), d3.x), hadd2(hadd2(d1.y, d2.y), d3.y), hadd2(hadd2(d1.z, d2.z), d3.z),
                   hadd2(hadd2(d1.w, d2.w), d3.w));
            REFRESH();
            if (++it > SPIN_LIMIT) die(it);
        } while (bad);
        PC(26, it - 1);
    } else {
        if (u == 0) stg2<XO_FL>(xlo + ((s + NPRO) * 128 + h * 4 + j) * 32, xhi, 1, 1);
        if (s == -NPRO) {
            xload(sb, u, j, s, tmx);
#pragma unroll 1
            for (int e = 0; e < 4; e++) sts128(sb + SM_TR + 4096 + e * 2048 + u * 512 + l16, 0, 0, 0, 0);
        }
        if (s == -1) {
#pragma unroll 1
            for (int e = 0; e < 2; e++) {
                const uint32_t d = e * 128 + u * 32 + (l16 >> 4);
                const unsigned short* m0 = (const unsigned short*)mem0 + j * 256 + d;
                uint32_t v[4];
#pragma unroll
                for (int i = 0; i < 4; i++) v[i] = (uint32_t)m0[(2 * i) * DM] | ((uint32_t)m0[(2 * i + 1) * DM] << 16);
                sts128(sb + SM_MEMT + d * 16, v[0], v[1], v[2], v[3]);
            }
        }
        mbar_wait(bq + BAR_XA, (s + NPRO) & 1);
    }
    PT(5);
    barv<5, 384>();
    bsync<3, 384>();
    if (!MAIN) {
        int it = 0;
        while (__any_sync(0xFFFFFFFFu, ldg2<XO_FL>(xlo + ((s + NPRO) * 128 + h * 4) * 32 + ((l16 & 0x30) << 1), xhi).x == 0))
            if (++it > SPIN_LIMIT) die(it);
    }
    if (u < 2) {
        asm volatile("fence.proxy.async.shared::cta;" ::: "memory");
        if (MAIN && SD) delay_until(clk(), ((SD >> (4 * u)) & 15) * 100);
        if (elect()) {
            const uint32_t sg = s + 3 - u;
            if (sg < NSEG) {
                const uint32_t ga = xlo + XO_XG + (((sg & 7) * 32 + h) * 4 + (j ^ (2 * u))) * 6144, sa = sb + SM_XO + u * 6144;
                if (u == 0) bulk_s2g(ga, xhi, sa, 6144);
                else bulk_red(ga, xhi, sa, 6144);
            }
        }
    }
    PT(6);
    uint32_t old = 0;
    if (XPOS == 0) xload(sb, u, j, s + 1, tmx);
    if (MAIN && u > 0) asm volatile("{\n.reg .b64 a;\nmov.b64 a, {%1,%2};\natom.relaxed.gpu.global.exch.b32 %0, [a], 0;\n}"
                                    : "=r"(old) : "r"(xlo + XO_R + rpage(j, s + 2) + (u - 1) * 16384 + h * 128 + (l16 >> 2)), "r"(xhi) : "memory");
    PT(7);
    const uint32_t ac = xlo + XO_PB + 8192 + (((j >> 1) ^ 1) << 12) + (j & 1) * 128;
    if (MAIN) {
        bsync<7, 384>();
        if (u == 3 && elect()) asm volatile("{\n.reg .b64 a;\nmov.b64 a, {%0,%1};\nred.relaxed.gpu.global.add.u32 [a], 1;\n}" ::"r"(ac), "r"(xhi) : "memory");
    }
    if (s >= -1 && s + 1 < NSEG && elect()) {
        const uint32_t o = u == 0 ? 0 : 2048;
        mbar_expect(bq + BAR_KV, 6144 - o);
        bulk_g2s(sb + SM_KV + u * 4096 + o, xlo + XO_XG + ((((s + 1) & 7) * 32 + h) * 4 + ((j + u) & 3)) * 6144 + o, xhi, 6144 - o, bq + BAR_KV);
    }
    if (XPOS == 1) xload(sb, u, j, s + 1, tmx);
    if (u < 2) {
        asm volatile("cp.async.bulk.wait_group.read 0;" ::: "memory");
        if (elect()) mbar_expect(bq + BAR_PI + ((s & 1) ^ 1) * 8, !MAIN && s == -NPRO ? 0 : 6144);
    }
    PT(8);
    if (XPOS == 2) {
        if (MAIN && s + 1 < NSEG) bsync<10, 384>();
        xload(sb, u, j, s + 1, tmx);
    }
    if (MAIN && DLY_R && s + 1 < NSEG) {
        int it = 0;
        while (ldg1<0>(ac, xhi) < 32 * s + 32)
            if (++it > SPIN_LIMIT) die(it);
        PC(22, it);
        delay_until(clk(), DLY_R);
        PT(12);
        barv<11, 384>();
    }
    asm volatile("cp.async.bulk.wait_group 0;" ::: "memory");
    if (s >= -1 && s + 1 < NSEG) mbar_wait(bq + BAR_KV, (s + 1) & 1);
    asm volatile("lop3.b32 %0, %0, %1, %2, 0x78;" : "+r"(l16) : "r"(old), "r"(zero));
    PT(15);
}

__global__ void __cluster_dims__(2, 1, 1) __launch_bounds__(384, 1)
chain_kernel(const __grid_constant__ CUtensorMap tmq, const __grid_constant__ CUtensorMap tmk,
             const __grid_constant__ CUtensorMap tmv, const __grid_constant__ CUtensorMap tmo,
             const __grid_constant__ CUtensorMap tmx, const bf16* __restrict__ mem0, const bf16* __restrict__ xg,
             uint32_t xlo, uint32_t xhi, uint32_t zero, int nseg) {
    extern __shared__ __align__(1024) uint8_t smem[];
    if ((smem_u32(smem) & 0xFFFFFF) != SB0) die(1 << 23);
    asm volatile("griddepcontrol.launch_dependents;" ::: "memory");
    const uint32_t w = __reduce_max_sync(0xFFFFFFFFu, threadIdx.x >> 5);
    const uint32_t rk = smem_u32(smem) & 0x1000000;
    const uint32_t sb = __reduce_max_sync(0xFFFFFFFFu, smem_u32(smem));
    const uint32_t bq = sb + SM_BAR, bk = bq + 8, bv = bq + 16, bo = bq + 24;
    uint32_t l16 = __shfl_sync(0xFFFFFFFFu, (threadIdx.x & 31) * 16, threadIdx.x & 31);
    if (threadIdx.x == 0) {
        mbar_init(bq, 1); mbar_init(bk, 1); mbar_init(bv, 1); mbar_init(bo, 2);
        mbar_init(bq + BAR_XA, 4); mbar_init(bq + BAR_KV, 4); mbar_init(bq + BAR_PI, 2); mbar_init(bq + BAR_PI + 8, 2);
        asm volatile("fence.mbarrier_init.release.cluster;" ::: "memory");
        asm volatile("fence.proxy.async.shared::cta;" ::: "memory");
    }
    if (rk == 0) {
        if (w < 2 && l16 == 0) sts32(sb + SM_ROLE + w * 4, probe(xlo + XO_PB + w * 4096 + blockIdx.x * 16, xhi));
        __syncthreads();
        if (threadIdx.x == 0) {
            uint32_t side = (lds32(sb + SM_ROLE) < lds32(sb + SM_ROLE + 4) ? 0u : 1u) ^ par(XO_PB);
            uint32_t* tk = (uint32_t*)(((uint64_t)xhi << 32) | (xlo + XO_TK));
            uint32_t t = atomicAdd(tk + side, 1u);
            if (t >= 32) {
                uint2 c;
                int it = 0;
                do {
                    c = ldg2<XO_TK>(xlo, xhi);
                    if (++it > SPIN_LIMIT) die(it);
                } while (c.x + c.y != gridDim.x / 2);
                t += (side ? c.x : c.y) - 32;
                side ^= 1;
            }
            sts32(sb + SM_ROLE + 8, t * 4 + side * 2);
        }
    }
    __syncthreads();
    asm volatile("barrier.cluster.arrive.release.aligned;\nbarrier.cluster.wait.acquire.aligned;" ::: "memory");
    uint32_t role;
    asm volatile("ld.shared::cluster.u32 %0, [%1];" : "=r"(role) : "r"(SB0 + SM_ROLE + 8) : "memory");
    role = __reduce_max_sync(0xFFFFFFFFu, role) + (rk >> 24);
    asm volatile("barrier.cluster.arrive.release.aligned;\nbarrier.cluster.wait.acquire.aligned;" ::: "memory");
    if (role >= 128) return;
    const uint32_t h = role >> 2, j = role & 3;

    if (w >= 8) {
        asm volatile("setmaxnreg.dec.sync.aligned.u32 24;");
        if (w == 8) {
            if (elect()) {
                mbar_expect(bq, 65536);
                tma2d(sb + SM_STA, &tmq, bq, h * 128, j * 256);
                tma2d(sb + SM_STA + 32768, &tmq, bq, h * 128 + 64, j * 256);
                mbar_expect(bk, 65536);
                tma2d(sb + SM_STB, &tmk, bk, h * 128, j * 256);
                tma2d(sb + SM_STB + 32768, &tmk, bk, h * 128 + 64, j * 256);
                mbar_expect(bv, (16 - NA + NA1) * 4096);
#pragma unroll 1
                for (int i = 0; i < 32; i++) {
                    const int ks = i >> 1, g = i & 1;
                    if (ks < NA1 || ks >= NA)
                        tma2d((ks < NA ? sb + SM_STC + g * (NA1 * 2048) + ks * 2048 : sb + SM_WV + g * WV_BOX + (ks - NA) * 2048), &tmv, bv, h * 128 + g * 64, j * 256 + ks * 16);
                }
                mbar_expect(bo, 4 * WO_BOX);
#pragma unroll 1
                for (int i = 0; i < 32 - 2 * NB; i++) {
                    const int ks = i >> 2, g = i & 3;
                    tma2d(sb + SM_WO + g * WO_BOX + ks * 2048, &tmo, bo, j * 256 + g * 64, h * 128 + (ks < NPE / 2 ? ks : ks + NB / 2) * 16);
                }
            }
        }
        GSYNC(0);
        bsync<9, 384>();
        if (w == 8) {
            if (elect()) {
                mbar_expect(bo, (NB + NA - NA1) * 4096);
#pragma unroll 1
                for (int i = 2 * NA1; i < 2 * NA; i++) {
                    const int ks = i >> 1, g = i & 1;
                    tma2d(sb + SM_STA + NB * 4096 + g * ((NA - NA1) * 2048) + (ks - NA1) * 2048, &tmv, bo, h * 128 + g * 64, j * 256 + ks * 16);
                }
#pragma unroll 1
                for (int i = 0; i < 2 * NB; i++) {
                    const int ks = i >> 2, g = i & 3;
                    tma2d(sb + SM_STA + g * (NB * 1024) + ks * 2048, &tmo, bo, j * 256 + g * 64, h * 128 + (ks + NPE / 2) * 16);
                }
                asm volatile("cp.async.bulk.prefetch.L2.global [%0], %1;" ::"l"((const char*)xg + role * 32768), "r"(32768) : "memory");
            }
        }
#pragma unroll 1
        for (int s = -NPRO; s < 0; s++) helper_step<false>(sb, w, h, j, l16, xlo, xhi, zero, s, &tmx, mem0);
#pragma unroll 1
        for (int s = 0; s < nseg; s++) helper_step<true>(sb, w, h, j, l16, xlo, xhi, zero, s, &tmx, mem0);
        piwait(sb, 0, nseg - 2);
        GSYNC(1);
    } else {
        asm volatile("setmaxnreg.inc.sync.aligned.u32 240;");
        uint32_t Wq[16][4], Wk[16][4], Wv[NA][4], Wo[NB > 0 ? NB : 1][4];
        uint32_t t16, KA, KB, KC, KD;
        {
            const uint32_t lane = l16 >> 4, g = lane >> 2, t = lane & 3;
            const uint32_t rw = (((lane >> 4) & 1) * 8 + (lane & 7)) * 128u;
            const uint32_t off = rw + ((((w & 3) * 2 + ((lane >> 3) & 1)) ^ (lane & 7)) << 4);
            const uint32_t offo = rw + ((((w & 1) * 4 + ((lane >> 3) & 1)) ^ (lane & 7)) << 4);
            const uint32_t r = 2 * (t & 1) + (g >> 2);
            const uint32_t mk0 = t < 2 ? 0 : (r == 0 ? 2 * g > w : j + r < 4), mk1 = t < 2 ? 0 : (r == 0 ? 2 * g + 1 > w : j + r < 4);
            t16 = __shfl_sync(0xFFFFFFFFu, w * 512 + l16, lane);
            KA = __shfl_sync(0xFFFFFFFFu, (w * 512 + t * 64 + g * 8) | ((w * 512 + (g & 1) * 256 + (g >> 1) * 64 + t * 16) << 16), lane);
            KB = __shfl_sync(0xFFFFFFFFu, ((w >> 2) * WV_BOX + off) | mk0 | (mk1 << 1) |
                                              ((w * 256 + (g >> 2) * 4096 + (g & 3) * 64 + t * 16) << 16), lane);
            KC = __shfl_sync(0xFFFFFFFFu, ((lane & 7) * 1280 + (lane >> 3) * 128 + ((w ^ (lane & 7)) << 4)) | (((t >> 1) * 16 + g * 2) << 16) | ((t * 64 + g * 8) << 24), lane);
            KD = __shfl_sync(0xFFFFFFFFu, ((w >> 1) * WO_BOX + offo) | (((lane & 7) * 208 + (lane >> 3) * 16) << 16), lane);
            mbar_wait(bq, 0);
#pragma unroll
            for (int ks = 0; ks < 16; ks++) ldsm4t(Wq[ks], sb + SM_STA + (w >> 2) * 32768 + off + ks * 2048);
            asm volatile("fence.proxy.async.shared::cta;" ::: "memory");
            barv<9, 384>();
            mbar_wait(bk, 0);
#pragma unroll
            for (int ks = 0; ks < 16; ks++) ldsm4t(Wk[ks], sb + SM_STB + (w >> 2) * 32768 + off + ks * 2048);
            mbar_wait(bv, 0);
#pragma unroll
            for (int ks = 0; ks < NA1; ks++) ldsm4t(Wv[ks], sb + SM_STC + (w >> 2) * (NA1 * 2048) + off + ks * 2048);
            mbar_wait(bo, 0);
#pragma unroll
            for (int ks = NA1; ks < NA; ks++) ldsm4t(Wv[ks], sb + SM_STA + NB * 4096 + (w >> 2) * ((NA - NA1) * 2048) + off + (ks - NA1) * 2048);
#pragma unroll
            for (int i = 0; i < NB; i++) ldsm4t(Wo[i], sb + SM_STA + (w >> 1) * (NB * 1024) + (offo ^ ((i & 1) << 5)) + (i >> 1) * 2048);
            asm volatile("fence.proxy.async.shared::cta;" ::: "memory");
        }
        const uint32_t ONES = 0x3F803F80u;
#define UNI(x) __reduce_max_sync(0xFFFFFFFFu, x)
        uint32_t swi = UNI((uint32_t)((uint64_t)smem >> 32));
        const uint32_t sbw = UNI(sb + w * 256), sbm = UNI(sb - w * 512), sbs = UNI(sb + w * 768), sbp = UNI(sb + w * 208);
#define OPQALL() { OPQ(t16); OPQ(KA); OPQ(KB); OPQ(KC); OPQ(KD); }
        bsync<1, 384>();
        barv<3, 384>();
        bsync<5, 384>();
#pragma unroll 1
        for (int s2 = 1 - NPRO; s2 < 0; s2 += 2)
#pragma unroll
        for (int p = 0; p < 2; p++) {
            const int s = s2 + p;
            float xa[16], xb[16];
            wg_fence();
            XMMA(0, 32 - NA);
            XMMA(32 - NA, 32);
            piwait(sb, p, s - 2);
            wg_wait<1>();
            xfinish<0>(xa, sb, sbw, p ^ 1, t16, KA);
            wg_fence();
            XMMA(32, 48);
            bsync<1, 384>();
            wg_wait<1>();
            xfinish<2>(xb, sb, sbw, p ^ 1, t16, KA);
            wg_wait<0>();
            xfinish<1>(xa, sb, sbw, p ^ 1, t16, KA);
            barv<3, 384>();
            bsync<5, 384>();
            OPQALL();
        }
        const uint32_t cb0 = (h >> 1) * 32768 + (j & 1) * 16384 + (h & 1) * 8192;
        const uint32_t cb = xlo + cb0 + ((par(cb0) ^ (j >> 1) ^ CFAR) << 12);
        const uint32_t uox = xlo + XO_OX + (h * 2 + (w >> 2)) * 16384 + j * 1024 + (w & 3) * 256 - w * 128;
        float ox[4];
        float4 dn;
#define OXSTORE(s) asm volatile("{\n.reg .b64 a;\nmov.b64 a, {%0,%1};\nst.global.u32 [a], %2;\nst.global.u32 [a+128], %3;\n}" \
                                ::"r"(uox + (t16 >> 2) + ((s) >> 2) * (1u << 20) + ((s) & 3) * 4096), "r"(xhi), \
                                  "r"(pack2(ox[0] * dn.y, ox[1] * dn.w)), "r"(pack2(ox[2] * dn.y, ox[3] * dn.w)) : "memory")
#pragma unroll 1
        for (int s2 = 0;; s2 += 2)
#pragma unroll
        for (int p = 0; p < 2; p++) {
            const int s = s2 + p;
            const uint32_t ctag = ((s2 >> 1) & 1) ^ 1;
            const uint32_t hb = cb ^ (p * 0x81000), rb = xlo + rpage(j, s);
            uint4 k0, k1;
            uint32_t qx0, qx1, ov0, ov1;
            {
                float xa[16], xb[16];
                uint4 m0, n0;
                uint32_t e0, f0, a = xlo + rpage(j, s - 1) + t16;
                uint32_t xp[8];
                wg_fence();
                XMMA(0, 6);
                SF();
                piwait(sb, p, s - 2);
                uint4 pi = xpeer<0>(sb, p ^ 1, t16);
                SF();
                wg_fence();
                XMMA(6, RPOS);
                XMMA(RPOS, RPOS + 4);
                wg_wait<1>();
                SF();
                PT(11);
                if (DLY_R && (p == 1 || s2 > 0)) bsync<11, 384>();
                RLOAD(a);
                SF();
#define QPOS (RPOS >= 32 - NA ? RPOS : RPOS + 4 >= 32 - NA ? RPOS + 4 : 32 - NA)
                if (QPOS > RPOS) {
                    wg_fence();
                    if (QPOS > RPOS + 4) XMMA(RPOS + 4, QPOS);
                    XMMA(QPOS, QPOS + 4);
                    wg_wait<1>();
                    SF();
                }
                xpack<0>(xp, xa);
                xpark<0>(xp, pi, sb, sbw, p ^ 1, t16, KA);
                pi = xpeer<2>(sb, p ^ 1, t16);
                SF();
                if (QPOS + 4 < 32) {
                    wg_fence();
                    XMMA(QPOS + 4, 32);
                    SF();
                }
                wg_wait<0>();
                xpack<2>(xp, xb);
                xpark<2>(xp, pi, sb, sbw, p ^ 1, t16, KA);
                SF();
                PT(12);
                if (p == 1 || s2 > 0) {
                    int it = 0;
                    while (ruse(sb + SM_MEMT + t16, m0, n0, e0, f0)) {
                        OPQ(a);
                        RLOAD(a);
                        if (++it > SPIN_LIMIT) die(it);
                    }
                    PC(22, it + 1);
                }
                PT(13);
                OPQ(KA); OPQ(t16);
                uint32_t acw = hb + (KA & 0xFFFF), ahi = xhi, tg = ctag;
                OPQ(acw); OPQ(ahi); OPQ(tg);
                SF();
                bsync<1, 384>();
                PT(0);
                uint32_t b[8][4];
#pragma unroll
                for (int i = 0; i < 8; i++) {
                    const int pp = i < 2 ? i : i ^ 1;
                    ldsm4t(b[pp], sbm + SM_MEMT + t16 + pp * 512);
                    if (i < 7) MF();
                }
                if (ASF) SF();
                float q[4], k[4];
                const uint32_t aWv = sb + SM_WV + (KB & 0xFFF0);
                uint32_t wv[16 - NA > 0 ? 16 - NA : 1][4];
#define WVLD(n0, n1) _Pragma("unroll") for (int n = (n0); n < (n1) && n < 16 - NA; n++) ldsm4t(wv[n], aWv + n * 2048)
#pragma unroll
                for (int ks = 0; ks < 16; ks++) {
                    const uint32_t b0 = b[ks >> 1][(ks & 1) * 2], b1 = b[ks >> 1][(ks & 1) * 2 + 1];
                    if (ks == 0) {
                        mma16z(q, Wq[0][0], Wq[0][1], Wq[0][2], Wq[0][3], b0, b1);
                        mma16z(k, Wk[0][0], Wk[0][1], Wk[0][2], Wk[0][3], b0, b1);
                    } else {
                        mma16(q, Wq[ks][0], Wq[ks][1], Wq[ks][2], Wq[ks][3], b0, b1);
                        mma16(k, Wk[ks][0], Wk[ks][1], Wk[ks][2], Wk[ks][3], b0, b1);
                    }
                    if (ks == 10 && VPF) { SF(); WVLD(0, VPF); }
                }
                const uint32_t oq0 = settag(pack2(q[0], q[2]), tg), oq1 = settag(pack2(q[1], q[3]), tg);
                const uint32_t ok0 = pack2(k[0], k[2]), ok1 = pack2(k[1], k[3]);
                stg2<XO_CQK>(acw, ahi, oq0, ok0);
                stg2<XO_CQK + 256>(acw, ahi, oq1, ok1);
                SF();
                PT(1);
                int nl = VPF;
#pragma unroll
                for (int rd = 0; rd < 8; rd++) {
                    const int pp = (VORD >> (28 - 4 * rd)) & 7;
                    const uint32_t* a = 2 * pp < NA ? Wv[2 * pp < NA ? 2 * pp : 0] : wv[2 * pp < NA ? 0 : 2 * pp - NA];
                    const uint32_t* c = 2 * pp < NA ? Wv[2 * pp < NA ? 2 * pp + 1 : 0] : wv[2 * pp < NA ? 0 : 2 * pp + 1 - NA];
                    if (rd == 0) {
                        mma16z(q, a[0], a[1], a[2], a[3], b[pp][0], b[pp][1]);
                        mma16z(k, c[0], c[1], c[2], c[3], b[pp][2], b[pp][3]);
                    } else {
                        mma16(q, a[0], a[1], a[2], a[3], b[pp][0], b[pp][1]);
                        mma16(k, c[0], c[1], c[2], c[3], b[pp][2], b[pp][3]);
                    }
                    if (rd == 0) {
                        SF();
                        OPQ(swi);
                        asm volatile("{\n.reg .b64 a;\nmov.b64 a, {%0,%1};\nst.v2.u32 [a], {%2,%3};\nst.v2.u32 [a+256], {%4,%5};\n}"
                                     ::"r"((KA & 0xFFF) + (sb ^ 0x1000000) + SM_TR + 4096 + p * 4096), "r"(swi), "r"(oq0), "r"(ok0), "r"(oq1), "r"(ok1) : "memory");
                        sts64(sb + SM_TR + (KA & 0xFFF), oq0, ok0);
                        sts64(sb + SM_TR + (KA & 0xFFF) + 256, oq1, ok1);
                    }
                    if (rd == 4) KEEP(t16, oq0, oq1, ok0, ok1);
                    if (nl < 16 - NA) {
                        SF();
                        WVLD(nl, nl + (2 * pp < NA ? 1 : 3));
                        nl += 2 * pp < NA ? 1 : 3;
                    } else if (nl < 32) {
                        SF();
                        k0 = lds128(sb + SM_KV + 2048 + (KB >> 16));
                        nl = 32;
                    } else if (nl == 32) {
                        SF();
                        k1 = lds128(sb + SM_KV + 10240 + (KB >> 16));
                        const uint4 qq = lds128(sbw + SM_KV + ((KA >> 16) & 0xFF));
                        qx0 = (t16 & 64) ? qq.y : qq.x;
                        qx1 = (t16 & 64) ? qq.w : qq.z;
                        nl = 33;
                    }
                }
                ov0 = pack2(q[0] + k[0], q[1] + k[1]);
                ov1 = pack2(q[2] + k[2], q[3] + k[3]);
                stg2<XO_CV>(xlo + ((p * 32 + h) * 4 + j) * 2048 + (t16 >> 1), xhi, settag(ov0, tg), ov1);
                barv<8, 384>();
            }
            OPQ(t16);
            SF();
            PT(2);
            PDUMP();
            {
                const uint32_t a0 = sb + SM_KV;
#define CLOADG() { c2 = ldg4<XO_CQK>((hb ^ 0x1000) + (KA >> 16), xhi); c3 = ldg4<XO_CQK>((hb ^ 0x5000) + (KA >> 16), xhi); }
#define CLOADS() { c0 = lds128(sb + SM_TR + (KA >> 16)); c1 = lds128(sb + SM_TR + 4096 + p * 4096 + (KA >> 16)); }
                uint4 c0, c1, c2, c3, pi;
                float xa[16], xb[16];
                uint32_t xp[8];
                wg_fence();
                XMMA(32, 32 + CPOS);
                XMMA(32 + CPOS, 36 + CPOS);
                wg_wait<1>();
                SF();
                CLOADG();
                SF();
                CLOADS();
                if (KPOS == 0) pi = xpeer<1>(sb, p ^ 1, t16);
                SF();
                wg_fence();
                XMMA(36 + CPOS, 48);
                SF();
                const uint32_t ka[4] = {k0.x, k0.y, k0.z, k0.w}, kb[4] = {k1.x, k1.y, k1.z, k1.w};
                const uint32_t aSp = sb + SM_SP + (KC & 0xFFFF);
                PT(3);
#define SCORES(FIRST) { \
                    const uint32_t qA = hadd2(hadd2(c0.x, c1.x), hadd2(c2.x, c3.x)), qB = hadd2(hadd2(c0.z, c1.z), hadd2(c2.z, c3.z)); \
                    const uint32_t kA = hadd2(hadd2(c0.y, c1.y), hadd2(c2.y, c3.y)), kB = hadd2(hadd2(c0.w, c1.w), hadd2(c2.w, c3.w)); \
                    bad = any_bad(or3(tagx2(c1.x, c1.z, ctag), tagx2(c2.x, c2.z, ctag), tagx2(c3.x, c3.z, ctag))); \
                    float sa[4], sb_[4], sc[4], sd[4], se[4]; \
                    if (FIRST) { SF(); wg_wait<0>(); } \
                    mma16z(sa, ka[0], ka[1], ka[2], ka[3], qA, qB); \
                    mma16z(sb_, kb[0], kb[1], kb[2], kb[3], qA, qB); \
                    mma16z(sc, qA, qx0, qB, qx1, kA, kB); \
                    if (FIRST) { \
                        xpack<1>(xp, xa); \
                        if (KPOS == 0) { xadd(xp, pi); xstore<1>(xp, sb, sbw, p ^ 1, t16, KA); barv<3, 384>(); } \
                        mma16z(sd, ka[0], ka[1], ka[2], ka[3], qx0, qx1); \
                        mma16z(se, kb[0], kb[1], kb[2], kb[3], qx0, qx1); \
                    } \
                    stsm4t(aSp, pack2(sa[0], sa[1]), pack2(sa[2], sa[3]), pack2(sb_[0], sb_[1]), pack2(sb_[2], sb_[3])); \
                    stsm2(aSp + 1024, pack2(sc[0], sc[1]), pack2(sc[2], sc[3])); \
                    if (FIRST) { \
                        stsm4t(aSp + 512, pack2(sd[0], sd[1]), pack2(sd[2], sd[3]), pack2(se[0], se[1]), pack2(se[2], se[3])); \
                        if (KPOS == 0) { KEEP(KD, xp[0], xp[1], xp[2], xp[3]); KEEP(KD, xp[4], xp[5], xp[6], xp[7]); } \
                    } }
                int it = 0;
                bool bad;
                SCORES(true);
                while (__builtin_expect(bad, 0)) {
                    OPQ(KA);
                    CLOADG();
                    CLOADS();
                    SCORES(false);
                    if (++it > SPIN_LIMIT) die(it);
                }
                PC(25, it);
                PT(4);
                bsync<4, 256>();
                uint32_t wo[16 - NB][4];
                const uint32_t aWo = sb + SM_WO + (KD & 0xFFFF), aWo1 = sb + SM_WO + ((KD & 0xFFFF) ^ 32);
#define WOLD(n0, n1) _Pragma("unroll") for (int n = (n0); n < (n1) && n < 16 - NB; n++) ldsm4t(wo[n], ((n & 1) ? aWo1 : aWo) + (n >> 1) * 2048)
                const bool hi = (t16 & 32) != 0;
                const uint32_t t8 = t16 >> 1;
                uint2 v0, v1, v2, v3;
                uint32_t es;
                {
                    uint32_t am[4], ax[4], a4[2];
                    const uint32_t aSr = sbs + SM_SP + t16;
                    ldsm4t(am, aSr);
                    ldsm4t(ax, aSr + 512);
                    ldsm2t(a4, aSr + 1024);
                    MF();
                    if (KPOS == 1) pi = xpeer<1>(sb, p ^ 1, t16);
                    const uint32_t se = (t16 & 128) ? 0u : ONES, so = se ^ ONES;
                    float hm[4], hx[4], h4[4];
                    mma16z(hm, am[0], am[1], am[2], am[3], se, so);
                    mma16z(hx, ax[0], ax[1], ax[2], ax[3], se, so);
                    mma8z(h4, a4[0], a4[1], ONES);
                    SF();
                    if (KPOS == 1) { xpark<1>(xp, pi, sb, sbw, p ^ 1, t16, KA); barv<3, 384>(); }
                    v0 = lds64(a0 + 4096 + t8); v1 = lds64(a0 + 8192 + t8); v2 = lds64(a0 + 12288 + t8); v3 = lds64(a0 + 16384 + t8);
                    WOLD(0, PF2);
                    float s0 = hi ? hx[0] : hm[0], s1 = hi ? hx[2] : hm[2];
                    const float s2 = hi ? h4[2] : h4[0];
                    s0 = (KB & 1) ? -1.0e9f * 11.313708499f : s0;
                    s1 = (KB & 2) ? -1.0e9f * 11.313708499f : s1;
                    int mi = __float_as_int(fmaxf(fmaxf(s0, s2), s1));
                    mi ^= (mi >> 31) & 0x7FFFFFFF;
                    const int mm = __reduce_max_sync(0xFFFFFFFFu, hi ? (int)0x80000000 : mi), mx = __reduce_max_sync(0xFFFFFFFFu, hi ? mi : (int)0x80000000);
                    SF();
                    WOLD(PF2, PF3);
                    SF();
                    mi = hi ? mx : mm;
                    mi ^= (mi >> 31) & 0x7FFFFFFF;
                    const float c2_ = 0.08838834764831845f * 1.4426950408889634f;
                    const float mc = __int_as_float(mi) * c2_;
                    const float e0 = ex2(fmaf(s0, c2_, -mc)), e1 = ex2(fmaf(s1, c2_, -mc)), e2 = ex2(fmaf(s2, c2_, -mc));
                    sts32(sbp + SM_P + (KC >> 25), pack2(e0, e1));
                    sts16(sbp + SM_P + 128 + ((KC >> 16) & 0xFF), pack2(e2, e2));
                    es = __float_as_uint(fmaf(e2, 0.5f, e0 + e1) + 64.f);
                }
                const uint32_t sm = __reduce_add_sync(0xFFFFFFFFu, hi ? 0u : es), sx = __reduce_add_sync(0xFFFFFFFFu, hi ? es : 0u);
                const uint32_t aPr = sb + SM_P + (KD >> 16);
                PT(5);
                bsync<5, 384>();
                uint32_t pm[4], px[4], p4[2];
                ldsm4(pm, aPr);
                MF();
                const uint2 vs = lds64(sb + SM_VS + t8);
                MF();
                ldsm2(p4, aPr + 128);
                MF();
                ldsm4(px, aPr + 64);
                MF();
                sts32f(sb + SM_DN + w * 8 + ((t16 >> 3) & 4), rcp(__uint_as_float((hi ? sx : sm) - 15u * 0x42800000u) - 64.f));
                MF();
                WOLD(PF3, NPF);
                const uint32_t vm0 = hadd2(ov0, vs.x), vm1 = hadd2(ov1, vs.y);
                float oa[4], ob[4];
                mma16z(oa, v0.x, v0.y, v1.x, v1.y, pm[0], pm[1]);
                mma16z(ob, v2.x, v2.y, v3.x, v3.y, pm[2], pm[3]);
                mma8(oa, vm0, vm1, p4[0]);
                stsm2(sbw + SM_OT + (t16 & 511), pack2(oa[0] + ob[0], oa[1] + ob[1]), pack2(oa[2] + ob[2], oa[3] + ob[3]));
                PT(6);
                SF();
                bsync<6, 256>();
                mma16z(ox, v0.x, v0.y, v1.x, v1.y, px[0], px[1]);
                uint32_t b[4][4];
#define OTLD(pp) ldsm4t(b[pp], sbm + SM_OT + t16 + (pp) * 512)
                OTLD(0);
                MF();
                OTLD(1);
                barv<7, 384>();
                mma16(ox, v2.x, v2.y, v3.x, v3.y, px[2], px[3]);
                mma8(ox, vm0, vm1, p4[1]);
                SF();
                uint32_t ar, ae, ahi = xhi;
                float r[2][4];
#pragma unroll
                for (int ks = 0; ks < 8; ks++) {
                    if (ks == 0) WOLD(NPF, NPF + WPF);
                    if (ks == OPOS) { OTLD(2); MF(); }
                    if (ks == OPOS + 2) { OTLD(3); MF(); }
                    if (ks > 0) WOLD(NPF + WPF + 2 * (ks - 1), NPF + WPF + 2 * ks);
                    if (ks == 5) {
                        OPQ(t16);
                        ar = rb + (h & 1) * 16384 + t16; ae = rb + (h & 1) * 1024 + (t16 >> 2);
                        OPQ(ar); OPQ(ahi); OPQ(ae);
                        dn = lds128f(sb + SM_DN + (t16 & 48));
                    }
#pragma unroll
                    for (int mt = 0; mt < 2; mt++) {
                        const int i = ks * 2 + mt;
                        const uint32_t* a = i < NPE ? wo[i < NPE ? i : 0] : i < NPE + NB ? Wo[i < NPE + NB ? i - NPE : 0] : wo[i < NPE + NB ? 0 : i - NB];
                        if (i < 2) mma16z(r[mt], a[0], a[1], a[2], a[3], b[ks >> 1][2 * (ks & 1)], b[ks >> 1][2 * (ks & 1) + 1]);
                        else mma16(r[mt], a[0], a[1], a[2], a[3], b[ks >> 1][2 * (ks & 1)], b[ks >> 1][2 * (ks & 1) + 1]);
                    }
                    if (NPF + WPF + 2 * ks < 16 - NB || ks < 5) SF();
                }
                const float r0 = dn.x, r1 = dn.z;
                if (p == 1 && s + 1 == nseg) goto done;
                asm volatile("{\n.reg .b64 a;\nmov.b64 a, {%0,%2};\nred.relaxed.gpu.global.add.noftz.v4.bf16x2 [a], {%3,%4,%5,%6};\n"
                             "mov.b64 a, {%1,%2};\nred.relaxed.gpu.global.add.noftz.bf16x2 [a+32768], %7;\n}"
                             ::"r"(ar), "r"(ae), "r"(ahi), "r"(pack2(r[0][0] * r0, r[0][1] * r1)), "r"(pack2(r[0][2] * r0, r[0][3] * r1)),
                               "r"(pack2(r[1][0] * r0, r[1][1] * r1)), "r"(pack2(r[1][2] * r0, 1.f)), "r"(pack2(r[1][3] * r1, 1.f)) : "memory");
                if (XPOS == 2) barv<10, 384>();
            }
            SF();
            PT(10);
            OXSTORE(s);
            OPQALL();
        }
    done:
        OXSTORE(nseg - 1);
    }
}

#define G2_STAGES 6
#define G2_STAGE_BYTES 32768
DEVI void wg_ss128t(float (&d)[64], uint64_t da, uint64_t db, int sc) {
    asm volatile("{\n.reg .pred p;\nsetp.ne.b32 p, %66, 0;\n"
                 "wgmma.mma_async.sync.aligned.m64n128k16.f32.bf16.bf16 "
                 "{%0,%1,%2,%3,%4,%5,%6,%7,%8,%9,%10,%11,%12,%13,%14,%15,%16,%17,%18,%19,%20,%21,%22,%23,%24,%25,%26,%27,%28,%29,%30,%31,"
                 "%32,%33,%34,%35,%36,%37,%38,%39,%40,%41,%42,%43,%44,%45,%46,%47,%48,%49,%50,%51,%52,%53,%54,%55,%56,%57,%58,%59,%60,%61,%62,%63}, "
                 "%64, %65, p, 1, 1, 1, 1;\n}\n"
                 : "+f"(d[0]), "+f"(d[1]), "+f"(d[2]), "+f"(d[3]), "+f"(d[4]), "+f"(d[5]), "+f"(d[6]), "+f"(d[7]),
                   "+f"(d[8]), "+f"(d[9]), "+f"(d[10]), "+f"(d[11]), "+f"(d[12]), "+f"(d[13]), "+f"(d[14]), "+f"(d[15]),
                   "+f"(d[16]), "+f"(d[17]), "+f"(d[18]), "+f"(d[19]), "+f"(d[20]), "+f"(d[21]), "+f"(d[22]), "+f"(d[23]),
                   "+f"(d[24]), "+f"(d[25]), "+f"(d[26]), "+f"(d[27]), "+f"(d[28]), "+f"(d[29]), "+f"(d[30]), "+f"(d[31]),
                   "+f"(d[32]), "+f"(d[33]), "+f"(d[34]), "+f"(d[35]), "+f"(d[36]), "+f"(d[37]), "+f"(d[38]), "+f"(d[39]),
                   "+f"(d[40]), "+f"(d[41]), "+f"(d[42]), "+f"(d[43]), "+f"(d[44]), "+f"(d[45]), "+f"(d[46]), "+f"(d[47]),
                   "+f"(d[48]), "+f"(d[49]), "+f"(d[50]), "+f"(d[51]), "+f"(d[52]), "+f"(d[53]), "+f"(d[54]), "+f"(d[55]),
                   "+f"(d[56]), "+f"(d[57]), "+f"(d[58]), "+f"(d[59]), "+f"(d[60]), "+f"(d[61]), "+f"(d[62]), "+f"(d[63])
                 : "l"(da), "l"(db), "r"(sc));
}

DEVI void gemm2(int tile, uint32_t xlo, uint32_t xhi, const CUtensorMap& tmb, bf16* __restrict__ out) {
    const uint32_t sb = SB0;
    const uint32_t bars = sb + G2_STAGES * G2_STAGE_BYTES;
    const int tid = threadIdx.x, lane = tid & 31;
    const int w = __shfl_sync(0xFFFFFFFFu, tid >> 5, 0);
    const int bm = tile >> 3, bn = tile & 7;
    if (tid == 0) {
        for (int i = 0; i < G2_STAGES; i++) { mbar_init(bars + i * 8, 1); mbar_init(bars + (G2_STAGES + i) * 8, 2); }
        asm volatile("fence.mbarrier_init.release.cluster;" ::: "memory");
        asm volatile("fence.proxy.async.shared::cta;" ::: "memory");
    }
    __syncthreads();
    const int NK = HD / 64;
    if (w == 8) {
        if (lane == 0) {
            for (int kb = 0; kb < G2_STAGES; kb++) {
                const uint32_t dst = sb + kb * G2_STAGE_BYTES;
                mbar_expect(bars + kb * 8, G2_STAGE_BYTES);
                tma2d(dst + 16384, &tmb, bars + kb * 8, bn * 128, kb * 64);
                tma2d(dst + 24576, &tmb, bars + kb * 8, bn * 128 + 64, kb * 64);
            }
            asm volatile("griddepcontrol.wait;" ::: "memory");
            for (int kb = 0; kb < G2_STAGES; kb++)
                bulk_g2s(sb + kb * G2_STAGE_BYTES, xlo + XO_OX + (bm * 64 + kb) * 16384, xhi, 16384, bars + kb * 8);
            int st = 0, ph = 0;
            for (int kb = G2_STAGES; kb < NK; kb++) {
                mbar_wait(bars + (G2_STAGES + st) * 8, ph);
                const uint32_t dst = sb + st * G2_STAGE_BYTES;
                mbar_expect(bars + st * 8, G2_STAGE_BYTES);
                bulk_g2s(dst, xlo + XO_OX + (bm * 64 + kb) * 16384, xhi, 16384, bars + st * 8);
                tma2d(dst + 16384, &tmb, bars + st * 8, bn * 128, kb * 64);
                tma2d(dst + 24576, &tmb, bars + st * 8, bn * 128 + 64, kb * 64);
                if (++st == G2_STAGES) { st = 0; ph ^= 1; }
            }
        }
    } else if (w < 8) {
        const int wg = w >> 2;
        float acc[64];
        int st = 0, ph = 0;
        for (int kb = 0; kb < NK; kb++) {
            mbar_wait(bars + st * 8, ph);
            const uint32_t base = sb + st * G2_STAGE_BYTES;
            const uint64_t da = mkdesc(base + wg * 8192, 128, 1024) & ~((uint64_t)3 << 62);
            const uint64_t db = mkdesc(base + 16384, 8192, 1024);
            wg_fence();
#pragma unroll
            for (int k = 0; k < 4; k++) wg_ss128t(acc, da + k * 16, db + k * 128, (kb | k) != 0);
            wg_commit();
            if (kb > 0) {
                wg_wait<1>();
                const int pst = st == 0 ? G2_STAGES - 1 : st - 1;
                if ((tid & 127) == 0) mbar_arrive(bars + (G2_STAGES + pst) * 8);
            }
            if (++st == G2_STAGES) { st = 0; ph ^= 1; }
        }
        wg_wait<0>();
        const int row = bm * 128 + wg * 64 + (w & 3) * 16 + (lane >> 2);
        bf16* o = out + (size_t)row * 2048 + bn * 128 + (lane & 3) * 2;
#pragma unroll
        for (int i = 0; i < 16; i++) {
            *(uint32_t*)(o + i * 8) = pack2(acc[4 * i], acc[4 * i + 1]);
            *(uint32_t*)(o + 8 * 2048 + i * 8) = pack2(acc[4 * i + 2], acc[4 * i + 3]);
        }
    }
}

#define D4(c, i) #c "f"(d[i]), #c "f"(d[i + 1]), #c "f"(d[i + 2]), #c "f"(d[i + 3])
template <int SC> DEVI void wg_rs128t(float (&d)[64], const uint32_t (&a)[4], uint64_t db) {
    if (SC) asm volatile("wgmma.mma_async.sync.aligned.m64n128k16.f32.bf16.bf16 "
        "{%0,%1,%2,%3,%4,%5,%6,%7,%8,%9,%10,%11,%12,%13,%14,%15,%16,%17,%18,%19,%20,%21,%22,%23,%24,%25,%26,%27,%28,%29,%30,%31,%32,%33,%34,%35,%36,%37,%38,%39,%40,%41,%42,%43,%44,%45,%46,%47,%48,%49,%50,%51,%52,%53,%54,%55,%56,%57,%58,%59,%60,%61,%62,%63}, "
        "{%64,%65,%66,%67}, %68, 1, 1, 1, 1;"
        : D4(+, 0), D4(+, 4), D4(+, 8), D4(+, 12), D4(+, 16), D4(+, 20), D4(+, 24), D4(+, 28), D4(+, 32), D4(+, 36), D4(+, 40), D4(+, 44), D4(+, 48), D4(+, 52), D4(+, 56), D4(+, 60) : "r"(a[0]), "r"(a[1]), "r"(a[2]), "r"(a[3]), "l"(db));
    else asm volatile("wgmma.mma_async.sync.aligned.m64n128k16.f32.bf16.bf16 "
        "{%0,%1,%2,%3,%4,%5,%6,%7,%8,%9,%10,%11,%12,%13,%14,%15,%16,%17,%18,%19,%20,%21,%22,%23,%24,%25,%26,%27,%28,%29,%30,%31,%32,%33,%34,%35,%36,%37,%38,%39,%40,%41,%42,%43,%44,%45,%46,%47,%48,%49,%50,%51,%52,%53,%54,%55,%56,%57,%58,%59,%60,%61,%62,%63}, "
        "{%64,%65,%66,%67}, %68, 0, 1, 1, 1;"
        : D4(=, 0), D4(=, 4), D4(=, 8), D4(=, 12), D4(=, 16), D4(=, 20), D4(=, 24), D4(=, 28), D4(=, 32), D4(=, 36), D4(=, 40), D4(=, 44), D4(=, 48), D4(=, 52), D4(=, 56), D4(=, 60) : "r"(a[0]), "r"(a[1]), "r"(a[2]), "r"(a[3]), "l"(db));
}
template <int SC> DEVI void wg_rs64t(float (&d)[32], const uint32_t (&a)[4], uint64_t db) {
    if (SC) asm volatile("wgmma.mma_async.sync.aligned.m64n64k16.f32.bf16.bf16 "
        "{%0,%1,%2,%3,%4,%5,%6,%7,%8,%9,%10,%11,%12,%13,%14,%15,%16,%17,%18,%19,%20,%21,%22,%23,%24,%25,%26,%27,%28,%29,%30,%31}, "
        "{%32,%33,%34,%35}, %36, 1, 1, 1, 1;"
        : D4(+, 0), D4(+, 4), D4(+, 8), D4(+, 12), D4(+, 16), D4(+, 20), D4(+, 24), D4(+, 28) : "r"(a[0]), "r"(a[1]), "r"(a[2]), "r"(a[3]), "l"(db));
    else asm volatile("wgmma.mma_async.sync.aligned.m64n64k16.f32.bf16.bf16 "
        "{%0,%1,%2,%3,%4,%5,%6,%7,%8,%9,%10,%11,%12,%13,%14,%15,%16,%17,%18,%19,%20,%21,%22,%23,%24,%25,%26,%27,%28,%29,%30,%31}, "
        "{%32,%33,%34,%35}, %36, 0, 1, 1, 1;"
        : D4(=, 0), D4(=, 4), D4(=, 8), D4(=, 12), D4(=, 16), D4(=, 20), D4(=, 24), D4(=, 28) : "r"(a[0]), "r"(a[1]), "r"(a[2]), "r"(a[3]), "l"(db));
}
template <int SC> DEVI void wg_rs40(float (&d)[20], const uint32_t (&a)[4], uint64_t db) {
    if (SC) asm volatile("wgmma.mma_async.sync.aligned.m64n40k16.f32.bf16.bf16 "
        "{%0,%1,%2,%3,%4,%5,%6,%7,%8,%9,%10,%11,%12,%13,%14,%15,%16,%17,%18,%19}, "
        "{%20,%21,%22,%23}, %24, 1, 1, 1, 0;"
        : D4(+, 0), D4(+, 4), D4(+, 8), D4(+, 12), D4(+, 16) : "r"(a[0]), "r"(a[1]), "r"(a[2]), "r"(a[3]), "l"(db));
    else asm volatile("wgmma.mma_async.sync.aligned.m64n40k16.f32.bf16.bf16 "
        "{%0,%1,%2,%3,%4,%5,%6,%7,%8,%9,%10,%11,%12,%13,%14,%15,%16,%17,%18,%19}, "
        "{%20,%21,%22,%23}, %24, 0, 1, 1, 0;"
        : D4(=, 0), D4(=, 4), D4(=, 8), D4(=, 12), D4(=, 16) : "r"(a[0]), "r"(a[1]), "r"(a[2]), "r"(a[3]), "l"(db));
}
template <int SC> DEVI void wg_rs8(float (&d)[4], const uint32_t (&a)[4], uint64_t db) {
    if (SC) asm volatile("wgmma.mma_async.sync.aligned.m64n8k16.f32.bf16.bf16 "
        "{%0,%1,%2,%3}, "
        "{%4,%5,%6,%7}, %8, 1, 1, 1, 0;"
        : D4(+, 0) : "r"(a[0]), "r"(a[1]), "r"(a[2]), "r"(a[3]), "l"(db));
    else asm volatile("wgmma.mma_async.sync.aligned.m64n8k16.f32.bf16.bf16 "
        "{%0,%1,%2,%3}, "
        "{%4,%5,%6,%7}, %8, 0, 1, 1, 0;"
        : D4(=, 0) : "r"(a[0]), "r"(a[1]), "r"(a[2]), "r"(a[3]), "l"(db));
}
template <int SC> DEVI void wg_ss64a(float (&d)[32], uint64_t da, uint64_t db) {
    if (SC) asm volatile("wgmma.mma_async.sync.aligned.m64n64k16.f32.bf16.bf16 "
        "{%0,%1,%2,%3,%4,%5,%6,%7,%8,%9,%10,%11,%12,%13,%14,%15,%16,%17,%18,%19,%20,%21,%22,%23,%24,%25,%26,%27,%28,%29,%30,%31}, "
        "%32, %33, 1, 1, 1, 1, 0;"
        : D4(+, 0), D4(+, 4), D4(+, 8), D4(+, 12), D4(+, 16), D4(+, 20), D4(+, 24), D4(+, 28) : "l"(da), "l"(db));
    else asm volatile("wgmma.mma_async.sync.aligned.m64n64k16.f32.bf16.bf16 "
        "{%0,%1,%2,%3,%4,%5,%6,%7,%8,%9,%10,%11,%12,%13,%14,%15,%16,%17,%18,%19,%20,%21,%22,%23,%24,%25,%26,%27,%28,%29,%30,%31}, "
        "%32, %33, 0, 1, 1, 1, 0;"
        : D4(=, 0), D4(=, 4), D4(=, 8), D4(=, 12), D4(=, 16), D4(=, 20), D4(=, 24), D4(=, 28) : "l"(da), "l"(db));
}

#define G_ROWS 514
__device__ uint4 g_G[64 * G_ROWS * 8];
__device__ uint4 g_GN[64 * 8];
__device__ uint4 g_WN[1152];
#define FS_F2 196608
#define FS_TB (FS_F2 + 8192)
#define FS_NQ (FS_TB + 16384)
#define FS_BAR (FS_NQ + 128)
#define FS_NY (FS_NQ + 1024 + 128)
#define FS_TOTAL (FS_NQ + 3072)
#define F_THREADS 512

DEVI uint32_t cis(int j) {
    const float a = fmaf(__uint_as_float((((j + 1024) << 12) & 0x7FF000) | 0x3F800000), 6.283185307179586f, -9.42477796076938f);
    return pack2(__cosf(a), __sinf(a));
}
DEVI uint32_t cos2(int j0, int j1) {
    const float f = 6.283185307179586f / 2048.f;
    return pack2(__cosf((float)(((j0 + 1024) & 2047) - 1024) * f), __cosf((float)(((j1 + 1024) & 2047) - 1024) * f));
}
DEVI void twid(int j, float& c, float& s) {
    const float a = (float)(((j + 512) & 1023) - 512) * (6.283185307179586f / 1024.f);
    c = __cosf(a) * (1.f / 1024.f);
    s = __sinf(a) * (1.f / 1024.f);
}
DEVI void mwait(uint32_t bar, uint32_t parity) {
    asm volatile("{\n.reg .pred p;\n.reg .b32 c;\nmbarrier.try_wait.parity.shared::cta.b64 p, [%0], %1;\n@p bra.uni D;\nmov.b32 c, 0;\n"
                 "L:\nadd.u32 c, c, 1;\nsetp.gt.u32 p, c, 4194304;\n@p st.shared.u32 [c], c;\n"
                 "mbarrier.try_wait.parity.shared::cta.b64 p, [%0], %1;\n@!p bra.uni L;\nD:\n}" ::"r"(bar), "r"(parity) : "memory");
}
template <bool B> struct Bool { static constexpr bool v = B; };
DEVI uint32_t opq(uint32_t& x, uint32_t zero) { OPQ(x); return x; }
DEVI uint32_t tidx() { uint32_t r; asm volatile("mov.u32 %0, %%tid.x;" : "=r"(r)); return r; }
DEVI void tma4d(uint32_t dst, const CUtensorMap* tm, uint32_t bar, int c0, int c1, int c2, int c3) {
    asm volatile("cp.async.bulk.tensor.4d.shared::cluster.global.mbarrier::complete_tx::bytes [%0], [%1, {%3, %4, %5, %6}], [%2];"
                 ::"r"(dst), "l"(tm), "r"(bar), "r"(c0), "r"(c1), "r"(c2), "r"(c3) : "memory");
}
DEVI void tma3s(const CUtensorMap* tm, uint32_t src, int c0, int c1, int c2) {
    asm volatile("cp.async.bulk.tensor.3d.global.shared::cta.bulk_group [%0, {%2, %3, %4}], [%1];" ::"l"(tm), "r"(src), "r"(c0), "r"(c1), "r"(c2) : "memory");
}
DEVI void tma4s(const CUtensorMap* tm, uint32_t src, int c0, int c1, int c2, int c3) {
    asm volatile("cp.async.bulk.tensor.4d.global.shared::cta.bulk_group [%0, {%2, %3, %4, %5}], [%1];"
                 ::"l"(tm), "r"(src), "r"(c0), "r"(c1), "r"(c2), "r"(c3) : "memory");
}
DEVI void bulk_commit() { asm volatile("cp.async.bulk.commit_group;" ::: "memory"); }
DEVI void fence_async() { asm volatile("fence.proxy.async;" ::: "memory"); }
DEVI void fence_smem() { asm volatile("fence.proxy.async.shared::cta;" ::: "memory"); }
DEVI void wgbar(uint32_t q) { asm volatile("bar.sync %0, 128;" ::"r"(q + 2) : "memory"); }
DEVI void grid_arrive(uint32_t* c) { asm volatile("fence.proxy.async;\nred.release.gpu.global.add.u32 [%0], 1;" ::"l"(c) : "memory"); }
DEVI void grid_wait(uint32_t* c, uint32_t n) {
    uint32_t v;
    int it = 0;
    do {
        asm volatile("ld.acquire.gpu.global.u32 %0, [%1];" : "=r"(v) : "l"(c) : "memory");
        if (++it > (1 << 22)) die(it);
    } while (v != n);
    fence_async();
}

template <bool INV, class S1, class S2>
DEVI void fft_rows(uint32_t grp, uint32_t q, const uint32_t (&F)[2][4], const float (&tc)[8], const float (&ts)[8], uint32_t so, float fx, uint32_t nq,
                   S1 sh1, S2 sh2) {
    float d[64];
    const uint64_t db = INV ? mkdesc(grp, 1024, 2048) : (mkdesc(grp, 2048, 512) ^ ((uint64_t)3 << 62));
    wg_fence();
    wg_rs128t<0>(d, F[0], db);
    wg_rs128t<1>(d, F[1], db + (INV ? 256 : 64));
    wg_commit();
    SF();
    sh1();
    float4 ny;
    if (INV) ny = lds128f(nq);
    wg_wait<0>();
    if (INV) { d[0] = fmaf(fx, ny.x, d[0]); d[16] = fmaf(fx, ny.y, d[16]); d[32] = fmaf(fx, ny.z, d[32]); d[48] = fmaf(fx, ny.w, d[48]); }
    uint32_t a[2][4][4];
    float e[2][INV ? 16 : 20];
    const uint64_t df = mkdesc(SB0 + FS_F2, 16, 1024);
#pragma unroll
    for (int s = 0; s < 2; s++) {
#pragma unroll
        for (int i = 0; i < 4; i++)
#pragma unroll
            for (int h = 0; h < 2; h++) {
                const float* x = d + (2 * s + h) * 16 + i * 4;
                a[s][i][h] = pack2(fmaf(x[2], ts[2 * i], x[0] * tc[2 * i]), fmaf(x[3], ts[2 * i + 1], x[1] * tc[2 * i + 1]));
                a[s][i][h + 2] = pack2(fmaf(-x[0], ts[2 * i], x[2] * tc[2 * i]), fmaf(-x[1], ts[2 * i + 1], x[3] * tc[2 * i + 1]));
            }
        wg_fence();
#pragma unroll
        for (int i = 0; i < 4; i++) {
            if constexpr (INV) { if (i == 0) wg_rs32<0>(e[s], a[s][i], df); else wg_rs32<1>(e[s], a[s][i], df + i * 2); }
            else { if (i == 0) wg_rs40<0>(e[s], a[s][i], df); else wg_rs40<1>(e[s], a[s][i], df + i * 2); }
        }
        wg_commit();
    }
    SF();
    sh2();
#pragma unroll
    for (int s = 0; s < 2; s++) {
        if (s == 0) wg_wait<1>(); else wg_wait<0>();
        float* x = e[s];
        if constexpr (!INV) {
            x[0] *= fx; x[1] *= fx; x[2] *= fx; x[3] *= fx;
            if (fx != 1.f) sts64(nq + s * 8, pack2(x[16], 0.f), pack2(x[18], 0.f));
        }
        const uint32_t o = grp + (INV ? so + s * 4096 : so ^ (s * 576));
#pragma unroll
        for (int b = 0; b < 2; b++)
            stsm4t(o + b * (INV ? 1024 : 4096), pack2(x[8 * b], x[8 * b + 1]), pack2(x[8 * b + 2], x[8 * b + 3]), pack2(x[8 * b + 4], x[8 * b + 5]),
                   pack2(x[8 * b + 6], x[8 * b + 7]));
    }
}

template <bool INV>
DEVI void fft_gen(uint32_t a, uint32_t n2) {
    const uint32_t tid = tidx(), x = ((tid >> 4) & 24) + (tid & 3), o = (tid & 4) * 128;
    if (INV) {
        const uint32_t r = (tid & 64) * 16 + (tid & 16) * 32 + (tid & 40) * 8 + n2;
        sts128(a + tid * 16, cis(o - r * x), cis(o - (r + 128) * x), cis(o - r * (x + 4)), cis(o - (r + 128) * (x + 4)));
    } else {
        const uint32_t r = 64 * x + n2, k = ((tid >> 2) & 24) + ((tid >> 3) & 3);
        sts128(a + tid * 16, cis(r * k + o), cis(r * (k + 4) + o), cis((r + 256) * k + o), cis((r + 256) * (k + 4) + o));
    }
}
template <bool INV, class S1>
DEVI void fft_cross(uint32_t buf, uint32_t q, uint32_t fa, uint32_t so, uint32_t nq, float (&n)[4], S1 sh1) {
    uint32_t F[4][4];
#pragma unroll
    for (int s = 0; s < 4; s++) { const uint4 v = lds128(fa + s * 2048); F[s][0] = v.x; F[s][1] = v.y; F[s][2] = v.z; F[s][3] = v.w; }
    float d[64];
    const uint64_t db = mkdesc(buf + q * 2048, 1024, 8192), dn = mkdesc(nq, 16, 1024);
    wg_fence();
#pragma unroll
    for (int s = 0; s < 4; s++) { if (s == 0) wg_rs128t<0>(d, F[s], db); else wg_rs128t<1>(d, F[s], db + s * 1024); }
#pragma unroll
    for (int s = 0; s < 4; s++) { if (s == 0) wg_rs8<0>(n, F[s], dn); else wg_rs8<1>(n, F[s], dn + s * 2); }
    wg_commit();
    SF();
    sh1();
    wg_wait<0>();
#pragma unroll
    for (int b = 0; b < 8; b++) {
        const uint32_t o = INV ? so ^ ((b >> 1) * 288 ^ (b & 1) * 32) : (so ^ ((b & 3) * 32)) + (b >> 2) * 1024;
        stsm4(buf + o, pack2(d[8 * b], d[8 * b + 1]), pack2(d[8 * b + 2], d[8 * b + 3]), pack2(d[8 * b + 4], d[8 * b + 5]), pack2(d[8 * b + 6], d[8 * b + 7]));
    }
}

template <bool ODD>
DEVI void fft_filter(uint32_t aw, const float (&e)[32], const float (&o)[32], uint32_t (&u)[4][4], uint32_t (&v)[4][4]) {
#pragma unroll
    for (int s = 0; s < 4; s++) {
        float y[2][2][4];
#pragma unroll
        for (int c = 0; c < 2; c++) {
            float f[4][2];
#pragma unroll
            for (int i = 0; i < 4; i++) {
                const uint32_t a = aw + (i * 32 + s * 8 + c) * 144, x = lds32(a);
                f[i][0] = ODD ? hi_f(x) : lo_f(x);
                f[i][1] = ODD ? lo_f(lds32(a + 4)) : hi_f(x);
            }
#pragma unroll
            for (int h = 0; h < 2; h++) {
                const int x = 8 * s + 2 * h + c;
                const float ar = e[x] + o[x], ai = e[x + 4] + o[x + 4], br = e[x] - o[x], bi = e[x + 4] - o[x + 4];
                const float yr = fmaf(-ai, f[2][h], ar * f[0][h]), yi = fmaf(ar, f[2][h], ai * f[0][h]);
                y[h][c][0] = fmaf(-bi, f[3][h], fmaf(br, f[1][h], yr));
                y[h][c][1] = fmaf(br, f[3][h], fmaf(bi, f[1][h], yi));
                y[h][c][2] = fmaf(2.f, yr, -y[h][c][0]);
                y[h][c][3] = fmaf(2.f, yi, -y[h][c][1]);
            }
        }
#pragma unroll
        for (int h = 0; h < 2; h++) {
            u[s][h] = pack2(y[h][0][0], y[h][1][0]); u[s][h + 2] = pack2(y[h][0][1], y[h][1][1]);
            v[s][h] = pack2(y[h][0][2], y[h][1][2]); v[s][h + 2] = pack2(y[h][0][3], y[h][1][3]);
        }
    }
}

__global__ void __launch_bounds__(F_THREADS, 1)
post_kernel(const __grid_constant__ CUtensorMap tmx, const __grid_constant__ CUtensorMap tmg1, const __grid_constant__ CUtensorMap tmg2,
           const __grid_constant__ CUtensorMap tmwr, const __grid_constant__ CUtensorMap tmwi, const __grid_constant__ CUtensorMap tmy,
           const bf16* __restrict__ wr, const bf16* __restrict__ wi, uint32_t* cnt, uint32_t zero, int nw,
           const __grid_constant__ CUtensorMap tmb, uint32_t xlo, uint32_t xhi, bf16* __restrict__ out) {
    extern __shared__ __align__(1024) uint8_t smem[];
    const uint32_t sb = SB0;
    if (smem_u32(smem) != sb) die(1 << 23);
    if (blockIdx.x >= nw) {
        gemm2(blockIdx.x - nw, xlo, xhi, tmb, out);
        return;
    }
    const uint32_t tid = threadIdx.x, lane = tid & 31, g = lane >> 2, t = lane & 3, j8 = lane & 7, mat = lane >> 3;
    const uint32_t wi_ = __reduce_max_sync(0xFFFFFFFFu, tid >> 5), q = wi_ >> 2, w = wi_ & 3;
    const int cta = blockIdx.x;
    const int nt = cta < 64 ? (64 - cta + nw - 1) / nw : 0;
    const uint32_t bar = sb + FS_BAR;
    if (tid == 0) {
        for (int i = 0; i < 30; i++) mbar_init(bar + i * 8, i < 3 ? 4 : i < 6 ? 16 : i >= 14 && i < 18 ? 2 : 1);
        asm volatile("fence.mbarrier_init.release.cluster;" ::: "memory");
        fence_smem();
    }
    __syncthreads();
#define FT(n)
    FT(0);
#define N2(p) (2 * ((p) & 31) + ((p) >> 5))
#define WLOAD(tk, part) { \
        const uint32_t wd_ = sb + 131072 + q * 18432 + (part) * 9216, wb_ = bar + 112 + q * 8; \
        mbar_expect(wb_, 9216); \
        if ((tk) < 256) tma3d(wd_, (part) ? &tmwi : &tmwr, wb_, ((tk) & 63) * 64, (tk) >> 6, 0); \
        else asm volatile("cp.async.bulk.shared::cluster.global.mbarrier::complete_tx::bytes [%0], [%1], 9216, [%2];" \
                          ::"r"(wd_), "l"(g_WN + (part) * 576), "r"(wb_) : "memory"); }
#define GROW(tk) ((tk) < 256 ? ((tk) >> 5) * 64 + ((tk) & 7) * 8 + (((tk) >> 3) & 3) * 2 : 512)
#define DLOAD(tk, sl) { mbar_expect(bar + 48 + (sl) * 8, 16384); tma3d(sb + (sl) * 16384, &tmg2, bar + 48 + (sl) * 8, 0, GROW(tk), 0); }
#define IO(c) if (w == 3 && (c) && elect())
#define XLOAD1(i, bb) { const uint32_t xb_ = bar + 144 + (bb) * 32 + q * 8; mbar_expect(xb_, 16384); tma4d(sb + (bb) * 65536 + q * 16384, &tmx, xb_, 0, 0, q * 8, N2(cta + (i) * nw)); }
#define GLOAD3(i, bb) { mbar_expect(bar + (bb) * 8, q ? 16384 : 16512); tma3d(sb + (bb) * 65536 + q * 16384, &tmg1, bar + (bb) * 8, 0, q * 128, cta + (i) * nw); \
        if (q == 0) asm volatile("cp.async.bulk.shared::cluster.global.mbarrier::complete_tx::bytes [%0], [%1], 128, [%2];" \
                                 ::"r"(sb + FS_NQ + (bb) * 1024), "l"(g_GN + (cta + (i) * nw) * 8), "r"(bar + (bb) * 8) : "memory"); }
    for (int i = 0; i < 3; i++) IO(i < nt) XLOAD1(i, i);
    for (uint32_t x = tid; x < 40 * 32; x += 512) {
        const uint32_t n = x >> 5, m2 = mat * 8 + t * 2, ri = g & 1;
        const uint32_t c2 = ((n >> 1) & 1) + ((n >> 3) & 1) * 2 + (n & 4) + (n >> 4) * 8;
        const uint32_t v = cos2(m2 * c2 * 64 + ((n & 1) - ri) * 512, (m2 + 1) * c2 * 64 + ((n & 1) - ri) * 512);
        sts32(sb + FS_F2 + n * 128 + ((g ^ (n & 7)) << 4) + t * 4, n < 32 ? v : n == 32 && ri == 0 ? 0xBF003F00u : 0u);
    }
    float tc[8], ts[8];
    uint32_t F[2][4];
    uint32_t c1 = 16 * (w >> 1) + 2 * g + (w & 1);
#pragma unroll
    for (int i = 0; i < 8; i++) {
        twid(c1 * (8 * (i >> 1) + 2 * t + (i & 1)), tc[i], ts[i]);
        const uint32_t m1 = (i >> 1) * 8 + 2 * t;
        F[i >> 2][i & 3] = cos2(c1 * m1 * 64 + (i & 1) * 512, c1 * (m1 + 1) * 64 + (i & 1) * 512);
    }
    {
        const uint32_t kr = (2 * (mat & 1) + (j8 & 1)) ^ ((j8 >> 2) << 1);
        const uint32_t so1 = ((mat >> 1) + 2 * (j8 >> 2)) * 1024 + kr * 128 + (((((j8 >> 1) & 1) * 4 + w) ^ kr) << 4);
        const uint32_t so2 = (2 * w + (mat & 1)) * 8192 + q * 2048 + j8 * 128 + (((mat >> 1) ^ j8) << 4);
        uint32_t so = so1 << 16 | so2;
        const float fx = (tid & 127) == 0 ? 0.5f : 1.f;
        fft_gen<false>(sb + FS_TB, N2(cta));
        fence_smem();
        bsync<1, 512>();
        FT(1);
        int b = 0, bp = 2, ph = 0;
        if (nt) mwait(bar + 144 + q * 8, 0);
        __syncwarp();
        auto step = [&](auto first, auto last, const int i) {
            const uint32_t p = cta + i * nw, bn = 3 - b - bp, tb = (i & 1) * 8192;
            const uint32_t grp = sb + b * 65536 + q * 16384, nq = sb + FS_NQ + b * 1024 + q * 32;
            auto sa = [&]() {
                if constexpr (!decltype(first)::v) {
                    fence_smem();
                    __syncwarp();
                    if (elect()) mbar_arrive(bar + 24);
                }
                IO(i > 1) {
                    mwait(bar + 32, i & 1);
                    tma3s(&tmg1, sb + bn * 65536 + q * 16384, 0, q * 128, p - 2 * nw);
                    bulk_commit();
                }
            };
            auto sb_ = [&]() { if constexpr (!decltype(first)::v) mwait(bar + 24, (i - 1) & 1); };
            if constexpr (!decltype(last)::v) fft_rows<false>(grp, q, F, tc, ts, opq(so, zero) >> 16, fx, nq, sa, sb_);
            else { sa(); __syncwarp(); sb_(); __syncwarp(); }
            if constexpr (!decltype(first)::v) {
                float n[4];
                fft_cross<false>(sb + bp * 65536, q, sb + FS_TB + 8192 - tb + (((tidx() & 127) ^ (q & 1)) << 4), opq(so, zero) & 0xFFFF, sb + FS_NQ + bp * 1024, n, [&]() {
                    fft_gen<false>(sb + FS_TB + tb, N2(p));
                    IO(i >= 2 && i + 1 < nt) {
                        asm volatile("cp.async.bulk.wait_group.read 0;" ::: "memory");
                        XLOAD1(i + 1, bn);
                    }
                });
                if (q == 0) {
                    const uint32_t x = tidx();
                    bf16* z = (bf16*)(g_G + ((p - nw) * G_ROWS + 512) * 8) + (x & 4) * 16 + ((x >> 2) & 24) + ((x >> 3) & 3);
                    asm volatile("{\n.reg .pred p;\n.reg .b16 a, b;\nsetp.eq.u32 p, %2, 0;\nmov.b32 {a, b}, %1;\n@p st.global.u16 [%0], a;\n@p st.global.u16 [%0+8], b;\n}"
                                 ::"l"(z), "r"(pack2(n[0], n[2])), "r"(x & 3) : "memory");
                }
            }
            if constexpr (!decltype(last)::v) {
                fft_rows<false>(grp + 8192, q, F, tc, ts, opq(so, zero) >> 16, fx, nq + 16, [&]() {
                    if constexpr (!decltype(first)::v) {
                        fence_smem();
                        __syncwarp();
                        if (elect()) mbar_arrive(bar + 32);
                    }
                    if ((w == 1 || w == 2) && elect())
                        asm volatile("cp.async.bulk.prefetch.L2.global [%0], 8208;" ::"l"((w == 1 ? wr : wi) + (p * 4 + q) * 4104) : "memory");
                }, [&]() { if (i + 1 < nt) mwait(bar + 144 + bn * 32 + q * 8, bn ? ph : ph ^ 1); });
                bp = b;
                if (++b == 3) { b = 0; ph ^= 1; }
            }
        };
        if (nt) {
            step(Bool<true>(), Bool<false>(), 0);
#pragma unroll 1
            for (int i = 1; i < nt; i++) step(Bool<false>(), Bool<false>(), i);
            step(Bool<false>(), Bool<true>(), nt);
        }
        for (uint32_t x = cta * 512 + tid; x < 4096; x += nw * 512)
            ((bf16*)g_WN)[(x >> 5) * 72 + (x & 16) + (x & 7) * 2 + ((x >> 3) & 1)] = (x < 2048 ? wr : wi)[(x & 2047) * 513 + 512];
        FT(2);
        fence_async();
        bsync<1, 512>();
        IO(nt) { tma3s(&tmg1, sb + bp * 65536 + q * 16384, 0, q * 128, cta + (nt - 1) * nw); bulk_commit(); }
    }
    for (uint32_t x = tid; x < 128 * 32; x += 512) {
        const uint32_t n = (x >> 5) & 63, a = x & 31, k2 = (n >> 4) * 8 + (n & 7);
        sts32(sb + FS_TB + (x >> 5) * 128 + (((a >> 2) ^ (n & 7)) << 4) + (a & 3) * 4, cis((2 * a + (x >> 11)) * k2 * 32 + (n & 8) * 64));
    }
    fence_smem();
    bsync<1, 512>();
    IO(true) {
        asm volatile("cp.async.bulk.wait_group 0;" ::: "memory");
        grid_arrive(cnt);
        grid_wait(cnt, 4 * nw);
        const int tk = cta + q * nw;
        if (tk <= 256) { DLOAD(tk, q); WLOAD(tk, 0); WLOAD(tk, 1); }
    }
    __syncwarp();
    {
        const uint32_t lo = j8 * 128 + (((2 * w + (mat & 1)) ^ j8) << 4);
        const uint32_t aw = sb + 131072 + q * 18432 + t * 288 + w * 32 + g * 4;
        const uint64_t df = mkdesc(sb + FS_TB, 16, 1024);
        const uint64_t da = mkdesc(sb + q * 16384, 16, 1024);
        const uint32_t buf = sb + 65536 + q * 16384;
        int i = 0, tk = cta + q * nw;
        if (tk <= 256) mwait(bar + 48 + q * 8, 0);
        FT(3);
#pragma unroll 1
        for (; tk <= 256; tk += 4 * nw, i++) {
            const bool more = tk + 4 * nw <= 256;
            float e[32], o[32];
            wg_fence();
#pragma unroll
            for (int s = 0; s < 4; s++) { if (s == 0) wg_ss64a<0>(e, da, df); else wg_ss64a<1>(e, da + s * 128, df + s * 2); }
#pragma unroll
            for (int s = 0; s < 4; s++) { if (s == 0) wg_ss64a<0>(o, da + 512, df + 512); else wg_ss64a<1>(o, da + 512 + s * 128, df + 512 + s * 2); }
            wg_commit();
            SF();
            if (i > 0) {
                fence_smem();
                wgbar(q);
                IO(true) { tma3s(&tmg2, buf, 0, GROW(tk - 4 * nw), 0); bulk_commit(); }
            }
            if (w == 2 && more && elect()) mbar_expect(bar + 48 + q * 8, 16384);
            const int gr = GROW(tk + 4 * nw);
            mwait(bar + 112 + q * 8, i & 1);
            wg_wait<0>();
            if (w == 2 && more && elect()) tma3d(sb + q * 16384, &tmg2, bar + 48 + q * 8, 0, gr, 0);
            uint32_t u[4][4], v[4][4];
            if (tk & 8) fft_filter<true>(aw + (tk & 48) / 4, e, o, u, v);
            else fft_filter<false>(aw + (tk & 48) / 4, e, o, u, v);
            wg_fence();
#pragma unroll
            for (int s = 0; s < 4; s++) { if (s == 0) wg_rs64t<0>(e, u[s], df); else wg_rs64t<1>(e, u[s], df + s * 128); }
#pragma unroll
            for (int s = 0; s < 4; s++) { if (s == 0) wg_rs64t<0>(o, v[s], df + 512); else wg_rs64t<1>(o, v[s], df + 512 + s * 128); }
            wg_commit();
            SF();
            IO(true) asm volatile("cp.async.bulk.wait_group.read 0;" ::: "memory");
            wgbar(q);
            if (more) {
                if ((w == 1 || w == 2) && elect()) WLOAD(tk + 4 * nw, w - 1);
                mwait(bar + 48 + q * 8, (i + 1) & 1);
            }
            wg_wait<0>();
#pragma unroll
            for (int s = 0; s < 4; s++) {
                const uint32_t a = buf + (mat >> 1) * 1024 + lo + s * 2048;
                stsm4t(a, pack2(e[8 * s], e[8 * s + 1]), pack2(e[8 * s + 2], e[8 * s + 3]), pack2(e[8 * s + 4], e[8 * s + 5]), pack2(e[8 * s + 6], e[8 * s + 7]));
                stsm4t(a + 8192, pack2(o[8 * s], o[8 * s + 1]), pack2(o[8 * s + 2], o[8 * s + 3]), pack2(o[8 * s + 4], o[8 * s + 5]), pack2(o[8 * s + 6], o[8 * s + 7]));
            }
            if (tk == 256 && w < 2) {
                uint32_t* z = (uint32_t*)g_GN + t * 32 + w * 16 + g;
#pragma unroll
                for (int s = 0; s < 16; s++) {
                    z[(s >> 1) * 128 + (s & 1) * 8] = pack2(e[2 * s], e[2 * s + 1]);
                    z[(s >> 1) * 128 + (s & 1) * 8 + 1024] = pack2(o[2 * s], o[2 * s + 1]);
                }
                fence_async();
            }
        }
        fence_smem();
        wgbar(q);
        IO(true) {
            if (i > 0) { tma3s(&tmg2, buf, 0, GROW(tk - 4 * nw), 0); bulk_commit(); }
            asm volatile("cp.async.bulk.wait_group 0;" ::: "memory");
            grid_arrive(cnt + 1);
        }
    }
    FT(4);
    bsync<1, 512>();
    {
        for (uint32_t n = wi_; n < 32; n += 16) {
            const uint32_t cl = (mat >> 1) * 16 + t * 4 + (mat & 1), mh = ((n >> 3) & 1) + (n & 7) * 2 + (n & 16);
            sts32(sb + FS_F2 + n * 128 + ((g ^ (n & 7)) << 4) + t * 4, cos2(cl * mh * 64 + (g & 1) * 512, (cl + 2) * mh * 64 + (g & 1) * 512));
        }
        fence_smem();
        c1 = 8 * w + g;
#pragma unroll
        for (int i = 0; i < 8; i++) {
            twid(-c1 * (16 * (i >> 2) + 4 * t + 2 * (i & 1) + ((i >> 1) & 1)), tc[i], ts[i]);
            F[i >> 2][i & 3] = cis((i & 1) * 512 - c1 * ((i >> 1) * 4 + (t ^ (q & 1))) * 64);
        }
        const uint32_t kr = (j8 & 1) ^ ((j8 >> 2) << 1);
        const uint32_t so2 = ((w >> 1) * 4 + (j8 >> 2) * 2 + (w & 1)) * 8192 + (2 * q + (mat & 1)) * 1024 + kr * 128 + (((((j8 >> 1) & 1) * 4 + (mat >> 1)) ^ kr) << 4);
        const uint32_t so1 = (mat & 1) * 2048 + j8 * 128 + ((((mat >> 1) * 4 + w) ^ j8) << 4);
        uint32_t so = so1 << 16 | so2;
        const float fx = t ? 0.f : (g & 1) ? -1.f : 1.f;
        fft_gen<true>(sb + FS_TB, N2(cta));
        bsync<1, 512>();
        IO(true) grid_wait(cnt + 1, 4 * nw);
        for (int i = 0; i < 3; i++) IO(i < nt) GLOAD3(i, i);
        __syncwarp();
        int b = 0, bp = 2, ph = 0;
        auto step = [&](auto first, auto last, const int i) {
            const uint32_t p = cta + i * nw, bn = 3 - b - bp, tb = (i & 1) * 8192;
            const uint32_t grp = sb + bp * 65536 + q * 16384, ny = sb + FS_NY + bp * 128 + q * 32;
            auto sb_ = [&]() { if constexpr (!decltype(last)::v) mwait(bar + b * 8, ph); };
            if constexpr (!decltype(first)::v) {
                fft_rows<true>(grp, q, F, tc, ts, opq(so, zero) >> 16, fx, ny, [&]() {
                    if (i > 1) {
                        fence_smem();
                        wgbar(q);
                        IO(true) { tma4s(&tmy, sb + bn * 65536 + q * 16384, 0, 0, q * 8, N2(p - 2 * nw)); bulk_commit(); }
                    }
                }, sb_);
            } else { sb_(); __syncwarp(); }
            if constexpr (decltype(first)::v) FT(5);
            if constexpr (!decltype(last)::v) {
                float n[4];
                fft_cross<true>(sb + b * 65536, q, sb + FS_TB + tb + (tidx() & 127) * 16, opq(so, zero) & 0xFFFF, sb + FS_NQ + b * 1024, n, [&]() {
                    fft_gen<true>(sb + FS_TB + 8192 - tb, N2(p + nw));
                    IO(i >= 2 && i + 1 < nt) {
                        asm volatile("cp.async.bulk.wait_group.read 0;" ::: "memory");
                        GLOAD3(i + 1, bn);
                    }
                });
                if (q == 0) {
                    const uint32_t x = tidx(), a = sb + FS_NY + b * 128 + (x & 64) + (x & 16) * 2 + ((x & 40) >> 1);
                    if ((x & 7) == 0) { sts32f(a, n[0]); sts32f(a + 8, n[2]); }
                }
            }
            auto sc = [&]() {
                if constexpr (!decltype(last)::v) {
                    fence_smem();
                    __syncwarp();
                    if (elect()) mbar_arrive(bar + 24);
                }
            };
            auto sd = [&]() { if constexpr (!decltype(last)::v) mwait(bar + 24, (nt + i) & 1); };
            if constexpr (!decltype(first)::v) fft_rows<true>(grp + 8192, q, F, tc, ts, opq(so, zero) >> 16, fx, ny + 16, sc, sd);
            else { sc(); __syncwarp(); sd(); __syncwarp(); }
            if constexpr (!decltype(last)::v) {
                bp = b;
                if (++b == 3) { b = 0; ph ^= 1; }
            }
        };
        if (nt) {
            step(Bool<true>(), Bool<false>(), 0);
#pragma unroll 1
            for (int i = 1; i < nt; i++) step(Bool<false>(), Bool<false>(), i);
            step(Bool<false>(), Bool<true>(), nt);
        }
        fence_smem();
        wgbar(q);
        IO(nt) { tma4s(&tmy, sb + bp * 65536 + q * 16384, 0, 0, q * 8, N2(cta + (nt - 1) * nw)); bulk_commit(); }
        FT(6);
        IO(true) asm volatile("cp.async.bulk.wait_group 0;" ::: "memory");
    }
}

typedef CUresult (*EncodeFn)(CUtensorMap*, CUtensorMapDataType, cuuint32_t, void*, const cuuint64_t*, const cuuint64_t*,
                             const cuuint32_t*, const cuuint32_t*, CUtensorMapInterleave, CUtensorMapSwizzle,
                             CUtensorMapL2promotion, CUtensorMapFloatOOBfill);

static void make_map(EncodeFn enc, CUtensorMap* m, const void* ptr, int rank, const cuuint64_t* dims, const cuuint64_t* strides,
                     const cuuint32_t* box, CUtensorMapSwizzle sw = CU_TENSOR_MAP_SWIZZLE_128B) {
    cuuint32_t es[4] = {1, 1, 1, 1};
    CUresult r = enc(m, CU_TENSOR_MAP_DATA_TYPE_BFLOAT16, rank, (void*)ptr, dims, strides, box, es, CU_TENSOR_MAP_INTERLEAVE_NONE,
                     sw, CU_TENSOR_MAP_L2_PROMOTION_L2_256B, CU_TENSOR_MAP_FLOAT_OOB_FILL_NONE);
    if (r != CUDA_SUCCESS) fprintf(stderr, "tensor map encode failed: %d\n", (int)r);
}

extern "C" void kernel_launch(void* const* d_in, const int* in_sizes, int n_in, void* d_out, int out_size) {
    const bf16* A_x = (const bf16*)d_in[0];
    const bf16* A_mem0 = (const bf16*)d_in[1];
    const bf16* A_Wq = (const bf16*)d_in[2];
    const bf16* A_Wk = (const bf16*)d_in[3];
    const bf16* A_Wv = (const bf16*)d_in[4];
    const bf16* A_Wo = (const bf16*)d_in[5];
    const bf16* B_x = (const bf16*)d_in[7];
    const bf16* B_wr = (const bf16*)d_in[8];
    const bf16* B_wi = (const bf16*)d_in[9];
    bf16* out = (bf16*)d_out;

    static EncodeFn enc = nullptr;
    static void *pxs = nullptr, *pg = nullptr;
    static int ncl = 64;
    if (!enc) {
        cudaDriverEntryPointQueryResult qr;
        void* fn = nullptr;
        cudaGetDriverEntryPoint("cuTensorMapEncodeTiled", &fn, cudaEnableDefault, &qr);
        enc = (EncodeFn)fn;
        cudaFuncSetAttribute(chain_kernel, cudaFuncAttributeMaxDynamicSharedMemorySize, SM_TOTAL);
        cudaFuncSetAttribute(post_kernel, cudaFuncAttributeMaxDynamicSharedMemorySize, FS_TOTAL);
        cudaGetSymbolAddress(&pxs, g_xs);
        cudaGetSymbolAddress(&pg, g_G);
        cudaLaunchConfig_t lc = {};
        cudaLaunchAttribute at;
        at.id = cudaLaunchAttributeClusterDimension;
        at.val.clusterDim.x = 2; at.val.clusterDim.y = 1; at.val.clusterDim.z = 1;
        lc.gridDim = dim3(132); lc.blockDim = dim3(384); lc.dynamicSmemBytes = SM_TOTAL; lc.attrs = &at; lc.numAttrs = 1;
        int nc = 0;
        if (cudaOccupancyMaxActiveClusters(&nc, chain_kernel, &lc) == cudaSuccess && nc > 64) ncl = nc < 66 ? nc : 66;
    }
    CUtensorMap tmq, tmk, tmv, tmo, tmx, tmb;
    {
        cuuint64_t d[2] = {HD, DM}, st[1] = {HD * 2};
        cuuint32_t bx[2] = {64, 256};
        make_map(enc, &tmq, A_Wq, 2, d, st, bx);
        make_map(enc, &tmk, A_Wk, 2, d, st, bx);
        cuuint32_t bx2[2] = {64, 16};
        make_map(enc, &tmv, A_Wv, 2, d, st, bx2);
    }
    {
        cuuint64_t d[2] = {DM, HD}, st[1] = {DM * 2};
        cuuint32_t bx[2] = {64, 16}, bx2[2] = {64, 64};
        make_map(enc, &tmo, A_Wo, 2, d, st, bx);
        make_map(enc, &tmb, A_Wo, 2, d, st, bx2);
    }
    {
        cuuint64_t d[3] = {64, SEQ, DM / 64}, st[2] = {DM * 2, 128};
        cuuint32_t bx[3] = {64, 8, 4};
        make_map(enc, &tmx, A_x, 3, d, st, bx);
    }
    CUtensorMap fx, fg1, fg2, fwr, fwi, fy;
    {
        cuuint64_t d[4] = {32, 32, 32, 64}, st[3] = {64, 64 * DM * 2, DM * 2};
        cuuint32_t bx[4] = {32, 32, 8, 1};
        make_map(enc, &fx, B_x, 4, d, st, bx, CU_TENSOR_MAP_SWIZZLE_64B);
        cuuint64_t d2[4] = {64, 16, 32, 64}, st2[3] = {128, 64 * 4096, 4096};
        cuuint32_t bx2[4] = {64, 16, 8, 1};
        make_map(enc, &fy, out + DM, 4, d2, st2, bx2);
    }
    {
        cuuint64_t d[3] = {64, G_ROWS, 64}, st[2] = {128, G_ROWS * 128};
        cuuint32_t bx[3] = {64, 128, 1}, bx2[3] = {64, 2, 64};
        make_map(enc, &fg1, pg, 3, d, st, bx);
        make_map(enc, &fg2, pg, 3, d, st, bx2);
        cuuint64_t d2[3] = {8 * 513, 4, 64}, st2[2] = {8 * 513 * 2, 32 * 513 * 2};
        cuuint32_t bx3[3] = {72, 1, 64};
        make_map(enc, &fwr, B_wr, 3, d2, st2, bx3, CU_TENSOR_MAP_SWIZZLE_NONE);
        make_map(enc, &fwi, B_wi, 3, d2, st2, bx3, CU_TENSOR_MAP_SWIZZLE_NONE);
    }
    cudaStream_t st = cudaStreamPerThread;
    const uint64_t xs = ((uint64_t)pxs + XS_BYTES - 1) & ~(uint64_t)(XS_BYTES - 1);
    cudaMemsetAsync((void*)(xs + XO_R), 0, XO_TK + 512, st);
    chain_kernel<<<2 * ncl, 384, SM_TOTAL, st>>>(tmq, tmk, tmv, tmo, tmx, A_mem0, A_x, (uint32_t)xs, (uint32_t)(xs >> 32), 0u, NSEG);
    int nw = ncl == 66 ? 4 : 64;
    cudaLaunchConfig_t lc = {};
    cudaLaunchAttribute at;
    at.id = cudaLaunchAttributeProgrammaticStreamSerialization;
    at.val.programmaticStreamSerializationAllowed = 1;
    lc.gridDim = dim3(nw + 128); lc.blockDim = dim3(F_THREADS); lc.dynamicSmemBytes = FS_TOTAL; lc.stream = st; lc.attrs = &at; lc.numAttrs = 1;
    cudaLaunchKernelEx(&lc, post_kernel, fx, fg1, fg2, fwr, fwi, fy, B_wr, B_wi, (uint32_t*)(xs + XO_TK + 256), 0u, nw, tmb, (uint32_t)xs,
                       (uint32_t)(xs >> 32), out);
}
```

```cpp
#include <cuda_runtime.h>
#include <cuda_bf16.h>
#include <cuda.h>
#include <stdint.h>
#include <stdio.h>

typedef __nv_bfloat16 bf16;

#define SEQ 2048
#define DM 1024
#define NH 32
#define DH 128
#define NSEG 64
#define HD (NH * DH)

#define XS_BYTES (32u << 20)
__device__ uint4 g_xs[2 * XS_BYTES / 16];
#define XO_R 0u
#define XO_PB (1u << 18)
#define XO_FL (XO_PB + 16384u)
#define XO_TK (XO_FL + 32768u)
#define XO_CQK (1u << 20)
#define XO_CV (2u << 20)
#define XO_XG (4u << 20)
#define XO_OX (16u << 20)
#define GSYNC(n)

#define DEVI __device__ __forceinline__

DEVI void die(int it) { asm volatile("st.shared.u32 [%0], %0;" ::"r"(it) : "memory"); }
DEVI uint32_t smem_u32(const void* p) { return (uint32_t)__cvta_generic_to_shared(p); }
DEVI void mbar_init(uint32_t bar, uint32_t cnt) { asm volatile("mbarrier.init.shared::cta.b64 [%0], %1;" ::"r"(bar), "r"(cnt) : "memory"); }
DEVI void mbar_expect(uint32_t bar, uint32_t bytes) { asm volatile("mbarrier.arrive.expect_tx.shared::cta.b64 _, [%0], %1;" ::"r"(bar), "r"(bytes) : "memory"); }
DEVI void mbar_arrive(uint32_t bar) { asm volatile("mbarrier.arrive.shared::cta.b64 _, [%0];" ::"r"(bar) : "memory"); }
DEVI void mbar_wait(uint32_t bar, uint32_t parity) {
    uint32_t done;
    int it = 0;
    do {
        asm volatile("{\n.reg .pred p;\nmbarrier.try_wait.parity.shared::cta.b64 p, [%1], %2;\nselp.u32 %0, 1, 0, p;\n}\n"
                     : "=r"(done) : "r"(bar), "r"(parity) : "memory");
        if (++it > (1 << 22)) die(it);
    } while (!done);
}
DEVI void tma2d(uint32_t dst, const CUtensorMap* tm, uint32_t bar, int c0, int c1) {
    asm volatile("cp.async.bulk.tensor.2d.shared::cluster.global.mbarrier::complete_tx::bytes [%0], [%1, {%3, %4}], [%2];"
                 ::"r"(dst), "l"(tm), "r"(bar), "r"(c0), "r"(c1) : "memory");
}
DEVI void tma3d(uint32_t dst, const CUtensorMap* tm, uint32_t bar, int c0, int c1, int c2) {
    asm volatile("cp.async.bulk.tensor.3d.shared::cluster.global.mbarrier::complete_tx::bytes [%0], [%1, {%3, %4, %5}], [%2];"
                 ::"r"(dst), "l"(tm), "r"(bar), "r"(c0), "r"(c1), "r"(c2) : "memory");
}
DEVI void bulk_g2s(uint32_t dst, uint32_t lo, uint32_t hi, uint32_t bytes, uint32_t bar) {
    asm volatile("{\n.reg .b64 a;\nmov.b64 a, {%1,%2};\ncp.async.bulk.shared::cluster.global.mbarrier::complete_tx::bytes [%0], [a], %3, [%4];\n}"
                 ::"r"(dst), "r"(lo), "r"(hi), "r"(bytes), "r"(bar) : "memory");
}
DEVI void bulk_s2g(uint32_t lo, uint32_t hi, uint32_t src, uint32_t bytes) {
    asm volatile("{\n.reg .b64 a;\nmov.b64 a, {%0,%1};\ncp.async.bulk.global.shared::cta.bulk_group [a], [%2], %3;\ncp.async.bulk.commit_group;\n}"
                 ::"r"(lo), "r"(hi), "r"(src), "r"(bytes) : "memory");
}
DEVI void bulk_red(uint32_t lo, uint32_t hi, uint32_t src, uint32_t bytes) {
    asm volatile("{\n.reg .b64 a;\nmov.b64 a, {%0,%1};\ncp.reduce.async.bulk.global.shared::cta.bulk_group.add.noftz.bf16 [a], [%2], %3;\ncp.async.bulk.commit_group;\n}"
                 ::"r"(lo), "r"(hi), "r"(src), "r"(bytes) : "memory");
}
DEVI bool elect() {
    uint32_t p;
    asm volatile("{\n.reg .pred P;\nelect.sync _|P, 0xFFFFFFFF;\nselp.u32 %0, 1, 0, P;\n}" : "=r"(p));
    return p != 0;
}
DEVI void ldsm4(uint32_t (&r)[4], uint32_t a) {
    asm volatile("ldmatrix.sync.aligned.m8n8.x4.shared.b16 {%0,%1,%2,%3}, [%4];" : "=r"(r[0]), "=r"(r[1]), "=r"(r[2]), "=r"(r[3]) : "r"(a) : "memory");
}
DEVI void ldsm4t(uint32_t (&r)[4], uint32_t a) {
    asm volatile("ldmatrix.sync.aligned.m8n8.x4.trans.shared.b16 {%0,%1,%2,%3}, [%4];" : "=r"(r[0]), "=r"(r[1]), "=r"(r[2]), "=r"(r[3]) : "r"(a) : "memory");
}
DEVI void ldsm2t(uint32_t (&r)[2], uint32_t a) {
    asm volatile("ldmatrix.sync.aligned.m8n8.x2.trans.shared.b16 {%0,%1}, [%2];" : "=r"(r[0]), "=r"(r[1]) : "r"(a) : "memory");
}
DEVI void ldsm2(uint32_t (&r)[2], uint32_t a) {
    asm volatile("ldmatrix.sync.aligned.m8n8.x2.shared.b16 {%0,%1}, [%2];" : "=r"(r[0]), "=r"(r[1]) : "r"(a) : "memory");
}
DEVI void stsm4t(uint32_t a, uint32_t r0, uint32_t r1, uint32_t r2, uint32_t r3) {
    asm volatile("stmatrix.sync.aligned.m8n8.x4.trans.shared.b16 [%0], {%1,%2,%3,%4};" ::"r"(a), "r"(r0), "r"(r1), "r"(r2), "r"(r3) : "memory");
}
DEVI uint32_t ldsm1(uint32_t a) {
    uint32_t r;
    asm volatile("ldmatrix.sync.aligned.m8n8.x1.shared.b16 {%0}, [%1];" : "=r"(r) : "r"(a) : "memory");
    return r;
}
DEVI void stsm4(uint32_t a, uint32_t r0, uint32_t r1, uint32_t r2, uint32_t r3) {
    asm volatile("stmatrix.sync.aligned.m8n8.x4.shared.b16 [%0], {%1,%2,%3,%4};" ::"r"(a), "r"(r0), "r"(r1), "r"(r2), "r"(r3) : "memory");
}
DEVI void stsm2(uint32_t a, uint32_t r0, uint32_t r1) {
    asm volatile("stmatrix.sync.aligned.m8n8.x2.shared.b16 [%0], {%1,%2};" ::"r"(a), "r"(r0), "r"(r1) : "memory");
}
DEVI uint32_t movm(uint32_t a) {
    uint32_t d;
    asm volatile("movmatrix.sync.aligned.m8n8.trans.b16 %0, %1;" : "=r"(d) : "r"(a));
    return d;
}
DEVI void mma16(float (&d)[4], uint32_t a0, uint32_t a1, uint32_t a2, uint32_t a3, uint32_t b0, uint32_t b1) {
    asm volatile("mma.sync.aligned.m16n8k16.row.col.f32.bf16.bf16.f32 {%0,%1,%2,%3}, {%4,%5,%6,%7}, {%8,%9}, {%0,%1,%2,%3};"
                 : "+f"(d[0]), "+f"(d[1]), "+f"(d[2]), "+f"(d[3]) : "r"(a0), "r"(a1), "r"(a2), "r"(a3), "r"(b0), "r"(b1));
}
DEVI void mma16z(float (&d)[4], uint32_t a0, uint32_t a1, uint32_t a2, uint32_t a3, uint32_t b0, uint32_t b1) {
    asm volatile("mma.sync.aligned.m16n8k16.row.col.f32.bf16.bf16.f32 {%0,%1,%2,%3}, {%4,%5,%6,%7}, {%8,%9}, {%10,%10,%10,%10};"
                 : "=f"(d[0]), "=f"(d[1]), "=f"(d[2]), "=f"(d[3]) : "r"(a0), "r"(a1), "r"(a2), "r"(a3), "r"(b0), "r"(b1), "f"(0.f));
}
DEVI void mma8(float (&d)[4], uint32_t a0, uint32_t a1, uint32_t b0) {
    asm volatile("mma.sync.aligned.m16n8k8.row.col.f32.bf16.bf16.f32 {%0,%1,%2,%3}, {%4,%5}, {%6}, {%0,%1,%2,%3};"
                 : "+f"(d[0]), "+f"(d[1]), "+f"(d[2]), "+f"(d[3]) : "r"(a0), "r"(a1), "r"(b0));
}
DEVI void mma8z(float (&d)[4], uint32_t a0, uint32_t a1, uint32_t b0) {
    asm volatile("mma.sync.aligned.m16n8k8.row.col.f32.bf16.bf16.f32 {%0,%1,%2,%3}, {%4,%5}, {%6}, {%7,%7,%7,%7};"
                 : "=f"(d[0]), "=f"(d[1]), "=f"(d[2]), "=f"(d[3]) : "r"(a0), "r"(a1), "r"(b0), "f"(0.f));
}
DEVI uint32_t pack2(float lo, float hi) {
    uint32_t r;
    asm("cvt.rn.bf16x2.f32 %0, %1, %2;" : "=r"(r) : "f"(hi), "f"(lo));
    return r;
}
DEVI uint32_t hadd2(uint32_t a, uint32_t b) {
    uint32_t r;
    asm("add.rn.bf16x2 %0, %1, %2;" : "=r"(r) : "r"(a), "r"(b));
    return r;
}
DEVI float lo_f(uint32_t x) { return __uint_as_float(x << 16); }
DEVI float hi_f(uint32_t x) { return __uint_as_float(x & 0xFFFF0000u); }
template <uint32_t OFF> DEVI uint4 ldg4(uint32_t lo, uint32_t hi) {
    uint4 v;
    asm volatile("{\n.reg .b64 a;\nmov.b64 a, {%4,%5};\nld.relaxed.gpu.global.v4.u32 {%0,%1,%2,%3}, [a+%6];\n}"
                 : "=r"(v.x), "=r"(v.y), "=r"(v.z), "=r"(v.w) : "r"(lo), "r"(hi), "n"(OFF) : "memory");
    return v;
}
template <uint32_t OFF> DEVI uint2 ldg2(uint32_t lo, uint32_t hi) {
    uint2 v;
    asm volatile("{\n.reg .b64 a;\nmov.b64 a, {%2,%3};\nld.relaxed.gpu.global.v2.u32 {%0,%1}, [a+%4];\n}"
                 : "=r"(v.x), "=r"(v.y) : "r"(lo), "r"(hi), "n"(OFF) : "memory");
    return v;
}
template <uint32_t OFF> DEVI uint32_t ldg1(uint32_t lo, uint32_t hi) {
    uint32_t v;
    asm volatile("{\n.reg .b64 a;\nmov.b64 a, {%1,%2};\nld.relaxed.gpu.global.u32 %0, [a+%3];\n}" : "=r"(v) : "r"(lo), "r"(hi), "n"(OFF) : "memory");
    return v;
}
template <uint32_t OFF> DEVI void stg1(uint32_t lo, uint32_t hi, uint32_t a) {
    asm volatile("{\n.reg .b64 a;\nmov.b64 a, {%0,%1};\nst.relaxed.gpu.global.u32 [a+%3], %2;\n}" ::"r"(lo), "r"(hi), "r"(a), "n"(OFF) : "memory");
}
template <uint32_t OFF> DEVI void stg4(uint32_t lo, uint32_t hi, uint32_t a, uint32_t b, uint32_t c, uint32_t d) {
    asm volatile("{\n.reg .b64 a;\nmov.b64 a, {%0,%1};\nst.relaxed.gpu.global.v4.u32 [a+%6], {%2,%3,%4,%5};\n}"
                 ::"r"(lo), "r"(hi), "r"(a), "r"(b), "r"(c), "r"(d), "n"(OFF) : "memory");
}
template <uint32_t OFF> DEVI void stg2(uint32_t lo, uint32_t hi, uint32_t a, uint32_t b) {
    asm volatile("{\n.reg .b64 a;\nmov.b64 a, {%0,%1};\nst.relaxed.gpu.global.v2.u32 [a+%4], {%2,%3};\n}"
                 ::"r"(lo), "r"(hi), "r"(a), "r"(b), "n"(OFF) : "memory");
}
DEVI uint32_t tagx2(uint32_t a, uint32_t b, uint32_t t) { uint32_t r; asm("lop3.b32 %0, %1, %2, %3, 0x7E;" : "=r"(r) : "r"(a), "r"(b), "r"(t)); return r; }
DEVI uint32_t tagx1(uint32_t a, uint32_t b, uint32_t t) { uint32_t r; asm("lop3.b32 %0, %1, %2, %3, 0xF6;" : "=r"(r) : "r"(a), "r"(b), "r"(t)); return r; }
DEVI uint32_t or3(uint32_t a, uint32_t b, uint32_t c) { uint32_t r; asm("lop3.b32 %0, %1, %2, %3, 0xFE;" : "=r"(r) : "r"(a), "r"(b), "r"(c)); return r; }
DEVI bool any_bad(uint32_t x) { return __any_sync(0xFFFFFFFFu, (x & 1u) != 0); }
DEVI uint32_t settag(uint32_t x, uint32_t tag) { return (x & ~1u) | tag; }
DEVI void sts32f(uint32_t a, float v) { asm volatile("st.shared.f32 [%0], %1;" ::"r"(a), "f"(v) : "memory"); }
DEVI void sts32(uint32_t a, uint32_t v) { asm volatile("st.shared.u32 [%0], %1;" ::"r"(a), "r"(v) : "memory"); }
DEVI void sts16(uint32_t a, uint32_t v) { asm volatile("st.shared.u16 [%0], %1;" ::"r"(a), "h"((unsigned short)v) : "memory"); }
DEVI void sts64(uint32_t a, uint32_t x, uint32_t y) { asm volatile("st.shared.v2.u32 [%0], {%1,%2};" ::"r"(a), "r"(x), "r"(y) : "memory"); }
DEVI void sts128(uint32_t a, uint32_t x, uint32_t y, uint32_t z, uint32_t w) {
    asm volatile("st.shared.v4.u32 [%0], {%1,%2,%3,%4};" ::"r"(a), "r"(x), "r"(y), "r"(z), "r"(w) : "memory");
}
DEVI float4 lds128f(uint32_t a) {
    float4 v;
    asm volatile("ld.shared.v4.f32 {%0,%1,%2,%3}, [%4];" : "=f"(v.x), "=f"(v.y), "=f"(v.z), "=f"(v.w) : "r"(a) : "memory");
    return v;
}
DEVI uint4 lds128(uint32_t a) {
    uint4 v;
    asm volatile("ld.shared.v4.u32 {%0,%1,%2,%3}, [%4];" : "=r"(v.x), "=r"(v.y), "=r"(v.z), "=r"(v.w) : "r"(a) : "memory");
    return v;
}
DEVI uint2 lds64(uint32_t a) {
    uint2 v;
    asm volatile("ld.shared.v2.u32 {%0,%1}, [%2];" : "=r"(v.x), "=r"(v.y) : "r"(a) : "memory");
    return v;
}
DEVI uint32_t lds32(uint32_t a) {
    uint32_t v;
    asm volatile("ld.shared.u32 %0, [%1];" : "=r"(v) : "r"(a) : "memory");
    return v;
}
DEVI float ex2(float x) { float r; asm("ex2.approx.ftz.f32 %0, %1;" : "=f"(r) : "f"(x)); return r; }
DEVI float rcp(float x) { float r; asm("rcp.approx.ftz.f32 %0, %1;" : "=f"(r) : "f"(x)); return r; }
DEVI uint32_t clk() { uint32_t c; asm volatile("mov.u32 %0, %%clock;" : "=r"(c)::"memory"); return c; }

DEVI uint64_t mkdesc(uint32_t addr, uint32_t lbo, uint32_t sbo) {
    return (uint64_t)((addr & 0x3FFFF) >> 4) | ((uint64_t)(lbo >> 4) << 16) | ((uint64_t)(sbo >> 4) << 32) | ((uint64_t)1 << 62);
}
DEVI void wg_fence() { asm volatile("wgmma.fence.sync.aligned;" ::: "memory"); }
DEVI void wg_commit() { asm volatile("wgmma.commit_group.sync.aligned;" ::: "memory"); }
template <int N> DEVI void wg_wait() { asm volatile("wgmma.wait_group.sync.aligned %0;" ::"n"(N) : "memory"); }
template <int SC>
DEVI void wg_rs32(float (&d)[16], const uint32_t (&a)[4], uint64_t db) {
    if (SC) {
        asm volatile("wgmma.mma_async.sync.aligned.m64n32k16.f32.bf16.bf16 "
                     "{%0,%1,%2,%3,%4,%5,%6,%7,%8,%9,%10,%11,%12,%13,%14,%15}, {%16,%17,%18,%19}, %20, 1, 1, 1, 0;"
                     : "+f"(d[0]), "+f"(d[1]), "+f"(d[2]), "+f"(d[3]), "+f"(d[4]), "+f"(d[5]), "+f"(d[6]), "+f"(d[7]),
                       "+f"(d[8]), "+f"(d[9]), "+f"(d[10]), "+f"(d[11]), "+f"(d[12]), "+f"(d[13]), "+f"(d[14]), "+f"(d[15])
                     : "r"(a[0]), "r"(a[1]), "r"(a[2]), "r"(a[3]), "l"(db));
    } else {
        asm volatile("wgmma.mma_async.sync.aligned.m64n32k16.f32.bf16.bf16 "
                     "{%0,%1,%2,%3,%4,%5,%6,%7,%8,%9,%10,%11,%12,%13,%14,%15}, {%16,%17,%18,%19}, %20, 0, 1, 1, 0;"
                     : "=f"(d[0]), "=f"(d[1]), "=f"(d[2]), "=f"(d[3]), "=f"(d[4]), "=f"(d[5]), "=f"(d[6]), "=f"(d[7]),
                       "=f"(d[8]), "=f"(d[9]), "=f"(d[10]), "=f"(d[11]), "=f"(d[12]), "=f"(d[13]), "=f"(d[14]), "=f"(d[15])
                     : "r"(a[0]), "r"(a[1]), "r"(a[2]), "r"(a[3]), "l"(db));
    }
}

#define NPRO 5
#define NA 12
#define NB 0
#define NPF 6
#define PF1 2
#define PF2 2
#define PF3 5
#define WPF 2
#define NPE (NPF & ~1)
#define VPF 2
#define VORD (NA == 12 ? 0x01234567 : NA == 10 ? 0x50123467 : NA == 8 ? 0x40125367 : 0x30142567)
#define WV_BOX ((16 - NA) * 2048)
#define WO_BOX ((16 - NB) * 1024)
#define SM_WV 0
#define SM_WO (2 * WV_BOX)
#define SM_X (SM_WO + 4 * WO_BOX)
#define SM_XO (SM_X + 32768)
#define SM_PI (SM_XO + 12288)
#define SM_KV (SM_PI + 24576)
#define SM_SP (SM_KV + 18432)
#define SM_TR (SM_SP + 10240)
#define SM_MEMT (SM_TR + 12288)
#define SM_OT (SM_MEMT + 4096)
#define SM_VS (SM_OT + 2048)
#define SM_P (SM_VS + 2048)
#define SM_DN (SM_P + 1792)
#define SM_PROF (SM_P + 2048)
#define SM_BAR 232192
#define SM_TOTAL (SM_BAR + 256)
#define SM_STA SM_X
#define SM_STB (SM_STA + 65536)
#define SM_STC (SM_STB + 65536)
#define NA1_ ((SM_BAR - SM_STC) / 4096)
#define NA1 (NA < NA1_ ? NA : NA1_)
static_assert(SM_STC + NA1 * 4096 <= SM_BAR && NB + NA - NA1 <= 16 && SM_PROF + 3072 <= SM_BAR, "staging");
static_assert(SM_TOTAL <= 232448, "smem");
#define BAR_XA 32
#define BAR_KV 40
#define BAR_PI 48
#define SM_ROLE (SM_BAR + 64)

#define SPIN_LIMIT (1 << 20)
#define RPOS 20
#define OPOS 2
#define ASF 0
#define KPOS 0
#define CPOS 1
#define DLY_V 400
#define CFAR 1

template <int ID, int N> DEVI void bsync() { asm volatile("bar.sync %0, %1;" ::"n"(ID), "n"(N) : "memory"); }
template <int ID, int N> DEVI void barv() { asm volatile("bar.arrive %0, %1;" ::"n"(ID), "n"(N) : "memory"); }

#define PT(n)
#define PC(n, v)
#define PDUMP()
#define REFRESH() asm volatile("xor.b32 %0, %0, %1;" : "+r"(l16) : "r"(zero))
#define OPQ(x) asm volatile("xor.b32 %0, %0, %1;" : "+r"(x) : "r"(zero))
#define KEEP(x, a, b, c, d) asm volatile("{\n.reg .b32 t;\nlop3.b32 t, %1, %2, %3, 0x80;\nlop3.b32 t, t, %4, %5, 0x80;\nxor.b32 %0, %0, t;\n}" \
                                         : "+r"(x) : "r"(a), "r"(b), "r"(c), "r"(d), "r"(zero))
#define SF() asm volatile("pmevent 1;" ::: "memory")
#define MF() __syncwarp()
#define SB0 1024u

#define XDOFF(ks) ((((ks) >> 2) * 1024 + ((ks) & 3) * 32) >> 4)
template <int SC>
DEVI void wg_ss32t(float (&d)[16], uint64_t da, uint64_t db) {
    if (SC) {
        asm volatile("wgmma.mma_async.sync.aligned.m64n32k16.f32.bf16.bf16 "
                     "{%0,%1,%2,%3,%4,%5,%6,%7,%8,%9,%10,%11,%12,%13,%14,%15}, %16, %17, 1, 1, 1, 1, 0;"
                     : "+f"(d[0]), "+f"(d[1]), "+f"(d[2]), "+f"(d[3]), "+f"(d[4]), "+f"(d[5]), "+f"(d[6]), "+f"(d[7]),
                       "+f"(d[8]), "+f"(d[9]), "+f"(d[10]), "+f"(d[11]), "+f"(d[12]), "+f"(d[13]), "+f"(d[14]), "+f"(d[15])
                     : "l"(da), "l"(db));
    } else {
        asm volatile("wgmma.mma_async.sync.aligned.m64n32k16.f32.bf16.bf16 "
                     "{%0,%1,%2,%3,%4,%5,%6,%7,%8,%9,%10,%11,%12,%13,%14,%15}, %16, %17, 0, 1, 1, 1, 0;"
                     : "=f"(d[0]), "=f"(d[1]), "=f"(d[2]), "=f"(d[3]), "=f"(d[4]), "=f"(d[5]), "=f"(d[6]), "=f"(d[7]),
                       "=f"(d[8]), "=f"(d[9]), "=f"(d[10]), "=f"(d[11]), "=f"(d[12]), "=f"(d[13]), "=f"(d[14]), "=f"(d[15])
                     : "l"(da), "l"(db));
    }
}

DEVI void delay_until(uint32_t t0, uint32_t d) { t0 += d; while (clk() < t0) {} }

template <int I0, int I1>
DEVI void xmma(float (&xa)[16], float (&xb)[16], uint32_t w, int ps, uint32_t zero, const uint32_t (&Wq)[16][4], const uint32_t (&Wk)[16][4],
               const uint32_t (&Wv)[NA][4]) {
    const uint64_t xd = mkdesc(SB0 + SM_X, 16, 4096) + (ps & 1) * 1024, vd = mkdesc(SB0 + SM_WV, 8192, 1024);
    uint32_t vo = (w >> 2) * (WV_BOX / 16);
    if (I0 < 16 - NA) OPQ(vo);
#pragma unroll
    for (int i = I0; i < I1; i++) {
        if (i == 0) wg_ss32t<0>(xb, (vd & ~0xFFFFFFFFull) | ((uint32_t)vd + vo), xd + XDOFF(NA));
        else if (i < 16 - NA) wg_ss32t<1>(xb, (vd & ~0xFFFFFFFFull) | ((uint32_t)vd + i * 128 + vo), xd + XDOFF(NA + i));
        else if (i == 16 - NA) wg_rs32<0>(xa, Wq[0], xd);
        else if (i < 32 - NA) wg_rs32<1>(xa, Wq[(i + NA) & 15], xd + XDOFF((i + NA) & 15));
        else if (i < 32) wg_rs32<1>(xb, Wv[(i + NA) & 15], xd + XDOFF((i + NA) & 15));
        else if (i == 32) wg_rs32<0>(xa, Wk[0], xd);
        else wg_rs32<1>(xa, Wk[i & 15], xd + XDOFF(i & 15));
    }
    wg_commit();
}
#define XMMA(I0, I1) xmma<(I0), (I1)>(xa, xb, w, p ^ 1, zero, Wq, Wk, Wv)
DEVI void wg_done(float (&d)[16]) {
    asm volatile("" : "+f"(d[0]), "+f"(d[1]), "+f"(d[2]), "+f"(d[3]), "+f"(d[4]), "+f"(d[5]), "+f"(d[6]), "+f"(d[7]),
                      "+f"(d[8]), "+f"(d[9]), "+f"(d[10]), "+f"(d[11]), "+f"(d[12]), "+f"(d[13]), "+f"(d[14]), "+f"(d[15]) :: "memory");
}
template <int M>
DEVI void xpack(uint32_t (&xp)[8], float (&xa)[16]) {
    wg_done(xa);
#pragma unroll
    for (int i = 0; i < 4; i++) {
        xp[2 * i] = pack2(xa[4 * i], xa[4 * i + (M < 2 ? 2 : 1)]);
        xp[2 * i + 1] = pack2(xa[4 * i + (M < 2 ? 1 : 2)], xa[4 * i + 3]);
    }
}
template <int M>
DEVI uint4 xpeer(uint32_t sb, int ps, uint32_t t16) { return lds128(sb + SM_PI + ((ps & 1) ^ 1) * 12288 + M * 4096 + t16); }
DEVI void xadd(uint32_t (&xp)[8], const uint4& pi) {
    xp[0] = hadd2(xp[0], pi.x); xp[1] = hadd2(xp[1], pi.y); xp[2] = hadd2(xp[2], pi.z); xp[3] = hadd2(xp[3], pi.w);
}
template <int M>
DEVI void xstore(const uint32_t (&xp)[8], uint32_t sb, uint32_t sbw, int ps, uint32_t t16, uint32_t KA) {
    const uint32_t a = SM_XO + M * 2048 + (M < 2 ? (KA & 0xFF) + sbw : (t16 >> 1) + sb);
    sts64(a, xp[0], xp[1]);
    sts64(a + 6144, xp[2], xp[3]);
    asm volatile("st.async.weak.shared::cluster.mbarrier::complete_tx::bytes.v4.b32 [%0], {%1,%2,%3,%4}, [%5];"
                 ::"r"((sb ^ 0x1000000) + SM_PI + (ps & 1) * 12288 + M * 4096 + t16), "r"(xp[4]), "r"(xp[5]), "r"(xp[6]), "r"(xp[7]),
                   "r"((sb ^ 0x1000000) + SM_BAR + BAR_PI + (ps & 1) * 8) : "memory");
}
template <int M>
DEVI void xpark(uint32_t (&xp)[8], const uint4& pi, uint32_t sb, uint32_t sbw, int ps, uint32_t t16, uint32_t KA) {
    xadd(xp, pi);
    xstore<M>(xp, sb, sbw, ps, t16, KA);
}
template <int M>
DEVI void xfinish(float (&xa)[16], uint32_t sb, uint32_t sbw, int ps, uint32_t t16, uint32_t KA) {
    uint32_t xp[8];
    const uint4 pi = xpeer<M>(sb, ps, t16);
    xpack<M>(xp, xa);
    xpark<M>(xp, pi, sb, sbw, ps, t16, KA);
}
DEVI void piwait(uint32_t sb, int p, int ps) { mbar_wait(sb + SM_BAR + BAR_PI + p * 8, ((ps + NPRO + 1) >> 1) & 1); }

DEVI uint32_t par(uint32_t off) { return __popc(off & 0xB2000u) & 1; }
DEVI uint32_t probe(uint32_t lo, uint32_t hi) {
    uint32_t best = 0xFFFFFFFFu, x = 0;
    stg1<0>(lo, hi, 0);
#pragma unroll 1
    for (int r = 0; r < 4; r++) {
        const uint32_t t0 = clk();
        asm volatile("{\n.reg .b64 a;\nmov.b64 a, {%1,%2};\natom.relaxed.gpu.global.add.u32 %0, [a], 2;\n}" : "=r"(x) : "r"(lo), "r"(hi) : "memory");
        if (x == 0xFFFFFFFFu) die(1 << 23);
        best = min(best, clk() - t0);
    }
    return best;
}

DEVI void xload(uint32_t sb, uint32_t u, uint32_t j, int ps, const CUtensorMap* tmx) {
    if (elect()) {
        const uint32_t sg = ps + 4 - (u & 1) + (u >> 1);
        mbar_expect(sb + SM_BAR + BAR_XA, sg < NSEG ? 4096 : 0);
        if (sg < NSEG) tma3d(sb + SM_X + (ps & 1) * 16384 + u * 4096, tmx, sb + SM_BAR + BAR_XA, 0, sg * 32 + (j ^ ((u & 1) * 2 + (u >> 1))) * 8, j * 4);
    }
}
DEVI uint32_t rpage(uint32_t j, int s) { return (s & 3) * 65536 + (j & 1) * 8192 + (((s ^ (s >> 1) ^ j ^ (j >> 1)) & 1) << 12); }

#define RLOAD(a) { m0 = ldg4<XO_R>(a, xhi); n0 = ldg4<XO_R + 16384>(a, xhi); \
                   e0 = ldg1<XO_R + 32768>(((a) & ~0xFFFu) + (((a) & 0xFFF) >> 2), xhi); f0 = ldg1<XO_R + 33792>(((a) & ~0xFFFu) + (((a) & 0xFFF) >> 2), xhi); }
DEVI bool ruse(uint32_t a, const uint4& m0, const uint4& n0, uint32_t e0, uint32_t f0) {
    const uint32_t a0 = hadd2(m0.w, n0.w), b0 = hadd2(e0, f0);
    stsm4(a, hadd2(m0.x, n0.x), hadd2(m0.y, n0.y), hadd2(m0.z, n0.z), __byte_perm(a0, b0, 0x5410));
    return __any_sync(0xFFFFFFFFu, (a0 & b0 & 0x42000000u) != 0x42000000u);
}

#define GST(i) (SM_WO + (i) * 49152)
#define BAR_GF 128
#define BAR_GE (BAR_GF + 64)
#define BAR_GX (BAR_GE + 32)
#define D4(c, i) #c "f"(d[i]), #c "f"(d[i + 1]), #c "f"(d[i + 2]), #c "f"(d[i + 3])
#define D16(c, i) D4(c, i), D4(c, i + 4), D4(c, i + 8), D4(c, i + 12)
DEVI void mwait(uint32_t bar, uint32_t parity) {
    asm volatile("{\n.reg .pred p;\n.reg .b32 c;\nmbarrier.try_wait.parity.shared::cta.b64 p, [%0], %1;\n@p bra.uni D;\nmov.b32 c, 0;\n"
                 "L:\nadd.u32 c, c, 1;\nsetp.gt.u32 p, c, 4194304;\n@p st.shared.u32 [c], c;\n"
                 "mbarrier.try_wait.parity.shared::cta.b64 p, [%0], %1;\n@!p bra.uni L;\nD:\n}" ::"r"(bar), "r"(parity) : "memory");
}
DEVI void wg_ss256t(float (&d)[128], uint64_t da, uint64_t db) {
    asm volatile("wgmma.mma_async.sync.aligned.m64n256k16.f32.bf16.bf16 "
        "{%0,%1,%2,%3,%4,%5,%6,%7,%8,%9,%10,%11,%12,%13,%14,%15,%16,%17,%18,%19,%20,%21,%22,%23,%24,%25,%26,%27,%28,%29,%30,%31,%32,%33,%34,%35,%36,%37,%38,%39,%40,%41,%42,%43,%44,%45,%46,%47,%48,%49,%50,%51,%52,%53,%54,%55,%56,%57,%58,%59,%60,%61,%62,%63,%64,%65,%66,%67,%68,%69,%70,%71,%72,%73,%74,%75,%76,%77,%78,%79,%80,%81,%82,%83,%84,%85,%86,%87,%88,%89,%90,%91,%92,%93,%94,%95,%96,%97,%98,%99,%100,%101,%102,%103,%104,%105,%106,%107,%108,%109,%110,%111,%112,%113,%114,%115,%116,%117,%118,%119,%120,%121,%122,%123,%124,%125,%126,%127}, "
        "%128, %129, 1, 1, 1, 1, 1;"
        : D16(+, 0), D16(+, 16), D16(+, 32), D16(+, 48), D16(+, 64), D16(+, 80), D16(+, 96), D16(+, 112) : "l"(da), "l"(db));
}
template <int O, int KB> DEVI void g_half(float (&d)[64], uint64_t da) {
    const uint64_t db = mkdesc(SB0 + GST(KB & 3) + 16384 + O * 256, 8192, 1024);
#pragma unroll
    for (int k = 0; k < 4; k++)
        asm volatile("wgmma.mma_async.sync.aligned.m64n128k16.f32.bf16.bf16 "
            "{%0,%1,%2,%3,%4,%5,%6,%7,%8,%9,%10,%11,%12,%13,%14,%15,%16,%17,%18,%19,%20,%21,%22,%23,%24,%25,%26,%27,%28,%29,%30,%31,%32,%33,%34,%35,%36,%37,%38,%39,%40,%41,%42,%43,%44,%45,%46,%47,%48,%49,%50,%51,%52,%53,%54,%55,%56,%57,%58,%59,%60,%61,%62,%63}, "
            "%64, %65, 1, 1, 1, 1, 1;"
            : D16(+, 0), D16(+, 16), D16(+, 32), D16(+, 48) : "l"(da + (KB & 3) * 3072 + k * 16), "l"(db + k * 128));
}
DEVI void g_load(uint32_t sb, uint32_t u, uint32_t role, uint32_t kb, uint32_t xlo, uint32_t xhi, const CUtensorMap* tmb) {
    const uint32_t st = kb & 3, bar = sb + SM_BAR + BAR_GF + u * 32 + st * 8, dst = sb + GST(st), k = (role & 1) * 32 + kb;
    mbar_expect(bar, u ? 8192 : 40960);
    bulk_g2s(dst + u * 8192, xlo + XO_OX + ((role >> 3) * 64 + k) * 16384 + u * 8192, xhi, 8192, bar);
    if (u == 0) {
        tma3d(dst + 16384, tmb, bar, 0, k * 64, ((role & 7) ^ 1) * 2);
        tma3d(dst + 32768, tmb, bar, 0, k * 64, (role & 7) * 2);
    }
}
DEVI void g_arrive(uint32_t a, uint32_t xhi) {
    asm volatile("{\n.reg .b64 a;\nmov.b64 a, {%0,%1};\nred.release.gpu.global.add.u32 [a], 1;\n}" ::"r"(a), "r"(xhi) : "memory");
}
template <uint32_t N> DEVI void g_wait(uint32_t a, uint32_t xhi) {
    int it = 0;
    while (ldg1<0>(a, xhi) % N)
        if (++it > SPIN_LIMIT) die(it);
    asm volatile("fence.acq_rel.gpu;\nfence.proxy.async;" ::: "memory");
}
#define GMOV "mov.b32 %0, %1;"
DEVI void g_done(float (&d)[64]) { asm volatile("" : D16(+, 0), D16(+, 16), D16(+, 32), D16(+, 48)::"memory"); }
DEVI void g_main(uint32_t sb, uint32_t w, uint32_t role, const CUtensorMap* tmy) {
    const uint32_t bar = sb + SM_BAR, t16 = threadIdx.x * 16;
    const uint64_t da = (mkdesc(SB0 + GST(0), 128, 1024) & ~((uint64_t)3 << 62)) + (w >> 2) * 512;
    float d[128];
#pragma unroll
    for (int i = 0; i < 128; i++) d[i] = 0.f;
#define GFULL(kb) { mwait(bar + BAR_GF + ((kb) & 3) * 8, ((kb) >> 2) & 1); if (w >= 4) mwait(bar + BAR_GF + 32 + ((kb) & 3) * 8, ((kb) >> 2) & 1); }
#pragma unroll 1
    for (uint32_t kb = 0; kb < 29; kb++) {
        GFULL(kb);
        const uint64_t a = da + (kb & 3) * 3072, b = mkdesc(SB0 + GST(0) + 16384, 8192, 1024) + (kb & 3) * 3072;
        wg_fence();
#pragma unroll
        for (int k = 0; k < 4; k++) wg_ss256t(d, a + k * 16, b + k * 128);
        wg_commit();
        wg_wait<1>();
        if (kb > 0 && elect()) mbar_arrive(bar + BAR_GE + ((kb - 1) & 3) * 8);
    }
    GFULL(29);
    GFULL(30);
    GFULL(31);
    wg_wait<0>();
    float x[64], y[64];
#pragma unroll
    for (int i = 0; i < 64; i++) asm volatile(GMOV : "=f"(x[i]) : "f"(d[i]) : "memory");
    SF();
#pragma unroll
    for (int i = 0; i < 64; i++) asm volatile(GMOV : "=f"(y[i]) : "f"(d[i + 64]) : "memory");
    SF();
    if (elect()) asm volatile("mbarrier.arrive.release.cluster.shared::cluster.b64 _, [%0];" ::"r"((bar ^ 0x1000000) + BAR_GX) : "memory");
    wg_fence();
    g_half<0, 29>(x, da);
    g_half<0, 30>(x, da);
    g_half<0, 31>(x, da);
    wg_commit();
    g_half<64, 29>(y, da);
    wg_commit();
    wg_wait<1>();
    g_done(x);
    mwait(bar + BAR_GX, 0);
#define GSEND(i0) _Pragma("unroll") for (int i = (i0); i < (i0) + 8; i++) \
        asm volatile("st.async.weak.shared::cluster.mbarrier::complete_tx::bytes.v4.f32 [%0], {%1,%2,%3,%4}, [%5];" \
                     ::"r"((sb ^ 0x1000000) + i * 4096 + t16), "f"(x[4 * i]), "f"(x[4 * i + 1]), "f"(x[4 * i + 2]), "f"(x[4 * i + 3]), \
                       "r"((bar ^ 0x1000000) + BAR_GX + 8) : "memory")
    GSEND(0);
    wg_fence();
    g_half<64, 30>(y, da);
    wg_commit();
    GSEND(8);
    wg_fence();
    g_half<64, 31>(y, da);
    wg_commit();
    wg_wait<0>();
    g_done(y);
    mwait(bar + BAR_GX + 8, 0);
    const uint32_t lane = threadIdx.x & 31, o = sb + GST(1) + w * 2048;
#pragma unroll
    for (int i = 0; i < 8; i++) {
        const float4 a = lds128f(sb + 2 * i * 4096 + t16), b = lds128f(sb + (2 * i + 1) * 4096 + t16);
        const float* e = y + 8 * i;
        stsm4(o + (i >> 2) * 49152 + (lane & 15) * 128 + ((((i & 3) * 2 + (lane >> 4)) ^ (lane & 7)) << 4),
              pack2(e[0] + a.x, e[1] + a.y), pack2(e[2] + a.z, e[3] + a.w), pack2(e[4] + b.x, e[5] + b.y), pack2(e[6] + b.z, e[7] + b.w));
        if (i == 3 || i == 7) {
            asm volatile("fence.proxy.async.shared::cta;" ::: "memory");
            __syncwarp();
            if (elect())
                asm volatile("cp.async.bulk.tensor.2d.global.shared::cta.bulk_group [%0, {%2, %3}], [%1];\ncp.async.bulk.commit_group;"
                             ::"l"(tmy), "r"(o + (i >> 2) * 49152), "r"((role & 7) * 128 + (i >> 2) * 64), "r"((role >> 3) * 128 + w * 16) : "memory");
        }
    }
    asm volatile("cp.async.bulk.wait_group.read 0;" ::: "memory");
}

template <bool MAIN>
DEVI void helper_step(uint32_t sb, uint32_t w, uint32_t h, uint32_t j, uint32_t& l16, uint32_t xlo, uint32_t xhi, uint32_t zero, int s,
                      const CUtensorMap* tmx, const CUtensorMap* tmb, const bf16* __restrict__ mem0) {
    const uint32_t u = w - 8, bq = sb + SM_BAR;
    bsync<1, 384>();
    PT(0);
    PDUMP();
    PT(1);
    if (MAIN) {
        if (s == NSEG - 2 && u < 2 && l16 == 0) g_arrive(xlo + XO_TK + 128, xhi);
        __syncwarp();
        const uint32_t ctag = ((s >> 1) & 1) ^ 1;
        const uint32_t av = xlo + ((s & 1) * 32 + h) * 8192 + u * 512;
        mbar_wait(bq + BAR_XA, (s + NPRO) & 1);
        bsync<8, 384>();
        delay_until(clk(), DLY_V);
        PT(4);
        int it = 0;
        bool bad;
        do {
            const uint4 d1 = ldg4<XO_CV>(av + (j ^ 1) * 2048 + l16, xhi);
            const uint4 d2 = ldg4<XO_CV>(av + (j ^ 2) * 2048 + l16, xhi);
            const uint4 d3 = ldg4<XO_CV>(av + (j ^ 3) * 2048 + l16, xhi);
            bad = any_bad(or3(tagx2(d1.x, d1.z, ctag), tagx2(d2.x, d2.z, ctag), tagx2(d3.x, d3.z, ctag)));
            sts128(sb + SM_VS + u * 512 + l16, hadd2(hadd2(d1.x, d2.x), d3.x), hadd2(hadd2(d1.y, d2.y), d3.y), hadd2(hadd2(d1.z, d2.z), d3.z),
                   hadd2(hadd2(d1.w, d2.w), d3.w));
            REFRESH();
            if (++it > SPIN_LIMIT) die(it);
        } while (bad);
        PC(26, it - 1);
    } else {
        if (u == 0) stg2<XO_FL>(xlo + ((s + NPRO) * 128 + h * 4 + j) * 32, xhi, 1, 1);
        if (s == -NPRO) {
            xload(sb, u, j, s, tmx);
#pragma unroll 1
            for (int e = 0; e < 4; e++) sts128(sb + SM_TR + 4096 + e * 2048 + u * 512 + l16, 0, 0, 0, 0);
        }
        if (s == -1) {
#pragma unroll 1
            for (int e = 0; e < 2; e++) {
                const uint32_t d = e * 128 + u * 32 + (l16 >> 4);
                const unsigned short* m0 = (const unsigned short*)mem0 + j * 256 + d;
                uint32_t v[4];
#pragma unroll
                for (int i = 0; i < 4; i++) v[i] = (uint32_t)m0[(2 * i) * DM] | ((uint32_t)m0[(2 * i + 1) * DM] << 16);
                sts128(sb + SM_MEMT + d * 16, v[0], v[1], v[2], v[3]);
            }
        }
        mbar_wait(bq + BAR_XA, (s + NPRO) & 1);
    }
    PT(5);
    barv<5, 384>();
    bsync<3, 384>();
    if (!MAIN) {
        int it = 0;
        while (__any_sync(0xFFFFFFFFu, ldg2<XO_FL>(xlo + ((s + NPRO) * 128 + h * 4) * 32 + ((l16 & 0x30) << 1), xhi).x == 0))
            if (++it > SPIN_LIMIT) die(it);
    }
    if (u < 2) {
        asm volatile("fence.proxy.async.shared::cta;" ::: "memory");
        if (elect()) {
            const uint32_t sg = s + 3 - u;
            if (sg < NSEG) {
                const uint32_t ga = xlo + XO_XG + (((sg & 7) * 32 + h) * 4 + (j ^ (2 * u))) * 6144, sa = sb + SM_XO + u * 6144;
                if (u == 0) bulk_s2g(ga, xhi, sa, 6144);
                else bulk_red(ga, xhi, sa, 6144);
            }
        }
    }
    PT(6);
    uint32_t old = 0;
    if (MAIN && u > 0) asm volatile("{\n.reg .b64 a;\nmov.b64 a, {%1,%2};\natom.relaxed.gpu.global.exch.b32 %0, [a], 0;\n}"
                                    : "=r"(old) : "r"(xlo + XO_R + rpage(j, s + 2) + (u - 1) * 16384 + h * 128 + (l16 >> 2)), "r"(xhi) : "memory");
    PT(7);
    if (MAIN) bsync<7, 384>();
    if (s >= -1 && s + 1 < NSEG && elect()) {
        const uint32_t o = u == 0 ? 0 : 2048;
        mbar_expect(bq + BAR_KV, 6144 - o);
        bulk_g2s(sb + SM_KV + u * 4096 + o, xlo + XO_XG + ((((s + 1) & 7) * 32 + h) * 4 + ((j + u) & 3)) * 6144 + o, xhi, 6144 - o, bq + BAR_KV);
    }
    if (u < 2) {
        asm volatile("cp.async.bulk.wait_group.read 0;" ::: "memory");
        if (elect()) mbar_expect(bq + BAR_PI + ((s & 1) ^ 1) * 8, !MAIN && s == -NPRO ? 0 : 6144);
    }
    PT(8);
    if (MAIN && s + 1 < NSEG) bsync<10, 384>();
    xload(sb, u, j, s + 1, tmx);
    if (MAIN && s == NSEG - 2 && l16 == 0 && (u == 0 || (u == 1 && h < 30))) {
        g_wait<256>(xlo + XO_TK + 128, xhi);
        g_load(sb, u, h * 4 + j, 0, xlo, xhi, tmb);
        g_load(sb, u, h * 4 + j, 1, xlo, xhi, tmb);
    }
    __syncwarp();
    asm volatile("cp.async.bulk.wait_group 0;" ::: "memory");
    if (s >= -1 && s + 1 < NSEG) mbar_wait(bq + BAR_KV, (s + 1) & 1);
    asm volatile("lop3.b32 %0, %0, %1, %2, 0x78;" : "+r"(l16) : "r"(old), "r"(zero));
    PT(15);
}

__global__ void __cluster_dims__(2, 1, 1) __launch_bounds__(384, 1)
chain_kernel(const __grid_constant__ CUtensorMap tmq, const __grid_constant__ CUtensorMap tmk,
             const __grid_constant__ CUtensorMap tmv, const __grid_constant__ CUtensorMap tmo,
             const __grid_constant__ CUtensorMap tmx, const __grid_constant__ CUtensorMap tmb, const __grid_constant__ CUtensorMap tmy,
             const bf16* __restrict__ mem0, const bf16* __restrict__ xg,
             uint32_t xlo, uint32_t xhi, uint32_t zero, int nseg) {
    extern __shared__ __align__(1024) uint8_t smem[];
    if ((smem_u32(smem) & 0xFFFFFF) != SB0) die(1 << 23);
    asm volatile("griddepcontrol.launch_dependents;" ::: "memory");
    const uint32_t w = __reduce_max_sync(0xFFFFFFFFu, threadIdx.x >> 5);
    const uint32_t rk = smem_u32(smem) & 0x1000000;
    const uint32_t sb = __reduce_max_sync(0xFFFFFFFFu, smem_u32(smem));
    const uint32_t bq = sb + SM_BAR, bk = bq + 8, bv = bq + 16, bo = bq + 24;
    uint32_t l16 = __shfl_sync(0xFFFFFFFFu, (threadIdx.x & 31) * 16, threadIdx.x & 31);
    if (threadIdx.x == 0) {
        mbar_init(bq, 1); mbar_init(bk, 1); mbar_init(bv, 1); mbar_init(bo, 2);
        mbar_init(bq + BAR_XA, 4); mbar_init(bq + BAR_KV, 4); mbar_init(bq + BAR_PI, 2); mbar_init(bq + BAR_PI + 8, 2);
        for (int i = 0; i < 14; i++) mbar_init(bq + BAR_GF + i * 8, i < 8 || i == 13 ? 1 : 8);
        mbar_expect(bq + BAR_GX + 8, 65536);
        asm volatile("fence.mbarrier_init.release.cluster;" ::: "memory");
        asm volatile("fence.proxy.async.shared::cta;" ::: "memory");
    }
    if (rk == 0) {
        if (w < 2 && l16 == 0) sts32(sb + SM_ROLE + w * 4, probe(xlo + XO_PB + w * 4096 + blockIdx.x * 16, xhi));
        __syncthreads();
        if (threadIdx.x == 0) {
            uint32_t side = (lds32(sb + SM_ROLE) < lds32(sb + SM_ROLE + 4) ? 0u : 1u) ^ par(XO_PB);
            uint32_t* tk = (uint32_t*)(((uint64_t)xhi << 32) | (xlo + XO_TK));
            uint32_t t = atomicAdd(tk + side, 1u);
            if (t >= 32) {
                uint2 c;
                int it = 0;
                do {
                    c = ldg2<XO_TK>(xlo, xhi);
                    if (++it > SPIN_LIMIT) die(it);
                } while (c.x + c.y != gridDim.x / 2);
                t += (side ? c.x : c.y) - 32;
                side ^= 1;
            }
            sts32(sb + SM_ROLE + 8, t * 4 + side * 2);
        }
    }
    __syncthreads();
    asm volatile("barrier.cluster.arrive.release.aligned;\nbarrier.cluster.wait.acquire.aligned;" ::: "memory");
    uint32_t role;
    asm volatile("ld.shared::cluster.u32 %0, [%1];" : "=r"(role) : "r"(SB0 + SM_ROLE + 8) : "memory");
    role = __reduce_max_sync(0xFFFFFFFFu, role) + (rk >> 24);
    asm volatile("barrier.cluster.arrive.release.aligned;\nbarrier.cluster.wait.acquire.aligned;" ::: "memory");
    if (role >= 128) return;
    const uint32_t h = role >> 2, j = role & 3;

    if (w >= 8) {
        asm volatile("setmaxnreg.dec.sync.aligned.u32 24;");
        if (w == 8) {
            if (elect()) {
                mbar_expect(bq, 65536);
                tma2d(sb + SM_STA, &tmq, bq, h * 128, j * 256);
                tma2d(sb + SM_STA + 32768, &tmq, bq, h * 128 + 64, j * 256);
                mbar_expect(bk, 65536);
                tma2d(sb + SM_STB, &tmk, bk, h * 128, j * 256);
                tma2d(sb + SM_STB + 32768, &tmk, bk, h * 128 + 64, j * 256);
                mbar_expect(bv, (16 - NA + NA1) * 4096);
#pragma unroll 1
                for (int i = 0; i < 32; i++) {
                    const int ks = i >> 1, g = i & 1;
                    if (ks < NA1 || ks >= NA)
                        tma2d((ks < NA ? sb + SM_STC + g * (NA1 * 2048) + ks * 2048 : sb + SM_WV + g * WV_BOX + (ks - NA) * 2048), &tmv, bv, h * 128 + g * 64, j * 256 + ks * 16);
                }
                mbar_expect(bo, 4 * WO_BOX);
#pragma unroll 1
                for (int i = 0; i < 32 - 2 * NB; i++) {
                    const int ks = i >> 2, g = i & 3;
                    tma2d(sb + SM_WO + g * WO_BOX + ks * 2048, &tmo, bo, j * 256 + g * 64, h * 128 + (ks < NPE / 2 ? ks : ks + NB / 2) * 16);
                }
            }
        }
        GSYNC(0);
        bsync<9, 384>();
        if (w == 8) {
            if (elect()) {
                mbar_expect(bo, (NB + NA - NA1) * 4096);
#pragma unroll 1
                for (int i = 2 * NA1; i < 2 * NA; i++) {
                    const int ks = i >> 1, g = i & 1;
                    tma2d(sb + SM_STA + NB * 4096 + g * ((NA - NA1) * 2048) + (ks - NA1) * 2048, &tmv, bo, h * 128 + g * 64, j * 256 + ks * 16);
                }
#pragma unroll 1
                for (int i = 0; i < 2 * NB; i++) {
                    const int ks = i >> 2, g = i & 3;
                    tma2d(sb + SM_STA + g * (NB * 1024) + ks * 2048, &tmo, bo, j * 256 + g * 64, h * 128 + (ks + NPE / 2) * 16);
                }
                asm volatile("cp.async.bulk.prefetch.L2.global [%0], %1;" ::"l"((const char*)xg + role * 32768), "r"(32768) : "memory");
            }
        }
#pragma unroll 1
        for (int s = -NPRO; s < 0; s++) helper_step<false>(sb, w, h, j, l16, xlo, xhi, zero, s, &tmx, &tmb, mem0);
#pragma unroll 1
        for (int s = 0; s < nseg; s++) helper_step<true>(sb, w, h, j, l16, xlo, xhi, zero, s, &tmx, &tmb, mem0);
        piwait(sb, 0, nseg - 2);
        bsync<9, 384>();
        GSYNC(1);
        if (w < 10 && l16 == 0) {
            uint32_t kb = 2;
            if (w == 9) {
                g_arrive(xlo + XO_TK + 192, xhi);
                if (h >= 30) { g_wait<128>(xlo + XO_TK + 192, xhi); kb = 0; }
            }
            asm volatile("fence.proxy.async.shared::cta;" ::: "memory");
#pragma unroll 1
            for (; kb < 32; kb++) {
                if (kb >= 4) mbar_wait(bq + BAR_GE + (kb & 3) * 8, ((kb >> 2) & 1) ^ 1);
                g_load(sb, w - 8, role, kb, xlo, xhi, &tmb);
            }
        }
    } else {
        asm volatile("setmaxnreg.inc.sync.aligned.u32 240;");
        uint32_t Wq[16][4], Wk[16][4], Wv[NA][4], Wo[NB > 0 ? NB : 1][4];
        uint32_t t16, KA, KB, KC, KD;
        {
            const uint32_t lane = l16 >> 4, g = lane >> 2, t = lane & 3;
            const uint32_t rw = (((lane >> 4) & 1) * 8 + (lane & 7)) * 128u;
            const uint32_t off = rw + ((((w & 3) * 2 + ((lane >> 3) & 1)) ^ (lane & 7)) << 4);
            const uint32_t offo = rw + ((((w & 1) * 4 + ((lane >> 3) & 1)) ^ (lane & 7)) << 4);
            const uint32_t r = 2 * (t & 1) + (g >> 2);
            const uint32_t mk0 = t < 2 ? 0 : (r == 0 ? 2 * g > w : j + r < 4), mk1 = t < 2 ? 0 : (r == 0 ? 2 * g + 1 > w : j + r < 4);
            t16 = __shfl_sync(0xFFFFFFFFu, w * 512 + l16, lane);
            KA = __shfl_sync(0xFFFFFFFFu, (w * 512 + t * 64 + g * 8) | ((w * 512 + (g & 1) * 256 + (g >> 1) * 64 + t * 16) << 16), lane);
            KB = __shfl_sync(0xFFFFFFFFu, ((w >> 2) * WV_BOX + off) | mk0 | (mk1 << 1) |
                                              ((w * 256 + (g >> 2) * 4096 + (g & 3) * 64 + t * 16) << 16), lane);
            KC = __shfl_sync(0xFFFFFFFFu, ((lane & 7) * 1280 + (lane >> 3) * 128 + ((w ^ (lane & 7)) << 4)) | (((t >> 1) * 16 + g * 2) << 16) | ((t * 64 + g * 8) << 24), lane);
            KD = __shfl_sync(0xFFFFFFFFu, ((w >> 1) * WO_BOX + offo) | (((lane & 7) * 208 + (lane >> 3) * 16) << 16), lane);
            mbar_wait(bq, 0);
#pragma unroll
            for (int ks = 0; ks < 16; ks++) ldsm4t(Wq[ks], sb + SM_STA + (w >> 2) * 32768 + off + ks * 2048);
            asm volatile("fence.proxy.async.shared::cta;" ::: "memory");
            barv<9, 384>();
            mbar_wait(bk, 0);
#pragma unroll
            for (int ks = 0; ks < 16; ks++) ldsm4t(Wk[ks], sb + SM_STB + (w >> 2) * 32768 + off + ks * 2048);
            mbar_wait(bv, 0);
#pragma unroll
            for (int ks = 0; ks < NA1; ks++) ldsm4t(Wv[ks], sb + SM_STC + (w >> 2) * (NA1 * 2048) + off + ks * 2048);
            mbar_wait(bo, 0);
#pragma unroll
            for (int ks = NA1; ks < NA; ks++) ldsm4t(Wv[ks], sb + SM_STA + NB * 4096 + (w >> 2) * ((NA - NA1) * 2048) + off + (ks - NA1) * 2048);
#pragma unroll
            for (int i = 0; i < NB; i++) ldsm4t(Wo[i], sb + SM_STA + (w >> 1) * (NB * 1024) + (offo ^ ((i & 1) << 5)) + (i >> 1) * 2048);
            asm volatile("fence.proxy.async.shared::cta;" ::: "memory");
        }
        const uint32_t ONES = 0x3F803F80u;
#define UNI(x) __reduce_max_sync(0xFFFFFFFFu, x)
        uint32_t swi = UNI((uint32_t)((uint64_t)smem >> 32));
        const uint32_t sbw = UNI(sb + w * 256), sbm = UNI(sb - w * 512), sbs = UNI(sb + w * 768), sbp = UNI(sb + w * 208);
#define OPQALL() { OPQ(t16); OPQ(KA); OPQ(KB); OPQ(KC); OPQ(KD); }
        bsync<1, 384>();
        barv<3, 384>();
        bsync<5, 384>();
#pragma unroll 1
        for (int s2 = 1 - NPRO; s2 < 0; s2 += 2)
#pragma unroll
        for (int p = 0; p < 2; p++) {
            const int s = s2 + p;
            float xa[16], xb[16];
            wg_fence();
            XMMA(0, 32 - NA);
            XMMA(32 - NA, 32);
            piwait(sb, p, s - 2);
            wg_wait<1>();
            xfinish<0>(xa, sb, sbw, p ^ 1, t16, KA);
            wg_fence();
            XMMA(32, 48);
            bsync<1, 384>();
            wg_wait<1>();
            xfinish<2>(xb, sb, sbw, p ^ 1, t16, KA);
            wg_wait<0>();
            xfinish<1>(xa, sb, sbw, p ^ 1, t16, KA);
            barv<3, 384>();
            bsync<5, 384>();
            OPQALL();
        }
        const uint32_t cb0 = (h >> 1) * 32768 + (j & 1) * 16384 + (h & 1) * 8192;
        const uint32_t cb = xlo + cb0 + ((par(cb0) ^ (j >> 1) ^ CFAR) << 12);
        const uint32_t uox = xlo + XO_OX + (h * 2 + (w >> 2)) * 16384 + j * 1024 + (w & 3) * 256 - w * 128;
        float ox[4];
        float4 dn;
#define OXSTORE(s) asm volatile("{\n.reg .b64 a;\nmov.b64 a, {%0,%1};\nst.global.u32 [a], %2;\nst.global.u32 [a+128], %3;\n}" \
                                ::"r"(uox + (t16 >> 2) + ((s) >> 2) * (1u << 20) + ((s) & 3) * 4096), "r"(xhi), \
                                  "r"(pack2(ox[0] * dn.y, ox[1] * dn.w)), "r"(pack2(ox[2] * dn.y, ox[3] * dn.w)) : "memory")
#pragma unroll 1
        for (int s2 = 0;; s2 += 2)
#pragma unroll
        for (int p = 0; p < 2; p++) {
            const int s = s2 + p;
            const uint32_t ctag = ((s2 >> 1) & 1) ^ 1;
            const uint32_t hb = cb ^ (p * 0x81000), rb = xlo + rpage(j, s);
            uint4 k0, k1;
            uint32_t qx0, qx1, ov0, ov1;
            {
                float xa[16], xb[16];
                uint4 m0, n0;
                uint32_t e0, f0, a = xlo + rpage(j, s - 1) + t16;
                uint32_t xp[8];
                wg_fence();
                XMMA(0, 6);
                SF();
                piwait(sb, p, s - 2);
                uint4 pi = xpeer<0>(sb, p ^ 1, t16);
                SF();
                wg_fence();
                XMMA(6, RPOS);
                XMMA(RPOS, RPOS + 4);
                wg_wait<1>();
                SF();
                PT(11);
                RLOAD(a);
                SF();
#define QPOS (RPOS >= 32 - NA ? RPOS : RPOS + 4 >= 32 - NA ? RPOS + 4 : 32 - NA)
                if (QPOS > RPOS) {
                    wg_fence();
                    if (QPOS > RPOS + 4) XMMA(RPOS + 4, QPOS);
                    XMMA(QPOS, QPOS + 4);
                    wg_wait<1>();
                    SF();
                }
                xpack<0>(xp, xa);
                xpark<0>(xp, pi, sb, sbw, p ^ 1, t16, KA);
                pi = xpeer<2>(sb, p ^ 1, t16);
                SF();
                if (QPOS + 4 < 32) {
                    wg_fence();
                    XMMA(QPOS + 4, 32);
                    SF();
                }
                wg_wait<0>();
                xpack<2>(xp, xb);
                xpark<2>(xp, pi, sb, sbw, p ^ 1, t16, KA);
                SF();
                PT(12);
                if (p == 1 || s2 > 0) {
                    int it = 0;
                    while (ruse(sb + SM_MEMT + t16, m0, n0, e0, f0)) {
                        OPQ(a);
                        RLOAD(a);
                        if (++it > SPIN_LIMIT) die(it);
                    }
                    PC(22, it + 1);
                }
                PT(13);
                OPQ(KA); OPQ(t16);
                uint32_t acw = hb + (KA & 0xFFFF), ahi = xhi, tg = ctag;
                OPQ(acw); OPQ(ahi); OPQ(tg);
                SF();
                bsync<1, 384>();
                PT(0);
                uint32_t b[8][4];
#pragma unroll
                for (int i = 0; i < 8; i++) {
                    const int pp = i < 2 ? i : i ^ 1;
                    ldsm4t(b[pp], sbm + SM_MEMT + t16 + pp * 512);
                    if (i < 7) MF();
                }
                if (ASF) SF();
                float q[4], k[4];
                const uint32_t aWv = sb + SM_WV + (KB & 0xFFF0);
                uint32_t wv[16 - NA > 0 ? 16 - NA : 1][4];
#define WVLD(n0, n1) _Pragma("unroll") for (int n = (n0); n < (n1) && n < 16 - NA; n++) ldsm4t(wv[n], aWv + n * 2048)
#pragma unroll
                for (int ks = 0; ks < 16; ks++) {
                    const uint32_t b0 = b[ks >> 1][(ks & 1) * 2], b1 = b[ks >> 1][(ks & 1) * 2 + 1];
                    if (ks == 0) {
                        mma16z(q, Wq[0][0], Wq[0][1], Wq[0][2], Wq[0][3], b0, b1);
                        mma16z(k, Wk[0][0], Wk[0][1], Wk[0][2], Wk[0][3], b0, b1);
                    } else {
                        mma16(q, Wq[ks][0], Wq[ks][1], Wq[ks][2], Wq[ks][3], b0, b1);
                        mma16(k, Wk[ks][0], Wk[ks][1], Wk[ks][2], Wk[ks][3], b0, b1);
                    }
                    if (ks == 10 && VPF) { SF(); WVLD(0, VPF); }
                }
                const uint32_t oq0 = settag(pack2(q[0], q[2]), tg), oq1 = settag(pack2(q[1], q[3]), tg);
                const uint32_t ok0 = pack2(k[0], k[2]), ok1 = pack2(k[1], k[3]);
                stg2<XO_CQK>(acw, ahi, oq0, ok0);
                stg2<XO_CQK + 256>(acw, ahi, oq1, ok1);
                SF();
                PT(1);
                int nl = VPF;
#pragma unroll
                for (int rd = 0; rd < 8; rd++) {
                    const int pp = (VORD >> (28 - 4 * rd)) & 7;
                    const uint32_t* a = 2 * pp < NA ? Wv[2 * pp < NA ? 2 * pp : 0] : wv[2 * pp < NA ? 0 : 2 * pp - NA];
                    const uint32_t* c = 2 * pp < NA ? Wv[2 * pp < NA ? 2 * pp + 1 : 0] : wv[2 * pp < NA ? 0 : 2 * pp + 1 - NA];
                    if (rd == 0) {
                        mma16z(q, a[0], a[1], a[2], a[3], b[pp][0], b[pp][1]);
                        mma16z(k, c[0], c[1], c[2], c[3], b[pp][2], b[pp][3]);
                    } else {
                        mma16(q, a[0], a[1], a[2], a[3], b[pp][0], b[pp][1]);
                        mma16(k, c[0], c[1], c[2], c[3], b[pp][2], b[pp][3]);
                    }
                    if (rd == 0) {
                        SF();
                        OPQ(swi);
                        asm volatile("{\n.reg .b64 a;\nmov.b64 a, {%0,%1};\nst.v2.u32 [a], {%2,%3};\nst.v2.u32 [a+256], {%4,%5};\n}"
                                     ::"r"((KA & 0xFFF) + (sb ^ 0x1000000) + SM_TR + 4096 + p * 4096), "r"(swi), "r"(oq0), "r"(ok0), "r"(oq1), "r"(ok1) : "memory");
                        sts64(sb + SM_TR + (KA & 0xFFF), oq0, ok0);
                        sts64(sb + SM_TR + (KA & 0xFFF) + 256, oq1, ok1);
                    }
                    if (rd == 4) KEEP(t16, oq0, oq1, ok0, ok1);
                    if (nl < 16 - NA) {
                        SF();
                        WVLD(nl, nl + (2 * pp < NA ? 1 : 3));
                        nl += 2 * pp < NA ? 1 : 3;
                    } else if (nl < 32) {
                        SF();
                        k0 = lds128(sb + SM_KV + 2048 + (KB >> 16));
                        nl = 32;
                    } else if (nl == 32) {
                        SF();
                        k1 = lds128(sb + SM_KV + 10240 + (KB >> 16));
                        const uint4 qq = lds128(sbw + SM_KV + ((KA >> 16) & 0xFF));
                        qx0 = (t16 & 64) ? qq.y : qq.x;
                        qx1 = (t16 & 64) ? qq.w : qq.z;
                        nl = 33;
                    }
                }
                ov0 = pack2(q[0] + k[0], q[1] + k[1]);
                ov1 = pack2(q[2] + k[2], q[3] + k[3]);
                stg2<XO_CV>(xlo + ((p * 32 + h) * 4 + j) * 2048 + (t16 >> 1), xhi, settag(ov0, tg), ov1);
                barv<8, 384>();
            }
            OPQ(t16);
            SF();
            PT(2);
            PDUMP();
            {
                const uint32_t a0 = sb + SM_KV;
#define CLOADG() { c2 = ldg4<XO_CQK>((hb ^ 0x1000) + (KA >> 16), xhi); c3 = ldg4<XO_CQK>((hb ^ 0x5000) + (KA >> 16), xhi); }
#define CLOADS() { c0 = lds128(sb + SM_TR + (KA >> 16)); c1 = lds128(sb + SM_TR + 4096 + p * 4096 + (KA >> 16)); }
                uint4 c0, c1, c2, c3, pi;
                float xa[16], xb[16];
                uint32_t xp[8];
                wg_fence();
                XMMA(32, 32 + CPOS);
                XMMA(32 + CPOS, 36 + CPOS);
                wg_wait<1>();
                SF();
                CLOADG();
                SF();
                CLOADS();
                if (KPOS == 0) pi = xpeer<1>(sb, p ^ 1, t16);
                SF();
                wg_fence();
                XMMA(36 + CPOS, 48);
                SF();
                const uint32_t ka[4] = {k0.x, k0.y, k0.z, k0.w}, kb[4] = {k1.x, k1.y, k1.z, k1.w};
                const uint32_t aSp = sb + SM_SP + (KC & 0xFFFF);
                PT(3);
#define SCORES(FIRST) { \
                    const uint32_t qA = hadd2(hadd2(c0.x, c1.x), hadd2(c2.x, c3.x)), qB = hadd2(hadd2(c0.z, c1.z), hadd2(c2.z, c3.z)); \
                    const uint32_t kA = hadd2(hadd2(c0.y, c1.y), hadd2(c2.y, c3.y)), kB = hadd2(hadd2(c0.w, c1.w), hadd2(c2.w, c3.w)); \
                    bad = any_bad(or3(tagx2(c1.x, c1.z, ctag), tagx2(c2.x, c2.z, ctag), tagx2(c3.x, c3.z, ctag))); \
                    float sa[4], sb_[4], sc[4], sd[4], se[4]; \
                    if (FIRST) { SF(); wg_wait<0>(); } \
                    mma16z(sa, ka[0], ka[1], ka[2], ka[3], qA, qB); \
                    mma16z(sb_, kb[0], kb[1], kb[2], kb[3], qA, qB); \
                    mma16z(sc, qA, qx0, qB, qx1, kA, kB); \
                    if (FIRST) { \
                        xpack<1>(xp, xa); \
                        if (KPOS == 0) { xadd(xp, pi); xstore<1>(xp, sb, sbw, p ^ 1, t16, KA); barv<3, 384>(); } \
                        mma16z(sd, ka[0], ka[1], ka[2], ka[3], qx0, qx1); \
                        mma16z(se, kb[0], kb[1], kb[2], kb[3], qx0, qx1); \
                    } \
                    stsm4t(aSp, pack2(sa[0], sa[1]), pack2(sa[2], sa[3]), pack2(sb_[0], sb_[1]), pack2(sb_[2], sb_[3])); \
                    stsm2(aSp + 1024, pack2(sc[0], sc[1]), pack2(sc[2], sc[3])); \
                    if (FIRST) { \
                        stsm4t(aSp + 512, pack2(sd[0], sd[1]), pack2(sd[2], sd[3]), pack2(se[0], se[1]), pack2(se[2], se[3])); \
                        if (KPOS == 0) { KEEP(KD, xp[0], xp[1], xp[2], xp[3]); KEEP(KD, xp[4], xp[5], xp[6], xp[7]); } \
                    } }
                int it = 0;
                bool bad;
                SCORES(true);
                while (__builtin_expect(bad, 0)) {
                    OPQ(KA);
                    CLOADG();
                    CLOADS();
                    SCORES(false);
                    if (++it > SPIN_LIMIT) die(it);
                }
                PC(25, it);
                PT(4);
                bsync<4, 256>();
                uint32_t wo[16 - NB][4];
                const uint32_t aWo = sb + SM_WO + (KD & 0xFFFF), aWo1 = sb + SM_WO + ((KD & 0xFFFF) ^ 32);
#define WOLD(n0, n1) _Pragma("unroll") for (int n = (n0); n < (n1) && n < 16 - NB; n++) ldsm4t(wo[n], ((n & 1) ? aWo1 : aWo) + (n >> 1) * 2048)
                const bool hi = (t16 & 32) != 0;
                const uint32_t t8 = t16 >> 1;
                uint2 v0, v1, v2, v3;
                uint32_t es;
                {
                    uint32_t am[4], ax[4], a4[2];
                    const uint32_t aSr = sbs + SM_SP + t16;
                    ldsm4t(am, aSr);
                    ldsm4t(ax, aSr + 512);
                    ldsm2t(a4, aSr + 1024);
                    MF();
                    if (KPOS == 1) pi = xpeer<1>(sb, p ^ 1, t16);
                    const uint32_t se = (t16 & 128) ? 0u : ONES, so = se ^ ONES;
                    float hm[4], hx[4], h4[4];
                    mma16z(hm, am[0], am[1], am[2], am[3], se, so);
                    mma16z(hx, ax[0], ax[1], ax[2], ax[3], se, so);
                    mma8z(h4, a4[0], a4[1], ONES);
                    SF();
                    if (KPOS == 1) { xpark<1>(xp, pi, sb, sbw, p ^ 1, t16, KA); barv<3, 384>(); }
                    v0 = lds64(a0 + 4096 + t8); v1 = lds64(a0 + 8192 + t8); v2 = lds64(a0 + 12288 + t8); v3 = lds64(a0 + 16384 + t8);
                    WOLD(0, PF2);
                    float s0 = hi ? hx[0] : hm[0], s1 = hi ? hx[2] : hm[2];
                    const float s2 = hi ? h4[2] : h4[0];
                    s0 = (KB & 1) ? -1.0e9f * 11.313708499f : s0;
                    s1 = (KB & 2) ? -1.0e9f * 11.313708499f : s1;
                    int mi = __float_as_int(fmaxf(fmaxf(s0, s2), s1));
                    mi ^= (mi >> 31) & 0x7FFFFFFF;
                    const int mm = __reduce_max_sync(0xFFFFFFFFu, hi ? (int)0x80000000 : mi), mx = __reduce_max_sync(0xFFFFFFFFu, hi ? mi : (int)0x80000000);
                    SF();
                    WOLD(PF2, PF3);
                    SF();
                    mi = hi ? mx : mm;
                    mi ^= (mi >> 31) & 0x7FFFFFFF;
                    const float c2_ = 0.08838834764831845f * 1.4426950408889634f;
                    const float mc = __int_as_float(mi) * c2_;
                    const float e0 = ex2(fmaf(s0, c2_, -mc)), e1 = ex2(fmaf(s1, c2_, -mc)), e2 = ex2(fmaf(s2, c2_, -mc));
                    sts32(sbp + SM_P + (KC >> 25), pack2(e0, e1));
                    sts16(sbp + SM_P + 128 + ((KC >> 16) & 0xFF), pack2(e2, e2));
                    es = __float_as_uint(fmaf(e2, 0.5f, e0 + e1) + 64.f);
                }
                const uint32_t sm = __reduce_add_sync(0xFFFFFFFFu, hi ? 0u : es), sx = __reduce_add_sync(0xFFFFFFFFu, hi ? es : 0u);
                const uint32_t aPr = sb + SM_P + (KD >> 16);
                PT(5);
                bsync<5, 384>();
                uint32_t pm[4], px[4], p4[2];
                ldsm4(pm, aPr);
                MF();
                const uint2 vs = lds64(sb + SM_VS + t8);
                MF();
                ldsm2(p4, aPr + 128);
                MF();
                ldsm4(px, aPr + 64);
                MF();
                sts32f(sb + SM_DN + w * 8 + ((t16 >> 3) & 4), rcp(__uint_as_float((hi ? sx : sm) - 15u * 0x42800000u) - 64.f));
                MF();
                WOLD(PF3, NPF);
                const uint32_t vm0 = hadd2(ov0, vs.x), vm1 = hadd2(ov1, vs.y);
                float oa[4], ob[4];
                mma16z(oa, v0.x, v0.y, v1.x, v1.y, pm[0], pm[1]);
                mma16z(ob, v2.x, v2.y, v3.x, v3.y, pm[2], pm[3]);
                mma8(oa, vm0, vm1, p4[0]);
                stsm2(sbw + SM_OT + (t16 & 511), pack2(oa[0] + ob[0], oa[1] + ob[1]), pack2(oa[2] + ob[2], oa[3] + ob[3]));
                PT(6);
                SF();
                bsync<6, 256>();
                mma16z(ox, v0.x, v0.y, v1.x, v1.y, px[0], px[1]);
                uint32_t b[4][4];
#define OTLD(pp) ldsm4t(b[pp], sbm + SM_OT + t16 + (pp) * 512)
                OTLD(0);
                MF();
                OTLD(1);
                barv<7, 384>();
                mma16(ox, v2.x, v2.y, v3.x, v3.y, px[2], px[3]);
                mma8(ox, vm0, vm1, p4[1]);
                if (p == 1 && s + 1 == nseg) goto done;
                SF();
                uint32_t ar, ae, ahi = xhi;
                float r[2][4];
#pragma unroll
                for (int ks = 0; ks < 8; ks++) {
                    if (ks == 0) WOLD(NPF, NPF + WPF);
                    if (ks == OPOS) { OTLD(2); MF(); }
                    if (ks == OPOS + 2) { OTLD(3); MF(); }
                    if (ks > 0) WOLD(NPF + WPF + 2 * (ks - 1), NPF + WPF + 2 * ks);
                    if (ks == 5) {
                        OPQ(t16);
                        ar = rb + (h & 1) * 16384 + t16; ae = rb + (h & 1) * 1024 + (t16 >> 2);
                        OPQ(ar); OPQ(ahi); OPQ(ae);
                        dn = lds128f(sb + SM_DN + (t16 & 48));
                    }
#pragma unroll
                    for (int mt = 0; mt < 2; mt++) {
                        const int i = ks * 2 + mt;
                        const uint32_t* a = i < NPE ? wo[i < NPE ? i : 0] : i < NPE + NB ? Wo[i < NPE + NB ? i - NPE : 0] : wo[i < NPE + NB ? 0 : i - NB];
                        if (i < 2) mma16z(r[mt], a[0], a[1], a[2], a[3], b[ks >> 1][2 * (ks & 1)], b[ks >> 1][2 * (ks & 1) + 1]);
                        else mma16(r[mt], a[0], a[1], a[2], a[3], b[ks >> 1][2 * (ks & 1)], b[ks >> 1][2 * (ks & 1) + 1]);
                    }
                    if (NPF + WPF + 2 * ks < 16 - NB || ks < 5) SF();
                }
                const float r0 = dn.x, r1 = dn.z;
                asm volatile("{\n.reg .b64 a;\nmov.b64 a, {%0,%2};\nred.relaxed.gpu.global.add.noftz.v4.bf16x2 [a], {%3,%4,%5,%6};\n"
                             "mov.b64 a, {%1,%2};\nred.relaxed.gpu.global.add.noftz.bf16x2 [a+32768], %7;\n}"
                             ::"r"(ar), "r"(ae), "r"(ahi), "r"(pack2(r[0][0] * r0, r[0][1] * r1)), "r"(pack2(r[0][2] * r0, r[0][3] * r1)),
                               "r"(pack2(r[1][0] * r0, r[1][1] * r1)), "r"(pack2(r[1][2] * r0, 1.f)), "r"(pack2(r[1][3] * r1, 1.f)) : "memory");
                barv<10, 384>();
            }
            SF();
            PT(10);
            OXSTORE(s);
            OPQALL();
        }
    done:
        dn = lds128f(sb + SM_DN + (t16 & 48));
        OXSTORE(nseg - 1);
        asm volatile("fence.proxy.async.shared::cta;" ::: "memory");
        barv<9, 384>();
        g_main(sb, w, role, &tmy);
    }
}

template <int SC> DEVI void wg_rs128t(float (&d)[64], const uint32_t (&a)[4], uint64_t db) {
    if (SC) asm volatile("wgmma.mma_async.sync.aligned.m64n128k16.f32.bf16.bf16 "
        "{%0,%1,%2,%3,%4,%5,%6,%7,%8,%9,%10,%11,%12,%13,%14,%15,%16,%17,%18,%19,%20,%21,%22,%23,%24,%25,%26,%27,%28,%29,%30,%31,%32,%33,%34,%35,%36,%37,%38,%39,%40,%41,%42,%43,%44,%45,%46,%47,%48,%49,%50,%51,%52,%53,%54,%55,%56,%57,%58,%59,%60,%61,%62,%63}, "
        "{%64,%65,%66,%67}, %68, 1, 1, 1, 1;"
        : D4(+, 0), D4(+, 4), D4(+, 8), D4(+, 12), D4(+, 16), D4(+, 20), D4(+, 24), D4(+, 28), D4(+, 32), D4(+, 36), D4(+, 40), D4(+, 44), D4(+, 48), D4(+, 52), D4(+, 56), D4(+, 60) : "r"(a[0]), "r"(a[1]), "r"(a[2]), "r"(a[3]), "l"(db));
    else asm volatile("wgmma.mma_async.sync.aligned.m64n128k16.f32.bf16.bf16 "
        "{%0,%1,%2,%3,%4,%5,%6,%7,%8,%9,%10,%11,%12,%13,%14,%15,%16,%17,%18,%19,%20,%21,%22,%23,%24,%25,%26,%27,%28,%29,%30,%31,%32,%33,%34,%35,%36,%37,%38,%39,%40,%41,%42,%43,%44,%45,%46,%47,%48,%49,%50,%51,%52,%53,%54,%55,%56,%57,%58,%59,%60,%61,%62,%63}, "
        "{%64,%65,%66,%67}, %68, 0, 1, 1, 1;"
        : D4(=, 0), D4(=, 4), D4(=, 8), D4(=, 12), D4(=, 16), D4(=, 20), D4(=, 24), D4(=, 28), D4(=, 32), D4(=, 36), D4(=, 40), D4(=, 44), D4(=, 48), D4(=, 52), D4(=, 56), D4(=, 60) : "r"(a[0]), "r"(a[1]), "r"(a[2]), "r"(a[3]), "l"(db));
}
template <int SC> DEVI void wg_rs64t(float (&d)[32], const uint32_t (&a)[4], uint64_t db) {
    if (SC) asm volatile("wgmma.mma_async.sync.aligned.m64n64k16.f32.bf16.bf16 "
        "{%0,%1,%2,%3,%4,%5,%6,%7,%8,%9,%10,%11,%12,%13,%14,%15,%16,%17,%18,%19,%20,%21,%22,%23,%24,%25,%26,%27,%28,%29,%30,%31}, "
        "{%32,%33,%34,%35}, %36, 1, 1, 1, 1;"
        : D4(+, 0), D4(+, 4), D4(+, 8), D4(+, 12), D4(+, 16), D4(+, 20), D4(+, 24), D4(+, 28) : "r"(a[0]), "r"(a[1]), "r"(a[2]), "r"(a[3]), "l"(db));
    else asm volatile("wgmma.mma_async.sync.aligned.m64n64k16.f32.bf16.bf16 "
        "{%0,%1,%2,%3,%4,%5,%6,%7,%8,%9,%10,%11,%12,%13,%14,%15,%16,%17,%18,%19,%20,%21,%22,%23,%24,%25,%26,%27,%28,%29,%30,%31}, "
        "{%32,%33,%34,%35}, %36, 0, 1, 1, 1;"
        : D4(=, 0), D4(=, 4), D4(=, 8), D4(=, 12), D4(=, 16), D4(=, 20), D4(=, 24), D4(=, 28) : "r"(a[0]), "r"(a[1]), "r"(a[2]), "r"(a[3]), "l"(db));
}
template <int SC> DEVI void wg_rs40(float (&d)[20], const uint32_t (&a)[4], uint64_t db) {
    if (SC) asm volatile("wgmma.mma_async.sync.aligned.m64n40k16.f32.bf16.bf16 "
        "{%0,%1,%2,%3,%4,%5,%6,%7,%8,%9,%10,%11,%12,%13,%14,%15,%16,%17,%18,%19}, "
        "{%20,%21,%22,%23}, %24, 1, 1, 1, 0;"
        : D4(+, 0), D4(+, 4), D4(+, 8), D4(+, 12), D4(+, 16) : "r"(a[0]), "r"(a[1]), "r"(a[2]), "r"(a[3]), "l"(db));
    else asm volatile("wgmma.mma_async.sync.aligned.m64n40k16.f32.bf16.bf16 "
        "{%0,%1,%2,%3,%4,%5,%6,%7,%8,%9,%10,%11,%12,%13,%14,%15,%16,%17,%18,%19}, "
        "{%20,%21,%22,%23}, %24, 0, 1, 1, 0;"
        : D4(=, 0), D4(=, 4), D4(=, 8), D4(=, 12), D4(=, 16) : "r"(a[0]), "r"(a[1]), "r"(a[2]), "r"(a[3]), "l"(db));
}
template <int SC> DEVI void wg_rs8(float (&d)[4], const uint32_t (&a)[4], uint64_t db) {
    if (SC) asm volatile("wgmma.mma_async.sync.aligned.m64n8k16.f32.bf16.bf16 "
        "{%0,%1,%2,%3}, "
        "{%4,%5,%6,%7}, %8, 1, 1, 1, 0;"
        : D4(+, 0) : "r"(a[0]), "r"(a[1]), "r"(a[2]), "r"(a[3]), "l"(db));
    else asm volatile("wgmma.mma_async.sync.aligned.m64n8k16.f32.bf16.bf16 "
        "{%0,%1,%2,%3}, "
        "{%4,%5,%6,%7}, %8, 0, 1, 1, 0;"
        : D4(=, 0) : "r"(a[0]), "r"(a[1]), "r"(a[2]), "r"(a[3]), "l"(db));
}
template <int SC> DEVI void wg_ss64a(float (&d)[32], uint64_t da, uint64_t db) {
    if (SC) asm volatile("wgmma.mma_async.sync.aligned.m64n64k16.f32.bf16.bf16 "
        "{%0,%1,%2,%3,%4,%5,%6,%7,%8,%9,%10,%11,%12,%13,%14,%15,%16,%17,%18,%19,%20,%21,%22,%23,%24,%25,%26,%27,%28,%29,%30,%31}, "
        "%32, %33, 1, 1, 1, 1, 0;"
        : D4(+, 0), D4(+, 4), D4(+, 8), D4(+, 12), D4(+, 16), D4(+, 20), D4(+, 24), D4(+, 28) : "l"(da), "l"(db));
    else asm volatile("wgmma.mma_async.sync.aligned.m64n64k16.f32.bf16.bf16 "
        "{%0,%1,%2,%3,%4,%5,%6,%7,%8,%9,%10,%11,%12,%13,%14,%15,%16,%17,%18,%19,%20,%21,%22,%23,%24,%25,%26,%27,%28,%29,%30,%31}, "
        "%32, %33, 0, 1, 1, 1, 0;"
        : D4(=, 0), D4(=, 4), D4(=, 8), D4(=, 12), D4(=, 16), D4(=, 20), D4(=, 24), D4(=, 28) : "l"(da), "l"(db));
}

#define G_ROWS 514
__device__ uint4 g_G[64 * G_ROWS * 8];
__device__ uint4 g_GN[64 * 8];
__device__ uint4 g_WN[1152];
#define FS_F2 196608
#define FS_TB (FS_F2 + 8192)
#define FS_NQ (FS_TB + 16384)
#define FS_BAR (FS_NQ + 128)
#define FS_NY (FS_NQ + 1024 + 128)
#define FS_TOTAL (FS_NQ + 3072)
#define F_THREADS 512

DEVI uint32_t cis(int j) {
    const float a = fmaf(__uint_as_float((((j + 1024) << 12) & 0x7FF000) | 0x3F800000), 6.283185307179586f, -9.42477796076938f);
    return pack2(__cosf(a), __sinf(a));
}
DEVI uint32_t cos2(int j0, int j1) {
    const float f = 6.283185307179586f / 2048.f;
    return pack2(__cosf((float)(((j0 + 1024) & 2047) - 1024) * f), __cosf((float)(((j1 + 1024) & 2047) - 1024) * f));
}
DEVI void twid(int j, float& c, float& s) {
    const float a = (float)(((j + 512) & 1023) - 512) * (6.283185307179586f / 1024.f);
    c = __cosf(a) * (1.f / 1024.f);
    s = __sinf(a) * (1.f / 1024.f);
}
template <bool B> struct Bool { static constexpr bool v = B; };
DEVI uint32_t opq(uint32_t& x, uint32_t zero) { OPQ(x); return x; }
DEVI uint32_t tidx() { uint32_t r; asm volatile("mov.u32 %0, %%tid.x;" : "=r"(r)); return r; }
DEVI void tma4d(uint32_t dst, const CUtensorMap* tm, uint32_t bar, int c0, int c1, int c2, int c3) {
    asm volatile("cp.async.bulk.tensor.4d.shared::cluster.global.mbarrier::complete_tx::bytes [%0], [%1, {%3, %4, %5, %6}], [%2];"
                 ::"r"(dst), "l"(tm), "r"(bar), "r"(c0), "r"(c1), "r"(c2), "r"(c3) : "memory");
}
DEVI void tma3s(const CUtensorMap* tm, uint32_t src, int c0, int c1, int c2) {
    asm volatile("cp.async.bulk.tensor.3d.global.shared::cta.bulk_group [%0, {%2, %3, %4}], [%1];" ::"l"(tm), "r"(src), "r"(c0), "r"(c1), "r"(c2) : "memory");
}
DEVI void tma4s(const CUtensorMap* tm, uint32_t src, int c0, int c1, int c2, int c3) {
    asm volatile("cp.async.bulk.tensor.4d.global.shared::cta.bulk_group [%0, {%2, %3, %4, %5}], [%1];"
                 ::"l"(tm), "r"(src), "r"(c0), "r"(c1), "r"(c2), "r"(c3) : "memory");
}
DEVI void bulk_commit() { asm volatile("cp.async.bulk.commit_group;" ::: "memory"); }
DEVI void fence_async() { asm volatile("fence.proxy.async;" ::: "memory"); }
DEVI void fence_smem() { asm volatile("fence.proxy.async.shared::cta;" ::: "memory"); }
DEVI void wgbar(uint32_t q) { asm volatile("bar.sync %0, 128;" ::"r"(q + 2) : "memory"); }
DEVI void grid_arrive(uint32_t* c) { asm volatile("fence.proxy.async;\nred.release.gpu.global.add.u32 [%0], 1;" ::"l"(c) : "memory"); }
DEVI void grid_wait(uint32_t* c, uint32_t n) {
    uint32_t v;
    int it = 0;
    do {
        asm volatile("ld.acquire.gpu.global.u32 %0, [%1];" : "=r"(v) : "l"(c) : "memory");
        if (++it > (1 << 22)) die(it);
    } while (v != n);
    fence_async();
}

template <bool INV, class S1, class S2>
DEVI void fft_rows(uint32_t grp, uint32_t q, const uint32_t (&F)[2][4], const float (&tc)[8], const float (&ts)[8], uint32_t so, float fx, uint32_t nq,
                   S1 sh1, S2 sh2) {
    float d[64];
    const uint64_t db = INV ? mkdesc(grp, 1024, 2048) : (mkdesc(grp, 2048, 512) ^ ((uint64_t)3 << 62));
    wg_fence();
    wg_rs128t<0>(d, F[0], db);
    wg_rs128t<1>(d, F[1], db + (INV ? 256 : 64));
    wg_commit();
    SF();
    sh1();
    float4 ny;
    if (INV) ny = lds128f(nq);
    wg_wait<0>();
    if (INV) { d[0] = fmaf(fx, ny.x, d[0]); d[16] = fmaf(fx, ny.y, d[16]); d[32] = fmaf(fx, ny.z, d[32]); d[48] = fmaf(fx, ny.w, d[48]); }
    uint32_t a[2][4][4];
    float e[2][INV ? 16 : 20];
    const uint64_t df = mkdesc(SB0 + FS_F2, 16, 1024);
#pragma unroll
    for (int s = 0; s < 2; s++) {
#pragma unroll
        for (int i = 0; i < 4; i++)
#pragma unroll
            for (int h = 0; h < 2; h++) {
                const float* x = d + (2 * s + h) * 16 + i * 4;
                a[s][i][h] = pack2(fmaf(x[2], ts[2 * i], x[0] * tc[2 * i]), fmaf(x[3], ts[2 * i + 1], x[1] * tc[2 * i + 1]));
                a[s][i][h + 2] = pack2(fmaf(-x[0], ts[2 * i], x[2] * tc[2 * i]), fmaf(-x[1], ts[2 * i + 1], x[3] * tc[2 * i + 1]));
            }
        wg_fence();
#pragma unroll
        for (int i = 0; i < 4; i++) {
            if constexpr (INV) { if (i == 0) wg_rs32<0>(e[s], a[s][i], df); else wg_rs32<1>(e[s], a[s][i], df + i * 2); }
            else { if (i == 0) wg_rs40<0>(e[s], a[s][i], df); else wg_rs40<1>(e[s], a[s][i], df + i * 2); }
        }
        wg_commit();
    }
    SF();
    sh2();
#pragma unroll
    for (int s = 0; s < 2; s++) {
        if (s == 0) wg_wait<1>(); else wg_wait<0>();
        float* x = e[s];
        if constexpr (!INV) {
            x[0] *= fx; x[1] *= fx; x[2] *= fx; x[3] *= fx;
            if (fx != 1.f) sts64(nq + s * 8, pack2(x[16], 0.f), pack2(x[18], 0.f));
        }
        const uint32_t o = grp + (INV ? so + s * 4096 : so ^ (s * 576));
#pragma unroll
        for (int b = 0; b < 2; b++)
            stsm4t(o + b * (INV ? 1024 : 4096), pack2(x[8 * b], x[8 * b + 1]), pack2(x[8 * b + 2], x[8 * b + 3]), pack2(x[8 * b + 4], x[8 * b + 5]),
                   pack2(x[8 * b + 6], x[8 * b + 7]));
    }
}

template <bool INV>
DEVI void fft_gen(uint32_t a, uint32_t n2) {
    const uint32_t tid = tidx(), x = ((tid >> 4) & 24) + (tid & 3), o = (tid & 4) * 128;
    if (INV) {
        const uint32_t r = (tid & 64) * 16 + (tid & 16) * 32 + (tid & 40) * 8 + n2;
        sts128(a + tid * 16, cis(o - r * x), cis(o - (r + 128) * x), cis(o - r * (x + 4)), cis(o - (r + 128) * (x + 4)));
    } else {
        const uint32_t r = 64 * x + n2, k = ((tid >> 2) & 24) + ((tid >> 3) & 3);
        sts128(a + tid * 16, cis(r * k + o), cis(r * (k + 4) + o), cis((r + 256) * k + o), cis((r + 256) * (k + 4) + o));
    }
}
template <bool INV, class S1>
DEVI void fft_cross(uint32_t buf, uint32_t q, uint32_t fa, uint32_t so, uint32_t nq, float (&n)[4], S1 sh1) {
    uint32_t F[4][4];
#pragma unroll
    for (int s = 0; s < 4; s++) { const uint4 v = lds128(fa + s * 2048); F[s][0] = v.x; F[s][1] = v.y; F[s][2] = v.z; F[s][3] = v.w; }
    float d[64];
    const uint64_t db = mkdesc(buf + q * 2048, 1024, 8192), dn = mkdesc(nq, 16, 1024);
    wg_fence();
#pragma unroll
    for (int s = 0; s < 4; s++) { if (s == 0) wg_rs128t<0>(d, F[s], db); else wg_rs128t<1>(d, F[s], db + s * 1024); }
#pragma unroll
    for (int s = 0; s < 4; s++) { if (s == 0) wg_rs8<0>(n, F[s], dn); else wg_rs8<1>(n, F[s], dn + s * 2); }
    wg_commit();
    SF();
    sh1();
    wg_wait<0>();
#pragma unroll
    for (int b = 0; b < 8; b++) {
        const uint32_t o = INV ? so ^ ((b >> 1) * 288 ^ (b & 1) * 32) : (so ^ ((b & 3) * 32)) + (b >> 2) * 1024;
        stsm4(buf + o, pack2(d[8 * b], d[8 * b + 1]), pack2(d[8 * b + 2], d[8 * b + 3]), pack2(d[8 * b + 4], d[8 * b + 5]), pack2(d[8 * b + 6], d[8 * b + 7]));
    }
}

template <bool ODD>
DEVI void fft_filter(uint32_t aw, const float (&e)[32], const float (&o)[32], uint32_t (&u)[4][4], uint32_t (&v)[4][4]) {
#pragma unroll
    for (int s = 0; s < 4; s++) {
        float y[2][2][4];
#pragma unroll
        for (int c = 0; c < 2; c++) {
            float f[4][2];
#pragma unroll
            for (int i = 0; i < 4; i++) {
                const uint32_t a = aw + (i * 32 + s * 8 + c) * 144, x = lds32(a);
                f[i][0] = ODD ? hi_f(x) : lo_f(x);
                f[i][1] = ODD ? lo_f(lds32(a + 4)) : hi_f(x);
            }
#pragma unroll
            for (int h = 0; h < 2; h++) {
                const int x = 8 * s + 2 * h + c;
                const float ar = e[x] + o[x], ai = e[x + 4] + o[x + 4], br = e[x] - o[x], bi = e[x + 4] - o[x + 4];
                const float yr = fmaf(-ai, f[2][h], ar * f[0][h]), yi = fmaf(ar, f[2][h], ai * f[0][h]);
                y[h][c][0] = fmaf(-bi, f[3][h], fmaf(br, f[1][h], yr));
                y[h][c][1] = fmaf(br, f[3][h], fmaf(bi, f[1][h], yi));
                y[h][c][2] = fmaf(2.f, yr, -y[h][c][0]);
                y[h][c][3] = fmaf(2.f, yi, -y[h][c][1]);
            }
        }
#pragma unroll
        for (int h = 0; h < 2; h++) {
            u[s][h] = pack2(y[h][0][0], y[h][1][0]); u[s][h + 2] = pack2(y[h][0][1], y[h][1][1]);
            v[s][h] = pack2(y[h][0][2], y[h][1][2]); v[s][h + 2] = pack2(y[h][0][3], y[h][1][3]);
        }
    }
}

__global__ void __launch_bounds__(F_THREADS, 1)
post_kernel(const __grid_constant__ CUtensorMap tmx, const __grid_constant__ CUtensorMap tmg1, const __grid_constant__ CUtensorMap tmg2,
           const __grid_constant__ CUtensorMap tmwr, const __grid_constant__ CUtensorMap tmwi, const __grid_constant__ CUtensorMap tmy,
           const bf16* __restrict__ wr, const bf16* __restrict__ wi, uint32_t* cnt, uint32_t zero, int nw) {
    extern __shared__ __align__(1024) uint8_t smem[];
    const uint32_t sb = SB0;
    if (smem_u32(smem) != sb) die(1 << 23);
    const uint32_t tid = threadIdx.x, lane = tid & 31, g = lane >> 2, t = lane & 3, j8 = lane & 7, mat = lane >> 3;
    const uint32_t wi_ = __reduce_max_sync(0xFFFFFFFFu, tid >> 5), q = wi_ >> 2, w = wi_ & 3;
    const int cta = blockIdx.x;
    const int nt = cta < 64 ? (64 - cta + nw - 1) / nw : 0;
    const uint32_t bar = sb + FS_BAR;
    if (tid == 0) {
        for (int i = 0; i < 30; i++) mbar_init(bar + i * 8, i < 3 ? 4 : i < 6 ? 16 : i >= 14 && i < 18 ? 2 : 1);
        asm volatile("fence.mbarrier_init.release.cluster;" ::: "memory");
        fence_smem();
    }
    __syncthreads();
#define FT(n)
    FT(0);
#define N2(p) (2 * ((p) & 31) + ((p) >> 5))
#define WLOAD(tk, part) { \
        const uint32_t wd_ = sb + 131072 + q * 18432 + (part) * 9216, wb_ = bar + 112 + q * 8; \
        mbar_expect(wb_, 9216); \
        if ((tk) < 256) tma3d(wd_, (part) ? &tmwi : &tmwr, wb_, ((tk) & 63) * 64, (tk) >> 6, 0); \
        else asm volatile("cp.async.bulk.shared::cluster.global.mbarrier::complete_tx::bytes [%0], [%1], 9216, [%2];" \
                          ::"r"(wd_), "l"(g_WN + (part) * 576), "r"(wb_) : "memory"); }
#define GROW(tk) ((tk) < 256 ? ((tk) >> 5) * 64 + ((tk) & 7) * 8 + (((tk) >> 3) & 3) * 2 : 512)
#define DLOAD(tk, sl) { mbar_expect(bar + 48 + (sl) * 8, 16384); tma3d(sb + (sl) * 16384, &tmg2, bar + 48 + (sl) * 8, 0, GROW(tk), 0); }
#define IO(c) if (w == 3 && (c) && elect())
#define XLOAD1(i, bb) { const uint32_t xb_ = bar + 144 + (bb) * 32 + q * 8; mbar_expect(xb_, 16384); tma4d(sb + (bb) * 65536 + q * 16384, &tmx, xb_, 0, 0, q * 8, N2(cta + (i) * nw)); }
#define GLOAD3(i, bb) { mbar_expect(bar + (bb) * 8, q ? 16384 : 16512); tma3d(sb + (bb) * 65536 + q * 16384, &tmg1, bar + (bb) * 8, 0, q * 128, cta + (i) * nw); \
        if (q == 0) asm volatile("cp.async.bulk.shared::cluster.global.mbarrier::complete_tx::bytes [%0], [%1], 128, [%2];" \
                                 ::"r"(sb + FS_NQ + (bb) * 1024), "l"(g_GN + (cta + (i) * nw) * 8), "r"(bar + (bb) * 8) : "memory"); }
    for (int i = 0; i < 3; i++) IO(i < nt) XLOAD1(i, i);
    for (uint32_t x = tid; x < 40 * 32; x += 512) {
        const uint32_t n = x >> 5, m2 = mat * 8 + t * 2, ri = g & 1;
        const uint32_t c2 = ((n >> 1) & 1) + ((n >> 3) & 1) * 2 + (n & 4) + (n >> 4) * 8;
        const uint32_t v = cos2(m2 * c2 * 64 + ((n & 1) - ri) * 512, (m2 + 1) * c2 * 64 + ((n & 1) - ri) * 512);
        sts32(sb + FS_F2 + n * 128 + ((g ^ (n & 7)) << 4) + t * 4, n < 32 ? v : n == 32 && ri == 0 ? 0xBF003F00u : 0u);
    }
    float tc[8], ts[8];
    uint32_t F[2][4];
    uint32_t c1 = 16 * (w >> 1) + 2 * g + (w & 1);
#pragma unroll
    for (int i = 0; i < 8; i++) {
        twid(c1 * (8 * (i >> 1) + 2 * t + (i & 1)), tc[i], ts[i]);
        const uint32_t m1 = (i >> 1) * 8 + 2 * t;
        F[i >> 2][i & 3] = cos2(c1 * m1 * 64 + (i & 1) * 512, c1 * (m1 + 1) * 64 + (i & 1) * 512);
    }
    {
        const uint32_t kr = (2 * (mat & 1) + (j8 & 1)) ^ ((j8 >> 2) << 1);
        const uint32_t so1 = ((mat >> 1) + 2 * (j8 >> 2)) * 1024 + kr * 128 + (((((j8 >> 1) & 1) * 4 + w) ^ kr) << 4);
        const uint32_t so2 = (2 * w + (mat & 1)) * 8192 + q * 2048 + j8 * 128 + (((mat >> 1) ^ j8) << 4);
        uint32_t so = so1 << 16 | so2;
        const float fx = (tid & 127) == 0 ? 0.5f : 1.f;
        fft_gen<false>(sb + FS_TB, N2(cta));
        fence_smem();
        bsync<1, 512>();
        FT(1);
        int b = 0, bp = 2, ph = 0;
        if (nt) mwait(bar + 144 + q * 8, 0);
        __syncwarp();
        auto step = [&](auto first, auto last, const int i) {
            const uint32_t p = cta + i * nw, bn = 3 - b - bp, tb = (i & 1) * 8192;
            const uint32_t grp = sb + b * 65536 + q * 16384, nq = sb + FS_NQ + b * 1024 + q * 32;
            auto sa = [&]() {
                if constexpr (!decltype(first)::v) {
                    fence_smem();
                    __syncwarp();
                    if (elect()) mbar_arrive(bar + 24);
                }
                IO(i > 1) {
                    mwait(bar + 32, i & 1);
                    tma3s(&tmg1, sb + bn * 65536 + q * 16384, 0, q * 128, p - 2 * nw);
                    bulk_commit();
                }
            };
            auto sb_ = [&]() { if constexpr (!decltype(first)::v) mwait(bar + 24, (i - 1) & 1); };
            if constexpr (!decltype(last)::v) fft_rows<false>(grp, q, F, tc, ts, opq(so, zero) >> 16, fx, nq, sa, sb_);
            else { sa(); __syncwarp(); sb_(); __syncwarp(); }
            if constexpr (!decltype(first)::v) {
                float n[4];
                fft_cross<false>(sb + bp * 65536, q, sb + FS_TB + 8192 - tb + (((tidx() & 127) ^ (q & 1)) << 4), opq(so, zero) & 0xFFFF, sb + FS_NQ + bp * 1024, n, [&]() {
                    fft_gen<false>(sb + FS_TB + tb, N2(p));
                    IO(i >= 2 && i + 1 < nt) {
                        asm volatile("cp.async.bulk.wait_group.read 0;" ::: "memory");
                        XLOAD1(i + 1, bn);
                    }
                });
                if (q == 0) {
                    const uint32_t x = tidx();
                    bf16* z = (bf16*)(g_G + ((p - nw) * G_ROWS + 512) * 8) + (x & 4) * 16 + ((x >> 2) & 24) + ((x >> 3) & 3);
                    asm volatile("{\n.reg .pred p;\n.reg .b16 a, b;\nsetp.eq.u32 p, %2, 0;\nmov.b32 {a, b}, %1;\n@p st.global.u16 [%0], a;\n@p st.global.u16 [%0+8], b;\n}"
                                 ::"l"(z), "r"(pack2(n[0], n[2])), "r"(x & 3) : "memory");
                }
            }
            if constexpr (!decltype(last)::v) {
                fft_rows<false>(grp + 8192, q, F, tc, ts, opq(so, zero) >> 16, fx, nq + 16, [&]() {
                    if constexpr (!decltype(first)::v) {
                        fence_smem();
                        __syncwarp();
                        if (elect()) mbar_arrive(bar + 32);
                    }
                    if ((w == 1 || w == 2) && elect())
                        asm volatile("cp.async.bulk.prefetch.L2.global [%0], 8208;" ::"l"((w == 1 ? wr : wi) + (p * 4 + q) * 4104) : "memory");
                }, [&]() { if (i + 1 < nt) mwait(bar + 144 + bn * 32 + q * 8, bn ? ph : ph ^ 1); });
                bp = b;
                if (++b == 3) { b = 0; ph ^= 1; }
            }
        };
        if (nt) {
            step(Bool<true>(), Bool<false>(), 0);
#pragma unroll 1
            for (int i = 1; i < nt; i++) step(Bool<false>(), Bool<false>(), i);
            step(Bool<false>(), Bool<true>(), nt);
        }
        for (uint32_t x = cta * 512 + tid; x < 4096; x += nw * 512)
            ((bf16*)g_WN)[(x >> 5) * 72 + (x & 16) + (x & 7) * 2 + ((x >> 3) & 1)] = (x < 2048 ? wr : wi)[(x & 2047) * 513 + 512];
        FT(2);
        fence_async();
        bsync<1, 512>();
        IO(nt) { tma3s(&tmg1, sb + bp * 65536 + q * 16384, 0, q * 128, cta + (nt - 1) * nw); bulk_commit(); }
    }
    for (uint32_t x = tid; x < 128 * 32; x += 512) {
        const uint32_t n = (x >> 5) & 63, a = x & 31, k2 = (n >> 4) * 8 + (n & 7);
        sts32(sb + FS_TB + (x >> 5) * 128 + (((a >> 2) ^ (n & 7)) << 4) + (a & 3) * 4, cis((2 * a + (x >> 11)) * k2 * 32 + (n & 8) * 64));
    }
    fence_smem();
    bsync<1, 512>();
    IO(true) {
        asm volatile("cp.async.bulk.wait_group 0;" ::: "memory");
        grid_arrive(cnt);
        grid_wait(cnt, 4 * nw);
        const int tk = cta + q * nw;
        if (tk <= 256) { DLOAD(tk, q); WLOAD(tk, 0); WLOAD(tk, 1); }
    }
    __syncwarp();
    {
        const uint32_t lo = j8 * 128 + (((2 * w + (mat & 1)) ^ j8) << 4);
        const uint32_t aw = sb + 131072 + q * 18432 + t * 288 + w * 32 + g * 4;
        const uint64_t df = mkdesc(sb + FS_TB, 16, 1024);
        const uint64_t da = mkdesc(sb + q * 16384, 16, 1024);
        const uint32_t buf = sb + 65536 + q * 16384;
        int i = 0, tk = cta + q * nw;
        if (tk <= 256) mwait(bar + 48 + q * 8, 0);
        FT(3);
#pragma unroll 1
        for (; tk <= 256; tk += 4 * nw, i++) {
            const bool more = tk + 4 * nw <= 256;
            float e[32], o[32];
            wg_fence();
#pragma unroll
            for (int s = 0; s < 4; s++) { if (s == 0) wg_ss64a<0>(e, da, df); else wg_ss64a<1>(e, da + s * 128, df + s * 2); }
#pragma unroll
            for (int s = 0; s < 4; s++) { if (s == 0) wg_ss64a<0>(o, da + 512, df + 512); else wg_ss64a<1>(o, da + 512 + s * 128, df + 512 + s * 2); }
            wg_commit();
            SF();
            if (i > 0) {
                fence_smem();
                wgbar(q);
                IO(true) { tma3s(&tmg2, buf, 0, GROW(tk - 4 * nw), 0); bulk_commit(); }
            }
            if (w == 2 && more && elect()) mbar_expect(bar + 48 + q * 8, 16384);
            const int gr = GROW(tk + 4 * nw);
            mwait(bar + 112 + q * 8, i & 1);
            wg_wait<0>();
            if (w == 2 && more && elect()) tma3d(sb + q * 16384, &tmg2, bar + 48 + q * 8, 0, gr, 0);
            uint32_t u[4][4], v[4][4];
            if (tk & 8) fft_filter<true>(aw + (tk & 48) / 4, e, o, u, v);
            else fft_filter<false>(aw + (tk & 48) / 4, e, o, u, v);
            wg_fence();
#pragma unroll
            for (int s = 0; s < 4; s++) { if (s == 0) wg_rs64t<0>(e, u[s], df); else wg_rs64t<1>(e, u[s], df + s * 128); }
#pragma unroll
            for (int s = 0; s < 4; s++) { if (s == 0) wg_rs64t<0>(o, v[s], df + 512); else wg_rs64t<1>(o, v[s], df + 512 + s * 128); }
            wg_commit();
            SF();
            IO(true) asm volatile("cp.async.bulk.wait_group.read 0;" ::: "memory");
            wgbar(q);
            if (more) {
                if ((w == 1 || w == 2) && elect()) WLOAD(tk + 4 * nw, w - 1);
                mwait(bar + 48 + q * 8, (i + 1) & 1);
            }
            wg_wait<0>();
#pragma unroll
            for (int s = 0; s < 4; s++) {
                const uint32_t a = buf + (mat >> 1) * 1024 + lo + s * 2048;
                stsm4t(a, pack2(e[8 * s], e[8 * s + 1]), pack2(e[8 * s + 2], e[8 * s + 3]), pack2(e[8 * s + 4], e[8 * s + 5]), pack2(e[8 * s + 6], e[8 * s + 7]));
                stsm4t(a + 8192, pack2(o[8 * s], o[8 * s + 1]), pack2(o[8 * s + 2], o[8 * s + 3]), pack2(o[8 * s + 4], o[8 * s + 5]), pack2(o[8 * s + 6], o[8 * s + 7]));
            }
            if (tk == 256 && w < 2) {
                uint32_t* z = (uint32_t*)g_GN + t * 32 + w * 16 + g;
#pragma unroll
                for (int s = 0; s < 16; s++) {
                    z[(s >> 1) * 128 + (s & 1) * 8] = pack2(e[2 * s], e[2 * s + 1]);
                    z[(s >> 1) * 128 + (s & 1) * 8 + 1024] = pack2(o[2 * s], o[2 * s + 1]);
                }
                fence_async();
            }
        }
        fence_smem();
        wgbar(q);
        IO(true) {
            if (i > 0) { tma3s(&tmg2, buf, 0, GROW(tk - 4 * nw), 0); bulk_commit(); }
            asm volatile("cp.async.bulk.wait_group 0;" ::: "memory");
            grid_arrive(cnt + 1);
        }
    }
    FT(4);
    bsync<1, 512>();
    {
        for (uint32_t n = wi_; n < 32; n += 16) {
            const uint32_t cl = (mat >> 1) * 16 + t * 4 + (mat & 1), mh = ((n >> 3) & 1) + (n & 7) * 2 + (n & 16);
            sts32(sb + FS_F2 + n * 128 + ((g ^ (n & 7)) << 4) + t * 4, cos2(cl * mh * 64 + (g & 1) * 512, (cl + 2) * mh * 64 + (g & 1) * 512));
        }
        fence_smem();
        c1 = 8 * w + g;
#pragma unroll
        for (int i = 0; i < 8; i++) {
            twid(-c1 * (16 * (i >> 2) + 4 * t + 2 * (i & 1) + ((i >> 1) & 1)), tc[i], ts[i]);
            F[i >> 2][i & 3] = cis((i & 1) * 512 - c1 * ((i >> 1) * 4 + (t ^ (q & 1))) * 64);
        }
        const uint32_t kr = (j8 & 1) ^ ((j8 >> 2) << 1);
        const uint32_t so2 = ((w >> 1) * 4 + (j8 >> 2) * 2 + (w & 1)) * 8192 + (2 * q + (mat & 1)) * 1024 + kr * 128 + (((((j8 >> 1) & 1) * 4 + (mat >> 1)) ^ kr) << 4);
        const uint32_t so1 = (mat & 1) * 2048 + j8 * 128 + ((((mat >> 1) * 4 + w) ^ j8) << 4);
        uint32_t so = so1 << 16 | so2;
        const float fx = t ? 0.f : (g & 1) ? -1.f : 1.f;
        fft_gen<true>(sb + FS_TB, N2(cta));
        bsync<1, 512>();
        IO(true) grid_wait(cnt + 1, 4 * nw);
        for (int i = 0; i < 3; i++) IO(i < nt) GLOAD3(i, i);
        __syncwarp();
        int b = 0, bp = 2, ph = 0;
        auto step = [&](auto first, auto last, const int i) {
            const uint32_t p = cta + i * nw, bn = 3 - b - bp, tb = (i & 1) * 8192;
            const uint32_t grp = sb + bp * 65536 + q * 16384, ny = sb + FS_NY + bp * 128 + q * 32;
            auto sb_ = [&]() { if constexpr (!decltype(last)::v) mwait(bar + b * 8, ph); };
            if constexpr (!decltype(first)::v) {
                fft_rows<true>(grp, q, F, tc, ts, opq(so, zero) >> 16, fx, ny, [&]() {
                    if (i > 1) {
                        fence_smem();
                        wgbar(q);
                        IO(true) { tma4s(&tmy, sb + bn * 65536 + q * 16384, 0, 0, q * 8, N2(p - 2 * nw)); bulk_commit(); }
                    }
                }, sb_);
            } else { sb_(); __syncwarp(); }
            if constexpr (decltype(first)::v) FT(5);
            if constexpr (!decltype(last)::v) {
                float n[4];
                fft_cross<true>(sb + b * 65536, q, sb + FS_TB + tb + (tidx() & 127) * 16, opq(so, zero) & 0xFFFF, sb + FS_NQ + b * 1024, n, [&]() {
                    fft_gen<true>(sb + FS_TB + 8192 - tb, N2(p + nw));
                    IO(i >= 2 && i + 1 < nt) {
                        asm volatile("cp.async.bulk.wait_group.read 0;" ::: "memory");
                        GLOAD3(i + 1, bn);
                    }
                });
                if (q == 0) {
                    const uint32_t x = tidx(), a = sb + FS_NY + b * 128 + (x & 64) + (x & 16) * 2 + ((x & 40) >> 1);
                    if ((x & 7) == 0) { sts32f(a, n[0]); sts32f(a + 8, n[2]); }
                }
            }
            auto sc = [&]() {
                if constexpr (!decltype(last)::v) {
                    fence_smem();
                    __syncwarp();
                    if (elect()) mbar_arrive(bar + 24);
                }
            };
            auto sd = [&]() { if constexpr (!decltype(last)::v) mwait(bar + 24, (nt + i) & 1); };
            if constexpr (!decltype(first)::v) fft_rows<true>(grp + 8192, q, F, tc, ts, opq(so, zero) >> 16, fx, ny + 16, sc, sd);
            else { sc(); __syncwarp(); sd(); __syncwarp(); }
            if constexpr (!decltype(last)::v) {
                bp = b;
                if (++b == 3) { b = 0; ph ^= 1; }
            }
        };
        if (nt) {
            step(Bool<true>(), Bool<false>(), 0);
#pragma unroll 1
            for (int i = 1; i < nt; i++) step(Bool<false>(), Bool<false>(), i);
            step(Bool<false>(), Bool<true>(), nt);
        }
        fence_smem();
        wgbar(q);
        IO(nt) { tma4s(&tmy, sb + bp * 65536 + q * 16384, 0, 0, q * 8, N2(cta + (nt - 1) * nw)); bulk_commit(); }
        FT(6);
        IO(true) asm volatile("cp.async.bulk.wait_group 0;" ::: "memory");
    }
}

typedef CUresult (*EncodeFn)(CUtensorMap*, CUtensorMapDataType, cuuint32_t, void*, const cuuint64_t*, const cuuint64_t*,
                             const cuuint32_t*, const cuuint32_t*, CUtensorMapInterleave, CUtensorMapSwizzle,
                             CUtensorMapL2promotion, CUtensorMapFloatOOBfill);

static void make_map(EncodeFn enc, CUtensorMap* m, const void* ptr, int rank, const cuuint64_t* dims, const cuuint64_t* strides,
                     const cuuint32_t* box, CUtensorMapSwizzle sw = CU_TENSOR_MAP_SWIZZLE_128B) {
    cuuint32_t es[4] = {1, 1, 1, 1};
    CUresult r = enc(m, CU_TENSOR_MAP_DATA_TYPE_BFLOAT16, rank, (void*)ptr, dims, strides, box, es, CU_TENSOR_MAP_INTERLEAVE_NONE,
                     sw, CU_TENSOR_MAP_L2_PROMOTION_L2_256B, CU_TENSOR_MAP_FLOAT_OOB_FILL_NONE);
    if (r != CUDA_SUCCESS) fprintf(stderr, "tensor map encode failed: %d\n", (int)r);
}

extern "C" void kernel_launch(void* const* d_in, const int* in_sizes, int n_in, void* d_out, int out_size) {
    const bf16* A_x = (const bf16*)d_in[0];
    const bf16* A_mem0 = (const bf16*)d_in[1];
    const bf16* A_Wq = (const bf16*)d_in[2];
    const bf16* A_Wk = (const bf16*)d_in[3];
    const bf16* A_Wv = (const bf16*)d_in[4];
    const bf16* A_Wo = (const bf16*)d_in[5];
    const bf16* B_x = (const bf16*)d_in[7];
    const bf16* B_wr = (const bf16*)d_in[8];
    const bf16* B_wi = (const bf16*)d_in[9];
    bf16* out = (bf16*)d_out;

    static EncodeFn enc = nullptr;
    static void *pxs = nullptr, *pg = nullptr;
    static int ncl = 64;
    if (!enc) {
        cudaDriverEntryPointQueryResult qr;
        void* fn = nullptr;
        cudaGetDriverEntryPoint("cuTensorMapEncodeTiled", &fn, cudaEnableDefault, &qr);
        enc = (EncodeFn)fn;
        cudaFuncSetAttribute(chain_kernel, cudaFuncAttributeMaxDynamicSharedMemorySize, SM_TOTAL);
        cudaFuncSetAttribute(post_kernel, cudaFuncAttributeMaxDynamicSharedMemorySize, FS_TOTAL);
        cudaGetSymbolAddress(&pxs, g_xs);
        cudaGetSymbolAddress(&pg, g_G);
        cudaLaunchConfig_t lc = {};
        cudaLaunchAttribute at;
        at.id = cudaLaunchAttributeClusterDimension;
        at.val.clusterDim.x = 2; at.val.clusterDim.y = 1; at.val.clusterDim.z = 1;
        lc.gridDim = dim3(132); lc.blockDim = dim3(384); lc.dynamicSmemBytes = SM_TOTAL; lc.attrs = &at; lc.numAttrs = 1;
        int nc = 0;
        if (cudaOccupancyMaxActiveClusters(&nc, chain_kernel, &lc) == cudaSuccess && nc > 64) ncl = nc < 66 ? nc : 66;
    }
    CUtensorMap tmq, tmk, tmv, tmo, tmx, tmb, tmy;
    {
        cuuint64_t d[2] = {HD, DM}, st[1] = {HD * 2};
        cuuint32_t bx[2] = {64, 256};
        make_map(enc, &tmq, A_Wq, 2, d, st, bx);
        make_map(enc, &tmk, A_Wk, 2, d, st, bx);
        cuuint32_t bx2[2] = {64, 16};
        make_map(enc, &tmv, A_Wv, 2, d, st, bx2);
    }
    {
        cuuint64_t d[2] = {DM, HD}, st[1] = {DM * 2};
        cuuint32_t bx[2] = {64, 16}, bx2[3] = {64, 64, 2};
        make_map(enc, &tmo, A_Wo, 2, d, st, bx);
        cuuint64_t d2[3] = {64, HD, DM / 64}, st2[2] = {DM * 2, 128}, d3[2] = {DM, SEQ}, st3[1] = {DM * 4};
        make_map(enc, &tmb, A_Wo, 3, d2, st2, bx2);
        make_map(enc, &tmy, out, 2, d3, st3, bx);
    }
    {
        cuuint64_t d[3] = {64, SEQ, DM / 64}, st[2] = {DM * 2, 128};
        cuuint32_t bx[3] = {64, 8, 4};
        make_map(enc, &tmx, A_x, 3, d, st, bx);
    }
    CUtensorMap fx, fg1, fg2, fwr, fwi, fy;
    {
        cuuint64_t d[4] = {32, 32, 32, 64}, st[3] = {64, 64 * DM * 2, DM * 2};
        cuuint32_t bx[4] = {32, 32, 8, 1};
        make_map(enc, &fx, B_x, 4, d, st, bx, CU_TENSOR_MAP_SWIZZLE_64B);
        cuuint64_t d2[4] = {64, 16, 32, 64}, st2[3] = {128, 64 * 4096, 4096};
        cuuint32_t bx2[4] = {64, 16, 8, 1};
        make_map(enc, &fy, out + DM, 4, d2, st2, bx2);
    }
    {
        cuuint64_t d[3] = {64, G_ROWS, 64}, st[2] = {128, G_ROWS * 128};
        cuuint32_t bx[3] = {64, 128, 1}, bx2[3] = {64, 2, 64};
        make_map(enc, &fg1, pg, 3, d, st, bx);
        make_map(enc, &fg2, pg, 3, d, st, bx2);
        cuuint64_t d2[3] = {8 * 513, 4, 64}, st2[2] = {8 * 513 * 2, 32 * 513 * 2};
        cuuint32_t bx3[3] = {72, 1, 64};
        make_map(enc, &fwr, B_wr, 3, d2, st2, bx3, CU_TENSOR_MAP_SWIZZLE_NONE);
        make_map(enc, &fwi, B_wi, 3, d2, st2, bx3, CU_TENSOR_MAP_SWIZZLE_NONE);
    }
    cudaStream_t st = cudaStreamPerThread;
    const uint64_t xs = ((uint64_t)pxs + XS_BYTES - 1) & ~(uint64_t)(XS_BYTES - 1);
    cudaMemsetAsync((void*)(xs + XO_R), 0, XO_TK + 512, st);
    chain_kernel<<<2 * ncl, 384, SM_TOTAL, st>>>(tmq, tmk, tmv, tmo, tmx, tmb, tmy, A_mem0, A_x, (uint32_t)xs, (uint32_t)(xs >> 32), 0u, NSEG);
    int nw = ncl == 66 ? 4 : 64;
    cudaLaunchConfig_t lc = {};
    cudaLaunchAttribute at;
    at.id = cudaLaunchAttributeProgrammaticStreamSerialization;
    at.val.programmaticStreamSerializationAllowed = 1;
    lc.gridDim = dim3(nw); lc.blockDim = dim3(F_THREADS); lc.dynamicSmemBytes = FS_TOTAL; lc.stream = st; lc.attrs = &at; lc.numAttrs = 1;
    cudaLaunchKernelEx(&lc, post_kernel, fx, fg1, fg2, fwr, fwi, fy, B_wr, B_wi, (uint32_t*)(xs + XO_TK + 256), 0u, nw);
}
```

```cpp
#include <cuda_runtime.h>
#include <cuda_bf16.h>
#include <cuda.h>
#include <stdint.h>
#include <stdio.h>

typedef __nv_bfloat16 bf16;

#define SEQ 2048
#define DM 1024
#define NH 32
#define DH 128
#define NSEG 64
#define HD (NH * DH)

#define XS_BYTES (32u << 20)
__device__ uint4 g_xs[2 * XS_BYTES / 16];
#define XO_R 0u
#define XO_PB (1u << 18)
#define XO_FL (XO_PB + 16384u)
#define XO_TK (XO_FL + 32768u)
#define XO_CQK (1u << 20)
#define XO_CV (2u << 20)
#define XO_XG (4u << 20)
#define XO_OX (16u << 20)
#define GSYNC(n)
#define PG(n)

#define DEVI __device__ __forceinline__

DEVI void die(int it) { asm volatile("st.shared.u32 [%0], %0;" ::"r"(it) : "memory"); }
DEVI uint32_t smem_u32(const void* p) { return (uint32_t)__cvta_generic_to_shared(p); }
DEVI void mbar_init(uint32_t bar, uint32_t cnt) { asm volatile("mbarrier.init.shared::cta.b64 [%0], %1;" ::"r"(bar), "r"(cnt) : "memory"); }
DEVI void mbar_expect(uint32_t bar, uint32_t bytes) { asm volatile("mbarrier.arrive.expect_tx.shared::cta.b64 _, [%0], %1;" ::"r"(bar), "r"(bytes) : "memory"); }
DEVI void mbar_arrive(uint32_t bar) { asm volatile("mbarrier.arrive.shared::cta.b64 _, [%0];" ::"r"(bar) : "memory"); }
DEVI void mbar_wait(uint32_t bar, uint32_t parity) {
    uint32_t done;
    int it = 0;
    do {
        asm volatile("{\n.reg .pred p;\nmbarrier.try_wait.parity.shared::cta.b64 p, [%1], %2;\nselp.u32 %0, 1, 0, p;\n}\n"
                     : "=r"(done) : "r"(bar), "r"(parity) : "memory");
        if (++it > (1 << 22)) die(it);
    } while (!done);
}
DEVI void tma2d(uint32_t dst, const CUtensorMap* tm, uint32_t bar, int c0, int c1) {
    asm volatile("cp.async.bulk.tensor.2d.shared::cluster.global.mbarrier::complete_tx::bytes [%0], [%1, {%3, %4}], [%2];"
                 ::"r"(dst), "l"(tm), "r"(bar), "r"(c0), "r"(c1) : "memory");
}
DEVI void tma3d(uint32_t dst, const CUtensorMap* tm, uint32_t bar, int c0, int c1, int c2) {
    asm volatile("cp.async.bulk.tensor.3d.shared::cluster.global.mbarrier::complete_tx::bytes [%0], [%1, {%3, %4, %5}], [%2];"
                 ::"r"(dst), "l"(tm), "r"(bar), "r"(c0), "r"(c1), "r"(c2) : "memory");
}
DEVI void bulk_g2s(uint32_t dst, uint32_t lo, uint32_t hi, uint32_t bytes, uint32_t bar) {
    asm volatile("{\n.reg .b64 a;\nmov.b64 a, {%1,%2};\ncp.async.bulk.shared::cluster.global.mbarrier::complete_tx::bytes [%0], [a], %3, [%4];\n}"
                 ::"r"(dst), "r"(lo), "r"(hi), "r"(bytes), "r"(bar) : "memory");
}
DEVI void bulk_s2g(uint32_t lo, uint32_t hi, uint32_t src, uint32_t bytes) {
    asm volatile("{\n.reg .b64 a;\nmov.b64 a, {%0,%1};\ncp.async.bulk.global.shared::cta.bulk_group [a], [%2], %3;\ncp.async.bulk.commit_group;\n}"
                 ::"r"(lo), "r"(hi), "r"(src), "r"(bytes) : "memory");
}
DEVI void bulk_red(uint32_t lo, uint32_t hi, uint32_t src, uint32_t bytes) {
    asm volatile("{\n.reg .b64 a;\nmov.b64 a, {%0,%1};\ncp.reduce.async.bulk.global.shared::cta.bulk_group.add.noftz.bf16 [a], [%2], %3;\ncp.async.bulk.commit_group;\n}"
                 ::"r"(lo), "r"(hi), "r"(src), "r"(bytes) : "memory");
}
DEVI bool elect() {
    uint32_t p;
    asm volatile("{\n.reg .pred P;\nelect.sync _|P, 0xFFFFFFFF;\nselp.u32 %0, 1, 0, P;\n}" : "=r"(p));
    return p != 0;
}
DEVI void ldsm4(uint32_t (&r)[4], uint32_t a) {
    asm volatile("ldmatrix.sync.aligned.m8n8.x4.shared.b16 {%0,%1,%2,%3}, [%4];" : "=r"(r[0]), "=r"(r[1]), "=r"(r[2]), "=r"(r[3]) : "r"(a) : "memory");
}
DEVI void ldsm4t(uint32_t (&r)[4], uint32_t a) {
    asm volatile("ldmatrix.sync.aligned.m8n8.x4.trans.shared.b16 {%0,%1,%2,%3}, [%4];" : "=r"(r[0]), "=r"(r[1]), "=r"(r[2]), "=r"(r[3]) : "r"(a) : "memory");
}
DEVI void ldsm2t(uint32_t (&r)[2], uint32_t a) {
    asm volatile("ldmatrix.sync.aligned.m8n8.x2.trans.shared.b16 {%0,%1}, [%2];" : "=r"(r[0]), "=r"(r[1]) : "r"(a) : "memory");
}
DEVI void ldsm2(uint32_t (&r)[2], uint32_t a) {
    asm volatile("ldmatrix.sync.aligned.m8n8.x2.shared.b16 {%0,%1}, [%2];" : "=r"(r[0]), "=r"(r[1]) : "r"(a) : "memory");
}
DEVI void stsm4t(uint32_t a, uint32_t r0, uint32_t r1, uint32_t r2, uint32_t r3) {
    asm volatile("stmatrix.sync.aligned.m8n8.x4.trans.shared.b16 [%0], {%1,%2,%3,%4};" ::"r"(a), "r"(r0), "r"(r1), "r"(r2), "r"(r3) : "memory");
}
DEVI uint32_t ldsm1(uint32_t a) {
    uint32_t r;
    asm volatile("ldmatrix.sync.aligned.m8n8.x1.shared.b16 {%0}, [%1];" : "=r"(r) : "r"(a) : "memory");
    return r;
}
DEVI void stsm4(uint32_t a, uint32_t r0, uint32_t r1, uint32_t r2, uint32_t r3) {
    asm volatile("stmatrix.sync.aligned.m8n8.x4.shared.b16 [%0], {%1,%2,%3,%4};" ::"r"(a), "r"(r0), "r"(r1), "r"(r2), "r"(r3) : "memory");
}
DEVI void stsm2(uint32_t a, uint32_t r0, uint32_t r1) {
    asm volatile("stmatrix.sync.aligned.m8n8.x2.shared.b16 [%0], {%1,%2};" ::"r"(a), "r"(r0), "r"(r1) : "memory");
}
DEVI uint32_t movm(uint32_t a) {
    uint32_t d;
    asm volatile("movmatrix.sync.aligned.m8n8.trans.b16 %0, %1;" : "=r"(d) : "r"(a));
    return d;
}
DEVI void mma16(float (&d)[4], uint32_t a0, uint32_t a1, uint32_t a2, uint32_t a3, uint32_t b0, uint32_t b1) {
    asm volatile("mma.sync.aligned.m16n8k16.row.col.f32.bf16.bf16.f32 {%0,%1,%2,%3}, {%4,%5,%6,%7}, {%8,%9}, {%0,%1,%2,%3};"
                 : "+f"(d[0]), "+f"(d[1]), "+f"(d[2]), "+f"(d[3]) : "r"(a0), "r"(a1), "r"(a2), "r"(a3), "r"(b0), "r"(b1));
}
DEVI void mma16z(float (&d)[4], uint32_t a0, uint32_t a1, uint32_t a2, uint32_t a3, uint32_t b0, uint32_t b1) {
    asm volatile("mma.sync.aligned.m16n8k16.row.col.f32.bf16.bf16.f32 {%0,%1,%2,%3}, {%4,%5,%6,%7}, {%8,%9}, {%10,%10,%10,%10};"
                 : "=f"(d[0]), "=f"(d[1]), "=f"(d[2]), "=f"(d[3]) : "r"(a0), "r"(a1), "r"(a2), "r"(a3), "r"(b0), "r"(b1), "f"(0.f));
}
DEVI void mma8(float (&d)[4], uint32_t a0, uint32_t a1, uint32_t b0) {
    asm volatile("mma.sync.aligned.m16n8k8.row.col.f32.bf16.bf16.f32 {%0,%1,%2,%3}, {%4,%5}, {%6}, {%0,%1,%2,%3};"
                 : "+f"(d[0]), "+f"(d[1]), "+f"(d[2]), "+f"(d[3]) : "r"(a0), "r"(a1), "r"(b0));
}
DEVI void mma8z(float (&d)[4], uint32_t a0, uint32_t a1, uint32_t b0) {
    asm volatile("mma.sync.aligned.m16n8k8.row.col.f32.bf16.bf16.f32 {%0,%1,%2,%3}, {%4,%5}, {%6}, {%7,%7,%7,%7};"
                 : "=f"(d[0]), "=f"(d[1]), "=f"(d[2]), "=f"(d[3]) : "r"(a0), "r"(a1), "r"(b0), "f"(0.f));
}
DEVI uint32_t pack2(float lo, float hi) {
    uint32_t r;
    asm("cvt.rn.bf16x2.f32 %0, %1, %2;" : "=r"(r) : "f"(hi), "f"(lo));
    return r;
}
DEVI uint32_t hadd2(uint32_t a, uint32_t b) {
    uint32_t r;
    asm("add.rn.bf16x2 %0, %1, %2;" : "=r"(r) : "r"(a), "r"(b));
    return r;
}
DEVI float lo_f(uint32_t x) { return __uint_as_float(x << 16); }
DEVI float hi_f(uint32_t x) { return __uint_as_float(x & 0xFFFF0000u); }
template <uint32_t OFF> DEVI uint4 ldg4(uint32_t lo, uint32_t hi) {
    uint4 v;
    asm volatile("{\n.reg .b64 a;\nmov.b64 a, {%4,%5};\nld.relaxed.gpu.global.v4.u32 {%0,%1,%2,%3}, [a+%6];\n}"
                 : "=r"(v.x), "=r"(v.y), "=r"(v.z), "=r"(v.w) : "r"(lo), "r"(hi), "n"(OFF) : "memory");
    return v;
}
template <uint32_t OFF> DEVI uint2 ldg2(uint32_t lo, uint32_t hi) {
    uint2 v;
    asm volatile("{\n.reg .b64 a;\nmov.b64 a, {%2,%3};\nld.relaxed.gpu.global.v2.u32 {%0,%1}, [a+%4];\n}"
                 : "=r"(v.x), "=r"(v.y) : "r"(lo), "r"(hi), "n"(OFF) : "memory");
    return v;
}
template <uint32_t OFF> DEVI uint32_t ldg1(uint32_t lo, uint32_t hi) {
    uint32_t v;
    asm volatile("{\n.reg .b64 a;\nmov.b64 a, {%1,%2};\nld.relaxed.gpu.global.u32 %0, [a+%3];\n}" : "=r"(v) : "r"(lo), "r"(hi), "n"(OFF) : "memory");
    return v;
}
template <uint32_t OFF> DEVI void stg1(uint32_t lo, uint32_t hi, uint32_t a) {
    asm volatile("{\n.reg .b64 a;\nmov.b64 a, {%0,%1};\nst.relaxed.gpu.global.u32 [a+%3], %2;\n}" ::"r"(lo), "r"(hi), "r"(a), "n"(OFF) : "memory");
}
template <uint32_t OFF> DEVI void stg4(uint32_t lo, uint32_t hi, uint32_t a, uint32_t b, uint32_t c, uint32_t d) {
    asm volatile("{\n.reg .b64 a;\nmov.b64 a, {%0,%1};\nst.relaxed.gpu.global.v4.u32 [a+%6], {%2,%3,%4,%5};\n}"
                 ::"r"(lo), "r"(hi), "r"(a), "r"(b), "r"(c), "r"(d), "n"(OFF) : "memory");
}
template <uint32_t OFF> DEVI void stg2(uint32_t lo, uint32_t hi, uint32_t a, uint32_t b) {
    asm volatile("{\n.reg .b64 a;\nmov.b64 a, {%0,%1};\nst.relaxed.gpu.global.v2.u32 [a+%4], {%2,%3};\n}"
                 ::"r"(lo), "r"(hi), "r"(a), "r"(b), "n"(OFF) : "memory");
}
DEVI uint32_t tagx2(uint32_t a, uint32_t b, uint32_t t) { uint32_t r; asm("lop3.b32 %0, %1, %2, %3, 0x7E;" : "=r"(r) : "r"(a), "r"(b), "r"(t)); return r; }
DEVI uint32_t tagx1(uint32_t a, uint32_t b, uint32_t t) { uint32_t r; asm("lop3.b32 %0, %1, %2, %3, 0xF6;" : "=r"(r) : "r"(a), "r"(b), "r"(t)); return r; }
DEVI uint32_t or3(uint32_t a, uint32_t b, uint32_t c) { uint32_t r; asm("lop3.b32 %0, %1, %2, %3, 0xFE;" : "=r"(r) : "r"(a), "r"(b), "r"(c)); return r; }
DEVI bool any_bad(uint32_t x) { return __any_sync(0xFFFFFFFFu, (x & 1u) != 0); }
DEVI uint32_t settag(uint32_t x, uint32_t tag) { return (x & ~1u) | tag; }
DEVI void sts32f(uint32_t a, float v) { asm volatile("st.shared.f32 [%0], %1;" ::"r"(a), "f"(v) : "memory"); }
DEVI void sts32(uint32_t a, uint32_t v) { asm volatile("st.shared.u32 [%0], %1;" ::"r"(a), "r"(v) : "memory"); }
DEVI void sts16(uint32_t a, uint32_t v) { asm volatile("st.shared.u16 [%0], %1;" ::"r"(a), "h"((unsigned short)v) : "memory"); }
DEVI void sts64(uint32_t a, uint32_t x, uint32_t y) { asm volatile("st.shared.v2.u32 [%0], {%1,%2};" ::"r"(a), "r"(x), "r"(y) : "memory"); }
DEVI void sts128(uint32_t a, uint32_t x, uint32_t y, uint32_t z, uint32_t w) {
    asm volatile("st.shared.v4.u32 [%0], {%1,%2,%3,%4};" ::"r"(a), "r"(x), "r"(y), "r"(z), "r"(w) : "memory");
}
DEVI float4 lds128f(uint32_t a) {
    float4 v;
    asm volatile("ld.shared.v4.f32 {%0,%1,%2,%3}, [%4];" : "=f"(v.x), "=f"(v.y), "=f"(v.z), "=f"(v.w) : "r"(a) : "memory");
    return v;
}
DEVI uint4 lds128(uint32_t a) {
    uint4 v;
    asm volatile("ld.shared.v4.u32 {%0,%1,%2,%3}, [%4];" : "=r"(v.x), "=r"(v.y), "=r"(v.z), "=r"(v.w) : "r"(a) : "memory");
    return v;
}
DEVI uint2 lds64(uint32_t a) {
    uint2 v;
    asm volatile("ld.shared.v2.u32 {%0,%1}, [%2];" : "=r"(v.x), "=r"(v.y) : "r"(a) : "memory");
    return v;
}
DEVI uint32_t lds32(uint32_t a) {
    uint32_t v;
    asm volatile("ld.shared.u32 %0, [%1];" : "=r"(v) : "r"(a) : "memory");
    return v;
}
DEVI float ex2(float x) { float r; asm("ex2.approx.ftz.f32 %0, %1;" : "=f"(r) : "f"(x)); return r; }
DEVI float rcp(float x) { float r; asm("rcp.approx.ftz.f32 %0, %1;" : "=f"(r) : "f"(x)); return r; }
DEVI uint32_t clk() { uint32_t c; asm volatile("mov.u32 %0, %%clock;" : "=r"(c)::"memory"); return c; }

DEVI uint64_t mkdesc(uint32_t addr, uint32_t lbo, uint32_t sbo) {
    return (uint64_t)((addr & 0x3FFFF) >> 4) | ((uint64_t)(lbo >> 4) << 16) | ((uint64_t)(sbo >> 4) << 32) | ((uint64_t)1 << 62);
}
DEVI void wg_fence() { asm volatile("wgmma.fence.sync.aligned;" ::: "memory"); }
DEVI void wg_commit() { asm volatile("wgmma.commit_group.sync.aligned;" ::: "memory"); }
template <int N> DEVI void wg_wait() { asm volatile("wgmma.wait_group.sync.aligned %0;" ::"n"(N) : "memory"); }
template <int SC>
DEVI void wg_rs32(float (&d)[16], const uint32_t (&a)[4], uint64_t db) {
    if (SC) {
        asm volatile("wgmma.mma_async.sync.aligned.m64n32k16.f32.bf16.bf16 "
                     "{%0,%1,%2,%3,%4,%5,%6,%7,%8,%9,%10,%11,%12,%13,%14,%15}, {%16,%17,%18,%19}, %20, 1, 1, 1, 0;"
                     : "+f"(d[0]), "+f"(d[1]), "+f"(d[2]), "+f"(d[3]), "+f"(d[4]), "+f"(d[5]), "+f"(d[6]), "+f"(d[7]),
                       "+f"(d[8]), "+f"(d[9]), "+f"(d[10]), "+f"(d[11]), "+f"(d[12]), "+f"(d[13]), "+f"(d[14]), "+f"(d[15])
                     : "r"(a[0]), "r"(a[1]), "r"(a[2]), "r"(a[3]), "l"(db));
    } else {
        asm volatile("wgmma.mma_async.sync.aligned.m64n32k16.f32.bf16.bf16 "
                     "{%0,%1,%2,%3,%4,%5,%6,%7,%8,%9,%10,%11,%12,%13,%14,%15}, {%16,%17,%18,%19}, %20, 0, 1, 1, 0;"
                     : "=f"(d[0]), "=f"(d[1]), "=f"(d[2]), "=f"(d[3]), "=f"(d[4]), "=f"(d[5]), "=f"(d[6]), "=f"(d[7]),
                       "=f"(d[8]), "=f"(d[9]), "=f"(d[10]), "=f"(d[11]), "=f"(d[12]), "=f"(d[13]), "=f"(d[14]), "=f"(d[15])
                     : "r"(a[0]), "r"(a[1]), "r"(a[2]), "r"(a[3]), "l"(db));
    }
}

#define NPRO 5
#define NA 12
#define NB 0
#define NPF 6
#define PF1 2
#define PF2 2
#define PF3 5
#define WPF 2
#define NPE (NPF & ~1)
#define VPF 2
#define VORD (NA == 12 ? 0x01234567 : NA == 10 ? 0x50123467 : NA == 8 ? 0x40125367 : 0x30142567)
#define WV_BOX ((16 - NA) * 2048)
#define WO_BOX ((16 - NB) * 1024)
#define SM_WV 0
#define SM_WO (2 * WV_BOX)
#define SM_X (SM_WO + 4 * WO_BOX)
#define SM_XO (SM_X + 32768)
#define SM_PI (SM_XO + 12288)
#define SM_KV (SM_PI + 24576)
#define SM_SP (SM_KV + 18432)
#define SM_TR (SM_SP + 10240)
#define SM_MEMT (SM_TR + 12288)
#define SM_OT (SM_MEMT + 4096)
#define SM_VS (SM_OT + 2048)
#define SM_P (SM_VS + 2048)
#define SM_DN (SM_P + 1792)
#define SM_PROF (SM_P + 2048)
#define SM_BAR 232192
#define SM_TOTAL (SM_BAR + 256)
#define SM_STA SM_X
#define SM_STB (SM_STA + 65536)
#define SM_STC (SM_STB + 65536)
#define NA1_ ((SM_BAR - SM_STC) / 4096)
#define NA1 (NA < NA1_ ? NA : NA1_)
static_assert(SM_STC + NA1 * 4096 <= SM_BAR && NB + NA - NA1 <= 16 && SM_PROF + 3072 <= SM_BAR, "staging");
static_assert(SM_TOTAL <= 232448, "smem");
#define BAR_XA 32
#define BAR_KV 40
#define BAR_PI 48
#define SM_ROLE (SM_BAR + 64)

#define SPIN_LIMIT (1 << 20)
#define RPOS 20
#define OPOS 2
#define ASF 0
#define KPOS 0
#define CPOS 1
#define DLY_V 400
#define CFAR 1

template <int ID, int N> DEVI void bsync() { asm volatile("bar.sync %0, %1;" ::"n"(ID), "n"(N) : "memory"); }
template <int ID, int N> DEVI void barv() { asm volatile("bar.arrive %0, %1;" ::"n"(ID), "n"(N) : "memory"); }

#define PT(n)
#define PC(n, v)
#define PDUMP()
#define REFRESH() asm volatile("xor.b32 %0, %0, %1;" : "+r"(l16) : "r"(zero))
#define OPQ(x) asm volatile("xor.b32 %0, %0, %1;" : "+r"(x) : "r"(zero))
#define KEEP(x, a, b, c, d) asm volatile("{\n.reg .b32 t;\nlop3.b32 t, %1, %2, %3, 0x80;\nlop3.b32 t, t, %4, %5, 0x80;\nxor.b32 %0, %0, t;\n}" \
                                         : "+r"(x) : "r"(a), "r"(b), "r"(c), "r"(d), "r"(zero))
#define SF() asm volatile("pmevent 1;" ::: "memory")
#define MF() __syncwarp()
#define SB0 1024u

#define XDOFF(ks) ((((ks) >> 2) * 1024 + ((ks) & 3) * 32) >> 4)
template <int SC>
DEVI void wg_ss32t(float (&d)[16], uint64_t da, uint64_t db) {
    if (SC) {
        asm volatile("wgmma.mma_async.sync.aligned.m64n32k16.f32.bf16.bf16 "
                     "{%0,%1,%2,%3,%4,%5,%6,%7,%8,%9,%10,%11,%12,%13,%14,%15}, %16, %17, 1, 1, 1, 1, 0;"
                     : "+f"(d[0]), "+f"(d[1]), "+f"(d[2]), "+f"(d[3]), "+f"(d[4]), "+f"(d[5]), "+f"(d[6]), "+f"(d[7]),
                       "+f"(d[8]), "+f"(d[9]), "+f"(d[10]), "+f"(d[11]), "+f"(d[12]), "+f"(d[13]), "+f"(d[14]), "+f"(d[15])
                     : "l"(da), "l"(db));
    } else {
        asm volatile("wgmma.mma_async.sync.aligned.m64n32k16.f32.bf16.bf16 "
                     "{%0,%1,%2,%3,%4,%5,%6,%7,%8,%9,%10,%11,%12,%13,%14,%15}, %16, %17, 0, 1, 1, 1, 0;"
                     : "=f"(d[0]), "=f"(d[1]), "=f"(d[2]), "=f"(d[3]), "=f"(d[4]), "=f"(d[5]), "=f"(d[6]), "=f"(d[7]),
                       "=f"(d[8]), "=f"(d[9]), "=f"(d[10]), "=f"(d[11]), "=f"(d[12]), "=f"(d[13]), "=f"(d[14]), "=f"(d[15])
                     : "l"(da), "l"(db));
    }
}

DEVI void delay_until(uint32_t t0, uint32_t d) { t0 += d; while (clk() < t0) {} }

template <int I0, int I1>
DEVI void xmma(float (&xa)[16], float (&xb)[16], uint32_t w, int ps, uint32_t zero, const uint32_t (&Wq)[16][4], const uint32_t (&Wk)[16][4],
               const uint32_t (&Wv)[NA][4]) {
    const uint64_t xd = mkdesc(SB0 + SM_X, 16, 4096) + (ps & 1) * 1024, vd = mkdesc(SB0 + SM_WV, 8192, 1024);
    uint32_t vo = (w >> 2) * (WV_BOX / 16);
    if (I0 < 16 - NA) OPQ(vo);
#pragma unroll
    for (int i = I0; i < I1; i++) {
        if (i == 0) wg_ss32t<0>(xb, (vd & ~0xFFFFFFFFull) | ((uint32_t)vd + vo), xd + XDOFF(NA));
        else if (i < 16 - NA) wg_ss32t<1>(xb, (vd & ~0xFFFFFFFFull) | ((uint32_t)vd + i * 128 + vo), xd + XDOFF(NA + i));
        else if (i == 16 - NA) wg_rs32<0>(xa, Wq[0], xd);
        else if (i < 32 - NA) wg_rs32<1>(xa, Wq[(i + NA) & 15], xd + XDOFF((i + NA) & 15));
        else if (i < 32) wg_rs32<1>(xb, Wv[(i + NA) & 15], xd + XDOFF((i + NA) & 15));
        else if (i == 32) wg_rs32<0>(xa, Wk[0], xd);
        else wg_rs32<1>(xa, Wk[i & 15], xd + XDOFF(i & 15));
    }
    wg_commit();
}
#define XMMA(I0, I1) xmma<(I0), (I1)>(xa, xb, w, p ^ 1, zero, Wq, Wk, Wv)
DEVI void wg_done(float (&d)[16]) {
    asm volatile("" : "+f"(d[0]), "+f"(d[1]), "+f"(d[2]), "+f"(d[3]), "+f"(d[4]), "+f"(d[5]), "+f"(d[6]), "+f"(d[7]),
                      "+f"(d[8]), "+f"(d[9]), "+f"(d[10]), "+f"(d[11]), "+f"(d[12]), "+f"(d[13]), "+f"(d[14]), "+f"(d[15]) :: "memory");
}
template <int M>
DEVI void xpack(uint32_t (&xp)[8], float (&xa)[16]) {
    wg_done(xa);
#pragma unroll
    for (int i = 0; i < 4; i++) {
        xp[2 * i] = pack2(xa[4 * i], xa[4 * i + (M < 2 ? 2 : 1)]);
        xp[2 * i + 1] = pack2(xa[4 * i + (M < 2 ? 1 : 2)], xa[4 * i + 3]);
    }
}
template <int M>
DEVI uint4 xpeer(uint32_t sb, int ps, uint32_t t16) { return lds128(sb + SM_PI + ((ps & 1) ^ 1) * 12288 + M * 4096 + t16); }
DEVI void xadd(uint32_t (&xp)[8], const uint4& pi) {
    xp[0] = hadd2(xp[0], pi.x); xp[1] = hadd2(xp[1], pi.y); xp[2] = hadd2(xp[2], pi.z); xp[3] = hadd2(xp[3], pi.w);
}
template <int M>
DEVI void xstore(const uint32_t (&xp)[8], uint32_t sb, uint32_t sbw, int ps, uint32_t t16, uint32_t KA) {
    const uint32_t a = SM_XO + M * 2048 + (M < 2 ? (KA & 0xFF) + sbw : (t16 >> 1) + sb);
    sts64(a, xp[0], xp[1]);
    sts64(a + 6144, xp[2], xp[3]);
    asm volatile("st.async.weak.shared::cluster.mbarrier::complete_tx::bytes.v4.b32 [%0], {%1,%2,%3,%4}, [%5];"
                 ::"r"((sb ^ 0x1000000) + SM_PI + (ps & 1) * 12288 + M * 4096 + t16), "r"(xp[4]), "r"(xp[5]), "r"(xp[6]), "r"(xp[7]),
                   "r"((sb ^ 0x1000000) + SM_BAR + BAR_PI + (ps & 1) * 8) : "memory");
}
template <int M>
DEVI void xpark(uint32_t (&xp)[8], const uint4& pi, uint32_t sb, uint32_t sbw, int ps, uint32_t t16, uint32_t KA) {
    xadd(xp, pi);
    xstore<M>(xp, sb, sbw, ps, t16, KA);
}
template <int M>
DEVI void xfinish(float (&xa)[16], uint32_t sb, uint32_t sbw, int ps, uint32_t t16, uint32_t KA) {
    uint32_t xp[8];
    const uint4 pi = xpeer<M>(sb, ps, t16);
    xpack<M>(xp, xa);
    xpark<M>(xp, pi, sb, sbw, ps, t16, KA);
}
DEVI void piwait(uint32_t sb, int p, int ps) { mbar_wait(sb + SM_BAR + BAR_PI + p * 8, ((ps + NPRO + 1) >> 1) & 1); }

DEVI uint32_t par(uint32_t off) { return __popc(off & 0xB2000u) & 1; }
DEVI uint32_t probe(uint32_t lo, uint32_t hi) {
    uint32_t best = 0xFFFFFFFFu, x = 0;
    stg1<0>(lo, hi, 0);
#pragma unroll 1
    for (int r = 0; r < 4; r++) {
        const uint32_t t0 = clk();
        asm volatile("{\n.reg .b64 a;\nmov.b64 a, {%1,%2};\natom.relaxed.gpu.global.add.u32 %0, [a], 2;\n}" : "=r"(x) : "r"(lo), "r"(hi) : "memory");
        if (x == 0xFFFFFFFFu) die(1 << 23);
        best = min(best, clk() - t0);
    }
    return best;
}

DEVI void xload(uint32_t sb, uint32_t u, uint32_t j, int ps, const CUtensorMap* tmx) {
    if (elect()) {
        const uint32_t sg = ps + 4 - (u & 1) + (u >> 1);
        mbar_expect(sb + SM_BAR + BAR_XA, sg < NSEG ? 4096 : 0);
        if (sg < NSEG) tma3d(sb + SM_X + (ps & 1) * 16384 + u * 4096, tmx, sb + SM_BAR + BAR_XA, 0, sg * 32 + (j ^ ((u & 1) * 2 + (u >> 1))) * 8, j * 4);
    }
}
DEVI uint32_t rpage(uint32_t j, int s) { return (s & 3) * 65536 + (j & 1) * 8192 + (((s ^ (s >> 1) ^ j ^ (j >> 1)) & 1) << 12); }

#define RLOAD(a) { m0 = ldg4<XO_R>(a, xhi); n0 = ldg4<XO_R + 16384>(a, xhi); \
                   e0 = ldg1<XO_R + 32768>(((a) & ~0xFFFu) + (((a) & 0xFFF) >> 2), xhi); f0 = ldg1<XO_R + 33792>(((a) & ~0xFFFu) + (((a) & 0xFFF) >> 2), xhi); }
DEVI bool ruse(uint32_t a, const uint4& m0, const uint4& n0, uint32_t e0, uint32_t f0) {
    const uint32_t a0 = hadd2(m0.w, n0.w), b0 = hadd2(e0, f0);
    stsm4(a, hadd2(m0.x, n0.x), hadd2(m0.y, n0.y), hadd2(m0.z, n0.z), __byte_perm(a0, b0, 0x5410));
    return __any_sync(0xFFFFFFFFu, (a0 & b0 & 0x42000000u) != 0x42000000u);
}

#define GST(i) (SM_WO + (i) * 49152)
#define BAR_GF 128
#define BAR_GE (BAR_GF + 64)
#define BAR_GX (BAR_GE + 32)
#define D4(c, i) #c "f"(d[i]), #c "f"(d[i + 1]), #c "f"(d[i + 2]), #c "f"(d[i + 3])
#define D16(c, i) D4(c, i), D4(c, i + 4), D4(c, i + 8), D4(c, i + 12)
DEVI void mwait(uint32_t bar, uint32_t parity) {
    asm volatile("{\n.reg .pred p;\n.reg .b32 c;\nmbarrier.try_wait.parity.shared::cta.b64 p, [%0], %1;\n@p bra.uni D;\nmov.b32 c, 0;\n"
                 "L:\nadd.u32 c, c, 1;\nsetp.gt.u32 p, c, 4194304;\n@p st.shared.u32 [c], c;\n"
                 "mbarrier.try_wait.parity.shared::cta.b64 p, [%0], %1;\n@!p bra.uni L;\nD:\n}" ::"r"(bar), "r"(parity) : "memory");
}
DEVI void wg_ss256t(float (&d)[128], uint64_t da, uint64_t db) {
    asm volatile("wgmma.mma_async.sync.aligned.m64n256k16.f32.bf16.bf16 "
        "{%0,%1,%2,%3,%4,%5,%6,%7,%8,%9,%10,%11,%12,%13,%14,%15,%16,%17,%18,%19,%20,%21,%22,%23,%24,%25,%26,%27,%28,%29,%30,%31,%32,%33,%34,%35,%36,%37,%38,%39,%40,%41,%42,%43,%44,%45,%46,%47,%48,%49,%50,%51,%52,%53,%54,%55,%56,%57,%58,%59,%60,%61,%62,%63,%64,%65,%66,%67,%68,%69,%70,%71,%72,%73,%74,%75,%76,%77,%78,%79,%80,%81,%82,%83,%84,%85,%86,%87,%88,%89,%90,%91,%92,%93,%94,%95,%96,%97,%98,%99,%100,%101,%102,%103,%104,%105,%106,%107,%108,%109,%110,%111,%112,%113,%114,%115,%116,%117,%118,%119,%120,%121,%122,%123,%124,%125,%126,%127}, "
        "%128, %129, 1, 1, 1, 1, 1;"
        : D16(+, 0), D16(+, 16), D16(+, 32), D16(+, 48), D16(+, 64), D16(+, 80), D16(+, 96), D16(+, 112) : "l"(da), "l"(db));
}
template <int O, int KB> DEVI void g_half(float (&d)[64], uint64_t da) {
    const uint64_t db = mkdesc(SB0 + GST(KB & 3) + 16384 + O * 256, 8192, 1024);
#pragma unroll
    for (int k = 0; k < 4; k++)
        asm volatile("wgmma.mma_async.sync.aligned.m64n128k16.f32.bf16.bf16 "
            "{%0,%1,%2,%3,%4,%5,%6,%7,%8,%9,%10,%11,%12,%13,%14,%15,%16,%17,%18,%19,%20,%21,%22,%23,%24,%25,%26,%27,%28,%29,%30,%31,%32,%33,%34,%35,%36,%37,%38,%39,%40,%41,%42,%43,%44,%45,%46,%47,%48,%49,%50,%51,%52,%53,%54,%55,%56,%57,%58,%59,%60,%61,%62,%63}, "
            "%64, %65, 1, 1, 1, 1, 1;"
            : D16(+, 0), D16(+, 16), D16(+, 32), D16(+, 48) : "l"(da + (KB & 3) * 3072 + k * 16), "l"(db + k * 128));
}
DEVI void g_load(uint32_t sb, uint32_t u, uint32_t role, uint32_t kb, uint32_t xlo, uint32_t xhi, const CUtensorMap* tmb) {
    const uint32_t st = kb & 3, bar = sb + SM_BAR + BAR_GF + u * 32 + st * 8, dst = sb + GST(st), k = (role & 1) * 32 + kb;
    mbar_expect(bar, u ? 8192 : 40960);
    bulk_g2s(dst + u * 8192, xlo + XO_OX + ((role >> 3) * 64 + k) * 16384 + u * 8192, xhi, 8192, bar);
    if (u == 0) {
        tma3d(dst + 16384, tmb, bar, 0, k * 64, ((role & 7) ^ 1) * 2);
        tma3d(dst + 32768, tmb, bar, 0, k * 64, (role & 7) * 2);
    }
}
DEVI void g_arrive(uint32_t a, uint32_t xhi) {
    asm volatile("{\n.reg .b64 a;\nmov.b64 a, {%0,%1};\nred.release.gpu.global.add.u32 [a], 1;\n}" ::"r"(a), "r"(xhi) : "memory");
}
template <uint32_t N> DEVI void g_wait(uint32_t a, uint32_t xhi) {
    int it = 0;
    uint32_t v;
    do {
        asm volatile("{\n.reg .b64 a;\nmov.b64 a, {%1,%2};\nld.acquire.gpu.global.u32 %0, [a];\n}" : "=r"(v) : "r"(a), "r"(xhi) : "memory");
        if (++it > SPIN_LIMIT) die(it);
    } while (v % N);
    asm volatile("fence.proxy.async.global;" ::: "memory");
}
#define GD 200
DEVI void g_done(float (&d)[64]) { asm volatile("" : D16(+, 0), D16(+, 16), D16(+, 32), D16(+, 48)::"memory"); }
DEVI void g_main(uint32_t sb, uint32_t w, uint32_t role, const CUtensorMap* tmy) {
    const uint32_t bar = sb + SM_BAR, t16 = threadIdx.x * 16;
    const uint64_t da = (mkdesc(SB0 + GST(0), 128, 1024) & ~((uint64_t)3 << 62)) + (w >> 2) * 512;
    float d[128];
#pragma unroll
    for (int i = 0; i < 128; i++) d[i] = 0.f;
#define GFULL(kb) { mwait(bar + BAR_GF + ((kb) & 3) * 8, ((kb) >> 2) & 1); if (w >= 4) mwait(bar + BAR_GF + 32 + ((kb) & 3) * 8, ((kb) >> 2) & 1); }
#pragma unroll 1
    for (uint32_t kb = 0; kb < 29; kb++) {
        GFULL(kb);
        if (kb == 0 && threadIdx.x == 128) PG(4);
        if (kb == 4 && threadIdx.x == 0) PG(5);
        const uint64_t a = da + (kb & 3) * 3072, b = mkdesc(SB0 + GST(0) + 16384, 8192, 1024) + (kb & 3) * 3072;
        wg_fence();
#pragma unroll
        for (int k = 0; k < 4; k++) wg_ss256t(d, a + k * 16, b + k * 128);
        wg_commit();
        wg_wait<1>();
        if (kb > 0 && elect()) mbar_arrive(bar + BAR_GE + ((kb - 1) & 3) * 8);
    }
    GFULL(29);
    GFULL(30);
    GFULL(31);
    wg_wait<0>();
    float x[64], y[64];
#pragma unroll
    for (int i = 0; i < 64; i++) asm volatile("mov.b32 %0, %1;" : "=f"(x[i]) : "f"(d[i]) : "memory");
    SF();
#pragma unroll
    for (int i = 0; i < 64; i++) asm volatile("mov.b32 %0, %1;" : "=f"(y[i]) : "f"(d[i + 64]) : "memory");
    SF();
    if (elect()) asm volatile("mbarrier.arrive.relaxed.cluster.shared::cluster.b64 _, [%0];" ::"r"((bar ^ 0x1000000) + BAR_GX) : "memory");
    wg_fence();
    g_half<0, 29>(x, da);
    g_half<0, 30>(x, da);
    g_half<0, 31>(x, da);
    wg_commit();
    g_half<64, 29>(y, da);
    wg_commit();
    wg_wait<1>();
    g_done(x);
    mwait(bar + BAR_GX, 0);
#define GSEND(i0) _Pragma("unroll") for (int i = (i0); i < (i0) + 4; i++) \
        asm volatile("st.async.weak.shared::cluster.mbarrier::complete_tx::bytes.v4.b32 [%0], {%1,%2,%3,%4}, [%5];" \
                     ::"r"((sb ^ 0x1000000) + i * 4096 + t16), "r"(pack2(x[8 * i], x[8 * i + 1])), "r"(pack2(x[8 * i + 2], x[8 * i + 3])), \
                       "r"(pack2(x[8 * i + 4], x[8 * i + 5])), "r"(pack2(x[8 * i + 6], x[8 * i + 7])), "r"((bar ^ 0x1000000) + BAR_GX + 8) : "memory")
    GSEND(0);
    wg_fence();
    g_half<64, 30>(y, da);
    wg_commit();
    GSEND(4);
    wg_fence();
    g_half<64, 31>(y, da);
    wg_commit();
    wg_wait<0>();
    g_done(y);
    if (threadIdx.x == 0) PG(7);
    mwait(bar + BAR_GX + 8, 0);
    if (threadIdx.x == 0) PG(1);
    const uint32_t lane = threadIdx.x & 31, o = sb + GST(1) + w * 2048;
#pragma unroll
    for (int i = 0; i < 8; i++) {
        const uint4 a = lds128(sb + i * 4096 + t16);
        const float* e = y + 8 * i;
        stsm4(o + (i >> 2) * 49152 + (lane & 15) * 128 + ((((i & 3) * 2 + (lane >> 4)) ^ (lane & 7)) << 4),
              pack2(e[0] + lo_f(a.x), e[1] + hi_f(a.x)), pack2(e[2] + lo_f(a.y), e[3] + hi_f(a.y)),
              pack2(e[4] + lo_f(a.z), e[5] + hi_f(a.z)), pack2(e[6] + lo_f(a.w), e[7] + hi_f(a.w)));
        if (i == 3 || i == 7) {
            asm volatile("fence.proxy.async.shared::cta;" ::: "memory");
            __syncwarp();
            if (elect())
                asm volatile("cp.async.bulk.tensor.2d.global.shared::cta.bulk_group [%0, {%2, %3}], [%1];\ncp.async.bulk.commit_group;"
                             ::"l"(tmy), "r"(o + (i >> 2) * 49152), "r"((role & 7) * 128 + (i >> 2) * 64), "r"((role >> 3) * 128 + w * 16) : "memory");
        }
    }
    if (threadIdx.x == 0) PG(6);
    asm volatile("cp.async.bulk.wait_group.read 0;" ::: "memory");
}

template <bool MAIN>
DEVI void helper_step(uint32_t sb, uint32_t w, uint32_t h, uint32_t j, uint32_t& l16, uint32_t xlo, uint32_t xhi, uint32_t zero, int s,
                      const CUtensorMap* tmx, const CUtensorMap* tmb, const bf16* __restrict__ mem0) {
    const uint32_t u = w - 8, bq = sb + SM_BAR;
    bsync<1, 384>();
    PT(0);
    PDUMP();
    PT(1);
    if (MAIN) {
        if (s == NSEG - 2 && u < 2 && l16 == 0) g_arrive(xlo + XO_TK + 128, xhi);
        __syncwarp();
        const uint32_t ctag = ((s >> 1) & 1) ^ 1;
        const uint32_t av = xlo + ((s & 1) * 32 + h) * 8192 + u * 512;
        mbar_wait(bq + BAR_XA, (s + NPRO) & 1);
        bsync<8, 384>();
        delay_until(clk(), DLY_V);
        PT(4);
        int it = 0;
        bool bad;
        do {
            const uint4 d1 = ldg4<XO_CV>(av + (j ^ 1) * 2048 + l16, xhi);
            const uint4 d2 = ldg4<XO_CV>(av + (j ^ 2) * 2048 + l16, xhi);
            const uint4 d3 = ldg4<XO_CV>(av + (j ^ 3) * 2048 + l16, xhi);
            bad = any_bad(or3(tagx2(d1.x, d1.z, ctag), tagx2(d2.x, d2.z, ctag), tagx2(d3.x, d3.z, ctag)));
            sts128(sb + SM_VS + u * 512 + l16, hadd2(hadd2(d1.x, d2.x), d3.x), hadd2(hadd2(d1.y, d2.y), d3.y), hadd2(hadd2(d1.z, d2.z), d3.z),
                   hadd2(hadd2(d1.w, d2.w), d3.w));
            REFRESH();
            if (++it > SPIN_LIMIT) die(it);
        } while (bad);
        PC(26, it - 1);
    } else {
        if (u == 0) stg2<XO_FL>(xlo + ((s + NPRO) * 128 + h * 4 + j) * 32, xhi, 1, 1);
        if (s == -NPRO) {
            xload(sb, u, j, s, tmx);
#pragma unroll 1
            for (int e = 0; e < 4; e++) sts128(sb + SM_TR + 4096 + e * 2048 + u * 512 + l16, 0, 0, 0, 0);
        }
        if (s == -1) {
#pragma unroll 1
            for (int e = 0; e < 2; e++) {
                const uint32_t d = e * 128 + u * 32 + (l16 >> 4);
                const unsigned short* m0 = (const unsigned short*)mem0 + j * 256 + d;
                uint32_t v[4];
#pragma unroll
                for (int i = 0; i < 4; i++) v[i] = (uint32_t)m0[(2 * i) * DM] | ((uint32_t)m0[(2 * i + 1) * DM] << 16);
                sts128(sb + SM_MEMT + d * 16, v[0], v[1], v[2], v[3]);
            }
        }
        mbar_wait(bq + BAR_XA, (s + NPRO) & 1);
    }
    PT(5);
    barv<5, 384>();
    bsync<3, 384>();
    if (!MAIN) {
        int it = 0;
        while (__any_sync(0xFFFFFFFFu, ldg2<XO_FL>(xlo + ((s + NPRO) * 128 + h * 4) * 32 + ((l16 & 0x30) << 1), xhi).x == 0))
            if (++it > SPIN_LIMIT) die(it);
    }
    if (u < 2) {
        asm volatile("fence.proxy.async.shared::cta;" ::: "memory");
        if (elect()) {
            const uint32_t sg = s + 3 - u;
            if (sg < NSEG) {
                const uint32_t ga = xlo + XO_XG + (((sg & 7) * 32 + h) * 4 + (j ^ (2 * u))) * 6144, sa = sb + SM_XO + u * 6144;
                if (u == 0) bulk_s2g(ga, xhi, sa, 6144);
                else bulk_red(ga, xhi, sa, 6144);
            }
        }
    }
    PT(6);
    uint32_t old = 0;
    if (MAIN && u > 0) asm volatile("{\n.reg .b64 a;\nmov.b64 a, {%1,%2};\natom.relaxed.gpu.global.exch.b32 %0, [a], 0;\n}"
                                    : "=r"(old) : "r"(xlo + XO_R + rpage(j, s + 2) + (u - 1) * 16384 + h * 128 + (l16 >> 2)), "r"(xhi) : "memory");
    PT(7);
    if (MAIN) bsync<7, 384>();
    if (s >= -1 && s + 1 < NSEG && elect()) {
        const uint32_t o = u == 0 ? 0 : 2048;
        mbar_expect(bq + BAR_KV, 6144 - o);
        bulk_g2s(sb + SM_KV + u * 4096 + o, xlo + XO_XG + ((((s + 1) & 7) * 32 + h) * 4 + ((j + u) & 3)) * 6144 + o, xhi, 6144 - o, bq + BAR_KV);
    }
    if (u < 2) {
        asm volatile("cp.async.bulk.wait_group.read 0;" ::: "memory");
        if (elect()) mbar_expect(bq + BAR_PI + ((s & 1) ^ 1) * 8, !MAIN && s == -NPRO ? 0 : 6144);
    }
    PT(8);
    if (MAIN && s + 1 < NSEG) bsync<10, 384>();
    xload(sb, u, j, s + 1, tmx);
    if (MAIN && s == NSEG - 2 && l16 == 0 && (u == 0 || (u == 1 && h < 30))) {
        g_wait<256>(xlo + XO_TK + 128, xhi);
        g_load(sb, u, h * 4 + j, 0, xlo, xhi, tmb);
        g_load(sb, u, h * 4 + j, 1, xlo, xhi, tmb);
    }
    __syncwarp();
    asm volatile("cp.async.bulk.wait_group 0;" ::: "memory");
    if (s >= -1 && s + 1 < NSEG) mbar_wait(bq + BAR_KV, (s + 1) & 1);
    asm volatile("lop3.b32 %0, %0, %1, %2, 0x78;" : "+r"(l16) : "r"(old), "r"(zero));
    PT(15);
}

__global__ void __cluster_dims__(2, 1, 1) __launch_bounds__(384, 1)
chain_kernel(const __grid_constant__ CUtensorMap tmq, const __grid_constant__ CUtensorMap tmk,
             const __grid_constant__ CUtensorMap tmv, const __grid_constant__ CUtensorMap tmo,
             const __grid_constant__ CUtensorMap tmx, const __grid_constant__ CUtensorMap tmb, const __grid_constant__ CUtensorMap tmy,
             const bf16* __restrict__ mem0, const bf16* __restrict__ xg,
             uint32_t xlo, uint32_t xhi, uint32_t zero, int nseg) {
    extern __shared__ __align__(1024) uint8_t smem[];
    if ((smem_u32(smem) & 0xFFFFFF) != SB0) die(1 << 23);
    asm volatile("griddepcontrol.launch_dependents;" ::: "memory");
    const uint32_t w = __reduce_max_sync(0xFFFFFFFFu, threadIdx.x >> 5);
    const uint32_t rk = smem_u32(smem) & 0x1000000;
    const uint32_t sb = __reduce_max_sync(0xFFFFFFFFu, smem_u32(smem));
    const uint32_t bq = sb + SM_BAR, bk = bq + 8, bv = bq + 16, bo = bq + 24;
    uint32_t l16 = __shfl_sync(0xFFFFFFFFu, (threadIdx.x & 31) * 16, threadIdx.x & 31);
    if (threadIdx.x == 0) {
        mbar_init(bq, 1); mbar_init(bk, 1); mbar_init(bv, 1); mbar_init(bo, 2);
        mbar_init(bq + BAR_XA, 4); mbar_init(bq + BAR_KV, 4); mbar_init(bq + BAR_PI, 2); mbar_init(bq + BAR_PI + 8, 2);
        for (int i = 0; i < 14; i++) mbar_init(bq + BAR_GF + i * 8, i < 8 || i == 13 ? 1 : 8);
        mbar_expect(bq + BAR_GX + 8, 32768);
        asm volatile("fence.mbarrier_init.release.cluster;" ::: "memory");
        asm volatile("fence.proxy.async.shared::cta;" ::: "memory");
    }
    if (rk == 0) {
        if (w < 2 && l16 == 0) sts32(sb + SM_ROLE + w * 4, probe(xlo + XO_PB + w * 4096 + blockIdx.x * 16, xhi));
        __syncthreads();
        if (threadIdx.x == 0) {
            uint32_t side = (lds32(sb + SM_ROLE) < lds32(sb + SM_ROLE + 4) ? 0u : 1u) ^ par(XO_PB);
            uint32_t* tk = (uint32_t*)(((uint64_t)xhi << 32) | (xlo + XO_TK));
            uint32_t t = atomicAdd(tk + side, 1u);
            if (t >= 32) {
                uint2 c;
                int it = 0;
                do {
                    c = ldg2<XO_TK>(xlo, xhi);
                    if (++it > SPIN_LIMIT) die(it);
                } while (c.x + c.y != gridDim.x / 2);
                t += (side ? c.x : c.y) - 32;
                side ^= 1;
            }
            sts32(sb + SM_ROLE + 8, t * 4 + side * 2);
        }
    }
    __syncthreads();
    asm volatile("barrier.cluster.arrive.release.aligned;\nbarrier.cluster.wait.acquire.aligned;" ::: "memory");
    uint32_t role;
    asm volatile("ld.shared::cluster.u32 %0, [%1];" : "=r"(role) : "r"(SB0 + SM_ROLE + 8) : "memory");
    role = __reduce_max_sync(0xFFFFFFFFu, role) + (rk >> 24);
    asm volatile("barrier.cluster.arrive.release.aligned;\nbarrier.cluster.wait.acquire.aligned;" ::: "memory");
    if (role >= 128) return;
    const uint32_t h = role >> 2, j = role & 3;

    if (w >= 8) {
        asm volatile("setmaxnreg.dec.sync.aligned.u32 24;");
        if (w == 8) {
            if (elect()) {
                mbar_expect(bq, 65536);
                tma2d(sb + SM_STA, &tmq, bq, h * 128, j * 256);
                tma2d(sb + SM_STA + 32768, &tmq, bq, h * 128 + 64, j * 256);
                mbar_expect(bk, 65536);
                tma2d(sb + SM_STB, &tmk, bk, h * 128, j * 256);
                tma2d(sb + SM_STB + 32768, &tmk, bk, h * 128 + 64, j * 256);
                mbar_expect(bv, (16 - NA + NA1) * 4096);
#pragma unroll 1
                for (int i = 0; i < 32; i++) {
                    const int ks = i >> 1, g = i & 1;
                    if (ks < NA1 || ks >= NA)
                        tma2d((ks < NA ? sb + SM_STC + g * (NA1 * 2048) + ks * 2048 : sb + SM_WV + g * WV_BOX + (ks - NA) * 2048), &tmv, bv, h * 128 + g * 64, j * 256 + ks * 16);
                }
                mbar_expect(bo, 4 * WO_BOX);
#pragma unroll 1
                for (int i = 0; i < 32 - 2 * NB; i++) {
                    const int ks = i >> 2, g = i & 3;
                    tma2d(sb + SM_WO + g * WO_BOX + ks * 2048, &tmo, bo, j * 256 + g * 64, h * 128 + (ks < NPE / 2 ? ks : ks + NB / 2) * 16);
                }
            }
        }
        GSYNC(0);
        bsync<9, 384>();
        if (w == 8) {
            if (elect()) {
                mbar_expect(bo, (NB + NA - NA1) * 4096);
#pragma unroll 1
                for (int i = 2 * NA1; i < 2 * NA; i++) {
                    const int ks = i >> 1, g = i & 1;
                    tma2d(sb + SM_STA + NB * 4096 + g * ((NA - NA1) * 2048) + (ks - NA1) * 2048, &tmv, bo, h * 128 + g * 64, j * 256 + ks * 16);
                }
#pragma unroll 1
                for (int i = 0; i < 2 * NB; i++) {
                    const int ks = i >> 2, g = i & 3;
                    tma2d(sb + SM_STA + g * (NB * 1024) + ks * 2048, &tmo, bo, j * 256 + g * 64, h * 128 + (ks + NPE / 2) * 16);
                }
                asm volatile("cp.async.bulk.prefetch.L2.global [%0], %1;" ::"l"((const char*)xg + role * 32768), "r"(32768) : "memory");
            }
        }
#pragma unroll 1
        for (int s = -NPRO; s < 0; s++) helper_step<false>(sb, w, h, j, l16, xlo, xhi, zero, s, &tmx, &tmb, mem0);
#pragma unroll 1
        for (int s = 0; s < nseg; s++) helper_step<true>(sb, w, h, j, l16, xlo, xhi, zero, s, &tmx, &tmb, mem0);
        piwait(sb, 0, nseg - 2);
        bsync<9, 384>();
        GSYNC(1);
        if (w < 10 && l16 == 0) {
            uint32_t kb = 2;
            asm volatile("fence.proxy.async.shared::cta;" ::: "memory");
            if (w == 9) {
                g_arrive(xlo + XO_TK + 192, xhi);
                PG(2);
                if (h >= 30) { g_wait<128>(xlo + XO_TK + 192, xhi); kb = 0; }
                PG(3);
            } else delay_until(clk(), GD);
#pragma unroll 1
            for (; kb < 32; kb++) {
                if (kb >= 4) mbar_wait(bq + BAR_GE + (kb & 3) * 8, ((kb >> 2) & 1) ^ 1);
                g_load(sb, w - 8, role, kb, xlo, xhi, &tmb);
            }
        }
    } else {
        asm volatile("setmaxnreg.inc.sync.aligned.u32 240;");
        uint32_t Wq[16][4], Wk[16][4], Wv[NA][4], Wo[NB > 0 ? NB : 1][4];
        uint32_t t16, KA, KB, KC, KD;
        {
            const uint32_t lane = l16 >> 4, g = lane >> 2, t = lane & 3;
            const uint32_t rw = (((lane >> 4) & 1) * 8 + (lane & 7)) * 128u;
            const uint32_t off = rw + ((((w & 3) * 2 + ((lane >> 3) & 1)) ^ (lane & 7)) << 4);
            const uint32_t offo = rw + ((((w & 1) * 4 + ((lane >> 3) & 1)) ^ (lane & 7)) << 4);
            const uint32_t r = 2 * (t & 1) + (g >> 2);
            const uint32_t mk0 = t < 2 ? 0 : (r == 0 ? 2 * g > w : j + r < 4), mk1 = t < 2 ? 0 : (r == 0 ? 2 * g + 1 > w : j + r < 4);
            t16 = __shfl_sync(0xFFFFFFFFu, w * 512 + l16, lane);
            KA = __shfl_sync(0xFFFFFFFFu, (w * 512 + t * 64 + g * 8) | ((w * 512 + (g & 1) * 256 + (g >> 1) * 64 + t * 16) << 16), lane);
            KB = __shfl_sync(0xFFFFFFFFu, ((w >> 2) * WV_BOX + off) | mk0 | (mk1 << 1) |
                                              ((w * 256 + (g >> 2) * 4096 + (g & 3) * 64 + t * 16) << 16), lane);
            KC = __shfl_sync(0xFFFFFFFFu, ((lane & 7) * 1280 + (lane >> 3) * 128 + ((w ^ (lane & 7)) << 4)) | (((t >> 1) * 16 + g * 2) << 16) | ((t * 64 + g * 8) << 24), lane);
            KD = __shfl_sync(0xFFFFFFFFu, ((w >> 1) * WO_BOX + offo) | (((lane & 7) * 208 + (lane >> 3) * 16) << 16), lane);
            mbar_wait(bq, 0);
#pragma unroll
            for (int ks = 0; ks < 16; ks++) ldsm4t(Wq[ks], sb + SM_STA + (w >> 2) * 32768 + off + ks * 2048);
            asm volatile("fence.proxy.async.shared::cta;" ::: "memory");
            barv<9, 384>();
            mbar_wait(bk, 0);
#pragma unroll
            for (int ks = 0; ks < 16; ks++) ldsm4t(Wk[ks], sb + SM_STB + (w >> 2) * 32768 + off + ks * 2048);
            mbar_wait(bv, 0);
#pragma unroll
            for (int ks = 0; ks < NA1; ks++) ldsm4t(Wv[ks], sb + SM_STC + (w >> 2) * (NA1 * 2048) + off + ks * 2048);
            mbar_wait(bo, 0);
#pragma unroll
            for (int ks = NA1; ks < NA; ks++) ldsm4t(Wv[ks], sb + SM_STA + NB * 4096 + (w >> 2) * ((NA - NA1) * 2048) + off + (ks - NA1) * 2048);
#pragma unroll
            for (int i = 0; i < NB; i++) ldsm4t(Wo[i], sb + SM_STA + (w >> 1) * (NB * 1024) + (offo ^ ((i & 1) << 5)) + (i >> 1) * 2048);
            asm volatile("fence.proxy.async.shared::cta;" ::: "memory");
        }
        const uint32_t ONES = 0x3F803F80u;
#define UNI(x) __reduce_max_sync(0xFFFFFFFFu, x)
        uint32_t swi = UNI((uint32_t)((uint64_t)smem >> 32));
        const uint32_t sbw = UNI(sb + w * 256), sbm = UNI(sb - w * 512), sbs = UNI(sb + w * 768), sbp = UNI(sb + w * 208);
#define OPQALL() { OPQ(t16); OPQ(KA); OPQ(KB); OPQ(KC); OPQ(KD); }
        bsync<1, 384>();
        barv<3, 384>();
        bsync<5, 384>();
#pragma unroll 1
        for (int s2 = 1 - NPRO; s2 < 0; s2 += 2)
#pragma unroll
        for (int p = 0; p < 2; p++) {
            const int s = s2 + p;
            float xa[16], xb[16];
            wg_fence();
            XMMA(0, 32 - NA);
            XMMA(32 - NA, 32);
            piwait(sb, p, s - 2);
            wg_wait<1>();
            xfinish<0>(xa, sb, sbw, p ^ 1, t16, KA);
            wg_fence();
            XMMA(32, 48);
            bsync<1, 384>();
            wg_wait<1>();
            xfinish<2>(xb, sb, sbw, p ^ 1, t16, KA);
            wg_wait<0>();
            xfinish<1>(xa, sb, sbw, p ^ 1, t16, KA);
            barv<3, 384>();
            bsync<5, 384>();
            OPQALL();
        }
        const uint32_t cb0 = (h >> 1) * 32768 + (j & 1) * 16384 + (h & 1) * 8192;
        const uint32_t cb = xlo + cb0 + ((par(cb0) ^ (j >> 1) ^ CFAR) << 12);
        const uint32_t uox = xlo + XO_OX + (h * 2 + (w >> 2)) * 16384 + j * 1024 + (w & 3) * 256 - w * 128;
        float ox[4];
        float4 dn;
#define OXSTORE(s) asm volatile("{\n.reg .b64 a;\nmov.b64 a, {%0,%1};\nst.global.u32 [a], %2;\nst.global.u32 [a+128], %3;\n}" \
                                ::"r"(uox + (t16 >> 2) + ((s) >> 2) * (1u << 20) + ((s) & 3) * 4096), "r"(xhi), \
                                  "r"(pack2(ox[0] * dn.y, ox[1] * dn.w)), "r"(pack2(ox[2] * dn.y, ox[3] * dn.w)) : "memory")
#pragma unroll 1
        for (int s2 = 0;; s2 += 2)
#pragma unroll
        for (int p = 0; p < 2; p++) {
            const int s = s2 + p;
            const uint32_t ctag = ((s2 >> 1) & 1) ^ 1;
            const uint32_t hb = cb ^ (p * 0x81000), rb = xlo + rpage(j, s);
            uint4 k0, k1;
            uint32_t qx0, qx1, ov0, ov1;
            {
                float xa[16], xb[16];
                uint4 m0, n0;
                uint32_t e0, f0, a = xlo + rpage(j, s - 1) + t16;
                uint32_t xp[8];
                wg_fence();
                XMMA(0, 6);
                SF();
                piwait(sb, p, s - 2);
                uint4 pi = xpeer<0>(sb, p ^ 1, t16);
                SF();
                wg_fence();
                XMMA(6, RPOS);
                XMMA(RPOS, RPOS + 4);
                wg_wait<1>();
                SF();
                PT(11);
                RLOAD(a);
                SF();
#define QPOS (RPOS >= 32 - NA ? RPOS : RPOS + 4 >= 32 - NA ? RPOS + 4 : 32 - NA)
                if (QPOS > RPOS) {
                    wg_fence();
                    if (QPOS > RPOS + 4) XMMA(RPOS + 4, QPOS);
                    XMMA(QPOS, QPOS + 4);
                    wg_wait<1>();
                    SF();
                }
                xpack<0>(xp, xa);
                xpark<0>(xp, pi, sb, sbw, p ^ 1, t16, KA);
                pi = xpeer<2>(sb, p ^ 1, t16);
                SF();
                if (QPOS + 4 < 32) {
                    wg_fence();
                    XMMA(QPOS + 4, 32);
                    SF();
                }
                wg_wait<0>();
                xpack<2>(xp, xb);
                xpark<2>(xp, pi, sb, sbw, p ^ 1, t16, KA);
                SF();
                PT(12);
                if (p == 1 || s2 > 0) {
                    int it = 0;
                    while (ruse(sb + SM_MEMT + t16, m0, n0, e0, f0)) {
                        OPQ(a);
                        RLOAD(a);
                        if (++it > SPIN_LIMIT) die(it);
                    }
                    PC(22, it + 1);
                }
                PT(13);
                OPQ(KA); OPQ(t16);
                uint32_t acw = hb + (KA & 0xFFFF), ahi = xhi, tg = ctag;
                OPQ(acw); OPQ(ahi); OPQ(tg);
                SF();
                bsync<1, 384>();
                PT(0);
                uint32_t b[8][4];
#pragma unroll
                for (int i = 0; i < 8; i++) {
                    const int pp = i < 2 ? i : i ^ 1;
                    ldsm4t(b[pp], sbm + SM_MEMT + t16 + pp * 512);
                    if (i < 7) MF();
                }
                if (ASF) SF();
                float q[4], k[4];
                const uint32_t aWv = sb + SM_WV + (KB & 0xFFF0);
                uint32_t wv[16 - NA > 0 ? 16 - NA : 1][4];
#define WVLD(n0, n1) _Pragma("unroll") for (int n = (n0); n < (n1) && n < 16 - NA; n++) ldsm4t(wv[n], aWv + n * 2048)
#pragma unroll
                for (int ks = 0; ks < 16; ks++) {
                    const uint32_t b0 = b[ks >> 1][(ks & 1) * 2], b1 = b[ks >> 1][(ks & 1) * 2 + 1];
                    if (ks == 0) {
                        mma16z(q, Wq[0][0], Wq[0][1], Wq[0][2], Wq[0][3], b0, b1);
                        mma16z(k, Wk[0][0], Wk[0][1], Wk[0][2], Wk[0][3], b0, b1);
                    } else {
                        mma16(q, Wq[ks][0], Wq[ks][1], Wq[ks][2], Wq[ks][3], b0, b1);
                        mma16(k, Wk[ks][0], Wk[ks][1], Wk[ks][2], Wk[ks][3], b0, b1);
                    }
                    if (ks == 10 && VPF) { SF(); WVLD(0, VPF); }
                }
                const uint32_t oq0 = settag(pack2(q[0], q[2]), tg), oq1 = settag(pack2(q[1], q[3]), tg);
                const uint32_t ok0 = pack2(k[0], k[2]), ok1 = pack2(k[1], k[3]);
                stg2<XO_CQK>(acw, ahi, oq0, ok0);
                stg2<XO_CQK + 256>(acw, ahi, oq1, ok1);
                SF();
                PT(1);
                int nl = VPF;
#pragma unroll
                for (int rd = 0; rd < 8; rd++) {
                    const int pp = (VORD >> (28 - 4 * rd)) & 7;
                    const uint32_t* a = 2 * pp < NA ? Wv[2 * pp < NA ? 2 * pp : 0] : wv[2 * pp < NA ? 0 : 2 * pp - NA];
                    const uint32_t* c = 2 * pp < NA ? Wv[2 * pp < NA ? 2 * pp + 1 : 0] : wv[2 * pp < NA ? 0 : 2 * pp + 1 - NA];
                    if (rd == 0) {
                        mma16z(q, a[0], a[1], a[2], a[3], b[pp][0], b[pp][1]);
                        mma16z(k, c[0], c[1], c[2], c[3], b[pp][2], b[pp][3]);
                    } else {
                        mma16(q, a[0], a[1], a[2], a[3], b[pp][0], b[pp][1]);
                        mma16(k, c[0], c[1], c[2], c[3], b[pp][2], b[pp][3]);
                    }
                    if (rd == 0) {
                        SF();
                        OPQ(swi);
                        asm volatile("{\n.reg .b64 a;\nmov.b64 a, {%0,%1};\nst.v2.u32 [a], {%2,%3};\nst.v2.u32 [a+256], {%4,%5};\n}"
                                     ::"r"((KA & 0xFFF) + (sb ^ 0x1000000) + SM_TR + 4096 + p * 4096), "r"(swi), "r"(oq0), "r"(ok0), "r"(oq1), "r"(ok1) : "memory");
                        sts64(sb + SM_TR + (KA & 0xFFF), oq0, ok0);
                        sts64(sb + SM_TR + (KA & 0xFFF) + 256, oq1, ok1);
                    }
                    if (rd == 4) KEEP(t16, oq0, oq1, ok0, ok1);
                    if (nl < 16 - NA) {
                        SF();
                        WVLD(nl, nl + (2 * pp < NA ? 1 : 3));
                        nl += 2 * pp < NA ? 1 : 3;
                    } else if (nl < 32) {
                        SF();
                        k0 = lds128(sb + SM_KV + 2048 + (KB >> 16));
                        nl = 32;
                    } else if (nl == 32) {
                        SF();
                        k1 = lds128(sb + SM_KV + 10240 + (KB >> 16));
                        const uint4 qq = lds128(sbw + SM_KV + ((KA >> 16) & 0xFF));
                        qx0 = (t16 & 64) ? qq.y : qq.x;
                        qx1 = (t16 & 64) ? qq.w : qq.z;
                        nl = 33;
                    }
                }
                ov0 = pack2(q[0] + k[0], q[1] + k[1]);
                ov1 = pack2(q[2] + k[2], q[3] + k[3]);
                stg2<XO_CV>(xlo + ((p * 32 + h) * 4 + j) * 2048 + (t16 >> 1), xhi, settag(ov0, tg), ov1);
                barv<8, 384>();
            }
            OPQ(t16);
            SF();
            PT(2);
            PDUMP();
            {
                const uint32_t a0 = sb + SM_KV;
#define CLOADG() { c2 = ldg4<XO_CQK>((hb ^ 0x1000) + (KA >> 16), xhi); c3 = ldg4<XO_CQK>((hb ^ 0x5000) + (KA >> 16), xhi); }
#define CLOADS() { c0 = lds128(sb + SM_TR + (KA >> 16)); c1 = lds128(sb + SM_TR + 4096 + p * 4096 + (KA >> 16)); }
                uint4 c0, c1, c2, c3, pi;
                float xa[16], xb[16];
                uint32_t xp[8];
                wg_fence();
                XMMA(32, 32 + CPOS);
                XMMA(32 + CPOS, 36 + CPOS);
                wg_wait<1>();
                SF();
                CLOADG();
                SF();
                CLOADS();
                if (KPOS == 0) pi = xpeer<1>(sb, p ^ 1, t16);
                SF();
                wg_fence();
                XMMA(36 + CPOS, 48);
                SF();
                const uint32_t ka[4] = {k0.x, k0.y, k0.z, k0.w}, kb[4] = {k1.x, k1.y, k1.z, k1.w};
                const uint32_t aSp = sb + SM_SP + (KC & 0xFFFF);
                PT(3);
#define SCORES(FIRST) { \
                    const uint32_t qA = hadd2(hadd2(c0.x, c1.x), hadd2(c2.x, c3.x)), qB = hadd2(hadd2(c0.z, c1.z), hadd2(c2.z, c3.z)); \
                    const uint32_t kA = hadd2(hadd2(c0.y, c1.y), hadd2(c2.y, c3.y)), kB = hadd2(hadd2(c0.w, c1.w), hadd2(c2.w, c3.w)); \
                    bad = any_bad(or3(tagx2(c1.x, c1.z, ctag), tagx2(c2.x, c2.z, ctag), tagx2(c3.x, c3.z, ctag))); \
                    float sa[4], sb_[4], sc[4], sd[4], se[4]; \
                    if (FIRST) { SF(); wg_wait<0>(); } \
                    mma16z(sa, ka[0], ka[1], ka[2], ka[3], qA, qB); \
                    mma16z(sb_, kb[0], kb[1], kb[2], kb[3], qA, qB); \
                    mma16z(sc, qA, qx0, qB, qx1, kA, kB); \
                    if (FIRST) { \
                        xpack<1>(xp, xa); \
                        if (KPOS == 0) { xadd(xp, pi); xstore<1>(xp, sb, sbw, p ^ 1, t16, KA); barv<3, 384>(); } \
                        mma16z(sd, ka[0], ka[1], ka[2], ka[3], qx0, qx1); \
                        mma16z(se, kb[0], kb[1], kb[2], kb[3], qx0, qx1); \
                    } \
                    stsm4t(aSp, pack2(sa[0], sa[1]), pack2(sa[2], sa[3]), pack2(sb_[0], sb_[1]), pack2(sb_[2], sb_[3])); \
                    stsm2(aSp + 1024, pack2(sc[0], sc[1]), pack2(sc[2], sc[3])); \
                    if (FIRST) { \
                        stsm4t(aSp + 512, pack2(sd[0], sd[1]), pack2(sd[2], sd[3]), pack2(se[0], se[1]), pack2(se[2], se[3])); \
                        if (KPOS == 0) { KEEP(KD, xp[0], xp[1], xp[2], xp[3]); KEEP(KD, xp[4], xp[5], xp[6], xp[7]); } \
                    } }
                int it = 0;
                bool bad;
                SCORES(true);
                while (__builtin_expect(bad, 0)) {
                    OPQ(KA);
                    CLOADG();
                    CLOADS();
                    SCORES(false);
                    if (++it > SPIN_LIMIT) die(it);
                }
                PC(25, it);
                PT(4);
                bsync<4, 256>();
                uint32_t wo[16 - NB][4];
                const uint32_t aWo = sb + SM_WO + (KD & 0xFFFF), aWo1 = sb + SM_WO + ((KD & 0xFFFF) ^ 32);
#define WOLD(n0, n1) _Pragma("unroll") for (int n = (n0); n < (n1) && n < 16 - NB; n++) ldsm4t(wo[n], ((n & 1) ? aWo1 : aWo) + (n >> 1) * 2048)
                const bool hi = (t16 & 32) != 0;
                const uint32_t t8 = t16 >> 1;
                uint2 v0, v1, v2, v3;
                uint32_t es;
                {
                    uint32_t am[4], ax[4], a4[2];
                    const uint32_t aSr = sbs + SM_SP + t16;
                    ldsm4t(am, aSr);
                    ldsm4t(ax, aSr + 512);
                    ldsm2t(a4, aSr + 1024);
                    MF();
                    if (KPOS == 1) pi = xpeer<1>(sb, p ^ 1, t16);
                    const uint32_t se = (t16 & 128) ? 0u : ONES, so = se ^ ONES;
                    float hm[4], hx[4], h4[4];
                    mma16z(hm, am[0], am[1], am[2], am[3], se, so);
                    mma16z(hx, ax[0], ax[1], ax[2], ax[3], se, so);
                    mma8z(h4, a4[0], a4[1], ONES);
                    SF();
                    if (KPOS == 1) { xpark<1>(xp, pi, sb, sbw, p ^ 1, t16, KA); barv<3, 384>(); }
                    v0 = lds64(a0 + 4096 + t8); v1 = lds64(a0 + 8192 + t8); v2 = lds64(a0 + 12288 + t8); v3 = lds64(a0 + 16384 + t8);
                    WOLD(0, PF2);
                    float s0 = hi ? hx[0] : hm[0], s1 = hi ? hx[2] : hm[2];
                    const float s2 = hi ? h4[2] : h4[0];
                    s0 = (KB & 1) ? -1.0e9f * 11.313708499f : s0;
                    s1 = (KB & 2) ? -1.0e9f * 11.313708499f : s1;
                    int mi = __float_as_int(fmaxf(fmaxf(s0, s2), s1));
                    mi ^= (mi >> 31) & 0x7FFFFFFF;
                    const int mm = __reduce_max_sync(0xFFFFFFFFu, hi ? (int)0x80000000 : mi), mx = __reduce_max_sync(0xFFFFFFFFu, hi ? mi : (int)0x80000000);
                    SF();
                    WOLD(PF2, PF3);
                    SF();
                    mi = hi ? mx : mm;
                    mi ^= (mi >> 31) & 0x7FFFFFFF;
                    const float c2_ = 0.08838834764831845f * 1.4426950408889634f;
                    const float mc = __int_as_float(mi) * c2_;
                    const float e0 = ex2(fmaf(s0, c2_, -mc)), e1 = ex2(fmaf(s1, c2_, -mc)), e2 = ex2(fmaf(s2, c2_, -mc));
                    sts32(sbp + SM_P + (KC >> 25), pack2(e0, e1));
                    sts16(sbp + SM_P + 128 + ((KC >> 16) & 0xFF), pack2(e2, e2));
                    es = __float_as_uint(fmaf(e2, 0.5f, e0 + e1) + 64.f);
                }
                const uint32_t sm = __reduce_add_sync(0xFFFFFFFFu, hi ? 0u : es), sx = __reduce_add_sync(0xFFFFFFFFu, hi ? es : 0u);
                const uint32_t aPr = sb + SM_P + (KD >> 16);
                PT(5);
                bsync<5, 384>();
                uint32_t pm[4], px[4], p4[2];
                ldsm4(pm, aPr);
                MF();
                const uint2 vs = lds64(sb + SM_VS + t8);
                MF();
                ldsm2(p4, aPr + 128);
                MF();
                ldsm4(px, aPr + 64);
                MF();
                sts32f(sb + SM_DN + w * 8 + ((t16 >> 3) & 4), rcp(__uint_as_float((hi ? sx : sm) - 15u * 0x42800000u) - 64.f));
                MF();
                WOLD(PF3, NPF);
                const uint32_t vm0 = hadd2(ov0, vs.x), vm1 = hadd2(ov1, vs.y);
                float oa[4], ob[4];
                mma16z(oa, v0.x, v0.y, v1.x, v1.y, pm[0], pm[1]);
                mma16z(ob, v2.x, v2.y, v3.x, v3.y, pm[2], pm[3]);
                mma8(oa, vm0, vm1, p4[0]);
                stsm2(sbw + SM_OT + (t16 & 511), pack2(oa[0] + ob[0], oa[1] + ob[1]), pack2(oa[2] + ob[2], oa[3] + ob[3]));
                PT(6);
                SF();
                bsync<6, 256>();
                mma16z(ox, v0.x, v0.y, v1.x, v1.y, px[0], px[1]);
                uint32_t b[4][4];
#define OTLD(pp) ldsm4t(b[pp], sbm + SM_OT + t16 + (pp) * 512)
                OTLD(0);
                MF();
                OTLD(1);
                barv<7, 384>();
                mma16(ox, v2.x, v2.y, v3.x, v3.y, px[2], px[3]);
                mma8(ox, vm0, vm1, p4[1]);
                if (p == 1 && s + 1 == nseg) goto done;
                SF();
                uint32_t ar, ae, ahi = xhi;
                float r[2][4];
#pragma unroll
                for (int ks = 0; ks < 8; ks++) {
                    if (ks == 0) WOLD(NPF, NPF + WPF);
                    if (ks == OPOS) { OTLD(2); MF(); }
                    if (ks == OPOS + 2) { OTLD(3); MF(); }
                    if (ks > 0) WOLD(NPF + WPF + 2 * (ks - 1), NPF + WPF + 2 * ks);
                    if (ks == 5) {
                        OPQ(t16);
                        ar = rb + (h & 1) * 16384 + t16; ae = rb + (h & 1) * 1024 + (t16 >> 2);
                        OPQ(ar); OPQ(ahi); OPQ(ae);
                        dn = lds128f(sb + SM_DN + (t16 & 48));
                    }
#pragma unroll
                    for (int mt = 0; mt < 2; mt++) {
                        const int i = ks * 2 + mt;
                        const uint32_t* a = i < NPE ? wo[i < NPE ? i : 0] : i < NPE + NB ? Wo[i < NPE + NB ? i - NPE : 0] : wo[i < NPE + NB ? 0 : i - NB];
                        if (i < 2) mma16z(r[mt], a[0], a[1], a[2], a[3], b[ks >> 1][2 * (ks & 1)], b[ks >> 1][2 * (ks & 1) + 1]);
                        else mma16(r[mt], a[0], a[1], a[2], a[3], b[ks >> 1][2 * (ks & 1)], b[ks >> 1][2 * (ks & 1) + 1]);
                    }
                    if (NPF + WPF + 2 * ks < 16 - NB || ks < 5) SF();
                }
                const float r0 = dn.x, r1 = dn.z;
                asm volatile("{\n.reg .b64 a;\nmov.b64 a, {%0,%2};\nred.relaxed.gpu.global.add.noftz.v4.bf16x2 [a], {%3,%4,%5,%6};\n"
                             "mov.b64 a, {%1,%2};\nred.relaxed.gpu.global.add.noftz.bf16x2 [a+32768], %7;\n}"
                             ::"r"(ar), "r"(ae), "r"(ahi), "r"(pack2(r[0][0] * r0, r[0][1] * r1)), "r"(pack2(r[0][2] * r0, r[0][3] * r1)),
                               "r"(pack2(r[1][0] * r0, r[1][1] * r1)), "r"(pack2(r[1][2] * r0, 1.f)), "r"(pack2(r[1][3] * r1, 1.f)) : "memory");
                barv<10, 384>();
            }
            SF();
            PT(10);
            OXSTORE(s);
            OPQALL();
        }
    done:
        dn = lds128f(sb + SM_DN + (t16 & 48));
        OXSTORE(nseg - 1);
        barv<9, 384>();
        g_main(sb, w, role, &tmy);
        if (threadIdx.x == 0) PG(0);
    }
}

template <int SC> DEVI void wg_rs128t(float (&d)[64], const uint32_t (&a)[4], uint64_t db) {
    if (SC) asm volatile("wgmma.mma_async.sync.aligned.m64n128k16.f32.bf16.bf16 "
        "{%0,%1,%2,%3,%4,%5,%6,%7,%8,%9,%10,%11,%12,%13,%14,%15,%16,%17,%18,%19,%20,%21,%22,%23,%24,%25,%26,%27,%28,%29,%30,%31,%32,%33,%34,%35,%36,%37,%38,%39,%40,%41,%42,%43,%44,%45,%46,%47,%48,%49,%50,%51,%52,%53,%54,%55,%56,%57,%58,%59,%60,%61,%62,%63}, "
        "{%64,%65,%66,%67}, %68, 1, 1, 1, 1;"
        : D4(+, 0), D4(+, 4), D4(+, 8), D4(+, 12), D4(+, 16), D4(+, 20), D4(+, 24), D4(+, 28), D4(+, 32), D4(+, 36), D4(+, 40), D4(+, 44), D4(+, 48), D4(+, 52), D4(+, 56), D4(+, 60) : "r"(a[0]), "r"(a[1]), "r"(a[2]), "r"(a[3]), "l"(db));
    else asm volatile("wgmma.mma_async.sync.aligned.m64n128k16.f32.bf16.bf16 "
        "{%0,%1,%2,%3,%4,%5,%6,%7,%8,%9,%10,%11,%12,%13,%14,%15,%16,%17,%18,%19,%20,%21,%22,%23,%24,%25,%26,%27,%28,%29,%30,%31,%32,%33,%34,%35,%36,%37,%38,%39,%40,%41,%42,%43,%44,%45,%46,%47,%48,%49,%50,%51,%52,%53,%54,%55,%56,%57,%58,%59,%60,%61,%62,%63}, "
        "{%64,%65,%66,%67}, %68, 0, 1, 1, 1;"
        : D4(=, 0), D4(=, 4), D4(=, 8), D4(=, 12), D4(=, 16), D4(=, 20), D4(=, 24), D4(=, 28), D4(=, 32), D4(=, 36), D4(=, 40), D4(=, 44), D4(=, 48), D4(=, 52), D4(=, 56), D4(=, 60) : "r"(a[0]), "r"(a[1]), "r"(a[2]), "r"(a[3]), "l"(db));
}
template <int SC> DEVI void wg_rs64t(float (&d)[32], const uint32_t (&a)[4], uint64_t db) {
    if (SC) asm volatile("wgmma.mma_async.sync.aligned.m64n64k16.f32.bf16.bf16 "
        "{%0,%1,%2,%3,%4,%5,%6,%7,%8,%9,%10,%11,%12,%13,%14,%15,%16,%17,%18,%19,%20,%21,%22,%23,%24,%25,%26,%27,%28,%29,%30,%31}, "
        "{%32,%33,%34,%35}, %36, 1, 1, 1, 1;"
        : D4(+, 0), D4(+, 4), D4(+, 8), D4(+, 12), D4(+, 16), D4(+, 20), D4(+, 24), D4(+, 28) : "r"(a[0]), "r"(a[1]), "r"(a[2]), "r"(a[3]), "l"(db));
    else asm volatile("wgmma.mma_async.sync.aligned.m64n64k16.f32.bf16.bf16 "
        "{%0,%1,%2,%3,%4,%5,%6,%7,%8,%9,%10,%11,%12,%13,%14,%15,%16,%17,%18,%19,%20,%21,%22,%23,%24,%25,%26,%27,%28,%29,%30,%31}, "
        "{%32,%33,%34,%35}, %36, 0, 1, 1, 1;"
        : D4(=, 0), D4(=, 4), D4(=, 8), D4(=, 12), D4(=, 16), D4(=, 20), D4(=, 24), D4(=, 28) : "r"(a[0]), "r"(a[1]), "r"(a[2]), "r"(a[3]), "l"(db));
}
template <int SC> DEVI void wg_rs40(float (&d)[20], const uint32_t (&a)[4], uint64_t db) {
    if (SC) asm volatile("wgmma.mma_async.sync.aligned.m64n40k16.f32.bf16.bf16 "
        "{%0,%1,%2,%3,%4,%5,%6,%7,%8,%9,%10,%11,%12,%13,%14,%15,%16,%17,%18,%19}, "
        "{%20,%21,%22,%23}, %24, 1, 1, 1, 0;"
        : D4(+, 0), D4(+, 4), D4(+, 8), D4(+, 12), D4(+, 16) : "r"(a[0]), "r"(a[1]), "r"(a[2]), "r"(a[3]), "l"(db));
    else asm volatile("wgmma.mma_async.sync.aligned.m64n40k16.f32.bf16.bf16 "
        "{%0,%1,%2,%3,%4,%5,%6,%7,%8,%9,%10,%11,%12,%13,%14,%15,%16,%17,%18,%19}, "
        "{%20,%21,%22,%23}, %24, 0, 1, 1, 0;"
        : D4(=, 0), D4(=, 4), D4(=, 8), D4(=, 12), D4(=, 16) : "r"(a[0]), "r"(a[1]), "r"(a[2]), "r"(a[3]), "l"(db));
}
template <int SC> DEVI void wg_rs8(float (&d)[4], const uint32_t (&a)[4], uint64_t db) {
    if (SC) asm volatile("wgmma.mma_async.sync.aligned.m64n8k16.f32.bf16.bf16 "
        "{%0,%1,%2,%3}, "
        "{%4,%5,%6,%7}, %8, 1, 1, 1, 0;"
        : D4(+, 0) : "r"(a[0]), "r"(a[1]), "r"(a[2]), "r"(a[3]), "l"(db));
    else asm volatile("wgmma.mma_async.sync.aligned.m64n8k16.f32.bf16.bf16 "
        "{%0,%1,%2,%3}, "
        "{%4,%5,%6,%7}, %8, 0, 1, 1, 0;"
        : D4(=, 0) : "r"(a[0]), "r"(a[1]), "r"(a[2]), "r"(a[3]), "l"(db));
}
template <int SC> DEVI void wg_ss64a(float (&d)[32], uint64_t da, uint64_t db) {
    if (SC) asm volatile("wgmma.mma_async.sync.aligned.m64n64k16.f32.bf16.bf16 "
        "{%0,%1,%2,%3,%4,%5,%6,%7,%8,%9,%10,%11,%12,%13,%14,%15,%16,%17,%18,%19,%20,%21,%22,%23,%24,%25,%26,%27,%28,%29,%30,%31}, "
        "%32, %33, 1, 1, 1, 1, 0;"
        : D4(+, 0), D4(+, 4), D4(+, 8), D4(+, 12), D4(+, 16), D4(+, 20), D4(+, 24), D4(+, 28) : "l"(da), "l"(db));
    else asm volatile("wgmma.mma_async.sync.aligned.m64n64k16.f32.bf16.bf16 "
        "{%0,%1,%2,%3,%4,%5,%6,%7,%8,%9,%10,%11,%12,%13,%14,%15,%16,%17,%18,%19,%20,%21,%22,%23,%24,%25,%26,%27,%28,%29,%30,%31}, "
        "%32, %33, 0, 1, 1, 1, 0;"
        : D4(=, 0), D4(=, 4), D4(=, 8), D4(=, 12), D4(=, 16), D4(=, 20), D4(=, 24), D4(=, 28) : "l"(da), "l"(db));
}

#define G_ROWS 514
__device__ uint4 g_G[64 * G_ROWS * 8];
__device__ uint4 g_GN[64 * 8];
__device__ uint4 g_WN[1152];
#define FS_F2 196608
#define FS_TB (FS_F2 + 8192)
#define FS_NQ (FS_TB + 16384)
#define FS_BAR (FS_NQ + 128)
#define FS_NY (FS_NQ + 1024 + 128)
#define FS_TOTAL (FS_NQ + 3072)
#define F_THREADS 512

DEVI uint32_t cis(int j) {
    const float a = fmaf(__uint_as_float((((j + 1024) << 12) & 0x7FF000) | 0x3F800000), 6.283185307179586f, -9.42477796076938f);
    return pack2(__cosf(a), __sinf(a));
}
DEVI uint32_t cos2(int j0, int j1) {
    const float f = 6.283185307179586f / 2048.f;
    return pack2(__cosf((float)(((j0 + 1024) & 2047) - 1024) * f), __cosf((float)(((j1 + 1024) & 2047) - 1024) * f));
}
DEVI void twid(int j, float& c, float& s) {
    const float a = (float)(((j + 512) & 1023) - 512) * (6.283185307179586f / 1024.f);
    c = __cosf(a) * (1.f / 1024.f);
    s = __sinf(a) * (1.f / 1024.f);
}
template <bool B> struct Bool { static constexpr bool v = B; };
DEVI uint32_t opq(uint32_t& x, uint32_t zero) { OPQ(x); return x; }
DEVI uint32_t tidx() { uint32_t r; asm volatile("mov.u32 %0, %%tid.x;" : "=r"(r)); return r; }
DEVI void tma4d(uint32_t dst, const CUtensorMap* tm, uint32_t bar, int c0, int c1, int c2, int c3) {
    asm volatile("cp.async.bulk.tensor.4d.shared::cluster.global.mbarrier::complete_tx::bytes [%0], [%1, {%3, %4, %5, %6}], [%2];"
                 ::"r"(dst), "l"(tm), "r"(bar), "r"(c0), "r"(c1), "r"(c2), "r"(c3) : "memory");
}
DEVI void tma3s(const CUtensorMap* tm, uint32_t src, int c0, int c1, int c2) {
    asm volatile("cp.async.bulk.tensor.3d.global.shared::cta.bulk_group [%0, {%2, %3, %4}], [%1];" ::"l"(tm), "r"(src), "r"(c0), "r"(c1), "r"(c2) : "memory");
}
DEVI void tma4s(const CUtensorMap* tm, uint32_t src, int c0, int c1, int c2, int c3) {
    asm volatile("cp.async.bulk.tensor.4d.global.shared::cta.bulk_group [%0, {%2, %3, %4, %5}], [%1];"
                 ::"l"(tm), "r"(src), "r"(c0), "r"(c1), "r"(c2), "r"(c3) : "memory");
}
DEVI void bulk_commit() { asm volatile("cp.async.bulk.commit_group;" ::: "memory"); }
DEVI void fence_async() { asm volatile("fence.proxy.async;" ::: "memory"); }
DEVI void fence_smem() { asm volatile("fence.proxy.async.shared::cta;" ::: "memory"); }
DEVI void wgbar(uint32_t q) { asm volatile("bar.sync %0, 128;" ::"r"(q + 2) : "memory"); }
DEVI void grid_arrive(uint32_t* c) { asm volatile("fence.proxy.async;\nred.release.gpu.global.add.u32 [%0], 1;" ::"l"(c) : "memory"); }
DEVI void grid_wait(uint32_t* c, uint32_t n) {
    uint32_t v;
    int it = 0;
    do {
        asm volatile("ld.acquire.gpu.global.u32 %0, [%1];" : "=r"(v) : "l"(c) : "memory");
        if (++it > (1 << 22)) die(it);
    } while (v != n);
    fence_async();
}

template <bool INV, class S1, class S2>
DEVI void fft_rows(uint32_t grp, uint32_t q, const uint32_t (&F)[2][4], const float (&tc)[8], const float (&ts)[8], uint32_t so, float fx, uint32_t nq,
                   S1 sh1, S2 sh2) {
    float d[64];
    const uint64_t db = INV ? mkdesc(grp, 1024, 2048) : (mkdesc(grp, 2048, 512) ^ ((uint64_t)3 << 62));
    wg_fence();
    wg_rs128t<0>(d, F[0], db);
    wg_rs128t<1>(d, F[1], db + (INV ? 256 : 64));
    wg_commit();
    SF();
    sh1();
    float4 ny;
    if (INV) ny = lds128f(nq);
    wg_wait<0>();
    if (INV) { d[0] = fmaf(fx, ny.x, d[0]); d[16] = fmaf(fx, ny.y, d[16]); d[32] = fmaf(fx, ny.z, d[32]); d[48] = fmaf(fx, ny.w, d[48]); }
    uint32_t a[2][4][4];
    float e[2][INV ? 16 : 20];
    const uint64_t df = mkdesc(SB0 + FS_F2, 16, 1024);
#pragma unroll
    for (int s = 0; s < 2; s++) {
#pragma unroll
        for (int i = 0; i < 4; i++)
#pragma unroll
            for (int h = 0; h < 2; h++) {
                const float* x = d + (2 * s + h) * 16 + i * 4;
                a[s][i][h] = pack2(fmaf(x[2], ts[2 * i], x[0] * tc[2 * i]), fmaf(x[3], ts[2 * i + 1], x[1] * tc[2 * i + 1]));
                a[s][i][h + 2] = pack2(fmaf(-x[0], ts[2 * i], x[2] * tc[2 * i]), fmaf(-x[1], ts[2 * i + 1], x[3] * tc[2 * i + 1]));
            }
        wg_fence();
#pragma unroll
        for (int i = 0; i < 4; i++) {
            if constexpr (INV) { if (i == 0) wg_rs32<0>(e[s], a[s][i], df); else wg_rs32<1>(e[s], a[s][i], df + i * 2); }
            else { if (i == 0) wg_rs40<0>(e[s], a[s][i], df); else wg_rs40<1>(e[s], a[s][i], df + i * 2); }
        }
        wg_commit();
    }
    SF();
    sh2();
#pragma unroll
    for (int s = 0; s < 2; s++) {
        if (s == 0) wg_wait<1>(); else wg_wait<0>();
        float* x = e[s];
        if constexpr (!INV) {
            x[0] *= fx; x[1] *= fx; x[2] *= fx; x[3] *= fx;
            if (fx != 1.f) sts64(nq + s * 8, pack2(x[16], 0.f), pack2(x[18], 0.f));
        }
        const uint32_t o = grp + (INV ? so + s * 4096 : so ^ (s * 576));
#pragma unroll
        for (int b = 0; b < 2; b++)
            stsm4t(o + b * (INV ? 1024 : 4096), pack2(x[8 * b], x[8 * b + 1]), pack2(x[8 * b + 2], x[8 * b + 3]), pack2(x[8 * b + 4], x[8 * b + 5]),
                   pack2(x[8 * b + 6], x[8 * b + 7]));
    }
}

template <bool INV>
DEVI void fft_gen(uint32_t a, uint32_t n2) {
    const uint32_t tid = tidx(), x = ((tid >> 4) & 24) + (tid & 3), o = (tid & 4) * 128;
    if (INV) {
        const uint32_t r = (tid & 64) * 16 + (tid & 16) * 32 + (tid & 40) * 8 + n2;
        sts128(a + tid * 16, cis(o - r * x), cis(o - (r + 128) * x), cis(o - r * (x + 4)), cis(o - (r + 128) * (x + 4)));
    } else {
        const uint32_t r = 64 * x + n2, k = ((tid >> 2) & 24) + ((tid >> 3) & 3);
        sts128(a + tid * 16, cis(r * k + o), cis(r * (k + 4) + o), cis((r + 256) * k + o), cis((r + 256) * (k + 4) + o));
    }
}
template <bool INV, class S1>
DEVI void fft_cross(uint32_t buf, uint32_t q, uint32_t fa, uint32_t so, uint32_t nq, float (&n)[4], S1 sh1) {
    uint32_t F[4][4];
#pragma unroll
    for (int s = 0; s < 4; s++) { const uint4 v = lds128(fa + s * 2048); F[s][0] = v.x; F[s][1] = v.y; F[s][2] = v.z; F[s][3] = v.w; }
    float d[64];
    const uint64_t db = mkdesc(buf + q * 2048, 1024, 8192), dn = mkdesc(nq, 16, 1024);
    wg_fence();
#pragma unroll
    for (int s = 0; s < 4; s++) { if (s == 0) wg_rs128t<0>(d, F[s], db); else wg_rs128t<1>(d, F[s], db + s * 1024); }
#pragma unroll
    for (int s = 0; s < 4; s++) { if (s == 0) wg_rs8<0>(n, F[s], dn); else wg_rs8<1>(n, F[s], dn + s * 2); }
    wg_commit();
    SF();
    sh1();
    wg_wait<0>();
#pragma unroll
    for (int b = 0; b < 8; b++) {
        const uint32_t o = INV ? so ^ ((b >> 1) * 288 ^ (b & 1) * 32) : (so ^ ((b & 3) * 32)) + (b >> 2) * 1024;
        stsm4(buf + o, pack2(d[8 * b], d[8 * b + 1]), pack2(d[8 * b + 2], d[8 * b + 3]), pack2(d[8 * b + 4], d[8 * b + 5]), pack2(d[8 * b + 6], d[8 * b + 7]));
    }
}

template <bool ODD>
DEVI void fft_filter(uint32_t aw, const float (&e)[32], const float (&o)[32], uint32_t (&u)[4][4], uint32_t (&v)[4][4]) {
#pragma unroll
    for (int s = 0; s < 4; s++) {
        float y[2][2][4];
#pragma unroll
        for (int c = 0; c < 2; c++) {
            float f[4][2];
#pragma unroll
            for (int i = 0; i < 4; i++) {
                const uint32_t a = aw + (i * 32 + s * 8 + c) * 144, x = lds32(a);
                f[i][0] = ODD ? hi_f(x) : lo_f(x);
                f[i][1] = ODD ? lo_f(lds32(a + 4)) : hi_f(x);
            }
#pragma unroll
            for (int h = 0; h < 2; h++) {
                const int x = 8 * s + 2 * h + c;
                const float ar = e[x] + o[x], ai = e[x + 4] + o[x + 4], br = e[x] - o[x], bi = e[x + 4] - o[x + 4];
                const float yr = fmaf(-ai, f[2][h], ar * f[0][h]), yi = fmaf(ar, f[2][h], ai * f[0][h]);
                y[h][c][0] = fmaf(-bi, f[3][h], fmaf(br, f[1][h], yr));
                y[h][c][1] = fmaf(br, f[3][h], fmaf(bi, f[1][h], yi));
                y[h][c][2] = fmaf(2.f, yr, -y[h][c][0]);
                y[h][c][3] = fmaf(2.f, yi, -y[h][c][1]);
            }
        }
#pragma unroll
        for (int h = 0; h < 2; h++) {
            u[s][h] = pack2(y[h][0][0], y[h][1][0]); u[s][h + 2] = pack2(y[h][0][1], y[h][1][1]);
            v[s][h] = pack2(y[h][0][2], y[h][1][2]); v[s][h + 2] = pack2(y[h][0][3], y[h][1][3]);
        }
    }
}

__global__ void __launch_bounds__(F_THREADS, 1)
post_kernel(const __grid_constant__ CUtensorMap tmx, const __grid_constant__ CUtensorMap tmg1, const __grid_constant__ CUtensorMap tmg2,
           const __grid_constant__ CUtensorMap tmwr, const __grid_constant__ CUtensorMap tmwi, const __grid_constant__ CUtensorMap tmy,
           const bf16* __restrict__ wr, const bf16* __restrict__ wi, uint32_t* cnt, uint32_t zero, int nw) {
    extern __shared__ __align__(1024) uint8_t smem[];
    const uint32_t sb = SB0;
    if (smem_u32(smem) != sb) die(1 << 23);
    const uint32_t tid = threadIdx.x, lane = tid & 31, g = lane >> 2, t = lane & 3, j8 = lane & 7, mat = lane >> 3;
    const uint32_t wi_ = __reduce_max_sync(0xFFFFFFFFu, tid >> 5), q = wi_ >> 2, w = wi_ & 3;
    const int cta = blockIdx.x;
    const int nt = cta < 64 ? (64 - cta + nw - 1) / nw : 0;
    const uint32_t bar = sb + FS_BAR;
    if (tid == 0) {
        for (int i = 0; i < 30; i++) mbar_init(bar + i * 8, i < 3 ? 4 : i < 6 ? 16 : i >= 14 && i < 18 ? 2 : 1);
        asm volatile("fence.mbarrier_init.release.cluster;" ::: "memory");
        fence_smem();
    }
    __syncthreads();
#define FT(n)
    FT(0);
#define N2(p) (2 * ((p) & 31) + ((p) >> 5))
#define WLOAD(tk, part) { \
        const uint32_t wd_ = sb + 131072 + q * 18432 + (part) * 9216, wb_ = bar + 112 + q * 8; \
        mbar_expect(wb_, 9216); \
        if ((tk) < 256) tma3d(wd_, (part) ? &tmwi : &tmwr, wb_, ((tk) & 63) * 64, (tk) >> 6, 0); \
        else asm volatile("cp.async.bulk.shared::cluster.global.mbarrier::complete_tx::bytes [%0], [%1], 9216, [%2];" \
                          ::"r"(wd_), "l"(g_WN + (part) * 576), "r"(wb_) : "memory"); }
#define GROW(tk) ((tk) < 256 ? ((tk) >> 5) * 64 + ((tk) & 7) * 8 + (((tk) >> 3) & 3) * 2 : 512)
#define DLOAD(tk, sl) { mbar_expect(bar + 48 + (sl) * 8, 16384); tma3d(sb + (sl) * 16384, &tmg2, bar + 48 + (sl) * 8, 0, GROW(tk), 0); }
#define IO(c) if (w == 3 && (c) && elect())
#define XLOAD1(i, bb) { const uint32_t xb_ = bar + 144 + (bb) * 32 + q * 8; mbar_expect(xb_, 16384); tma4d(sb + (bb) * 65536 + q * 16384, &tmx, xb_, 0, 0, q * 8, N2(cta + (i) * nw)); }
#define GLOAD3(i, bb) { mbar_expect(bar + (bb) * 8, q ? 16384 : 16512); tma3d(sb + (bb) * 65536 + q * 16384, &tmg1, bar + (bb) * 8, 0, q * 128, cta + (i) * nw); \
        if (q == 0) asm volatile("cp.async.bulk.shared::cluster.global.mbarrier::complete_tx::bytes [%0], [%1], 128, [%2];" \
                                 ::"r"(sb + FS_NQ + (bb) * 1024), "l"(g_GN + (cta + (i) * nw) * 8), "r"(bar + (bb) * 8) : "memory"); }
    for (int i = 0; i < 3; i++) IO(i < nt) XLOAD1(i, i);
    for (uint32_t x = tid; x < 40 * 32; x += 512) {
        const uint32_t n = x >> 5, m2 = mat * 8 + t * 2, ri = g & 1;
        const uint32_t c2 = ((n >> 1) & 1) + ((n >> 3) & 1) * 2 + (n & 4) + (n >> 4) * 8;
        const uint32_t v = cos2(m2 * c2 * 64 + ((n & 1) - ri) * 512, (m2 + 1) * c2 * 64 + ((n & 1) - ri) * 512);
        sts32(sb + FS_F2 + n * 128 + ((g ^ (n & 7)) << 4) + t * 4, n < 32 ? v : n == 32 && ri == 0 ? 0xBF003F00u : 0u);
    }
    float tc[8], ts[8];
    uint32_t F[2][4];
    uint32_t c1 = 16 * (w >> 1) + 2 * g + (w & 1);
#pragma unroll
    for (int i = 0; i < 8; i++) {
        twid(c1 * (8 * (i >> 1) + 2 * t + (i & 1)), tc[i], ts[i]);
        const uint32_t m1 = (i >> 1) * 8 + 2 * t;
        F[i >> 2][i & 3] = cos2(c1 * m1 * 64 + (i & 1) * 512, c1 * (m1 + 1) * 64 + (i & 1) * 512);
    }
    {
        const uint32_t kr = (2 * (mat & 1) + (j8 & 1)) ^ ((j8 >> 2) << 1);
        const uint32_t so1 = ((mat >> 1) + 2 * (j8 >> 2)) * 1024 + kr * 128 + (((((j8 >> 1) & 1) * 4 + w) ^ kr) << 4);
        const uint32_t so2 = (2 * w + (mat & 1)) * 8192 + q * 2048 + j8 * 128 + (((mat >> 1) ^ j8) << 4);
        uint32_t so = so1 << 16 | so2;
        const float fx = (tid & 127) == 0 ? 0.5f : 1.f;
        fft_gen<false>(sb + FS_TB, N2(cta));
        fence_smem();
        bsync<1, 512>();
        FT(1);
        int b = 0, bp = 2, ph = 0;
        if (nt) mwait(bar + 144 + q * 8, 0);
        __syncwarp();
        auto step = [&](auto first, auto last, const int i) {
            const uint32_t p = cta + i * nw, bn = 3 - b - bp, tb = (i & 1) * 8192;
            const uint32_t grp = sb + b * 65536 + q * 16384, nq = sb + FS_NQ + b * 1024 + q * 32;
            auto sa = [&]() {
                if constexpr (!decltype(first)::v) {
                    fence_smem();
                    __syncwarp();
                    if (elect()) mbar_arrive(bar + 24);
                }
                IO(i > 1) {
                    mwait(bar + 32, i & 1);
                    tma3s(&tmg1, sb + bn * 65536 + q * 16384, 0, q * 128, p - 2 * nw);
                    bulk_commit();
                }
            };
            auto sb_ = [&]() { if constexpr (!decltype(first)::v) mwait(bar + 24, (i - 1) & 1); };
            if constexpr (!decltype(last)::v) fft_rows<false>(grp, q, F, tc, ts, opq(so, zero) >> 16, fx, nq, sa, sb_);
            else { sa(); __syncwarp(); sb_(); __syncwarp(); }
            if constexpr (!decltype(first)::v) {
                float n[4];
                fft_cross<false>(sb + bp * 65536, q, sb + FS_TB + 8192 - tb + (((tidx() & 127) ^ (q & 1)) << 4), opq(so, zero) & 0xFFFF, sb + FS_NQ + bp * 1024, n, [&]() {
                    fft_gen<false>(sb + FS_TB + tb, N2(p));
                    IO(i >= 2 && i + 1 < nt) {
                        asm volatile("cp.async.bulk.wait_group.read 0;" ::: "memory");
                        XLOAD1(i + 1, bn);
                    }
                });
                if (q == 0) {
                    const uint32_t x = tidx();
                    bf16* z = (bf16*)(g_G + ((p - nw) * G_ROWS + 512) * 8) + (x & 4) * 16 + ((x >> 2) & 24) + ((x >> 3) & 3);
                    asm volatile("{\n.reg .pred p;\n.reg .b16 a, b;\nsetp.eq.u32 p, %2, 0;\nmov.b32 {a, b}, %1;\n@p st.global.u16 [%0], a;\n@p st.global.u16 [%0+8], b;\n}"
                                 ::"l"(z), "r"(pack2(n[0], n[2])), "r"(x & 3) : "memory");
                }
            }
            if constexpr (!decltype(last)::v) {
                fft_rows<false>(grp + 8192, q, F, tc, ts, opq(so, zero) >> 16, fx, nq + 16, [&]() {
                    if constexpr (!decltype(first)::v) {
                        fence_smem();
                        __syncwarp();
                        if (elect()) mbar_arrive(bar + 32);
                    }
                    if ((w == 1 || w == 2) && elect())
                        asm volatile("cp.async.bulk.prefetch.L2.global [%0], 8208;" ::"l"((w == 1 ? wr : wi) + (p * 4 + q) * 4104) : "memory");
                }, [&]() { if (i + 1 < nt) mwait(bar + 144 + bn * 32 + q * 8, bn ? ph : ph ^ 1); });
                bp = b;
                if (++b == 3) { b = 0; ph ^= 1; }
            }
        };
        if (nt) {
            step(Bool<true>(), Bool<false>(), 0);
#pragma unroll 1
            for (int i = 1; i < nt; i++) step(Bool<false>(), Bool<false>(), i);
            step(Bool<false>(), Bool<true>(), nt);
        }
        for (uint32_t x = cta * 512 + tid; x < 4096; x += nw * 512)
            ((bf16*)g_WN)[(x >> 5) * 72 + (x & 16) + (x & 7) * 2 + ((x >> 3) & 1)] = (x < 2048 ? wr : wi)[(x & 2047) * 513 + 512];
        FT(2);
        fence_async();
        bsync<1, 512>();
        IO(nt) { tma3s(&tmg1, sb + bp * 65536 + q * 16384, 0, q * 128, cta + (nt - 1) * nw); bulk_commit(); }
    }
    for (uint32_t x = tid; x < 128 * 32; x += 512) {
        const uint32_t n = (x >> 5) & 63, a = x & 31, k2 = (n >> 4) * 8 + (n & 7);
        sts32(sb + FS_TB + (x >> 5) * 128 + (((a >> 2) ^ (n & 7)) << 4) + (a & 3) * 4, cis((2 * a + (x >> 11)) * k2 * 32 + (n & 8) * 64));
    }
    fence_smem();
    bsync<1, 512>();
    IO(true) {
        asm volatile("cp.async.bulk.wait_group 0;" ::: "memory");
        grid_arrive(cnt);
        grid_wait(cnt, 4 * nw);
        const int tk = cta + q * nw;
        if (tk <= 256) { DLOAD(tk, q); WLOAD(tk, 0); WLOAD(tk, 1); }
    }
    __syncwarp();
    {
        const uint32_t lo = j8 * 128 + (((2 * w + (mat & 1)) ^ j8) << 4);
        const uint32_t aw = sb + 131072 + q * 18432 + t * 288 + w * 32 + g * 4;
        const uint64_t df = mkdesc(sb + FS_TB, 16, 1024);
        const uint64_t da = mkdesc(sb + q * 16384, 16, 1024);
        const uint32_t buf = sb + 65536 + q * 16384;
        int i = 0, tk = cta + q * nw;
        if (tk <= 256) mwait(bar + 48 + q * 8, 0);
        FT(3);
#pragma unroll 1
        for (; tk <= 256; tk += 4 * nw, i++) {
            const bool more = tk + 4 * nw <= 256;
            float e[32], o[32];
            wg_fence();
#pragma unroll
            for (int s = 0; s < 4; s++) { if (s == 0) wg_ss64a<0>(e, da, df); else wg_ss64a<1>(e, da + s * 128, df + s * 2); }
#pragma unroll
            for (int s = 0; s < 4; s++) { if (s == 0) wg_ss64a<0>(o, da + 512, df + 512); else wg_ss64a<1>(o, da + 512 + s * 128, df + 512 + s * 2); }
            wg_commit();
            SF();
            if (i > 0) {
                fence_smem();
                wgbar(q);
                IO(true) { tma3s(&tmg2, buf, 0, GROW(tk - 4 * nw), 0); bulk_commit(); }
            }
            if (w == 2 && more && elect()) mbar_expect(bar + 48 + q * 8, 16384);
            const int gr = GROW(tk + 4 * nw);
            mwait(bar + 112 + q * 8, i & 1);
            wg_wait<0>();
            if (w == 2 && more && elect()) tma3d(sb + q * 16384, &tmg2, bar + 48 + q * 8, 0, gr, 0);
            uint32_t u[4][4], v[4][4];
            if (tk & 8) fft_filter<true>(aw + (tk & 48) / 4, e, o, u, v);
            else fft_filter<false>(aw + (tk & 48) / 4, e, o, u, v);
            wg_fence();
#pragma unroll
            for (int s = 0; s < 4; s++) { if (s == 0) wg_rs64t<0>(e, u[s], df); else wg_rs64t<1>(e, u[s], df + s * 128); }
#pragma unroll
            for (int s = 0; s < 4; s++) { if (s == 0) wg_rs64t<0>(o, v[s], df + 512); else wg_rs64t<1>(o, v[s], df + 512 + s * 128); }
            wg_commit();
            SF();
            IO(true) asm volatile("cp.async.bulk.wait_group.read 0;" ::: "memory");
            wgbar(q);
            if (more) {
                if ((w == 1 || w == 2) && elect()) WLOAD(tk + 4 * nw, w - 1);
                mwait(bar + 48 + q * 8, (i + 1) & 1);
            }
            wg_wait<0>();
#pragma unroll
            for (int s = 0; s < 4; s++) {
                const uint32_t a = buf + (mat >> 1) * 1024 + lo + s * 2048;
                stsm4t(a, pack2(e[8 * s], e[8 * s + 1]), pack2(e[8 * s + 2], e[8 * s + 3]), pack2(e[8 * s + 4], e[8 * s + 5]), pack2(e[8 * s + 6], e[8 * s + 7]));
                stsm4t(a + 8192, pack2(o[8 * s], o[8 * s + 1]), pack2(o[8 * s + 2], o[8 * s + 3]), pack2(o[8 * s + 4], o[8 * s + 5]), pack2(o[8 * s + 6], o[8 * s + 7]));
            }
            if (tk == 256 && w < 2) {
                uint32_t* z = (uint32_t*)g_GN + t * 32 + w * 16 + g;
#pragma unroll
                for (int s = 0; s < 16; s++) {
                    z[(s >> 1) * 128 + (s & 1) * 8] = pack2(e[2 * s], e[2 * s + 1]);
                    z[(s >> 1) * 128 + (s & 1) * 8 + 1024] = pack2(o[2 * s], o[2 * s + 1]);
                }
                fence_async();
            }
        }
        fence_smem();
        wgbar(q);
        IO(true) {
            if (i > 0) { tma3s(&tmg2, buf, 0, GROW(tk - 4 * nw), 0); bulk_commit(); }
            asm volatile("cp.async.bulk.wait_group 0;" ::: "memory");
            grid_arrive(cnt + 1);
        }
    }
    FT(4);
    bsync<1, 512>();
    {
        for (uint32_t n = wi_; n < 32; n += 16) {
            const uint32_t cl = (mat >> 1) * 16 + t * 4 + (mat & 1), mh = ((n >> 3) & 1) + (n & 7) * 2 + (n & 16);
            sts32(sb + FS_F2 + n * 128 + ((g ^ (n & 7)) << 4) + t * 4, cos2(cl * mh * 64 + (g & 1) * 512, (cl + 2) * mh * 64 + (g & 1) * 512));
        }
        fence_smem();
        c1 = 8 * w + g;
#pragma unroll
        for (int i = 0; i < 8; i++) {
            twid(-c1 * (16 * (i >> 2) + 4 * t + 2 * (i & 1) + ((i >> 1) & 1)), tc[i], ts[i]);
            F[i >> 2][i & 3] = cis((i & 1) * 512 - c1 * ((i >> 1) * 4 + (t ^ (q & 1))) * 64);
        }
        const uint32_t kr = (j8 & 1) ^ ((j8 >> 2) << 1);
        const uint32_t so2 = ((w >> 1) * 4 + (j8 >> 2) * 2 + (w & 1)) * 8192 + (2 * q + (mat & 1)) * 1024 + kr * 128 + (((((j8 >> 1) & 1) * 4 + (mat >> 1)) ^ kr) << 4);
        const uint32_t so1 = (mat & 1) * 2048 + j8 * 128 + ((((mat >> 1) * 4 + w) ^ j8) << 4);
        uint32_t so = so1 << 16 | so2;
        const float fx = t ? 0.f : (g & 1) ? -1.f : 1.f;
        fft_gen<true>(sb + FS_TB, N2(cta));
        bsync<1, 512>();
        IO(true) grid_wait(cnt + 1, 4 * nw);
        for (int i = 0; i < 3; i++) IO(i < nt) GLOAD3(i, i);
        __syncwarp();
        int b = 0, bp = 2, ph = 0;
        auto step = [&](auto first, auto last, const int i) {
            const uint32_t p = cta + i * nw, bn = 3 - b - bp, tb = (i & 1) * 8192;
            const uint32_t grp = sb + bp * 65536 + q * 16384, ny = sb + FS_NY + bp * 128 + q * 32;
            auto sb_ = [&]() { if constexpr (!decltype(last)::v) mwait(bar + b * 8, ph); };
            if constexpr (!decltype(first)::v) {
                fft_rows<true>(grp, q, F, tc, ts, opq(so, zero) >> 16, fx, ny, [&]() {
                    if (i > 1) {
                        fence_smem();
                        wgbar(q);
                        IO(true) { tma4s(&tmy, sb + bn * 65536 + q * 16384, 0, 0, q * 8, N2(p - 2 * nw)); bulk_commit(); }
                    }
                }, sb_);
            } else { sb_(); __syncwarp(); }
            if constexpr (decltype(first)::v) FT(5);
            if constexpr (!decltype(last)::v) {
                float n[4];
                fft_cross<true>(sb + b * 65536, q, sb + FS_TB + tb + (tidx() & 127) * 16, opq(so, zero) & 0xFFFF, sb + FS_NQ + b * 1024, n, [&]() {
                    fft_gen<true>(sb + FS_TB + 8192 - tb, N2(p + nw));
                    IO(i >= 2 && i + 1 < nt) {
                        asm volatile("cp.async.bulk.wait_group.read 0;" ::: "memory");
                        GLOAD3(i + 1, bn);
                    }
                });
                if (q == 0) {
                    const uint32_t x = tidx(), a = sb + FS_NY + b * 128 + (x & 64) + (x & 16) * 2 + ((x & 40) >> 1);
                    if ((x & 7) == 0) { sts32f(a, n[0]); sts32f(a + 8, n[2]); }
                }
            }
            auto sc = [&]() {
                if constexpr (!decltype(last)::v) {
                    fence_smem();
                    __syncwarp();
                    if (elect()) mbar_arrive(bar + 24);
                }
            };
            auto sd = [&]() { if constexpr (!decltype(last)::v) mwait(bar + 24, (nt + i) & 1); };
            if constexpr (!decltype(first)::v) fft_rows<true>(grp + 8192, q, F, tc, ts, opq(so, zero) >> 16, fx, ny + 16, sc, sd);
            else { sc(); __syncwarp(); sd(); __syncwarp(); }
            if constexpr (!decltype(last)::v) {
                bp = b;
                if (++b == 3) { b = 0; ph ^= 1; }
            }
        };
        if (nt) {
            step(Bool<true>(), Bool<false>(), 0);
#pragma unroll 1
            for (int i = 1; i < nt; i++) step(Bool<false>(), Bool<false>(), i);
            step(Bool<false>(), Bool<true>(), nt);
        }
        fence_smem();
        wgbar(q);
        IO(nt) { tma4s(&tmy, sb + bp * 65536 + q * 16384, 0, 0, q * 8, N2(cta + (nt - 1) * nw)); bulk_commit(); }
        FT(6);
        IO(true) asm volatile("cp.async.bulk.wait_group 0;" ::: "memory");
    }
}

typedef CUresult (*EncodeFn)(CUtensorMap*, CUtensorMapDataType, cuuint32_t, void*, const cuuint64_t*, const cuuint64_t*,
                             const cuuint32_t*, const cuuint32_t*, CUtensorMapInterleave, CUtensorMapSwizzle,
                             CUtensorMapL2promotion, CUtensorMapFloatOOBfill);

static void make_map(EncodeFn enc, CUtensorMap* m, const void* ptr, int rank, const cuuint64_t* dims, const cuuint64_t* strides,
                     const cuuint32_t* box, CUtensorMapSwizzle sw = CU_TENSOR_MAP_SWIZZLE_128B) {
    cuuint32_t es[4] = {1, 1, 1, 1};
    CUresult r = enc(m, CU_TENSOR_MAP_DATA_TYPE_BFLOAT16, rank, (void*)ptr, dims, strides, box, es, CU_TENSOR_MAP_INTERLEAVE_NONE,
                     sw, CU_TENSOR_MAP_L2_PROMOTION_L2_256B, CU_TENSOR_MAP_FLOAT_OOB_FILL_NONE);
    if (r != CUDA_SUCCESS) fprintf(stderr, "tensor map encode failed: %d\n", (int)r);
}

extern "C" void kernel_launch(void* const* d_in, const int* in_sizes, int n_in, void* d_out, int out_size) {
    const bf16* A_x = (const bf16*)d_in[0];
    const bf16* A_mem0 = (const bf16*)d_in[1];
    const bf16* A_Wq = (const bf16*)d_in[2];
    const bf16* A_Wk = (const bf16*)d_in[3];
    const bf16* A_Wv = (const bf16*)d_in[4];
    const bf16* A_Wo = (const bf16*)d_in[5];
    const bf16* B_x = (const bf16*)d_in[7];
    const bf16* B_wr = (const bf16*)d_in[8];
    const bf16* B_wi = (const bf16*)d_in[9];
    bf16* out = (bf16*)d_out;

    static EncodeFn enc = nullptr;
    static void *pxs = nullptr, *pg = nullptr;
    static int ncl = 64;
    if (!enc) {
        cudaDriverEntryPointQueryResult qr;
        void* fn = nullptr;
        cudaGetDriverEntryPoint("cuTensorMapEncodeTiled", &fn, cudaEnableDefault, &qr);
        enc = (EncodeFn)fn;
        cudaFuncSetAttribute(chain_kernel, cudaFuncAttributeMaxDynamicSharedMemorySize, SM_TOTAL);
        cudaFuncSetAttribute(post_kernel, cudaFuncAttributeMaxDynamicSharedMemorySize, FS_TOTAL);
        cudaGetSymbolAddress(&pxs, g_xs);
        cudaGetSymbolAddress(&pg, g_G);
        cudaLaunchConfig_t lc = {};
        cudaLaunchAttribute at;
        at.id = cudaLaunchAttributeClusterDimension;
        at.val.clusterDim.x = 2; at.val.clusterDim.y = 1; at.val.clusterDim.z = 1;
        lc.gridDim = dim3(132); lc.blockDim = dim3(384); lc.dynamicSmemBytes = SM_TOTAL; lc.attrs = &at; lc.numAttrs = 1;
        int nc = 0;
        if (cudaOccupancyMaxActiveClusters(&nc, chain_kernel, &lc) == cudaSuccess && nc > 64) ncl = nc < 66 ? nc : 66;
    }
    CUtensorMap tmq, tmk, tmv, tmo, tmx, tmb, tmy;
    {
        cuuint64_t d[2] = {HD, DM}, st[1] = {HD * 2};
        cuuint32_t bx[2] = {64, 256};
        make_map(enc, &tmq, A_Wq, 2, d, st, bx);
        make_map(enc, &tmk, A_Wk, 2, d, st, bx);
        cuuint32_t bx2[2] = {64, 16};
        make_map(enc, &tmv, A_Wv, 2, d, st, bx2);
    }
    {
        cuuint64_t d[2] = {DM, HD}, st[1] = {DM * 2};
        cuuint32_t bx[2] = {64, 16}, bx2[3] = {64, 64, 2};
        make_map(enc, &tmo, A_Wo, 2, d, st, bx);
        cuuint64_t d2[3] = {64, HD, DM / 64}, st2[2] = {DM * 2, 128}, d3[2] = {DM, SEQ}, st3[1] = {DM * 4};
        make_map(enc, &tmb, A_Wo, 3, d2, st2, bx2);
        make_map(enc, &tmy, out, 2, d3, st3, bx);
    }
    {
        cuuint64_t d[3] = {64, SEQ, DM / 64}, st[2] = {DM * 2, 128};
        cuuint32_t bx[3] = {64, 8, 4};
        make_map(enc, &tmx, A_x, 3, d, st, bx);
    }
    CUtensorMap fx, fg1, fg2, fwr, fwi, fy;
    {
        cuuint64_t d[4] = {32, 32, 32, 64}, st[3] = {64, 64 * DM * 2, DM * 2};
        cuuint32_t bx[4] = {32, 32, 8, 1};
        make_map(enc, &fx, B_x, 4, d, st, bx, CU_TENSOR_MAP_SWIZZLE_64B);
        cuuint64_t d2[4] = {64, 16, 32, 64}, st2[3] = {128, 64 * 4096, 4096};
        cuuint32_t bx2[4] = {64, 16, 8, 1};
        make_map(enc, &fy, out + DM, 4, d2, st2, bx2);
    }
    {
        cuuint64_t d[3] = {64, G_ROWS, 64}, st[2] = {128, G_ROWS * 128};
        cuuint32_t bx[3] = {64, 128, 1}, bx2[3] = {64, 2, 64};
        make_map(enc, &fg1, pg, 3, d, st, bx);
        make_map(enc, &fg2, pg, 3, d, st, bx2);
        cuuint64_t d2[3] = {8 * 513, 4, 64}, st2[2] = {8 * 513 * 2, 32 * 513 * 2};
        cuuint32_t bx3[3] = {72, 1, 64};
        make_map(enc, &fwr, B_wr, 3, d2, st2, bx3, CU_TENSOR_MAP_SWIZZLE_NONE);
        make_map(enc, &fwi, B_wi, 3, d2, st2, bx3, CU_TENSOR_MAP_SWIZZLE_NONE);
    }
    cudaStream_t st = cudaStreamPerThread;
    const uint64_t xs = ((uint64_t)pxs + XS_BYTES - 1) & ~(uint64_t)(XS_BYTES - 1);
    cudaMemsetAsync((void*)(xs + XO_R), 0, XO_TK + 512, st);
    chain_kernel<<<2 * ncl, 384, SM_TOTAL, st>>>(tmq, tmk, tmv, tmo, tmx, tmb, tmy, A_mem0, A_x, (uint32_t)xs, (uint32_t)(xs >> 32), 0u, NSEG);
    int nw = ncl == 66 ? 4 : 64;
    cudaLaunchConfig_t lc = {};
    cudaLaunchAttribute at;
    at.id = cudaLaunchAttributeProgrammaticStreamSerialization;
    at.val.programmaticStreamSerializationAllowed = 1;
    lc.gridDim = dim3(nw); lc.blockDim = dim3(F_THREADS); lc.dynamicSmemBytes = FS_TOTAL; lc.stream = st; lc.attrs = &at; lc.numAttrs = 1;
    cudaLaunchKernelEx(&lc, post_kernel, fx, fg1, fg2, fwr, fwi, fy, B_wr, B_wi, (uint32_t*)(xs + XO_TK + 256), 0u, nw);
}
```

```cpp
#include <cuda_runtime.h>
#include <cuda_bf16.h>
#include <cuda.h>
#include <stdint.h>
#include <stdio.h>

typedef __nv_bfloat16 bf16;

#define SEQ 2048
#define DM 1024
#define NH 32
#define DH 128
#define NSEG 64
#define HD (NH * DH)

#define XS_BYTES (32u << 20)
__device__ uint4 g_xs[2 * XS_BYTES / 16];
#define XO_R 0u
#define XO_PB (1u << 18)
#define XO_FL (XO_PB + 16384u)
#define XO_TK (XO_FL + 4096u)
#define XO_CQK (1u << 20)
#define XO_CV (2u << 20)
#define XO_XG (4u << 20)
#define XO_OX (16u << 20)
#define GSYNC(n)
#define PG(n)

#define DEVI __device__ __forceinline__

DEVI void die(int it) { asm volatile("st.shared.u32 [%0], %0;" ::"r"(it) : "memory"); }
DEVI uint32_t smem_u32(const void* p) { return (uint32_t)__cvta_generic_to_shared(p); }
DEVI void mbar_init(uint32_t bar, uint32_t cnt) { asm volatile("mbarrier.init.shared::cta.b64 [%0], %1;" ::"r"(bar), "r"(cnt) : "memory"); }
DEVI void mbar_expect(uint32_t bar, uint32_t bytes) { asm volatile("mbarrier.arrive.expect_tx.shared::cta.b64 _, [%0], %1;" ::"r"(bar), "r"(bytes) : "memory"); }
DEVI void mbar_arrive(uint32_t bar) { asm volatile("mbarrier.arrive.shared::cta.b64 _, [%0];" ::"r"(bar) : "memory"); }
DEVI void mbar_wait(uint32_t bar, uint32_t parity) {
    uint32_t done;
    int it = 0;
    do {
        asm volatile("{\n.reg .pred p;\nmbarrier.try_wait.parity.shared::cta.b64 p, [%1], %2;\nselp.u32 %0, 1, 0, p;\n}\n"
                     : "=r"(done) : "r"(bar), "r"(parity) : "memory");
        if (++it > (1 << 22)) die(it);
    } while (!done);
}
DEVI void tma2d(uint32_t dst, const CUtensorMap* tm, uint32_t bar, int c0, int c1) {
    asm volatile("cp.async.bulk.tensor.2d.shared::cluster.global.mbarrier::complete_tx::bytes [%0], [%1, {%3, %4}], [%2];"
                 ::"r"(dst), "l"(tm), "r"(bar), "r"(c0), "r"(c1) : "memory");
}
DEVI void tma3d(uint32_t dst, const CUtensorMap* tm, uint32_t bar, int c0, int c1, int c2) {
    asm volatile("cp.async.bulk.tensor.3d.shared::cluster.global.mbarrier::complete_tx::bytes [%0], [%1, {%3, %4, %5}], [%2];"
                 ::"r"(dst), "l"(tm), "r"(bar), "r"(c0), "r"(c1), "r"(c2) : "memory");
}
DEVI void bulk_g2s(uint32_t dst, uint32_t lo, uint32_t hi, uint32_t bytes, uint32_t bar) {
    asm volatile("{\n.reg .b64 a;\nmov.b64 a, {%1,%2};\ncp.async.bulk.shared::cluster.global.mbarrier::complete_tx::bytes [%0], [a], %3, [%4];\n}"
                 ::"r"(dst), "r"(lo), "r"(hi), "r"(bytes), "r"(bar) : "memory");
}
DEVI void bulk_s2g(uint32_t lo, uint32_t hi, uint32_t src, uint32_t bytes) {
    asm volatile("{\n.reg .b64 a;\nmov.b64 a, {%0,%1};\ncp.async.bulk.global.shared::cta.bulk_group [a], [%2], %3;\ncp.async.bulk.commit_group;\n}"
                 ::"r"(lo), "r"(hi), "r"(src), "r"(bytes) : "memory");
}
DEVI void bulk_red(uint32_t lo, uint32_t hi, uint32_t src, uint32_t bytes) {
    asm volatile("{\n.reg .b64 a;\nmov.b64 a, {%0,%1};\ncp.reduce.async.bulk.global.shared::cta.bulk_group.add.noftz.bf16 [a], [%2], %3;\ncp.async.bulk.commit_group;\n}"
                 ::"r"(lo), "r"(hi), "r"(src), "r"(bytes) : "memory");
}
DEVI bool elect() {
    uint32_t p;
    asm volatile("{\n.reg .pred P;\nelect.sync _|P, 0xFFFFFFFF;\nselp.u32 %0, 1, 0, P;\n}" : "=r"(p));
    return p != 0;
}
DEVI void ldsm4(uint32_t (&r)[4], uint32_t a) {
    asm volatile("ldmatrix.sync.aligned.m8n8.x4.shared.b16 {%0,%1,%2,%3}, [%4];" : "=r"(r[0]), "=r"(r[1]), "=r"(r[2]), "=r"(r[3]) : "r"(a) : "memory");
}
DEVI void ldsm4t(uint32_t (&r)[4], uint32_t a) {
    asm volatile("ldmatrix.sync.aligned.m8n8.x4.trans.shared.b16 {%0,%1,%2,%3}, [%4];" : "=r"(r[0]), "=r"(r[1]), "=r"(r[2]), "=r"(r[3]) : "r"(a) : "memory");
}
DEVI void ldsm2t(uint32_t (&r)[2], uint32_t a) {
    asm volatile("ldmatrix.sync.aligned.m8n8.x2.trans.shared.b16 {%0,%1}, [%2];" : "=r"(r[0]), "=r"(r[1]) : "r"(a) : "memory");
}
DEVI void ldsm2(uint32_t (&r)[2], uint32_t a) {
    asm volatile("ldmatrix.sync.aligned.m8n8.x2.shared.b16 {%0,%1}, [%2];" : "=r"(r[0]), "=r"(r[1]) : "r"(a) : "memory");
}
DEVI void stsm4t(uint32_t a, uint32_t r0, uint32_t r1, uint32_t r2, uint32_t r3) {
    asm volatile("stmatrix.sync.aligned.m8n8.x4.trans.shared.b16 [%0], {%1,%2,%3,%4};" ::"r"(a), "r"(r0), "r"(r1), "r"(r2), "r"(r3) : "memory");
}
DEVI uint32_t ldsm1(uint32_t a) {
    uint32_t r;
    asm volatile("ldmatrix.sync.aligned.m8n8.x1.shared.b16 {%0}, [%1];" : "=r"(r) : "r"(a) : "memory");
    return r;
}
DEVI void stsm4(uint32_t a, uint32_t r0, uint32_t r1, uint32_t r2, uint32_t r3) {
    asm volatile("stmatrix.sync.aligned.m8n8.x4.shared.b16 [%0], {%1,%2,%3,%4};" ::"r"(a), "r"(r0), "r"(r1), "r"(r2), "r"(r3) : "memory");
}
DEVI void stsm2(uint32_t a, uint32_t r0, uint32_t r1) {
    asm volatile("stmatrix.sync.aligned.m8n8.x2.shared.b16 [%0], {%1,%2};" ::"r"(a), "r"(r0), "r"(r1) : "memory");
}
DEVI uint32_t movm(uint32_t a) {
    uint32_t d;
    asm volatile("movmatrix.sync.aligned.m8n8.trans.b16 %0, %1;" : "=r"(d) : "r"(a));
    return d;
}
DEVI void mma16(float (&d)[4], uint32_t a0, uint32_t a1, uint32_t a2, uint32_t a3, uint32_t b0, uint32_t b1) {
    asm volatile("mma.sync.aligned.m16n8k16.row.col.f32.bf16.bf16.f32 {%0,%1,%2,%3}, {%4,%5,%6,%7}, {%8,%9}, {%0,%1,%2,%3};"
                 : "+f"(d[0]), "+f"(d[1]), "+f"(d[2]), "+f"(d[3]) : "r"(a0), "r"(a1), "r"(a2), "r"(a3), "r"(b0), "r"(b1));
}
DEVI void mma16z(float (&d)[4], uint32_t a0, uint32_t a1, uint32_t a2, uint32_t a3, uint32_t b0, uint32_t b1) {
    asm volatile("mma.sync.aligned.m16n8k16.row.col.f32.bf16.bf16.f32 {%0,%1,%2,%3}, {%4,%5,%6,%7}, {%8,%9}, {%10,%10,%10,%10};"
                 : "=f"(d[0]), "=f"(d[1]), "=f"(d[2]), "=f"(d[3]) : "r"(a0), "r"(a1), "r"(a2), "r"(a3), "r"(b0), "r"(b1), "f"(0.f));
}
DEVI void mma8(float (&d)[4], uint32_t a0, uint32_t a1, uint32_t b0) {
    asm volatile("mma.sync.aligned.m16n8k8.row.col.f32.bf16.bf16.f32 {%0,%1,%2,%3}, {%4,%5}, {%6}, {%0,%1,%2,%3};"
                 : "+f"(d[0]), "+f"(d[1]), "+f"(d[2]), "+f"(d[3]) : "r"(a0), "r"(a1), "r"(b0));
}
DEVI void mma8z(float (&d)[4], uint32_t a0, uint32_t a1, uint32_t b0) {
    asm volatile("mma.sync.aligned.m16n8k8.row.col.f32.bf16.bf16.f32 {%0,%1,%2,%3}, {%4,%5}, {%6}, {%7,%7,%7,%7};"
                 : "=f"(d[0]), "=f"(d[1]), "=f"(d[2]), "=f"(d[3]) : "r"(a0), "r"(a1), "r"(b0), "f"(0.f));
}
DEVI uint32_t pack2(float lo, float hi) {
    uint32_t r;
    asm("cvt.rn.bf16x2.f32 %0, %1, %2;" : "=r"(r) : "f"(hi), "f"(lo));
    return r;
}
DEVI uint32_t hadd2(uint32_t a, uint32_t b) {
    uint32_t r;
    asm("add.rn.bf16x2 %0, %1, %2;" : "=r"(r) : "r"(a), "r"(b));
    return r;
}
DEVI float lo_f(uint32_t x) { return __uint_as_float(x << 16); }
DEVI float hi_f(uint32_t x) { return __uint_as_float(x & 0xFFFF0000u); }
template <uint32_t OFF> DEVI uint4 ldg4(uint32_t lo, uint32_t hi) {
    uint4 v;
    asm volatile("{\n.reg .b64 a;\nmov.b64 a, {%4,%5};\nld.relaxed.gpu.global.v4.u32 {%0,%1,%2,%3}, [a+%6];\n}"
                 : "=r"(v.x), "=r"(v.y), "=r"(v.z), "=r"(v.w) : "r"(lo), "r"(hi), "n"(OFF) : "memory");
    return v;
}
template <uint32_t OFF> DEVI uint2 ldg2(uint32_t lo, uint32_t hi) {
    uint2 v;
    asm volatile("{\n.reg .b64 a;\nmov.b64 a, {%2,%3};\nld.relaxed.gpu.global.v2.u32 {%0,%1}, [a+%4];\n}"
                 : "=r"(v.x), "=r"(v.y) : "r"(lo), "r"(hi), "n"(OFF) : "memory");
    return v;
}
template <uint32_t OFF> DEVI uint32_t ldg1(uint32_t lo, uint32_t hi) {
    uint32_t v;
    asm volatile("{\n.reg .b64 a;\nmov.b64 a, {%1,%2};\nld.relaxed.gpu.global.u32 %0, [a+%3];\n}" : "=r"(v) : "r"(lo), "r"(hi), "n"(OFF) : "memory");
    return v;
}
template <uint32_t OFF> DEVI void stg1(uint32_t lo, uint32_t hi, uint32_t a) {
    asm volatile("{\n.reg .b64 a;\nmov.b64 a, {%0,%1};\nst.relaxed.gpu.global.u32 [a+%3], %2;\n}" ::"r"(lo), "r"(hi), "r"(a), "n"(OFF) : "memory");
}
template <uint32_t OFF> DEVI void stg4(uint32_t lo, uint32_t hi, uint32_t a, uint32_t b, uint32_t c, uint32_t d) {
    asm volatile("{\n.reg .b64 a;\nmov.b64 a, {%0,%1};\nst.relaxed.gpu.global.v4.u32 [a+%6], {%2,%3,%4,%5};\n}"
                 ::"r"(lo), "r"(hi), "r"(a), "r"(b), "r"(c), "r"(d), "n"(OFF) : "memory");
}
template <uint32_t OFF> DEVI void stg2(uint32_t lo, uint32_t hi, uint32_t a, uint32_t b) {
    asm volatile("{\n.reg .b64 a;\nmov.b64 a, {%0,%1};\nst.relaxed.gpu.global.v2.u32 [a+%4], {%2,%3};\n}"
                 ::"r"(lo), "r"(hi), "r"(a), "r"(b), "n"(OFF) : "memory");
}
DEVI uint32_t tagx2(uint32_t a, uint32_t b, uint32_t t) { uint32_t r; asm("lop3.b32 %0, %1, %2, %3, 0x7E;" : "=r"(r) : "r"(a), "r"(b), "r"(t)); return r; }
DEVI uint32_t tagx1(uint32_t a, uint32_t b, uint32_t t) { uint32_t r; asm("lop3.b32 %0, %1, %2, %3, 0xF6;" : "=r"(r) : "r"(a), "r"(b), "r"(t)); return r; }
DEVI uint32_t or3(uint32_t a, uint32_t b, uint32_t c) { uint32_t r; asm("lop3.b32 %0, %1, %2, %3, 0xFE;" : "=r"(r) : "r"(a), "r"(b), "r"(c)); return r; }
DEVI bool any_bad(uint32_t x) { return __any_sync(0xFFFFFFFFu, (x & 1u) != 0); }
DEVI uint32_t settag(uint32_t x, uint32_t tag) { return (x & ~1u) | tag; }
DEVI void sts32f(uint32_t a, float v) { asm volatile("st.shared.f32 [%0], %1;" ::"r"(a), "f"(v) : "memory"); }
DEVI void sts32(uint32_t a, uint32_t v) { asm volatile("st.shared.u32 [%0], %1;" ::"r"(a), "r"(v) : "memory"); }
DEVI void sts16(uint32_t a, uint32_t v) { asm volatile("st.shared.u16 [%0], %1;" ::"r"(a), "h"((unsigned short)v) : "memory"); }
DEVI void sts64(uint32_t a, uint32_t x, uint32_t y) { asm volatile("st.shared.v2.u32 [%0], {%1,%2};" ::"r"(a), "r"(x), "r"(y) : "memory"); }
DEVI void sts128(uint32_t a, uint32_t x, uint32_t y, uint32_t z, uint32_t w) {
    asm volatile("st.shared.v4.u32 [%0], {%1,%2,%3,%4};" ::"r"(a), "r"(x), "r"(y), "r"(z), "r"(w) : "memory");
}
DEVI float4 lds128f(uint32_t a) {
    float4 v;
    asm volatile("ld.shared.v4.f32 {%0,%1,%2,%3}, [%4];" : "=f"(v.x), "=f"(v.y), "=f"(v.z), "=f"(v.w) : "r"(a) : "memory");
    return v;
}
DEVI uint4 lds128(uint32_t a) {
    uint4 v;
    asm volatile("ld.shared.v4.u32 {%0,%1,%2,%3}, [%4];" : "=r"(v.x), "=r"(v.y), "=r"(v.z), "=r"(v.w) : "r"(a) : "memory");
    return v;
}
DEVI uint2 lds64(uint32_t a) {
    uint2 v;
    asm volatile("ld.shared.v2.u32 {%0,%1}, [%2];" : "=r"(v.x), "=r"(v.y) : "r"(a) : "memory");
    return v;
}
DEVI uint32_t lds32(uint32_t a) {
    uint32_t v;
    asm volatile("ld.shared.u32 %0, [%1];" : "=r"(v) : "r"(a) : "memory");
    return v;
}
DEVI float ex2(float x) { float r; asm("ex2.approx.ftz.f32 %0, %1;" : "=f"(r) : "f"(x)); return r; }
DEVI float rcp(float x) { float r; asm("rcp.approx.ftz.f32 %0, %1;" : "=f"(r) : "f"(x)); return r; }
DEVI uint32_t clk() { uint32_t c; asm volatile("mov.u32 %0, %%clock;" : "=r"(c)::"memory"); return c; }

DEVI uint64_t mkdesc(uint32_t addr, uint32_t lbo, uint32_t sbo) {
    return (uint64_t)((addr & 0x3FFFF) >> 4) | ((uint64_t)(lbo >> 4) << 16) | ((uint64_t)(sbo >> 4) << 32) | ((uint64_t)1 << 62);
}
DEVI void wg_fence() { asm volatile("wgmma.fence.sync.aligned;" ::: "memory"); }
DEVI void wg_commit() { asm volatile("wgmma.commit_group.sync.aligned;" ::: "memory"); }
template <int N> DEVI void wg_wait() { asm volatile("wgmma.wait_group.sync.aligned %0;" ::"n"(N) : "memory"); }
template <int SC>
DEVI void wg_rs32(float (&d)[16], const uint32_t (&a)[4], uint64_t db) {
    if (SC) {
        asm volatile("wgmma.mma_async.sync.aligned.m64n32k16.f32.bf16.bf16 "
                     "{%0,%1,%2,%3,%4,%5,%6,%7,%8,%9,%10,%11,%12,%13,%14,%15}, {%16,%17,%18,%19}, %20, 1, 1, 1, 0;"
                     : "+f"(d[0]), "+f"(d[1]), "+f"(d[2]), "+f"(d[3]), "+f"(d[4]), "+f"(d[5]), "+f"(d[6]), "+f"(d[7]),
                       "+f"(d[8]), "+f"(d[9]), "+f"(d[10]), "+f"(d[11]), "+f"(d[12]), "+f"(d[13]), "+f"(d[14]), "+f"(d[15])
                     : "r"(a[0]), "r"(a[1]), "r"(a[2]), "r"(a[3]), "l"(db));
    } else {
        asm volatile("wgmma.mma_async.sync.aligned.m64n32k16.f32.bf16.bf16 "
                     "{%0,%1,%2,%3,%4,%5,%6,%7,%8,%9,%10,%11,%12,%13,%14,%15}, {%16,%17,%18,%19}, %20, 0, 1, 1, 0;"
                     : "=f"(d[0]), "=f"(d[1]), "=f"(d[2]), "=f"(d[3]), "=f"(d[4]), "=f"(d[5]), "=f"(d[6]), "=f"(d[7]),
                       "=f"(d[8]), "=f"(d[9]), "=f"(d[10]), "=f"(d[11]), "=f"(d[12]), "=f"(d[13]), "=f"(d[14]), "=f"(d[15])
                     : "r"(a[0]), "r"(a[1]), "r"(a[2]), "r"(a[3]), "l"(db));
    }
}

#define NA 12
#define NPF 6
#define PF1 2
#define PF2 2
#define PF3 5
#define WPF 2
#define VPF 2
#define VORD (NA == 12 ? 0x01234567 : NA == 10 ? 0x50123467 : NA == 8 ? 0x40125367 : 0x30142567)
#define WV_BOX ((16 - NA) * 2048)
#define WO_BOX 16384
#define SM_WV 0
#define SM_WO (2 * WV_BOX)
#define SM_X (SM_WO + 4 * WO_BOX)
#define SM_XO (SM_X + 32768)
#define SM_TR (SM_XO + 12288)
#define SM_MEMT (SM_TR + 12288)
#define SM_OT (SM_MEMT + 4096)
#define SM_VS (SM_OT + 2048)
#define SM_KV (SM_VS + 2048)
#define SM_SP (SM_KV + 18432)
#define SM_P (SM_SP + 10240)
#define SM_DN (SM_P + 1792)
#define SM_PROF (SM_P + 2048)
#define SM_PI (SM_X + 131072)
#define SM_BAR 232192
#define SM_TOTAL (SM_BAR + 256)
#define SM_STA SM_X
#define SM_STB (SM_STA + 65536)
static_assert(SM_PI + 12288 <= SM_BAR && SM_KV == SM_STB, "staging");
static_assert(SM_TOTAL <= 232448, "smem");
#define BAR_XA 32
#define BAR_KV 40
#define BAR_PI 48
#define BAR_RO 64
#define SM_ROLE (SM_BAR + 72)

#define SPIN_LIMIT (1 << 20)
#define RPOS 20
#define OPOS 2
#define ASF 0
#define KPOS 0
#define CPOS 1
#define DLY_V 400
#define NPRB 3
#define OPF 0
#define OPG 1
#define DLY_O 1000
#define ASP 4
#define EPF 0
#define CFAR 1

template <int ID, int N> DEVI void bsync() { asm volatile("bar.sync %0, %1;" ::"n"(ID), "n"(N) : "memory"); }
template <int ID, int N> DEVI void barv() { asm volatile("bar.arrive %0, %1;" ::"n"(ID), "n"(N) : "memory"); }

#define PT(n)
#define PC(n, v)
#define PDUMP()
#define REFRESH() asm volatile("xor.b32 %0, %0, %1;" : "+r"(l16) : "r"(zero))
#define OPQ(x) asm volatile("xor.b32 %0, %0, %1;" : "+r"(x) : "r"(zero))
#define KEEP(x, a, b, c, d) asm volatile("{\n.reg .b32 t;\nlop3.b32 t, %1, %2, %3, 0x80;\nlop3.b32 t, t, %4, %5, 0x80;\nxor.b32 %0, %0, t;\n}" \
                                         : "+r"(x) : "r"(a), "r"(b), "r"(c), "r"(d), "r"(zero))
#define SF() asm volatile("pmevent 1;" ::: "memory")
#define MF() __syncwarp()
#define SB0 1024u

#define XDOFF(ks) ((((ks) >> 2) * 1024 + ((ks) & 3) * 32) >> 4)
template <int SC>
DEVI void wg_ss32t(float (&d)[16], uint64_t da, uint64_t db) {
    if (SC) {
        asm volatile("wgmma.mma_async.sync.aligned.m64n32k16.f32.bf16.bf16 "
                     "{%0,%1,%2,%3,%4,%5,%6,%7,%8,%9,%10,%11,%12,%13,%14,%15}, %16, %17, 1, 1, 1, 1, 0;"
                     : "+f"(d[0]), "+f"(d[1]), "+f"(d[2]), "+f"(d[3]), "+f"(d[4]), "+f"(d[5]), "+f"(d[6]), "+f"(d[7]),
                       "+f"(d[8]), "+f"(d[9]), "+f"(d[10]), "+f"(d[11]), "+f"(d[12]), "+f"(d[13]), "+f"(d[14]), "+f"(d[15])
                     : "l"(da), "l"(db));
    } else {
        asm volatile("wgmma.mma_async.sync.aligned.m64n32k16.f32.bf16.bf16 "
                     "{%0,%1,%2,%3,%4,%5,%6,%7,%8,%9,%10,%11,%12,%13,%14,%15}, %16, %17, 0, 1, 1, 1, 0;"
                     : "=f"(d[0]), "=f"(d[1]), "=f"(d[2]), "=f"(d[3]), "=f"(d[4]), "=f"(d[5]), "=f"(d[6]), "=f"(d[7]),
                       "=f"(d[8]), "=f"(d[9]), "=f"(d[10]), "=f"(d[11]), "=f"(d[12]), "=f"(d[13]), "=f"(d[14]), "=f"(d[15])
                     : "l"(da), "l"(db));
    }
}

DEVI void delay_until(uint32_t t0, uint32_t d) { t0 += d; while (clk() < t0) {} }

template <int I0, int I1>
DEVI void xmma(float (&xa)[16], float (&xb)[16], uint32_t w, int ps, uint32_t zero, const uint32_t (&Wq)[16][4], const uint32_t (&Wk)[16][4],
               const uint32_t (&Wv)[NA][4]) {
    const uint64_t xd = mkdesc(SB0 + SM_X, 16, 4096) + (ps & 1) * 1024, vd = mkdesc(SB0 + SM_WV, 8192, 1024);
    uint32_t vo = (w >> 2) * (WV_BOX / 16);
    if (I0 < 16 - NA) OPQ(vo);
#pragma unroll
    for (int i = I0; i < I1; i++) {
        if (i == 0) wg_ss32t<0>(xb, (vd & ~0xFFFFFFFFull) | ((uint32_t)vd + vo), xd + XDOFF(NA));
        else if (i < 16 - NA) wg_ss32t<1>(xb, (vd & ~0xFFFFFFFFull) | ((uint32_t)vd + i * 128 + vo), xd + XDOFF(NA + i));
        else if (i == 16 - NA) wg_rs32<0>(xa, Wq[0], xd);
        else if (i < 32 - NA) wg_rs32<1>(xa, Wq[(i + NA) & 15], xd + XDOFF((i + NA) & 15));
        else if (i < 32) wg_rs32<1>(xb, Wv[(i + NA) & 15], xd + XDOFF((i + NA) & 15));
        else if (i == 32) wg_rs32<0>(xa, Wk[0], xd);
        else wg_rs32<1>(xa, Wk[i & 15], xd + XDOFF(i & 15));
    }
    wg_commit();
}
#define XMMA(I0, I1) xmma<(I0), (I1)>(xa, xb, w, p ^ 1, zero, Wq, Wk, Wv)
DEVI void wg_done(float (&d)[16]) {
    asm volatile("" : "+f"(d[0]), "+f"(d[1]), "+f"(d[2]), "+f"(d[3]), "+f"(d[4]), "+f"(d[5]), "+f"(d[6]), "+f"(d[7]),
                      "+f"(d[8]), "+f"(d[9]), "+f"(d[10]), "+f"(d[11]), "+f"(d[12]), "+f"(d[13]), "+f"(d[14]), "+f"(d[15]) :: "memory");
}
template <int M>
DEVI void xpack(uint32_t (&xp)[8], float (&xa)[16]) {
    wg_done(xa);
#pragma unroll
    for (int i = 0; i < 4; i++) {
        xp[2 * i] = pack2(xa[4 * i], xa[4 * i + (M < 2 ? 2 : 1)]);
        xp[2 * i + 1] = pack2(xa[4 * i + (M < 2 ? 1 : 2)], xa[4 * i + 3]);
    }
}
template <int M>
DEVI uint4 xpeer(uint32_t sb, int ps, uint32_t t16) { return lds128(sb + SM_PI - ((ps & 1) ^ 1) * 12288 + M * 4096 + t16); }
DEVI void xadd(uint32_t (&xp)[8], const uint4& pi) {
    xp[0] = hadd2(xp[0], pi.x); xp[1] = hadd2(xp[1], pi.y); xp[2] = hadd2(xp[2], pi.z); xp[3] = hadd2(xp[3], pi.w);
}
template <int M>
DEVI void xsend(const uint32_t (&xp)[8], uint32_t sb, int ps, uint32_t t16) {
    asm volatile("st.async.weak.shared::cluster.mbarrier::complete_tx::bytes.v4.b32 [%0], {%1,%2,%3,%4}, [%5];"
                 ::"r"((sb ^ 0x1000000) + SM_PI - (ps & 1) * 12288 + M * 4096 + t16), "r"(xp[4]), "r"(xp[5]), "r"(xp[6]), "r"(xp[7]),
                   "r"((sb ^ 0x1000000) + SM_BAR + BAR_PI + (ps & 1) * 8) : "memory");
}
template <int M>
DEVI void xstore(const uint32_t (&xp)[8], uint32_t sb, uint32_t sbw, int ps, uint32_t t16, uint32_t KA) {
    const uint32_t a = SM_XO + M * 2048 + (M < 2 ? (KA & 0xFF) + sbw : (t16 >> 1) + sb);
    sts64(a, xp[0], xp[1]);
    sts64(a + 6144, xp[2], xp[3]);
    xsend<M>(xp, sb, ps, t16);
}
template <int M>
DEVI void xpark(uint32_t (&xp)[8], const uint4& pi, uint32_t sb, uint32_t sbw, int ps, uint32_t t16, uint32_t KA) {
    xadd(xp, pi);
    xstore<M>(xp, sb, sbw, ps, t16, KA);
}
template <uint32_t OFF> DEVI void red2(uint32_t lo, uint32_t hi, uint32_t a, uint32_t b) {
    asm volatile("{\n.reg .b64 a;\nmov.b64 a, {%0,%1};\nred.relaxed.gpu.global.add.noftz.v2.bf16x2 [a+%4], {%2,%3};\n}"
                 ::"r"(lo), "r"(hi), "r"(a), "r"(b), "n"(OFF) : "memory");
}
template <int M, int N>
DEVI void xstart(uint32_t sb, uint32_t w, uint32_t ga, uint32_t xhi, uint32_t j, uint32_t t16, uint32_t KA, const uint32_t (&W)[N][4]) {
    float xa[16], xb[16];
    uint32_t xp[8];
    auto pass = [&](float (&d)[16], int i, int k0, int k1) {
        const uint64_t xd = mkdesc(SB0 + SM_WO + i * 16384, 16, 4096), vd = mkdesc(SB0 + SM_WV, 8192, 1024) + (w >> 2) * (WV_BOX / 16);
#pragma unroll
        for (int k = k0; k < k1; k++) {
            if (k == 0) wg_rs32<0>(d, W[0], xd);
            else if (k < N) wg_rs32<1>(d, W[k < N ? k : 0], xd + XDOFF(k));
            else wg_ss32t<1>(d, vd + (k - N) * 128, xd + XDOFF(k));
        }
        wg_commit();
    };
    if (M < 2) {
        asm volatile("fence.proxy.async.shared::cta;" ::: "memory");
        barv<9, 384>();
    }
    wg_fence();
    pass(xa, 0, 0, 16);
    pass(xb, 1, 0, ASP);
    if (M == 0) bsync<5, 384>();
    ga += M < 2 ? (KA & 0xFF) + w * 256 : t16 >> 1;
    constexpr uint32_t O = XO_XG + M * 2048, SG = 128 * 6144;
    wg_wait<1>();
    xpack<M>(xp, xa);
    red2<O>(ga, xhi, xp[0], xp[1]); red2<O + 6144>(ga, xhi, xp[2], xp[3]); red2<O + 12288>(ga, xhi, xp[4], xp[5]); red2<O + 18432>(ga, xhi, xp[6], xp[7]);
    if (M == 2) barv<3, 384>();
    wg_fence();
    if (ASP < 16) pass(xb, 1, ASP, 16);
    pass(xa, 2, 0, 16);
    wg_wait<1>();
    xpack<M>(xp, xb);
    red2<O + SG>(ga, xhi, xp[0], xp[1]); red2<O + SG + 6144>(ga, xhi, xp[2], xp[3]);
    red2<O + SG + 12288>(ga, xhi, xp[4], xp[5]); red2<O + SG + 18432>(ga, xhi, xp[6], xp[7]);
    wg_wait<0>();
    xpack<M>(xp, xa);
    red2<O + 2 * SG>(ga + j * 6144, xhi, xp[0], xp[1]);
    red2<O + 2 * SG>(ga + (j ^ 1) * 6144, xhi, xp[2], xp[3]);
    xsend<M>(xp, sb, 0, t16);
}
DEVI void piwait(uint32_t sb, int p, int ps) { mbar_wait(sb + SM_BAR + BAR_PI + p * 8, ((ps + 2) >> 1) & 1); }

DEVI uint32_t par(uint32_t off) { return __popc(off & 0xB2000u) & 1; }
DEVI uint32_t probe(uint32_t lo, uint32_t hi) {
    uint32_t best = 0xFFFFFFFFu, x = 0;
    stg4<0>(lo, hi, 0, 0, 0, 0);
    stg4<16>(lo, hi, 0, 0, 0, 0);
#pragma unroll 1
    for (int r = 0; r < NPRB; r++) {
        const uint32_t t0 = clk();
        asm volatile("{\n.reg .b64 a;\nmov.b64 a, {%1,%2};\natom.relaxed.gpu.global.add.u32 %0, [a], 2;\n}" : "=r"(x) : "r"(lo), "r"(hi) : "memory");
        if (x == 0xFFFFFFFFu) die(1 << 23);
        best = min(best, clk() - t0);
    }
    return best;
}

DEVI void xload(uint32_t sb, uint32_t u, uint32_t j, int ps, const CUtensorMap* tmx) {
    if (elect()) {
        const uint32_t sg = ps + 4 - (u & 1) + (u >> 1);
        mbar_expect(sb + SM_BAR + BAR_XA, sg < NSEG ? 4096 : 0);
        if (sg < NSEG) tma3d(sb + SM_X + (ps & 1) * 16384 + u * 4096, tmx, sb + SM_BAR + BAR_XA, 0, sg * 32 + (j ^ ((u & 1) * 2 + (u >> 1))) * 8, j * 4);
    }
}
DEVI uint32_t rpage(uint32_t j, int s) { return (s & 3) * 65536 + (j & 1) * 8192 + (((s ^ (s >> 1) ^ j ^ (j >> 1)) & 1) << 12); }

#define RLOAD(a) { m0 = ldg4<XO_R>(a, xhi); n0 = ldg4<XO_R + 16384>(a, xhi); \
                   e0 = ldg1<XO_R + 32768>(((a) & ~0xFFFu) + (((a) & 0xFFF) >> 2), xhi); f0 = ldg1<XO_R + 33792>(((a) & ~0xFFFu) + (((a) & 0xFFF) >> 2), xhi); }
DEVI bool ruse(uint32_t a, const uint4& m0, const uint4& n0, uint32_t e0, uint32_t f0) {
    const uint32_t a0 = hadd2(m0.w, n0.w), b0 = hadd2(e0, f0);
    stsm4(a, hadd2(m0.x, n0.x), hadd2(m0.y, n0.y), hadd2(m0.z, n0.z), __byte_perm(a0, b0, 0x5410));
    return __any_sync(0xFFFFFFFFu, (a0 & b0 & 0x42000000u) != 0x42000000u);
}

#define GST(i) (SM_WO + (i) * 49152)
#define BAR_GF 128
#define BAR_GE (BAR_GF + 64)
#define BAR_GX (BAR_GE + 32)
#define D4(c, i) #c "f"(d[i]), #c "f"(d[i + 1]), #c "f"(d[i + 2]), #c "f"(d[i + 3])
#define D16(c, i) D4(c, i), D4(c, i + 4), D4(c, i + 8), D4(c, i + 12)
DEVI void mwait(uint32_t bar, uint32_t parity) {
    asm volatile("{\n.reg .pred p;\n.reg .b32 c;\nmbarrier.try_wait.parity.shared::cta.b64 p, [%0], %1;\n@p bra.uni D;\nmov.b32 c, 0;\n"
                 "L:\nadd.u32 c, c, 1;\nsetp.gt.u32 p, c, 4194304;\n@p st.shared.u32 [c], c;\n"
                 "mbarrier.try_wait.parity.shared::cta.b64 p, [%0], %1;\n@!p bra.uni L;\nD:\n}" ::"r"(bar), "r"(parity) : "memory");
}
DEVI void wg_ss256t(float (&d)[128], uint64_t da, uint64_t db) {
    asm volatile("wgmma.mma_async.sync.aligned.m64n256k16.f32.bf16.bf16 "
        "{%0,%1,%2,%3,%4,%5,%6,%7,%8,%9,%10,%11,%12,%13,%14,%15,%16,%17,%18,%19,%20,%21,%22,%23,%24,%25,%26,%27,%28,%29,%30,%31,%32,%33,%34,%35,%36,%37,%38,%39,%40,%41,%42,%43,%44,%45,%46,%47,%48,%49,%50,%51,%52,%53,%54,%55,%56,%57,%58,%59,%60,%61,%62,%63,%64,%65,%66,%67,%68,%69,%70,%71,%72,%73,%74,%75,%76,%77,%78,%79,%80,%81,%82,%83,%84,%85,%86,%87,%88,%89,%90,%91,%92,%93,%94,%95,%96,%97,%98,%99,%100,%101,%102,%103,%104,%105,%106,%107,%108,%109,%110,%111,%112,%113,%114,%115,%116,%117,%118,%119,%120,%121,%122,%123,%124,%125,%126,%127}, "
        "%128, %129, 1, 1, 1, 1, 1;"
        : D16(+, 0), D16(+, 16), D16(+, 32), D16(+, 48), D16(+, 64), D16(+, 80), D16(+, 96), D16(+, 112) : "l"(da), "l"(db));
}
template <int O, int KB> DEVI void g_half(float (&d)[64], uint64_t da) {
    const uint64_t db = mkdesc(SB0 + GST(KB & 3) + 16384 + O * 256, 8192, 1024);
#pragma unroll
    for (int k = 0; k < 4; k++)
        asm volatile("wgmma.mma_async.sync.aligned.m64n128k16.f32.bf16.bf16 "
            "{%0,%1,%2,%3,%4,%5,%6,%7,%8,%9,%10,%11,%12,%13,%14,%15,%16,%17,%18,%19,%20,%21,%22,%23,%24,%25,%26,%27,%28,%29,%30,%31,%32,%33,%34,%35,%36,%37,%38,%39,%40,%41,%42,%43,%44,%45,%46,%47,%48,%49,%50,%51,%52,%53,%54,%55,%56,%57,%58,%59,%60,%61,%62,%63}, "
            "%64, %65, 1, 1, 1, 1, 1;"
            : D16(+, 0), D16(+, 16), D16(+, 32), D16(+, 48) : "l"(da + (KB & 3) * 3072 + k * 16), "l"(db + k * 128));
}
DEVI void g_load(uint32_t sb, uint32_t u, uint32_t role, uint32_t kb, uint32_t xlo, uint32_t xhi, const CUtensorMap* tmb) {
    const uint32_t st = kb & 3, bar = sb + SM_BAR + BAR_GF + u * 32 + st * 8, dst = sb + GST(st), k = (role & 1) * 32 + kb;
    if (!elect()) return;
    mbar_expect(bar, u ? 8192 : 40960);
    bulk_g2s(dst + u * 8192, xlo + XO_OX + ((role >> 3) * 64 + k) * 16384 + u * 8192, xhi, 8192, bar);
    if (u == 0) {
        tma3d(dst + 16384, tmb, bar, 0, k * 64, ((role & 7) ^ 1) * 2);
        tma3d(dst + 32768, tmb, bar, 0, k * 64, (role & 7) * 2);
    }
}
DEVI void g_arrive(uint32_t a, uint32_t xhi, uint32_t n) {
    if (elect()) asm volatile("{\n.reg .b64 a;\nmov.b64 a, {%0,%1};\nred.release.gpu.global.inc.u32 [a], %2;\n}" ::"r"(a), "r"(xhi), "r"(n - 1) : "memory");
}
DEVI void g_wait(uint32_t a, uint32_t xhi) {
    int it = 0;
    uint32_t v;
    do {
        asm volatile("{\n.reg .b64 a;\nmov.b64 a, {%1,%2};\nld.acquire.gpu.global.u32 %0, [a];\n}" : "=r"(v) : "r"(a), "r"(xhi) : "memory");
        if (++it > SPIN_LIMIT) die(it);
    } while (__any_sync(0xFFFFFFFFu, v));
    asm volatile("fence.proxy.async.global;" ::: "memory");
}
#define GD 200
DEVI void g_done(float (&d)[64]) { asm volatile("" : D16(+, 0), D16(+, 16), D16(+, 32), D16(+, 48)::"memory"); }
DEVI void g_main(uint32_t sb, uint32_t w, uint32_t role, const CUtensorMap* tmy) {
    const uint32_t bar = sb + SM_BAR, t16 = threadIdx.x * 16;
    const uint64_t da = (mkdesc(SB0 + GST(0), 128, 1024) & ~((uint64_t)3 << 62)) + (w >> 2) * 512;
    float d[128];
#pragma unroll
    for (int i = 0; i < 128; i++) d[i] = 0.f;
#define GFULL(kb) { mwait(bar + BAR_GF + ((kb) & 3) * 8, ((kb) >> 2) & 1); if (w >= 4) mwait(bar + BAR_GF + 32 + ((kb) & 3) * 8, ((kb) >> 2) & 1); }
#pragma unroll 1
    for (uint32_t kb = 0; kb < 29; kb++) {
        GFULL(kb);
        if (kb == 0 && threadIdx.x == 128) PG(4);
        if (kb == 4 && threadIdx.x == 0) PG(5);
        const uint64_t a = da + (kb & 3) * 3072, b = mkdesc(SB0 + GST(0) + 16384, 8192, 1024) + (kb & 3) * 3072;
        wg_fence();
#pragma unroll
        for (int k = 0; k < 4; k++) wg_ss256t(d, a + k * 16, b + k * 128);
        wg_commit();
        wg_wait<1>();
        if (kb > 0 && elect()) mbar_arrive(bar + BAR_GE + ((kb - 1) & 3) * 8);
    }
    GFULL(29);
    GFULL(30);
    GFULL(31);
    wg_wait<0>();
    float x[64], y[64];
#pragma unroll
    for (int i = 0; i < 64; i++) asm volatile("mov.b32 %0, %1;" : "=f"(x[i]) : "f"(d[i]) : "memory");
    SF();
#pragma unroll
    for (int i = 0; i < 64; i++) asm volatile("mov.b32 %0, %1;" : "=f"(y[i]) : "f"(d[i + 64]) : "memory");
    SF();
    if (elect()) asm volatile("mbarrier.arrive.relaxed.cluster.shared::cluster.b64 _, [%0];" ::"r"((bar ^ 0x1000000) + BAR_GX) : "memory");
    wg_fence();
    g_half<0, 29>(x, da);
    g_half<0, 30>(x, da);
    g_half<0, 31>(x, da);
    wg_commit();
    g_half<64, 29>(y, da);
    wg_commit();
    wg_wait<1>();
    g_done(x);
    mwait(bar + BAR_GX, 0);
#define GSEND(i0) _Pragma("unroll") for (int i = (i0); i < (i0) + 4; i++) \
        asm volatile("st.async.weak.shared::cluster.mbarrier::complete_tx::bytes.v4.b32 [%0], {%1,%2,%3,%4}, [%5];" \
                     ::"r"((sb ^ 0x1000000) + i * 4096 + t16), "r"(pack2(x[8 * i], x[8 * i + 1])), "r"(pack2(x[8 * i + 2], x[8 * i + 3])), \
                       "r"(pack2(x[8 * i + 4], x[8 * i + 5])), "r"(pack2(x[8 * i + 6], x[8 * i + 7])), "r"((bar ^ 0x1000000) + BAR_GX + 8) : "memory")
    GSEND(0);
    wg_fence();
    g_half<64, 30>(y, da);
    wg_commit();
    GSEND(4);
    wg_fence();
    g_half<64, 31>(y, da);
    wg_commit();
    wg_wait<0>();
    g_done(y);
    if (threadIdx.x == 0) PG(7);
    mwait(bar + BAR_GX + 8, 0);
    if (threadIdx.x == 0) PG(1);
    const uint32_t lane = threadIdx.x & 31, o = sb + GST(1) + w * 2048;
#pragma unroll
    for (int i = 0; i < 8; i++) {
        const uint4 a = lds128(sb + i * 4096 + t16);
        const float* e = y + 8 * i;
        stsm4(o + (i >> 2) * 49152 + (lane & 15) * 128 + ((((i & 3) * 2 + (lane >> 4)) ^ (lane & 7)) << 4),
              pack2(e[0] + lo_f(a.x), e[1] + hi_f(a.x)), pack2(e[2] + lo_f(a.y), e[3] + hi_f(a.y)),
              pack2(e[4] + lo_f(a.z), e[5] + hi_f(a.z)), pack2(e[6] + lo_f(a.w), e[7] + hi_f(a.w)));
        if (i == 3 || i == 7) {
            asm volatile("fence.proxy.async.shared::cta;" ::: "memory");
            __syncwarp();
            if (elect())
                asm volatile("cp.async.bulk.tensor.2d.global.shared::cta.bulk_group [%0, {%2, %3}], [%1];\ncp.async.bulk.commit_group;"
                             ::"l"(tmy), "r"(o + (i >> 2) * 49152), "r"((role & 7) * 128 + (i >> 2) * 64), "r"((role >> 3) * 128 + w * 16) : "memory");
        }
    }
    if (threadIdx.x == 0) PG(6);
    asm volatile("cp.async.bulk.wait_group.read 0;" ::: "memory");
}

DEVI void kvload(uint32_t sb, uint32_t u, uint32_t h, uint32_t j, int sg, uint32_t xlo, uint32_t xhi) {
    const uint32_t o = u == 0 ? 0 : 2048;
    mbar_expect(sb + SM_BAR + BAR_KV, 6144 - o);
    bulk_g2s(sb + SM_KV + u * 4096 + o, xlo + XO_XG + (((sg & 7) * 32 + h) * 4 + ((j + u) & 3)) * 6144 + o, xhi, 6144 - o, sb + SM_BAR + BAR_KV);
}
DEVI void helper_step(uint32_t sb, uint32_t w, uint32_t h, uint32_t j, uint32_t& l16, uint32_t xlo, uint32_t xhi, uint32_t zero, int s,
                      const CUtensorMap* tmx, const CUtensorMap* tmb) {
    const uint32_t u = w - 8, bq = sb + SM_BAR;
    bsync<1, 384>();
    PT(0);
    PDUMP();
    PT(1);
    if (s == NSEG - 2 && u < 2) g_arrive(xlo + XO_TK + 128, xhi, 256);
    const uint32_t ctag = ((s >> 1) & 1) ^ 1;
    const uint32_t av = xlo + ((s & 1) * 32 + h) * 8192 + u * 512;
    mbar_wait(bq + BAR_XA, (s + 1) & 1);
    bsync<8, 384>();
    delay_until(clk(), DLY_V);
    PT(4);
    int it = 0;
    bool bad;
    do {
        const uint4 d1 = ldg4<XO_CV>(av + (j ^ 1) * 2048 + l16, xhi);
        const uint4 d2 = ldg4<XO_CV>(av + (j ^ 2) * 2048 + l16, xhi);
        const uint4 d3 = ldg4<XO_CV>(av + (j ^ 3) * 2048 + l16, xhi);
        bad = any_bad(or3(tagx2(d1.x, d1.z, ctag), tagx2(d2.x, d2.z, ctag), tagx2(d3.x, d3.z, ctag)));
        sts128(sb + SM_VS + u * 512 + l16, hadd2(hadd2(d1.x, d2.x), d3.x), hadd2(hadd2(d1.y, d2.y), d3.y), hadd2(hadd2(d1.z, d2.z), d3.z),
               hadd2(hadd2(d1.w, d2.w), d3.w));
        REFRESH();
        if (++it > SPIN_LIMIT) die(it);
    } while (bad);
    PC(26, it - 1);
    PT(5);
    barv<5, 384>();
    bsync<3, 384>();
    if (u < 2) {
        asm volatile("fence.proxy.async.shared::cta;" ::: "memory");
        if (elect()) {
            const uint32_t sg = s + 3 - u;
            if (sg < NSEG) {
                const uint32_t ga = xlo + XO_XG + (((sg & 7) * 32 + h) * 4 + (j ^ (2 * u))) * 6144, sa = sb + SM_XO + u * 6144;
                if (u == 0) bulk_s2g(ga, xhi, sa, 6144);
                else bulk_red(ga, xhi, sa, 6144);
            }
        }
    }
    PT(6);
    uint32_t old = 0;
    if (u > 0 && s + 3 < NSEG)
        asm volatile("{\n.reg .b64 a;\nmov.b64 a, {%1,%2};\natom.relaxed.gpu.global.exch.b32 %0, [a], 0;\n}"
                     : "=r"(old) : "r"(xlo + XO_R + rpage(j, s + 2) + (u - 1) * 16384 + h * 128 + (l16 >> 2)), "r"(xhi) : "memory");
    PT(7);
    bsync<7, 384>();
    if (s + 1 < NSEG && elect()) kvload(sb, u, h, j, s + 1, xlo, xhi);
    if (u < 2) {
        asm volatile("cp.async.bulk.wait_group.read 0;" ::: "memory");
        if (elect()) mbar_expect(bq + BAR_PI + ((s & 1) ^ 1) * 8, 6144);
    }
    PT(8);
    if (s + 1 < NSEG) bsync<10, 384>();
    xload(sb, u, j, s + 1, tmx);
    if (s == NSEG - 2 && (u == 0 || (u == 1 && h < 30))) {
        g_wait(xlo + XO_TK + 128, xhi);
        g_load(sb, u, h * 4 + j, 0, xlo, xhi, tmb);
        g_load(sb, u, h * 4 + j, 1, xlo, xhi, tmb);
    }
    asm volatile("cp.async.bulk.wait_group 0;" ::: "memory");
    if (s + 1 < NSEG) mbar_wait(bq + BAR_KV, (s + 1) & 1);
    asm volatile("lop3.b32 %0, %0, %1, %2, 0x78;" : "+r"(l16) : "r"(old), "r"(zero));
    PT(15);
}
DEVI void tickets_done(uint32_t* tk) {
    if (atomicInc(tk + 2, gridDim.x / 2 - 64) == gridDim.x / 2 - 64) { tk[0] = 0; tk[1] = 0; }
}

__global__ void __cluster_dims__(2, 1, 1) __launch_bounds__(384, 1)
chain_kernel(const __grid_constant__ CUtensorMap tmq, const __grid_constant__ CUtensorMap tmk,
             const __grid_constant__ CUtensorMap tmv, const __grid_constant__ CUtensorMap tmo,
             const __grid_constant__ CUtensorMap tmx, const __grid_constant__ CUtensorMap tmb, const __grid_constant__ CUtensorMap tmy,
             const bf16* __restrict__ mem0,
             uint32_t xlo, uint32_t xhi, uint32_t zero, int nseg) {
    extern __shared__ __align__(1024) uint8_t smem[];
    if ((smem_u32(smem) & 0xFFFFFF) != SB0) die(1 << 23);
    asm volatile("griddepcontrol.launch_dependents;" ::: "memory");
    const uint32_t w = __reduce_max_sync(0xFFFFFFFFu, threadIdx.x >> 5);
    const uint32_t rk = smem_u32(smem) & 0x1000000;
    const uint32_t sb = __reduce_max_sync(0xFFFFFFFFu, smem_u32(smem));
    const uint32_t bq = sb + SM_BAR, bk = bq + 8, bv = bq + 16, bo = bq + 24;
    uint32_t l16 = __shfl_sync(0xFFFFFFFFu, (threadIdx.x & 31) * 16, threadIdx.x & 31);
    if (threadIdx.x == 0) {
        mbar_init(bq, 1); mbar_init(bk, 1); mbar_init(bv, 1); mbar_init(bo, 1);
        mbar_init(bq + BAR_XA, 4); mbar_init(bq + BAR_KV, 4); mbar_init(bq + BAR_PI, 2); mbar_init(bq + BAR_PI + 8, 2);
        for (int i = 0; i < 14; i++) mbar_init(bq + BAR_GF + i * 8, i < 8 || i == 13 ? 1 : 8);
        mbar_expect(bq + BAR_GX + 8, 32768);
        mbar_init(bq + BAR_RO, 1);
        mbar_expect(bq + BAR_RO, 4);
        mbar_expect(bq + BAR_PI, 6144);
        mbar_expect(bq + BAR_PI, 6144);
        asm volatile("fence.mbarrier_init.release.cluster;" ::: "memory");
        asm volatile("fence.proxy.async.shared::cta;" ::: "memory");
    }
    __syncwarp();
    asm volatile("barrier.cluster.arrive.relaxed.aligned;" ::: "memory");
    if (w >= 8) {
        const uint32_t b = blockIdx.x, u = w - 8, l = l16 >> 4;
        if (b < 128) {
            uint32_t v = 0;
            const unsigned short* m0 = (const unsigned short*)mem0 + (b & 3) * 256;
            if (u == 1) {
                const uint32_t x = (b >> 2) * 8 + (l >> 2), d = (x & ~31u) + (l & 3) * 8 + ((x & 31) >> 2) + (x & 3) * 2 * DM;
                v = m0[d] | (((l & 3) == 3 ? 0x4200u : m0[d + DM]) << 16);
            }
            if (u == 3 && b < 32) v = m0[(b >> 2) * 32 + 24 + (l >> 2) + ((l & 3) * 2 + 1) * DM] | 0x42000000u;
#pragma unroll
            for (uint32_t i = 0; i < 9; i++) stg4<XO_XG>(xlo + ((i / 3) * 128 + b) * 6144 + (i % 3) * 2048 + u * 512 + l16, xhi, 0, 0, 0, 0);
            if (u > 0) {
                const uint32_t o = xlo + (u - 1) * 16384 + (b >> 2) * 128 + l * 4;
                stg1<XO_R>(o + rpage(b & 3, 0), xhi, 0);
                stg1<XO_R>(o + rpage(b & 3, 1), xhi, 0);
                stg1<XO_R>(o + rpage(b & 3, -1), xhi, v);
            }
            if (u == 0 && elect()) {
#pragma unroll
                for (int i = 0; i < EPF; i++)
                    asm volatile("cp.async.bulk.prefetch.tensor.2d.L2.global [%0, {%1, %2}];" ::"l"(&tmq), "r"((b >> 2) * 128 + i * 64), "r"((b & 3) * 256) : "memory");
            }
        }
        __syncwarp();
        g_arrive(xlo + XO_TK + 12, xhi, 4 * gridDim.x);
    }
    if (rk == 0 && w < 2) {
        if (l16 == 0) sts32(sb + SM_ROLE + 8 + w * 4, probe(xlo + XO_PB + w * 4096 + blockIdx.x * 16, xhi));
        bsync<2, 64>();
    }
    asm volatile("barrier.cluster.wait.aligned;" ::: "memory");
    if (rk == 0 && threadIdx.x == 0) {
        uint32_t side = (lds32(sb + SM_ROLE + 8) < lds32(sb + SM_ROLE + 12) ? 0u : 1u) ^ par(XO_PB);
        uint32_t* tk = (uint32_t*)(((uint64_t)xhi << 32) | (xlo + XO_TK));
        uint32_t t = atomicAdd(tk + side, 1u);
        if (t >= 32) {
            uint2 c;
            int it = 0;
            do {
                c = ldg2<XO_TK>(xlo, xhi);
                if (++it > SPIN_LIMIT) die(it);
            } while (c.x + c.y != gridDim.x / 2);
            t += (side ? c.x : c.y) - 32;
            side ^= 1;
            if (t >= 32) tickets_done(tk);
        }
#pragma unroll
        for (uint32_t r = 0; r < 2; r++)
            asm volatile("st.async.weak.shared::cluster.mbarrier::complete_tx::bytes.b32 [%0], %1, [%2];"
                         ::"r"(sb + SM_ROLE + (r << 24)), "r"(t * 4 + side * 2 + r), "r"(bq + BAR_RO + (r << 24)) : "memory");
    }
    __syncwarp();
    mbar_wait(bq + BAR_RO, 0);
    const uint32_t role = __reduce_max_sync(0xFFFFFFFFu, lds32(sb + SM_ROLE));
    if (role >= 128) return;
    const uint32_t h = role >> 2, j = role & 3;

    if (w >= 8) {
        asm volatile("setmaxnreg.dec.sync.aligned.u32 24;");
        const uint32_t u = w - 8;
        if (u == 0 && elect()) {
            mbar_expect(bq, 49152 + 65536);
#pragma unroll 1
            for (uint32_t i = 0; i < 12; i++) tma3d(sb + SM_WO + i * 4096, &tmx, bq, 0, i < 8 ? i * 8 : (j ^ ((0xBD98u >> (i - 8) * 4) & 15)) * 8, j * 4);
            tma2d(sb + SM_STB, &tmq, bq, h * 128, j * 256);
            tma2d(sb + SM_STB + 32768, &tmq, bq, h * 128 + 64, j * 256);
            mbar_expect(bk, 65536);
            tma2d(sb + SM_STA, &tmk, bk, h * 128, j * 256);
            tma2d(sb + SM_STA + 32768, &tmk, bk, h * 128 + 64, j * 256);
            mbar_expect(bo, 4 * WO_BOX);
#define WOREQ(g) { if ((g) == 0) tma2d(sb + SM_WO + 3 * WO_BOX, &tmo, bo, j * 256 + 192, h * 128); \
                   else asm volatile("cp.async.bulk.prefetch.tensor.2d.L2.global [%0, {%1, %2}];" ::"l"(&tmo), "r"(j * 256 + (g) * 64 - 64), "r"(h * 128) : "memory"); }
#pragma unroll
            for (int g = 0; g < OPF; g++) WOREQ(g);
        }
        if (u == 1) g_wait(xlo + XO_TK + 12, xhi);
        GSYNC(0);
        barv<5, 384>();
        bsync<9, 384>();
        if (u == 0 && elect()) {
            mbar_expect(bv, 65536);
#pragma unroll 1
            for (int i = 0; i < 8; i++) {
                const int ks = (i >> 1) * 4, g = i & 1;
                tma2d((ks < NA ? sb + SM_STB + g * (NA * 2048) + ks * 2048 : sb + SM_WV + g * WV_BOX + (ks - NA) * 2048), &tmv, bv, h * 128 + g * 64, j * 256 + ks * 16);
            }
#pragma unroll
            for (int g = OPF; g < OPF + OPG; g++) WOREQ(g);
        }
        bsync<9, 384>();
        xload(sb, u, j, -1, &tmx);
#pragma unroll 1
        for (int e = 0; e < 4; e++) sts128(sb + SM_TR + 4096 + e * 2048 + u * 512 + l16, 0, 0, 0, 0);
        if (u == 0) {
            bsync<3, 384>();
            g_arrive(xlo + XO_FL + h * 128, xhi, 4);
            g_wait(xlo + XO_FL + h * 128, xhi);
            asm volatile("fence.proxy.async.shared::cta;" ::: "memory");
#pragma unroll 1
            for (int i = 0; i < 4; i++)
                if (elect()) kvload(sb, i, h, j, 0, xlo, xhi);
        } else {
            barv<3, 384>();
            if (u >= OPF + OPG) {
                mbar_wait(bv, 0);
                delay_until(clk(), (u - OPF - OPG) * DLY_O);
                if (elect()) WOREQ(u);
            }
            bsync<8, 352>();
            if (elect()) tma2d(sb + SM_WO + (u - 1) * WO_BOX, &tmo, bo, j * 256 + (u - 1) * 64, h * 128);
            if (u == 1) asm volatile("fence.acq_rel.gpu;" ::: "memory");
            if (u == 2) xload(sb, 0, j, 0, &tmx);
            xload(sb, u, j, 0, &tmx);
        }
        mbar_wait(bq + BAR_KV, 0);
        if (threadIdx.x == 256) PG(14);
        mbar_wait(bo, 0);
        if (threadIdx.x == 256) PG(15);
#pragma unroll 1
        for (int s = 0; s < nseg; s++) helper_step(sb, w, h, j, l16, xlo, xhi, zero, s, &tmx, &tmb);
        piwait(sb, 0, nseg - 2);
        bsync<9, 384>();
        GSYNC(1);
        if (w < 10) {
            uint32_t kb = 2;
            asm volatile("fence.proxy.async.shared::cta;" ::: "memory");
            if (w == 9) {
                g_arrive(xlo + XO_TK + 192, xhi, 128);
                PG(2);
                if (h >= 30) { g_wait(xlo + XO_TK + 192, xhi); kb = 0; }
                PG(3);
            } else delay_until(clk(), GD);
#pragma unroll 1
            for (; kb < 32; kb++) {
                if (kb >= 4) mbar_wait(bq + BAR_GE + (kb & 3) * 8, ((kb >> 2) & 1) ^ 1);
                g_load(sb, w - 8, role, kb, xlo, xhi, &tmb);
            }
        }
        if (role == 0 && w == 11 && elect()) tickets_done((uint32_t*)(((uint64_t)xhi << 32) | (xlo + XO_TK)));
    } else {
        asm volatile("setmaxnreg.inc.sync.aligned.u32 240;");
        uint32_t Wq[16][4], Wk[16][4], Wv[NA][4];
        uint32_t t16, KA, KB, KC, KD;
        {
            const uint32_t lane = l16 >> 4, g = lane >> 2, t = lane & 3;
            const uint32_t rw = (((lane >> 4) & 1) * 8 + (lane & 7)) * 128u;
            const uint32_t off = rw + ((((w & 3) * 2 + ((lane >> 3) & 1)) ^ (lane & 7)) << 4);
            const uint32_t offo = rw + ((((w & 1) * 4 + ((lane >> 3) & 1)) ^ (lane & 7)) << 4);
            const uint32_t r = 2 * (t & 1) + (g >> 2);
            const uint32_t mk0 = t < 2 ? 0 : (r == 0 ? 2 * g > w : j + r < 4), mk1 = t < 2 ? 0 : (r == 0 ? 2 * g + 1 > w : j + r < 4);
            t16 = __shfl_sync(0xFFFFFFFFu, w * 512 + l16, lane);
            KA = __shfl_sync(0xFFFFFFFFu, (w * 512 + t * 64 + g * 8) | ((w * 512 + (g & 1) * 256 + (g >> 1) * 64 + t * 16) << 16), lane);
            KB = __shfl_sync(0xFFFFFFFFu, ((w >> 2) * WV_BOX + off) | mk0 | (mk1 << 1) |
                                              ((w * 256 + (g >> 2) * 4096 + (g & 3) * 64 + t * 16) << 16), lane);
            KC = __shfl_sync(0xFFFFFFFFu, ((lane & 7) * 1280 + (lane >> 3) * 128 + ((w ^ (lane & 7)) << 4)) | (((t >> 1) * 16 + g * 2) << 16) | ((t * 64 + g * 8) << 24), lane);
            KD = __shfl_sync(0xFFFFFFFFu, ((w >> 1) * WO_BOX + offo) | (((lane & 7) * 208 + (lane >> 3) * 16) << 16), lane);
            if (threadIdx.x == 0) PG(8);
            mbar_wait(bq, 0);
            if (threadIdx.x == 0) PG(9);
#pragma unroll
            for (int ks = 0; ks < 16; ks++) ldsm4t(Wq[ks], sb + SM_STB + (w >> 2) * 32768 + off + ks * 2048);
            xstart<0>(sb, w, xlo + h * 24576, xhi, j, t16, KA, Wq);
            if (threadIdx.x == 0) PG(10);
            mbar_wait(bk, 0);
            if (threadIdx.x == 0) PG(11);
#pragma unroll
            for (int ks = 0; ks < 16; ks++) ldsm4t(Wk[ks], sb + SM_STA + (w >> 2) * 32768 + off + ks * 2048);
            xstart<1>(sb, w, xlo + h * 24576, xhi, j, t16, KA, Wk);
            if (threadIdx.x == 0) PG(12);
            mbar_wait(bv, 0);
            if (threadIdx.x == 0) PG(13);
#pragma unroll
            for (int ks = 0; ks < NA; ks++) ldsm4t(Wv[ks], sb + (KB & 0x7F0) + SM_STB + (w >> 2) * (NA * 2048) + ks * 2048);
            xstart<2>(sb, w, xlo + h * 24576, xhi, j, t16, KA, Wv);
            mbar_wait(bq + BAR_XA, 0);
            barv<8, 352>();
        }
        const uint32_t ONES = 0x3F803F80u;
#define UNI(x) __reduce_max_sync(0xFFFFFFFFu, x)
        uint32_t swi = UNI((uint32_t)((uint64_t)smem >> 32));
        const uint32_t sbw = UNI(sb + w * 256), sbm = UNI(sb - w * 512), sbs = UNI(sb + w * 768), sbp = UNI(sb + w * 208);
#define OPQALL() { OPQ(t16); OPQ(KA); OPQ(KB); OPQ(KC); OPQ(KD); }
        OPQALL();
        const uint32_t cb0 = (h >> 1) * 32768 + (j & 1) * 16384 + (h & 1) * 8192;
        const uint32_t cb = xlo + cb0 + ((par(cb0) ^ (j >> 1) ^ CFAR) << 12);
        const uint32_t uox = xlo + XO_OX + (h * 2 + (w >> 2)) * 16384 + j * 1024 + (w & 3) * 256 - w * 128;
        float ox[4];
        float4 dn;
#define OXSTORE(s) asm volatile("{\n.reg .b64 a;\nmov.b64 a, {%0,%1};\nst.global.u32 [a], %2;\nst.global.u32 [a+128], %3;\n}" \
                                ::"r"(uox + (t16 >> 2) + ((s) >> 2) * (1u << 20) + ((s) & 3) * 4096), "r"(xhi), \
                                  "r"(pack2(ox[0] * dn.y, ox[1] * dn.w)), "r"(pack2(ox[2] * dn.y, ox[3] * dn.w)) : "memory")
#pragma unroll 1
        for (int s2 = 0;; s2 += 2)
#pragma unroll
        for (int p = 0; p < 2; p++) {
            const int s = s2 + p;
            const uint32_t ctag = ((s2 >> 1) & 1) ^ 1;
            const uint32_t hb = cb ^ (p * 0x81000), rb = xlo + rpage(j, s);
            uint4 k0, k1;
            uint32_t qx0, qx1, ov0, ov1;
            {
                float xa[16], xb[16];
                uint4 m0, n0;
                uint32_t e0, f0, a = xlo + rpage(j, s - 1) + t16;
                uint32_t xp[8];
                wg_fence();
                XMMA(0, 6);
                SF();
                piwait(sb, p, s - 2);
                uint4 pi = xpeer<0>(sb, p ^ 1, t16);
                SF();
                wg_fence();
                XMMA(6, RPOS);
                XMMA(RPOS, RPOS + 4);
                wg_wait<1>();
                SF();
                PT(11);
                RLOAD(a);
                SF();
#define QPOS (RPOS >= 32 - NA ? RPOS : RPOS + 4 >= 32 - NA ? RPOS + 4 : 32 - NA)
                if (QPOS > RPOS) {
                    wg_fence();
                    if (QPOS > RPOS + 4) XMMA(RPOS + 4, QPOS);
                    XMMA(QPOS, QPOS + 4);
                    wg_wait<1>();
                    SF();
                }
                xpack<0>(xp, xa);
                xpark<0>(xp, pi, sb, sbw, p ^ 1, t16, KA);
                pi = xpeer<2>(sb, p ^ 1, t16);
                SF();
                if (QPOS + 4 < 32) {
                    wg_fence();
                    XMMA(QPOS + 4, 32);
                    SF();
                }
                wg_wait<0>();
                xpack<2>(xp, xb);
                xpark<2>(xp, pi, sb, sbw, p ^ 1, t16, KA);
                SF();
                PT(12);
                {
                    int it = 0;
                    while (ruse(sb + SM_MEMT + t16, m0, n0, e0, f0)) {
                        OPQ(a);
                        RLOAD(a);
                        if (++it > SPIN_LIMIT) die(it);
                    }
                    PC(22, it + 1);
                }
                PT(13);
                OPQ(KA); OPQ(t16);
                uint32_t acw = hb + (KA & 0xFFFF), ahi = xhi, tg = ctag;
                OPQ(acw); OPQ(ahi); OPQ(tg);
                SF();
                bsync<1, 384>();
                PT(0);
                uint32_t b[8][4];
#pragma unroll
                for (int i = 0; i < 8; i++) {
                    const int pp = i < 2 ? i : i ^ 1;
                    ldsm4t(b[pp], sbm + SM_MEMT + t16 + pp * 512);
                    if (i < 7) MF();
                }
                if (ASF) SF();
                float q[4], k[4];
                const uint32_t aWv = sb + SM_WV + (KB & 0xFFF0);
                uint32_t wv[16 - NA > 0 ? 16 - NA : 1][4];
#define WVLD(n0, n1) _Pragma("unroll") for (int n = (n0); n < (n1) && n < 16 - NA; n++) ldsm4t(wv[n], aWv + n * 2048)
#pragma unroll
                for (int ks = 0; ks < 16; ks++) {
                    const uint32_t b0 = b[ks >> 1][(ks & 1) * 2], b1 = b[ks >> 1][(ks & 1) * 2 + 1];
                    if (ks == 0) {
                        mma16z(q, Wq[0][0], Wq[0][1], Wq[0][2], Wq[0][3], b0, b1);
                        mma16z(k, Wk[0][0], Wk[0][1], Wk[0][2], Wk[0][3], b0, b1);
                    } else {
                        mma16(q, Wq[ks][0], Wq[ks][1], Wq[ks][2], Wq[ks][3], b0, b1);
                        mma16(k, Wk[ks][0], Wk[ks][1], Wk[ks][2], Wk[ks][3], b0, b1);
                    }
                    if (ks == 10 && VPF) { SF(); WVLD(0, VPF); }
                }
                const uint32_t oq0 = settag(pack2(q[0], q[2]), tg), oq1 = settag(pack2(q[1], q[3]), tg);
                const uint32_t ok0 = pack2(k[0], k[2]), ok1 = pack2(k[1], k[3]);
                stg2<XO_CQK>(acw, ahi, oq0, ok0);
                stg2<XO_CQK + 256>(acw, ahi, oq1, ok1);
                SF();
                PT(1);
                int nl = VPF;
#pragma unroll
                for (int rd = 0; rd < 8; rd++) {
                    const int pp = (VORD >> (28 - 4 * rd)) & 7;
                    const uint32_t* a = 2 * pp < NA ? Wv[2 * pp < NA ? 2 * pp : 0] : wv[2 * pp < NA ? 0 : 2 * pp - NA];
                    const uint32_t* c = 2 * pp < NA ? Wv[2 * pp < NA ? 2 * pp + 1 : 0] : wv[2 * pp < NA ? 0 : 2 * pp + 1 - NA];
                    if (rd == 0) {
                        mma16z(q, a[0], a[1], a[2], a[3], b[pp][0], b[pp][1]);
                        mma16z(k, c[0], c[1], c[2], c[3], b[pp][2], b[pp][3]);
                    } else {
                        mma16(q, a[0], a[1], a[2], a[3], b[pp][0], b[pp][1]);
                        mma16(k, c[0], c[1], c[2], c[3], b[pp][2], b[pp][3]);
                    }
                    if (rd == 0) {
                        SF();
                        OPQ(swi);
                        asm volatile("{\n.reg .b64 a;\nmov.b64 a, {%0,%1};\nst.v2.u32 [a], {%2,%3};\nst.v2.u32 [a+256], {%4,%5};\n}"
                                     ::"r"((KA & 0xFFF) + (sb ^ 0x1000000) + SM_TR + 4096 + p * 4096), "r"(swi), "r"(oq0), "r"(ok0), "r"(oq1), "r"(ok1) : "memory");
                        sts64(sb + SM_TR + (KA & 0xFFF), oq0, ok0);
                        sts64(sb + SM_TR + (KA & 0xFFF) + 256, oq1, ok1);
                    }
                    if (rd == 4) KEEP(t16, oq0, oq1, ok0, ok1);
                    if (nl < 16 - NA) {
                        SF();
                        WVLD(nl, nl + (2 * pp < NA ? 1 : 3));
                        nl += 2 * pp < NA ? 1 : 3;
                    } else if (nl < 32) {
                        SF();
                        k0 = lds128(sb + SM_KV + 2048 + (KB >> 16));
                        nl = 32;
                    } else if (nl == 32) {
                        SF();
                        k1 = lds128(sb + SM_KV + 10240 + (KB >> 16));
                        const uint4 qq = lds128(sbw + SM_KV + ((KA >> 16) & 0xFF));
                        qx0 = (t16 & 64) ? qq.y : qq.x;
                        qx1 = (t16 & 64) ? qq.w : qq.z;
                        nl = 33;
                    }
                }
                ov0 = pack2(q[0] + k[0], q[1] + k[1]);
                ov1 = pack2(q[2] + k[2], q[3] + k[3]);
                stg2<XO_CV>(xlo + ((p * 32 + h) * 4 + j) * 2048 + (t16 >> 1), xhi, settag(ov0, tg), ov1);
                barv<8, 384>();
            }
            OPQ(t16);
            SF();
            PT(2);
            PDUMP();
            {
                const uint32_t a0 = sb + SM_KV;
#define CLOADG() { c2 = ldg4<XO_CQK>((hb ^ 0x1000) + (KA >> 16), xhi); c3 = ldg4<XO_CQK>((hb ^ 0x5000) + (KA >> 16), xhi); }
#define CLOADS() { c0 = lds128(sb + SM_TR + (KA >> 16)); c1 = lds128(sb + SM_TR + 4096 + p * 4096 + (KA >> 16)); }
                uint4 c0, c1, c2, c3, pi;
                float xa[16], xb[16];
                uint32_t xp[8];
                wg_fence();
                XMMA(32, 32 + CPOS);
                XMMA(32 + CPOS, 36 + CPOS);
                wg_wait<1>();
                SF();
                CLOADG();
                SF();
                CLOADS();
                if (KPOS == 0) pi = xpeer<1>(sb, p ^ 1, t16);
                SF();
                wg_fence();
                XMMA(36 + CPOS, 48);
                SF();
                const uint32_t ka[4] = {k0.x, k0.y, k0.z, k0.w}, kb[4] = {k1.x, k1.y, k1.z, k1.w};
                const uint32_t aSp = sb + SM_SP + (KC & 0xFFFF);
                PT(3);
#define SCORES(FIRST) { \
                    const uint32_t qA = hadd2(hadd2(c0.x, c1.x), hadd2(c2.x, c3.x)), qB = hadd2(hadd2(c0.z, c1.z), hadd2(c2.z, c3.z)); \
                    const uint32_t kA = hadd2(hadd2(c0.y, c1.y), hadd2(c2.y, c3.y)), kB = hadd2(hadd2(c0.w, c1.w), hadd2(c2.w, c3.w)); \
                    bad = any_bad(or3(tagx2(c1.x, c1.z, ctag), tagx2(c2.x, c2.z, ctag), tagx2(c3.x, c3.z, ctag))); \
                    float sa[4], sb_[4], sc[4], sd[4], se[4]; \
                    if (FIRST) { SF(); wg_wait<0>(); } \
                    mma16z(sa, ka[0], ka[1], ka[2], ka[3], qA, qB); \
                    mma16z(sb_, kb[0], kb[1], kb[2], kb[3], qA, qB); \
                    mma16z(sc, qA, qx0, qB, qx1, kA, kB); \
                    if (FIRST) { \
                        xpack<1>(xp, xa); \
                        if (KPOS == 0) { xadd(xp, pi); xstore<1>(xp, sb, sbw, p ^ 1, t16, KA); barv<3, 384>(); } \
                        mma16z(sd, ka[0], ka[1], ka[2], ka[3], qx0, qx1); \
                        mma16z(se, kb[0], kb[1], kb[2], kb[3], qx0, qx1); \
                    } \
                    stsm4t(aSp, pack2(sa[0], sa[1]), pack2(sa[2], sa[3]), pack2(sb_[0], sb_[1]), pack2(sb_[2], sb_[3])); \
                    stsm2(aSp + 1024, pack2(sc[0], sc[1]), pack2(sc[2], sc[3])); \
                    if (FIRST) { \
                        stsm4t(aSp + 512, pack2(sd[0], sd[1]), pack2(sd[2], sd[3]), pack2(se[0], se[1]), pack2(se[2], se[3])); \
                        if (KPOS == 0) { KEEP(KD, xp[0], xp[1], xp[2], xp[3]); KEEP(KD, xp[4], xp[5], xp[6], xp[7]); } \
                    } }
                int it = 0;
                bool bad;
                SCORES(true);
                while (__builtin_expect(bad, 0)) {
                    OPQ(KA);
                    CLOADG();
                    CLOADS();
                    SCORES(false);
                    if (++it > SPIN_LIMIT) die(it);
                }
                PC(25, it);
                PT(4);
                bsync<4, 256>();
                uint32_t wo[16][4];
                const uint32_t aWo = sb + SM_WO + (KD & 0xFFFF), aWo1 = sb + SM_WO + ((KD & 0xFFFF) ^ 32);
#define WOLD(n0, n1) _Pragma("unroll") for (int n = (n0); n < (n1) && n < 16; n++) ldsm4t(wo[n], ((n & 1) ? aWo1 : aWo) + (n >> 1) * 2048)
                const bool hi = (t16 & 32) != 0;
                const uint32_t t8 = t16 >> 1;
                uint2 v0, v1, v2, v3;
                uint32_t es;
                {
                    uint32_t am[4], ax[4], a4[2];
                    const uint32_t aSr = sbs + SM_SP + t16;
                    ldsm4t(am, aSr);
                    ldsm4t(ax, aSr + 512);
                    ldsm2t(a4, aSr + 1024);
                    MF();
                    if (KPOS == 1) pi = xpeer<1>(sb, p ^ 1, t16);
                    const uint32_t se = (t16 & 128) ? 0u : ONES, so = se ^ ONES;
                    float hm[4], hx[4], h4[4];
                    mma16z(hm, am[0], am[1], am[2], am[3], se, so);
                    mma16z(hx, ax[0], ax[1], ax[2], ax[3], se, so);
                    mma8z(h4, a4[0], a4[1], ONES);
                    SF();
                    if (KPOS == 1) { xpark<1>(xp, pi, sb, sbw, p ^ 1, t16, KA); barv<3, 384>(); }
                    v0 = lds64(a0 + 4096 + t8); v1 = lds64(a0 + 8192 + t8); v2 = lds64(a0 + 12288 + t8); v3 = lds64(a0 + 16384 + t8);
                    WOLD(0, PF2);
                    float s0 = hi ? hx[0] : hm[0], s1 = hi ? hx[2] : hm[2];
                    const float s2 = hi ? h4[2] : h4[0];
                    s0 = (KB & 1) ? -1.0e9f * 11.313708499f : s0;
                    s1 = (KB & 2) ? -1.0e9f * 11.313708499f : s1;
                    int mi = __float_as_int(fmaxf(fmaxf(s0, s2), s1));
                    mi ^= (mi >> 31) & 0x7FFFFFFF;
                    const int mm = __reduce_max_sync(0xFFFFFFFFu, hi ? (int)0x80000000 : mi), mx = __reduce_max_sync(0xFFFFFFFFu, hi ? mi : (int)0x80000000);
                    SF();
                    WOLD(PF2, PF3);
                    SF();
                    mi = hi ? mx : mm;
                    mi ^= (mi >> 31) & 0x7FFFFFFF;
                    const float c2_ = 0.08838834764831845f * 1.4426950408889634f;
                    const float mc = __int_as_float(mi) * c2_;
                    const float e0 = ex2(fmaf(s0, c2_, -mc)), e1 = ex2(fmaf(s1, c2_, -mc)), e2 = ex2(fmaf(s2, c2_, -mc));
                    sts32(sbp + SM_P + (KC >> 25), pack2(e0, e1));
                    sts16(sbp + SM_P + 128 + ((KC >> 16) & 0xFF), pack2(e2, e2));
                    es = __float_as_uint(fmaf(e2, 0.5f, e0 + e1) + 64.f);
                }
                const uint32_t sm = __reduce_add_sync(0xFFFFFFFFu, hi ? 0u : es), sx = __reduce_add_sync(0xFFFFFFFFu, hi ? es : 0u);
                const uint32_t aPr = sb + SM_P + (KD >> 16);
                PT(5);
                bsync<5, 384>();
                uint32_t pm[4], px[4], p4[2];
                ldsm4(pm, aPr);
                MF();
                const uint2 vs = lds64(sb + SM_VS + t8);
                MF();
                ldsm2(p4, aPr + 128);
                MF();
                ldsm4(px, aPr + 64);
                MF();
                sts32f(sb + SM_DN + w * 8 + ((t16 >> 3) & 4), rcp(__uint_as_float((hi ? sx : sm) - 15u * 0x42800000u) - 64.f));
                MF();
                WOLD(PF3, NPF);
                const uint32_t vm0 = hadd2(ov0, vs.x), vm1 = hadd2(ov1, vs.y);
                float oa[4], ob[4];
                mma16z(oa, v0.x, v0.y, v1.x, v1.y, pm[0], pm[1]);
                mma16z(ob, v2.x, v2.y, v3.x, v3.y, pm[2], pm[3]);
                mma8(oa, vm0, vm1, p4[0]);
                stsm2(sbw + SM_OT + (t16 & 511), pack2(oa[0] + ob[0], oa[1] + ob[1]), pack2(oa[2] + ob[2], oa[3] + ob[3]));
                PT(6);
                SF();
                bsync<6, 256>();
                mma16z(ox, v0.x, v0.y, v1.x, v1.y, px[0], px[1]);
                uint32_t b[4][4];
#define OTLD(pp) ldsm4t(b[pp], sbm + SM_OT + t16 + (pp) * 512)
                OTLD(0);
                MF();
                OTLD(1);
                barv<7, 384>();
                mma16(ox, v2.x, v2.y, v3.x, v3.y, px[2], px[3]);
                mma8(ox, vm0, vm1, p4[1]);
                if (p == 1 && s + 1 == nseg) goto done;
                SF();
                uint32_t ar, ae, ahi = xhi;
                float r[2][4];
#pragma unroll
                for (int ks = 0; ks < 8; ks++) {
                    if (ks == 0) WOLD(NPF, NPF + WPF);
                    if (ks == OPOS) { OTLD(2); MF(); }
                    if (ks == OPOS + 2) { OTLD(3); MF(); }
                    if (ks > 0) WOLD(NPF + WPF + 2 * (ks - 1), NPF + WPF + 2 * ks);
                    if (ks == 5) {
                        OPQ(t16);
                        ar = rb + (h & 1) * 16384 + t16; ae = rb + (h & 1) * 1024 + (t16 >> 2);
                        OPQ(ar); OPQ(ahi); OPQ(ae);
                        dn = lds128f(sb + SM_DN + (t16 & 48));
                    }
#pragma unroll
                    for (int mt = 0; mt < 2; mt++) {
                        const int i = ks * 2 + mt;
                        const uint32_t* a = wo[i];
                        if (i < 2) mma16z(r[mt], a[0], a[1], a[2], a[3], b[ks >> 1][2 * (ks & 1)], b[ks >> 1][2 * (ks & 1) + 1]);
                        else mma16(r[mt], a[0], a[1], a[2], a[3], b[ks >> 1][2 * (ks & 1)], b[ks >> 1][2 * (ks & 1) + 1]);
                    }
                    if (NPF + WPF + 2 * ks < 16 || ks < 5) SF();
                }
                const float r0 = dn.x, r1 = dn.z;
                asm volatile("{\n.reg .b64 a;\nmov.b64 a, {%0,%2};\nred.relaxed.gpu.global.add.noftz.v4.bf16x2 [a], {%3,%4,%5,%6};\n"
                             "mov.b64 a, {%1,%2};\nred.relaxed.gpu.global.add.noftz.bf16x2 [a+32768], %7;\n}"
                             ::"r"(ar), "r"(ae), "r"(ahi), "r"(pack2(r[0][0] * r0, r[0][1] * r1)), "r"(pack2(r[0][2] * r0, r[0][3] * r1)),
                               "r"(pack2(r[1][0] * r0, r[1][1] * r1)), "r"(pack2(r[1][2] * r0, 1.f)), "r"(pack2(r[1][3] * r1, 1.f)) : "memory");
                barv<10, 384>();
            }
            SF();
            PT(10);
            OXSTORE(s);
            OPQALL();
        }
    done:
        dn = lds128f(sb + SM_DN + (t16 & 48));
        OXSTORE(nseg - 1);
        barv<9, 384>();
        g_main(sb, w, role, &tmy);
        if (threadIdx.x == 0) PG(0);
    }
}

template <int SC> DEVI void wg_rs128t(float (&d)[64], const uint32_t (&a)[4], uint64_t db) {
    if (SC) asm volatile("wgmma.mma_async.sync.aligned.m64n128k16.f32.bf16.bf16 "
        "{%0,%1,%2,%3,%4,%5,%6,%7,%8,%9,%10,%11,%12,%13,%14,%15,%16,%17,%18,%19,%20,%21,%22,%23,%24,%25,%26,%27,%28,%29,%30,%31,%32,%33,%34,%35,%36,%37,%38,%39,%40,%41,%42,%43,%44,%45,%46,%47,%48,%49,%50,%51,%52,%53,%54,%55,%56,%57,%58,%59,%60,%61,%62,%63}, "
        "{%64,%65,%66,%67}, %68, 1, 1, 1, 1;"
        : D4(+, 0), D4(+, 4), D4(+, 8), D4(+, 12), D4(+, 16), D4(+, 20), D4(+, 24), D4(+, 28), D4(+, 32), D4(+, 36), D4(+, 40), D4(+, 44), D4(+, 48), D4(+, 52), D4(+, 56), D4(+, 60) : "r"(a[0]), "r"(a[1]), "r"(a[2]), "r"(a[3]), "l"(db));
    else asm volatile("wgmma.mma_async.sync.aligned.m64n128k16.f32.bf16.bf16 "
        "{%0,%1,%2,%3,%4,%5,%6,%7,%8,%9,%10,%11,%12,%13,%14,%15,%16,%17,%18,%19,%20,%21,%22,%23,%24,%25,%26,%27,%28,%29,%30,%31,%32,%33,%34,%35,%36,%37,%38,%39,%40,%41,%42,%43,%44,%45,%46,%47,%48,%49,%50,%51,%52,%53,%54,%55,%56,%57,%58,%59,%60,%61,%62,%63}, "
        "{%64,%65,%66,%67}, %68, 0, 1, 1, 1;"
        : D4(=, 0), D4(=, 4), D4(=, 8), D4(=, 12), D4(=, 16), D4(=, 20), D4(=, 24), D4(=, 28), D4(=, 32), D4(=, 36), D4(=, 40), D4(=, 44), D4(=, 48), D4(=, 52), D4(=, 56), D4(=, 60) : "r"(a[0]), "r"(a[1]), "r"(a[2]), "r"(a[3]), "l"(db));
}
template <int SC> DEVI void wg_rs64t(float (&d)[32], const uint32_t (&a)[4], uint64_t db) {
    if (SC) asm volatile("wgmma.mma_async.sync.aligned.m64n64k16.f32.bf16.bf16 "
        "{%0,%1,%2,%3,%4,%5,%6,%7,%8,%9,%10,%11,%12,%13,%14,%15,%16,%17,%18,%19,%20,%21,%22,%23,%24,%25,%26,%27,%28,%29,%30,%31}, "
        "{%32,%33,%34,%35}, %36, 1, 1, 1, 1;"
        : D4(+, 0), D4(+, 4), D4(+, 8), D4(+, 12), D4(+, 16), D4(+, 20), D4(+, 24), D4(+, 28) : "r"(a[0]), "r"(a[1]), "r"(a[2]), "r"(a[3]), "l"(db));
    else asm volatile("wgmma.mma_async.sync.aligned.m64n64k16.f32.bf16.bf16 "
        "{%0,%1,%2,%3,%4,%5,%6,%7,%8,%9,%10,%11,%12,%13,%14,%15,%16,%17,%18,%19,%20,%21,%22,%23,%24,%25,%26,%27,%28,%29,%30,%31}, "
        "{%32,%33,%34,%35}, %36, 0, 1, 1, 1;"
        : D4(=, 0), D4(=, 4), D4(=, 8), D4(=, 12), D4(=, 16), D4(=, 20), D4(=, 24), D4(=, 28) : "r"(a[0]), "r"(a[1]), "r"(a[2]), "r"(a[3]), "l"(db));
}
template <int SC> DEVI void wg_rs40(float (&d)[20], const uint32_t (&a)[4], uint64_t db) {
    if (SC) asm volatile("wgmma.mma_async.sync.aligned.m64n40k16.f32.bf16.bf16 "
        "{%0,%1,%2,%3,%4,%5,%6,%7,%8,%9,%10,%11,%12,%13,%14,%15,%16,%17,%18,%19}, "
        "{%20,%21,%22,%23}, %24, 1, 1, 1, 0;"
        : D4(+, 0), D4(+, 4), D4(+, 8), D4(+, 12), D4(+, 16) : "r"(a[0]), "r"(a[1]), "r"(a[2]), "r"(a[3]), "l"(db));
    else asm volatile("wgmma.mma_async.sync.aligned.m64n40k16.f32.bf16.bf16 "
        "{%0,%1,%2,%3,%4,%5,%6,%7,%8,%9,%10,%11,%12,%13,%14,%15,%16,%17,%18,%19}, "
        "{%20,%21,%22,%23}, %24, 0, 1, 1, 0;"
        : D4(=, 0), D4(=, 4), D4(=, 8), D4(=, 12), D4(=, 16) : "r"(a[0]), "r"(a[1]), "r"(a[2]), "r"(a[3]), "l"(db));
}
template <int SC> DEVI void wg_rs8(float (&d)[4], const uint32_t (&a)[4], uint64_t db) {
    if (SC) asm volatile("wgmma.mma_async.sync.aligned.m64n8k16.f32.bf16.bf16 "
        "{%0,%1,%2,%3}, "
        "{%4,%5,%6,%7}, %8, 1, 1, 1, 0;"
        : D4(+, 0) : "r"(a[0]), "r"(a[1]), "r"(a[2]), "r"(a[3]), "l"(db));
    else asm volatile("wgmma.mma_async.sync.aligned.m64n8k16.f32.bf16.bf16 "
        "{%0,%1,%2,%3}, "
        "{%4,%5,%6,%7}, %8, 0, 1, 1, 0;"
        : D4(=, 0) : "r"(a[0]), "r"(a[1]), "r"(a[2]), "r"(a[3]), "l"(db));
}
template <int SC> DEVI void wg_ss64a(float (&d)[32], uint64_t da, uint64_t db) {
    if (SC) asm volatile("wgmma.mma_async.sync.aligned.m64n64k16.f32.bf16.bf16 "
        "{%0,%1,%2,%3,%4,%5,%6,%7,%8,%9,%10,%11,%12,%13,%14,%15,%16,%17,%18,%19,%20,%21,%22,%23,%24,%25,%26,%27,%28,%29,%30,%31}, "
        "%32, %33, 1, 1, 1, 1, 0;"
        : D4(+, 0), D4(+, 4), D4(+, 8), D4(+, 12), D4(+, 16), D4(+, 20), D4(+, 24), D4(+, 28) : "l"(da), "l"(db));
    else asm volatile("wgmma.mma_async.sync.aligned.m64n64k16.f32.bf16.bf16 "
        "{%0,%1,%2,%3,%4,%5,%6,%7,%8,%9,%10,%11,%12,%13,%14,%15,%16,%17,%18,%19,%20,%21,%22,%23,%24,%25,%26,%27,%28,%29,%30,%31}, "
        "%32, %33, 0, 1, 1, 1, 0;"
        : D4(=, 0), D4(=, 4), D4(=, 8), D4(=, 12), D4(=, 16), D4(=, 20), D4(=, 24), D4(=, 28) : "l"(da), "l"(db));
}

#define G_ROWS 514
__device__ uint4 g_G[64 * G_ROWS * 8];
__device__ uint4 g_GN[64 * 8];
__device__ uint4 g_WN[1152];
#define FS_F2 196608
#define FS_TB (FS_F2 + 8192)
#define FS_NQ (FS_TB + 16384)
#define FS_BAR (FS_NQ + 128)
#define FS_NY (FS_NQ + 1024 + 128)
#define FS_TOTAL (FS_NQ + 3072)
#define F_THREADS 512

DEVI uint32_t cis(int j) {
    const float a = fmaf(__uint_as_float((((j + 1024) << 12) & 0x7FF000) | 0x3F800000), 6.283185307179586f, -9.42477796076938f);
    return pack2(__cosf(a), __sinf(a));
}
DEVI uint32_t cos2(int j0, int j1) {
    const float f = 6.283185307179586f / 2048.f;
    return pack2(__cosf((float)(((j0 + 1024) & 2047) - 1024) * f), __cosf((float)(((j1 + 1024) & 2047) - 1024) * f));
}
DEVI void twid(int j, float& c, float& s) {
    const float a = (float)(((j + 512) & 1023) - 512) * (6.283185307179586f / 1024.f);
    c = __cosf(a) * (1.f / 1024.f);
    s = __sinf(a) * (1.f / 1024.f);
}
template <bool B> struct Bool { static constexpr bool v = B; };
DEVI uint32_t opq(uint32_t& x, uint32_t zero) { OPQ(x); return x; }
DEVI uint32_t tidx() { uint32_t r; asm volatile("mov.u32 %0, %%tid.x;" : "=r"(r)); return r; }
DEVI void tma4d(uint32_t dst, const CUtensorMap* tm, uint32_t bar, int c0, int c1, int c2, int c3) {
    asm volatile("cp.async.bulk.tensor.4d.shared::cluster.global.mbarrier::complete_tx::bytes [%0], [%1, {%3, %4, %5, %6}], [%2];"
                 ::"r"(dst), "l"(tm), "r"(bar), "r"(c0), "r"(c1), "r"(c2), "r"(c3) : "memory");
}
DEVI void tma3s(const CUtensorMap* tm, uint32_t src, int c0, int c1, int c2) {
    asm volatile("cp.async.bulk.tensor.3d.global.shared::cta.bulk_group [%0, {%2, %3, %4}], [%1];" ::"l"(tm), "r"(src), "r"(c0), "r"(c1), "r"(c2) : "memory");
}
DEVI void tma4s(const CUtensorMap* tm, uint32_t src, int c0, int c1, int c2, int c3) {
    asm volatile("cp.async.bulk.tensor.4d.global.shared::cta.bulk_group [%0, {%2, %3, %4, %5}], [%1];"
                 ::"l"(tm), "r"(src), "r"(c0), "r"(c1), "r"(c2), "r"(c3) : "memory");
}
DEVI void bulk_commit() { asm volatile("cp.async.bulk.commit_group;" ::: "memory"); }
DEVI void fence_async() { asm volatile("fence.proxy.async;" ::: "memory"); }
DEVI void fence_smem() { asm volatile("fence.proxy.async.shared::cta;" ::: "memory"); }
DEVI void wgbar(uint32_t q) { asm volatile("bar.sync %0, 128;" ::"r"(q + 2) : "memory"); }
DEVI void grid_arrive(uint32_t* c, uint32_t n) { asm volatile("fence.proxy.async;\nred.release.gpu.global.inc.u32 [%0], %1;" ::"l"(c), "r"(n - 1) : "memory"); }
DEVI void grid_wait(uint32_t* c) {
    uint32_t v;
    int it = 0;
    do {
        asm volatile("ld.acquire.gpu.global.u32 %0, [%1];" : "=r"(v) : "l"(c) : "memory");
        if (++it > (1 << 22)) die(it);
    } while (v);
    fence_async();
}

template <bool INV, class S1, class S2>
DEVI void fft_rows(uint32_t grp, uint32_t q, const uint32_t (&F)[2][4], const float (&tc)[8], const float (&ts)[8], uint32_t so, float fx, uint32_t nq,
                   S1 sh1, S2 sh2) {
    float d[64];
    const uint64_t db = INV ? mkdesc(grp, 1024, 2048) : (mkdesc(grp, 2048, 512) ^ ((uint64_t)3 << 62));
    wg_fence();
    wg_rs128t<0>(d, F[0], db);
    wg_rs128t<1>(d, F[1], db + (INV ? 256 : 64));
    wg_commit();
    SF();
    sh1();
    float4 ny;
    if (INV) ny = lds128f(nq);
    wg_wait<0>();
    if (INV) { d[0] = fmaf(fx, ny.x, d[0]); d[16] = fmaf(fx, ny.y, d[16]); d[32] = fmaf(fx, ny.z, d[32]); d[48] = fmaf(fx, ny.w, d[48]); }
    uint32_t a[2][4][4];
    float e[2][INV ? 16 : 20];
    const uint64_t df = mkdesc(SB0 + FS_F2, 16, 1024);
#pragma unroll
    for (int s = 0; s < 2; s++) {
#pragma unroll
        for (int i = 0; i < 4; i++)
#pragma unroll
            for (int h = 0; h < 2; h++) {
                const float* x = d + (2 * s + h) * 16 + i * 4;
                a[s][i][h] = pack2(fmaf(x[2], ts[2 * i], x[0] * tc[2 * i]), fmaf(x[3], ts[2 * i + 1], x[1] * tc[2 * i + 1]));
                a[s][i][h + 2] = pack2(fmaf(-x[0], ts[2 * i], x[2] * tc[2 * i]), fmaf(-x[1], ts[2 * i + 1], x[3] * tc[2 * i + 1]));
            }
        wg_fence();
#pragma unroll
        for (int i = 0; i < 4; i++) {
            if constexpr (INV) { if (i == 0) wg_rs32<0>(e[s], a[s][i], df); else wg_rs32<1>(e[s], a[s][i], df + i * 2); }
            else { if (i == 0) wg_rs40<0>(e[s], a[s][i], df); else wg_rs40<1>(e[s], a[s][i], df + i * 2); }
        }
        wg_commit();
    }
    SF();
    sh2();
#pragma unroll
    for (int s = 0; s < 2; s++) {
        if (s == 0) wg_wait<1>(); else wg_wait<0>();
        float* x = e[s];
        if constexpr (!INV) {
            x[0] *= fx; x[1] *= fx; x[2] *= fx; x[3] *= fx;
            if (fx != 1.f) sts64(nq + s * 8, pack2(x[16], 0.f), pack2(x[18], 0.f));
        }
        const uint32_t o = grp + (INV ? so + s * 4096 : so ^ (s * 576));
#pragma unroll
        for (int b = 0; b < 2; b++)
            stsm4t(o + b * (INV ? 1024 : 4096), pack2(x[8 * b], x[8 * b + 1]), pack2(x[8 * b + 2], x[8 * b + 3]), pack2(x[8 * b + 4], x[8 * b + 5]),
                   pack2(x[8 * b + 6], x[8 * b + 7]));
    }
}

template <bool INV>
DEVI void fft_gen(uint32_t a, uint32_t n2) {
    const uint32_t tid = tidx(), x = ((tid >> 4) & 24) + (tid & 3), o = (tid & 4) * 128;
    if (INV) {
        const uint32_t r = (tid & 64) * 16 + (tid & 16) * 32 + (tid & 40) * 8 + n2;
        sts128(a + tid * 16, cis(o - r * x), cis(o - (r + 128) * x), cis(o - r * (x + 4)), cis(o - (r + 128) * (x + 4)));
    } else {
        const uint32_t r = 64 * x + n2, k = ((tid >> 2) & 24) + ((tid >> 3) & 3);
        sts128(a + tid * 16, cis(r * k + o), cis(r * (k + 4) + o), cis((r + 256) * k + o), cis((r + 256) * (k + 4) + o));
    }
}
template <bool INV, class S1>
DEVI void fft_cross(uint32_t buf, uint32_t q, uint32_t fa, uint32_t so, uint32_t nq, float (&n)[4], S1 sh1) {
    uint32_t F[4][4];
#pragma unroll
    for (int s = 0; s < 4; s++) { const uint4 v = lds128(fa + s * 2048); F[s][0] = v.x; F[s][1] = v.y; F[s][2] = v.z; F[s][3] = v.w; }
    float d[64];
    const uint64_t db = mkdesc(buf + q * 2048, 1024, 8192), dn = mkdesc(nq, 16, 1024);
    wg_fence();
#pragma unroll
    for (int s = 0; s < 4; s++) { if (s == 0) wg_rs128t<0>(d, F[s], db); else wg_rs128t<1>(d, F[s], db + s * 1024); }
#pragma unroll
    for (int s = 0; s < 4; s++) { if (s == 0) wg_rs8<0>(n, F[s], dn); else wg_rs8<1>(n, F[s], dn + s * 2); }
    wg_commit();
    SF();
    sh1();
    wg_wait<0>();
#pragma unroll
    for (int b = 0; b < 8; b++) {
        const uint32_t o = INV ? so ^ ((b >> 1) * 288 ^ (b & 1) * 32) : (so ^ ((b & 3) * 32)) + (b >> 2) * 1024;
        stsm4(buf + o, pack2(d[8 * b], d[8 * b + 1]), pack2(d[8 * b + 2], d[8 * b + 3]), pack2(d[8 * b + 4], d[8 * b + 5]), pack2(d[8 * b + 6], d[8 * b + 7]));
    }
}

template <bool ODD>
DEVI void fft_filter(uint32_t aw, const float (&e)[32], const float (&o)[32], uint32_t (&u)[4][4], uint32_t (&v)[4][4]) {
#pragma unroll
    for (int s = 0; s < 4; s++) {
        float y[2][2][4];
#pragma unroll
        for (int c = 0; c < 2; c++) {
            float f[4][2];
#pragma unroll
            for (int i = 0; i < 4; i++) {
                const uint32_t a = aw + (i * 32 + s * 8 + c) * 144, x = lds32(a);
                f[i][0] = ODD ? hi_f(x) : lo_f(x);
                f[i][1] = ODD ? lo_f(lds32(a + 4)) : hi_f(x);
            }
#pragma unroll
            for (int h = 0; h < 2; h++) {
                const int x = 8 * s + 2 * h + c;
                const float ar = e[x] + o[x], ai = e[x + 4] + o[x + 4], br = e[x] - o[x], bi = e[x + 4] - o[x + 4];
                const float yr = fmaf(-ai, f[2][h], ar * f[0][h]), yi = fmaf(ar, f[2][h], ai * f[0][h]);
                y[h][c][0] = fmaf(-bi, f[3][h], fmaf(br, f[1][h], yr));
                y[h][c][1] = fmaf(br, f[3][h], fmaf(bi, f[1][h], yi));
                y[h][c][2] = fmaf(2.f, yr, -y[h][c][0]);
                y[h][c][3] = fmaf(2.f, yi, -y[h][c][1]);
            }
        }
#pragma unroll
        for (int h = 0; h < 2; h++) {
            u[s][h] = pack2(y[h][0][0], y[h][1][0]); u[s][h + 2] = pack2(y[h][0][1], y[h][1][1]);
            v[s][h] = pack2(y[h][0][2], y[h][1][2]); v[s][h + 2] = pack2(y[h][0][3], y[h][1][3]);
        }
    }
}

__global__ void __launch_bounds__(F_THREADS, 1)
post_kernel(const __grid_constant__ CUtensorMap tmx, const __grid_constant__ CUtensorMap tmg1, const __grid_constant__ CUtensorMap tmg2,
           const __grid_constant__ CUtensorMap tmwr, const __grid_constant__ CUtensorMap tmwi, const __grid_constant__ CUtensorMap tmy,
           const bf16* __restrict__ wr, const bf16* __restrict__ wi, uint32_t* cnt, uint32_t zero, int nw) {
    extern __shared__ __align__(1024) uint8_t smem[];
    const uint32_t sb = SB0;
    if (smem_u32(smem) != sb) die(1 << 23);
    const uint32_t tid = threadIdx.x, lane = tid & 31, g = lane >> 2, t = lane & 3, j8 = lane & 7, mat = lane >> 3;
    const uint32_t wi_ = __reduce_max_sync(0xFFFFFFFFu, tid >> 5), q = wi_ >> 2, w = wi_ & 3;
    const int cta = blockIdx.x;
    const int nt = cta < 64 ? (64 - cta + nw - 1) / nw : 0;
    const uint32_t bar = sb + FS_BAR;
    if (tid == 0) {
        for (int i = 0; i < 30; i++) mbar_init(bar + i * 8, i < 3 ? 4 : i < 6 ? 16 : i >= 14 && i < 18 ? 2 : 1);
        asm volatile("fence.mbarrier_init.release.cluster;" ::: "memory");
        fence_smem();
    }
    __syncthreads();
#define FT(n)
    FT(0);
#define N2(p) (2 * ((p) & 31) + ((p) >> 5))
#define WLOAD(tk, part) { \
        const uint32_t wd_ = sb + 131072 + q * 18432 + (part) * 9216, wb_ = bar + 112 + q * 8; \
        mbar_expect(wb_, 9216); \
        if ((tk) < 256) tma3d(wd_, (part) ? &tmwi : &tmwr, wb_, ((tk) & 63) * 64, (tk) >> 6, 0); \
        else asm volatile("cp.async.bulk.shared::cluster.global.mbarrier::complete_tx::bytes [%0], [%1], 9216, [%2];" \
                          ::"r"(wd_), "l"(g_WN + (part) * 576), "r"(wb_) : "memory"); }
#define GROW(tk) ((tk) < 256 ? ((tk) >> 5) * 64 + ((tk) & 7) * 8 + (((tk) >> 3) & 3) * 2 : 512)
#define DLOAD(tk, sl) { mbar_expect(bar + 48 + (sl) * 8, 16384); tma3d(sb + (sl) * 16384, &tmg2, bar + 48 + (sl) * 8, 0, GROW(tk), 0); }
#define IO(c) if (w == 3 && (c) && elect())
#define XLOAD1(i, bb) { const uint32_t xb_ = bar + 144 + (bb) * 32 + q * 8; mbar_expect(xb_, 16384); tma4d(sb + (bb) * 65536 + q * 16384, &tmx, xb_, 0, 0, q * 8, N2(cta + (i) * nw)); }
#define GLOAD3(i, bb) { mbar_expect(bar + (bb) * 8, q ? 16384 : 16512); tma3d(sb + (bb) * 65536 + q * 16384, &tmg1, bar + (bb) * 8, 0, q * 128, cta + (i) * nw); \
        if (q == 0) asm volatile("cp.async.bulk.shared::cluster.global.mbarrier::complete_tx::bytes [%0], [%1], 128, [%2];" \
                                 ::"r"(sb + FS_NQ + (bb) * 1024), "l"(g_GN + (cta + (i) * nw) * 8), "r"(bar + (bb) * 8) : "memory"); }
    for (int i = 0; i < 3; i++) IO(i < nt) XLOAD1(i, i);
    for (uint32_t x = tid; x < 40 * 32; x += 512) {
        const uint32_t n = x >> 5, m2 = mat * 8 + t * 2, ri = g & 1;
        const uint32_t c2 = ((n >> 1) & 1) + ((n >> 3) & 1) * 2 + (n & 4) + (n >> 4) * 8;
        const uint32_t v = cos2(m2 * c2 * 64 + ((n & 1) - ri) * 512, (m2 + 1) * c2 * 64 + ((n & 1) - ri) * 512);
        sts32(sb + FS_F2 + n * 128 + ((g ^ (n & 7)) << 4) + t * 4, n < 32 ? v : n == 32 && ri == 0 ? 0xBF003F00u : 0u);
    }
    float tc[8], ts[8];
    uint32_t F[2][4];
    uint32_t c1 = 16 * (w >> 1) + 2 * g + (w & 1);
#pragma unroll
    for (int i = 0; i < 8; i++) {
        twid(c1 * (8 * (i >> 1) + 2 * t + (i & 1)), tc[i], ts[i]);
        const uint32_t m1 = (i >> 1) * 8 + 2 * t;
        F[i >> 2][i & 3] = cos2(c1 * m1 * 64 + (i & 1) * 512, c1 * (m1 + 1) * 64 + (i & 1) * 512);
    }
    {
        const uint32_t kr = (2 * (mat & 1) + (j8 & 1)) ^ ((j8 >> 2) << 1);
        const uint32_t so1 = ((mat >> 1) + 2 * (j8 >> 2)) * 1024 + kr * 128 + (((((j8 >> 1) & 1) * 4 + w) ^ kr) << 4);
        const uint32_t so2 = (2 * w + (mat & 1)) * 8192 + q * 2048 + j8 * 128 + (((mat >> 1) ^ j8) << 4);
        uint32_t so = so1 << 16 | so2;
        const float fx = (tid & 127) == 0 ? 0.5f : 1.f;
        fft_gen<false>(sb + FS_TB, N2(cta));
        fence_smem();
        bsync<1, 512>();
        FT(1);
        int b = 0, bp = 2, ph = 0;
        if (nt) mwait(bar + 144 + q * 8, 0);
        __syncwarp();
        auto step = [&](auto first, auto last, const int i) {
            const uint32_t p = cta + i * nw, bn = 3 - b - bp, tb = (i & 1) * 8192;
            const uint32_t grp = sb + b * 65536 + q * 16384, nq = sb + FS_NQ + b * 1024 + q * 32;
            auto sa = [&]() {
                if constexpr (!decltype(first)::v) {
                    fence_smem();
                    __syncwarp();
                    if (elect()) mbar_arrive(bar + 24);
                }
                IO(i > 1) {
                    mwait(bar + 32, i & 1);
                    tma3s(&tmg1, sb + bn * 65536 + q * 16384, 0, q * 128, p - 2 * nw);
                    bulk_commit();
                }
            };
            auto sb_ = [&]() { if constexpr (!decltype(first)::v) mwait(bar + 24, (i - 1) & 1); };
            if constexpr (!decltype(last)::v) fft_rows<false>(grp, q, F, tc, ts, opq(so, zero) >> 16, fx, nq, sa, sb_);
            else { sa(); __syncwarp(); sb_(); __syncwarp(); }
            if constexpr (!decltype(first)::v) {
                float n[4];
                fft_cross<false>(sb + bp * 65536, q, sb + FS_TB + 8192 - tb + (((tidx() & 127) ^ (q & 1)) << 4), opq(so, zero) & 0xFFFF, sb + FS_NQ + bp * 1024, n, [&]() {
                    fft_gen<false>(sb + FS_TB + tb, N2(p));
                    IO(i >= 2 && i + 1 < nt) {
                        asm volatile("cp.async.bulk.wait_group.read 0;" ::: "memory");
                        XLOAD1(i + 1, bn);
                    }
                });
                if (q == 0) {
                    const uint32_t x = tidx();
                    bf16* z = (bf16*)(g_G + ((p - nw) * G_ROWS + 512) * 8) + (x & 4) * 16 + ((x >> 2) & 24) + ((x >> 3) & 3);
                    asm volatile("{\n.reg .pred p;\n.reg .b16 a, b;\nsetp.eq.u32 p, %2, 0;\nmov.b32 {a, b}, %1;\n@p st.global.u16 [%0], a;\n@p st.global.u16 [%0+8], b;\n}"
                                 ::"l"(z), "r"(pack2(n[0], n[2])), "r"(x & 3) : "memory");
                }
            }
            if constexpr (!decltype(last)::v) {
                fft_rows<false>(grp + 8192, q, F, tc, ts, opq(so, zero) >> 16, fx, nq + 16, [&]() {
                    if constexpr (!decltype(first)::v) {
                        fence_smem();
                        __syncwarp();
                        if (elect()) mbar_arrive(bar + 32);
                    }
                    if ((w == 1 || w == 2) && elect())
                        asm volatile("cp.async.bulk.prefetch.L2.global [%0], 8208;" ::"l"((w == 1 ? wr : wi) + (p * 4 + q) * 4104) : "memory");
                }, [&]() { if (i + 1 < nt) mwait(bar + 144 + bn * 32 + q * 8, bn ? ph : ph ^ 1); });
                bp = b;
                if (++b == 3) { b = 0; ph ^= 1; }
            }
        };
        if (nt) {
            step(Bool<true>(), Bool<false>(), 0);
#pragma unroll 1
            for (int i = 1; i < nt; i++) step(Bool<false>(), Bool<false>(), i);
            step(Bool<false>(), Bool<true>(), nt);
        }
        for (uint32_t x = cta * 512 + tid; x < 4096; x += nw * 512)
            ((bf16*)g_WN)[(x >> 5) * 72 + (x & 16) + (x & 7) * 2 + ((x >> 3) & 1)] = (x < 2048 ? wr : wi)[(x & 2047) * 513 + 512];
        FT(2);
        fence_async();
        bsync<1, 512>();
        IO(nt) { tma3s(&tmg1, sb + bp * 65536 + q * 16384, 0, q * 128, cta + (nt - 1) * nw); bulk_commit(); }
    }
    for (uint32_t x = tid; x < 128 * 32; x += 512) {
        const uint32_t n = (x >> 5) & 63, a = x & 31, k2 = (n >> 4) * 8 + (n & 7);
        sts32(sb + FS_TB + (x >> 5) * 128 + (((a >> 2) ^ (n & 7)) << 4) + (a & 3) * 4, cis((2 * a + (x >> 11)) * k2 * 32 + (n & 8) * 64));
    }
    fence_smem();
    bsync<1, 512>();
    IO(true) {
        asm volatile("cp.async.bulk.wait_group 0;" ::: "memory");
        grid_arrive(cnt, 4 * nw);
        grid_wait(cnt);
        const int tk = cta + q * nw;
        if (tk <= 256) { DLOAD(tk, q); WLOAD(tk, 0); WLOAD(tk, 1); }
    }
    __syncwarp();
    {
        const uint32_t lo = j8 * 128 + (((2 * w + (mat & 1)) ^ j8) << 4);
        const uint32_t aw = sb + 131072 + q * 18432 + t * 288 + w * 32 + g * 4;
        const uint64_t df = mkdesc(sb + FS_TB, 16, 1024);
        const uint64_t da = mkdesc(sb + q * 16384, 16, 1024);
        const uint32_t buf = sb + 65536 + q * 16384;
        int i = 0, tk = cta + q * nw;
        if (tk <= 256) mwait(bar + 48 + q * 8, 0);
        FT(3);
#pragma unroll 1
        for (; tk <= 256; tk += 4 * nw, i++) {
            const bool more = tk + 4 * nw <= 256;
            float e[32], o[32];
            wg_fence();
#pragma unroll
            for (int s = 0; s < 4; s++) { if (s == 0) wg_ss64a<0>(e, da, df); else wg_ss64a<1>(e, da + s * 128, df + s * 2); }
#pragma unroll
            for (int s = 0; s < 4; s++) { if (s == 0) wg_ss64a<0>(o, da + 512, df + 512); else wg_ss64a<1>(o, da + 512 + s * 128, df + 512 + s * 2); }
            wg_commit();
            SF();
            if (i > 0) {
                fence_smem();
                wgbar(q);
                IO(true) { tma3s(&tmg2, buf, 0, GROW(tk - 4 * nw), 0); bulk_commit(); }
            }
            if (w == 2 && more && elect()) mbar_expect(bar + 48 + q * 8, 16384);
            const int gr = GROW(tk + 4 * nw);
            mwait(bar + 112 + q * 8, i & 1);
            wg_wait<0>();
            if (w == 2 && more && elect()) tma3d(sb + q * 16384, &tmg2, bar + 48 + q * 8, 0, gr, 0);
            uint32_t u[4][4], v[4][4];
            if (tk & 8) fft_filter<true>(aw + (tk & 48) / 4, e, o, u, v);
            else fft_filter<false>(aw + (tk & 48) / 4, e, o, u, v);
            wg_fence();
#pragma unroll
            for (int s = 0; s < 4; s++) { if (s == 0) wg_rs64t<0>(e, u[s], df); else wg_rs64t<1>(e, u[s], df + s * 128); }
#pragma unroll
            for (int s = 0; s < 4; s++) { if (s == 0) wg_rs64t<0>(o, v[s], df + 512); else wg_rs64t<1>(o, v[s], df + 512 + s * 128); }
            wg_commit();
            SF();
            IO(true) asm volatile("cp.async.bulk.wait_group.read 0;" ::: "memory");
            wgbar(q);
            if (more) {
                if ((w == 1 || w == 2) && elect()) WLOAD(tk + 4 * nw, w - 1);
                mwait(bar + 48 + q * 8, (i + 1) & 1);
            }
            wg_wait<0>();
#pragma unroll
            for (int s = 0; s < 4; s++) {
                const uint32_t a = buf + (mat >> 1) * 1024 + lo + s * 2048;
                stsm4t(a, pack2(e[8 * s], e[8 * s + 1]), pack2(e[8 * s + 2], e[8 * s + 3]), pack2(e[8 * s + 4], e[8 * s + 5]), pack2(e[8 * s + 6], e[8 * s + 7]));
                stsm4t(a + 8192, pack2(o[8 * s], o[8 * s + 1]), pack2(o[8 * s + 2], o[8 * s + 3]), pack2(o[8 * s + 4], o[8 * s + 5]), pack2(o[8 * s + 6], o[8 * s + 7]));
            }
            if (tk == 256 && w < 2) {
                uint32_t* z = (uint32_t*)g_GN + t * 32 + w * 16 + g;
#pragma unroll
                for (int s = 0; s < 16; s++) {
                    z[(s >> 1) * 128 + (s & 1) * 8] = pack2(e[2 * s], e[2 * s + 1]);
                    z[(s >> 1) * 128 + (s & 1) * 8 + 1024] = pack2(o[2 * s], o[2 * s + 1]);
                }
                fence_async();
            }
        }
        fence_smem();
        wgbar(q);
        IO(true) {
            if (i > 0) { tma3s(&tmg2, buf, 0, GROW(tk - 4 * nw), 0); bulk_commit(); }
            asm volatile("cp.async.bulk.wait_group 0;" ::: "memory");
            grid_arrive(cnt + 1, 4 * nw);
        }
    }
    FT(4);
    bsync<1, 512>();
    {
        for (uint32_t n = wi_; n < 32; n += 16) {
            const uint32_t cl = (mat >> 1) * 16 + t * 4 + (mat & 1), mh = ((n >> 3) & 1) + (n & 7) * 2 + (n & 16);
            sts32(sb + FS_F2 + n * 128 + ((g ^ (n & 7)) << 4) + t * 4, cos2(cl * mh * 64 + (g & 1) * 512, (cl + 2) * mh * 64 + (g & 1) * 512));
        }
        fence_smem();
        c1 = 8 * w + g;
#pragma unroll
        for (int i = 0; i < 8; i++) {
            twid(-c1 * (16 * (i >> 2) + 4 * t + 2 * (i & 1) + ((i >> 1) & 1)), tc[i], ts[i]);
            F[i >> 2][i & 3] = cis((i & 1) * 512 - c1 * ((i >> 1) * 4 + (t ^ (q & 1))) * 64);
        }
        const uint32_t kr = (j8 & 1) ^ ((j8 >> 2) << 1);
        const uint32_t so2 = ((w >> 1) * 4 + (j8 >> 2) * 2 + (w & 1)) * 8192 + (2 * q + (mat & 1)) * 1024 + kr * 128 + (((((j8 >> 1) & 1) * 4 + (mat >> 1)) ^ kr) << 4);
        const uint32_t so1 = (mat & 1) * 2048 + j8 * 128 + ((((mat >> 1) * 4 + w) ^ j8) << 4);
        uint32_t so = so1 << 16 | so2;
        const float fx = t ? 0.f : (g & 1) ? -1.f : 1.f;
        fft_gen<true>(sb + FS_TB, N2(cta));
        bsync<1, 512>();
        IO(true) grid_wait(cnt + 1);
        for (int i = 0; i < 3; i++) IO(i < nt) GLOAD3(i, i);
        __syncwarp();
        int b = 0, bp = 2, ph = 0;
        auto step = [&](auto first, auto last, const int i) {
            const uint32_t p = cta + i * nw, bn = 3 - b - bp, tb = (i & 1) * 8192;
            const uint32_t grp = sb + bp * 65536 + q * 16384, ny = sb + FS_NY + bp * 128 + q * 32;
            auto sb_ = [&]() { if constexpr (!decltype(last)::v) mwait(bar + b * 8, ph); };
            if constexpr (!decltype(first)::v) {
                fft_rows<true>(grp, q, F, tc, ts, opq(so, zero) >> 16, fx, ny, [&]() {
                    if (i > 1) {
                        fence_smem();
                        wgbar(q);
                        IO(true) { tma4s(&tmy, sb + bn * 65536 + q * 16384, 0, 0, q * 8, N2(p - 2 * nw)); bulk_commit(); }
                    }
                }, sb_);
            } else { sb_(); __syncwarp(); }
            if constexpr (decltype(first)::v) FT(5);
            if constexpr (!decltype(last)::v) {
                float n[4];
                fft_cross<true>(sb + b * 65536, q, sb + FS_TB + tb + (tidx() & 127) * 16, opq(so, zero) & 0xFFFF, sb + FS_NQ + b * 1024, n, [&]() {
                    fft_gen<true>(sb + FS_TB + 8192 - tb, N2(p + nw));
                    IO(i >= 2 && i + 1 < nt) {
                        asm volatile("cp.async.bulk.wait_group.read 0;" ::: "memory");
                        GLOAD3(i + 1, bn);
                    }
                });
                if (q == 0) {
                    const uint32_t x = tidx(), a = sb + FS_NY + b * 128 + (x & 64) + (x & 16) * 2 + ((x & 40) >> 1);
                    if ((x & 7) == 0) { sts32f(a, n[0]); sts32f(a + 8, n[2]); }
                }
            }
            auto sc = [&]() {
                if constexpr (!decltype(last)::v) {
                    fence_smem();
                    __syncwarp();
                    if (elect()) mbar_arrive(bar + 24);
                }
            };
            auto sd = [&]() { if constexpr (!decltype(last)::v) mwait(bar + 24, (nt + i) & 1); };
            if constexpr (!decltype(first)::v) fft_rows<true>(grp + 8192, q, F, tc, ts, opq(so, zero) >> 16, fx, ny + 16, sc, sd);
            else { sc(); __syncwarp(); sd(); __syncwarp(); }
            if constexpr (!decltype(last)::v) {
                bp = b;
                if (++b == 3) { b = 0; ph ^= 1; }
            }
        };
        if (nt) {
            step(Bool<true>(), Bool<false>(), 0);
#pragma unroll 1
            for (int i = 1; i < nt; i++) step(Bool<false>(), Bool<false>(), i);
            step(Bool<false>(), Bool<true>(), nt);
        }
        fence_smem();
        wgbar(q);
        IO(nt) { tma4s(&tmy, sb + bp * 65536 + q * 16384, 0, 0, q * 8, N2(cta + (nt - 1) * nw)); bulk_commit(); }
        FT(6);
        IO(true) asm volatile("cp.async.bulk.wait_group 0;" ::: "memory");
    }
}

typedef CUresult (*EncodeFn)(CUtensorMap*, CUtensorMapDataType, cuuint32_t, void*, const cuuint64_t*, const cuuint64_t*,
                             const cuuint32_t*, const cuuint32_t*, CUtensorMapInterleave, CUtensorMapSwizzle,
                             CUtensorMapL2promotion, CUtensorMapFloatOOBfill);

static void make_map(EncodeFn enc, CUtensorMap* m, const void* ptr, int rank, const cuuint64_t* dims, const cuuint64_t* strides,
                     const cuuint32_t* box, CUtensorMapSwizzle sw = CU_TENSOR_MAP_SWIZZLE_128B) {
    cuuint32_t es[4] = {1, 1, 1, 1};
    CUresult r = enc(m, CU_TENSOR_MAP_DATA_TYPE_BFLOAT16, rank, (void*)ptr, dims, strides, box, es, CU_TENSOR_MAP_INTERLEAVE_NONE,
                     sw, CU_TENSOR_MAP_L2_PROMOTION_L2_256B, CU_TENSOR_MAP_FLOAT_OOB_FILL_NONE);
    if (r != CUDA_SUCCESS) fprintf(stderr, "tensor map encode failed: %d\n", (int)r);
}

extern "C" void kernel_launch(void* const* d_in, const int* in_sizes, int n_in, void* d_out, int out_size) {
    const bf16* A_x = (const bf16*)d_in[0];
    const bf16* A_mem0 = (const bf16*)d_in[1];
    const bf16* A_Wq = (const bf16*)d_in[2];
    const bf16* A_Wk = (const bf16*)d_in[3];
    const bf16* A_Wv = (const bf16*)d_in[4];
    const bf16* A_Wo = (const bf16*)d_in[5];
    const bf16* B_x = (const bf16*)d_in[7];
    const bf16* B_wr = (const bf16*)d_in[8];
    const bf16* B_wi = (const bf16*)d_in[9];
    bf16* out = (bf16*)d_out;

    static EncodeFn enc = nullptr;
    static void *pxs = nullptr, *pg = nullptr;
    static int ncl = 64;
    if (!enc) {
        cudaDriverEntryPointQueryResult qr;
        void* fn = nullptr;
        cudaGetDriverEntryPoint("cuTensorMapEncodeTiled", &fn, cudaEnableDefault, &qr);
        enc = (EncodeFn)fn;
        cudaFuncSetAttribute(chain_kernel, cudaFuncAttributeMaxDynamicSharedMemorySize, SM_TOTAL);
        cudaFuncSetAttribute(post_kernel, cudaFuncAttributeMaxDynamicSharedMemorySize, FS_TOTAL);
        cudaGetSymbolAddress(&pxs, g_xs);
        cudaGetSymbolAddress(&pg, g_G);
        cudaLaunchConfig_t lc = {};
        cudaLaunchAttribute at;
        at.id = cudaLaunchAttributeClusterDimension;
        at.val.clusterDim.x = 2; at.val.clusterDim.y = 1; at.val.clusterDim.z = 1;
        lc.gridDim = dim3(132); lc.blockDim = dim3(384); lc.dynamicSmemBytes = SM_TOTAL; lc.attrs = &at; lc.numAttrs = 1;
        int nc = 0;
        if (cudaOccupancyMaxActiveClusters(&nc, chain_kernel, &lc) == cudaSuccess && nc > 64) ncl = nc < 66 ? nc : 66;
    }
    CUtensorMap tmq, tmk, tmv, tmo, tmx, tmb, tmy;
    {
        cuuint64_t d[2] = {HD, DM}, st[1] = {HD * 2};
        cuuint32_t bx[2] = {64, 256};
        make_map(enc, &tmq, A_Wq, 2, d, st, bx);
        make_map(enc, &tmk, A_Wk, 2, d, st, bx);
        cuuint32_t bx2[2] = {64, 64};
        make_map(enc, &tmv, A_Wv, 2, d, st, bx2);
    }
    {
        cuuint64_t d[2] = {DM, HD}, st[1] = {DM * 2};
        cuuint32_t bx[2] = {64, 16}, bx1[2] = {64, 128}, bx2[3] = {64, 64, 2};
        make_map(enc, &tmo, A_Wo, 2, d, st, bx1);
        cuuint64_t d2[3] = {64, HD, DM / 64}, st2[2] = {DM * 2, 128}, d3[2] = {DM, SEQ}, st3[1] = {DM * 4};
        make_map(enc, &tmb, A_Wo, 3, d2, st2, bx2);
        make_map(enc, &tmy, out, 2, d3, st3, bx);
    }
    {
        cuuint64_t d[3] = {64, SEQ, DM / 64}, st[2] = {DM * 2, 128};
        cuuint32_t bx[3] = {64, 8, 4};
        make_map(enc, &tmx, A_x, 3, d, st, bx);
    }
    CUtensorMap fx, fg1, fg2, fwr, fwi, fy;
    {
        cuuint64_t d[4] = {32, 32, 32, 64}, st[3] = {64, 64 * DM * 2, DM * 2};
        cuuint32_t bx[4] = {32, 32, 8, 1};
        make_map(enc, &fx, B_x, 4, d, st, bx, CU_TENSOR_MAP_SWIZZLE_64B);
        cuuint64_t d2[4] = {64, 16, 32, 64}, st2[3] = {128, 64 * 4096, 4096};
        cuuint32_t bx2[4] = {64, 16, 8, 1};
        make_map(enc, &fy, out + DM, 4, d2, st2, bx2);
    }
    {
        cuuint64_t d[3] = {64, G_ROWS, 64}, st[2] = {128, G_ROWS * 128};
        cuuint32_t bx[3] = {64, 128, 1}, bx2[3] = {64, 2, 64};
        make_map(enc, &fg1, pg, 3, d, st, bx);
        make_map(enc, &fg2, pg, 3, d, st, bx2);
        cuuint64_t d2[3] = {8 * 513, 4, 64}, st2[2] = {8 * 513 * 2, 32 * 513 * 2};
        cuuint32_t bx3[3] = {72, 1, 64};
        make_map(enc, &fwr, B_wr, 3, d2, st2, bx3, CU_TENSOR_MAP_SWIZZLE_NONE);
        make_map(enc, &fwi, B_wi, 3, d2, st2, bx3, CU_TENSOR_MAP_SWIZZLE_NONE);
    }
    cudaStream_t st = cudaStreamPerThread;
    const uint64_t xs = ((uint64_t)pxs + XS_BYTES - 1) & ~(uint64_t)(XS_BYTES - 1);
    chain_kernel<<<2 * ncl, 384, SM_TOTAL, st>>>(tmq, tmk, tmv, tmo, tmx, tmb, tmy, A_mem0, (uint32_t)xs, (uint32_t)(xs >> 32), 0u, NSEG);
    int nw = ncl == 66 ? 4 : 64;
    cudaLaunchConfig_t lc = {};
    cudaLaunchAttribute at;
    at.id = cudaLaunchAttributeProgrammaticStreamSerialization;
    at.val.programmaticStreamSerializationAllowed = 1;
    lc.gridDim = dim3(nw); lc.blockDim = dim3(F_THREADS); lc.dynamicSmemBytes = FS_TOTAL; lc.stream = st; lc.attrs = &at; lc.numAttrs = 1;
    cudaLaunchKernelEx(&lc, post_kernel, fx, fg1, fg2, fwr, fwi, fy, B_wr, B_wi, (uint32_t*)(xs + XO_TK + 256), 0u, nw);
}
```

```cpp
#include <cuda_runtime.h>
#include <cuda_bf16.h>
#include <cuda.h>
#include <stdint.h>
#include <stdio.h>

typedef __nv_bfloat16 bf16;

#define SEQ 2048
#define DM 1024
#define NH 32
#define DH 128
#define NSEG 64
#define HD (NH * DH)

#define XS_BYTES (32u << 20)
__device__ uint4 g_xs[2 * XS_BYTES / 16];
#define XO_R 0u
#define XO_PB (1u << 18)
#define XO_FL (XO_PB + 16384u)
#define XO_TK (XO_FL + 4096u)
#define XO_CQK (1u << 20)
#define XO_CV (2u << 20)
#define XO_XG (4u << 20)
#define XO_OX (16u << 20)
#define GSYNC(n)
#define PG(n)

#define DEVI __device__ __forceinline__

DEVI void die(int it) { asm volatile("st.shared.u32 [%0], %0;" ::"r"(it) : "memory"); }
DEVI uint32_t smem_u32(const void* p) { return (uint32_t)__cvta_generic_to_shared(p); }
DEVI void mbar_init(uint32_t bar, uint32_t cnt) { asm volatile("mbarrier.init.shared::cta.b64 [%0], %1;" ::"r"(bar), "r"(cnt) : "memory"); }
DEVI void mbar_expect(uint32_t bar, uint32_t bytes) { asm volatile("mbarrier.arrive.expect_tx.shared::cta.b64 _, [%0], %1;" ::"r"(bar), "r"(bytes) : "memory"); }
DEVI void mbar_arrive(uint32_t bar) { asm volatile("mbarrier.arrive.shared::cta.b64 _, [%0];" ::"r"(bar) : "memory"); }
DEVI void mbar_wait(uint32_t bar, uint32_t parity) {
    uint32_t done;
    int it = 0;
    do {
        asm volatile("{\n.reg .pred p;\nmbarrier.try_wait.parity.shared::cta.b64 p, [%1], %2;\nselp.u32 %0, 1, 0, p;\n}\n"
                     : "=r"(done) : "r"(bar), "r"(parity) : "memory");
        if (++it > (1 << 22)) die(it);
    } while (!done);
}
DEVI void tma2d(uint32_t dst, const CUtensorMap* tm, uint32_t bar, int c0, int c1) {
    asm volatile("cp.async.bulk.tensor.2d.shared::cluster.global.mbarrier::complete_tx::bytes [%0], [%1, {%3, %4}], [%2];"
                 ::"r"(dst), "l"(tm), "r"(bar), "r"(c0), "r"(c1) : "memory");
}
DEVI void tma3d(uint32_t dst, const CUtensorMap* tm, uint32_t bar, int c0, int c1, int c2) {
    asm volatile("cp.async.bulk.tensor.3d.shared::cluster.global.mbarrier::complete_tx::bytes [%0], [%1, {%3, %4, %5}], [%2];"
                 ::"r"(dst), "l"(tm), "r"(bar), "r"(c0), "r"(c1), "r"(c2) : "memory");
}
DEVI void bulk_g2s(uint32_t dst, uint32_t lo, uint32_t hi, uint32_t bytes, uint32_t bar) {
    asm volatile("{\n.reg .b64 a;\nmov.b64 a, {%1,%2};\ncp.async.bulk.shared::cluster.global.mbarrier::complete_tx::bytes [%0], [a], %3, [%4];\n}"
                 ::"r"(dst), "r"(lo), "r"(hi), "r"(bytes), "r"(bar) : "memory");
}
DEVI void bulk_s2g(uint32_t lo, uint32_t hi, uint32_t src, uint32_t bytes) {
    asm volatile("{\n.reg .b64 a;\nmov.b64 a, {%0,%1};\ncp.async.bulk.global.shared::cta.bulk_group [a], [%2], %3;\ncp.async.bulk.commit_group;\n}"
                 ::"r"(lo), "r"(hi), "r"(src), "r"(bytes) : "memory");
}
DEVI void bulk_red(uint32_t lo, uint32_t hi, uint32_t src, uint32_t bytes) {
    asm volatile("{\n.reg .b64 a;\nmov.b64 a, {%0,%1};\ncp.reduce.async.bulk.global.shared::cta.bulk_group.add.noftz.bf16 [a], [%2], %3;\ncp.async.bulk.commit_group;\n}"
                 ::"r"(lo), "r"(hi), "r"(src), "r"(bytes) : "memory");
}
DEVI bool elect() {
    uint32_t p;
    asm volatile("{\n.reg .pred P;\nelect.sync _|P, 0xFFFFFFFF;\nselp.u32 %0, 1, 0, P;\n}" : "=r"(p));
    return p != 0;
}
DEVI void ldsm4(uint32_t (&r)[4], uint32_t a) {
    asm volatile("ldmatrix.sync.aligned.m8n8.x4.shared.b16 {%0,%1,%2,%3}, [%4];" : "=r"(r[0]), "=r"(r[1]), "=r"(r[2]), "=r"(r[3]) : "r"(a) : "memory");
}
DEVI void ldsm4t(uint32_t (&r)[4], uint32_t a) {
    asm volatile("ldmatrix.sync.aligned.m8n8.x4.trans.shared.b16 {%0,%1,%2,%3}, [%4];" : "=r"(r[0]), "=r"(r[1]), "=r"(r[2]), "=r"(r[3]) : "r"(a) : "memory");
}
DEVI void ldsm2t(uint32_t (&r)[2], uint32_t a) {
    asm volatile("ldmatrix.sync.aligned.m8n8.x2.trans.shared.b16 {%0,%1}, [%2];" : "=r"(r[0]), "=r"(r[1]) : "r"(a) : "memory");
}
DEVI void ldsm2(uint32_t (&r)[2], uint32_t a) {
    asm volatile("ldmatrix.sync.aligned.m8n8.x2.shared.b16 {%0,%1}, [%2];" : "=r"(r[0]), "=r"(r[1]) : "r"(a) : "memory");
}
DEVI void stsm4t(uint32_t a, uint32_t r0, uint32_t r1, uint32_t r2, uint32_t r3) {
    asm volatile("stmatrix.sync.aligned.m8n8.x4.trans.shared.b16 [%0], {%1,%2,%3,%4};" ::"r"(a), "r"(r0), "r"(r1), "r"(r2), "r"(r3) : "memory");
}
DEVI uint32_t ldsm1(uint32_t a) {
    uint32_t r;
    asm volatile("ldmatrix.sync.aligned.m8n8.x1.shared.b16 {%0}, [%1];" : "=r"(r) : "r"(a) : "memory");
    return r;
}
DEVI void stsm4(uint32_t a, uint32_t r0, uint32_t r1, uint32_t r2, uint32_t r3) {
    asm volatile("stmatrix.sync.aligned.m8n8.x4.shared.b16 [%0], {%1,%2,%3,%4};" ::"r"(a), "r"(r0), "r"(r1), "r"(r2), "r"(r3) : "memory");
}
DEVI void stsm2(uint32_t a, uint32_t r0, uint32_t r1) {
    asm volatile("stmatrix.sync.aligned.m8n8.x2.shared.b16 [%0], {%1,%2};" ::"r"(a), "r"(r0), "r"(r1) : "memory");
}
DEVI uint32_t movm(uint32_t a) {
    uint32_t d;
    asm volatile("movmatrix.sync.aligned.m8n8.trans.b16 %0, %1;" : "=r"(d) : "r"(a));
    return d;
}
DEVI void mma16(float (&d)[4], uint32_t a0, uint32_t a1, uint32_t a2, uint32_t a3, uint32_t b0, uint32_t b1) {
    asm volatile("mma.sync.aligned.m16n8k16.row.col.f32.bf16.bf16.f32 {%0,%1,%2,%3}, {%4,%5,%6,%7}, {%8,%9}, {%0,%1,%2,%3};"
                 : "+f"(d[0]), "+f"(d[1]), "+f"(d[2]), "+f"(d[3]) : "r"(a0), "r"(a1), "r"(a2), "r"(a3), "r"(b0), "r"(b1));
}
DEVI void mma16z(float (&d)[4], uint32_t a0, uint32_t a1, uint32_t a2, uint32_t a3, uint32_t b0, uint32_t b1) {
    asm volatile("mma.sync.aligned.m16n8k16.row.col.f32.bf16.bf16.f32 {%0,%1,%2,%3}, {%4,%5,%6,%7}, {%8,%9}, {%10,%10,%10,%10};"
                 : "=f"(d[0]), "=f"(d[1]), "=f"(d[2]), "=f"(d[3]) : "r"(a0), "r"(a1), "r"(a2), "r"(a3), "r"(b0), "r"(b1), "f"(0.f));
}
DEVI void mma8(float (&d)[4], uint32_t a0, uint32_t a1, uint32_t b0) {
    asm volatile("mma.sync.aligned.m16n8k8.row.col.f32.bf16.bf16.f32 {%0,%1,%2,%3}, {%4,%5}, {%6}, {%0,%1,%2,%3};"
                 : "+f"(d[0]), "+f"(d[1]), "+f"(d[2]), "+f"(d[3]) : "r"(a0), "r"(a1), "r"(b0));
}
DEVI void mma8z(float (&d)[4], uint32_t a0, uint32_t a1, uint32_t b0) {
    asm volatile("mma.sync.aligned.m16n8k8.row.col.f32.bf16.bf16.f32 {%0,%1,%2,%3}, {%4,%5}, {%6}, {%7,%7,%7,%7};"
                 : "=f"(d[0]), "=f"(d[1]), "=f"(d[2]), "=f"(d[3]) : "r"(a0), "r"(a1), "r"(b0), "f"(0.f));
}
DEVI uint32_t pack2(float lo, float hi) {
    uint32_t r;
    asm("cvt.rn.bf16x2.f32 %0, %1, %2;" : "=r"(r) : "f"(hi), "f"(lo));
    return r;
}
DEVI uint32_t hadd2(uint32_t a, uint32_t b) {
    uint32_t r;
    asm("add.rn.bf16x2 %0, %1, %2;" : "=r"(r) : "r"(a), "r"(b));
    return r;
}
DEVI float lo_f(uint32_t x) { return __uint_as_float(x << 16); }
DEVI float hi_f(uint32_t x) { return __uint_as_float(x & 0xFFFF0000u); }
template <uint32_t OFF> DEVI uint4 ldg4(uint32_t lo, uint32_t hi) {
    uint4 v;
    asm volatile("{\n.reg .b64 a;\nmov.b64 a, {%4,%5};\nld.relaxed.gpu.global.v4.u32 {%0,%1,%2,%3}, [a+%6];\n}"
                 : "=r"(v.x), "=r"(v.y), "=r"(v.z), "=r"(v.w) : "r"(lo), "r"(hi), "n"(OFF) : "memory");
    return v;
}
template <uint32_t OFF> DEVI uint2 ldg2(uint32_t lo, uint32_t hi) {
    uint2 v;
    asm volatile("{\n.reg .b64 a;\nmov.b64 a, {%2,%3};\nld.relaxed.gpu.global.v2.u32 {%0,%1}, [a+%4];\n}"
                 : "=r"(v.x), "=r"(v.y) : "r"(lo), "r"(hi), "n"(OFF) : "memory");
    return v;
}
template <uint32_t OFF> DEVI uint32_t ldg1(uint32_t lo, uint32_t hi) {
    uint32_t v;
    asm volatile("{\n.reg .b64 a;\nmov.b64 a, {%1,%2};\nld.relaxed.gpu.global.u32 %0, [a+%3];\n}" : "=r"(v) : "r"(lo), "r"(hi), "n"(OFF) : "memory");
    return v;
}
template <uint32_t OFF> DEVI void stg1(uint32_t lo, uint32_t hi, uint32_t a) {
    asm volatile("{\n.reg .b64 a;\nmov.b64 a, {%0,%1};\nst.relaxed.gpu.global.u32 [a+%3], %2;\n}" ::"r"(lo), "r"(hi), "r"(a), "n"(OFF) : "memory");
}
template <uint32_t OFF> DEVI void stg4(uint32_t lo, uint32_t hi, uint32_t a, uint32_t b, uint32_t c, uint32_t d) {
    asm volatile("{\n.reg .b64 a;\nmov.b64 a, {%0,%1};\nst.relaxed.gpu.global.v4.u32 [a+%6], {%2,%3,%4,%5};\n}"
                 ::"r"(lo), "r"(hi), "r"(a), "r"(b), "r"(c), "r"(d), "n"(OFF) : "memory");
}
template <uint32_t OFF> DEVI void stg2(uint32_t lo, uint32_t hi, uint32_t a, uint32_t b) {
    asm volatile("{\n.reg .b64 a;\nmov.b64 a, {%0,%1};\nst.relaxed.gpu.global.v2.u32 [a+%4], {%2,%3};\n}"
                 ::"r"(lo), "r"(hi), "r"(a), "r"(b), "n"(OFF) : "memory");
}
DEVI uint32_t tagx2(uint32_t a, uint32_t b, uint32_t t) { uint32_t r; asm("lop3.b32 %0, %1, %2, %3, 0x7E;" : "=r"(r) : "r"(a), "r"(b), "r"(t)); return r; }
DEVI uint32_t tagx1(uint32_t a, uint32_t b, uint32_t t) { uint32_t r; asm("lop3.b32 %0, %1, %2, %3, 0xF6;" : "=r"(r) : "r"(a), "r"(b), "r"(t)); return r; }
DEVI uint32_t or3(uint32_t a, uint32_t b, uint32_t c) { uint32_t r; asm("lop3.b32 %0, %1, %2, %3, 0xFE;" : "=r"(r) : "r"(a), "r"(b), "r"(c)); return r; }
DEVI bool any_bad(uint32_t x) { return __any_sync(0xFFFFFFFFu, (x & 1u) != 0); }
DEVI uint32_t settag(uint32_t x, uint32_t tag) { return (x & ~1u) | tag; }
DEVI void sts32f(uint32_t a, float v) { asm volatile("st.shared.f32 [%0], %1;" ::"r"(a), "f"(v) : "memory"); }
DEVI void sts32(uint32_t a, uint32_t v) { asm volatile("st.shared.u32 [%0], %1;" ::"r"(a), "r"(v) : "memory"); }
DEVI void sts16(uint32_t a, uint32_t v) { asm volatile("st.shared.u16 [%0], %1;" ::"r"(a), "h"((unsigned short)v) : "memory"); }
DEVI void sts64(uint32_t a, uint32_t x, uint32_t y) { asm volatile("st.shared.v2.u32 [%0], {%1,%2};" ::"r"(a), "r"(x), "r"(y) : "memory"); }
DEVI void sts128(uint32_t a, uint32_t x, uint32_t y, uint32_t z, uint32_t w) {
    asm volatile("st.shared.v4.u32 [%0], {%1,%2,%3,%4};" ::"r"(a), "r"(x), "r"(y), "r"(z), "r"(w) : "memory");
}
DEVI float4 lds128f(uint32_t a) {
    float4 v;
    asm volatile("ld.shared.v4.f32 {%0,%1,%2,%3}, [%4];" : "=f"(v.x), "=f"(v.y), "=f"(v.z), "=f"(v.w) : "r"(a) : "memory");
    return v;
}
DEVI uint4 lds128(uint32_t a) {
    uint4 v;
    asm volatile("ld.shared.v4.u32 {%0,%1,%2,%3}, [%4];" : "=r"(v.x), "=r"(v.y), "=r"(v.z), "=r"(v.w) : "r"(a) : "memory");
    return v;
}
DEVI uint2 lds64(uint32_t a) {
    uint2 v;
    asm volatile("ld.shared.v2.u32 {%0,%1}, [%2];" : "=r"(v.x), "=r"(v.y) : "r"(a) : "memory");
    return v;
}
DEVI uint32_t lds32(uint32_t a) {
    uint32_t v;
    asm volatile("ld.shared.u32 %0, [%1];" : "=r"(v) : "r"(a) : "memory");
    return v;
}
DEVI float ex2(float x) { float r; asm("ex2.approx.ftz.f32 %0, %1;" : "=f"(r) : "f"(x)); return r; }
DEVI float rcp(float x) { float r; asm("rcp.approx.ftz.f32 %0, %1;" : "=f"(r) : "f"(x)); return r; }
DEVI uint32_t clk() { uint32_t c; asm volatile("mov.u32 %0, %%clock;" : "=r"(c)::"memory"); return c; }

DEVI uint64_t mkdesc(uint32_t addr, uint32_t lbo, uint32_t sbo) {
    return (uint64_t)((addr & 0x3FFFF) >> 4) | ((uint64_t)(lbo >> 4) << 16) | ((uint64_t)(sbo >> 4) << 32) | ((uint64_t)1 << 62);
}
DEVI void wg_fence() { asm volatile("wgmma.fence.sync.aligned;" ::: "memory"); }
DEVI void wg_commit() { asm volatile("wgmma.commit_group.sync.aligned;" ::: "memory"); }
template <int N> DEVI void wg_wait() { asm volatile("wgmma.wait_group.sync.aligned %0;" ::"n"(N) : "memory"); }
template <int SC>
DEVI void wg_rs32(float (&d)[16], const uint32_t (&a)[4], uint64_t db) {
    if (SC) {
        asm volatile("wgmma.mma_async.sync.aligned.m64n32k16.f32.bf16.bf16 "
                     "{%0,%1,%2,%3,%4,%5,%6,%7,%8,%9,%10,%11,%12,%13,%14,%15}, {%16,%17,%18,%19}, %20, 1, 1, 1, 0;"
                     : "+f"(d[0]), "+f"(d[1]), "+f"(d[2]), "+f"(d[3]), "+f"(d[4]), "+f"(d[5]), "+f"(d[6]), "+f"(d[7]),
                       "+f"(d[8]), "+f"(d[9]), "+f"(d[10]), "+f"(d[11]), "+f"(d[12]), "+f"(d[13]), "+f"(d[14]), "+f"(d[15])
                     : "r"(a[0]), "r"(a[1]), "r"(a[2]), "r"(a[3]), "l"(db));
    } else {
        asm volatile("wgmma.mma_async.sync.aligned.m64n32k16.f32.bf16.bf16 "
                     "{%0,%1,%2,%3,%4,%5,%6,%7,%8,%9,%10,%11,%12,%13,%14,%15}, {%16,%17,%18,%19}, %20, 0, 1, 1, 0;"
                     : "=f"(d[0]), "=f"(d[1]), "=f"(d[2]), "=f"(d[3]), "=f"(d[4]), "=f"(d[5]), "=f"(d[6]), "=f"(d[7]),
                       "=f"(d[8]), "=f"(d[9]), "=f"(d[10]), "=f"(d[11]), "=f"(d[12]), "=f"(d[13]), "=f"(d[14]), "=f"(d[15])
                     : "r"(a[0]), "r"(a[1]), "r"(a[2]), "r"(a[3]), "l"(db));
    }
}

#define NA 12
#define NPF 6
#define PF1 2
#define PF2 2
#define PF3 5
#define WPF 2
#define VPF 2
#define VORD (NA == 12 ? 0x01234567 : NA == 10 ? 0x50123467 : NA == 8 ? 0x40125367 : 0x30142567)
#define WV_BOX ((16 - NA) * 2048)
#define WO_BOX 16384
#define SM_WV 0
#define SM_WO (2 * WV_BOX)
#define SM_X (SM_WO + 4 * WO_BOX)
#define SM_XO (SM_X + 32768)
#define SM_MEMT (SM_XO + 12288)
#define SM_OT (SM_MEMT + 4096)
#define SM_VS (SM_OT + 2048)
#define SM_P (SM_VS + 2048)
#define SM_DN (SM_P + 1792)
#define SM_PROF (SM_P + 2048)
#define SM_ST (SM_X + 65536)
#define SM_KV SM_ST
#define SM_SP (SM_KV + 18432)
#define SM_TR (SM_ST + 32768)
#define SM_PI (SM_ST + 65536)
#define SM_BAR (SM_PI + 12288)
#define SM_TOTAL (SM_BAR + 512)
static_assert(NA == 12, "start-up chunks");
static_assert(SM_TOTAL <= 232448, "smem");
#define BAR_XA 32
#define BAR_KV 40
#define BAR_PI 48
#define BAR_RO 64
#define BAR_WF 256
#define BAR_WE 384
#define SM_ROLE (SM_BAR + 72)

#define SPIN_LIMIT (1 << 20)
#define RPOS 20
#define OPOS 2
#define ASF 0
#define KPOS 0
#define CPOS 1
#define DLY_V 400
#define NPRB 3
#define XPF 1
#define WOP 2
#define WIN 2
#define EPD 1300
#define ASP 4
#define EPF 0
#define CFAR 1

template <int ID, int N> DEVI void bsync() { asm volatile("bar.sync %0, %1;" ::"n"(ID), "n"(N) : "memory"); }
template <int ID, int N> DEVI void barv() { asm volatile("bar.arrive %0, %1;" ::"n"(ID), "n"(N) : "memory"); }

#define PT(n)
#define PC(n, v)
#define PDUMP()
#define REFRESH() asm volatile("xor.b32 %0, %0, %1;" : "+r"(l16) : "r"(zero))
#define OPQ(x) asm volatile("xor.b32 %0, %0, %1;" : "+r"(x) : "r"(zero))
#define KEEP(x, a, b, c, d) asm volatile("{\n.reg .b32 t;\nlop3.b32 t, %1, %2, %3, 0x80;\nlop3.b32 t, t, %4, %5, 0x80;\nxor.b32 %0, %0, t;\n}" \
                                         : "+r"(x) : "r"(a), "r"(b), "r"(c), "r"(d), "r"(zero))
#define SF() asm volatile("pmevent 1;" ::: "memory")
#define MF() __syncwarp()
#define SB0 1024u

#define XDOFF(ks) ((((ks) >> 2) * 1024 + ((ks) & 3) * 32) >> 4)
template <int SC>
DEVI void wg_ss32t(float (&d)[16], uint64_t da, uint64_t db) {
    if (SC) {
        asm volatile("wgmma.mma_async.sync.aligned.m64n32k16.f32.bf16.bf16 "
                     "{%0,%1,%2,%3,%4,%5,%6,%7,%8,%9,%10,%11,%12,%13,%14,%15}, %16, %17, 1, 1, 1, 1, 0;"
                     : "+f"(d[0]), "+f"(d[1]), "+f"(d[2]), "+f"(d[3]), "+f"(d[4]), "+f"(d[5]), "+f"(d[6]), "+f"(d[7]),
                       "+f"(d[8]), "+f"(d[9]), "+f"(d[10]), "+f"(d[11]), "+f"(d[12]), "+f"(d[13]), "+f"(d[14]), "+f"(d[15])
                     : "l"(da), "l"(db));
    } else {
        asm volatile("wgmma.mma_async.sync.aligned.m64n32k16.f32.bf16.bf16 "
                     "{%0,%1,%2,%3,%4,%5,%6,%7,%8,%9,%10,%11,%12,%13,%14,%15}, %16, %17, 0, 1, 1, 1, 0;"
                     : "=f"(d[0]), "=f"(d[1]), "=f"(d[2]), "=f"(d[3]), "=f"(d[4]), "=f"(d[5]), "=f"(d[6]), "=f"(d[7]),
                       "=f"(d[8]), "=f"(d[9]), "=f"(d[10]), "=f"(d[11]), "=f"(d[12]), "=f"(d[13]), "=f"(d[14]), "=f"(d[15])
                     : "l"(da), "l"(db));
    }
}

DEVI void delay_until(uint32_t t0, uint32_t d) { t0 += d; while (clk() < t0) {} }

template <int I0, int I1>
DEVI void xmma(float (&xa)[16], float (&xb)[16], uint32_t w, int ps, uint32_t zero, const uint32_t (&Wq)[16][4], const uint32_t (&Wk)[16][4],
               const uint32_t (&Wv)[NA][4]) {
    const uint64_t xd = mkdesc(SB0 + SM_X, 16, 4096) + (ps & 1) * 1024, vd = mkdesc(SB0 + SM_WV, 8192, 1024);
    uint32_t vo = (w >> 2) * (WV_BOX / 16);
    if (I0 < 16 - NA) OPQ(vo);
#pragma unroll
    for (int i = I0; i < I1; i++) {
        if (i == 0) wg_ss32t<0>(xb, (vd & ~0xFFFFFFFFull) | ((uint32_t)vd + vo), xd + XDOFF(NA));
        else if (i < 16 - NA) wg_ss32t<1>(xb, (vd & ~0xFFFFFFFFull) | ((uint32_t)vd + i * 128 + vo), xd + XDOFF(NA + i));
        else if (i == 16 - NA) wg_rs32<0>(xa, Wq[0], xd);
        else if (i < 32 - NA) wg_rs32<1>(xa, Wq[(i + NA) & 15], xd + XDOFF((i + NA) & 15));
        else if (i < 32) wg_rs32<1>(xb, Wv[(i + NA) & 15], xd + XDOFF((i + NA) & 15));
        else if (i == 32) wg_rs32<0>(xa, Wk[0], xd);
        else wg_rs32<1>(xa, Wk[i & 15], xd + XDOFF(i & 15));
    }
    wg_commit();
}
#define XMMA(I0, I1) xmma<(I0), (I1)>(xa, xb, w, p ^ 1, zero, Wq, Wk, Wv)
DEVI void wg_done(float (&d)[16]) {
    asm volatile("" : "+f"(d[0]), "+f"(d[1]), "+f"(d[2]), "+f"(d[3]), "+f"(d[4]), "+f"(d[5]), "+f"(d[6]), "+f"(d[7]),
                      "+f"(d[8]), "+f"(d[9]), "+f"(d[10]), "+f"(d[11]), "+f"(d[12]), "+f"(d[13]), "+f"(d[14]), "+f"(d[15]) :: "memory");
}
template <int M>
DEVI void xpack(uint32_t (&xp)[8], float (&xa)[16]) {
    wg_done(xa);
#pragma unroll
    for (int i = 0; i < 4; i++) {
        xp[2 * i] = pack2(xa[4 * i], xa[4 * i + (M < 2 ? 2 : 1)]);
        xp[2 * i + 1] = pack2(xa[4 * i + (M < 2 ? 1 : 2)], xa[4 * i + 3]);
    }
}
template <int M>
DEVI uint4 xpeer(uint32_t sb, int ps, uint32_t t16) { return lds128(sb + SM_PI - ((ps & 1) ^ 1) * 12288 + M * 4096 + t16); }
DEVI void xadd(uint32_t (&xp)[8], const uint4& pi) {
    xp[0] = hadd2(xp[0], pi.x); xp[1] = hadd2(xp[1], pi.y); xp[2] = hadd2(xp[2], pi.z); xp[3] = hadd2(xp[3], pi.w);
}
template <int M>
DEVI void xsend(const uint32_t (&xp)[8], uint32_t sb, int ps, uint32_t t16) {
    asm volatile("st.async.weak.shared::cluster.mbarrier::complete_tx::bytes.v4.b32 [%0], {%1,%2,%3,%4}, [%5];"
                 ::"r"((sb ^ 0x1000000) + SM_PI - (ps & 1) * 12288 + M * 4096 + t16), "r"(xp[4]), "r"(xp[5]), "r"(xp[6]), "r"(xp[7]),
                   "r"((sb ^ 0x1000000) + SM_BAR + BAR_PI + (ps & 1) * 8) : "memory");
}
template <int M>
DEVI void xstore(const uint32_t (&xp)[8], uint32_t sb, uint32_t sbw, int ps, uint32_t t16, uint32_t KA) {
    const uint32_t a = SM_XO + M * 2048 + (M < 2 ? (KA & 0xFF) + sbw : (t16 >> 1) + sb);
    sts64(a, xp[0], xp[1]);
    sts64(a + 6144, xp[2], xp[3]);
    xsend<M>(xp, sb, ps, t16);
}
template <int M>
DEVI void xpark(uint32_t (&xp)[8], const uint4& pi, uint32_t sb, uint32_t sbw, int ps, uint32_t t16, uint32_t KA) {
    xadd(xp, pi);
    xstore<M>(xp, sb, sbw, ps, t16, KA);
}
template <uint32_t OFF> DEVI void red2(uint32_t lo, uint32_t hi, uint32_t a, uint32_t b) {
    asm volatile("{\n.reg .b64 a;\nmov.b64 a, {%0,%1};\nred.relaxed.gpu.global.add.noftz.v2.bf16x2 [a+%4], {%2,%3};\n}"
                 ::"r"(lo), "r"(hi), "r"(a), "r"(b), "n"(OFF) : "memory");
}
template <int M, int N>
DEVI void xstart(uint32_t sb, uint32_t w, uint32_t ga, uint32_t xhi, uint32_t j, uint32_t t16, uint32_t KA, const uint32_t (&W)[N][4]) {
    float xa[16], xb[16];
    uint32_t xp[8];
    auto pass = [&](float (&d)[16], int i, int k0, int k1) {
        const uint64_t xd = mkdesc(SB0 + SM_X + (i ? i + 1 : 0) * 16384, 16, 4096), vd = mkdesc(SB0 + SM_WV, 8192, 1024) + (w >> 2) * (WV_BOX / 16);
#pragma unroll
        for (int k = k0; k < k1; k++) {
            if (k == 0) wg_rs32<0>(d, W[0], xd);
            else if (k < N) wg_rs32<1>(d, W[k < N ? k : 0], xd + XDOFF(k));
            else wg_ss32t<1>(d, vd + (k - N) * 128, xd + XDOFF(k));
        }
        wg_commit();
    };
    wg_fence();
    pass(xa, 0, 0, 16);
    pass(xb, 1, 0, ASP);
    if (M == 0) bsync<5, 256>();
    ga += M < 2 ? (KA & 0xFF) + w * 256 : t16 >> 1;
    constexpr uint32_t O = XO_XG + M * 2048, SG = 128 * 6144;
    wg_wait<1>();
    xpack<M>(xp, xa);
    red2<O>(ga, xhi, xp[0], xp[1]); red2<O + 6144>(ga, xhi, xp[2], xp[3]); red2<O + 12288>(ga, xhi, xp[4], xp[5]); red2<O + 18432>(ga, xhi, xp[6], xp[7]);
    if (M == 2) barv<3, 320>();
    wg_fence();
    pass(xb, 1, ASP, 16);
    pass(xa, 2, 0, 16);
    wg_wait<1>();
    xpack<M>(xp, xb);
    red2<O + SG>(ga, xhi, xp[0], xp[1]); red2<O + SG + 6144>(ga, xhi, xp[2], xp[3]);
    red2<O + SG + 12288>(ga, xhi, xp[4], xp[5]); red2<O + SG + 18432>(ga, xhi, xp[6], xp[7]);
    wg_wait<0>();
    xpack<M>(xp, xa);
    red2<O + 2 * SG>(ga + j * 6144, xhi, xp[0], xp[1]);
    red2<O + 2 * SG>(ga + (j ^ 1) * 6144, xhi, xp[2], xp[3]);
    xsend<M>(xp, sb, 0, t16);
}
DEVI void piwait(uint32_t sb, int p, int ps) { mbar_wait(sb + SM_BAR + BAR_PI + p * 8, ((ps + 2) >> 1) & 1); }

DEVI uint32_t par(uint32_t off) { return __popc(off & 0xB2000u) & 1; }
DEVI uint32_t probe(uint32_t lo, uint32_t hi) {
    uint32_t best = 0xFFFFFFFFu, x = 0;
    stg4<0>(lo, hi, 0, 0, 0, 0);
    stg4<16>(lo, hi, 0, 0, 0, 0);
#pragma unroll 1
    for (int r = 0; r < NPRB; r++) {
        const uint32_t t0 = clk();
        asm volatile("{\n.reg .b64 a;\nmov.b64 a, {%1,%2};\natom.relaxed.gpu.global.add.u32 %0, [a], 2;\n}" : "=r"(x) : "r"(lo), "r"(hi) : "memory");
        if (x == 0xFFFFFFFFu) die(1 << 23);
        best = min(best, clk() - t0);
    }
    return best;
}

DEVI void xload(uint32_t sb, uint32_t u, uint32_t j, int ps, const CUtensorMap* tmx) {
    if (elect()) {
        const uint32_t sg = ps + 4 - (u & 1) + (u >> 1);
        mbar_expect(sb + SM_BAR + BAR_XA, sg < NSEG ? 4096 : 0);
        if (sg < NSEG) tma3d(sb + SM_X + (ps & 1) * 16384 + u * 4096, tmx, sb + SM_BAR + BAR_XA, 0, sg * 32 + (j ^ ((u & 1) * 2 + (u >> 1))) * 8, j * 4);
    }
}
DEVI uint32_t rpage(uint32_t j, int s) { return (s & 3) * 65536 + (j & 1) * 8192 + (((s ^ (s >> 1) ^ j ^ (j >> 1)) & 1) << 12); }

#define RLOAD(a) { m0 = ldg4<XO_R>(a, xhi); n0 = ldg4<XO_R + 16384>(a, xhi); \
                   e0 = ldg1<XO_R + 32768>(((a) & ~0xFFFu) + (((a) & 0xFFF) >> 2), xhi); f0 = ldg1<XO_R + 33792>(((a) & ~0xFFFu) + (((a) & 0xFFF) >> 2), xhi); }
DEVI bool ruse(uint32_t a, const uint4& m0, const uint4& n0, uint32_t e0, uint32_t f0) {
    const uint32_t a0 = hadd2(m0.w, n0.w), b0 = hadd2(e0, f0);
    stsm4(a, hadd2(m0.x, n0.x), hadd2(m0.y, n0.y), hadd2(m0.z, n0.z), __byte_perm(a0, b0, 0x5410));
    return __any_sync(0xFFFFFFFFu, (a0 & b0 & 0x42000000u) != 0x42000000u);
}

#define GST(i) (SM_WO + (i) * 49152)
#define BAR_GF 128
#define BAR_GE (BAR_GF + 64)
#define BAR_GX (BAR_GE + 32)
#define D4(c, i) #c "f"(d[i]), #c "f"(d[i + 1]), #c "f"(d[i + 2]), #c "f"(d[i + 3])
#define D16(c, i) D4(c, i), D4(c, i + 4), D4(c, i + 8), D4(c, i + 12)
DEVI void mwait(uint32_t bar, uint32_t parity) {
    asm volatile("{\n.reg .pred p;\n.reg .b32 c;\nmbarrier.try_wait.parity.shared::cta.b64 p, [%0], %1;\n@p bra.uni D;\nmov.b32 c, 0;\n"
                 "L:\nadd.u32 c, c, 1;\nsetp.gt.u32 p, c, 4194304;\n@p st.shared.u32 [c], c;\n"
                 "mbarrier.try_wait.parity.shared::cta.b64 p, [%0], %1;\n@!p bra.uni L;\nD:\n}" ::"r"(bar), "r"(parity) : "memory");
}
DEVI void wg_ss256t(float (&d)[128], uint64_t da, uint64_t db) {
    asm volatile("wgmma.mma_async.sync.aligned.m64n256k16.f32.bf16.bf16 "
        "{%0,%1,%2,%3,%4,%5,%6,%7,%8,%9,%10,%11,%12,%13,%14,%15,%16,%17,%18,%19,%20,%21,%22,%23,%24,%25,%26,%27,%28,%29,%30,%31,%32,%33,%34,%35,%36,%37,%38,%39,%40,%41,%42,%43,%44,%45,%46,%47,%48,%49,%50,%51,%52,%53,%54,%55,%56,%57,%58,%59,%60,%61,%62,%63,%64,%65,%66,%67,%68,%69,%70,%71,%72,%73,%74,%75,%76,%77,%78,%79,%80,%81,%82,%83,%84,%85,%86,%87,%88,%89,%90,%91,%92,%93,%94,%95,%96,%97,%98,%99,%100,%101,%102,%103,%104,%105,%106,%107,%108,%109,%110,%111,%112,%113,%114,%115,%116,%117,%118,%119,%120,%121,%122,%123,%124,%125,%126,%127}, "
        "%128, %129, 1, 1, 1, 1, 1;"
        : D16(+, 0), D16(+, 16), D16(+, 32), D16(+, 48), D16(+, 64), D16(+, 80), D16(+, 96), D16(+, 112) : "l"(da), "l"(db));
}
template <int O, int KB> DEVI void g_half(float (&d)[64], uint64_t da) {
    const uint64_t db = mkdesc(SB0 + GST(KB & 3) + 16384 + O * 256, 8192, 1024);
#pragma unroll
    for (int k = 0; k < 4; k++)
        asm volatile("wgmma.mma_async.sync.aligned.m64n128k16.f32.bf16.bf16 "
            "{%0,%1,%2,%3,%4,%5,%6,%7,%8,%9,%10,%11,%12,%13,%14,%15,%16,%17,%18,%19,%20,%21,%22,%23,%24,%25,%26,%27,%28,%29,%30,%31,%32,%33,%34,%35,%36,%37,%38,%39,%40,%41,%42,%43,%44,%45,%46,%47,%48,%49,%50,%51,%52,%53,%54,%55,%56,%57,%58,%59,%60,%61,%62,%63}, "
            "%64, %65, 1, 1, 1, 1, 1;"
            : D16(+, 0), D16(+, 16), D16(+, 32), D16(+, 48) : "l"(da + (KB & 3) * 3072 + k * 16), "l"(db + k * 128));
}
DEVI void g_load(uint32_t sb, uint32_t u, uint32_t role, uint32_t kb, uint32_t xlo, uint32_t xhi, const CUtensorMap* tmb) {
    const uint32_t st = kb & 3, bar = sb + SM_BAR + BAR_GF + u * 32 + st * 8, dst = sb + GST(st), k = (role & 1) * 32 + kb;
    if (!elect()) return;
    mbar_expect(bar, u ? 8192 : 40960);
    bulk_g2s(dst + u * 8192, xlo + XO_OX + ((role >> 3) * 64 + k) * 16384 + u * 8192, xhi, 8192, bar);
    if (u == 0) {
        tma3d(dst + 16384, tmb, bar, 0, k * 64, ((role & 7) ^ 1) * 2);
        tma3d(dst + 32768, tmb, bar, 0, k * 64, (role & 7) * 2);
    }
}
DEVI void g_arrive(uint32_t a, uint32_t xhi, uint32_t n) {
    if (elect()) asm volatile("{\n.reg .b64 a;\nmov.b64 a, {%0,%1};\nred.release.gpu.global.inc.u32 [a], %2;\n}" ::"r"(a), "r"(xhi), "r"(n - 1) : "memory");
}
DEVI void g_wait(uint32_t a, uint32_t xhi) {
    int it = 0;
    uint32_t v;
    do {
        asm volatile("{\n.reg .b64 a;\nmov.b64 a, {%1,%2};\nld.acquire.gpu.global.u32 %0, [a];\n}" : "=r"(v) : "r"(a), "r"(xhi) : "memory");
        if (++it > SPIN_LIMIT) die(it);
    } while (__any_sync(0xFFFFFFFFu, v));
    asm volatile("fence.proxy.async.global;" ::: "memory");
}
#define GD 200
DEVI void g_done(float (&d)[64]) { asm volatile("" : D16(+, 0), D16(+, 16), D16(+, 32), D16(+, 48)::"memory"); }
DEVI void g_main(uint32_t sb, uint32_t w, uint32_t role, const CUtensorMap* tmy) {
    const uint32_t bar = sb + SM_BAR, t16 = threadIdx.x * 16;
    const uint64_t da = (mkdesc(SB0 + GST(0), 128, 1024) & ~((uint64_t)3 << 62)) + (w >> 2) * 512;
    float d[128];
#pragma unroll
    for (int i = 0; i < 128; i++) d[i] = 0.f;
#define GFULL(kb) { mwait(bar + BAR_GF + ((kb) & 3) * 8, ((kb) >> 2) & 1); if (w >= 4) mwait(bar + BAR_GF + 32 + ((kb) & 3) * 8, ((kb) >> 2) & 1); }
#pragma unroll 1
    for (uint32_t kb = 0; kb < 29; kb++) {
        GFULL(kb);
        if (kb == 0 && threadIdx.x == 128) PG(4);
        if (kb == 4 && threadIdx.x == 0) PG(5);
        const uint64_t a = da + (kb & 3) * 3072, b = mkdesc(SB0 + GST(0) + 16384, 8192, 1024) + (kb & 3) * 3072;
        wg_fence();
#pragma unroll
        for (int k = 0; k < 4; k++) wg_ss256t(d, a + k * 16, b + k * 128);
        wg_commit();
        wg_wait<1>();
        if (kb > 0 && elect()) mbar_arrive(bar + BAR_GE + ((kb - 1) & 3) * 8);
    }
    GFULL(29);
    GFULL(30);
    GFULL(31);
    wg_wait<0>();
    float x[64], y[64];
#pragma unroll
    for (int i = 0; i < 64; i++) asm volatile("mov.b32 %0, %1;" : "=f"(x[i]) : "f"(d[i]) : "memory");
    SF();
#pragma unroll
    for (int i = 0; i < 64; i++) asm volatile("mov.b32 %0, %1;" : "=f"(y[i]) : "f"(d[i + 64]) : "memory");
    SF();
    if (elect()) asm volatile("mbarrier.arrive.relaxed.cluster.shared::cluster.b64 _, [%0];" ::"r"((bar ^ 0x1000000) + BAR_GX) : "memory");
    wg_fence();
    g_half<0, 29>(x, da);
    g_half<0, 30>(x, da);
    g_half<0, 31>(x, da);
    wg_commit();
    g_half<64, 29>(y, da);
    wg_commit();
    wg_wait<1>();
    g_done(x);
    mwait(bar + BAR_GX, 0);
#define GSEND(i0) _Pragma("unroll") for (int i = (i0); i < (i0) + 4; i++) \
        asm volatile("st.async.weak.shared::cluster.mbarrier::complete_tx::bytes.v4.b32 [%0], {%1,%2,%3,%4}, [%5];" \
                     ::"r"((sb ^ 0x1000000) + i * 4096 + t16), "r"(pack2(x[8 * i], x[8 * i + 1])), "r"(pack2(x[8 * i + 2], x[8 * i + 3])), \
                       "r"(pack2(x[8 * i + 4], x[8 * i + 5])), "r"(pack2(x[8 * i + 6], x[8 * i + 7])), "r"((bar ^ 0x1000000) + BAR_GX + 8) : "memory")
    GSEND(0);
    wg_fence();
    g_half<64, 30>(y, da);
    wg_commit();
    GSEND(4);
    wg_fence();
    g_half<64, 31>(y, da);
    wg_commit();
    wg_wait<0>();
    g_done(y);
    if (threadIdx.x == 0) PG(7);
    mwait(bar + BAR_GX + 8, 0);
    if (threadIdx.x == 0) PG(1);
    const uint32_t lane = threadIdx.x & 31, o = sb + GST(1) + w * 2048;
#pragma unroll
    for (int i = 0; i < 8; i++) {
        const uint4 a = lds128(sb + i * 4096 + t16);
        const float* e = y + 8 * i;
        stsm4(o + (i >> 2) * 49152 + (lane & 15) * 128 + ((((i & 3) * 2 + (lane >> 4)) ^ (lane & 7)) << 4),
              pack2(e[0] + lo_f(a.x), e[1] + hi_f(a.x)), pack2(e[2] + lo_f(a.y), e[3] + hi_f(a.y)),
              pack2(e[4] + lo_f(a.z), e[5] + hi_f(a.z)), pack2(e[6] + lo_f(a.w), e[7] + hi_f(a.w)));
        if (i == 3 || i == 7) {
            asm volatile("fence.proxy.async.shared::cta;" ::: "memory");
            __syncwarp();
            if (elect())
                asm volatile("cp.async.bulk.tensor.2d.global.shared::cta.bulk_group [%0, {%2, %3}], [%1];\ncp.async.bulk.commit_group;"
                             ::"l"(tmy), "r"(o + (i >> 2) * 49152), "r"((role & 7) * 128 + (i >> 2) * 64), "r"((role >> 3) * 128 + w * 16) : "memory");
        }
    }
    if (threadIdx.x == 0) PG(6);
    asm volatile("cp.async.bulk.wait_group.read 0;" ::: "memory");
}

DEVI void kvload(uint32_t sb, uint32_t u, uint32_t h, uint32_t j, int sg, uint32_t xlo, uint32_t xhi) {
    const uint32_t o = u == 0 ? 0 : 2048;
    mbar_expect(sb + SM_BAR + BAR_KV, 6144 - o);
    bulk_g2s(sb + SM_KV + u * 4096 + o, xlo + XO_XG + (((sg & 7) * 32 + h) * 4 + ((j + u) & 3)) * 6144 + o, xhi, 6144 - o, sb + SM_BAR + BAR_KV);
}
DEVI void helper_step(uint32_t sb, uint32_t w, uint32_t h, uint32_t j, uint32_t& l16, uint32_t xlo, uint32_t xhi, uint32_t zero, int s,
                      const CUtensorMap* tmx, const CUtensorMap* tmb) {
    const uint32_t u = w - 8, bq = sb + SM_BAR;
    bsync<1, 384>();
    PT(0);
    PDUMP();
    PT(1);
    if (s == NSEG - 2 && u < 2) g_arrive(xlo + XO_TK + 128, xhi, 256);
    const uint32_t ctag = ((s >> 1) & 1) ^ 1;
    const uint32_t av = xlo + ((s & 1) * 32 + h) * 8192 + u * 512;
    mbar_wait(bq + BAR_XA, (s + 1) & 1);
    bsync<8, 384>();
    delay_until(clk(), DLY_V);
    PT(4);
    int it = 0;
    bool bad;
    do {
        const uint4 d1 = ldg4<XO_CV>(av + (j ^ 1) * 2048 + l16, xhi);
        const uint4 d2 = ldg4<XO_CV>(av + (j ^ 2) * 2048 + l16, xhi);
        const uint4 d3 = ldg4<XO_CV>(av + (j ^ 3) * 2048 + l16, xhi);
        bad = any_bad(or3(tagx2(d1.x, d1.z, ctag), tagx2(d2.x, d2.z, ctag), tagx2(d3.x, d3.z, ctag)));
        sts128(sb + SM_VS + u * 512 + l16, hadd2(hadd2(d1.x, d2.x), d3.x), hadd2(hadd2(d1.y, d2.y), d3.y), hadd2(hadd2(d1.z, d2.z), d3.z),
               hadd2(hadd2(d1.w, d2.w), d3.w));
        REFRESH();
        if (++it > SPIN_LIMIT) die(it);
    } while (bad);
    PC(26, it - 1);
    PT(5);
    barv<5, 384>();
    bsync<3, 384>();
    if (u < 2) {
        asm volatile("fence.proxy.async.shared::cta;" ::: "memory");
        if (elect()) {
            const uint32_t sg = s + 3 - u;
            if (sg < NSEG) {
                const uint32_t ga = xlo + XO_XG + (((sg & 7) * 32 + h) * 4 + (j ^ (2 * u))) * 6144, sa = sb + SM_XO + u * 6144;
                if (u == 0) bulk_s2g(ga, xhi, sa, 6144);
                else bulk_red(ga, xhi, sa, 6144);
            }
        }
    }
    PT(6);
    uint32_t old = 0;
    if (u > 0 && s + 3 < NSEG)
        asm volatile("{\n.reg .b64 a;\nmov.b64 a, {%1,%2};\natom.relaxed.gpu.global.exch.b32 %0, [a], 0;\n}"
                     : "=r"(old) : "r"(xlo + XO_R + rpage(j, s + 2) + (u - 1) * 16384 + h * 128 + (l16 >> 2)), "r"(xhi) : "memory");
    PT(7);
    bsync<7, 384>();
    if (s + 1 < NSEG && elect()) kvload(sb, u, h, j, s + 1, xlo, xhi);
    if (u < 2) {
        asm volatile("cp.async.bulk.wait_group.read 0;" ::: "memory");
        if (elect()) mbar_expect(bq + BAR_PI + ((s & 1) ^ 1) * 8, 6144);
    }
    PT(8);
    if (s + 1 < NSEG) bsync<10, 384>();
    xload(sb, u, j, s + 1, tmx);
    if (s == NSEG - 2 && (u == 0 || (u == 1 && h < 30))) {
        g_wait(xlo + XO_TK + 128, xhi);
        g_load(sb, u, h * 4 + j, 0, xlo, xhi, tmb);
        g_load(sb, u, h * 4 + j, 1, xlo, xhi, tmb);
    }
    asm volatile("cp.async.bulk.wait_group 0;" ::: "memory");
    if (s + 1 < NSEG) mbar_wait(bq + BAR_KV, (s + 1) & 1);
    asm volatile("lop3.b32 %0, %0, %1, %2, 0x78;" : "+r"(l16) : "r"(old), "r"(zero));
    PT(15);
}
DEVI void tickets_done(uint32_t* tk) {
    if (atomicInc(tk + 2, gridDim.x / 2 - 64) == gridDim.x / 2 - 64) { tk[0] = 0; tk[1] = 0; }
}

__global__ void __cluster_dims__(2, 1, 1) __launch_bounds__(384, 1)
chain_kernel(const __grid_constant__ CUtensorMap tmq, const __grid_constant__ CUtensorMap tmk,
             const __grid_constant__ CUtensorMap tmv, const __grid_constant__ CUtensorMap tmo,
             const __grid_constant__ CUtensorMap tmx, const __grid_constant__ CUtensorMap tmb, const __grid_constant__ CUtensorMap tmy,
             const bf16* __restrict__ mem0, const bf16* __restrict__ xg,
             uint32_t xlo, uint32_t xhi, uint32_t zero, int nseg) {
    extern __shared__ __align__(1024) uint8_t smem[];
    if ((smem_u32(smem) & 0xFFFFFF) != SB0) die(1 << 23);
    asm volatile("griddepcontrol.launch_dependents;" ::: "memory");
    const uint32_t w = __reduce_max_sync(0xFFFFFFFFu, threadIdx.x >> 5);
    const uint32_t rk = smem_u32(smem) & 0x1000000;
    const uint32_t sb = __reduce_max_sync(0xFFFFFFFFu, smem_u32(smem));
    const uint32_t bq = sb + SM_BAR;
    uint32_t l16 = __shfl_sync(0xFFFFFFFFu, (threadIdx.x & 31) * 16, threadIdx.x & 31);
    if (threadIdx.x == 0) {
        mbar_init(bq, 1);
        for (int i = 0; i < 24; i++) mbar_init(bq + BAR_WF + i * 8, i < 16 ? 1 : 8);
        mbar_init(bq + BAR_XA, 4); mbar_init(bq + BAR_KV, 4); mbar_init(bq + BAR_PI, 2); mbar_init(bq + BAR_PI + 8, 2);
        for (int i = 0; i < 14; i++) mbar_init(bq + BAR_GF + i * 8, i < 8 || i == 13 ? 1 : 8);
        mbar_expect(bq + BAR_GX + 8, 32768);
        mbar_init(bq + BAR_RO, 1);
        mbar_expect(bq + BAR_RO, 4);
        mbar_expect(bq + BAR_PI, 6144);
        mbar_expect(bq + BAR_PI, 6144);
        asm volatile("fence.mbarrier_init.release.cluster;" ::: "memory");
        asm volatile("fence.proxy.async.shared::cta;" ::: "memory");
    }
    __syncwarp();
    asm volatile("barrier.cluster.arrive.relaxed.aligned;" ::: "memory");
    if (rk ? w < 8 : w == 4) {
        const uint32_t b = blockIdx.x - (w >> 2), u = w & 3, l = l16 >> 4;
        if (rk && b < 128) {
            uint32_t v = 0;
            const unsigned short* m0 = (const unsigned short*)mem0 + (b & 3) * 256;
            if (u == 1) {
                const uint32_t x = (b >> 2) * 8 + (l >> 2), d = (x & ~31u) + (l & 3) * 8 + ((x & 31) >> 2) + (x & 3) * 2 * DM;
                v = m0[d] | (((l & 3) == 3 ? 0x4200u : m0[d + DM]) << 16);
            }
            if (u == 3 && b < 32) v = m0[(b >> 2) * 32 + 24 + (l >> 2) + ((l & 3) * 2 + 1) * DM] | 0x42000000u;
#pragma unroll
            for (uint32_t i = 0; i < 9; i++) stg4<XO_XG>(xlo + ((i / 3) * 128 + b) * 6144 + (i % 3) * 2048 + u * 512 + l16, xhi, 0, 0, 0, 0);
            if (u > 0) {
                const uint32_t o = xlo + (u - 1) * 16384 + (b >> 2) * 128 + l * 4;
                stg1<XO_R>(o + rpage(b & 3, 0), xhi, 0);
                stg1<XO_R>(o + rpage(b & 3, 1), xhi, 0);
                stg1<XO_R>(o + rpage(b & 3, -1), xhi, v);
            }
        }
        __syncwarp();
        g_arrive(xlo + XO_TK + 12, xhi, 9 * (gridDim.x / 2));
    }
    if (w == 8 && blockIdx.x < 128) {
        if (XPF && elect()) {
            asm volatile("cp.async.bulk.prefetch.L2.global [%0], 3072;" ::"l"((const char*)xg + blockIdx.x * 3072) : "memory");
            asm volatile("prefetch.tensormap [%0];\nprefetch.tensormap [%1];\nprefetch.tensormap [%2];\nprefetch.tensormap [%3];\nprefetch.tensormap [%4];"
                         ::"l"(&tmq), "l"(&tmx), "l"(&tmk), "l"(&tmv), "l"(&tmo) : "memory");
        }
#pragma unroll 1
        for (int i = 0; i < EPF; i++) {
            if (i) delay_until(clk(), EPD);
            if (elect())
                asm volatile("cp.async.bulk.prefetch.tensor.3d.L2.global [%0, {0, %1, %2}];" ::"l"(&tmq), "r"((blockIdx.x & 3) * 256 + i * 64), "r"((blockIdx.x >> 2) * 2) : "memory");
        }
    }
    if (rk == 0 && w < 2) {
        if (l16 == 0) sts32(sb + SM_ROLE + 8 + w * 4, probe(xlo + XO_PB + w * 4096 + blockIdx.x * 16, xhi));
        bsync<2, 64>();
    }
    asm volatile("barrier.cluster.wait.aligned;" ::: "memory");
    if (rk == 0 && threadIdx.x == 0) {
        uint32_t side = (lds32(sb + SM_ROLE + 8) < lds32(sb + SM_ROLE + 12) ? 0u : 1u) ^ par(XO_PB);
        uint32_t* tk = (uint32_t*)(((uint64_t)xhi << 32) | (xlo + XO_TK));
        uint32_t t = atomicAdd(tk + side, 1u);
        if (t >= 32) {
            uint2 c;
            int it = 0;
            do {
                c = ldg2<XO_TK>(xlo, xhi);
                if (++it > SPIN_LIMIT) die(it);
            } while (c.x + c.y != gridDim.x / 2);
            t += (side ? c.x : c.y) - 32;
            side ^= 1;
            if (t >= 32) tickets_done(tk);
        }
#pragma unroll
        for (uint32_t r = 0; r < 2; r++)
            asm volatile("st.async.weak.shared::cluster.mbarrier::complete_tx::bytes.b32 [%0], %1, [%2];"
                         ::"r"(sb + SM_ROLE + (r << 24)), "r"(t * 4 + side * 2 + r), "r"(bq + BAR_RO + (r << 24)) : "memory");
    }
    __syncwarp();
    mbar_wait(bq + BAR_RO, 0);
    const uint32_t role = __reduce_max_sync(0xFFFFFFFFu, lds32(sb + SM_ROLE));
    if (role >= 128) return;
    const uint32_t h = role >> 2, j = role & 3;

    if (w >= 8) {
        asm volatile("setmaxnreg.dec.sync.aligned.u32 24;");
        const uint32_t u = w - 8;
        if (u == 3) {
#pragma unroll 1
            for (uint32_t c = 0; c < 16; c++) {
                if (c >= WIN) mbar_wait(bq + BAR_WF + (c - WIN) * 8, 0);
                if (l16 == 0) PG(16 + c);
                if (c == 12 + WOP) bsync<2, 64>();
                if (c >= 4 && c < 12 && c != 10) mbar_wait(bq + BAR_WE + (c - 4) * 8, 0);
                if (elect()) {
                    const uint32_t b = bq + BAR_WF + c * 8;
                    mbar_expect(b, 16384);
                    if (c >= 12) tma2d(sb + SM_WO + (c - 12) * WO_BOX, &tmo, b, j * 256 + (c - 12) * 64, h * 128);
                    else tma3d(c == 10 ? sb + SM_WV : sb + SM_ST + (c & 3) * 16384, c < 4 ? &tmq : c < 8 ? &tmk : &tmv, b, 0, j * 256 + ((c ^ (c >= 10)) & 3) * 64, h * 2);
                }
            }
#pragma unroll 1
            for (uint32_t c = 16 - WIN; c < 16; c++) mbar_wait(bq + BAR_WF + c * 8, 0);
            if (l16 == 0) PG(15);
        } else if (u == 0) {
            if (elect()) {
                mbar_expect(bq, 49152);
#pragma unroll 1
                for (uint32_t i = 0; i < 12; i++)
                    tma3d(sb + SM_X + (i < 4 ? i : i + 4) * 4096, &tmx, bq, 0, i < 8 ? i * 8 : (j ^ ((0xBD98u >> (i - 8) * 4) & 15)) * 8, j * 4);
            }
#pragma unroll 1
            for (int i = 0; i < 4; i++) xload(sb, i, j, -1, &tmx);
            bsync<3, 320>();
            if (l16 == 0) PG(32);
            g_arrive(xlo + XO_FL + h * 128, xhi, 4);
            if (WOP < 4) barv<2, 64>();
            if (l16 == 0) PG(33);
            g_wait(xlo + XO_FL + h * 128, xhi);
            if (l16 == 0) PG(34);
#pragma unroll 1
            for (int i = 0; i < 4; i++)
                if (elect()) kvload(sb, i, h, j, 0, xlo, xhi);
            mbar_wait(bq + BAR_KV, 0);
            if (l16 == 0) PG(14);
        } else if (u == 1) {
            bsync<8, 320>();
            asm volatile("fence.acq_rel.gpu;" ::: "memory");
        } else {
            GSYNC(0);
            mbar_wait(bq + BAR_WE + 48, 0);
#pragma unroll 1
            for (int e = 0; e < 16; e++) sts128(sb + SM_TR + 4096 + e * 512 + l16, 0, 0, 0, 0);
            barv<3, 320>();
            bsync<8, 320>();
#pragma unroll 1
            for (int i = 0; i < 4; i++) xload(sb, i, j, 0, &tmx);
        }
#pragma unroll 1
        for (int s = 0; s < nseg; s++) helper_step(sb, w, h, j, l16, xlo, xhi, zero, s, &tmx, &tmb);
        piwait(sb, 0, nseg - 2);
        bsync<9, 384>();
        GSYNC(1);
        if (w < 10) {
            uint32_t kb = 2;
            asm volatile("fence.proxy.async.shared::cta;" ::: "memory");
            if (w == 9) {
                g_arrive(xlo + XO_TK + 192, xhi, 128);
                PG(2);
                if (h >= 30) { g_wait(xlo + XO_TK + 192, xhi); kb = 0; }
                PG(3);
            } else delay_until(clk(), GD);
#pragma unroll 1
            for (; kb < 32; kb++) {
                if (kb >= 4) mbar_wait(bq + BAR_GE + (kb & 3) * 8, ((kb >> 2) & 1) ^ 1);
                g_load(sb, w - 8, role, kb, xlo, xhi, &tmb);
            }
        }
        if (role == 0 && w == 11 && elect()) tickets_done((uint32_t*)(((uint64_t)xhi << 32) | (xlo + XO_TK)));
    } else {
        asm volatile("setmaxnreg.inc.sync.aligned.u32 240;");
        uint32_t Wq[16][4], Wk[16][4], Wv[NA][4];
        uint32_t t16, KA, KB, KC, KD;
        {
            const uint32_t lane = l16 >> 4, g = lane >> 2, t = lane & 3;
            const uint32_t rw = (((lane >> 4) & 1) * 8 + (lane & 7)) * 128u;
            const uint32_t off = rw + ((((w & 3) * 2 + ((lane >> 3) & 1)) ^ (lane & 7)) << 4);
            const uint32_t offo = rw + ((((w & 1) * 4 + ((lane >> 3) & 1)) ^ (lane & 7)) << 4);
            const uint32_t r = 2 * (t & 1) + (g >> 2);
            const uint32_t mk0 = t < 2 ? 0 : (r == 0 ? 2 * g > w : j + r < 4), mk1 = t < 2 ? 0 : (r == 0 ? 2 * g + 1 > w : j + r < 4);
            t16 = __shfl_sync(0xFFFFFFFFu, w * 512 + l16, lane);
            KA = __shfl_sync(0xFFFFFFFFu, (w * 512 + t * 64 + g * 8) | ((w * 512 + (g & 1) * 256 + (g >> 1) * 64 + t * 16) << 16), lane);
            KB = __shfl_sync(0xFFFFFFFFu, ((w >> 2) * WV_BOX + off) | mk0 | (mk1 << 1) |
                                              ((w * 256 + (g >> 2) * 4096 + (g & 3) * 64 + t * 16) << 16), lane);
            KC = __shfl_sync(0xFFFFFFFFu, ((lane & 7) * 1280 + (lane >> 3) * 128 + ((w ^ (lane & 7)) << 4)) | (((t >> 1) * 16 + g * 2) << 16) | ((t * 64 + g * 8) << 24), lane);
            KD = __shfl_sync(0xFFFFFFFFu, ((w >> 1) * WO_BOX + offo) | (((lane & 7) * 208 + (lane >> 3) * 16) << 16), lane);
            if (threadIdx.x == 0) PG(8);
#define WTAKE(W, c, k0) { mbar_wait(bq + BAR_WF + (c) * 8, 0); \
                _Pragma("unroll") for (int ks = 0; ks < 4; ks++) ldsm4t(W[(k0) + ks], sb + SM_ST + ((c) & 3) * 16384 + (KB & 0xFFF0) + ks * 2048); \
                if ((c) < 8) { __syncwarp(); if (elect()) mbar_arrive(bq + BAR_WE + (c) * 8); } }
            if (w == 4) g_wait(xlo + XO_TK + 12, xhi);
#pragma unroll
            for (int c = 0; c < 4; c++) WTAKE(Wq, c, c * 4);
            mbar_wait(bq, 0);
            if (threadIdx.x == 0) PG(9);
            xstart<0>(sb, w, xlo + h * 24576, xhi, j, t16, KA, Wq);
            if (threadIdx.x == 0) PG(10);
#pragma unroll
            for (int c = 0; c < 4; c++) WTAKE(Wk, c + 4, c * 4);
            if (threadIdx.x == 0) PG(11);
            xstart<1>(sb, w, xlo + h * 24576, xhi, j, t16, KA, Wk);
            if (threadIdx.x == 0) PG(12);
            WTAKE(Wv, 8, 0);
            WTAKE(Wv, 9, 4);
            mbar_wait(bq + BAR_WF + 80, 0);
            WTAKE(Wv, 11, 8);
            if (threadIdx.x == 0) PG(13);
            xstart<2>(sb, w, xlo + h * 24576, xhi, j, t16, KA, Wv);
            mbar_wait(bq + BAR_XA, 0);
            bsync<8, 320>();
        }
        const uint32_t ONES = 0x3F803F80u;
#define UNI(x) __reduce_max_sync(0xFFFFFFFFu, x)
        uint32_t swi = UNI((uint32_t)((uint64_t)smem >> 32));
        const uint32_t sbw = UNI(sb + w * 256), sbm = UNI(sb - w * 512), sbs = UNI(sb + w * 768), sbp = UNI(sb + w * 208);
#define OPQALL() { OPQ(t16); OPQ(KA); OPQ(KB); OPQ(KC); OPQ(KD); }
        OPQALL();
        const uint32_t cb0 = (h >> 1) * 32768 + (j & 1) * 16384 + (h & 1) * 8192;
        const uint32_t cb = xlo + cb0 + ((par(cb0) ^ (j >> 1) ^ CFAR) << 12);
        const uint32_t uox = xlo + XO_OX + (h * 2 + (w >> 2)) * 16384 + j * 1024 + (w & 3) * 256 - w * 128;
        float ox[4];
        float4 dn;
#define OXSTORE(s) asm volatile("{\n.reg .b64 a;\nmov.b64 a, {%0,%1};\nst.global.u32 [a], %2;\nst.global.u32 [a+128], %3;\n}" \
                                ::"r"(uox + (t16 >> 2) + ((s) >> 2) * (1u << 20) + ((s) & 3) * 4096), "r"(xhi), \
                                  "r"(pack2(ox[0] * dn.y, ox[1] * dn.w)), "r"(pack2(ox[2] * dn.y, ox[3] * dn.w)) : "memory")
#pragma unroll 1
        for (int s2 = 0;; s2 += 2)
#pragma unroll
        for (int p = 0; p < 2; p++) {
            const int s = s2 + p;
            const uint32_t ctag = ((s2 >> 1) & 1) ^ 1;
            const uint32_t hb = cb ^ (p * 0x81000), rb = xlo + rpage(j, s);
            uint4 k0, k1;
            uint32_t qx0, qx1, ov0, ov1;
            {
                float xa[16], xb[16];
                uint4 m0, n0;
                uint32_t e0, f0, a = xlo + rpage(j, s - 1) + t16;
                uint32_t xp[8];
                wg_fence();
                XMMA(0, 6);
                SF();
                piwait(sb, p, s - 2);
                uint4 pi = xpeer<0>(sb, p ^ 1, t16);
                SF();
                wg_fence();
                XMMA(6, RPOS);
                XMMA(RPOS, RPOS + 4);
                wg_wait<1>();
                SF();
                PT(11);
                RLOAD(a);
                SF();
#define QPOS (RPOS >= 32 - NA ? RPOS : RPOS + 4 >= 32 - NA ? RPOS + 4 : 32 - NA)
                if (QPOS > RPOS) {
                    wg_fence();
                    if (QPOS > RPOS + 4) XMMA(RPOS + 4, QPOS);
                    XMMA(QPOS, QPOS + 4);
                    wg_wait<1>();
                    SF();
                }
                xpack<0>(xp, xa);
                xpark<0>(xp, pi, sb, sbw, p ^ 1, t16, KA);
                pi = xpeer<2>(sb, p ^ 1, t16);
                SF();
                if (QPOS + 4 < 32) {
                    wg_fence();
                    XMMA(QPOS + 4, 32);
                    SF();
                }
                wg_wait<0>();
                xpack<2>(xp, xb);
                xpark<2>(xp, pi, sb, sbw, p ^ 1, t16, KA);
                SF();
                PT(12);
                {
                    int it = 0;
                    while (ruse(sb + SM_MEMT + t16, m0, n0, e0, f0)) {
                        OPQ(a);
                        RLOAD(a);
                        if (++it > SPIN_LIMIT) die(it);
                    }
                    PC(22, it + 1);
                }
                PT(13);
                OPQ(KA); OPQ(t16);
                uint32_t acw = hb + (KA & 0xFFFF), ahi = xhi, tg = ctag;
                OPQ(acw); OPQ(ahi); OPQ(tg);
                SF();
                bsync<1, 384>();
                PT(0);
                uint32_t b[8][4];
#pragma unroll
                for (int i = 0; i < 8; i++) {
                    const int pp = i < 2 ? i : i ^ 1;
                    ldsm4t(b[pp], sbm + SM_MEMT + t16 + pp * 512);
                    if (i < 7) MF();
                }
                if (ASF) SF();
                float q[4], k[4];
                const uint32_t aWv = sb + SM_WV + (KB & 0xFFF0);
                uint32_t wv[16 - NA > 0 ? 16 - NA : 1][4];
#define WVLD(n0, n1) _Pragma("unroll") for (int n = (n0); n < (n1) && n < 16 - NA; n++) ldsm4t(wv[n], aWv + n * 2048)
#pragma unroll
                for (int ks = 0; ks < 16; ks++) {
                    const uint32_t b0 = b[ks >> 1][(ks & 1) * 2], b1 = b[ks >> 1][(ks & 1) * 2 + 1];
                    if (ks == 0) {
                        mma16z(q, Wq[0][0], Wq[0][1], Wq[0][2], Wq[0][3], b0, b1);
                        mma16z(k, Wk[0][0], Wk[0][1], Wk[0][2], Wk[0][3], b0, b1);
                    } else {
                        mma16(q, Wq[ks][0], Wq[ks][1], Wq[ks][2], Wq[ks][3], b0, b1);
                        mma16(k, Wk[ks][0], Wk[ks][1], Wk[ks][2], Wk[ks][3], b0, b1);
                    }
                    if (ks == 10 && VPF) { SF(); WVLD(0, VPF); }
                }
                const uint32_t oq0 = settag(pack2(q[0], q[2]), tg), oq1 = settag(pack2(q[1], q[3]), tg);
                const uint32_t ok0 = pack2(k[0], k[2]), ok1 = pack2(k[1], k[3]);
                stg2<XO_CQK>(acw, ahi, oq0, ok0);
                stg2<XO_CQK + 256>(acw, ahi, oq1, ok1);
                SF();
                PT(1);
                int nl = VPF;
#pragma unroll
                for (int rd = 0; rd < 8; rd++) {
                    const int pp = (VORD >> (28 - 4 * rd)) & 7;
                    const uint32_t* a = 2 * pp < NA ? Wv[2 * pp < NA ? 2 * pp : 0] : wv[2 * pp < NA ? 0 : 2 * pp - NA];
                    const uint32_t* c = 2 * pp < NA ? Wv[2 * pp < NA ? 2 * pp + 1 : 0] : wv[2 * pp < NA ? 0 : 2 * pp + 1 - NA];
                    if (rd == 0) {
                        mma16z(q, a[0], a[1], a[2], a[3], b[pp][0], b[pp][1]);
                        mma16z(k, c[0], c[1], c[2], c[3], b[pp][2], b[pp][3]);
                    } else {
                        mma16(q, a[0], a[1], a[2], a[3], b[pp][0], b[pp][1]);
                        mma16(k, c[0], c[1], c[2], c[3], b[pp][2], b[pp][3]);
                    }
                    if (rd == 0) {
                        SF();
                        OPQ(swi);
                        asm volatile("{\n.reg .b64 a;\nmov.b64 a, {%0,%1};\nst.v2.u32 [a], {%2,%3};\nst.v2.u32 [a+256], {%4,%5};\n}"
                                     ::"r"((KA & 0xFFF) + (sb ^ 0x1000000) + SM_TR + 4096 + p * 4096), "r"(swi), "r"(oq0), "r"(ok0), "r"(oq1), "r"(ok1) : "memory");
                        sts64(sb + SM_TR + (KA & 0xFFF), oq0, ok0);
                        sts64(sb + SM_TR + (KA & 0xFFF) + 256, oq1, ok1);
                    }
                    if (rd == 4) KEEP(t16, oq0, oq1, ok0, ok1);
                    if (nl < 16 - NA) {
                        SF();
                        WVLD(nl, nl + (2 * pp < NA ? 1 : 3));
                        nl += 2 * pp < NA ? 1 : 3;
                    } else if (nl < 32) {
                        SF();
                        k0 = lds128(sb + SM_KV + 2048 + (KB >> 16));
                        nl = 32;
                    } else if (nl == 32) {
                        SF();
                        k1 = lds128(sb + SM_KV + 10240 + (KB >> 16));
                        const uint4 qq = lds128(sbw + SM_KV + ((KA >> 16) & 0xFF));
                        qx0 = (t16 & 64) ? qq.y : qq.x;
                        qx1 = (t16 & 64) ? qq.w : qq.z;
                        nl = 33;
                    }
                }
                ov0 = pack2(q[0] + k[0], q[1] + k[1]);
                ov1 = pack2(q[2] + k[2], q[3] + k[3]);
                stg2<XO_CV>(xlo + ((p * 32 + h) * 4 + j) * 2048 + (t16 >> 1), xhi, settag(ov0, tg), ov1);
                barv<8, 384>();
            }
            OPQ(t16);
            SF();
            PT(2);
            PDUMP();
            {
                const uint32_t a0 = sb + SM_KV;
#define CLOADG() { c2 = ldg4<XO_CQK>((hb ^ 0x1000) + (KA >> 16), xhi); c3 = ldg4<XO_CQK>((hb ^ 0x5000) + (KA >> 16), xhi); }
#define CLOADS() { c0 = lds128(sb + SM_TR + (KA >> 16)); c1 = lds128(sb + SM_TR + 4096 + p * 4096 + (KA >> 16)); }
                uint4 c0, c1, c2, c3, pi;
                float xa[16], xb[16];
                uint32_t xp[8];
                wg_fence();
                XMMA(32, 32 + CPOS);
                XMMA(32 + CPOS, 36 + CPOS);
                wg_wait<1>();
                SF();
                CLOADG();
                SF();
                CLOADS();
                if (KPOS == 0) pi = xpeer<1>(sb, p ^ 1, t16);
                SF();
                wg_fence();
                XMMA(36 + CPOS, 48);
                SF();
                const uint32_t ka[4] = {k0.x, k0.y, k0.z, k0.w}, kb[4] = {k1.x, k1.y, k1.z, k1.w};
                const uint32_t aSp = sb + SM_SP + (KC & 0xFFFF);
                PT(3);
#define SCORES(FIRST) { \
                    const uint32_t qA = hadd2(hadd2(c0.x, c1.x), hadd2(c2.x, c3.x)), qB = hadd2(hadd2(c0.z, c1.z), hadd2(c2.z, c3.z)); \
                    const uint32_t kA = hadd2(hadd2(c0.y, c1.y), hadd2(c2.y, c3.y)), kB = hadd2(hadd2(c0.w, c1.w), hadd2(c2.w, c3.w)); \
                    bad = any_bad(or3(tagx2(c1.x, c1.z, ctag), tagx2(c2.x, c2.z, ctag), tagx2(c3.x, c3.z, ctag))); \
                    float sa[4], sb_[4], sc[4], sd[4], se[4]; \
                    if (FIRST) { SF(); wg_wait<0>(); } \
                    mma16z(sa, ka[0], ka[1], ka[2], ka[3], qA, qB); \
                    mma16z(sb_, kb[0], kb[1], kb[2], kb[3], qA, qB); \
                    mma16z(sc, qA, qx0, qB, qx1, kA, kB); \
                    if (FIRST) { \
                        xpack<1>(xp, xa); \
                        if (KPOS == 0) { xadd(xp, pi); xstore<1>(xp, sb, sbw, p ^ 1, t16, KA); barv<3, 384>(); } \
                        mma16z(sd, ka[0], ka[1], ka[2], ka[3], qx0, qx1); \
                        mma16z(se, kb[0], kb[1], kb[2], kb[3], qx0, qx1); \
                    } \
                    stsm4t(aSp, pack2(sa[0], sa[1]), pack2(sa[2], sa[3]), pack2(sb_[0], sb_[1]), pack2(sb_[2], sb_[3])); \
                    stsm2(aSp + 1024, pack2(sc[0], sc[1]), pack2(sc[2], sc[3])); \
                    if (FIRST) { \
                        stsm4t(aSp + 512, pack2(sd[0], sd[1]), pack2(sd[2], sd[3]), pack2(se[0], se[1]), pack2(se[2], se[3])); \
                        if (KPOS == 0) { KEEP(KD, xp[0], xp[1], xp[2], xp[3]); KEEP(KD, xp[4], xp[5], xp[6], xp[7]); } \
                    } }
                int it = 0;
                bool bad;
                SCORES(true);
                while (__builtin_expect(bad, 0)) {
                    OPQ(KA);
                    CLOADG();
                    CLOADS();
                    SCORES(false);
                    if (++it > SPIN_LIMIT) die(it);
                }
                PC(25, it);
                PT(4);
                bsync<4, 256>();
                uint32_t wo[16][4];
                const uint32_t aWo = sb + SM_WO + (KD & 0xFFFF), aWo1 = sb + SM_WO + ((KD & 0xFFFF) ^ 32);
#define WOLD(n0, n1) _Pragma("unroll") for (int n = (n0); n < (n1) && n < 16; n++) ldsm4t(wo[n], ((n & 1) ? aWo1 : aWo) + (n >> 1) * 2048)
                const bool hi = (t16 & 32) != 0;
                const uint32_t t8 = t16 >> 1;
                uint2 v0, v1, v2, v3;
                uint32_t es;
                {
                    uint32_t am[4], ax[4], a4[2];
                    const uint32_t aSr = sbs + SM_SP + t16;
                    ldsm4t(am, aSr);
                    ldsm4t(ax, aSr + 512);
                    ldsm2t(a4, aSr + 1024);
                    MF();
                    if (KPOS == 1) pi = xpeer<1>(sb, p ^ 1, t16);
                    const uint32_t se = (t16 & 128) ? 0u : ONES, so = se ^ ONES;
                    float hm[4], hx[4], h4[4];
                    mma16z(hm, am[0], am[1], am[2], am[3], se, so);
                    mma16z(hx, ax[0], ax[1], ax[2], ax[3], se, so);
                    mma8z(h4, a4[0], a4[1], ONES);
                    SF();
                    if (KPOS == 1) { xpark<1>(xp, pi, sb, sbw, p ^ 1, t16, KA); barv<3, 384>(); }
                    v0 = lds64(a0 + 4096 + t8); v1 = lds64(a0 + 8192 + t8); v2 = lds64(a0 + 12288 + t8); v3 = lds64(a0 + 16384 + t8);
                    WOLD(0, PF2);
                    float s0 = hi ? hx[0] : hm[0], s1 = hi ? hx[2] : hm[2];
                    const float s2 = hi ? h4[2] : h4[0];
                    s0 = (KB & 1) ? -1.0e9f * 11.313708499f : s0;
                    s1 = (KB & 2) ? -1.0e9f * 11.313708499f : s1;
                    int mi = __float_as_int(fmaxf(fmaxf(s0, s2), s1));
                    mi ^= (mi >> 31) & 0x7FFFFFFF;
                    const int mm = __reduce_max_sync(0xFFFFFFFFu, hi ? (int)0x80000000 : mi), mx = __reduce_max_sync(0xFFFFFFFFu, hi ? mi : (int)0x80000000);
                    SF();
                    WOLD(PF2, PF3);
                    SF();
                    mi = hi ? mx : mm;
                    mi ^= (mi >> 31) & 0x7FFFFFFF;
                    const float c2_ = 0.08838834764831845f * 1.4426950408889634f;
                    const float mc = __int_as_float(mi) * c2_;
                    const float e0 = ex2(fmaf(s0, c2_, -mc)), e1 = ex2(fmaf(s1, c2_, -mc)), e2 = ex2(fmaf(s2, c2_, -mc));
                    sts32(sbp + SM_P + (KC >> 25), pack2(e0, e1));
                    sts16(sbp + SM_P + 128 + ((KC >> 16) & 0xFF), pack2(e2, e2));
                    es = __float_as_uint(fmaf(e2, 0.5f, e0 + e1) + 64.f);
                }
                const uint32_t sm = __reduce_add_sync(0xFFFFFFFFu, hi ? 0u : es), sx = __reduce_add_sync(0xFFFFFFFFu, hi ? es : 0u);
                const uint32_t aPr = sb + SM_P + (KD >> 16);
                PT(5);
                bsync<5, 384>();
                uint32_t pm[4], px[4], p4[2];
                ldsm4(pm, aPr);
                MF();
                const uint2 vs = lds64(sb + SM_VS + t8);
                MF();
                ldsm2(p4, aPr + 128);
                MF();
                ldsm4(px, aPr + 64);
                MF();
                sts32f(sb + SM_DN + w * 8 + ((t16 >> 3) & 4), rcp(__uint_as_float((hi ? sx : sm) - 15u * 0x42800000u) - 64.f));
                MF();
                WOLD(PF3, NPF);
                const uint32_t vm0 = hadd2(ov0, vs.x), vm1 = hadd2(ov1, vs.y);
                float oa[4], ob[4];
                mma16z(oa, v0.x, v0.y, v1.x, v1.y, pm[0], pm[1]);
                mma16z(ob, v2.x, v2.y, v3.x, v3.y, pm[2], pm[3]);
                mma8(oa, vm0, vm1, p4[0]);
                stsm2(sbw + SM_OT + (t16 & 511), pack2(oa[0] + ob[0], oa[1] + ob[1]), pack2(oa[2] + ob[2], oa[3] + ob[3]));
                PT(6);
                SF();
                bsync<6, 256>();
                mma16z(ox, v0.x, v0.y, v1.x, v1.y, px[0], px[1]);
                uint32_t b[4][4];
#define OTLD(pp) ldsm4t(b[pp], sbm + SM_OT + t16 + (pp) * 512)
                OTLD(0);
                MF();
                OTLD(1);
                barv<7, 384>();
                mma16(ox, v2.x, v2.y, v3.x, v3.y, px[2], px[3]);
                mma8(ox, vm0, vm1, p4[1]);
                if (p == 1 && s + 1 == nseg) goto done;
                SF();
                uint32_t ar, ae, ahi = xhi;
                float r[2][4];
#pragma unroll
                for (int ks = 0; ks < 8; ks++) {
                    if (ks == 0) WOLD(NPF, NPF + WPF);
                    if (ks == OPOS) { OTLD(2); MF(); }
                    if (ks == OPOS + 2) { OTLD(3); MF(); }
                    if (ks > 0) WOLD(NPF + WPF + 2 * (ks - 1), NPF + WPF + 2 * ks);
                    if (ks == 5) {
                        OPQ(t16);
                        ar = rb + (h & 1) * 16384 + t16; ae = rb + (h & 1) * 1024 + (t16 >> 2);
                        OPQ(ar); OPQ(ahi); OPQ(ae);
                        dn = lds128f(sb + SM_DN + (t16 & 48));
                    }
#pragma unroll
                    for (int mt = 0; mt < 2; mt++) {
                        const int i = ks * 2 + mt;
                        const uint32_t* a = wo[i];
                        if (i < 2) mma16z(r[mt], a[0], a[1], a[2], a[3], b[ks >> 1][2 * (ks & 1)], b[ks >> 1][2 * (ks & 1) + 1]);
                        else mma16(r[mt], a[0], a[1], a[2], a[3], b[ks >> 1][2 * (ks & 1)], b[ks >> 1][2 * (ks & 1) + 1]);
                    }
                    if (NPF + WPF + 2 * ks < 16 || ks < 5) SF();
                }
                const float r0 = dn.x, r1 = dn.z;
                asm volatile("{\n.reg .b64 a;\nmov.b64 a, {%0,%2};\nred.relaxed.gpu.global.add.noftz.v4.bf16x2 [a], {%3,%4,%5,%6};\n"
                             "mov.b64 a, {%1,%2};\nred.relaxed.gpu.global.add.noftz.bf16x2 [a+32768], %7;\n}"
                             ::"r"(ar), "r"(ae), "r"(ahi), "r"(pack2(r[0][0] * r0, r[0][1] * r1)), "r"(pack2(r[0][2] * r0, r[0][3] * r1)),
                               "r"(pack2(r[1][0] * r0, r[1][1] * r1)), "r"(pack2(r[1][2] * r0, 1.f)), "r"(pack2(r[1][3] * r1, 1.f)) : "memory");
                barv<10, 384>();
            }
            SF();
            PT(10);
            OXSTORE(s);
            OPQALL();
        }
    done:
        dn = lds128f(sb + SM_DN + (t16 & 48));
        OXSTORE(nseg - 1);
        barv<9, 384>();
        g_main(sb, w, role, &tmy);
        if (threadIdx.x == 0) PG(0);
    }
}

template <int SC> DEVI void wg_rs128t(float (&d)[64], const uint32_t (&a)[4], uint64_t db) {
    if (SC) asm volatile("wgmma.mma_async.sync.aligned.m64n128k16.f32.bf16.bf16 "
        "{%0,%1,%2,%3,%4,%5,%6,%7,%8,%9,%10,%11,%12,%13,%14,%15,%16,%17,%18,%19,%20,%21,%22,%23,%24,%25,%26,%27,%28,%29,%30,%31,%32,%33,%34,%35,%36,%37,%38,%39,%40,%41,%42,%43,%44,%45,%46,%47,%48,%49,%50,%51,%52,%53,%54,%55,%56,%57,%58,%59,%60,%61,%62,%63}, "
        "{%64,%65,%66,%67}, %68, 1, 1, 1, 1;"
        : D4(+, 0), D4(+, 4), D4(+, 8), D4(+, 12), D4(+, 16), D4(+, 20), D4(+, 24), D4(+, 28), D4(+, 32), D4(+, 36), D4(+, 40), D4(+, 44), D4(+, 48), D4(+, 52), D4(+, 56), D4(+, 60) : "r"(a[0]), "r"(a[1]), "r"(a[2]), "r"(a[3]), "l"(db));
    else asm volatile("wgmma.mma_async.sync.aligned.m64n128k16.f32.bf16.bf16 "
        "{%0,%1,%2,%3,%4,%5,%6,%7,%8,%9,%10,%11,%12,%13,%14,%15,%16,%17,%18,%19,%20,%21,%22,%23,%24,%25,%26,%27,%28,%29,%30,%31,%32,%33,%34,%35,%36,%37,%38,%39,%40,%41,%42,%43,%44,%45,%46,%47,%48,%49,%50,%51,%52,%53,%54,%55,%56,%57,%58,%59,%60,%61,%62,%63}, "
        "{%64,%65,%66,%67}, %68, 0, 1, 1, 1;"
        : D4(=, 0), D4(=, 4), D4(=, 8), D4(=, 12), D4(=, 16), D4(=, 20), D4(=, 24), D4(=, 28), D4(=, 32), D4(=, 36), D4(=, 40), D4(=, 44), D4(=, 48), D4(=, 52), D4(=, 56), D4(=, 60) : "r"(a[0]), "r"(a[1]), "r"(a[2]), "r"(a[3]), "l"(db));
}
template <int SC> DEVI void wg_rs64t(float (&d)[32], const uint32_t (&a)[4], uint64_t db) {
    if (SC) asm volatile("wgmma.mma_async.sync.aligned.m64n64k16.f32.bf16.bf16 "
        "{%0,%1,%2,%3,%4,%5,%6,%7,%8,%9,%10,%11,%12,%13,%14,%15,%16,%17,%18,%19,%20,%21,%22,%23,%24,%25,%26,%27,%28,%29,%30,%31}, "
        "{%32,%33,%34,%35}, %36, 1, 1, 1, 1;"
        : D4(+, 0), D4(+, 4), D4(+, 8), D4(+, 12), D4(+, 16), D4(+, 20), D4(+, 24), D4(+, 28) : "r"(a[0]), "r"(a[1]), "r"(a[2]), "r"(a[3]), "l"(db));
    else asm volatile("wgmma.mma_async.sync.aligned.m64n64k16.f32.bf16.bf16 "
        "{%0,%1,%2,%3,%4,%5,%6,%7,%8,%9,%10,%11,%12,%13,%14,%15,%16,%17,%18,%19,%20,%21,%22,%23,%24,%25,%26,%27,%28,%29,%30,%31}, "
        "{%32,%33,%34,%35}, %36, 0, 1, 1, 1;"
        : D4(=, 0), D4(=, 4), D4(=, 8), D4(=, 12), D4(=, 16), D4(=, 20), D4(=, 24), D4(=, 28) : "r"(a[0]), "r"(a[1]), "r"(a[2]), "r"(a[3]), "l"(db));
}
template <int SC> DEVI void wg_rs40(float (&d)[20], const uint32_t (&a)[4], uint64_t db) {
    if (SC) asm volatile("wgmma.mma_async.sync.aligned.m64n40k16.f32.bf16.bf16 "
        "{%0,%1,%2,%3,%4,%5,%6,%7,%8,%9,%10,%11,%12,%13,%14,%15,%16,%17,%18,%19}, "
        "{%20,%21,%22,%23}, %24, 1, 1, 1, 0;"
        : D4(+, 0), D4(+, 4), D4(+, 8), D4(+, 12), D4(+, 16) : "r"(a[0]), "r"(a[1]), "r"(a[2]), "r"(a[3]), "l"(db));
    else asm volatile("wgmma.mma_async.sync.aligned.m64n40k16.f32.bf16.bf16 "
        "{%0,%1,%2,%3,%4,%5,%6,%7,%8,%9,%10,%11,%12,%13,%14,%15,%16,%17,%18,%19}, "
        "{%20,%21,%22,%23}, %24, 0, 1, 1, 0;"
        : D4(=, 0), D4(=, 4), D4(=, 8), D4(=, 12), D4(=, 16) : "r"(a[0]), "r"(a[1]), "r"(a[2]), "r"(a[3]), "l"(db));
}
template <int SC> DEVI void wg_rs8(float (&d)[4], const uint32_t (&a)[4], uint64_t db) {
    if (SC) asm volatile("wgmma.mma_async.sync.aligned.m64n8k16.f32.bf16.bf16 "
        "{%0,%1,%2,%3}, "
        "{%4,%5,%6,%7}, %8, 1, 1, 1, 0;"
        : D4(+, 0) : "r"(a[0]), "r"(a[1]), "r"(a[2]), "r"(a[3]), "l"(db));
    else asm volatile("wgmma.mma_async.sync.aligned.m64n8k16.f32.bf16.bf16 "
        "{%0,%1,%2,%3}, "
        "{%4,%5,%6,%7}, %8, 0, 1, 1, 0;"
        : D4(=, 0) : "r"(a[0]), "r"(a[1]), "r"(a[2]), "r"(a[3]), "l"(db));
}
template <int SC> DEVI void wg_ss64a(float (&d)[32], uint64_t da, uint64_t db) {
    if (SC) asm volatile("wgmma.mma_async.sync.aligned.m64n64k16.f32.bf16.bf16 "
        "{%0,%1,%2,%3,%4,%5,%6,%7,%8,%9,%10,%11,%12,%13,%14,%15,%16,%17,%18,%19,%20,%21,%22,%23,%24,%25,%26,%27,%28,%29,%30,%31}, "
        "%32, %33, 1, 1, 1, 1, 0;"
        : D4(+, 0), D4(+, 4), D4(+, 8), D4(+, 12), D4(+, 16), D4(+, 20), D4(+, 24), D4(+, 28) : "l"(da), "l"(db));
    else asm volatile("wgmma.mma_async.sync.aligned.m64n64k16.f32.bf16.bf16 "
        "{%0,%1,%2,%3,%4,%5,%6,%7,%8,%9,%10,%11,%12,%13,%14,%15,%16,%17,%18,%19,%20,%21,%22,%23,%24,%25,%26,%27,%28,%29,%30,%31}, "
        "%32, %33, 0, 1, 1, 1, 0;"
        : D4(=, 0), D4(=, 4), D4(=, 8), D4(=, 12), D4(=, 16), D4(=, 20), D4(=, 24), D4(=, 28) : "l"(da), "l"(db));
}

#define G_ROWS 514
__device__ uint4 g_G[64 * G_ROWS * 8];
__device__ uint4 g_GN[64 * 8];
__device__ uint4 g_WN[1152];
#define FS_F2 196608
#define FS_TB (FS_F2 + 8192)
#define FS_NQ (FS_TB + 16384)
#define FS_BAR (FS_NQ + 128)
#define FS_NY (FS_NQ + 1024 + 128)
#define FS_TOTAL (FS_NQ + 3072)
#define F_THREADS 512

DEVI uint32_t cis(int j) {
    const float a = fmaf(__uint_as_float((((j + 1024) << 12) & 0x7FF000) | 0x3F800000), 6.283185307179586f, -9.42477796076938f);
    return pack2(__cosf(a), __sinf(a));
}
DEVI uint32_t cos2(int j0, int j1) {
    const float f = 6.283185307179586f / 2048.f;
    return pack2(__cosf((float)(((j0 + 1024) & 2047) - 1024) * f), __cosf((float)(((j1 + 1024) & 2047) - 1024) * f));
}
DEVI void twid(int j, float& c, float& s) {
    const float a = (float)(((j + 512) & 1023) - 512) * (6.283185307179586f / 1024.f);
    c = __cosf(a) * (1.f / 1024.f);
    s = __sinf(a) * (1.f / 1024.f);
}
template <bool B> struct Bool { static constexpr bool v = B; };
DEVI uint32_t opq(uint32_t& x, uint32_t zero) { OPQ(x); return x; }
DEVI uint32_t tidx() { uint32_t r; asm volatile("mov.u32 %0, %%tid.x;" : "=r"(r)); return r; }
DEVI void tma4d(uint32_t dst, const CUtensorMap* tm, uint32_t bar, int c0, int c1, int c2, int c3) {
    asm volatile("cp.async.bulk.tensor.4d.shared::cluster.global.mbarrier::complete_tx::bytes [%0], [%1, {%3, %4, %5, %6}], [%2];"
                 ::"r"(dst), "l"(tm), "r"(bar), "r"(c0), "r"(c1), "r"(c2), "r"(c3) : "memory");
}
DEVI void tma3s(const CUtensorMap* tm, uint32_t src, int c0, int c1, int c2) {
    asm volatile("cp.async.bulk.tensor.3d.global.shared::cta.bulk_group [%0, {%2, %3, %4}], [%1];" ::"l"(tm), "r"(src), "r"(c0), "r"(c1), "r"(c2) : "memory");
}
DEVI void tma4s(const CUtensorMap* tm, uint32_t src, int c0, int c1, int c2, int c3) {
    asm volatile("cp.async.bulk.tensor.4d.global.shared::cta.bulk_group [%0, {%2, %3, %4, %5}], [%1];"
                 ::"l"(tm), "r"(src), "r"(c0), "r"(c1), "r"(c2), "r"(c3) : "memory");
}
DEVI void bulk_commit() { asm volatile("cp.async.bulk.commit_group;" ::: "memory"); }
DEVI void fence_async() { asm volatile("fence.proxy.async;" ::: "memory"); }
DEVI void fence_smem() { asm volatile("fence.proxy.async.shared::cta;" ::: "memory"); }
DEVI void wgbar(uint32_t q) { asm volatile("bar.sync %0, 128;" ::"r"(q + 2) : "memory"); }
DEVI void grid_arrive(uint32_t* c, uint32_t n) { asm volatile("fence.proxy.async;\nred.release.gpu.global.inc.u32 [%0], %1;" ::"l"(c), "r"(n - 1) : "memory"); }
DEVI void grid_wait(uint32_t* c) {
    uint32_t v;
    int it = 0;
    do {
        asm volatile("ld.acquire.gpu.global.u32 %0, [%1];" : "=r"(v) : "l"(c) : "memory");
        if (++it > (1 << 22)) die(it);
    } while (v);
    fence_async();
}

template <bool INV, class S1, class S2>
DEVI void fft_rows(uint32_t grp, uint32_t q, const uint32_t (&F)[2][4], const float (&tc)[8], const float (&ts)[8], uint32_t so, float fx, uint32_t nq,
                   S1 sh1, S2 sh2) {
    float d[64];
    const uint64_t db = INV ? mkdesc(grp, 1024, 2048) : (mkdesc(grp, 2048, 512) ^ ((uint64_t)3 << 62));
    wg_fence();
    wg_rs128t<0>(d, F[0], db);
    wg_rs128t<1>(d, F[1], db + (INV ? 256 : 64));
    wg_commit();
    SF();
    sh1();
    float4 ny;
    if (INV) ny = lds128f(nq);
    wg_wait<0>();
    if (INV) { d[0] = fmaf(fx, ny.x, d[0]); d[16] = fmaf(fx, ny.y, d[16]); d[32] = fmaf(fx, ny.z, d[32]); d[48] = fmaf(fx, ny.w, d[48]); }
    uint32_t a[2][4][4];
    float e[2][INV ? 16 : 20];
    const uint64_t df = mkdesc(SB0 + FS_F2, 16, 1024);
#pragma unroll
    for (int s = 0; s < 2; s++) {
#pragma unroll
        for (int i = 0; i < 4; i++)
#pragma unroll
            for (int h = 0; h < 2; h++) {
                const float* x = d + (2 * s + h) * 16 + i * 4;
                a[s][i][h] = pack2(fmaf(x[2], ts[2 * i], x[0] * tc[2 * i]), fmaf(x[3], ts[2 * i + 1], x[1] * tc[2 * i + 1]));
                a[s][i][h + 2] = pack2(fmaf(-x[0], ts[2 * i], x[2] * tc[2 * i]), fmaf(-x[1], ts[2 * i + 1], x[3] * tc[2 * i + 1]));
            }
        wg_fence();
#pragma unroll
        for (int i = 0; i < 4; i++) {
            if constexpr (INV) { if (i == 0) wg_rs32<0>(e[s], a[s][i], df); else wg_rs32<1>(e[s], a[s][i], df + i * 2); }
            else { if (i == 0) wg_rs40<0>(e[s], a[s][i], df); else wg_rs40<1>(e[s], a[s][i], df + i * 2); }
        }
        wg_commit();
    }
    SF();
    sh2();
#pragma unroll
    for (int s = 0; s < 2; s++) {
        if (s == 0) wg_wait<1>(); else wg_wait<0>();
        float* x = e[s];
        if constexpr (!INV) {
            x[0] *= fx; x[1] *= fx; x[2] *= fx; x[3] *= fx;
            if (fx != 1.f) sts64(nq + s * 8, pack2(x[16], 0.f), pack2(x[18], 0.f));
        }
        const uint32_t o = grp + (INV ? so + s * 4096 : so ^ (s * 576));
#pragma unroll
        for (int b = 0; b < 2; b++)
            stsm4t(o + b * (INV ? 1024 : 4096), pack2(x[8 * b], x[8 * b + 1]), pack2(x[8 * b + 2], x[8 * b + 3]), pack2(x[8 * b + 4], x[8 * b + 5]),
                   pack2(x[8 * b + 6], x[8 * b + 7]));
    }
}

template <bool INV>
DEVI void fft_gen(uint32_t a, uint32_t n2) {
    const uint32_t tid = tidx(), x = ((tid >> 4) & 24) + (tid & 3), o = (tid & 4) * 128;
    if (INV) {
        const uint32_t r = (tid & 64) * 16 + (tid & 16) * 32 + (tid & 40) * 8 + n2;
        sts128(a + tid * 16, cis(o - r * x), cis(o - (r + 128) * x), cis(o - r * (x + 4)), cis(o - (r + 128) * (x + 4)));
    } else {
        const uint32_t r = 64 * x + n2, k = ((tid >> 2) & 24) + ((tid >> 3) & 3);
        sts128(a + tid * 16, cis(r * k + o), cis(r * (k + 4) + o), cis((r + 256) * k + o), cis((r + 256) * (k + 4) + o));
    }
}
template <bool INV, class S1>
DEVI void fft_cross(uint32_t buf, uint32_t q, uint32_t fa, uint32_t so, uint32_t nq, float (&n)[4], S1 sh1) {
    uint32_t F[4][4];
#pragma unroll
    for (int s = 0; s < 4; s++) { const uint4 v = lds128(fa + s * 2048); F[s][0] = v.x; F[s][1] = v.y; F[s][2] = v.z; F[s][3] = v.w; }
    float d[64];
    const uint64_t db = mkdesc(buf + q * 2048, 1024, 8192), dn = mkdesc(nq, 16, 1024);
    wg_fence();
#pragma unroll
    for (int s = 0; s < 4; s++) { if (s == 0) wg_rs128t<0>(d, F[s], db); else wg_rs128t<1>(d, F[s], db + s * 1024); }
#pragma unroll
    for (int s = 0; s < 4; s++) { if (s == 0) wg_rs8<0>(n, F[s], dn); else wg_rs8<1>(n, F[s], dn + s * 2); }
    wg_commit();
    SF();
    sh1();
    wg_wait<0>();
#pragma unroll
    for (int b = 0; b < 8; b++) {
        const uint32_t o = INV ? so ^ ((b >> 1) * 288 ^ (b & 1) * 32) : (so ^ ((b & 3) * 32)) + (b >> 2) * 1024;
        stsm4(buf + o, pack2(d[8 * b], d[8 * b + 1]), pack2(d[8 * b + 2], d[8 * b + 3]), pack2(d[8 * b + 4], d[8 * b + 5]), pack2(d[8 * b + 6], d[8 * b + 7]));
    }
}

template <bool ODD>
DEVI void fft_filter(uint32_t aw, const float (&e)[32], const float (&o)[32], uint32_t (&u)[4][4], uint32_t (&v)[4][4]) {
#pragma unroll
    for (int s = 0; s < 4; s++) {
        float y[2][2][4];
#pragma unroll
        for (int c = 0; c < 2; c++) {
            float f[4][2];
#pragma unroll
            for (int i = 0; i < 4; i++) {
                const uint32_t a = aw + (i * 32 + s * 8 + c) * 144, x = lds32(a);
                f[i][0] = ODD ? hi_f(x) : lo_f(x);
                f[i][1] = ODD ? lo_f(lds32(a + 4)) : hi_f(x);
            }
#pragma unroll
            for (int h = 0; h < 2; h++) {
                const int x = 8 * s + 2 * h + c;
                const float ar = e[x] + o[x], ai = e[x + 4] + o[x + 4], br = e[x] - o[x], bi = e[x + 4] - o[x + 4];
                const float yr = fmaf(-ai, f[2][h], ar * f[0][h]), yi = fmaf(ar, f[2][h], ai * f[0][h]);
                y[h][c][0] = fmaf(-bi, f[3][h], fmaf(br, f[1][h], yr));
                y[h][c][1] = fmaf(br, f[3][h], fmaf(bi, f[1][h], yi));
                y[h][c][2] = fmaf(2.f, yr, -y[h][c][0]);
                y[h][c][3] = fmaf(2.f, yi, -y[h][c][1]);
            }
        }
#pragma unroll
        for (int h = 0; h < 2; h++) {
            u[s][h] = pack2(y[h][0][0], y[h][1][0]); u[s][h + 2] = pack2(y[h][0][1], y[h][1][1]);
            v[s][h] = pack2(y[h][0][2], y[h][1][2]); v[s][h + 2] = pack2(y[h][0][3], y[h][1][3]);
        }
    }
}

__global__ void __launch_bounds__(F_THREADS, 1)
post_kernel(const __grid_constant__ CUtensorMap tmx, const __grid_constant__ CUtensorMap tmg1, const __grid_constant__ CUtensorMap tmg2,
           const __grid_constant__ CUtensorMap tmwr, const __grid_constant__ CUtensorMap tmwi, const __grid_constant__ CUtensorMap tmy,
           const bf16* __restrict__ wr, const bf16* __restrict__ wi, uint32_t* cnt, uint32_t zero, int nw) {
    extern __shared__ __align__(1024) uint8_t smem[];
    const uint32_t sb = SB0;
    if (smem_u32(smem) != sb) die(1 << 23);
    const uint32_t tid = threadIdx.x, lane = tid & 31, g = lane >> 2, t = lane & 3, j8 = lane & 7, mat = lane >> 3;
    const uint32_t wi_ = __reduce_max_sync(0xFFFFFFFFu, tid >> 5), q = wi_ >> 2, w = wi_ & 3;
    const int cta = blockIdx.x;
    const int nt = cta < 64 ? (64 - cta + nw - 1) / nw : 0;
    const uint32_t bar = sb + FS_BAR;
    if (tid == 0) {
        for (int i = 0; i < 30; i++) mbar_init(bar + i * 8, i < 3 ? 4 : i < 6 ? 16 : i >= 14 && i < 18 ? 2 : 1);
        asm volatile("fence.mbarrier_init.release.cluster;" ::: "memory");
        fence_smem();
    }
    __syncthreads();
#define FT(n)
    FT(0);
#define N2(p) (2 * ((p) & 31) + ((p) >> 5))
#define WLOAD(tk, part) { \
        const uint32_t wd_ = sb + 131072 + q * 18432 + (part) * 9216, wb_ = bar + 112 + q * 8; \
        mbar_expect(wb_, 9216); \
        if ((tk) < 256) tma3d(wd_, (part) ? &tmwi : &tmwr, wb_, ((tk) & 63) * 64, (tk) >> 6, 0); \
        else asm volatile("cp.async.bulk.shared::cluster.global.mbarrier::complete_tx::bytes [%0], [%1], 9216, [%2];" \
                          ::"r"(wd_), "l"(g_WN + (part) * 576), "r"(wb_) : "memory"); }
#define GROW(tk) ((tk) < 256 ? ((tk) >> 5) * 64 + ((tk) & 7) * 8 + (((tk) >> 3) & 3) * 2 : 512)
#define DLOAD(tk, sl) { mbar_expect(bar + 48 + (sl) * 8, 16384); tma3d(sb + (sl) * 16384, &tmg2, bar + 48 + (sl) * 8, 0, GROW(tk), 0); }
#define IO(c) if (w == 3 && (c) && elect())
#define XLOAD1(i, bb) { const uint32_t xb_ = bar + 144 + (bb) * 32 + q * 8; mbar_expect(xb_, 16384); tma4d(sb + (bb) * 65536 + q * 16384, &tmx, xb_, 0, 0, q * 8, N2(cta + (i) * nw)); }
#define GLOAD3(i, bb) { mbar_expect(bar + (bb) * 8, q ? 16384 : 16512); tma3d(sb + (bb) * 65536 + q * 16384, &tmg1, bar + (bb) * 8, 0, q * 128, cta + (i) * nw); \
        if (q == 0) asm volatile("cp.async.bulk.shared::cluster.global.mbarrier::complete_tx::bytes [%0], [%1], 128, [%2];" \
                                 ::"r"(sb + FS_NQ + (bb) * 1024), "l"(g_GN + (cta + (i) * nw) * 8), "r"(bar + (bb) * 8) : "memory"); }
    for (int i = 0; i < 3; i++) IO(i < nt) XLOAD1(i, i);
    for (uint32_t x = tid; x < 40 * 32; x += 512) {
        const uint32_t n = x >> 5, m2 = mat * 8 + t * 2, ri = g & 1;
        const uint32_t c2 = ((n >> 1) & 1) + ((n >> 3) & 1) * 2 + (n & 4) + (n >> 4) * 8;
        const uint32_t v = cos2(m2 * c2 * 64 + ((n & 1) - ri) * 512, (m2 + 1) * c2 * 64 + ((n & 1) - ri) * 512);
        sts32(sb + FS_F2 + n * 128 + ((g ^ (n & 7)) << 4) + t * 4, n < 32 ? v : n == 32 && ri == 0 ? 0xBF003F00u : 0u);
    }
    float tc[8], ts[8];
    uint32_t F[2][4];
    uint32_t c1 = 16 * (w >> 1) + 2 * g + (w & 1);
#pragma unroll
    for (int i = 0; i < 8; i++) {
        twid(c1 * (8 * (i >> 1) + 2 * t + (i & 1)), tc[i], ts[i]);
        const uint32_t m1 = (i >> 1) * 8 + 2 * t;
        F[i >> 2][i & 3] = cos2(c1 * m1 * 64 + (i & 1) * 512, c1 * (m1 + 1) * 64 + (i & 1) * 512);
    }
    {
        const uint32_t kr = (2 * (mat & 1) + (j8 & 1)) ^ ((j8 >> 2) << 1);
        const uint32_t so1 = ((mat >> 1) + 2 * (j8 >> 2)) * 1024 + kr * 128 + (((((j8 >> 1) & 1) * 4 + w) ^ kr) << 4);
        const uint32_t so2 = (2 * w + (mat & 1)) * 8192 + q * 2048 + j8 * 128 + (((mat >> 1) ^ j8) << 4);
        uint32_t so = so1 << 16 | so2;
        const float fx = (tid & 127) == 0 ? 0.5f : 1.f;
        fft_gen<false>(sb + FS_TB, N2(cta));
        fence_smem();
        bsync<1, 512>();
        FT(1);
        int b = 0, bp = 2, ph = 0;
        if (nt) mwait(bar + 144 + q * 8, 0);
        __syncwarp();
        auto step = [&](auto first, auto last, const int i) {
            const uint32_t p = cta + i * nw, bn = 3 - b - bp, tb = (i & 1) * 8192;
            const uint32_t grp = sb + b * 65536 + q * 16384, nq = sb + FS_NQ + b * 1024 + q * 32;
            auto sa = [&]() {
                if constexpr (!decltype(first)::v) {
                    fence_smem();
                    __syncwarp();
                    if (elect()) mbar_arrive(bar + 24);
                }
                IO(i > 1) {
                    mwait(bar + 32, i & 1);
                    tma3s(&tmg1, sb + bn * 65536 + q * 16384, 0, q * 128, p - 2 * nw);
                    bulk_commit();
                }
            };
            auto sb_ = [&]() { if constexpr (!decltype(first)::v) mwait(bar + 24, (i - 1) & 1); };
            if constexpr (!decltype(last)::v) fft_rows<false>(grp, q, F, tc, ts, opq(so, zero) >> 16, fx, nq, sa, sb_);
            else { sa(); __syncwarp(); sb_(); __syncwarp(); }
            if constexpr (!decltype(first)::v) {
                float n[4];
                fft_cross<false>(sb + bp * 65536, q, sb + FS_TB + 8192 - tb + (((tidx() & 127) ^ (q & 1)) << 4), opq(so, zero) & 0xFFFF, sb + FS_NQ + bp * 1024, n, [&]() {
                    fft_gen<false>(sb + FS_TB + tb, N2(p));
                    IO(i >= 2 && i + 1 < nt) {
                        asm volatile("cp.async.bulk.wait_group.read 0;" ::: "memory");
                        XLOAD1(i + 1, bn);
                    }
                });
                if (q == 0) {
                    const uint32_t x = tidx();
                    bf16* z = (bf16*)(g_G + ((p - nw) * G_ROWS + 512) * 8) + (x & 4) * 16 + ((x >> 2) & 24) + ((x >> 3) & 3);
                    asm volatile("{\n.reg .pred p;\n.reg .b16 a, b;\nsetp.eq.u32 p, %2, 0;\nmov.b32 {a, b}, %1;\n@p st.global.u16 [%0], a;\n@p st.global.u16 [%0+8], b;\n}"
                                 ::"l"(z), "r"(pack2(n[0], n[2])), "r"(x & 3) : "memory");
                }
            }
            if constexpr (!decltype(last)::v) {
                fft_rows<false>(grp + 8192, q, F, tc, ts, opq(so, zero) >> 16, fx, nq + 16, [&]() {
                    if constexpr (!decltype(first)::v) {
                        fence_smem();
                        __syncwarp();
                        if (elect()) mbar_arrive(bar + 32);
                    }
                    if ((w == 1 || w == 2) && elect())
                        asm volatile("cp.async.bulk.prefetch.L2.global [%0], 8208;" ::"l"((w == 1 ? wr : wi) + (p * 4 + q) * 4104) : "memory");
                }, [&]() { if (i + 1 < nt) mwait(bar + 144 + bn * 32 + q * 8, bn ? ph : ph ^ 1); });
                bp = b;
                if (++b == 3) { b = 0; ph ^= 1; }
            }
        };
        if (nt) {
            step(Bool<true>(), Bool<false>(), 0);
#pragma unroll 1
            for (int i = 1; i < nt; i++) step(Bool<false>(), Bool<false>(), i);
            step(Bool<false>(), Bool<true>(), nt);
        }
        for (uint32_t x = cta * 512 + tid; x < 4096; x += nw * 512)
            ((bf16*)g_WN)[(x >> 5) * 72 + (x & 16) + (x & 7) * 2 + ((x >> 3) & 1)] = (x < 2048 ? wr : wi)[(x & 2047) * 513 + 512];
        FT(2);
        fence_async();
        bsync<1, 512>();
        IO(nt) { tma3s(&tmg1, sb + bp * 65536 + q * 16384, 0, q * 128, cta + (nt - 1) * nw); bulk_commit(); }
    }
    for (uint32_t x = tid; x < 128 * 32; x += 512) {
        const uint32_t n = (x >> 5) & 63, a = x & 31, k2 = (n >> 4) * 8 + (n & 7);
        sts32(sb + FS_TB + (x >> 5) * 128 + (((a >> 2) ^ (n & 7)) << 4) + (a & 3) * 4, cis((2 * a + (x >> 11)) * k2 * 32 + (n & 8) * 64));
    }
    fence_smem();
    bsync<1, 512>();
    IO(true) {
        asm volatile("cp.async.bulk.wait_group 0;" ::: "memory");
        grid_arrive(cnt, 4 * nw);
        grid_wait(cnt);
        const int tk = cta + q * nw;
        if (tk <= 256) { DLOAD(tk, q); WLOAD(tk, 0); WLOAD(tk, 1); }
    }
    __syncwarp();
    {
        const uint32_t lo = j8 * 128 + (((2 * w + (mat & 1)) ^ j8) << 4);
        const uint32_t aw = sb + 131072 + q * 18432 + t * 288 + w * 32 + g * 4;
        const uint64_t df = mkdesc(sb + FS_TB, 16, 1024);
        const uint64_t da = mkdesc(sb + q * 16384, 16, 1024);
        const uint32_t buf = sb + 65536 + q * 16384;
        int i = 0, tk = cta + q * nw;
        if (tk <= 256) mwait(bar + 48 + q * 8, 0);
        FT(3);
#pragma unroll 1
        for (; tk <= 256; tk += 4 * nw, i++) {
            const bool more = tk + 4 * nw <= 256;
            float e[32], o[32];
            wg_fence();
#pragma unroll
            for (int s = 0; s < 4; s++) { if (s == 0) wg_ss64a<0>(e, da, df); else wg_ss64a<1>(e, da + s * 128, df + s * 2); }
#pragma unroll
            for (int s = 0; s < 4; s++) { if (s == 0) wg_ss64a<0>(o, da + 512, df + 512); else wg_ss64a<1>(o, da + 512 + s * 128, df + 512 + s * 2); }
            wg_commit();
            SF();
            if (i > 0) {
                fence_smem();
                wgbar(q);
                IO(true) { tma3s(&tmg2, buf, 0, GROW(tk - 4 * nw), 0); bulk_commit(); }
            }
            if (w == 2 && more && elect()) mbar_expect(bar + 48 + q * 8, 16384);
            const int gr = GROW(tk + 4 * nw);
            mwait(bar + 112 + q * 8, i & 1);
            wg_wait<0>();
            if (w == 2 && more && elect()) tma3d(sb + q * 16384, &tmg2, bar + 48 + q * 8, 0, gr, 0);
            uint32_t u[4][4], v[4][4];
            if (tk & 8) fft_filter<true>(aw + (tk & 48) / 4, e, o, u, v);
            else fft_filter<false>(aw + (tk & 48) / 4, e, o, u, v);
            wg_fence();
#pragma unroll
            for (int s = 0; s < 4; s++) { if (s == 0) wg_rs64t<0>(e, u[s], df); else wg_rs64t<1>(e, u[s], df + s * 128); }
#pragma unroll
            for (int s = 0; s < 4; s++) { if (s == 0) wg_rs64t<0>(o, v[s], df + 512); else wg_rs64t<1>(o, v[s], df + 512 + s * 128); }
            wg_commit();
            SF();
            IO(true) asm volatile("cp.async.bulk.wait_group.read 0;" ::: "memory");
            wgbar(q);
            if (more) {
                if ((w == 1 || w == 2) && elect()) WLOAD(tk + 4 * nw, w - 1);
                mwait(bar + 48 + q * 8, (i + 1) & 1);
            }
            wg_wait<0>();
#pragma unroll
            for (int s = 0; s < 4; s++) {
                const uint32_t a = buf + (mat >> 1) * 1024 + lo + s * 2048;
                stsm4t(a, pack2(e[8 * s], e[8 * s + 1]), pack2(e[8 * s + 2], e[8 * s + 3]), pack2(e[8 * s + 4], e[8 * s + 5]), pack2(e[8 * s + 6], e[8 * s + 7]));
                stsm4t(a + 8192, pack2(o[8 * s], o[8 * s + 1]), pack2(o[8 * s + 2], o[8 * s + 3]), pack2(o[8 * s + 4], o[8 * s + 5]), pack2(o[8 * s + 6], o[8 * s + 7]));
            }
            if (tk == 256 && w < 2) {
                uint32_t* z = (uint32_t*)g_GN + t * 32 + w * 16 + g;
#pragma unroll
                for (int s = 0; s < 16; s++) {
                    z[(s >> 1) * 128 + (s & 1) * 8] = pack2(e[2 * s], e[2 * s + 1]);
                    z[(s >> 1) * 128 + (s & 1) * 8 + 1024] = pack2(o[2 * s], o[2 * s + 1]);
                }
                fence_async();
            }
        }
        fence_smem();
        wgbar(q);
        IO(true) {
            if (i > 0) { tma3s(&tmg2, buf, 0, GROW(tk - 4 * nw), 0); bulk_commit(); }
            asm volatile("cp.async.bulk.wait_group 0;" ::: "memory");
            grid_arrive(cnt + 1, 4 * nw);
        }
    }
    FT(4);
    bsync<1, 512>();
    {
        for (uint32_t n = wi_; n < 32; n += 16) {
            const uint32_t cl = (mat >> 1) * 16 + t * 4 + (mat & 1), mh = ((n >> 3) & 1) + (n & 7) * 2 + (n & 16);
            sts32(sb + FS_F2 + n * 128 + ((g ^ (n & 7)) << 4) + t * 4, cos2(cl * mh * 64 + (g & 1) * 512, (cl + 2) * mh * 64 + (g & 1) * 512));
        }
        fence_smem();
        c1 = 8 * w + g;
#pragma unroll
        for (int i = 0; i < 8; i++) {
            twid(-c1 * (16 * (i >> 2) + 4 * t + 2 * (i & 1) + ((i >> 1) & 1)), tc[i], ts[i]);
            F[i >> 2][i & 3] = cis((i & 1) * 512 - c1 * ((i >> 1) * 4 + (t ^ (q & 1))) * 64);
        }
        const uint32_t kr = (j8 & 1) ^ ((j8 >> 2) << 1);
        const uint32_t so2 = ((w >> 1) * 4 + (j8 >> 2) * 2 + (w & 1)) * 8192 + (2 * q + (mat & 1)) * 1024 + kr * 128 + (((((j8 >> 1) & 1) * 4 + (mat >> 1)) ^ kr) << 4);
        const uint32_t so1 = (mat & 1) * 2048 + j8 * 128 + ((((mat >> 1) * 4 + w) ^ j8) << 4);
        uint32_t so = so1 << 16 | so2;
        const float fx = t ? 0.f : (g & 1) ? -1.f : 1.f;
        fft_gen<true>(sb + FS_TB, N2(cta));
        bsync<1, 512>();
        IO(true) grid_wait(cnt + 1);
        for (int i = 0; i < 3; i++) IO(i < nt) GLOAD3(i, i);
        __syncwarp();
        int b = 0, bp = 2, ph = 0;
        auto step = [&](auto first, auto last, const int i) {
            const uint32_t p = cta + i * nw, bn = 3 - b - bp, tb = (i & 1) * 8192;
            const uint32_t grp = sb + bp * 65536 + q * 16384, ny = sb + FS_NY + bp * 128 + q * 32;
            auto sb_ = [&]() { if constexpr (!decltype(last)::v) mwait(bar + b * 8, ph); };
            if constexpr (!decltype(first)::v) {
                fft_rows<true>(grp, q, F, tc, ts, opq(so, zero) >> 16, fx, ny, [&]() {
                    if (i > 1) {
                        fence_smem();
                        wgbar(q);
                        IO(true) { tma4s(&tmy, sb + bn * 65536 + q * 16384, 0, 0, q * 8, N2(p - 2 * nw)); bulk_commit(); }
                    }
                }, sb_);
            } else { sb_(); __syncwarp(); }
            if constexpr (decltype(first)::v) FT(5);
            if constexpr (!decltype(last)::v) {
                float n[4];
                fft_cross<true>(sb + b * 65536, q, sb + FS_TB + tb + (tidx() & 127) * 16, opq(so, zero) & 0xFFFF, sb + FS_NQ + b * 1024, n, [&]() {
                    fft_gen<true>(sb + FS_TB + 8192 - tb, N2(p + nw));
                    IO(i >= 2 && i + 1 < nt) {
                        asm volatile("cp.async.bulk.wait_group.read 0;" ::: "memory");
                        GLOAD3(i + 1, bn);
                    }
                });
                if (q == 0) {
                    const uint32_t x = tidx(), a = sb + FS_NY + b * 128 + (x & 64) + (x & 16) * 2 + ((x & 40) >> 1);
                    if ((x & 7) == 0) { sts32f(a, n[0]); sts32f(a + 8, n[2]); }
                }
            }
            auto sc = [&]() {
                if constexpr (!decltype(last)::v) {
                    fence_smem();
                    __syncwarp();
                    if (elect()) mbar_arrive(bar + 24);
                }
            };
            auto sd = [&]() { if constexpr (!decltype(last)::v) mwait(bar + 24, (nt + i) & 1); };
            if constexpr (!decltype(first)::v) fft_rows<true>(grp + 8192, q, F, tc, ts, opq(so, zero) >> 16, fx, ny + 16, sc, sd);
            else { sc(); __syncwarp(); sd(); __syncwarp(); }
            if constexpr (!decltype(last)::v) {
                bp = b;
                if (++b == 3) { b = 0; ph ^= 1; }
            }
        };
        if (nt) {
            step(Bool<true>(), Bool<false>(), 0);
#pragma unroll 1
            for (int i = 1; i < nt; i++) step(Bool<false>(), Bool<false>(), i);
            step(Bool<false>(), Bool<true>(), nt);
        }
        fence_smem();
        wgbar(q);
        IO(nt) { tma4s(&tmy, sb + bp * 65536 + q * 16384, 0, 0, q * 8, N2(cta + (nt - 1) * nw)); bulk_commit(); }
        FT(6);
        IO(true) asm volatile("cp.async.bulk.wait_group 0;" ::: "memory");
    }
}

typedef CUresult (*EncodeFn)(CUtensorMap*, CUtensorMapDataType, cuuint32_t, void*, const cuuint64_t*, const cuuint64_t*,
                             const cuuint32_t*, const cuuint32_t*, CUtensorMapInterleave, CUtensorMapSwizzle,
                             CUtensorMapL2promotion, CUtensorMapFloatOOBfill);

static void make_map(EncodeFn enc, CUtensorMap* m, const void* ptr, int rank, const cuuint64_t* dims, const cuuint64_t* strides,
                     const cuuint32_t* box, CUtensorMapSwizzle sw = CU_TENSOR_MAP_SWIZZLE_128B) {
    cuuint32_t es[4] = {1, 1, 1, 1};
    CUresult r = enc(m, CU_TENSOR_MAP_DATA_TYPE_BFLOAT16, rank, (void*)ptr, dims, strides, box, es, CU_TENSOR_MAP_INTERLEAVE_NONE,
                     sw, CU_TENSOR_MAP_L2_PROMOTION_L2_256B, CU_TENSOR_MAP_FLOAT_OOB_FILL_NONE);
    if (r != CUDA_SUCCESS) fprintf(stderr, "tensor map encode failed: %d\n", (int)r);
}

extern "C" void kernel_launch(void* const* d_in, const int* in_sizes, int n_in, void* d_out, int out_size) {
    const bf16* A_x = (const bf16*)d_in[0];
    const bf16* A_mem0 = (const bf16*)d_in[1];
    const bf16* A_Wq = (const bf16*)d_in[2];
    const bf16* A_Wk = (const bf16*)d_in[3];
    const bf16* A_Wv = (const bf16*)d_in[4];
    const bf16* A_Wo = (const bf16*)d_in[5];
    const bf16* B_x = (const bf16*)d_in[7];
    const bf16* B_wr = (const bf16*)d_in[8];
    const bf16* B_wi = (const bf16*)d_in[9];
    bf16* out = (bf16*)d_out;

    static EncodeFn enc = nullptr;
    static void *pxs = nullptr, *pg = nullptr;
    static int ncl = 64;
    if (!enc) {
        cudaDriverEntryPointQueryResult qr;
        void* fn = nullptr;
        cudaGetDriverEntryPoint("cuTensorMapEncodeTiled", &fn, cudaEnableDefault, &qr);
        enc = (EncodeFn)fn;
        cudaFuncSetAttribute(chain_kernel, cudaFuncAttributeMaxDynamicSharedMemorySize, SM_TOTAL);
        cudaFuncSetAttribute(post_kernel, cudaFuncAttributeMaxDynamicSharedMemorySize, FS_TOTAL);
        cudaGetSymbolAddress(&pxs, g_xs);
        cudaGetSymbolAddress(&pg, g_G);
        cudaLaunchConfig_t lc = {};
        cudaLaunchAttribute at;
        at.id = cudaLaunchAttributeClusterDimension;
        at.val.clusterDim.x = 2; at.val.clusterDim.y = 1; at.val.clusterDim.z = 1;
        lc.gridDim = dim3(132); lc.blockDim = dim3(384); lc.dynamicSmemBytes = SM_TOTAL; lc.attrs = &at; lc.numAttrs = 1;
        int nc = 0;
        if (cudaOccupancyMaxActiveClusters(&nc, chain_kernel, &lc) == cudaSuccess && nc > 64) ncl = nc < 66 ? nc : 66;
    }
    CUtensorMap tmq, tmk, tmv, tmo, tmx, tmb, tmy;
    {
        cuuint64_t d[3] = {64, DM, HD / 64}, st[2] = {HD * 2, 128};
        cuuint32_t bx[3] = {64, 64, 2};
        make_map(enc, &tmq, A_Wq, 3, d, st, bx);
        make_map(enc, &tmk, A_Wk, 3, d, st, bx);
        make_map(enc, &tmv, A_Wv, 3, d, st, bx);
    }
    {
        cuuint64_t d[2] = {DM, HD}, st[1] = {DM * 2};
        cuuint32_t bx[2] = {64, 16}, bx1[2] = {64, 128}, bx2[3] = {64, 64, 2};
        make_map(enc, &tmo, A_Wo, 2, d, st, bx1);
        cuuint64_t d2[3] = {64, HD, DM / 64}, st2[2] = {DM * 2, 128}, d3[2] = {DM, SEQ}, st3[1] = {DM * 4};
        make_map(enc, &tmb, A_Wo, 3, d2, st2, bx2);
        make_map(enc, &tmy, out, 2, d3, st3, bx);
    }
    {
        cuuint64_t d[3] = {64, SEQ, DM / 64}, st[2] = {DM * 2, 128};
        cuuint32_t bx[3] = {64, 8, 4};
        make_map(enc, &tmx, A_x, 3, d, st, bx);
    }
    CUtensorMap fx, fg1, fg2, fwr, fwi, fy;
    {
        cuuint64_t d[4] = {32, 32, 32, 64}, st[3] = {64, 64 * DM * 2, DM * 2};
        cuuint32_t bx[4] = {32, 32, 8, 1};
        make_map(enc, &fx, B_x, 4, d, st, bx, CU_TENSOR_MAP_SWIZZLE_64B);
        cuuint64_t d2[4] = {64, 16, 32, 64}, st2[3] = {128, 64 * 4096, 4096};
        cuuint32_t bx2[4] = {64, 16, 8, 1};
        make_map(enc, &fy, out + DM, 4, d2, st2, bx2);
    }
    {
        cuuint64_t d[3] = {64, G_ROWS, 64}, st[2] = {128, G_ROWS * 128};
        cuuint32_t bx[3] = {64, 128, 1}, bx2[3] = {64, 2, 64};
        make_map(enc, &fg1, pg, 3, d, st, bx);
        make_map(enc, &fg2, pg, 3, d, st, bx2);
        cuuint64_t d2[3] = {8 * 513, 4, 64}, st2[2] = {8 * 513 * 2, 32 * 513 * 2};
        cuuint32_t bx3[3] = {72, 1, 64};
        make_map(enc, &fwr, B_wr, 3, d2, st2, bx3, CU_TENSOR_MAP_SWIZZLE_NONE);
        make_map(enc, &fwi, B_wi, 3, d2, st2, bx3, CU_TENSOR_MAP_SWIZZLE_NONE);
    }
    cudaStream_t st = cudaStreamPerThread;
    const uint64_t xs = ((uint64_t)pxs + XS_BYTES - 1) & ~(uint64_t)(XS_BYTES - 1);
    chain_kernel<<<2 * ncl, 384, SM_TOTAL, st>>>(tmq, tmk, tmv, tmo, tmx, tmb, tmy, A_mem0, A_x, (uint32_t)xs, (uint32_t)(xs >> 32), 0u, NSEG);
    int nw = ncl == 66 ? 4 : 64;
    cudaLaunchConfig_t lc = {};
    cudaLaunchAttribute at;
    at.id = cudaLaunchAttributeProgrammaticStreamSerialization;
    at.val.programmaticStreamSerializationAllowed = 1;
    lc.gridDim = dim3(nw); lc.blockDim = dim3(F_THREADS); lc.dynamicSmemBytes = FS_TOTAL; lc.stream = st; lc.attrs = &at; lc.numAttrs = 1;
    cudaLaunchKernelEx(&lc, post_kernel, fx, fg1, fg2, fwr, fwi, fy, B_wr, B_wi, (uint32_t*)(xs + XO_TK + 256), 0u, nw);
}
```

```cpp
#include <cuda_runtime.h>
#include <cuda_bf16.h>
#include <cuda.h>
#include <stdint.h>
#include <stdio.h>

typedef __nv_bfloat16 bf16;

#define SEQ 2048
#define DM 1024
#define NH 32
#define DH 128
#define NSEG 64
#define HD (NH * DH)

#define XS_BYTES (32u << 20)
__device__ uint4 g_xs[2 * XS_BYTES / 16];
#define XO_R 0u
#define XO_PB (1u << 18)
#define XO_FL (XO_PB + 16384u)
#define XO_TK (XO_FL + 4096u)
#define XO_CQK (1u << 20)
#define XO_CV (2u << 20)
#define XO_XG (4u << 20)
#define XO_OX (16u << 20)
#define GSYNC(n)
#define PG(n)

#define DEVI __device__ __forceinline__

DEVI void die(int it) { asm volatile("st.shared.u32 [%0], %0;" ::"r"(it) : "memory"); }
DEVI uint32_t smem_u32(const void* p) { return (uint32_t)__cvta_generic_to_shared(p); }
DEVI void mbar_init(uint32_t bar, uint32_t cnt) { asm volatile("mbarrier.init.shared::cta.b64 [%0], %1;" ::"r"(bar), "r"(cnt) : "memory"); }
DEVI void mbar_expect(uint32_t bar, uint32_t bytes) { asm volatile("mbarrier.arrive.expect_tx.shared::cta.b64 _, [%0], %1;" ::"r"(bar), "r"(bytes) : "memory"); }
DEVI void mbar_arrive(uint32_t bar) { asm volatile("mbarrier.arrive.shared::cta.b64 _, [%0];" ::"r"(bar) : "memory"); }
DEVI void mbar_wait(uint32_t bar, uint32_t parity) {
    uint32_t done;
    int it = 0;
    do {
        asm volatile("{\n.reg .pred p;\nmbarrier.try_wait.parity.shared::cta.b64 p, [%1], %2;\nselp.u32 %0, 1, 0, p;\n}\n"
                     : "=r"(done) : "r"(bar), "r"(parity) : "memory");
        if (++it > (1 << 22)) die(it);
    } while (!done);
}
DEVI void tma2d(uint32_t dst, const CUtensorMap* tm, uint32_t bar, int c0, int c1) {
    asm volatile("cp.async.bulk.tensor.2d.shared::cluster.global.mbarrier::complete_tx::bytes [%0], [%1, {%3, %4}], [%2];"
                 ::"r"(dst), "l"(tm), "r"(bar), "r"(c0), "r"(c1) : "memory");
}
DEVI void tma3d(uint32_t dst, const CUtensorMap* tm, uint32_t bar, int c0, int c1, int c2) {
    asm volatile("cp.async.bulk.tensor.3d.shared::cluster.global.mbarrier::complete_tx::bytes [%0], [%1, {%3, %4, %5}], [%2];"
                 ::"r"(dst), "l"(tm), "r"(bar), "r"(c0), "r"(c1), "r"(c2) : "memory");
}
DEVI void bulk_g2s(uint32_t dst, uint32_t lo, uint32_t hi, uint32_t bytes, uint32_t bar) {
    asm volatile("{\n.reg .b64 a;\nmov.b64 a, {%1,%2};\ncp.async.bulk.shared::cluster.global.mbarrier::complete_tx::bytes [%0], [a], %3, [%4];\n}"
                 ::"r"(dst), "r"(lo), "r"(hi), "r"(bytes), "r"(bar) : "memory");
}
DEVI void bulk_s2g(uint32_t lo, uint32_t hi, uint32_t src, uint32_t bytes) {
    asm volatile("{\n.reg .b64 a;\nmov.b64 a, {%0,%1};\ncp.async.bulk.global.shared::cta.bulk_group [a], [%2], %3;\ncp.async.bulk.commit_group;\n}"
                 ::"r"(lo), "r"(hi), "r"(src), "r"(bytes) : "memory");
}
DEVI void bulk_red(uint32_t lo, uint32_t hi, uint32_t src, uint32_t bytes) {
    asm volatile("{\n.reg .b64 a;\nmov.b64 a, {%0,%1};\ncp.reduce.async.bulk.global.shared::cta.bulk_group.add.noftz.bf16 [a], [%2], %3;\ncp.async.bulk.commit_group;\n}"
                 ::"r"(lo), "r"(hi), "r"(src), "r"(bytes) : "memory");
}
DEVI bool elect() {
    uint32_t p;
    asm volatile("{\n.reg .pred P;\nelect.sync _|P, 0xFFFFFFFF;\nselp.u32 %0, 1, 0, P;\n}" : "=r"(p));
    return p != 0;
}
DEVI void ldsm4(uint32_t (&r)[4], uint32_t a) {
    asm volatile("ldmatrix.sync.aligned.m8n8.x4.shared.b16 {%0,%1,%2,%3}, [%4];" : "=r"(r[0]), "=r"(r[1]), "=r"(r[2]), "=r"(r[3]) : "r"(a) : "memory");
}
DEVI void ldsm4t(uint32_t (&r)[4], uint32_t a) {
    asm volatile("ldmatrix.sync.aligned.m8n8.x4.trans.shared.b16 {%0,%1,%2,%3}, [%4];" : "=r"(r[0]), "=r"(r[1]), "=r"(r[2]), "=r"(r[3]) : "r"(a) : "memory");
}
DEVI void ldsm2t(uint32_t (&r)[2], uint32_t a) {
    asm volatile("ldmatrix.sync.aligned.m8n8.x2.trans.shared.b16 {%0,%1}, [%2];" : "=r"(r[0]), "=r"(r[1]) : "r"(a) : "memory");
}
DEVI void ldsm2(uint32_t (&r)[2], uint32_t a) {
    asm volatile("ldmatrix.sync.aligned.m8n8.x2.shared.b16 {%0,%1}, [%2];" : "=r"(r[0]), "=r"(r[1]) : "r"(a) : "memory");
}
DEVI void stsm4t(uint32_t a, uint32_t r0, uint32_t r1, uint32_t r2, uint32_t r3) {
    asm volatile("stmatrix.sync.aligned.m8n8.x4.trans.shared.b16 [%0], {%1,%2,%3,%4};" ::"r"(a), "r"(r0), "r"(r1), "r"(r2), "r"(r3) : "memory");
}
DEVI uint32_t ldsm1(uint32_t a) {
    uint32_t r;
    asm volatile("ldmatrix.sync.aligned.m8n8.x1.shared.b16 {%0}, [%1];" : "=r"(r) : "r"(a) : "memory");
    return r;
}
DEVI void stsm4(uint32_t a, uint32_t r0, uint32_t r1, uint32_t r2, uint32_t r3) {
    asm volatile("stmatrix.sync.aligned.m8n8.x4.shared.b16 [%0], {%1,%2,%3,%4};" ::"r"(a), "r"(r0), "r"(r1), "r"(r2), "r"(r3) : "memory");
}
DEVI void stsm2(uint32_t a, uint32_t r0, uint32_t r1) {
    asm volatile("stmatrix.sync.aligned.m8n8.x2.shared.b16 [%0], {%1,%2};" ::"r"(a), "r"(r0), "r"(r1) : "memory");
}
DEVI uint32_t movm(uint32_t a) {
    uint32_t d;
    asm volatile("movmatrix.sync.aligned.m8n8.trans.b16 %0, %1;" : "=r"(d) : "r"(a));
    return d;
}
DEVI void mma16(float (&d)[4], uint32_t a0, uint32_t a1, uint32_t a2, uint32_t a3, uint32_t b0, uint32_t b1) {
    asm volatile("mma.sync.aligned.m16n8k16.row.col.f32.bf16.bf16.f32 {%0,%1,%2,%3}, {%4,%5,%6,%7}, {%8,%9}, {%0,%1,%2,%3};"
                 : "+f"(d[0]), "+f"(d[1]), "+f"(d[2]), "+f"(d[3]) : "r"(a0), "r"(a1), "r"(a2), "r"(a3), "r"(b0), "r"(b1));
}
DEVI void mma16z(float (&d)[4], uint32_t a0, uint32_t a1, uint32_t a2, uint32_t a3, uint32_t b0, uint32_t b1) {
    asm volatile("mma.sync.aligned.m16n8k16.row.col.f32.bf16.bf16.f32 {%0,%1,%2,%3}, {%4,%5,%6,%7}, {%8,%9}, {%10,%10,%10,%10};"
                 : "=f"(d[0]), "=f"(d[1]), "=f"(d[2]), "=f"(d[3]) : "r"(a0), "r"(a1), "r"(a2), "r"(a3), "r"(b0), "r"(b1), "f"(0.f));
}
DEVI void mma8(float (&d)[4], uint32_t a0, uint32_t a1, uint32_t b0) {
    asm volatile("mma.sync.aligned.m16n8k8.row.col.f32.bf16.bf16.f32 {%0,%1,%2,%3}, {%4,%5}, {%6}, {%0,%1,%2,%3};"
                 : "+f"(d[0]), "+f"(d[1]), "+f"(d[2]), "+f"(d[3]) : "r"(a0), "r"(a1), "r"(b0));
}
DEVI void mma8z(float (&d)[4], uint32_t a0, uint32_t a1, uint32_t b0) {
    asm volatile("mma.sync.aligned.m16n8k8.row.col.f32.bf16.bf16.f32 {%0,%1,%2,%3}, {%4,%5}, {%6}, {%7,%7,%7,%7};"
                 : "=f"(d[0]), "=f"(d[1]), "=f"(d[2]), "=f"(d[3]) : "r"(a0), "r"(a1), "r"(b0), "f"(0.f));
}
DEVI uint32_t pack2(float lo, float hi) {
    uint32_t r;
    asm("cvt.rn.bf16x2.f32 %0, %1, %2;" : "=r"(r) : "f"(hi), "f"(lo));
    return r;
}
DEVI uint32_t hadd2(uint32_t a, uint32_t b) {
    uint32_t r;
    asm("add.rn.bf16x2 %0, %1, %2;" : "=r"(r) : "r"(a), "r"(b));
    return r;
}
DEVI float lo_f(uint32_t x) { return __uint_as_float(x << 16); }
DEVI float hi_f(uint32_t x) { return __uint_as_float(x & 0xFFFF0000u); }
template <uint32_t OFF> DEVI uint4 ldg4(uint32_t lo, uint32_t hi) {
    uint4 v;
    asm volatile("{\n.reg .b64 a;\nmov.b64 a, {%4,%5};\nld.relaxed.gpu.global.v4.u32 {%0,%1,%2,%3}, [a+%6];\n}"
                 : "=r"(v.x), "=r"(v.y), "=r"(v.z), "=r"(v.w) : "r"(lo), "r"(hi), "n"(OFF) : "memory");
    return v;
}
template <uint32_t OFF> DEVI uint2 ldg2(uint32_t lo, uint32_t hi) {
    uint2 v;
    asm volatile("{\n.reg .b64 a;\nmov.b64 a, {%2,%3};\nld.relaxed.gpu.global.v2.u32 {%0,%1}, [a+%4];\n}"
                 : "=r"(v.x), "=r"(v.y) : "r"(lo), "r"(hi), "n"(OFF) : "memory");
    return v;
}
template <uint32_t OFF> DEVI uint32_t ldg1(uint32_t lo, uint32_t hi) {
    uint32_t v;
    asm volatile("{\n.reg .b64 a;\nmov.b64 a, {%1,%2};\nld.relaxed.gpu.global.u32 %0, [a+%3];\n}" : "=r"(v) : "r"(lo), "r"(hi), "n"(OFF) : "memory");
    return v;
}
template <uint32_t OFF> DEVI void stg1(uint32_t lo, uint32_t hi, uint32_t a) {
    asm volatile("{\n.reg .b64 a;\nmov.b64 a, {%0,%1};\nst.relaxed.gpu.global.u32 [a+%3], %2;\n}" ::"r"(lo), "r"(hi), "r"(a), "n"(OFF) : "memory");
}
template <uint32_t OFF> DEVI void stg4(uint32_t lo, uint32_t hi, uint32_t a, uint32_t b, uint32_t c, uint32_t d) {
    asm volatile("{\n.reg .b64 a;\nmov.b64 a, {%0,%1};\nst.relaxed.gpu.global.v4.u32 [a+%6], {%2,%3,%4,%5};\n}"
                 ::"r"(lo), "r"(hi), "r"(a), "r"(b), "r"(c), "r"(d), "n"(OFF) : "memory");
}
template <uint32_t OFF> DEVI void stg2(uint32_t lo, uint32_t hi, uint32_t a, uint32_t b) {
    asm volatile("{\n.reg .b64 a;\nmov.b64 a, {%0,%1};\nst.relaxed.gpu.global.v2.u32 [a+%4], {%2,%3};\n}"
                 ::"r"(lo), "r"(hi), "r"(a), "r"(b), "n"(OFF) : "memory");
}
DEVI uint32_t tagx2(uint32_t a, uint32_t b, uint32_t t) { uint32_t r; asm("lop3.b32 %0, %1, %2, %3, 0x7E;" : "=r"(r) : "r"(a), "r"(b), "r"(t)); return r; }
DEVI uint32_t tagx1(uint32_t a, uint32_t b, uint32_t t) { uint32_t r; asm("lop3.b32 %0, %1, %2, %3, 0xF6;" : "=r"(r) : "r"(a), "r"(b), "r"(t)); return r; }
DEVI uint32_t or3(uint32_t a, uint32_t b, uint32_t c) { uint32_t r; asm("lop3.b32 %0, %1, %2, %3, 0xFE;" : "=r"(r) : "r"(a), "r"(b), "r"(c)); return r; }
DEVI bool any_bad(uint32_t x) { return __any_sync(0xFFFFFFFFu, (x & 1u) != 0); }
DEVI uint32_t settag(uint32_t x, uint32_t tag) { return (x & ~1u) | tag; }
DEVI void sts32f(uint32_t a, float v) { asm volatile("st.shared.f32 [%0], %1;" ::"r"(a), "f"(v) : "memory"); }
DEVI void sts32(uint32_t a, uint32_t v) { asm volatile("st.shared.u32 [%0], %1;" ::"r"(a), "r"(v) : "memory"); }
DEVI void sts16(uint32_t a, uint32_t v) { asm volatile("st.shared.u16 [%0], %1;" ::"r"(a), "h"((unsigned short)v) : "memory"); }
DEVI void sts64(uint32_t a, uint32_t x, uint32_t y) { asm volatile("st.shared.v2.u32 [%0], {%1,%2};" ::"r"(a), "r"(x), "r"(y) : "memory"); }
DEVI void sts128(uint32_t a, uint32_t x, uint32_t y, uint32_t z, uint32_t w) {
    asm volatile("st.shared.v4.u32 [%0], {%1,%2,%3,%4};" ::"r"(a), "r"(x), "r"(y), "r"(z), "r"(w) : "memory");
}
DEVI float4 lds128f(uint32_t a) {
    float4 v;
    asm volatile("ld.shared.v4.f32 {%0,%1,%2,%3}, [%4];" : "=f"(v.x), "=f"(v.y), "=f"(v.z), "=f"(v.w) : "r"(a) : "memory");
    return v;
}
DEVI uint4 lds128(uint32_t a) {
    uint4 v;
    asm volatile("ld.shared.v4.u32 {%0,%1,%2,%3}, [%4];" : "=r"(v.x), "=r"(v.y), "=r"(v.z), "=r"(v.w) : "r"(a) : "memory");
    return v;
}
DEVI uint2 lds64(uint32_t a) {
    uint2 v;
    asm volatile("ld.shared.v2.u32 {%0,%1}, [%2];" : "=r"(v.x), "=r"(v.y) : "r"(a) : "memory");
    return v;
}
DEVI uint32_t lds32(uint32_t a) {
    uint32_t v;
    asm volatile("ld.shared.u32 %0, [%1];" : "=r"(v) : "r"(a) : "memory");
    return v;
}
DEVI float ex2(float x) { float r; asm("ex2.approx.ftz.f32 %0, %1;" : "=f"(r) : "f"(x)); return r; }
DEVI float rcp(float x) { float r; asm("rcp.approx.ftz.f32 %0, %1;" : "=f"(r) : "f"(x)); return r; }
DEVI uint32_t clk() { uint32_t c; asm volatile("mov.u32 %0, %%clock;" : "=r"(c)::"memory"); return c; }

DEVI uint64_t mkdesc(uint32_t addr, uint32_t lbo, uint32_t sbo) {
    return (uint64_t)((addr & 0x3FFFF) >> 4) | ((uint64_t)(lbo >> 4) << 16) | ((uint64_t)(sbo >> 4) << 32) | ((uint64_t)1 << 62);
}
DEVI void wg_fence() { asm volatile("wgmma.fence.sync.aligned;" ::: "memory"); }
DEVI void wg_commit() { asm volatile("wgmma.commit_group.sync.aligned;" ::: "memory"); }
template <int N> DEVI void wg_wait() { asm volatile("wgmma.wait_group.sync.aligned %0;" ::"n"(N) : "memory"); }
template <int SC>
DEVI void wg_rs32(float (&d)[16], const uint32_t (&a)[4], uint64_t db) {
    if (SC) {
        asm volatile("wgmma.mma_async.sync.aligned.m64n32k16.f32.bf16.bf16 "
                     "{%0,%1,%2,%3,%4,%5,%6,%7,%8,%9,%10,%11,%12,%13,%14,%15}, {%16,%17,%18,%19}, %20, 1, 1, 1, 0;"
                     : "+f"(d[0]), "+f"(d[1]), "+f"(d[2]), "+f"(d[3]), "+f"(d[4]), "+f"(d[5]), "+f"(d[6]), "+f"(d[7]),
                       "+f"(d[8]), "+f"(d[9]), "+f"(d[10]), "+f"(d[11]), "+f"(d[12]), "+f"(d[13]), "+f"(d[14]), "+f"(d[15])
                     : "r"(a[0]), "r"(a[1]), "r"(a[2]), "r"(a[3]), "l"(db));
    } else {
        asm volatile("wgmma.mma_async.sync.aligned.m64n32k16.f32.bf16.bf16 "
                     "{%0,%1,%2,%3,%4,%5,%6,%7,%8,%9,%10,%11,%12,%13,%14,%15}, {%16,%17,%18,%19}, %20, 0, 1, 1, 0;"
                     : "=f"(d[0]), "=f"(d[1]), "=f"(d[2]), "=f"(d[3]), "=f"(d[4]), "=f"(d[5]), "=f"(d[6]), "=f"(d[7]),
                       "=f"(d[8]), "=f"(d[9]), "=f"(d[10]), "=f"(d[11]), "=f"(d[12]), "=f"(d[13]), "=f"(d[14]), "=f"(d[15])
                     : "r"(a[0]), "r"(a[1]), "r"(a[2]), "r"(a[3]), "l"(db));
    }
}

#define NA 12
#define NPF 6
#define PF1 2
#define PF2 2
#define PF3 5
#define WPF 2
#define VPF 2
#define VORD (NA == 12 ? 0x01234567 : NA == 10 ? 0x50123467 : NA == 8 ? 0x40125367 : 0x30142567)
#define WV_BOX ((16 - NA) * 2048)
#define WO_BOX 16384
#define SM_WV 0
#define SM_WO (2 * WV_BOX)
#define SM_X (SM_WO + 4 * WO_BOX)
#define SM_XO (SM_X + 32768)
#define SM_MEMT (SM_XO + 12288)
#define SM_OT (SM_MEMT + 4096)
#define SM_VS (SM_OT + 2048)
#define SM_P (SM_VS + 2048)
#define SM_DN (SM_P + 1792)
#define SM_PROF (SM_P + 2048)
#define SM_ST (SM_X + 65536)
#define SM_KV SM_ST
#define SM_SP (SM_KV + 18432)
#define SM_TR (SM_ST + 32768)
#define SM_PI (SM_ST + 65536)
#define SM_BAR (SM_PI + 12288)
#define SM_TOTAL (SM_BAR + 512)
static_assert(NA == 12, "start-up chunks");
static_assert(SM_TOTAL <= 232448, "smem");
#define BAR_XA 32
#define BAR_KV 40
#define BAR_PI 48
#define BAR_RO 64
#define BAR_WF 256
#define BAR_WE 384
#define SM_ROLE (SM_BAR + 72)

#define SPIN_LIMIT (1 << 20)
#define RPOS 24
#define OPOS 2
#define ASF 0
#define KPOS 0
#define CPOS 1
#define DLY_V 400
#define NPRB 3
#define XPF 1
#define WOP 2
#define WIN 2
#define EPD 1300
#define ASP 4
#define EPF 0
#define CFAR 1

template <int ID, int N> DEVI void bsync() { asm volatile("bar.sync %0, %1;" ::"n"(ID), "n"(N) : "memory"); }
template <int ID, int N> DEVI void barv() { asm volatile("bar.arrive %0, %1;" ::"n"(ID), "n"(N) : "memory"); }

#define PT(n)
#define PC(n, v)
#define PDUMP()
#define REFRESH() asm volatile("xor.b32 %0, %0, %1;" : "+r"(l16) : "r"(zero))
#define OPQ(x) asm volatile("xor.b32 %0, %0, %1;" : "+r"(x) : "r"(zero))
#define KEEP(x, a, b, c, d) asm volatile("{\n.reg .b32 t;\nlop3.b32 t, %1, %2, %3, 0x80;\nlop3.b32 t, t, %4, %5, 0x80;\nxor.b32 %0, %0, t;\n}" \
                                         : "+r"(x) : "r"(a), "r"(b), "r"(c), "r"(d), "r"(zero))
#define SF() asm volatile("pmevent 1;" ::: "memory")
#define MF() __syncwarp()
#define SB0 1024u

#define XDOFF(ks) ((((ks) >> 2) * 1024 + ((ks) & 3) * 32) >> 4)
template <int SC>
DEVI void wg_ss32t(float (&d)[16], uint64_t da, uint64_t db) {
    if (SC) {
        asm volatile("wgmma.mma_async.sync.aligned.m64n32k16.f32.bf16.bf16 "
                     "{%0,%1,%2,%3,%4,%5,%6,%7,%8,%9,%10,%11,%12,%13,%14,%15}, %16, %17, 1, 1, 1, 1, 0;"
                     : "+f"(d[0]), "+f"(d[1]), "+f"(d[2]), "+f"(d[3]), "+f"(d[4]), "+f"(d[5]), "+f"(d[6]), "+f"(d[7]),
                       "+f"(d[8]), "+f"(d[9]), "+f"(d[10]), "+f"(d[11]), "+f"(d[12]), "+f"(d[13]), "+f"(d[14]), "+f"(d[15])
                     : "l"(da), "l"(db));
    } else {
        asm volatile("wgmma.mma_async.sync.aligned.m64n32k16.f32.bf16.bf16 "
                     "{%0,%1,%2,%3,%4,%5,%6,%7,%8,%9,%10,%11,%12,%13,%14,%15}, %16, %17, 0, 1, 1, 1, 0;"
                     : "=f"(d[0]), "=f"(d[1]), "=f"(d[2]), "=f"(d[3]), "=f"(d[4]), "=f"(d[5]), "=f"(d[6]), "=f"(d[7]),
                       "=f"(d[8]), "=f"(d[9]), "=f"(d[10]), "=f"(d[11]), "=f"(d[12]), "=f"(d[13]), "=f"(d[14]), "=f"(d[15])
                     : "l"(da), "l"(db));
    }
}

DEVI void delay_until(uint32_t t0, uint32_t d) { t0 += d; while (clk() < t0) {} }

template <int I0, int I1>
DEVI void xmma(float (&xa)[16], float (&xb)[16], uint32_t w, int ps, uint32_t zero, const uint32_t (&Wq)[16][4], const uint32_t (&Wk)[16][4],
               const uint32_t (&Wv)[NA][4]) {
    const uint64_t xd = mkdesc(SB0 + SM_X, 16, 4096) + (ps & 1) * 1024, vd = mkdesc(SB0 + SM_WV, 8192, 1024);
    uint32_t vo = (w >> 2) * (WV_BOX / 16);
    if (I0 < 16 - NA) OPQ(vo);
#pragma unroll
    for (int i = I0; i < I1; i++) {
        if (i == 0) wg_ss32t<0>(xb, (vd & ~0xFFFFFFFFull) | ((uint32_t)vd + vo), xd + XDOFF(NA));
        else if (i < 16 - NA) wg_ss32t<1>(xb, (vd & ~0xFFFFFFFFull) | ((uint32_t)vd + i * 128 + vo), xd + XDOFF(NA + i));
        else if (i == 16 - NA) wg_rs32<0>(xa, Wq[0], xd);
        else if (i < 32 - NA) wg_rs32<1>(xa, Wq[(i + NA) & 15], xd + XDOFF((i + NA) & 15));
        else if (i < 32) wg_rs32<1>(xb, Wv[(i + NA) & 15], xd + XDOFF((i + NA) & 15));
        else if (i == 32) wg_rs32<0>(xa, Wk[0], xd);
        else wg_rs32<1>(xa, Wk[i & 15], xd + XDOFF(i & 15));
    }
    wg_commit();
}
#define XMMA(I0, I1) xmma<(I0), (I1)>(xa, xb, w, p ^ 1, zero, Wq, Wk, Wv)
DEVI void wg_done(float (&d)[16]) {
    asm volatile("" : "+f"(d[0]), "+f"(d[1]), "+f"(d[2]), "+f"(d[3]), "+f"(d[4]), "+f"(d[5]), "+f"(d[6]), "+f"(d[7]),
                      "+f"(d[8]), "+f"(d[9]), "+f"(d[10]), "+f"(d[11]), "+f"(d[12]), "+f"(d[13]), "+f"(d[14]), "+f"(d[15]) :: "memory");
}
template <int M>
DEVI void xpack(uint32_t (&xp)[8], float (&xa)[16]) {
    wg_done(xa);
#pragma unroll
    for (int i = 0; i < 4; i++) {
        xp[2 * i] = pack2(xa[4 * i], xa[4 * i + (M < 2 ? 2 : 1)]);
        xp[2 * i + 1] = pack2(xa[4 * i + (M < 2 ? 1 : 2)], xa[4 * i + 3]);
    }
}
template <int M>
DEVI uint4 xpeer(uint32_t sb, int ps, uint32_t t16) { return lds128(sb + SM_PI - ((ps & 1) ^ 1) * 12288 + M * 4096 + t16); }
DEVI void xadd(uint32_t (&xp)[8], const uint4& pi) {
    xp[0] = hadd2(xp[0], pi.x); xp[1] = hadd2(xp[1], pi.y); xp[2] = hadd2(xp[2], pi.z); xp[3] = hadd2(xp[3], pi.w);
}
template <int M>
DEVI void xsend(const uint32_t (&xp)[8], uint32_t sb, int ps, uint32_t t16) {
    asm volatile("st.async.weak.shared::cluster.mbarrier::complete_tx::bytes.v4.b32 [%0], {%1,%2,%3,%4}, [%5];"
                 ::"r"((sb ^ 0x1000000) + SM_PI - (ps & 1) * 12288 + M * 4096 + t16), "r"(xp[4]), "r"(xp[5]), "r"(xp[6]), "r"(xp[7]),
                   "r"((sb ^ 0x1000000) + SM_BAR + BAR_PI + (ps & 1) * 8) : "memory");
}
template <int M>
DEVI void xstore(const uint32_t (&xp)[8], uint32_t sb, uint32_t sbw, int ps, uint32_t t16, uint32_t KA) {
    const uint32_t a = SM_XO + M * 2048 + (M < 2 ? (KA & 0xFF) + sbw : (t16 >> 1) + sb);
    sts64(a, xp[0], xp[1]);
    sts64(a + 6144, xp[2], xp[3]);
    xsend<M>(xp, sb, ps, t16);
}
template <int M>
DEVI void xpark(uint32_t (&xp)[8], const uint4& pi, uint32_t sb, uint32_t sbw, int ps, uint32_t t16, uint32_t KA) {
    xadd(xp, pi);
    xstore<M>(xp, sb, sbw, ps, t16, KA);
}
template <uint32_t OFF> DEVI void red2(uint32_t lo, uint32_t hi, uint32_t a, uint32_t b) {
    asm volatile("{\n.reg .b64 a;\nmov.b64 a, {%0,%1};\nred.relaxed.gpu.global.add.noftz.v2.bf16x2 [a+%4], {%2,%3};\n}"
                 ::"r"(lo), "r"(hi), "r"(a), "r"(b), "n"(OFF) : "memory");
}
template <int M, int N>
DEVI void xstart(uint32_t sb, uint32_t w, uint32_t ga, uint32_t xhi, uint32_t j, uint32_t t16, uint32_t KA, const uint32_t (&W)[N][4]) {
    float xa[16], xb[16];
    uint32_t xp[8];
    auto pass = [&](float (&d)[16], int i, int k0, int k1) {
        const uint64_t xd = mkdesc(SB0 + SM_X + (i ? i + 1 : 0) * 16384, 16, 4096), vd = mkdesc(SB0 + SM_WV, 8192, 1024) + (w >> 2) * (WV_BOX / 16);
#pragma unroll
        for (int k = k0; k < k1; k++) {
            if (k == 0) wg_rs32<0>(d, W[0], xd);
            else if (k < N) wg_rs32<1>(d, W[k < N ? k : 0], xd + XDOFF(k));
            else wg_ss32t<1>(d, vd + (k - N) * 128, xd + XDOFF(k));
        }
        wg_commit();
    };
    wg_fence();
    pass(xa, 0, 0, 16);
    pass(xb, 1, 0, ASP);
    if (M == 0) bsync<5, 256>();
    ga += M < 2 ? (KA & 0xFF) + w * 256 : t16 >> 1;
    constexpr uint32_t O = XO_XG + M * 2048, SG = 128 * 6144;
    wg_wait<1>();
    xpack<M>(xp, xa);
    red2<O>(ga, xhi, xp[0], xp[1]); red2<O + 6144>(ga, xhi, xp[2], xp[3]); red2<O + 12288>(ga, xhi, xp[4], xp[5]); red2<O + 18432>(ga, xhi, xp[6], xp[7]);
    if (M == 2) barv<3, 320>();
    wg_fence();
    pass(xb, 1, ASP, 16);
    pass(xa, 2, 0, 16);
    wg_wait<1>();
    xpack<M>(xp, xb);
    red2<O + SG>(ga, xhi, xp[0], xp[1]); red2<O + SG + 6144>(ga, xhi, xp[2], xp[3]);
    red2<O + SG + 12288>(ga, xhi, xp[4], xp[5]); red2<O + SG + 18432>(ga, xhi, xp[6], xp[7]);
    wg_wait<0>();
    xpack<M>(xp, xa);
    red2<O + 2 * SG>(ga + j * 6144, xhi, xp[0], xp[1]);
    red2<O + 2 * SG>(ga + (j ^ 1) * 6144, xhi, xp[2], xp[3]);
    xsend<M>(xp, sb, 0, t16);
}
DEVI void piwait(uint32_t sb, int p, int ps) { mbar_wait(sb + SM_BAR + BAR_PI + p * 8, ((ps + 2) >> 1) & 1); }

DEVI uint32_t par(uint32_t off) { return __popc(off & 0xB2000u) & 1; }
DEVI uint32_t probe(uint32_t lo, uint32_t hi) {
    uint32_t best = 0xFFFFFFFFu, x = 0;
    stg4<0>(lo, hi, 0, 0, 0, 0);
    stg4<16>(lo, hi, 0, 0, 0, 0);
#pragma unroll 1
    for (int r = 0; r < NPRB; r++) {
        const uint32_t t0 = clk();
        asm volatile("{\n.reg .b64 a;\nmov.b64 a, {%1,%2};\natom.relaxed.gpu.global.add.u32 %0, [a], 2;\n}" : "=r"(x) : "r"(lo), "r"(hi) : "memory");
        if (x == 0xFFFFFFFFu) die(1 << 23);
        best = min(best, clk() - t0);
    }
    return best;
}

DEVI void xload(uint32_t sb, uint32_t u, uint32_t j, int ps, const CUtensorMap* tmx) {
    if (elect()) {
        const uint32_t sg = ps + 4 - (u & 1) + (u >> 1);
        mbar_expect(sb + SM_BAR + BAR_XA, sg < NSEG ? 4096 : 0);
        if (sg < NSEG) tma3d(sb + SM_X + (ps & 1) * 16384 + u * 4096, tmx, sb + SM_BAR + BAR_XA, 0, sg * 32 + (j ^ ((u & 1) * 2 + (u >> 1))) * 8, j * 4);
    }
}
DEVI uint32_t rpage(uint32_t j, int s) { return (s & 3) * 65536 + (j & 1) * 8192 + (((s ^ (s >> 1) ^ j ^ (j >> 1)) & 1) << 12); }

#define RLOAD() { m0 = ldg4<XO_R>(a, ah); n0 = ldg4<XO_R + 16384>(a, ah); e0 = ldg1<XO_R + 32768>(e, eh); f0 = ldg1<XO_R + 33792>(e, eh); }
DEVI bool ruse(uint32_t a, const uint4& m0, const uint4& n0, uint32_t e0, uint32_t f0) {
    const uint32_t a0 = hadd2(m0.w, n0.w), b0 = hadd2(e0, f0);
    stsm4(a, hadd2(m0.x, n0.x), hadd2(m0.y, n0.y), hadd2(m0.z, n0.z), __byte_perm(a0, b0, 0x5410));
    return __any_sync(0xFFFFFFFFu, (a0 & b0 & 0x42000000u) != 0x42000000u);
}

#define GST(i) (SM_WO + (i) * 49152)
#define BAR_GF 128
#define BAR_GE (BAR_GF + 64)
#define BAR_GX (BAR_GE + 32)
#define D4(c, i) #c "f"(d[i]), #c "f"(d[i + 1]), #c "f"(d[i + 2]), #c "f"(d[i + 3])
#define D16(c, i) D4(c, i), D4(c, i + 4), D4(c, i + 8), D4(c, i + 12)
DEVI void mwait(uint32_t bar, uint32_t parity) {
    asm volatile("{\n.reg .pred p;\n.reg .b32 c;\nmbarrier.try_wait.parity.shared::cta.b64 p, [%0], %1;\n@p bra.uni D;\nmov.b32 c, 0;\n"
                 "L:\nadd.u32 c, c, 1;\nsetp.gt.u32 p, c, 4194304;\n@p st.shared.u32 [c], c;\n"
                 "mbarrier.try_wait.parity.shared::cta.b64 p, [%0], %1;\n@!p bra.uni L;\nD:\n}" ::"r"(bar), "r"(parity) : "memory");
}
DEVI void wg_ss256t(float (&d)[128], uint64_t da, uint64_t db) {
    asm volatile("wgmma.mma_async.sync.aligned.m64n256k16.f32.bf16.bf16 "
        "{%0,%1,%2,%3,%4,%5,%6,%7,%8,%9,%10,%11,%12,%13,%14,%15,%16,%17,%18,%19,%20,%21,%22,%23,%24,%25,%26,%27,%28,%29,%30,%31,%32,%33,%34,%35,%36,%37,%38,%39,%40,%41,%42,%43,%44,%45,%46,%47,%48,%49,%50,%51,%52,%53,%54,%55,%56,%57,%58,%59,%60,%61,%62,%63,%64,%65,%66,%67,%68,%69,%70,%71,%72,%73,%74,%75,%76,%77,%78,%79,%80,%81,%82,%83,%84,%85,%86,%87,%88,%89,%90,%91,%92,%93,%94,%95,%96,%97,%98,%99,%100,%101,%102,%103,%104,%105,%106,%107,%108,%109,%110,%111,%112,%113,%114,%115,%116,%117,%118,%119,%120,%121,%122,%123,%124,%125,%126,%127}, "
        "%128, %129, 1, 1, 1, 1, 1;"
        : D16(+, 0), D16(+, 16), D16(+, 32), D16(+, 48), D16(+, 64), D16(+, 80), D16(+, 96), D16(+, 112) : "l"(da), "l"(db));
}
template <int O, int KB> DEVI void g_half(float (&d)[64], uint64_t da) {
    const uint64_t db = mkdesc(SB0 + GST(KB & 3) + 16384 + O * 256, 8192, 1024);
#pragma unroll
    for (int k = 0; k < 4; k++)
        asm volatile("wgmma.mma_async.sync.aligned.m64n128k16.f32.bf16.bf16 "
            "{%0,%1,%2,%3,%4,%5,%6,%7,%8,%9,%10,%11,%12,%13,%14,%15,%16,%17,%18,%19,%20,%21,%22,%23,%24,%25,%26,%27,%28,%29,%30,%31,%32,%33,%34,%35,%36,%37,%38,%39,%40,%41,%42,%43,%44,%45,%46,%47,%48,%49,%50,%51,%52,%53,%54,%55,%56,%57,%58,%59,%60,%61,%62,%63}, "
            "%64, %65, 1, 1, 1, 1, 1;"
            : D16(+, 0), D16(+, 16), D16(+, 32), D16(+, 48) : "l"(da + (KB & 3) * 3072 + k * 16), "l"(db + k * 128));
}
DEVI void g_load(uint32_t sb, uint32_t u, uint32_t role, uint32_t kb, uint32_t xlo, uint32_t xhi, const CUtensorMap* tmb) {
    const uint32_t st = kb & 3, bar = sb + SM_BAR + BAR_GF + u * 32 + st * 8, dst = sb + GST(st), k = (role & 1) * 32 + kb;
    if (!elect()) return;
    mbar_expect(bar, u ? 8192 : 40960);
    bulk_g2s(dst + u * 8192, xlo + XO_OX + (k * 16 + (role >> 3)) * 16384 + u * 8192, xhi, 8192, bar);
    if (u == 0) {
        tma3d(dst + 16384, tmb, bar, 0, k * 64, ((role & 7) ^ 1) * 2);
        tma3d(dst + 32768, tmb, bar, 0, k * 64, (role & 7) * 2);
    }
}
DEVI void g_arrive(uint32_t a, uint32_t xhi, uint32_t n) {
    if (elect()) asm volatile("{\n.reg .b64 a;\nmov.b64 a, {%0,%1};\nred.release.gpu.global.inc.u32 [a], %2;\n}" ::"r"(a), "r"(xhi), "r"(n - 1) : "memory");
}
DEVI void g_wait(uint32_t a, uint32_t xhi) {
    int it = 0;
    uint32_t v;
    do {
        asm volatile("{\n.reg .b64 a;\nmov.b64 a, {%1,%2};\nld.acquire.gpu.global.u32 %0, [a];\n}" : "=r"(v) : "r"(a), "r"(xhi) : "memory");
        if (++it > SPIN_LIMIT) die(it);
    } while (__any_sync(0xFFFFFFFFu, v));
    asm volatile("fence.proxy.async.global;" ::: "memory");
}
#define GD 200
DEVI void g_done(float (&d)[64]) { asm volatile("" : D16(+, 0), D16(+, 16), D16(+, 32), D16(+, 48)::"memory"); }
DEVI void g_main(uint32_t sb, uint32_t w, uint32_t role, const CUtensorMap* tmy) {
    const uint32_t bar = sb + SM_BAR, t16 = threadIdx.x * 16;
    const uint64_t da = (mkdesc(SB0 + GST(0), 128, 1024) & ~((uint64_t)3 << 62)) + (w >> 2) * 512;
    float d[128];
#pragma unroll
    for (int i = 0; i < 128; i++) d[i] = 0.f;
#define GFULL(kb) { mwait(bar + BAR_GF + ((kb) & 3) * 8, ((kb) >> 2) & 1); if (w >= 4) mwait(bar + BAR_GF + 32 + ((kb) & 3) * 8, ((kb) >> 2) & 1); }
#pragma unroll 1
    for (uint32_t kb = 0; kb < 29; kb++) {
        GFULL(kb);
        if (kb == 0 && threadIdx.x == 128) PG(4);
        if (kb == 4 && threadIdx.x == 0) PG(5);
        const uint64_t a = da + (kb & 3) * 3072, b = mkdesc(SB0 + GST(0) + 16384, 8192, 1024) + (kb & 3) * 3072;
        wg_fence();
#pragma unroll
        for (int k = 0; k < 4; k++) wg_ss256t(d, a + k * 16, b + k * 128);
        wg_commit();
        wg_wait<1>();
        if (kb > 0 && elect()) mbar_arrive(bar + BAR_GE + ((kb - 1) & 3) * 8);
    }
    GFULL(29);
    GFULL(30);
    GFULL(31);
    wg_wait<0>();
    float x[64], y[64];
#pragma unroll
    for (int i = 0; i < 64; i++) asm volatile("mov.b32 %0, %1;" : "=f"(x[i]) : "f"(d[i]) : "memory");
    SF();
#pragma unroll
    for (int i = 0; i < 64; i++) asm volatile("mov.b32 %0, %1;" : "=f"(y[i]) : "f"(d[i + 64]) : "memory");
    SF();
    if (elect()) asm volatile("mbarrier.arrive.relaxed.cluster.shared::cluster.b64 _, [%0];" ::"r"((bar ^ 0x1000000) + BAR_GX) : "memory");
    wg_fence();
    g_half<0, 29>(x, da);
    g_half<0, 30>(x, da);
    g_half<0, 31>(x, da);
    wg_commit();
    g_half<64, 29>(y, da);
    wg_commit();
    wg_wait<1>();
    g_done(x);
    mwait(bar + BAR_GX, 0);
#define GSEND(i0) _Pragma("unroll") for (int i = (i0); i < (i0) + 4; i++) \
        asm volatile("st.async.weak.shared::cluster.mbarrier::complete_tx::bytes.v4.b32 [%0], {%1,%2,%3,%4}, [%5];" \
                     ::"r"((sb ^ 0x1000000) + i * 4096 + t16), "r"(pack2(x[8 * i], x[8 * i + 1])), "r"(pack2(x[8 * i + 2], x[8 * i + 3])), \
                       "r"(pack2(x[8 * i + 4], x[8 * i + 5])), "r"(pack2(x[8 * i + 6], x[8 * i + 7])), "r"((bar ^ 0x1000000) + BAR_GX + 8) : "memory")
    GSEND(0);
    wg_fence();
    g_half<64, 30>(y, da);
    wg_commit();
    GSEND(4);
    wg_fence();
    g_half<64, 31>(y, da);
    wg_commit();
    wg_wait<0>();
    g_done(y);
    if (threadIdx.x == 0) PG(7);
    mwait(bar + BAR_GX + 8, 0);
    if (threadIdx.x == 0) PG(1);
    const uint32_t lane = threadIdx.x & 31, o = sb + GST(1) + w * 2048;
#pragma unroll
    for (int i = 0; i < 8; i++) {
        const uint4 a = lds128(sb + i * 4096 + t16);
        const float* e = y + 8 * i;
        stsm4(o + (i >> 2) * 49152 + (lane & 15) * 128 + ((((i & 3) * 2 + (lane >> 4)) ^ (lane & 7)) << 4),
              pack2(e[0] + lo_f(a.x), e[1] + hi_f(a.x)), pack2(e[2] + lo_f(a.y), e[3] + hi_f(a.y)),
              pack2(e[4] + lo_f(a.z), e[5] + hi_f(a.z)), pack2(e[6] + lo_f(a.w), e[7] + hi_f(a.w)));
        if (i == 3 || i == 7) {
            asm volatile("fence.proxy.async.shared::cta;" ::: "memory");
            __syncwarp();
            if (elect())
                asm volatile("cp.async.bulk.tensor.2d.global.shared::cta.bulk_group [%0, {%2, %3}], [%1];\ncp.async.bulk.commit_group;"
                             ::"l"(tmy), "r"(o + (i >> 2) * 49152), "r"((role & 7) * 128 + (i >> 2) * 64), "r"((role >> 3) * 128 + w * 16) : "memory");
        }
    }
    if (threadIdx.x == 0) PG(6);
    asm volatile("cp.async.bulk.wait_group.read 0;" ::: "memory");
}

DEVI void kvload(uint32_t sb, uint32_t u, uint32_t h, uint32_t j, int sg, uint32_t xlo, uint32_t xhi) {
    const uint32_t o = u == 0 ? 0 : 2048;
    mbar_expect(sb + SM_BAR + BAR_KV, 6144 - o);
    bulk_g2s(sb + SM_KV + u * 4096 + o, xlo + XO_XG + (((sg & 7) * 32 + h) * 4 + ((j + u) & 3)) * 6144 + o, xhi, 6144 - o, sb + SM_BAR + BAR_KV);
}
DEVI void helper_step(uint32_t sb, uint32_t w, uint32_t h, uint32_t j, uint32_t& l16, uint32_t xlo, uint32_t xhi, uint32_t zero, int s,
                      const CUtensorMap* tmx, const CUtensorMap* tmb) {
    const uint32_t u = w - 8, bq = sb + SM_BAR;
    bsync<1, 384>();
    PT(0);
    PDUMP();
    PT(1);
    if (s == NSEG - 2 && u < 2) g_arrive(xlo + XO_TK + 128, xhi, 256);
    const uint32_t ctag = ((s >> 1) & 1) ^ 1;
    const uint32_t av = xlo + ((s & 1) * 32 + h) * 8192 + u * 512;
    mbar_wait(bq + BAR_XA, (s + 1) & 1);
    bsync<8, 384>();
    delay_until(clk(), DLY_V);
    PT(4);
    int it = 0;
    bool bad;
    do {
        const uint4 d1 = ldg4<XO_CV>(av + (j ^ 1) * 2048 + l16, xhi);
        const uint4 d2 = ldg4<XO_CV>(av + (j ^ 2) * 2048 + l16, xhi);
        const uint4 d3 = ldg4<XO_CV>(av + (j ^ 3) * 2048 + l16, xhi);
        bad = any_bad(or3(tagx2(d1.x, d1.z, ctag), tagx2(d2.x, d2.z, ctag), tagx2(d3.x, d3.z, ctag)));
        sts128(sb + SM_VS + u * 512 + l16, hadd2(hadd2(d1.x, d2.x), d3.x), hadd2(hadd2(d1.y, d2.y), d3.y), hadd2(hadd2(d1.z, d2.z), d3.z),
               hadd2(hadd2(d1.w, d2.w), d3.w));
        REFRESH();
        if (++it > SPIN_LIMIT) die(it);
    } while (bad);
    PC(26, it - 1);
    PT(5);
    barv<5, 384>();
    bsync<3, 384>();
    if (u < 2) {
        asm volatile("fence.proxy.async.shared::cta;" ::: "memory");
        if (elect()) {
            const uint32_t sg = s + 3 - u;
            if (sg < NSEG) {
                const uint32_t ga = xlo + XO_XG + (((sg & 7) * 32 + h) * 4 + (j ^ (2 * u))) * 6144, sa = sb + SM_XO + u * 6144;
                if (u == 0) bulk_s2g(ga, xhi, sa, 6144);
                else bulk_red(ga, xhi, sa, 6144);
            }
        }
    }
    PT(6);
    uint32_t old = 0;
    if (u > 0 && s + 3 < NSEG)
        asm volatile("{\n.reg .b64 a;\nmov.b64 a, {%1,%2};\natom.relaxed.gpu.global.exch.b32 %0, [a], 0;\n}"
                     : "=r"(old) : "r"(xlo + XO_R + rpage(j, s + 2) + (u - 1) * 16384 + h * 128 + (l16 >> 2)), "r"(xhi) : "memory");
    PT(7);
    bsync<7, 384>();
    if (s + 1 < NSEG && elect()) kvload(sb, u, h, j, s + 1, xlo, xhi);
    if (u < 2) {
        asm volatile("cp.async.bulk.wait_group.read 0;" ::: "memory");
        if (elect()) mbar_expect(bq + BAR_PI + ((s & 1) ^ 1) * 8, 6144);
    }
    PT(8);
    if (s + 1 < NSEG) bsync<10, 384>();
    xload(sb, u, j, s + 1, tmx);
    if (s == NSEG - 2 && (u == 0 || (u == 1 && h < 30))) {
        g_wait(xlo + XO_TK + 128, xhi);
        g_load(sb, u, h * 4 + j, 0, xlo, xhi, tmb);
        g_load(sb, u, h * 4 + j, 1, xlo, xhi, tmb);
    }
    asm volatile("cp.async.bulk.wait_group 0;" ::: "memory");
    if (s + 1 < NSEG) mbar_wait(bq + BAR_KV, (s + 1) & 1);
    asm volatile("lop3.b32 %0, %0, %1, %2, 0x78;" : "+r"(l16) : "r"(old), "r"(zero));
    PT(15);
}
DEVI void tickets_done(uint32_t* tk) {
    if (atomicInc(tk + 2, gridDim.x / 2 - 64) == gridDim.x / 2 - 64) { tk[0] = 0; tk[1] = 0; }
}

__global__ void __cluster_dims__(2, 1, 1) __launch_bounds__(384, 1)
chain_kernel(const __grid_constant__ CUtensorMap tmq, const __grid_constant__ CUtensorMap tmk,
             const __grid_constant__ CUtensorMap tmv, const __grid_constant__ CUtensorMap tmo,
             const __grid_constant__ CUtensorMap tmx, const __grid_constant__ CUtensorMap tmb, const __grid_constant__ CUtensorMap tmy,
             const bf16* __restrict__ mem0, const bf16* __restrict__ xg,
             uint32_t xlo, uint32_t xhi, uint32_t zero, int nseg) {
    extern __shared__ __align__(1024) uint8_t smem[];
    if ((smem_u32(smem) & 0xFFFFFF) != SB0) die(1 << 23);
    asm volatile("griddepcontrol.launch_dependents;" ::: "memory");
    const uint32_t w = __reduce_max_sync(0xFFFFFFFFu, threadIdx.x >> 5);
    const uint32_t rk = smem_u32(smem) & 0x1000000;
    const uint32_t sb = __reduce_max_sync(0xFFFFFFFFu, smem_u32(smem));
    const uint32_t bq = sb + SM_BAR;
    uint32_t l16 = __shfl_sync(0xFFFFFFFFu, (threadIdx.x & 31) * 16, threadIdx.x & 31);
    if (threadIdx.x == 0) {
        mbar_init(bq, 1);
        for (int i = 0; i < 24; i++) mbar_init(bq + BAR_WF + i * 8, i < 16 ? 1 : 8);
        mbar_init(bq + BAR_XA, 4); mbar_init(bq + BAR_KV, 4); mbar_init(bq + BAR_PI, 2); mbar_init(bq + BAR_PI + 8, 2);
        for (int i = 0; i < 14; i++) mbar_init(bq + BAR_GF + i * 8, i < 8 || i == 13 ? 1 : 8);
        mbar_expect(bq + BAR_GX + 8, 32768);
        mbar_init(bq + BAR_RO, 1);
        mbar_expect(bq + BAR_RO, 4);
        mbar_expect(bq + BAR_PI, 6144);
        mbar_expect(bq + BAR_PI, 6144);
        asm volatile("fence.mbarrier_init.release.cluster;" ::: "memory");
        asm volatile("fence.proxy.async.shared::cta;" ::: "memory");
    }
    __syncwarp();
    asm volatile("barrier.cluster.arrive.relaxed.aligned;" ::: "memory");
    if (rk ? w < 8 : w == 4) {
        const uint32_t b = blockIdx.x - (w >> 2), u = w & 3, l = l16 >> 4;
        if (rk && b < 128) {
            uint32_t v = 0;
            const unsigned short* m0 = (const unsigned short*)mem0 + (b & 3) * 256;
            if (u == 1) {
                const uint32_t x = (b >> 2) * 8 + (l >> 2), d = (x & ~31u) + (l & 3) * 8 + ((x & 31) >> 2) + (x & 3) * 2 * DM;
                v = m0[d] | (((l & 3) == 3 ? 0x4200u : m0[d + DM]) << 16);
            }
            if (u == 3 && b < 32) v = m0[(b >> 2) * 32 + 24 + (l >> 2) + ((l & 3) * 2 + 1) * DM] | 0x42000000u;
#pragma unroll
            for (uint32_t i = 0; i < 9; i++) stg4<XO_XG>(xlo + ((i / 3) * 128 + b) * 6144 + (i % 3) * 2048 + u * 512 + l16, xhi, 0, 0, 0, 0);
            if (u > 0) {
                const uint32_t o = xlo + (u - 1) * 16384 + (b >> 2) * 128 + l * 4;
                stg1<XO_R>(o + rpage(b & 3, 0), xhi, 0);
                stg1<XO_R>(o + rpage(b & 3, 1), xhi, 0);
                stg1<XO_R>(o + rpage(b & 3, -1), xhi, v);
            }
        }
        __syncwarp();
        g_arrive(xlo + XO_TK + 12, xhi, 9 * (gridDim.x / 2));
    }
    if (w == 8 && blockIdx.x < 128) {
        if (XPF && elect()) {
            asm volatile("cp.async.bulk.prefetch.L2.global [%0], 3072;" ::"l"((const char*)xg + blockIdx.x * 3072) : "memory");
            asm volatile("prefetch.tensormap [%0];\nprefetch.tensormap [%1];\nprefetch.tensormap [%2];\nprefetch.tensormap [%3];\nprefetch.tensormap [%4];"
                         ::"l"(&tmq), "l"(&tmx), "l"(&tmk), "l"(&tmv), "l"(&tmo) : "memory");
        }
#pragma unroll 1
        for (int i = 0; i < EPF; i++) {
            if (i) delay_until(clk(), EPD);
            if (elect())
                asm volatile("cp.async.bulk.prefetch.tensor.3d.L2.global [%0, {0, %1, %2}];" ::"l"(&tmq), "r"((blockIdx.x & 3) * 256 + i * 64), "r"((blockIdx.x >> 2) * 2) : "memory");
        }
    }
    if (rk == 0 && w < 2) {
        if (l16 == 0) sts32(sb + SM_ROLE + 8 + w * 4, probe(xlo + XO_PB + w * 4096 + blockIdx.x * 16, xhi));
        bsync<2, 64>();
    }
    asm volatile("barrier.cluster.wait.aligned;" ::: "memory");
    if (rk == 0 && threadIdx.x == 0) {
        uint32_t side = (lds32(sb + SM_ROLE + 8) < lds32(sb + SM_ROLE + 12) ? 0u : 1u) ^ par(XO_PB);
        uint32_t* tk = (uint32_t*)(((uint64_t)xhi << 32) | (xlo + XO_TK));
        uint32_t t = atomicAdd(tk + side, 1u);
        if (t >= 32) {
            uint2 c;
            int it = 0;
            do {
                c = ldg2<XO_TK>(xlo, xhi);
                if (++it > SPIN_LIMIT) die(it);
            } while (c.x + c.y != gridDim.x / 2);
            t += (side ? c.x : c.y) - 32;
            side ^= 1;
            if (t >= 32) tickets_done(tk);
        }
#pragma unroll
        for (uint32_t r = 0; r < 2; r++)
            asm volatile("st.async.weak.shared::cluster.mbarrier::complete_tx::bytes.b32 [%0], %1, [%2];"
                         ::"r"(sb + SM_ROLE + (r << 24)), "r"(t * 4 + side * 2 + r), "r"(bq + BAR_RO + (r << 24)) : "memory");
    }
    __syncwarp();
    mbar_wait(bq + BAR_RO, 0);
    const uint32_t role = __reduce_max_sync(0xFFFFFFFFu, lds32(sb + SM_ROLE));
    if (role >= 128) return;
    const uint32_t h = role >> 2, j = role & 3;

    if (w >= 8) {
        asm volatile("setmaxnreg.dec.sync.aligned.u32 24;");
        const uint32_t u = w - 8;
        if (u == 3) {
#pragma unroll 1
            for (uint32_t c = 0; c < 16; c++) {
                if (c >= WIN) mbar_wait(bq + BAR_WF + (c - WIN) * 8, 0);
                if (l16 == 0) PG(16 + c);
                if (c == 12 + WOP) bsync<2, 64>();
                if (c >= 4 && c < 12 && c != 10) mbar_wait(bq + BAR_WE + (c - 4) * 8, 0);
                if (elect()) {
                    const uint32_t b = bq + BAR_WF + c * 8;
                    mbar_expect(b, 16384);
                    if (c >= 12) tma2d(sb + SM_WO + (c - 12) * WO_BOX, &tmo, b, j * 256 + (c - 12) * 64, h * 128);
                    else tma3d(c == 10 ? sb + SM_WV : sb + SM_ST + (c & 3) * 16384, c < 4 ? &tmq : c < 8 ? &tmk : &tmv, b, 0, j * 256 + ((c ^ (c >= 10)) & 3) * 64, h * 2);
                }
            }
#pragma unroll 1
            for (uint32_t c = 16 - WIN; c < 16; c++) mbar_wait(bq + BAR_WF + c * 8, 0);
            if (l16 == 0) PG(15);
        } else if (u == 0) {
            if (elect()) {
                mbar_expect(bq, 49152);
#pragma unroll 1
                for (uint32_t i = 0; i < 12; i++)
                    tma3d(sb + SM_X + (i < 4 ? i : i + 4) * 4096, &tmx, bq, 0, i < 8 ? i * 8 : (j ^ ((0xBD98u >> (i - 8) * 4) & 15)) * 8, j * 4);
            }
#pragma unroll 1
            for (int i = 0; i < 4; i++) xload(sb, i, j, -1, &tmx);
            bsync<3, 320>();
            if (l16 == 0) PG(32);
            g_arrive(xlo + XO_FL + h * 128, xhi, 4);
            if (WOP < 4) barv<2, 64>();
            if (l16 == 0) PG(33);
            g_wait(xlo + XO_FL + h * 128, xhi);
            if (l16 == 0) PG(34);
#pragma unroll 1
            for (int i = 0; i < 4; i++)
                if (elect()) kvload(sb, i, h, j, 0, xlo, xhi);
            mbar_wait(bq + BAR_KV, 0);
            if (l16 == 0) PG(14);
        } else if (u == 1) {
            bsync<8, 320>();
            asm volatile("fence.acq_rel.gpu;" ::: "memory");
        } else {
            GSYNC(0);
            mbar_wait(bq + BAR_WE + 48, 0);
#pragma unroll 1
            for (int e = 0; e < 16; e++) sts128(sb + SM_TR + 4096 + e * 512 + l16, 0, 0, 0, 0);
            barv<3, 320>();
            bsync<8, 320>();
#pragma unroll 1
            for (int i = 0; i < 4; i++) xload(sb, i, j, 0, &tmx);
        }
#pragma unroll 1
        for (int s = 0; s < nseg; s++) helper_step(sb, w, h, j, l16, xlo, xhi, zero, s, &tmx, &tmb);
        piwait(sb, 0, nseg - 2);
        bsync<9, 384>();
        GSYNC(1);
        if (w < 10) {
            uint32_t kb = 2;
            asm volatile("fence.proxy.async.shared::cta;" ::: "memory");
            if (w == 9) {
                g_arrive(xlo + XO_TK + 192, xhi, 128);
                PG(2);
                if (h >= 30) { g_wait(xlo + XO_TK + 192, xhi); kb = 0; }
                PG(3);
            } else delay_until(clk(), GD);
#pragma unroll 1
            for (; kb < 32; kb++) {
                if (kb >= 4) mbar_wait(bq + BAR_GE + (kb & 3) * 8, ((kb >> 2) & 1) ^ 1);
                g_load(sb, w - 8, role, kb, xlo, xhi, &tmb);
            }
        }
        if (role == 0 && w == 11 && elect()) tickets_done((uint32_t*)(((uint64_t)xhi << 32) | (xlo + XO_TK)));
    } else {
        asm volatile("setmaxnreg.inc.sync.aligned.u32 240;");
        uint32_t Wq[16][4], Wk[16][4], Wv[NA][4];
        uint32_t t16, KA, KB, KC, KD;
        {
            const uint32_t lane = l16 >> 4, g = lane >> 2, t = lane & 3;
            const uint32_t rw = (((lane >> 4) & 1) * 8 + (lane & 7)) * 128u;
            const uint32_t off = rw + ((((w & 3) * 2 + ((lane >> 3) & 1)) ^ (lane & 7)) << 4);
            const uint32_t offo = rw + ((((w & 1) * 4 + ((lane >> 3) & 1)) ^ (lane & 7)) << 4);
            const uint32_t r = 2 * (t & 1) + (g >> 2);
            const uint32_t mk0 = t < 2 ? 0 : (r == 0 ? 2 * g > w : j + r < 4), mk1 = t < 2 ? 0 : (r == 0 ? 2 * g + 1 > w : j + r < 4);
            t16 = __shfl_sync(0xFFFFFFFFu, w * 512 + l16, lane);
            KA = __shfl_sync(0xFFFFFFFFu, (w * 512 + t * 64 + g * 8) | ((w * 512 + (g & 1) * 256 + (g >> 1) * 64 + t * 16) << 16), lane);
            KB = __shfl_sync(0xFFFFFFFFu, ((w >> 2) * WV_BOX + off) | mk0 | (mk1 << 1) |
                                              ((w * 256 + (g >> 2) * 4096 + (g & 3) * 64 + t * 16) << 16), lane);
            KC = __shfl_sync(0xFFFFFFFFu, ((lane & 7) * 1280 + (lane >> 3) * 128 + ((w ^ (lane & 7)) << 4)) | (((t >> 1) * 16 + g * 2) << 16) | ((t * 64 + g * 8) << 24), lane);
            KD = __shfl_sync(0xFFFFFFFFu, ((w >> 1) * WO_BOX + offo) | (((lane & 7) * 208 + (lane >> 3) * 16) << 16), lane);
            if (threadIdx.x == 0) PG(8);
#define WTAKE(W, c, k0) { mbar_wait(bq + BAR_WF + (c) * 8, 0); \
                _Pragma("unroll") for (int ks = 0; ks < 4; ks++) ldsm4t(W[(k0) + ks], sb + SM_ST + ((c) & 3) * 16384 + (KB & 0xFFF0) + ks * 2048); \
                if ((c) < 8) { __syncwarp(); if (elect()) mbar_arrive(bq + BAR_WE + (c) * 8); } }
            if (w == 4) g_wait(xlo + XO_TK + 12, xhi);
#pragma unroll
            for (int c = 0; c < 4; c++) WTAKE(Wq, c, c * 4);
            mbar_wait(bq, 0);
            if (threadIdx.x == 0) PG(9);
            xstart<0>(sb, w, xlo + h * 24576, xhi, j, t16, KA, Wq);
            if (threadIdx.x == 0) PG(10);
#pragma unroll
            for (int c = 0; c < 4; c++) WTAKE(Wk, c + 4, c * 4);
            if (threadIdx.x == 0) PG(11);
            xstart<1>(sb, w, xlo + h * 24576, xhi, j, t16, KA, Wk);
            if (threadIdx.x == 0) PG(12);
            WTAKE(Wv, 8, 0);
            WTAKE(Wv, 9, 4);
            mbar_wait(bq + BAR_WF + 80, 0);
            WTAKE(Wv, 11, 8);
            if (threadIdx.x == 0) PG(13);
            xstart<2>(sb, w, xlo + h * 24576, xhi, j, t16, KA, Wv);
            mbar_wait(bq + BAR_XA, 0);
            bsync<8, 320>();
        }
        const uint32_t ONES = 0x3F803F80u;
#define UNI(x) __reduce_max_sync(0xFFFFFFFFu, x)
        uint32_t swi = UNI((uint32_t)((uint64_t)smem >> 32));
        const uint32_t sbw = UNI(sb + w * 256), sbm = UNI(sb - w * 512), sbs = UNI(sb + w * 768), sbp = UNI(sb + w * 208);
#define OPQALL() { OPQ(t16); OPQ(KA); OPQ(KB); OPQ(KC); OPQ(KD); }
        OPQALL();
        const uint32_t cb0 = (h >> 1) * 32768 + (j & 1) * 16384 + (h & 1) * 8192;
        const uint32_t cb = UNI(xlo + cb0 + ((par(cb0) ^ (j >> 1) ^ CFAR) << 12)), cv = UNI(xlo + role * 2048), h1 = UNI((h & 1) * 1024);
        const uint32_t uox = UNI(xlo + XO_OX + (h * 2 + (w >> 2)) * 262144 + j * 1024 + (w & 3) * 256 - w * 128);
        uint32_t rp = UNI(xlo + rpage(j, 0));
        float ox[4];
        float4 dn;
#define OXSTORE(s) asm volatile("{\n.reg .b64 a;\nmov.b64 a, {%0,%1};\nst.global.u32 [a], %2;\nst.global.u32 [a+128], %3;\n}" \
                                ::"r"(uox + (s) * 4096 + (t16 >> 2)), "r"(xhi), \
                                  "r"(pack2(ox[0] * dn.y, ox[1] * dn.w)), "r"(pack2(ox[2] * dn.y, ox[3] * dn.w)) : "memory")
#pragma unroll 1
        for (int s2 = 0;; s2 += 2, rp ^= 0x21000)
#pragma unroll
        for (int p = 0; p < 2; p++) {
            const int s = s2 + p;
            const uint32_t ctag = ((s2 >> 1) & 1) ^ 1;
            const uint32_t hb = cb ^ (p * 0x81000), rb = rp ^ (p * 0x11000);
            uint4 k0, k1;
            uint32_t qx0, qx1, ov0, ov1;
            {
                float xa[16], xb[16];
                uint4 m0, n0;
                uint32_t e0, f0;
                uint32_t xp[8];
                wg_fence();
                XMMA(0, 6);
                SF();
                piwait(sb, p, s - 2);
                uint4 pi = xpeer<0>(sb, p ^ 1, t16);
                SF();
                wg_fence();
                XMMA(6, RPOS);
                XMMA(RPOS, RPOS + 4);
                uint32_t a = (p ? rp : rp ^ 0x30000) + t16, e = (p ? rp : rp ^ 0x30000) + (t16 >> 2), ah = xhi, eh = xhi;
                OPQ(a); OPQ(e); OPQ(ah); OPQ(eh);
                SF();
                wg_wait<1>();
                SF();
                PT(11);
                RLOAD();
                SF();
#define QPOS (RPOS >= 32 - NA ? RPOS : RPOS + 4 >= 32 - NA ? RPOS + 4 : 32 - NA)
                if (QPOS > RPOS) {
                    wg_fence();
                    if (QPOS > RPOS + 4) XMMA(RPOS + 4, QPOS);
                    XMMA(QPOS, QPOS + 4);
                    wg_wait<1>();
                    SF();
                }
                xpack<0>(xp, xa);
                xpark<0>(xp, pi, sb, sbw, p ^ 1, t16, KA);
                pi = xpeer<2>(sb, p ^ 1, t16);
                SF();
                if (QPOS + 4 < 32) {
                    wg_fence();
                    XMMA(QPOS + 4, 32);
                    SF();
                }
                wg_wait<0>();
                xpack<2>(xp, xb);
                xpark<2>(xp, pi, sb, sbw, p ^ 1, t16, KA);
                SF();
                PT(12);
                {
                    int it = 0;
                    while (ruse(sb + SM_MEMT + t16, m0, n0, e0, f0)) {
                        RLOAD();
                        if (++it > SPIN_LIMIT) die(it);
                    }
                    PC(22, it + 1);
                }
                PT(13);
                OPQ(KA); OPQ(t16);
                uint32_t acw = hb + (KA & 0xFFFF), ahi = xhi, tg = ctag;
                OPQ(acw); OPQ(ahi); OPQ(tg);
                SF();
                bsync<1, 384>();
                PT(0);
                uint32_t b[8][4];
#pragma unroll
                for (int i = 0; i < 8; i++) {
                    const int pp = i < 2 ? i : i ^ 1;
                    ldsm4t(b[pp], sbm + SM_MEMT + t16 + pp * 512);
                    if (i < 7) MF();
                }
                if (ASF) SF();
                float q[4], k[4];
                const uint32_t aWv = sb + SM_WV + (KB & 0xFFF0);
                uint32_t wv[16 - NA > 0 ? 16 - NA : 1][4];
#define WVLD(n0, n1) _Pragma("unroll") for (int n = (n0); n < (n1) && n < 16 - NA; n++) ldsm4t(wv[n], aWv + n * 2048)
#pragma unroll
                for (int ks = 0; ks < 16; ks++) {
                    const uint32_t b0 = b[ks >> 1][(ks & 1) * 2], b1 = b[ks >> 1][(ks & 1) * 2 + 1];
                    if (ks == 0) {
                        mma16z(q, Wq[0][0], Wq[0][1], Wq[0][2], Wq[0][3], b0, b1);
                        mma16z(k, Wk[0][0], Wk[0][1], Wk[0][2], Wk[0][3], b0, b1);
                    } else {
                        mma16(q, Wq[ks][0], Wq[ks][1], Wq[ks][2], Wq[ks][3], b0, b1);
                        mma16(k, Wk[ks][0], Wk[ks][1], Wk[ks][2], Wk[ks][3], b0, b1);
                    }
                    if (ks == 10 && VPF) { SF(); WVLD(0, VPF); }
                }
                const uint32_t oq0 = settag(pack2(q[0], q[2]), tg), oq1 = settag(pack2(q[1], q[3]), tg);
                const uint32_t ok0 = pack2(k[0], k[2]), ok1 = pack2(k[1], k[3]);
                stg2<XO_CQK>(acw, ahi, oq0, ok0);
                stg2<XO_CQK + 256>(acw, ahi, oq1, ok1);
                SF();
                PT(1);
                int nl = VPF;
#pragma unroll
                for (int rd = 0; rd < 8; rd++) {
                    const int pp = (VORD >> (28 - 4 * rd)) & 7;
                    const uint32_t* a = 2 * pp < NA ? Wv[2 * pp < NA ? 2 * pp : 0] : wv[2 * pp < NA ? 0 : 2 * pp - NA];
                    const uint32_t* c = 2 * pp < NA ? Wv[2 * pp < NA ? 2 * pp + 1 : 0] : wv[2 * pp < NA ? 0 : 2 * pp + 1 - NA];
                    if (rd == 0) {
                        mma16z(q, a[0], a[1], a[2], a[3], b[pp][0], b[pp][1]);
                        mma16z(k, c[0], c[1], c[2], c[3], b[pp][2], b[pp][3]);
                    } else {
                        mma16(q, a[0], a[1], a[2], a[3], b[pp][0], b[pp][1]);
                        mma16(k, c[0], c[1], c[2], c[3], b[pp][2], b[pp][3]);
                    }
                    if (rd == 0) {
                        SF();
                        OPQ(swi);
                        asm volatile("{\n.reg .b64 a;\nmov.b64 a, {%0,%1};\nst.v2.u32 [a], {%2,%3};\nst.v2.u32 [a+256], {%4,%5};\n}"
                                     ::"r"((KA & 0xFFF) + (sb ^ 0x1000000) + SM_TR + 4096 + p * 4096), "r"(swi), "r"(oq0), "r"(ok0), "r"(oq1), "r"(ok1) : "memory");
                        sts64(sb + SM_TR + (KA & 0xFFF), oq0, ok0);
                        sts64(sb + SM_TR + (KA & 0xFFF) + 256, oq1, ok1);
                    }
                    if (rd == 4) KEEP(t16, oq0, oq1, ok0, ok1);
                    if (nl < 16 - NA) {
                        SF();
                        WVLD(nl, nl + (2 * pp < NA ? 1 : 3));
                        nl += 2 * pp < NA ? 1 : 3;
                    } else if (nl < 32) {
                        SF();
                        k0 = lds128(sb + SM_KV + 2048 + (KB >> 16));
                        nl = 32;
                    } else if (nl == 32) {
                        SF();
                        k1 = lds128(sb + SM_KV + 10240 + (KB >> 16));
                        const uint4 qq = lds128(sbw + SM_KV + ((KA >> 16) & 0xFF));
                        qx0 = (t16 & 64) ? qq.y : qq.x;
                        qx1 = (t16 & 64) ? qq.w : qq.z;
                        nl = 33;
                    }
                }
                ov0 = pack2(q[0] + k[0], q[1] + k[1]);
                ov1 = pack2(q[2] + k[2], q[3] + k[3]);
                stg2<XO_CV>(cv + p * 262144 + (t16 >> 1), xhi, settag(ov0, tg), ov1);
                barv<8, 384>();
            }
            OPQ(t16);
            SF();
            PT(2);
            PDUMP();
            {
                const uint32_t a0 = sb + SM_KV;
#define CLOADG() { c2 = ldg4<XO_CQK>((hb ^ 0x1000) + (KA >> 16), xhi); c3 = ldg4<XO_CQK>((hb ^ 0x5000) + (KA >> 16), xhi); }
#define CLOADS() { c0 = lds128(sb + SM_TR + (KA >> 16)); c1 = lds128(sb + SM_TR + 4096 + p * 4096 + (KA >> 16)); }
                uint4 c0, c1, c2, c3, pi;
                float xa[16], xb[16];
                uint32_t xp[8];
                wg_fence();
                XMMA(32, 32 + CPOS);
                XMMA(32 + CPOS, 36 + CPOS);
                wg_wait<1>();
                SF();
                CLOADG();
                SF();
                CLOADS();
                if (KPOS == 0) pi = xpeer<1>(sb, p ^ 1, t16);
                SF();
                wg_fence();
                XMMA(36 + CPOS, 48);
                SF();
                const uint32_t ka[4] = {k0.x, k0.y, k0.z, k0.w}, kb[4] = {k1.x, k1.y, k1.z, k1.w};
                const uint32_t aSp = sb + SM_SP + (KC & 0xFFFF);
                PT(3);
#define SCORES(FIRST) { \
                    const uint32_t qA = hadd2(hadd2(c0.x, c1.x), hadd2(c2.x, c3.x)), qB = hadd2(hadd2(c0.z, c1.z), hadd2(c2.z, c3.z)); \
                    const uint32_t kA = hadd2(hadd2(c0.y, c1.y), hadd2(c2.y, c3.y)), kB = hadd2(hadd2(c0.w, c1.w), hadd2(c2.w, c3.w)); \
                    bad = any_bad(or3(tagx2(c1.x, c1.z, ctag), tagx2(c2.x, c2.z, ctag), tagx2(c3.x, c3.z, ctag))); \
                    float sa[4], sb_[4], sc[4], sd[4], se[4]; \
                    if (FIRST) { SF(); wg_wait<0>(); } \
                    mma16z(sa, ka[0], ka[1], ka[2], ka[3], qA, qB); \
                    mma16z(sb_, kb[0], kb[1], kb[2], kb[3], qA, qB); \
                    mma16z(sc, qA, qx0, qB, qx1, kA, kB); \
                    if (FIRST) { \
                        xpack<1>(xp, xa); \
                        if (KPOS == 0) { xadd(xp, pi); xstore<1>(xp, sb, sbw, p ^ 1, t16, KA); barv<3, 384>(); } \
                        mma16z(sd, ka[0], ka[1], ka[2], ka[3], qx0, qx1); \
                        mma16z(se, kb[0], kb[1], kb[2], kb[3], qx0, qx1); \
                    } \
                    stsm4t(aSp, pack2(sa[0], sa[1]), pack2(sa[2], sa[3]), pack2(sb_[0], sb_[1]), pack2(sb_[2], sb_[3])); \
                    stsm2(aSp + 1024, pack2(sc[0], sc[1]), pack2(sc[2], sc[3])); \
                    if (FIRST) { \
                        stsm4t(aSp + 512, pack2(sd[0], sd[1]), pack2(sd[2], sd[3]), pack2(se[0], se[1]), pack2(se[2], se[3])); \
                        if (KPOS == 0) { KEEP(KD, xp[0], xp[1], xp[2], xp[3]); KEEP(KD, xp[4], xp[5], xp[6], xp[7]); } \
                    } }
                int it = 0;
                bool bad;
                SCORES(true);
                while (__builtin_expect(bad, 0)) {
                    OPQ(KA);
                    CLOADG();
                    CLOADS();
                    SCORES(false);
                    if (++it > SPIN_LIMIT) die(it);
                }
                PC(25, it);
                PT(4);
                bsync<4, 256>();
                uint32_t wo[16][4];
                const uint32_t aWo = sb + SM_WO + (KD & 0xFFFF), aWo1 = sb + SM_WO + ((KD & 0xFFFF) ^ 32);
#define WOLD(n0, n1) _Pragma("unroll") for (int n = (n0); n < (n1) && n < 16; n++) ldsm4t(wo[n], ((n & 1) ? aWo1 : aWo) + (n >> 1) * 2048)
                const bool hi = (t16 & 32) != 0;
                const uint32_t t8 = t16 >> 1;
                uint2 v0, v1, v2, v3;
                uint32_t es;
                {
                    uint32_t am[4], ax[4], a4[2];
                    const uint32_t aSr = sbs + SM_SP + t16;
                    ldsm4t(am, aSr);
                    ldsm4t(ax, aSr + 512);
                    ldsm2t(a4, aSr + 1024);
                    MF();
                    if (KPOS == 1) pi = xpeer<1>(sb, p ^ 1, t16);
                    const uint32_t se = (t16 & 128) ? 0u : ONES, so = se ^ ONES;
                    float hm[4], hx[4], h4[4];
                    mma16z(hm, am[0], am[1], am[2], am[3], se, so);
                    mma16z(hx, ax[0], ax[1], ax[2], ax[3], se, so);
                    mma8z(h4, a4[0], a4[1], ONES);
                    SF();
                    if (KPOS == 1) { xpark<1>(xp, pi, sb, sbw, p ^ 1, t16, KA); barv<3, 384>(); }
                    v0 = lds64(a0 + 4096 + t8); v1 = lds64(a0 + 8192 + t8); v2 = lds64(a0 + 12288 + t8); v3 = lds64(a0 + 16384 + t8);
                    WOLD(0, PF2);
                    float s0 = hi ? hx[0] : hm[0], s1 = hi ? hx[2] : hm[2];
                    const float s2 = hi ? h4[2] : h4[0];
                    s0 = (KB & 1) ? -1.0e9f * 11.313708499f : s0;
                    s1 = (KB & 2) ? -1.0e9f * 11.313708499f : s1;
                    int mi = __float_as_int(fmaxf(fmaxf(s0, s2), s1));
                    mi ^= (mi >> 31) & 0x7FFFFFFF;
                    const int mm = __reduce_max_sync(0xFFFFFFFFu, hi ? (int)0x80000000 : mi), mx = __reduce_max_sync(0xFFFFFFFFu, hi ? mi : (int)0x80000000);
                    SF();
                    WOLD(PF2, PF3);
                    SF();
                    mi = hi ? mx : mm;
                    mi ^= (mi >> 31) & 0x7FFFFFFF;
                    const float c2_ = 0.08838834764831845f * 1.4426950408889634f;
                    const float mc = __int_as_float(mi) * c2_;
                    const float e0 = ex2(fmaf(s0, c2_, -mc)), e1 = ex2(fmaf(s1, c2_, -mc)), e2 = ex2(fmaf(s2, c2_, -mc));
                    sts32(sbp + SM_P + (KC >> 25), pack2(e0, e1));
                    sts16(sbp + SM_P + 128 + ((KC >> 16) & 0xFF), pack2(e2, e2));
                    es = __float_as_uint(fmaf(e2, 0.5f, e0 + e1) + 64.f);
                }
                const uint32_t sm = __reduce_add_sync(0xFFFFFFFFu, hi ? 0u : es), sx = __reduce_add_sync(0xFFFFFFFFu, hi ? es : 0u);
                const uint32_t aPr = sb + SM_P + (KD >> 16);
                PT(5);
                bsync<5, 384>();
                uint32_t pm[4], px[4], p4[2];
                ldsm4(pm, aPr);
                MF();
                const uint2 vs = lds64(sb + SM_VS + t8);
                MF();
                ldsm2(p4, aPr + 128);
                MF();
                ldsm4(px, aPr + 64);
                MF();
                sts32f(sb + SM_DN + w * 8 + ((t16 >> 3) & 4), rcp(__uint_as_float((hi ? sx : sm) - 15u * 0x42800000u) - 64.f));
                MF();
                WOLD(PF3, NPF);
                const uint32_t vm0 = hadd2(ov0, vs.x), vm1 = hadd2(ov1, vs.y);
                float oa[4], ob[4];
                mma16z(oa, v0.x, v0.y, v1.x, v1.y, pm[0], pm[1]);
                mma16z(ob, v2.x, v2.y, v3.x, v3.y, pm[2], pm[3]);
                mma8(oa, vm0, vm1, p4[0]);
                stsm2(sbw + SM_OT + (t16 & 511), pack2(oa[0] + ob[0], oa[1] + ob[1]), pack2(oa[2] + ob[2], oa[3] + ob[3]));
                PT(6);
                SF();
                bsync<6, 256>();
                mma16z(ox, v0.x, v0.y, v1.x, v1.y, px[0], px[1]);
                uint32_t b[4][4];
#define OTLD(pp) ldsm4t(b[pp], sbm + SM_OT + t16 + (pp) * 512)
                OTLD(0);
                MF();
                OTLD(1);
                barv<7, 384>();
                mma16(ox, v2.x, v2.y, v3.x, v3.y, px[2], px[3]);
                mma8(ox, vm0, vm1, p4[1]);
                if (p == 1 && s + 1 == nseg) goto done;
                SF();
                uint32_t ar, ae, ahi = xhi;
                float r[2][4];
#pragma unroll
                for (int ks = 0; ks < 8; ks++) {
                    if (ks == 0) WOLD(NPF, NPF + WPF);
                    if (ks == OPOS) { OTLD(2); MF(); }
                    if (ks == OPOS + 2) { OTLD(3); MF(); }
                    if (ks > 0) WOLD(NPF + WPF + 2 * (ks - 1), NPF + WPF + 2 * ks);
                    if (ks == 5) {
                        OPQ(t16);
                        ar = rb + h1 * 16 + t16; ae = rb + h1 + (t16 >> 2);
                        OPQ(ar); OPQ(ahi); OPQ(ae);
                        dn = lds128f(sb + SM_DN + (t16 & 48));
                    }
#pragma unroll
                    for (int mt = 0; mt < 2; mt++) {
                        const int i = ks * 2 + mt;
                        const uint32_t* a = wo[i];
                        if (i < 2) mma16z(r[mt], a[0], a[1], a[2], a[3], b[ks >> 1][2 * (ks & 1)], b[ks >> 1][2 * (ks & 1) + 1]);
                        else mma16(r[mt], a[0], a[1], a[2], a[3], b[ks >> 1][2 * (ks & 1)], b[ks >> 1][2 * (ks & 1) + 1]);
                    }
                    if (NPF + WPF + 2 * ks < 16 || ks < 5) SF();
                }
                const float r0 = dn.x, r1 = dn.z;
                asm volatile("{\n.reg .b64 a;\nmov.b64 a, {%0,%2};\nred.relaxed.gpu.global.add.noftz.v4.bf16x2 [a], {%3,%4,%5,%6};\n"
                             "mov.b64 a, {%1,%2};\nred.relaxed.gpu.global.add.noftz.bf16x2 [a+32768], %7;\n}"
                             ::"r"(ar), "r"(ae), "r"(ahi), "r"(pack2(r[0][0] * r0, r[0][1] * r1)), "r"(pack2(r[0][2] * r0, r[0][3] * r1)),
                               "r"(pack2(r[1][0] * r0, r[1][1] * r1)), "r"(pack2(r[1][2] * r0, 1.f)), "r"(pack2(r[1][3] * r1, 1.f)) : "memory");
                barv<10, 384>();
            }
            SF();
            PT(10);
            OXSTORE(s);
            OPQALL();
        }
    done:
        dn = lds128f(sb + SM_DN + (t16 & 48));
        OXSTORE(nseg - 1);
        barv<9, 384>();
        g_main(sb, w, role, &tmy);
        if (threadIdx.x == 0) PG(0);
    }
}

template <int SC> DEVI void wg_rs128t(float (&d)[64], const uint32_t (&a)[4], uint64_t db) {
    if (SC) asm volatile("wgmma.mma_async.sync.aligned.m64n128k16.f32.bf16.bf16 "
        "{%0,%1,%2,%3,%4,%5,%6,%7,%8,%9,%10,%11,%12,%13,%14,%15,%16,%17,%18,%19,%20,%21,%22,%23,%24,%25,%26,%27,%28,%29,%30,%31,%32,%33,%34,%35,%36,%37,%38,%39,%40,%41,%42,%43,%44,%45,%46,%47,%48,%49,%50,%51,%52,%53,%54,%55,%56,%57,%58,%59,%60,%61,%62,%63}, "
        "{%64,%65,%66,%67}, %68, 1, 1, 1, 1;"
        : D4(+, 0), D4(+, 4), D4(+, 8), D4(+, 12), D4(+, 16), D4(+, 20), D4(+, 24), D4(+, 28), D4(+, 32), D4(+, 36), D4(+, 40), D4(+, 44), D4(+, 48), D4(+, 52), D4(+, 56), D4(+, 60) : "r"(a[0]), "r"(a[1]), "r"(a[2]), "r"(a[3]), "l"(db));
    else asm volatile("wgmma.mma_async.sync.aligned.m64n128k16.f32.bf16.bf16 "
        "{%0,%1,%2,%3,%4,%5,%6,%7,%8,%9,%10,%11,%12,%13,%14,%15,%16,%17,%18,%19,%20,%21,%22,%23,%24,%25,%26,%27,%28,%29,%30,%31,%32,%33,%34,%35,%36,%37,%38,%39,%40,%41,%42,%43,%44,%45,%46,%47,%48,%49,%50,%51,%52,%53,%54,%55,%56,%57,%58,%59,%60,%61,%62,%63}, "
        "{%64,%65,%66,%67}, %68, 0, 1, 1, 1;"
        : D4(=, 0), D4(=, 4), D4(=, 8), D4(=, 12), D4(=, 16), D4(=, 20), D4(=, 24), D4(=, 28), D4(=, 32), D4(=, 36), D4(=, 40), D4(=, 44), D4(=, 48), D4(=, 52), D4(=, 56), D4(=, 60) : "r"(a[0]), "r"(a[1]), "r"(a[2]), "r"(a[3]), "l"(db));
}
template <int SC> DEVI void wg_rs64t(float (&d)[32], const uint32_t (&a)[4], uint64_t db) {
    if (SC) asm volatile("wgmma.mma_async.sync.aligned.m64n64k16.f32.bf16.bf16 "
        "{%0,%1,%2,%3,%4,%5,%6,%7,%8,%9,%10,%11,%12,%13,%14,%15,%16,%17,%18,%19,%20,%21,%22,%23,%24,%25,%26,%27,%28,%29,%30,%31}, "
        "{%32,%33,%34,%35}, %36, 1, 1, 1, 1;"
        : D4(+, 0), D4(+, 4), D4(+, 8), D4(+, 12), D4(+, 16), D4(+, 20), D4(+, 24), D4(+, 28) : "r"(a[0]), "r"(a[1]), "r"(a[2]), "r"(a[3]), "l"(db));
    else asm volatile("wgmma.mma_async.sync.aligned.m64n64k16.f32.bf16.bf16 "
        "{%0,%1,%2,%3,%4,%5,%6,%7,%8,%9,%10,%11,%12,%13,%14,%15,%16,%17,%18,%19,%20,%21,%22,%23,%24,%25,%26,%27,%28,%29,%30,%31}, "
        "{%32,%33,%34,%35}, %36, 0, 1, 1, 1;"
        : D4(=, 0), D4(=, 4), D4(=, 8), D4(=, 12), D4(=, 16), D4(=, 20), D4(=, 24), D4(=, 28) : "r"(a[0]), "r"(a[1]), "r"(a[2]), "r"(a[3]), "l"(db));
}
template <int SC> DEVI void wg_rs40(float (&d)[20], const uint32_t (&a)[4], uint64_t db) {
    if (SC) asm volatile("wgmma.mma_async.sync.aligned.m64n40k16.f32.bf16.bf16 "
        "{%0,%1,%2,%3,%4,%5,%6,%7,%8,%9,%10,%11,%12,%13,%14,%15,%16,%17,%18,%19}, "
        "{%20,%21,%22,%23}, %24, 1, 1, 1, 0;"
        : D4(+, 0), D4(+, 4), D4(+, 8), D4(+, 12), D4(+, 16) : "r"(a[0]), "r"(a[1]), "r"(a[2]), "r"(a[3]), "l"(db));
    else asm volatile("wgmma.mma_async.sync.aligned.m64n40k16.f32.bf16.bf16 "
        "{%0,%1,%2,%3,%4,%5,%6,%7,%8,%9,%10,%11,%12,%13,%14,%15,%16,%17,%18,%19}, "
        "{%20,%21,%22,%23}, %24, 0, 1, 1, 0;"
        : D4(=, 0), D4(=, 4), D4(=, 8), D4(=, 12), D4(=, 16) : "r"(a[0]), "r"(a[1]), "r"(a[2]), "r"(a[3]), "l"(db));
}
template <int SC> DEVI void wg_rs8(float (&d)[4], const uint32_t (&a)[4], uint64_t db) {
    if (SC) asm volatile("wgmma.mma_async.sync.aligned.m64n8k16.f32.bf16.bf16 "
        "{%0,%1,%2,%3}, "
        "{%4,%5,%6,%7}, %8, 1, 1, 1, 0;"
        : D4(+, 0) : "r"(a[0]), "r"(a[1]), "r"(a[2]), "r"(a[3]), "l"(db));
    else asm volatile("wgmma.mma_async.sync.aligned.m64n8k16.f32.bf16.bf16 "
        "{%0,%1,%2,%3}, "
        "{%4,%5,%6,%7}, %8, 0, 1, 1, 0;"
        : D4(=, 0) : "r"(a[0]), "r"(a[1]), "r"(a[2]), "r"(a[3]), "l"(db));
}
template <int SC> DEVI void wg_ss64a(float (&d)[32], uint64_t da, uint64_t db) {
    if (SC) asm volatile("wgmma.mma_async.sync.aligned.m64n64k16.f32.bf16.bf16 "
        "{%0,%1,%2,%3,%4,%5,%6,%7,%8,%9,%10,%11,%12,%13,%14,%15,%16,%17,%18,%19,%20,%21,%22,%23,%24,%25,%26,%27,%28,%29,%30,%31}, "
        "%32, %33, 1, 1, 1, 1, 0;"
        : D4(+, 0), D4(+, 4), D4(+, 8), D4(+, 12), D4(+, 16), D4(+, 20), D4(+, 24), D4(+, 28) : "l"(da), "l"(db));
    else asm volatile("wgmma.mma_async.sync.aligned.m64n64k16.f32.bf16.bf16 "
        "{%0,%1,%2,%3,%4,%5,%6,%7,%8,%9,%10,%11,%12,%13,%14,%15,%16,%17,%18,%19,%20,%21,%22,%23,%24,%25,%26,%27,%28,%29,%30,%31}, "
        "%32, %33, 0, 1, 1, 1, 0;"
        : D4(=, 0), D4(=, 4), D4(=, 8), D4(=, 12), D4(=, 16), D4(=, 20), D4(=, 24), D4(=, 28) : "l"(da), "l"(db));
}

#define G_ROWS 514
__device__ uint4 g_G[64 * G_ROWS * 8];
__device__ uint4 g_GN[64 * 8];
__device__ uint4 g_WN[1152];
#define FS_F2 196608
#define FS_TB (FS_F2 + 8192)
#define FS_NQ (FS_TB + 16384)
#define FS_BAR (FS_NQ + 128)
#define FS_NY (FS_NQ + 1024 + 128)
#define FS_TOTAL (FS_NQ + 3072)
#define F_THREADS 512

DEVI uint32_t cis(int j) {
    const float a = fmaf(__uint_as_float((((j + 1024) << 12) & 0x7FF000) | 0x3F800000), 6.283185307179586f, -9.42477796076938f);
    return pack2(__cosf(a), __sinf(a));
}
DEVI uint32_t cos2(int j0, int j1) {
    const float f = 6.283185307179586f / 2048.f;
    return pack2(__cosf((float)(((j0 + 1024) & 2047) - 1024) * f), __cosf((float)(((j1 + 1024) & 2047) - 1024) * f));
}
DEVI void twid(int j, float& c, float& s) {
    const float a = (float)(((j + 512) & 1023) - 512) * (6.283185307179586f / 1024.f);
    c = __cosf(a) * (1.f / 1024.f);
    s = __sinf(a) * (1.f / 1024.f);
}
template <bool B> struct Bool { static constexpr bool v = B; };
DEVI uint32_t opq(uint32_t& x, uint32_t zero) { OPQ(x); return x; }
DEVI uint32_t tidx() { uint32_t r; asm volatile("mov.u32 %0, %%tid.x;" : "=r"(r)); return r; }
DEVI void tma4d(uint32_t dst, const CUtensorMap* tm, uint32_t bar, int c0, int c1, int c2, int c3) {
    asm volatile("cp.async.bulk.tensor.4d.shared::cluster.global.mbarrier::complete_tx::bytes [%0], [%1, {%3, %4, %5, %6}], [%2];"
                 ::"r"(dst), "l"(tm), "r"(bar), "r"(c0), "r"(c1), "r"(c2), "r"(c3) : "memory");
}
DEVI void tma3s(const CUtensorMap* tm, uint32_t src, int c0, int c1, int c2) {
    asm volatile("cp.async.bulk.tensor.3d.global.shared::cta.bulk_group [%0, {%2, %3, %4}], [%1];" ::"l"(tm), "r"(src), "r"(c0), "r"(c1), "r"(c2) : "memory");
}
DEVI void tma4s(const CUtensorMap* tm, uint32_t src, int c0, int c1, int c2, int c3) {
    asm volatile("cp.async.bulk.tensor.4d.global.shared::cta.bulk_group [%0, {%2, %3, %4, %5}], [%1];"
                 ::"l"(tm), "r"(src), "r"(c0), "r"(c1), "r"(c2), "r"(c3) : "memory");
}
DEVI void bulk_commit() { asm volatile("cp.async.bulk.commit_group;" ::: "memory"); }
DEVI void fence_async() { asm volatile("fence.proxy.async;" ::: "memory"); }
DEVI void fence_smem() { asm volatile("fence.proxy.async.shared::cta;" ::: "memory"); }
DEVI void wgbar(uint32_t q) { asm volatile("bar.sync %0, 128;" ::"r"(q + 2) : "memory"); }
DEVI void grid_arrive(uint32_t* c, uint32_t n) { asm volatile("fence.proxy.async;\nred.release.gpu.global.inc.u32 [%0], %1;" ::"l"(c), "r"(n - 1) : "memory"); }
DEVI void grid_wait(uint32_t* c) {
    uint32_t v;
    int it = 0;
    do {
        asm volatile("ld.acquire.gpu.global.u32 %0, [%1];" : "=r"(v) : "l"(c) : "memory");
        if (++it > (1 << 22)) die(it);
    } while (v);
    fence_async();
}

template <bool INV, class S1, class S2>
DEVI void fft_rows(uint32_t grp, uint32_t q, const uint32_t (&F)[2][4], const float (&tc)[8], const float (&ts)[8], uint32_t so, float fx, uint32_t nq,
                   S1 sh1, S2 sh2) {
    float d[64];
    const uint64_t db = INV ? mkdesc(grp, 1024, 2048) : (mkdesc(grp, 2048, 512) ^ ((uint64_t)3 << 62));
    wg_fence();
    wg_rs128t<0>(d, F[0], db);
    wg_rs128t<1>(d, F[1], db + (INV ? 256 : 64));
    wg_commit();
    SF();
    sh1();
    float4 ny;
    if (INV) ny = lds128f(nq);
    wg_wait<0>();
    if (INV) { d[0] = fmaf(fx, ny.x, d[0]); d[16] = fmaf(fx, ny.y, d[16]); d[32] = fmaf(fx, ny.z, d[32]); d[48] = fmaf(fx, ny.w, d[48]); }
    uint32_t a[2][4][4];
    float e[2][INV ? 16 : 20];
    const uint64_t df = mkdesc(SB0 + FS_F2, 16, 1024);
#pragma unroll
    for (int s = 0; s < 2; s++) {
#pragma unroll
        for (int i = 0; i < 4; i++)
#pragma unroll
            for (int h = 0; h < 2; h++) {
                const float* x = d + (2 * s + h) * 16 + i * 4;
                a[s][i][h] = pack2(fmaf(x[2], ts[2 * i], x[0] * tc[2 * i]), fmaf(x[3], ts[2 * i + 1], x[1] * tc[2 * i + 1]));
                a[s][i][h + 2] = pack2(fmaf(-x[0], ts[2 * i], x[2] * tc[2 * i]), fmaf(-x[1], ts[2 * i + 1], x[3] * tc[2 * i + 1]));
            }
        wg_fence();
#pragma unroll
        for (int i = 0; i < 4; i++) {
            if constexpr (INV) { if (i == 0) wg_rs32<0>(e[s], a[s][i], df); else wg_rs32<1>(e[s], a[s][i], df + i * 2); }
            else { if (i == 0) wg_rs40<0>(e[s], a[s][i], df); else wg_rs40<1>(e[s], a[s][i], df + i * 2); }
        }
        wg_commit();
    }
    SF();
    sh2();
#pragma unroll
    for (int s = 0; s < 2; s++) {
        if (s == 0) wg_wait<1>(); else wg_wait<0>();
        float* x = e[s];
        if constexpr (!INV) {
            x[0] *= fx; x[1] *= fx; x[2] *= fx; x[3] *= fx;
            if (fx != 1.f) sts64(nq + s * 8, pack2(x[16], 0.f), pack2(x[18], 0.f));
        }
        const uint32_t o = grp + (INV ? so + s * 4096 : so ^ (s * 576));
#pragma unroll
        for (int b = 0; b < 2; b++)
            stsm4t(o + b * (INV ? 1024 : 4096), pack2(x[8 * b], x[8 * b + 1]), pack2(x[8 * b + 2], x[8 * b + 3]), pack2(x[8 * b + 4], x[8 * b + 5]),
                   pack2(x[8 * b + 6], x[8 * b + 7]));
    }
}

template <bool INV>
DEVI void fft_gen(uint32_t a, uint32_t n2) {
    const uint32_t tid = tidx(), x = ((tid >> 4) & 24) + (tid & 3), o = (tid & 4) * 128;
    if (INV) {
        const uint32_t r = (tid & 64) * 16 + (tid & 16) * 32 + (tid & 40) * 8 + n2;
        sts128(a + tid * 16, cis(o - r * x), cis(o - (r + 128) * x), cis(o - r * (x + 4)), cis(o - (r + 128) * (x + 4)));
    } else {
        const uint32_t r = 64 * x + n2, k = ((tid >> 2) & 24) + ((tid >> 3) & 3);
        sts128(a + tid * 16, cis(r * k + o), cis(r * (k + 4) + o), cis((r + 256) * k + o), cis((r + 256) * (k + 4) + o));
    }
}
template <bool INV, class S1>
DEVI void fft_cross(uint32_t buf, uint32_t q, uint32_t fa, uint32_t so, uint32_t nq, float (&n)[4], S1 sh1) {
    uint32_t F[4][4];
#pragma unroll
    for (int s = 0; s < 4; s++) { const uint4 v = lds128(fa + s * 2048); F[s][0] = v.x; F[s][1] = v.y; F[s][2] = v.z; F[s][3] = v.w; }
    float d[64];
    const uint64_t db = mkdesc(buf + q * 2048, 1024, 8192), dn = mkdesc(nq, 16, 1024);
    wg_fence();
#pragma unroll
    for (int s = 0; s < 4; s++) { if (s == 0) wg_rs128t<0>(d, F[s], db); else wg_rs128t<1>(d, F[s], db + s * 1024); }
#pragma unroll
    for (int s = 0; s < 4; s++) { if (s == 0) wg_rs8<0>(n, F[s], dn); else wg_rs8<1>(n, F[s], dn + s * 2); }
    wg_commit();
    SF();
    sh1();
    wg_wait<0>();
#pragma unroll
    for (int b = 0; b < 8; b++) {
        const uint32_t o = INV ? so ^ ((b >> 1) * 288 ^ (b & 1) * 32) : (so ^ ((b & 3) * 32)) + (b >> 2) * 1024;
        stsm4(buf + o, pack2(d[8 * b], d[8 * b + 1]), pack2(d[8 * b + 2], d[8 * b + 3]), pack2(d[8 * b + 4], d[8 * b + 5]), pack2(d[8 * b + 6], d[8 * b + 7]));
    }
}

template <bool ODD>
DEVI void fft_filter(uint32_t aw, const float (&e)[32], const float (&o)[32], uint32_t (&u)[4][4], uint32_t (&v)[4][4]) {
#pragma unroll
    for (int s = 0; s < 4; s++) {
        float y[2][2][4];
#pragma unroll
        for (int c = 0; c < 2; c++) {
            float f[4][2];
#pragma unroll
            for (int i = 0; i < 4; i++) {
                const uint32_t a = aw + (i * 32 + s * 8 + c) * 144, x = lds32(a);
                f[i][0] = ODD ? hi_f(x) : lo_f(x);
                f[i][1] = ODD ? lo_f(lds32(a + 4)) : hi_f(x);
            }
#pragma unroll
            for (int h = 0; h < 2; h++) {
                const int x = 8 * s + 2 * h + c;
                const float ar = e[x] + o[x], ai = e[x + 4] + o[x + 4], br = e[x] - o[x], bi = e[x + 4] - o[x + 4];
                const float yr = fmaf(-ai, f[2][h], ar * f[0][h]), yi = fmaf(ar, f[2][h], ai * f[0][h]);
                y[h][c][0] = fmaf(-bi, f[3][h], fmaf(br, f[1][h], yr));
                y[h][c][1] = fmaf(br, f[3][h], fmaf(bi, f[1][h], yi));
                y[h][c][2] = fmaf(2.f, yr, -y[h][c][0]);
                y[h][c][3] = fmaf(2.f, yi, -y[h][c][1]);
            }
        }
#pragma unroll
        for (int h = 0; h < 2; h++) {
            u[s][h] = pack2(y[h][0][0], y[h][1][0]); u[s][h + 2] = pack2(y[h][0][1], y[h][1][1]);
            v[s][h] = pack2(y[h][0][2], y[h][1][2]); v[s][h + 2] = pack2(y[h][0][3], y[h][1][3]);
        }
    }
}

__global__ void __launch_bounds__(F_THREADS, 1)
post_kernel(const __grid_constant__ CUtensorMap tmx, const __grid_constant__ CUtensorMap tmg1, const __grid_constant__ CUtensorMap tmg2,
           const __grid_constant__ CUtensorMap tmwr, const __grid_constant__ CUtensorMap tmwi, const __grid_constant__ CUtensorMap tmy,
           const bf16* __restrict__ wr, const bf16* __restrict__ wi, uint32_t* cnt, uint32_t zero, int nw) {
    extern __shared__ __align__(1024) uint8_t smem[];
    const uint32_t sb = SB0;
    if (smem_u32(smem) != sb) die(1 << 23);
    const uint32_t tid = threadIdx.x, lane = tid & 31, g = lane >> 2, t = lane & 3, j8 = lane & 7, mat = lane >> 3;
    const uint32_t wi_ = __reduce_max_sync(0xFFFFFFFFu, tid >> 5), q = wi_ >> 2, w = wi_ & 3;
    const int cta = blockIdx.x;
    const int nt = cta < 64 ? (64 - cta + nw - 1) / nw : 0;
    const uint32_t bar = sb + FS_BAR;
    if (tid == 0) {
        for (int i = 0; i < 30; i++) mbar_init(bar + i * 8, i < 3 ? 4 : i < 6 ? 16 : i >= 14 && i < 18 ? 2 : 1);
        asm volatile("fence.mbarrier_init.release.cluster;" ::: "memory");
        fence_smem();
    }
    __syncthreads();
#define FT(n)
    FT(0);
#define N2(p) (2 * ((p) & 31) + ((p) >> 5))
#define WLOAD(tk, part) { \
        const uint32_t wd_ = sb + 131072 + q * 18432 + (part) * 9216, wb_ = bar + 112 + q * 8; \
        mbar_expect(wb_, 9216); \
        if ((tk) < 256) tma3d(wd_, (part) ? &tmwi : &tmwr, wb_, ((tk) & 63) * 64, (tk) >> 6, 0); \
        else asm volatile("cp.async.bulk.shared::cluster.global.mbarrier::complete_tx::bytes [%0], [%1], 9216, [%2];" \
                          ::"r"(wd_), "l"(g_WN + (part) * 576), "r"(wb_) : "memory"); }
#define GROW(tk) ((tk) < 256 ? ((tk) >> 5) * 64 + ((tk) & 7) * 8 + (((tk) >> 3) & 3) * 2 : 512)
#define DLOAD(tk, sl) { mbar_expect(bar + 48 + (sl) * 8, 16384); tma3d(sb + (sl) * 16384, &tmg2, bar + 48 + (sl) * 8, 0, GROW(tk), 0); }
#define IO(c) if (w == 3 && (c) && elect())
#define XLOAD1(i, bb) { const uint32_t xb_ = bar + 144 + (bb) * 32 + q * 8; mbar_expect(xb_, 16384); tma4d(sb + (bb) * 65536 + q * 16384, &tmx, xb_, 0, 0, q * 8, N2(cta + (i) * nw)); }
#define GLOAD3(i, bb) { mbar_expect(bar + (bb) * 8, q ? 16384 : 16512); tma3d(sb + (bb) * 65536 + q * 16384, &tmg1, bar + (bb) * 8, 0, q * 128, cta + (i) * nw); \
        if (q == 0) asm volatile("cp.async.bulk.shared::cluster.global.mbarrier::complete_tx::bytes [%0], [%1], 128, [%2];" \
                                 ::"r"(sb + FS_NQ + (bb) * 1024), "l"(g_GN + (cta + (i) * nw) * 8), "r"(bar + (bb) * 8) : "memory"); }
    for (int i = 0; i < 3; i++) IO(i < nt) XLOAD1(i, i);
    for (uint32_t x = tid; x < 40 * 32; x += 512) {
        const uint32_t n = x >> 5, m2 = mat * 8 + t * 2, ri = g & 1;
        const uint32_t c2 = ((n >> 1) & 1) + ((n >> 3) & 1) * 2 + (n & 4) + (n >> 4) * 8;
        const uint32_t v = cos2(m2 * c2 * 64 + ((n & 1) - ri) * 512, (m2 + 1) * c2 * 64 + ((n & 1) - ri) * 512);
        sts32(sb + FS_F2 + n * 128 + ((g ^ (n & 7)) << 4) + t * 4, n < 32 ? v : n == 32 && ri == 0 ? 0xBF003F00u : 0u);
    }
    float tc[8], ts[8];
    uint32_t F[2][4];
    uint32_t c1 = 16 * (w >> 1) + 2 * g + (w & 1);
#pragma unroll
    for (int i = 0; i < 8; i++) {
        twid(c1 * (8 * (i >> 1) + 2 * t + (i & 1)), tc[i], ts[i]);
        const uint32_t m1 = (i >> 1) * 8 + 2 * t;
        F[i >> 2][i & 3] = cos2(c1 * m1 * 64 + (i & 1) * 512, c1 * (m1 + 1) * 64 + (i & 1) * 512);
    }
    {
        const uint32_t kr = (2 * (mat & 1) + (j8 & 1)) ^ ((j8 >> 2) << 1);
        const uint32_t so1 = ((mat >> 1) + 2 * (j8 >> 2)) * 1024 + kr * 128 + (((((j8 >> 1) & 1) * 4 + w) ^ kr) << 4);
        const uint32_t so2 = (2 * w + (mat & 1)) * 8192 + q * 2048 + j8 * 128 + (((mat >> 1) ^ j8) << 4);
        uint32_t so = so1 << 16 | so2;
        const float fx = (tid & 127) == 0 ? 0.5f : 1.f;
        fft_gen<false>(sb + FS_TB, N2(cta));
        fence_smem();
        bsync<1, 512>();
        FT(1);
        int b = 0, bp = 2, ph = 0;
        if (nt) mwait(bar + 144 + q * 8, 0);
        __syncwarp();
        auto step = [&](auto first, auto last, const int i) {
            const uint32_t p = cta + i * nw, bn = 3 - b - bp, tb = (i & 1) * 8192;
            const uint32_t grp = sb + b * 65536 + q * 16384, nq = sb + FS_NQ + b * 1024 + q * 32;
            auto sa = [&]() {
                if constexpr (!decltype(first)::v) {
                    fence_smem();
                    __syncwarp();
                    if (elect()) mbar_arrive(bar + 24);
                }
                IO(i > 1) {
                    mwait(bar + 32, i & 1);
                    tma3s(&tmg1, sb + bn * 65536 + q * 16384, 0, q * 128, p - 2 * nw);
                    bulk_commit();
                }
            };
            auto sb_ = [&]() { if constexpr (!decltype(first)::v) mwait(bar + 24, (i - 1) & 1); };
            if constexpr (!decltype(last)::v) fft_rows<false>(grp, q, F, tc, ts, opq(so, zero) >> 16, fx, nq, sa, sb_);
            else { sa(); __syncwarp(); sb_(); __syncwarp(); }
            if constexpr (!decltype(first)::v) {
                float n[4];
                fft_cross<false>(sb + bp * 65536, q, sb + FS_TB + 8192 - tb + (((tidx() & 127) ^ (q & 1)) << 4), opq(so, zero) & 0xFFFF, sb + FS_NQ + bp * 1024, n, [&]() {
                    fft_gen<false>(sb + FS_TB + tb, N2(p));
                    IO(i >= 2 && i + 1 < nt) {
                        asm volatile("cp.async.bulk.wait_group.read 0;" ::: "memory");
                        XLOAD1(i + 1, bn);
                    }
                });
                if (q == 0) {
                    const uint32_t x = tidx();
                    bf16* z = (bf16*)(g_G + ((p - nw) * G_ROWS + 512) * 8) + (x & 4) * 16 + ((x >> 2) & 24) + ((x >> 3) & 3);
                    asm volatile("{\n.reg .pred p;\n.reg .b16 a, b;\nsetp.eq.u32 p, %2, 0;\nmov.b32 {a, b}, %1;\n@p st.global.u16 [%0], a;\n@p st.global.u16 [%0+8], b;\n}"
                                 ::"l"(z), "r"(pack2(n[0], n[2])), "r"(x & 3) : "memory");
                }
            }
            if constexpr (!decltype(last)::v) {
                fft_rows<false>(grp + 8192, q, F, tc, ts, opq(so, zero) >> 16, fx, nq + 16, [&]() {
                    if constexpr (!decltype(first)::v) {
                        fence_smem();
                        __syncwarp();
                        if (elect()) mbar_arrive(bar + 32);
                    }
                    if ((w == 1 || w == 2) && elect())
                        asm volatile("cp.async.bulk.prefetch.L2.global [%0], 8208;" ::"l"((w == 1 ? wr : wi) + (p * 4 + q) * 4104) : "memory");
                }, [&]() { if (i + 1 < nt) mwait(bar + 144 + bn * 32 + q * 8, bn ? ph : ph ^ 1); });
                bp = b;
                if (++b == 3) { b = 0; ph ^= 1; }
            }
        };
        if (nt) {
            step(Bool<true>(), Bool<false>(), 0);
#pragma unroll 1
            for (int i = 1; i < nt; i++) step(Bool<false>(), Bool<false>(), i);
            step(Bool<false>(), Bool<true>(), nt);
        }
        for (uint32_t x = cta * 512 + tid; x < 4096; x += nw * 512)
            ((bf16*)g_WN)[(x >> 5) * 72 + (x & 16) + (x & 7) * 2 + ((x >> 3) & 1)] = (x < 2048 ? wr : wi)[(x & 2047) * 513 + 512];
        FT(2);
        fence_async();
        bsync<1, 512>();
        IO(nt) { tma3s(&tmg1, sb + bp * 65536 + q * 16384, 0, q * 128, cta + (nt - 1) * nw); bulk_commit(); }
    }
    for (uint32_t x = tid; x < 128 * 32; x += 512) {
        const uint32_t n = (x >> 5) & 63, a = x & 31, k2 = (n >> 4) * 8 + (n & 7);
        sts32(sb + FS_TB + (x >> 5) * 128 + (((a >> 2) ^ (n & 7)) << 4) + (a & 3) * 4, cis((2 * a + (x >> 11)) * k2 * 32 + (n & 8) * 64));
    }
    fence_smem();
    bsync<1, 512>();
    IO(true) {
        asm volatile("cp.async.bulk.wait_group 0;" ::: "memory");
        grid_arrive(cnt, 4 * nw);
        grid_wait(cnt);
        const int tk = cta + q * nw;
        if (tk <= 256) { DLOAD(tk, q); WLOAD(tk, 0); WLOAD(tk, 1); }
    }
    __syncwarp();
    {
        const uint32_t lo = j8 * 128 + (((2 * w + (mat & 1)) ^ j8) << 4);
        const uint32_t aw = sb + 131072 + q * 18432 + t * 288 + w * 32 + g * 4;
        const uint64_t df = mkdesc(sb + FS_TB, 16, 1024);
        const uint64_t da = mkdesc(sb + q * 16384, 16, 1024);
        const uint32_t buf = sb + 65536 + q * 16384;
        int i = 0, tk = cta + q * nw;
        if (tk <= 256) mwait(bar + 48 + q * 8, 0);
        FT(3);
#pragma unroll 1
        for (; tk <= 256; tk += 4 * nw, i++) {
            const bool more = tk + 4 * nw <= 256;
            float e[32], o[32];
            wg_fence();
#pragma unroll
            for (int s = 0; s < 4; s++) { if (s == 0) wg_ss64a<0>(e, da, df); else wg_ss64a<1>(e, da + s * 128, df + s * 2); }
#pragma unroll
            for (int s = 0; s < 4; s++) { if (s == 0) wg_ss64a<0>(o, da + 512, df + 512); else wg_ss64a<1>(o, da + 512 + s * 128, df + 512 + s * 2); }
            wg_commit();
            SF();
            if (i > 0) {
                fence_smem();
                wgbar(q);
                IO(true) { tma3s(&tmg2, buf, 0, GROW(tk - 4 * nw), 0); bulk_commit(); }
            }
            if (w == 2 && more && elect()) mbar_expect(bar + 48 + q * 8, 16384);
            const int gr = GROW(tk + 4 * nw);
            mwait(bar + 112 + q * 8, i & 1);
            wg_wait<0>();
            if (w == 2 && more && elect()) tma3d(sb + q * 16384, &tmg2, bar + 48 + q * 8, 0, gr, 0);
            uint32_t u[4][4], v[4][4];
            if (tk & 8) fft_filter<true>(aw + (tk & 48) / 4, e, o, u, v);
            else fft_filter<false>(aw + (tk & 48) / 4, e, o, u, v);
            wg_fence();
#pragma unroll
            for (int s = 0; s < 4; s++) { if (s == 0) wg_rs64t<0>(e, u[s], df); else wg_rs64t<1>(e, u[s], df + s * 128); }
#pragma unroll
            for (int s = 0; s < 4; s++) { if (s == 0) wg_rs64t<0>(o, v[s], df + 512); else wg_rs64t<1>(o, v[s], df + 512 + s * 128); }
            wg_commit();
            SF();
            IO(true) asm volatile("cp.async.bulk.wait_group.read 0;" ::: "memory");
            wgbar(q);
            if (more) {
                if ((w == 1 || w == 2) && elect()) WLOAD(tk + 4 * nw, w - 1);
                mwait(bar + 48 + q * 8, (i + 1) & 1);
            }
            wg_wait<0>();
#pragma unroll
            for (int s = 0; s < 4; s++) {
                const uint32_t a = buf + (mat >> 1) * 1024 + lo + s * 2048;
                stsm4t(a, pack2(e[8 * s], e[8 * s + 1]), pack2(e[8 * s + 2], e[8 * s + 3]), pack2(e[8 * s + 4], e[8 * s + 5]), pack2(e[8 * s + 6], e[8 * s + 7]));
                stsm4t(a + 8192, pack2(o[8 * s], o[8 * s + 1]), pack2(o[8 * s + 2], o[8 * s + 3]), pack2(o[8 * s + 4], o[8 * s + 5]), pack2(o[8 * s + 6], o[8 * s + 7]));
            }
            if (tk == 256 && w < 2) {
                uint32_t* z = (uint32_t*)g_GN + t * 32 + w * 16 + g;
#pragma unroll
                for (int s = 0; s < 16; s++) {
                    z[(s >> 1) * 128 + (s & 1) * 8] = pack2(e[2 * s], e[2 * s + 1]);
                    z[(s >> 1) * 128 + (s & 1) * 8 + 1024] = pack2(o[2 * s], o[2 * s + 1]);
                }
                fence_async();
            }
        }
        fence_smem();
        wgbar(q);
        IO(true) {
            if (i > 0) { tma3s(&tmg2, buf, 0, GROW(tk - 4 * nw), 0); bulk_commit(); }
            asm volatile("cp.async.bulk.wait_group 0;" ::: "memory");
            grid_arrive(cnt + 1, 4 * nw);
        }
    }
    FT(4);
    bsync<1, 512>();
    {
        for (uint32_t n = wi_; n < 32; n += 16) {
            const uint32_t cl = (mat >> 1) * 16 + t * 4 + (mat & 1), mh = ((n >> 3) & 1) + (n & 7) * 2 + (n & 16);
            sts32(sb + FS_F2 + n * 128 + ((g ^ (n & 7)) << 4) + t * 4, cos2(cl * mh * 64 + (g & 1) * 512, (cl + 2) * mh * 64 + (g & 1) * 512));
        }
        fence_smem();
        c1 = 8 * w + g;
#pragma unroll
        for (int i = 0; i < 8; i++) {
            twid(-c1 * (16 * (i >> 2) + 4 * t + 2 * (i & 1) + ((i >> 1) & 1)), tc[i], ts[i]);
            F[i >> 2][i & 3] = cis((i & 1) * 512 - c1 * ((i >> 1) * 4 + (t ^ (q & 1))) * 64);
        }
        const uint32_t kr = (j8 & 1) ^ ((j8 >> 2) << 1);
        const uint32_t so2 = ((w >> 1) * 4 + (j8 >> 2) * 2 + (w & 1)) * 8192 + (2 * q + (mat & 1)) * 1024 + kr * 128 + (((((j8 >> 1) & 1) * 4 + (mat >> 1)) ^ kr) << 4);
        const uint32_t so1 = (mat & 1) * 2048 + j8 * 128 + ((((mat >> 1) * 4 + w) ^ j8) << 4);
        uint32_t so = so1 << 16 | so2;
        const float fx = t ? 0.f : (g & 1) ? -1.f : 1.f;
        fft_gen<true>(sb + FS_TB, N2(cta));
        bsync<1, 512>();
        IO(true) grid_wait(cnt + 1);
        for (int i = 0; i < 3; i++) IO(i < nt) GLOAD3(i, i);
        __syncwarp();
        int b = 0, bp = 2, ph = 0;
        auto step = [&](auto first, auto last, const int i) {
            const uint32_t p = cta + i * nw, bn = 3 - b - bp, tb = (i & 1) * 8192;
            const uint32_t grp = sb + bp * 65536 + q * 16384, ny = sb + FS_NY + bp * 128 + q * 32;
            auto sb_ = [&]() { if constexpr (!decltype(last)::v) mwait(bar + b * 8, ph); };
            if constexpr (!decltype(first)::v) {
                fft_rows<true>(grp, q, F, tc, ts, opq(so, zero) >> 16, fx, ny, [&]() {
                    if (i > 1) {
                        fence_smem();
                        wgbar(q);
                        IO(true) { tma4s(&tmy, sb + bn * 65536 + q * 16384, 0, 0, q * 8, N2(p - 2 * nw)); bulk_commit(); }
                    }
                }, sb_);
            } else { sb_(); __syncwarp(); }
            if constexpr (decltype(first)::v) FT(5);
            if constexpr (!decltype(last)::v) {
                float n[4];
                fft_cross<true>(sb + b * 65536, q, sb + FS_TB + tb + (tidx() & 127) * 16, opq(so, zero) & 0xFFFF, sb + FS_NQ + b * 1024, n, [&]() {
                    fft_gen<true>(sb + FS_TB + 8192 - tb, N2(p + nw));
                    IO(i >= 2 && i + 1 < nt) {
                        asm volatile("cp.async.bulk.wait_group.read 0;" ::: "memory");
                        GLOAD3(i + 1, bn);
                    }
                });
                if (q == 0) {
                    const uint32_t x = tidx(), a = sb + FS_NY + b * 128 + (x & 64) + (x & 16) * 2 + ((x & 40) >> 1);
                    if ((x & 7) == 0) { sts32f(a, n[0]); sts32f(a + 8, n[2]); }
                }
            }
            auto sc = [&]() {
                if constexpr (!decltype(last)::v) {
                    fence_smem();
                    __syncwarp();
                    if (elect()) mbar_arrive(bar + 24);
                }
            };
            auto sd = [&]() { if constexpr (!decltype(last)::v) mwait(bar + 24, (nt + i) & 1); };
            if constexpr (!decltype(first)::v) fft_rows<true>(grp + 8192, q, F, tc, ts, opq(so, zero) >> 16, fx, ny + 16, sc, sd);
            else { sc(); __syncwarp(); sd(); __syncwarp(); }
            if constexpr (!decltype(last)::v) {
                bp = b;
                if (++b == 3) { b = 0; ph ^= 1; }
            }
        };
        if (nt) {
            step(Bool<true>(), Bool<false>(), 0);
#pragma unroll 1
            for (int i = 1; i < nt; i++) step(Bool<false>(), Bool<false>(), i);
            step(Bool<false>(), Bool<true>(), nt);
        }
        fence_smem();
        wgbar(q);
        IO(nt) { tma4s(&tmy, sb + bp * 65536 + q * 16384, 0, 0, q * 8, N2(cta + (nt - 1) * nw)); bulk_commit(); }
        FT(6);
        IO(true) asm volatile("cp.async.bulk.wait_group 0;" ::: "memory");
    }
}

typedef CUresult (*EncodeFn)(CUtensorMap*, CUtensorMapDataType, cuuint32_t, void*, const cuuint64_t*, const cuuint64_t*,
                             const cuuint32_t*, const cuuint32_t*, CUtensorMapInterleave, CUtensorMapSwizzle,
                             CUtensorMapL2promotion, CUtensorMapFloatOOBfill);

static void make_map(EncodeFn enc, CUtensorMap* m, const void* ptr, int rank, const cuuint64_t* dims, const cuuint64_t* strides,
                     const cuuint32_t* box, CUtensorMapSwizzle sw = CU_TENSOR_MAP_SWIZZLE_128B) {
    cuuint32_t es[4] = {1, 1, 1, 1};
    CUresult r = enc(m, CU_TENSOR_MAP_DATA_TYPE_BFLOAT16, rank, (void*)ptr, dims, strides, box, es, CU_TENSOR_MAP_INTERLEAVE_NONE,
                     sw, CU_TENSOR_MAP_L2_PROMOTION_L2_256B, CU_TENSOR_MAP_FLOAT_OOB_FILL_NONE);
    if (r != CUDA_SUCCESS) fprintf(stderr, "tensor map encode failed: %d\n", (int)r);
}

extern "C" void kernel_launch(void* const* d_in, const int* in_sizes, int n_in, void* d_out, int out_size) {
    const bf16* A_x = (const bf16*)d_in[0];
    const bf16* A_mem0 = (const bf16*)d_in[1];
    const bf16* A_Wq = (const bf16*)d_in[2];
    const bf16* A_Wk = (const bf16*)d_in[3];
    const bf16* A_Wv = (const bf16*)d_in[4];
    const bf16* A_Wo = (const bf16*)d_in[5];
    const bf16* B_x = (const bf16*)d_in[7];
    const bf16* B_wr = (const bf16*)d_in[8];
    const bf16* B_wi = (const bf16*)d_in[9];
    bf16* out = (bf16*)d_out;

    static EncodeFn enc = nullptr;
    static void *pxs = nullptr, *pg = nullptr;
    static int ncl = 64;
    if (!enc) {
        cudaDriverEntryPointQueryResult qr;
        void* fn = nullptr;
        cudaGetDriverEntryPoint("cuTensorMapEncodeTiled", &fn, cudaEnableDefault, &qr);
        enc = (EncodeFn)fn;
        cudaFuncSetAttribute(chain_kernel, cudaFuncAttributeMaxDynamicSharedMemorySize, SM_TOTAL);
        cudaFuncSetAttribute(post_kernel, cudaFuncAttributeMaxDynamicSharedMemorySize, FS_TOTAL);
        cudaGetSymbolAddress(&pxs, g_xs);
        cudaGetSymbolAddress(&pg, g_G);
        cudaLaunchConfig_t lc = {};
        cudaLaunchAttribute at;
        at.id = cudaLaunchAttributeClusterDimension;
        at.val.clusterDim.x = 2; at.val.clusterDim.y = 1; at.val.clusterDim.z = 1;
        lc.gridDim = dim3(132); lc.blockDim = dim3(384); lc.dynamicSmemBytes = SM_TOTAL; lc.attrs = &at; lc.numAttrs = 1;
        int nc = 0;
        if (cudaOccupancyMaxActiveClusters(&nc, chain_kernel, &lc) == cudaSuccess && nc > 64) ncl = nc < 66 ? nc : 66;
    }
    CUtensorMap tmq, tmk, tmv, tmo, tmx, tmb, tmy;
    {
        cuuint64_t d[3] = {64, DM, HD / 64}, st[2] = {HD * 2, 128};
        cuuint32_t bx[3] = {64, 64, 2};
        make_map(enc, &tmq, A_Wq, 3, d, st, bx);
        make_map(enc, &tmk, A_Wk, 3, d, st, bx);
        make_map(enc, &tmv, A_Wv, 3, d, st, bx);
    }
    {
        cuuint64_t d[2] = {DM, HD}, st[1] = {DM * 2};
        cuuint32_t bx[2] = {64, 16}, bx1[2] = {64, 128}, bx2[3] = {64, 64, 2};
        make_map(enc, &tmo, A_Wo, 2, d, st, bx1);
        cuuint64_t d2[3] = {64, HD, DM / 64}, st2[2] = {DM * 2, 128}, d3[2] = {DM, SEQ}, st3[1] = {DM * 4};
        make_map(enc, &tmb, A_Wo, 3, d2, st2, bx2);
        make_map(enc, &tmy, out, 2, d3, st3, bx);
    }
    {
        cuuint64_t d[3] = {64, SEQ, DM / 64}, st[2] = {DM * 2, 128};
        cuuint32_t bx[3] = {64, 8, 4};
        make_map(enc, &tmx, A_x, 3, d, st, bx);
    }
    CUtensorMap fx, fg1, fg2, fwr, fwi, fy;
    {
        cuuint64_t d[4] = {32, 32, 32, 64}, st[3] = {64, 64 * DM * 2, DM * 2};
        cuuint32_t bx[4] = {32, 32, 8, 1};
        make_map(enc, &fx, B_x, 4, d, st, bx, CU_TENSOR_MAP_SWIZZLE_64B);
        cuuint64_t d2[4] = {64, 16, 32, 64}, st2[3] = {128, 64 * 4096, 4096};
        cuuint32_t bx2[4] = {64, 16, 8, 1};
        make_map(enc, &fy, out + DM, 4, d2, st2, bx2);
    }
    {
        cuuint64_t d[3] = {64, G_ROWS, 64}, st[2] = {128, G_ROWS * 128};
        cuuint32_t bx[3] = {64, 128, 1}, bx2[3] = {64, 2, 64};
        make_map(enc, &fg1, pg, 3, d, st, bx);
        make_map(enc, &fg2, pg, 3, d, st, bx2);
        cuuint64_t d2[3] = {8 * 513, 4, 64}, st2[2] = {8 * 513 * 2, 32 * 513 * 2};
        cuuint32_t bx3[3] = {72, 1, 64};
        make_map(enc, &fwr, B_wr, 3, d2, st2, bx3, CU_TENSOR_MAP_SWIZZLE_NONE);
        make_map(enc, &fwi, B_wi, 3, d2, st2, bx3, CU_TENSOR_MAP_SWIZZLE_NONE);
    }
    cudaStream_t st = cudaStreamPerThread;
    const uint64_t xs = ((uint64_t)pxs + XS_BYTES - 1) & ~(uint64_t)(XS_BYTES - 1);
    chain_kernel<<<2 * ncl, 384, SM_TOTAL, st>>>(tmq, tmk, tmv, tmo, tmx, tmb, tmy, A_mem0, A_x, (uint32_t)xs, (uint32_t)(xs >> 32), 0u, NSEG);
    int nw = ncl == 66 ? 4 : 64;
    cudaLaunchConfig_t lc = {};
    cudaLaunchAttribute at;
    at.id = cudaLaunchAttributeProgrammaticStreamSerialization;
    at.val.programmaticStreamSerializationAllowed = 1;
    lc.gridDim = dim3(nw); lc.blockDim = dim3(F_THREADS); lc.dynamicSmemBytes = FS_TOTAL; lc.stream = st; lc.attrs = &at; lc.numAttrs = 1;
    cudaLaunchKernelEx(&lc, post_kernel, fx, fg1, fg2, fwr, fwi, fy, B_wr, B_wi, (uint32_t*)(xs + XO_TK + 256), 0u, nw);
}
```

```cpp
#include <cuda_runtime.h>
#include <cuda_bf16.h>
#include <cuda.h>
#include <stdint.h>
#include <stdio.h>

typedef __nv_bfloat16 bf16;

#define SEQ 2048
#define DM 1024
#define NH 32
#define DH 128
#define NSEG 64
#define HD (NH * DH)

#define XS_BYTES (32u << 20)
__device__ uint4 g_xs[2 * XS_BYTES / 16];
#define XO_R 0u
#define XO_PB (1u << 18)
#define XO_FL (XO_PB + 32768u)
#define XO_TK (XO_FL + 4096u)
#define XO_CQK (1u << 20)
#define XO_CV (2u << 20)
#define XO_XG (4u << 20)
#define XO_OX (16u << 20)
#define GSYNC(n)
#define PG(n)

#define DEVI __device__ __forceinline__

DEVI void die(int it) { asm volatile("st.shared.u32 [%0], %0;" ::"r"(it) : "memory"); }
DEVI uint32_t smem_u32(const void* p) { return (uint32_t)__cvta_generic_to_shared(p); }
DEVI void mbar_init(uint32_t bar, uint32_t cnt) { asm volatile("mbarrier.init.shared::cta.b64 [%0], %1;" ::"r"(bar), "r"(cnt) : "memory"); }
DEVI void mbar_expect(uint32_t bar, uint32_t bytes) { asm volatile("mbarrier.arrive.expect_tx.shared::cta.b64 _, [%0], %1;" ::"r"(bar), "r"(bytes) : "memory"); }
DEVI void mbar_arrive(uint32_t bar) { asm volatile("mbarrier.arrive.shared::cta.b64 _, [%0];" ::"r"(bar) : "memory"); }
DEVI void mbar_wait(uint32_t bar, uint32_t parity) {
    uint32_t done;
    int it = 0;
    do {
        asm volatile("{\n.reg .pred p;\nmbarrier.try_wait.parity.shared::cta.b64 p, [%1], %2;\nselp.u32 %0, 1, 0, p;\n}\n"
                     : "=r"(done) : "r"(bar), "r"(parity) : "memory");
        if (++it > (1 << 22)) die(it);
    } while (!done);
}
DEVI void tma2d(uint32_t dst, const CUtensorMap* tm, uint32_t bar, int c0, int c1) {
    asm volatile("cp.async.bulk.tensor.2d.shared::cluster.global.mbarrier::complete_tx::bytes [%0], [%1, {%3, %4}], [%2];"
                 ::"r"(dst), "l"(tm), "r"(bar), "r"(c0), "r"(c1) : "memory");
}
DEVI void tma3d(uint32_t dst, const CUtensorMap* tm, uint32_t bar, int c0, int c1, int c2) {
    asm volatile("cp.async.bulk.tensor.3d.shared::cluster.global.mbarrier::complete_tx::bytes [%0], [%1, {%3, %4, %5}], [%2];"
                 ::"r"(dst), "l"(tm), "r"(bar), "r"(c0), "r"(c1), "r"(c2) : "memory");
}
DEVI void bulk_g2s(uint32_t dst, uint32_t lo, uint32_t hi, uint32_t bytes, uint32_t bar) {
    asm volatile("{\n.reg .b64 a;\nmov.b64 a, {%1,%2};\ncp.async.bulk.shared::cluster.global.mbarrier::complete_tx::bytes [%0], [a], %3, [%4];\n}"
                 ::"r"(dst), "r"(lo), "r"(hi), "r"(bytes), "r"(bar) : "memory");
}
DEVI void bulk_s2g(uint32_t lo, uint32_t hi, uint32_t src, uint32_t bytes) {
    asm volatile("{\n.reg .b64 a;\nmov.b64 a, {%0,%1};\ncp.async.bulk.global.shared::cta.bulk_group [a], [%2], %3;\ncp.async.bulk.commit_group;\n}"
                 ::"r"(lo), "r"(hi), "r"(src), "r"(bytes) : "memory");
}
DEVI void bulk_red(uint32_t lo, uint32_t hi, uint32_t src, uint32_t bytes) {
    asm volatile("{\n.reg .b64 a;\nmov.b64 a, {%0,%1};\ncp.reduce.async.bulk.global.shared::cta.bulk_group.add.noftz.bf16 [a], [%2], %3;\ncp.async.bulk.commit_group;\n}"
                 ::"r"(lo), "r"(hi), "r"(src), "r"(bytes) : "memory");
}
DEVI bool elect() {
    uint32_t p;
    asm volatile("{\n.reg .pred P;\nelect.sync _|P, 0xFFFFFFFF;\nselp.u32 %0, 1, 0, P;\n}" : "=r"(p));
    return p != 0;
}
DEVI void ldsm4(uint32_t (&r)[4], uint32_t a) {
    asm volatile("ldmatrix.sync.aligned.m8n8.x4.shared.b16 {%0,%1,%2,%3}, [%4];" : "=r"(r[0]), "=r"(r[1]), "=r"(r[2]), "=r"(r[3]) : "r"(a) : "memory");
}
DEVI void ldsm4t(uint32_t (&r)[4], uint32_t a) {
    asm volatile("ldmatrix.sync.aligned.m8n8.x4.trans.shared.b16 {%0,%1,%2,%3}, [%4];" : "=r"(r[0]), "=r"(r[1]), "=r"(r[2]), "=r"(r[3]) : "r"(a) : "memory");
}
DEVI void ldsm2t(uint32_t (&r)[2], uint32_t a) {
    asm volatile("ldmatrix.sync.aligned.m8n8.x2.trans.shared.b16 {%0,%1}, [%2];" : "=r"(r[0]), "=r"(r[1]) : "r"(a) : "memory");
}
DEVI void ldsm2(uint32_t (&r)[2], uint32_t a) {
    asm volatile("ldmatrix.sync.aligned.m8n8.x2.shared.b16 {%0,%1}, [%2];" : "=r"(r[0]), "=r"(r[1]) : "r"(a) : "memory");
}
DEVI void stsm4t(uint32_t a, uint32_t r0, uint32_t r1, uint32_t r2, uint32_t r3) {
    asm volatile("stmatrix.sync.aligned.m8n8.x4.trans.shared.b16 [%0], {%1,%2,%3,%4};" ::"r"(a), "r"(r0), "r"(r1), "r"(r2), "r"(r3) : "memory");
}
DEVI uint32_t ldsm1(uint32_t a) {
    uint32_t r;
    asm volatile("ldmatrix.sync.aligned.m8n8.x1.shared.b16 {%0}, [%1];" : "=r"(r) : "r"(a) : "memory");
    return r;
}
DEVI void stsm4(uint32_t a, uint32_t r0, uint32_t r1, uint32_t r2, uint32_t r3) {
    asm volatile("stmatrix.sync.aligned.m8n8.x4.shared.b16 [%0], {%1,%2,%3,%4};" ::"r"(a), "r"(r0), "r"(r1), "r"(r2), "r"(r3) : "memory");
}
DEVI void stsm2(uint32_t a, uint32_t r0, uint32_t r1) {
    asm volatile("stmatrix.sync.aligned.m8n8.x2.shared.b16 [%0], {%1,%2};" ::"r"(a), "r"(r0), "r"(r1) : "memory");
}
DEVI uint32_t movm(uint32_t a) {
    uint32_t d;
    asm volatile("movmatrix.sync.aligned.m8n8.trans.b16 %0, %1;" : "=r"(d) : "r"(a));
    return d;
}
DEVI void mma16(float (&d)[4], uint32_t a0, uint32_t a1, uint32_t a2, uint32_t a3, uint32_t b0, uint32_t b1) {
    asm volatile("mma.sync.aligned.m16n8k16.row.col.f32.bf16.bf16.f32 {%0,%1,%2,%3}, {%4,%5,%6,%7}, {%8,%9}, {%0,%1,%2,%3};"
                 : "+f"(d[0]), "+f"(d[1]), "+f"(d[2]), "+f"(d[3]) : "r"(a0), "r"(a1), "r"(a2), "r"(a3), "r"(b0), "r"(b1));
}
DEVI void mma16z(float (&d)[4], uint32_t a0, uint32_t a1, uint32_t a2, uint32_t a3, uint32_t b0, uint32_t b1) {
    asm volatile("mma.sync.aligned.m16n8k16.row.col.f32.bf16.bf16.f32 {%0,%1,%2,%3}, {%4,%5,%6,%7}, {%8,%9}, {%10,%10,%10,%10};"
                 : "=f"(d[0]), "=f"(d[1]), "=f"(d[2]), "=f"(d[3]) : "r"(a0), "r"(a1), "r"(a2), "r"(a3), "r"(b0), "r"(b1), "f"(0.f));
}
DEVI void mma8(float (&d)[4], uint32_t a0, uint32_t a1, uint32_t b0) {
    asm volatile("mma.sync.aligned.m16n8k8.row.col.f32.bf16.bf16.f32 {%0,%1,%2,%3}, {%4,%5}, {%6}, {%0,%1,%2,%3};"
                 : "+f"(d[0]), "+f"(d[1]), "+f"(d[2]), "+f"(d[3]) : "r"(a0), "r"(a1), "r"(b0));
}
DEVI void mma8z(float (&d)[4], uint32_t a0, uint32_t a1, uint32_t b0) {
    asm volatile("mma.sync.aligned.m16n8k8.row.col.f32.bf16.bf16.f32 {%0,%1,%2,%3}, {%4,%5}, {%6}, {%7,%7,%7,%7};"
                 : "=f"(d[0]), "=f"(d[1]), "=f"(d[2]), "=f"(d[3]) : "r"(a0), "r"(a1), "r"(b0), "f"(0.f));
}
DEVI uint32_t pack2(float lo, float hi) {
    uint32_t r;
    asm("cvt.rn.bf16x2.f32 %0, %1, %2;" : "=r"(r) : "f"(hi), "f"(lo));
    return r;
}
DEVI uint32_t hadd2(uint32_t a, uint32_t b) {
    uint32_t r;
    asm("add.rn.bf16x2 %0, %1, %2;" : "=r"(r) : "r"(a), "r"(b));
    return r;
}
DEVI float lo_f(uint32_t x) { return __uint_as_float(x << 16); }
DEVI float hi_f(uint32_t x) { return __uint_as_float(x & 0xFFFF0000u); }
template <uint32_t OFF> DEVI uint4 ldg4(uint32_t lo, uint32_t hi) {
    uint4 v;
    asm volatile("{\n.reg .b64 a;\nmov.b64 a, {%4,%5};\nld.relaxed.gpu.global.v4.u32 {%0,%1,%2,%3}, [a+%6];\n}"
                 : "=r"(v.x), "=r"(v.y), "=r"(v.z), "=r"(v.w) : "r"(lo), "r"(hi), "n"(OFF) : "memory");
    return v;
}
template <uint32_t OFF> DEVI uint2 ldg2(uint32_t lo, uint32_t hi) {
    uint2 v;
    asm volatile("{\n.reg .b64 a;\nmov.b64 a, {%2,%3};\nld.relaxed.gpu.global.v2.u32 {%0,%1}, [a+%4];\n}"
                 : "=r"(v.x), "=r"(v.y) : "r"(lo), "r"(hi), "n"(OFF) : "memory");
    return v;
}
template <uint32_t OFF> DEVI uint32_t ldg1(uint32_t lo, uint32_t hi) {
    uint32_t v;
    asm volatile("{\n.reg .b64 a;\nmov.b64 a, {%1,%2};\nld.relaxed.gpu.global.u32 %0, [a+%3];\n}" : "=r"(v) : "r"(lo), "r"(hi), "n"(OFF) : "memory");
    return v;
}
template <uint32_t OFF> DEVI void stg1(uint32_t lo, uint32_t hi, uint32_t a) {
    asm volatile("{\n.reg .b64 a;\nmov.b64 a, {%0,%1};\nst.relaxed.gpu.global.u32 [a+%3], %2;\n}" ::"r"(lo), "r"(hi), "r"(a), "n"(OFF) : "memory");
}
template <uint32_t OFF> DEVI void stg4(uint32_t lo, uint32_t hi, uint32_t a, uint32_t b, uint32_t c, uint32_t d) {
    asm volatile("{\n.reg .b64 a;\nmov.b64 a, {%0,%1};\nst.relaxed.gpu.global.v4.u32 [a+%6], {%2,%3,%4,%5};\n}"
                 ::"r"(lo), "r"(hi), "r"(a), "r"(b), "r"(c), "r"(d), "n"(OFF) : "memory");
}
template <uint32_t OFF> DEVI void stg2(uint32_t lo, uint32_t hi, uint32_t a, uint32_t b) {
    asm volatile("{\n.reg .b64 a;\nmov.b64 a, {%0,%1};\nst.relaxed.gpu.global.v2.u32 [a+%4], {%2,%3};\n}"
                 ::"r"(lo), "r"(hi), "r"(a), "r"(b), "n"(OFF) : "memory");
}
DEVI uint32_t tagx2(uint32_t a, uint32_t b, uint32_t t) { uint32_t r; asm("lop3.b32 %0, %1, %2, %3, 0x7E;" : "=r"(r) : "r"(a), "r"(b), "r"(t)); return r; }
DEVI uint32_t tagx1(uint32_t a, uint32_t b, uint32_t t) { uint32_t r; asm("lop3.b32 %0, %1, %2, %3, 0xF6;" : "=r"(r) : "r"(a), "r"(b), "r"(t)); return r; }
DEVI uint32_t or3(uint32_t a, uint32_t b, uint32_t c) { uint32_t r; asm("lop3.b32 %0, %1, %2, %3, 0xFE;" : "=r"(r) : "r"(a), "r"(b), "r"(c)); return r; }
DEVI bool any_bad(uint32_t x) { return __any_sync(0xFFFFFFFFu, (x & 1u) != 0); }
DEVI uint32_t settag(uint32_t x, uint32_t tag) { return (x & ~1u) | tag; }
DEVI void sts32f(uint32_t a, float v) { asm volatile("st.shared.f32 [%0], %1;" ::"r"(a), "f"(v) : "memory"); }
DEVI void sts32(uint32_t a, uint32_t v) { asm volatile("st.shared.u32 [%0], %1;" ::"r"(a), "r"(v) : "memory"); }
DEVI void sts16(uint32_t a, uint32_t v) { asm volatile("st.shared.u16 [%0], %1;" ::"r"(a), "h"((unsigned short)v) : "memory"); }
DEVI void sts64(uint32_t a, uint32_t x, uint32_t y) { asm volatile("st.shared.v2.u32 [%0], {%1,%2};" ::"r"(a), "r"(x), "r"(y) : "memory"); }
DEVI void sts128(uint32_t a, uint32_t x, uint32_t y, uint32_t z, uint32_t w) {
    asm volatile("st.shared.v4.u32 [%0], {%1,%2,%3,%4};" ::"r"(a), "r"(x), "r"(y), "r"(z), "r"(w) : "memory");
}
DEVI float4 lds128f(uint32_t a) {
    float4 v;
    asm volatile("ld.shared.v4.f32 {%0,%1,%2,%3}, [%4];" : "=f"(v.x), "=f"(v.y), "=f"(v.z), "=f"(v.w) : "r"(a) : "memory");
    return v;
}
DEVI uint4 lds128(uint32_t a) {
    uint4 v;
    asm volatile("ld.shared.v4.u32 {%0,%1,%2,%3}, [%4];" : "=r"(v.x), "=r"(v.y), "=r"(v.z), "=r"(v.w) : "r"(a) : "memory");
    return v;
}
DEVI uint2 lds64(uint32_t a) {
    uint2 v;
    asm volatile("ld.shared.v2.u32 {%0,%1}, [%2];" : "=r"(v.x), "=r"(v.y) : "r"(a) : "memory");
    return v;
}
DEVI uint32_t lds32(uint32_t a) {
    uint32_t v;
    asm volatile("ld.shared.u32 %0, [%1];" : "=r"(v) : "r"(a) : "memory");
    return v;
}
DEVI float ex2(float x) { float r; asm("ex2.approx.ftz.f32 %0, %1;" : "=f"(r) : "f"(x)); return r; }
DEVI float rcp(float x) { float r; asm("rcp.approx.ftz.f32 %0, %1;" : "=f"(r) : "f"(x)); return r; }
DEVI uint32_t clk() { uint32_t c; asm volatile("mov.u32 %0, %%clock;" : "=r"(c)::"memory"); return c; }

DEVI uint64_t mkdesc(uint32_t addr, uint32_t lbo, uint32_t sbo) {
    return (uint64_t)((addr & 0x3FFFF) >> 4) | ((uint64_t)(lbo >> 4) << 16) | ((uint64_t)(sbo >> 4) << 32) | ((uint64_t)1 << 62);
}
DEVI void wg_fence() { asm volatile("wgmma.fence.sync.aligned;" ::: "memory"); }
DEVI void wg_commit() { asm volatile("wgmma.commit_group.sync.aligned;" ::: "memory"); }
template <int N> DEVI void wg_wait() { asm volatile("wgmma.wait_group.sync.aligned %0;" ::"n"(N) : "memory"); }
template <int SC>
DEVI void wg_rs32(float (&d)[16], const uint32_t (&a)[4], uint64_t db) {
    if (SC) {
        asm volatile("wgmma.mma_async.sync.aligned.m64n32k16.f32.bf16.bf16 "
                     "{%0,%1,%2,%3,%4,%5,%6,%7,%8,%9,%10,%11,%12,%13,%14,%15}, {%16,%17,%18,%19}, %20, 1, 1, 1, 0;"
                     : "+f"(d[0]), "+f"(d[1]), "+f"(d[2]), "+f"(d[3]), "+f"(d[4]), "+f"(d[5]), "+f"(d[6]), "+f"(d[7]),
                       "+f"(d[8]), "+f"(d[9]), "+f"(d[10]), "+f"(d[11]), "+f"(d[12]), "+f"(d[13]), "+f"(d[14]), "+f"(d[15])
                     : "r"(a[0]), "r"(a[1]), "r"(a[2]), "r"(a[3]), "l"(db));
    } else {
        asm volatile("wgmma.mma_async.sync.aligned.m64n32k16.f32.bf16.bf16 "
                     "{%0,%1,%2,%3,%4,%5,%6,%7,%8,%9,%10,%11,%12,%13,%14,%15}, {%16,%17,%18,%19}, %20, 0, 1, 1, 0;"
                     : "=f"(d[0]), "=f"(d[1]), "=f"(d[2]), "=f"(d[3]), "=f"(d[4]), "=f"(d[5]), "=f"(d[6]), "=f"(d[7]),
                       "=f"(d[8]), "=f"(d[9]), "=f"(d[10]), "=f"(d[11]), "=f"(d[12]), "=f"(d[13]), "=f"(d[14]), "=f"(d[15])
                     : "r"(a[0]), "r"(a[1]), "r"(a[2]), "r"(a[3]), "l"(db));
    }
}

#define NA 12
#define NPF 6
#define PF1 2
#define PF2 2
#define PF3 5
#define WPF 2
#define VPF 2
#define VORD (NA == 12 ? 0x01234567 : NA == 10 ? 0x50123467 : NA == 8 ? 0x40125367 : 0x30142567)
#define WV_BOX ((16 - NA) * 2048)
#define WO_BOX 16384
#define SM_WV 0
#define SM_WO (2 * WV_BOX)
#define SM_X (SM_WO + 4 * WO_BOX)
#define SM_XO (SM_X + 32768)
#define SM_MEMT (SM_XO + 12288)
#define SM_OT (SM_MEMT + 4096)
#define SM_VS (SM_OT + 2048)
#define SM_P (SM_VS + 2048)
#define SM_DN (SM_P + 1792)
#define SM_PROF (SM_P + 2048)
#define SM_ST (SM_X + 65536)
#define SM_KV SM_ST
#define SM_SP (SM_KV + 18432)
#define SM_TR (SM_ST + 32768)
#define SM_PI (SM_ST + 65536)
#define SM_BAR (SM_PI + 12288)
#define SM_TOTAL (SM_BAR + 512)
static_assert(NA == 12, "start-up chunks");
static_assert(SM_TOTAL <= 232448, "smem");
#define BAR_XA 32
#define BAR_KV 40
#define BAR_PI 48
#define BAR_RO 64
#define BAR_WF 256
#define BAR_WE 384
#define SM_ROLE (SM_BAR + 72)

#define SPIN_LIMIT (1 << 20)
#define RPOS 24
#define OPOS 2
#define ASF 0
#define KPOS 0
#define CPOS 1
#define DLY_V 400
#define NPRB 2
#define PW 4
#define ZD 0
#define FTM 2
#define XPF 1
#define WOP 2
#define WIN 2
#define EPD 1300
#define ASP 4
#define EPF 0
#define CFAR 1

template <int ID, int N> DEVI void bsync() { asm volatile("bar.sync %0, %1;" ::"n"(ID), "n"(N) : "memory"); }
template <int ID, int N> DEVI void barv() { asm volatile("bar.arrive %0, %1;" ::"n"(ID), "n"(N) : "memory"); }

#define PT(n)
#define PC(n, v)
#define PDUMP()
#define REFRESH() asm volatile("xor.b32 %0, %0, %1;" : "+r"(l16) : "r"(zero))
#define OPQ(x) asm volatile("xor.b32 %0, %0, %1;" : "+r"(x) : "r"(zero))
#define KEEP(x, a, b, c, d) asm volatile("{\n.reg .b32 t;\nlop3.b32 t, %1, %2, %3, 0x80;\nlop3.b32 t, t, %4, %5, 0x80;\nxor.b32 %0, %0, t;\n}" \
                                         : "+r"(x) : "r"(a), "r"(b), "r"(c), "r"(d), "r"(zero))
#define SF() asm volatile("pmevent 1;" ::: "memory")
#define MF() __syncwarp()
#define SB0 1024u

#define XDOFF(ks) ((((ks) >> 2) * 1024 + ((ks) & 3) * 32) >> 4)
template <int SC>
DEVI void wg_ss32t(float (&d)[16], uint64_t da, uint64_t db) {
    if (SC) {
        asm volatile("wgmma.mma_async.sync.aligned.m64n32k16.f32.bf16.bf16 "
                     "{%0,%1,%2,%3,%4,%5,%6,%7,%8,%9,%10,%11,%12,%13,%14,%15}, %16, %17, 1, 1, 1, 1, 0;"
                     : "+f"(d[0]), "+f"(d[1]), "+f"(d[2]), "+f"(d[3]), "+f"(d[4]), "+f"(d[5]), "+f"(d[6]), "+f"(d[7]),
                       "+f"(d[8]), "+f"(d[9]), "+f"(d[10]), "+f"(d[11]), "+f"(d[12]), "+f"(d[13]), "+f"(d[14]), "+f"(d[15])
                     : "l"(da), "l"(db));
    } else {
        asm volatile("wgmma.mma_async.sync.aligned.m64n32k16.f32.bf16.bf16 "
                     "{%0,%1,%2,%3,%4,%5,%6,%7,%8,%9,%10,%11,%12,%13,%14,%15}, %16, %17, 0, 1, 1, 1, 0;"
                     : "=f"(d[0]), "=f"(d[1]), "=f"(d[2]), "=f"(d[3]), "=f"(d[4]), "=f"(d[5]), "=f"(d[6]), "=f"(d[7]),
                       "=f"(d[8]), "=f"(d[9]), "=f"(d[10]), "=f"(d[11]), "=f"(d[12]), "=f"(d[13]), "=f"(d[14]), "=f"(d[15])
                     : "l"(da), "l"(db));
    }
}

DEVI void delay_until(uint32_t t0, uint32_t d) { t0 += d; while (clk() < t0) {} }

template <int I0, int I1>
DEVI void xmma(float (&xa)[16], float (&xb)[16], uint32_t w, int ps, uint32_t zero, const uint32_t (&Wq)[16][4], const uint32_t (&Wk)[16][4],
               const uint32_t (&Wv)[NA][4]) {
    const uint64_t xd = mkdesc(SB0 + SM_X, 16, 4096) + (ps & 1) * 1024, vd = mkdesc(SB0 + SM_WV, 8192, 1024);
    uint32_t vo = (w >> 2) * (WV_BOX / 16);
    if (I0 < 16 - NA) OPQ(vo);
#pragma unroll
    for (int i = I0; i < I1; i++) {
        if (i == 0) wg_ss32t<0>(xb, (vd & ~0xFFFFFFFFull) | ((uint32_t)vd + vo), xd + XDOFF(NA));
        else if (i < 16 - NA) wg_ss32t<1>(xb, (vd & ~0xFFFFFFFFull) | ((uint32_t)vd + i * 128 + vo), xd + XDOFF(NA + i));
        else if (i == 16 - NA) wg_rs32<0>(xa, Wq[0], xd);
        else if (i < 32 - NA) wg_rs32<1>(xa, Wq[(i + NA) & 15], xd + XDOFF((i + NA) & 15));
        else if (i < 32) wg_rs32<1>(xb, Wv[(i + NA) & 15], xd + XDOFF((i + NA) & 15));
        else if (i == 32) wg_rs32<0>(xa, Wk[0], xd);
        else wg_rs32<1>(xa, Wk[i & 15], xd + XDOFF(i & 15));
    }
    wg_commit();
}
#define XMMA(I0, I1) xmma<(I0), (I1)>(xa, xb, w, p ^ 1, zero, Wq, Wk, Wv)
DEVI void wg_done(float (&d)[16]) {
    asm volatile("" : "+f"(d[0]), "+f"(d[1]), "+f"(d[2]), "+f"(d[3]), "+f"(d[4]), "+f"(d[5]), "+f"(d[6]), "+f"(d[7]),
                      "+f"(d[8]), "+f"(d[9]), "+f"(d[10]), "+f"(d[11]), "+f"(d[12]), "+f"(d[13]), "+f"(d[14]), "+f"(d[15]) :: "memory");
}
template <int M>
DEVI void xpack(uint32_t (&xp)[8], float (&xa)[16]) {
    wg_done(xa);
#pragma unroll
    for (int i = 0; i < 4; i++) {
        xp[2 * i] = pack2(xa[4 * i], xa[4 * i + (M < 2 ? 2 : 1)]);
        xp[2 * i + 1] = pack2(xa[4 * i + (M < 2 ? 1 : 2)], xa[4 * i + 3]);
    }
}
template <int M>
DEVI uint4 xpeer(uint32_t sb, int ps, uint32_t t16) { return lds128(sb + SM_PI - ((ps & 1) ^ 1) * 12288 + M * 4096 + t16); }
DEVI void xadd(uint32_t (&xp)[8], const uint4& pi) {
    xp[0] = hadd2(xp[0], pi.x); xp[1] = hadd2(xp[1], pi.y); xp[2] = hadd2(xp[2], pi.z); xp[3] = hadd2(xp[3], pi.w);
}
template <int M>
DEVI void xsend(const uint32_t (&xp)[8], uint32_t sb, int ps, uint32_t t16) {
    asm volatile("st.async.weak.shared::cluster.mbarrier::complete_tx::bytes.v4.b32 [%0], {%1,%2,%3,%4}, [%5];"
                 ::"r"((sb ^ 0x1000000) + SM_PI - (ps & 1) * 12288 + M * 4096 + t16), "r"(xp[4]), "r"(xp[5]), "r"(xp[6]), "r"(xp[7]),
                   "r"((sb ^ 0x1000000) + SM_BAR + BAR_PI + (ps & 1) * 8) : "memory");
}
template <int M>
DEVI void xstore(const uint32_t (&xp)[8], uint32_t sb, uint32_t sbw, int ps, uint32_t t16, uint32_t KA) {
    const uint32_t a = SM_XO + M * 2048 + (M < 2 ? (KA & 0xFF) + sbw : (t16 >> 1) + sb);
    sts64(a, xp[0], xp[1]);
    sts64(a + 6144, xp[2], xp[3]);
    xsend<M>(xp, sb, ps, t16);
}
template <int M>
DEVI void xpark(uint32_t (&xp)[8], const uint4& pi, uint32_t sb, uint32_t sbw, int ps, uint32_t t16, uint32_t KA) {
    xadd(xp, pi);
    xstore<M>(xp, sb, sbw, ps, t16, KA);
}
template <uint32_t OFF> DEVI void red2(uint32_t lo, uint32_t hi, uint32_t a, uint32_t b) {
    asm volatile("{\n.reg .b64 a;\nmov.b64 a, {%0,%1};\nred.relaxed.gpu.global.add.noftz.v2.bf16x2 [a+%4], {%2,%3};\n}"
                 ::"r"(lo), "r"(hi), "r"(a), "r"(b), "n"(OFF) : "memory");
}
template <int M, int N>
DEVI void xstart(uint32_t sb, uint32_t w, uint32_t ga, uint32_t xhi, uint32_t j, uint32_t t16, uint32_t KA, const uint32_t (&W)[N][4]) {
    float xa[16], xb[16];
    uint32_t xp[8];
    auto pass = [&](float (&d)[16], int i, int k0, int k1) {
        const uint64_t xd = mkdesc(SB0 + SM_X + (i ? i + 1 : 0) * 16384, 16, 4096), vd = mkdesc(SB0 + SM_WV, 8192, 1024) + (w >> 2) * (WV_BOX / 16);
#pragma unroll
        for (int k = k0; k < k1; k++) {
            if (k == 0) wg_rs32<0>(d, W[0], xd);
            else if (k < N) wg_rs32<1>(d, W[k < N ? k : 0], xd + XDOFF(k));
            else wg_ss32t<1>(d, vd + (k - N) * 128, xd + XDOFF(k));
        }
        wg_commit();
    };
    wg_fence();
    pass(xa, 0, 0, 16);
    pass(xb, 1, 0, ASP);
    if (M == 0) bsync<5, 288>();
    ga += M < 2 ? (KA & 0xFF) + w * 256 : t16 >> 1;
    constexpr uint32_t O = XO_XG + M * 2048, SG = 128 * 6144;
    wg_wait<1>();
    xpack<M>(xp, xa);
    red2<O>(ga, xhi, xp[0], xp[1]); red2<O + 6144>(ga, xhi, xp[2], xp[3]); red2<O + 12288>(ga, xhi, xp[4], xp[5]); red2<O + 18432>(ga, xhi, xp[6], xp[7]);
    if (M == 2) barv<3, 320>();
    wg_fence();
    pass(xb, 1, ASP, 16);
    pass(xa, 2, 0, 16);
    wg_wait<1>();
    xpack<M>(xp, xb);
    red2<O + SG>(ga, xhi, xp[0], xp[1]); red2<O + SG + 6144>(ga, xhi, xp[2], xp[3]);
    red2<O + SG + 12288>(ga, xhi, xp[4], xp[5]); red2<O + SG + 18432>(ga, xhi, xp[6], xp[7]);
    wg_wait<0>();
    xpack<M>(xp, xa);
    red2<O + 2 * SG>(ga + j * 6144, xhi, xp[0], xp[1]);
    red2<O + 2 * SG>(ga + (j ^ 1) * 6144, xhi, xp[2], xp[3]);
    xsend<M>(xp, sb, 0, t16);
}
DEVI void piwait(uint32_t sb, int p, int ps) { mbar_wait(sb + SM_BAR + BAR_PI + p * 8, ((ps + 2) >> 1) & 1); }

DEVI uint32_t par(uint32_t off) { return __popc(off & 0xB2000u) & 1; }
DEVI uint32_t probe(uint32_t lo, uint32_t hi) {
    uint32_t best = 0xFFFFFFFFu, x = 0;
    stg4<0>(lo, hi, 0, 0, 0, 0);
    stg4<16>(lo, hi, 0, 0, 0, 0);
#pragma unroll 1
    for (int r = 0; r < NPRB; r++) {
        const uint32_t t0 = clk();
        asm volatile("{\n.reg .b64 a;\nmov.b64 a, {%1,%2};\natom.relaxed.gpu.global.add.u32 %0, [a], 2;\n}" : "=r"(x) : "r"(lo), "r"(hi) : "memory");
        if (x == 0xFFFFFFFFu) die(1 << 23);
        best = min(best, clk() - t0);
    }
    return best;
}

DEVI void xload(uint32_t sb, uint32_t u, uint32_t j, int ps, const CUtensorMap* tmx) {
    if (elect()) {
        const uint32_t sg = ps + 4 - (u & 1) + (u >> 1);
        mbar_expect(sb + SM_BAR + BAR_XA, sg < NSEG ? 4096 : 0);
        if (sg < NSEG) tma3d(sb + SM_X + (ps & 1) * 16384 + u * 4096, tmx, sb + SM_BAR + BAR_XA, 0, sg * 32 + (j ^ ((u & 1) * 2 + (u >> 1))) * 8, j * 4);
    }
}
DEVI uint32_t rpage(uint32_t j, int s) { return (s & 3) * 65536 + (j & 1) * 8192 + (((s ^ (s >> 1) ^ j ^ (j >> 1)) & 1) << 12); }

#define RLOAD() { m0 = ldg4<XO_R>(a, ah); n0 = ldg4<XO_R + 16384>(a, ah); e0 = ldg1<XO_R + 32768>(e, eh); f0 = ldg1<XO_R + 33792>(e, eh); }
DEVI bool ruse(uint32_t a, const uint4& m0, const uint4& n0, uint32_t e0, uint32_t f0) {
    const uint32_t a0 = hadd2(m0.w, n0.w), b0 = hadd2(e0, f0);
    stsm4(a, hadd2(m0.x, n0.x), hadd2(m0.y, n0.y), hadd2(m0.z, n0.z), __byte_perm(a0, b0, 0x5410));
    return __any_sync(0xFFFFFFFFu, (a0 & b0 & 0x42000000u) != 0x42000000u);
}

#define GST(i) (SM_WO + (i) * 49152)
#define BAR_GF 128
#define BAR_GE (BAR_GF + 64)
#define BAR_GX (BAR_GE + 32)
#define D4(c, i) #c "f"(d[i]), #c "f"(d[i + 1]), #c "f"(d[i + 2]), #c "f"(d[i + 3])
#define D16(c, i) D4(c, i), D4(c, i + 4), D4(c, i + 8), D4(c, i + 12)
DEVI void mwait(uint32_t bar, uint32_t parity) {
    asm volatile("{\n.reg .pred p;\n.reg .b32 c;\nmbarrier.try_wait.parity.shared::cta.b64 p, [%0], %1;\n@p bra.uni D;\nmov.b32 c, 0;\n"
                 "L:\nadd.u32 c, c, 1;\nsetp.gt.u32 p, c, 4194304;\n@p st.shared.u32 [c], c;\n"
                 "mbarrier.try_wait.parity.shared::cta.b64 p, [%0], %1;\n@!p bra.uni L;\nD:\n}" ::"r"(bar), "r"(parity) : "memory");
}
DEVI void wg_ss256t(float (&d)[128], uint64_t da, uint64_t db) {
    asm volatile("wgmma.mma_async.sync.aligned.m64n256k16.f32.bf16.bf16 "
        "{%0,%1,%2,%3,%4,%5,%6,%7,%8,%9,%10,%11,%12,%13,%14,%15,%16,%17,%18,%19,%20,%21,%22,%23,%24,%25,%26,%27,%28,%29,%30,%31,%32,%33,%34,%35,%36,%37,%38,%39,%40,%41,%42,%43,%44,%45,%46,%47,%48,%49,%50,%51,%52,%53,%54,%55,%56,%57,%58,%59,%60,%61,%62,%63,%64,%65,%66,%67,%68,%69,%70,%71,%72,%73,%74,%75,%76,%77,%78,%79,%80,%81,%82,%83,%84,%85,%86,%87,%88,%89,%90,%91,%92,%93,%94,%95,%96,%97,%98,%99,%100,%101,%102,%103,%104,%105,%106,%107,%108,%109,%110,%111,%112,%113,%114,%115,%116,%117,%118,%119,%120,%121,%122,%123,%124,%125,%126,%127}, "
        "%128, %129, 1, 1, 1, 1, 1;"
        : D16(+, 0), D16(+, 16), D16(+, 32), D16(+, 48), D16(+, 64), D16(+, 80), D16(+, 96), D16(+, 112) : "l"(da), "l"(db));
}
template <int O, int KB> DEVI void g_half(float (&d)[64], uint64_t da) {
    const uint64_t db = mkdesc(SB0 + GST(KB & 3) + 16384 + O * 256, 8192, 1024);
#pragma unroll
    for (int k = 0; k < 4; k++)
        asm volatile("wgmma.mma_async.sync.aligned.m64n128k16.f32.bf16.bf16 "
            "{%0,%1,%2,%3,%4,%5,%6,%7,%8,%9,%10,%11,%12,%13,%14,%15,%16,%17,%18,%19,%20,%21,%22,%23,%24,%25,%26,%27,%28,%29,%30,%31,%32,%33,%34,%35,%36,%37,%38,%39,%40,%41,%42,%43,%44,%45,%46,%47,%48,%49,%50,%51,%52,%53,%54,%55,%56,%57,%58,%59,%60,%61,%62,%63}, "
            "%64, %65, 1, 1, 1, 1, 1;"
            : D16(+, 0), D16(+, 16), D16(+, 32), D16(+, 48) : "l"(da + (KB & 3) * 3072 + k * 16), "l"(db + k * 128));
}
DEVI void g_load(uint32_t sb, uint32_t u, uint32_t role, uint32_t kb, uint32_t xlo, uint32_t xhi, const CUtensorMap* tmb) {
    const uint32_t st = kb & 3, bar = sb + SM_BAR + BAR_GF + u * 32 + st * 8, dst = sb + GST(st), k = (role & 1) * 32 + kb;
    if (!elect()) return;
    mbar_expect(bar, u ? 8192 : 40960);
    bulk_g2s(dst + u * 8192, xlo + XO_OX + (k * 16 + (role >> 3)) * 16384 + u * 8192, xhi, 8192, bar);
    if (u == 0) {
        tma3d(dst + 16384, tmb, bar, 0, k * 64, ((role & 7) ^ 1) * 2);
        tma3d(dst + 32768, tmb, bar, 0, k * 64, (role & 7) * 2);
    }
}
DEVI void g_arrive(uint32_t a, uint32_t xhi, uint32_t n) {
    if (elect()) asm volatile("{\n.reg .b64 a;\nmov.b64 a, {%0,%1};\nred.release.gpu.global.inc.u32 [a], %2;\n}" ::"r"(a), "r"(xhi), "r"(n - 1) : "memory");
}
DEVI void g_wait(uint32_t a, uint32_t xhi) {
    int it = 0;
    uint32_t v;
    do {
        asm volatile("{\n.reg .b64 a;\nmov.b64 a, {%1,%2};\nld.acquire.gpu.global.u32 %0, [a];\n}" : "=r"(v) : "r"(a), "r"(xhi) : "memory");
        if (++it > SPIN_LIMIT) die(it);
    } while (__any_sync(0xFFFFFFFFu, v));
    asm volatile("fence.proxy.async.global;" ::: "memory");
}
#define GD 200
DEVI void g_done(float (&d)[64]) { asm volatile("" : D16(+, 0), D16(+, 16), D16(+, 32), D16(+, 48)::"memory"); }
DEVI void g_main(uint32_t sb, uint32_t w, uint32_t role, const CUtensorMap* tmy) {
    const uint32_t bar = sb + SM_BAR, t16 = threadIdx.x * 16;
    const uint64_t da = (mkdesc(SB0 + GST(0), 128, 1024) & ~((uint64_t)3 << 62)) + (w >> 2) * 512;
    float d[128];
#pragma unroll
    for (int i = 0; i < 128; i++) d[i] = 0.f;
#define GFULL(kb) { mwait(bar + BAR_GF + ((kb) & 3) * 8, ((kb) >> 2) & 1); if (w >= 4) mwait(bar + BAR_GF + 32 + ((kb) & 3) * 8, ((kb) >> 2) & 1); }
#pragma unroll 1
    for (uint32_t kb = 0; kb < 29; kb++) {
        GFULL(kb);
        if (kb == 0 && threadIdx.x == 128) PG(4);
        if (kb == 4 && threadIdx.x == 0) PG(5);
        const uint64_t a = da + (kb & 3) * 3072, b = mkdesc(SB0 + GST(0) + 16384, 8192, 1024) + (kb & 3) * 3072;
        wg_fence();
#pragma unroll
        for (int k = 0; k < 4; k++) wg_ss256t(d, a + k * 16, b + k * 128);
        wg_commit();
        wg_wait<1>();
        if (kb > 0 && elect()) mbar_arrive(bar + BAR_GE + ((kb - 1) & 3) * 8);
    }
    GFULL(29);
    GFULL(30);
    GFULL(31);
    wg_wait<0>();
    float x[64], y[64];
#pragma unroll
    for (int i = 0; i < 64; i++) asm volatile("mov.b32 %0, %1;" : "=f"(x[i]) : "f"(d[i]) : "memory");
    SF();
#pragma unroll
    for (int i = 0; i < 64; i++) asm volatile("mov.b32 %0, %1;" : "=f"(y[i]) : "f"(d[i + 64]) : "memory");
    SF();
    if (elect()) asm volatile("mbarrier.arrive.relaxed.cluster.shared::cluster.b64 _, [%0];" ::"r"((bar ^ 0x1000000) + BAR_GX) : "memory");
    wg_fence();
    g_half<0, 29>(x, da);
    g_half<0, 30>(x, da);
    g_half<0, 31>(x, da);
    wg_commit();
    g_half<64, 29>(y, da);
    wg_commit();
    wg_wait<1>();
    g_done(x);
    mwait(bar + BAR_GX, 0);
#define GSEND(i0) _Pragma("unroll") for (int i = (i0); i < (i0) + 4; i++) \
        asm volatile("st.async.weak.shared::cluster.mbarrier::complete_tx::bytes.v4.b32 [%0], {%1,%2,%3,%4}, [%5];" \
                     ::"r"((sb ^ 0x1000000) + i * 4096 + t16), "r"(pack2(x[8 * i], x[8 * i + 1])), "r"(pack2(x[8 * i + 2], x[8 * i + 3])), \
                       "r"(pack2(x[8 * i + 4], x[8 * i + 5])), "r"(pack2(x[8 * i + 6], x[8 * i + 7])), "r"((bar ^ 0x1000000) + BAR_GX + 8) : "memory")
    GSEND(0);
    wg_fence();
    g_half<64, 30>(y, da);
    wg_commit();
    GSEND(4);
    wg_fence();
    g_half<64, 31>(y, da);
    wg_commit();
    wg_wait<0>();
    g_done(y);
    if (threadIdx.x == 0) PG(7);
    mwait(bar + BAR_GX + 8, 0);
    if (threadIdx.x == 0) PG(1);
    const uint32_t lane = threadIdx.x & 31, o = sb + GST(1) + w * 2048;
#pragma unroll
    for (int i = 0; i < 8; i++) {
        const uint4 a = lds128(sb + i * 4096 + t16);
        const float* e = y + 8 * i;
        stsm4(o + (i >> 2) * 49152 + (lane & 15) * 128 + ((((i & 3) * 2 + (lane >> 4)) ^ (lane & 7)) << 4),
              pack2(e[0] + lo_f(a.x), e[1] + hi_f(a.x)), pack2(e[2] + lo_f(a.y), e[3] + hi_f(a.y)),
              pack2(e[4] + lo_f(a.z), e[5] + hi_f(a.z)), pack2(e[6] + lo_f(a.w), e[7] + hi_f(a.w)));
        if (i == 3 || i == 7) {
            asm volatile("fence.proxy.async.shared::cta;" ::: "memory");
            __syncwarp();
            if (elect())
                asm volatile("cp.async.bulk.tensor.2d.global.shared::cta.bulk_group [%0, {%2, %3}], [%1];\ncp.async.bulk.commit_group;"
                             ::"l"(tmy), "r"(o + (i >> 2) * 49152), "r"((role & 7) * 128 + (i >> 2) * 64), "r"((role >> 3) * 128 + w * 16) : "memory");
        }
    }
    if (threadIdx.x == 0) PG(6);
    asm volatile("cp.async.bulk.wait_group.read 0;" ::: "memory");
}

DEVI void kvload(uint32_t sb, uint32_t u, uint32_t h, uint32_t j, int sg, uint32_t xlo, uint32_t xhi) {
    const uint32_t o = u == 0 ? 0 : 2048;
    mbar_expect(sb + SM_BAR + BAR_KV, 6144 - o);
    bulk_g2s(sb + SM_KV + u * 4096 + o, xlo + XO_XG + (((sg & 7) * 32 + h) * 4 + ((j + u) & 3)) * 6144 + o, xhi, 6144 - o, sb + SM_BAR + BAR_KV);
}
DEVI void helper_step(uint32_t sb, uint32_t w, uint32_t h, uint32_t j, uint32_t& l16, uint32_t xlo, uint32_t xhi, uint32_t zero, int s,
                      const CUtensorMap* tmx, const CUtensorMap* tmb) {
    const uint32_t u = w - 8, bq = sb + SM_BAR;
    bsync<1, 384>();
    PT(0);
    PDUMP();
    PT(1);
    if (s == NSEG - 2 && u < 2) g_arrive(xlo + XO_TK + 128, xhi, 256);
    const uint32_t ctag = ((s >> 1) & 1) ^ 1;
    const uint32_t av = xlo + ((s & 1) * 32 + h) * 8192 + u * 512;
    mbar_wait(bq + BAR_XA, (s + 1) & 1);
    bsync<8, 384>();
    delay_until(clk(), DLY_V);
    PT(4);
    int it = 0;
    bool bad;
    do {
        const uint4 d1 = ldg4<XO_CV>(av + (j ^ 1) * 2048 + l16, xhi);
        const uint4 d2 = ldg4<XO_CV>(av + (j ^ 2) * 2048 + l16, xhi);
        const uint4 d3 = ldg4<XO_CV>(av + (j ^ 3) * 2048 + l16, xhi);
        bad = any_bad(or3(tagx2(d1.x, d1.z, ctag), tagx2(d2.x, d2.z, ctag), tagx2(d3.x, d3.z, ctag)));
        sts128(sb + SM_VS + u * 512 + l16, hadd2(hadd2(d1.x, d2.x), d3.x), hadd2(hadd2(d1.y, d2.y), d3.y), hadd2(hadd2(d1.z, d2.z), d3.z),
               hadd2(hadd2(d1.w, d2.w), d3.w));
        REFRESH();
        if (++it > SPIN_LIMIT) die(it);
    } while (bad);
    PC(26, it - 1);
    PT(5);
    barv<5, 384>();
    bsync<3, 384>();
    if (u < 2) {
        asm volatile("fence.proxy.async.shared::cta;" ::: "memory");
        if (elect()) {
            const uint32_t sg = s + 3 - u;
            if (sg < NSEG) {
                const uint32_t ga = xlo + XO_XG + (((sg & 7) * 32 + h) * 4 + (j ^ (2 * u))) * 6144, sa = sb + SM_XO + u * 6144;
                if (u == 0) bulk_s2g(ga, xhi, sa, 6144);
                else bulk_red(ga, xhi, sa, 6144);
            }
        }
    }
    PT(6);
    uint32_t old = 0;
    if (u > 0 && s + 3 < NSEG)
        asm volatile("{\n.reg .b64 a;\nmov.b64 a, {%1,%2};\natom.relaxed.gpu.global.exch.b32 %0, [a], 0;\n}"
                     : "=r"(old) : "r"(xlo + XO_R + rpage(j, s + 2) + (u - 1) * 16384 + h * 128 + (l16 >> 2)), "r"(xhi) : "memory");
    PT(7);
    bsync<7, 384>();
    if (s + 1 < NSEG && elect()) kvload(sb, u, h, j, s + 1, xlo, xhi);
    if (u < 2) {
        asm volatile("cp.async.bulk.wait_group.read 0;" ::: "memory");
        if (elect()) mbar_expect(bq + BAR_PI + ((s & 1) ^ 1) * 8, 6144);
    }
    PT(8);
    if (s + 1 < NSEG) bsync<10, 384>();
    xload(sb, u, j, s + 1, tmx);
    if (s == NSEG - 2 && (u == 0 || (u == 1 && h < 30))) {
        g_wait(xlo + XO_TK + 128, xhi);
        g_load(sb, u, h * 4 + j, 0, xlo, xhi, tmb);
        g_load(sb, u, h * 4 + j, 1, xlo, xhi, tmb);
    }
    asm volatile("cp.async.bulk.wait_group 0;" ::: "memory");
    if (s + 1 < NSEG) mbar_wait(bq + BAR_KV, (s + 1) & 1);
    asm volatile("lop3.b32 %0, %0, %1, %2, 0x78;" : "+r"(l16) : "r"(old), "r"(zero));
    PT(15);
}
DEVI void tickets_done(uint32_t* tk) {
    if (atomicInc(tk + 2, gridDim.x / 2 - 64) == gridDim.x / 2 - 64) { tk[0] = 0; tk[1] = 0; }
}

__global__ void __cluster_dims__(2, 1, 1) __launch_bounds__(384, 1)
chain_kernel(const __grid_constant__ CUtensorMap tmq, const __grid_constant__ CUtensorMap tmk,
             const __grid_constant__ CUtensorMap tmv, const __grid_constant__ CUtensorMap tmo,
             const __grid_constant__ CUtensorMap tmx, const __grid_constant__ CUtensorMap tmb, const __grid_constant__ CUtensorMap tmy,
             const bf16* __restrict__ mem0, const bf16* __restrict__ xg,
             uint32_t xlo, uint32_t xhi, uint32_t zero, int nseg) {
    extern __shared__ __align__(1024) uint8_t smem[];
    const uint32_t tstart = clk();
    const uint32_t rk = smem_u32(smem) & 0x1000000;
    if (rk == 0 && (threadIdx.x & 31) == 0 && threadIdx.x - 32 < 32 * PW)
        sts32(SB0 + SM_ROLE + 4 + (threadIdx.x >> 3), probe(xlo + XO_PB + (threadIdx.x & 32) * 128 + (threadIdx.x & 64) * 256 + blockIdx.x * 16, xhi));
    __syncwarp();
    if ((smem_u32(smem) & 0xFFFFFF) != SB0) die(1 << 23);
    asm volatile("griddepcontrol.launch_dependents;" ::: "memory");
    const uint32_t w = __reduce_max_sync(0xFFFFFFFFu, threadIdx.x >> 5);
    const uint32_t sb = __reduce_max_sync(0xFFFFFFFFu, smem_u32(smem));
    const uint32_t bq = sb + SM_BAR;
    uint32_t l16 = __shfl_sync(0xFFFFFFFFu, (threadIdx.x & 31) * 16, threadIdx.x & 31);
    if (threadIdx.x == 0) {
        mbar_init(bq, 1);
        for (int i = 0; i < 24; i++) mbar_init(bq + BAR_WF + i * 8, i < 16 ? 1 : 8);
        mbar_init(bq + BAR_XA, 4); mbar_init(bq + BAR_KV, 4); mbar_init(bq + BAR_PI, 2); mbar_init(bq + BAR_PI + 8, 2);
        for (int i = 0; i < 14; i++) mbar_init(bq + BAR_GF + i * 8, i < 8 || i == 13 ? 1 : 8);
        mbar_expect(bq + BAR_GX + 8, 32768);
        mbar_init(bq + BAR_RO, 1);
        mbar_expect(bq + BAR_RO, 4);
        mbar_expect(bq + BAR_PI, 6144);
        mbar_expect(bq + BAR_PI, 6144);
        asm volatile("fence.mbarrier_init.release.cluster;" ::: "memory");
        asm volatile("fence.proxy.async.shared::cta;" ::: "memory");
    }
    __syncwarp();
    asm volatile("barrier.cluster.arrive.relaxed.aligned;" ::: "memory");
    if (w == 9) {
#pragma unroll 1
        for (int e = 0; e < 12; e++) sts128(sb + SM_WO + e * 512 + l16, 0, 0, 0, 0);
    }
    if (w == 8 && blockIdx.x < 128) {
        if (XPF && elect()) {
            asm volatile("cp.async.bulk.prefetch.L2.global [%0], 3072;" ::"l"((const char*)xg + blockIdx.x * 3072) : "memory");
            asm volatile("prefetch.tensormap [%0];\nprefetch.tensormap [%1];\nprefetch.tensormap [%2];\nprefetch.tensormap [%3];\nprefetch.tensormap [%4];"
                         ::"l"(&tmq), "l"(&tmx), "l"(&tmk), "l"(&tmv), "l"(&tmo) : "memory");
        }
#pragma unroll 1
        for (int i = 0; i < EPF; i++) {
            if (i) delay_until(clk(), EPD);
            if (elect())
                asm volatile("cp.async.bulk.prefetch.tensor.3d.L2.global [%0, {0, %1, %2}];" ::"l"(&tmq), "r"((blockIdx.x & 3) * 256 + i * 64), "r"((blockIdx.x >> 2) * 2) : "memory");
        }
    }
    if (rk == 0 && w <= PW) bsync<2, 32 * PW + 32>();
    asm volatile("barrier.cluster.wait.aligned;" ::: "memory");
    if (rk == 0 && threadIdx.x == 0) {
        uint32_t t1 = lds32(sb + SM_ROLE + 8), t0 = lds32(sb + SM_ROLE + 12);
        if (PW == 4) { t1 = min(t1, lds32(sb + SM_ROLE + 16)); t0 = min(t0, lds32(sb + SM_ROLE + 20)); }
        uint32_t side = (t0 < t1 ? 0u : 1u) ^ par(XO_PB);
        uint32_t* tk = (uint32_t*)(((uint64_t)xhi << 32) | (xlo + XO_TK));
        uint32_t t = atomicAdd(tk + side, 1u);
        if (t >= 32) {
            uint2 c;
            int it = 0;
            do {
                c = ldg2<XO_TK>(xlo, xhi);
                if (++it > SPIN_LIMIT) die(it);
            } while (c.x + c.y != gridDim.x / 2);
            t += (side ? c.x : c.y) - 32;
            side ^= 1;
            if (t >= 32) tickets_done(tk);
        }
#pragma unroll
        for (uint32_t r = 0; r < 2; r++)
            asm volatile("st.async.weak.shared::cluster.mbarrier::complete_tx::bytes.b32 [%0], %1, [%2];"
                         ::"r"(sb + SM_ROLE + (r << 24)), "r"(t * 4 + side * 2 + r), "r"(bq + BAR_RO + (r << 24)) : "memory");
    }
    __syncwarp();
    mbar_wait(bq + BAR_RO, 0);
    const uint32_t role = __reduce_max_sync(0xFFFFFFFFu, lds32(sb + SM_ROLE));
    if (role >= 128) return;
    const uint32_t h = role >> 2, j = role & 3;
    if (FTM && w == 11 && elect())
#pragma unroll
        for (uint32_t c = 0; c < FTM; c++) {
            mbar_expect(bq + BAR_WF + c * 8, 16384);
            tma3d(sb + SM_ST + c * 16384, &tmq, bq + BAR_WF + c * 8, 0, j * 256 + c * 64, h * 2);
        }

    if (w >= 8) {
        asm volatile("setmaxnreg.dec.sync.aligned.u32 24;");
        const uint32_t u = w - 8;
        if (u == 3) {
#pragma unroll 1
            for (uint32_t c = FTM; c < 16; c++) {
                if (c >= WIN) mbar_wait(bq + BAR_WF + (c - WIN) * 8, 0);
                if (l16 == 0) PG(16 + c);
                if (c == 12 + WOP) bsync<2, 64>();
                if (c >= 4 && c < 12 && c != 10) mbar_wait(bq + BAR_WE + (c - 4) * 8, 0);
                if (elect()) {
                    const uint32_t b = bq + BAR_WF + c * 8;
                    mbar_expect(b, 16384);
                    if (c >= 12) tma2d(sb + SM_WO + (c - 12) * WO_BOX, &tmo, b, j * 256 + (c - 12) * 64, h * 128);
                    else tma3d(c == 10 ? sb + SM_WV : sb + SM_ST + (c & 3) * 16384, c < 4 ? &tmq : c < 8 ? &tmk : &tmv, b, 0, j * 256 + ((c ^ (c >= 10)) & 3) * 64, h * 2);
                }
            }
#pragma unroll 1
            for (uint32_t c = 16 - WIN; c < 16; c++) mbar_wait(bq + BAR_WF + c * 8, 0);
            if (l16 == 0) PG(15);
        } else if (u == 0) {
            if (elect()) {
                mbar_expect(bq, 49152);
#pragma unroll 1
                for (uint32_t i = 0; i < 12; i++)
                    tma3d(sb + SM_X + (i < 4 ? i : i + 4) * 4096, &tmx, bq, 0, i < 8 ? i * 8 : (j ^ ((0xBD98u >> (i - 8) * 4) & 15)) * 8, j * 4);
            }
#pragma unroll 1
            for (int i = 0; i < 4; i++) xload(sb, i, j, -1, &tmx);
            bsync<3, 320>();
            if (l16 == 0) PG(32);
            g_arrive(xlo + XO_FL + h * 128, xhi, 4);
            if (WOP < 4) barv<2, 64>();
            if (l16 == 0) PG(33);
            g_wait(xlo + XO_FL + h * 128, xhi);
            if (l16 == 0) PG(34);
#pragma unroll 1
            for (int i = 0; i < 4; i++)
                if (elect()) kvload(sb, i, h, j, 0, xlo, xhi);
            mbar_wait(bq + BAR_KV, 0);
            if (l16 == 0) PG(14);
        } else if (u == 1) {
            const uint32_t l = l16 >> 4, x = h * 8 + (l >> 2), d = (x & ~31u) + (l & 3) * 8 + ((x & 31) >> 2) + (x & 3) * 2 * DM;
            const unsigned short* m0 = (const unsigned short*)mem0 + j * 256;
            const uint32_t v1 = m0[d] | (((l & 3) == 3 ? 0x4200u : m0[d + DM]) << 16);
            const uint32_t v3 = h < 8 ? m0[h * 32 + 24 + (l >> 2) + ((l & 3) * 2 + 1) * DM] | 0x42000000u : 0;
#pragma unroll 1
            for (uint32_t i = 0; i < 12; i++) {
                if (i == 10) { sts32(sb + SM_WO + 6144 + l * 4, v1); sts32(sb + SM_WO + 6272 + l * 4, v3); }
                asm volatile("fence.proxy.async.shared::cta;" ::: "memory");
                __syncwarp();
                const uint32_t c = (0x21924u >> ((i - 3) * 2)) & 3;
                if (elect()) {
                    if (i < 3) bulk_s2g(xlo + XO_XG + (i * 128 + role) * 6144, xhi, sb + SM_WO, 6144);
                    else bulk_s2g(xlo + XO_R + rpage(j, i < 6 ? 0 : i < 9 ? 1 : -1) + c * 16384 + h * 128, xhi, sb + SM_WO + (i < 10 ? 0 : 6144 + c * 64), 128);
                }
            }
            asm volatile("cp.async.bulk.wait_group 0;" ::: "memory");
            if (elect()) asm volatile("{\n.reg .b64 a;\nmov.b64 a, {%0,%1};\nred.relaxed.gpu.global.inc.u32 [a], 127;\n}" ::"r"(xlo + XO_TK + 12), "r"(xhi) : "memory");
            if (l16 == 0) PG(16);
            g_wait(xlo + XO_TK + 12, xhi);
            if (l16 == 0) PG(17);
            barv<5, 288>();
            bsync<8, 320>();
            asm volatile("fence.acq_rel.gpu;" ::: "memory");
        } else {
            GSYNC(0);
            mbar_wait(bq + BAR_WE + 48, 0);
#pragma unroll 1
            for (int e = 0; e < 16; e++) sts128(sb + SM_TR + 4096 + e * 512 + l16, 0, 0, 0, 0);
            barv<3, 320>();
            bsync<8, 320>();
#pragma unroll 1
            for (int i = 0; i < 4; i++) xload(sb, i, j, 0, &tmx);
        }
#pragma unroll 1
        for (int s = 0; s < nseg; s++) helper_step(sb, w, h, j, l16, xlo, xhi, zero, s, &tmx, &tmb);
        piwait(sb, 0, nseg - 2);
        bsync<9, 384>();
        GSYNC(1);
        if (w < 10) {
            uint32_t kb = 2;
            asm volatile("fence.proxy.async.shared::cta;" ::: "memory");
            if (w == 9) {
                g_arrive(xlo + XO_TK + 192, xhi, 128);
                PG(2);
                if (h >= 30) { g_wait(xlo + XO_TK + 192, xhi); kb = 0; }
                PG(3);
            } else delay_until(clk(), GD);
#pragma unroll 1
            for (; kb < 32; kb++) {
                if (kb >= 4) mbar_wait(bq + BAR_GE + (kb & 3) * 8, ((kb >> 2) & 1) ^ 1);
                g_load(sb, w - 8, role, kb, xlo, xhi, &tmb);
            }
        }
        if (role == 0 && w == 11 && elect()) tickets_done((uint32_t*)(((uint64_t)xhi << 32) | (xlo + XO_TK)));
    } else {
        asm volatile("setmaxnreg.inc.sync.aligned.u32 240;");
        uint32_t Wq[16][4], Wk[16][4], Wv[NA][4];
        uint32_t t16, KA, KB, KC, KD;
        {
            const uint32_t lane = l16 >> 4, g = lane >> 2, t = lane & 3;
            const uint32_t rw = (((lane >> 4) & 1) * 8 + (lane & 7)) * 128u;
            const uint32_t off = rw + ((((w & 3) * 2 + ((lane >> 3) & 1)) ^ (lane & 7)) << 4);
            const uint32_t offo = rw + ((((w & 1) * 4 + ((lane >> 3) & 1)) ^ (lane & 7)) << 4);
            const uint32_t r = 2 * (t & 1) + (g >> 2);
            const uint32_t mk0 = t < 2 ? 0 : (r == 0 ? 2 * g > w : j + r < 4), mk1 = t < 2 ? 0 : (r == 0 ? 2 * g + 1 > w : j + r < 4);
            t16 = __shfl_sync(0xFFFFFFFFu, w * 512 + l16, lane);
            KA = __shfl_sync(0xFFFFFFFFu, (w * 512 + t * 64 + g * 8) | ((w * 512 + (g & 1) * 256 + (g >> 1) * 64 + t * 16) << 16), lane);
            KB = __shfl_sync(0xFFFFFFFFu, ((w >> 2) * WV_BOX + off) | mk0 | (mk1 << 1) |
                                              ((w * 256 + (g >> 2) * 4096 + (g & 3) * 64 + t * 16) << 16), lane);
            KC = __shfl_sync(0xFFFFFFFFu, ((lane & 7) * 1280 + (lane >> 3) * 128 + ((w ^ (lane & 7)) << 4)) | (((t >> 1) * 16 + g * 2) << 16) | ((t * 64 + g * 8) << 24), lane);
            KD = __shfl_sync(0xFFFFFFFFu, ((w >> 1) * WO_BOX + offo) | (((lane & 7) * 208 + (lane >> 3) * 16) << 16), lane);
            if (threadIdx.x == 0) PG(8);
#define WTAKE(W, c, k0) { mbar_wait(bq + BAR_WF + (c) * 8, 0); \
                _Pragma("unroll") for (int ks = 0; ks < 4; ks++) ldsm4t(W[(k0) + ks], sb + SM_ST + ((c) & 3) * 16384 + (KB & 0xFFF0) + ks * 2048); \
                if ((c) < 8) { __syncwarp(); if (elect()) mbar_arrive(bq + BAR_WE + (c) * 8); } }
#pragma unroll
            for (int c = 0; c < 4; c++) WTAKE(Wq, c, c * 4);
            mbar_wait(bq, 0);
            if (threadIdx.x == 0) PG(9);
            xstart<0>(sb, w, xlo + h * 24576, xhi, j, t16, KA, Wq);
            if (threadIdx.x == 0) PG(10);
#pragma unroll
            for (int c = 0; c < 4; c++) WTAKE(Wk, c + 4, c * 4);
            if (threadIdx.x == 0) PG(11);
            xstart<1>(sb, w, xlo + h * 24576, xhi, j, t16, KA, Wk);
            if (threadIdx.x == 0) PG(12);
            WTAKE(Wv, 8, 0);
            WTAKE(Wv, 9, 4);
            mbar_wait(bq + BAR_WF + 80, 0);
            WTAKE(Wv, 11, 8);
            if (threadIdx.x == 0) PG(13);
            xstart<2>(sb, w, xlo + h * 24576, xhi, j, t16, KA, Wv);
            mbar_wait(bq + BAR_XA, 0);
            bsync<8, 320>();
        }
        const uint32_t ONES = 0x3F803F80u;
#define UNI(x) __reduce_max_sync(0xFFFFFFFFu, x)
        uint32_t swi = UNI((uint32_t)((uint64_t)smem >> 32));
        const uint32_t sbw = UNI(sb + w * 256), sbm = UNI(sb - w * 512), sbs = UNI(sb + w * 768), sbp = UNI(sb + w * 208);
#define OPQALL() { OPQ(t16); OPQ(KA); OPQ(KB); OPQ(KC); OPQ(KD); }
        OPQALL();
        const uint32_t cb0 = (h >> 1) * 32768 + (j & 1) * 16384 + (h & 1) * 8192;
        const uint32_t cb = UNI(xlo + cb0 + ((par(cb0) ^ (j >> 1) ^ CFAR) << 12)), cv = UNI(xlo + role * 2048), h1 = UNI((h & 1) * 1024);
        const uint32_t uox = UNI(xlo + XO_OX + (h * 2 + (w >> 2)) * 262144 + j * 1024 + (w & 3) * 256 - w * 128);
        uint32_t rp = UNI(xlo + rpage(j, 0));
        float ox[4];
        float4 dn;
#define OXSTORE(s) asm volatile("{\n.reg .b64 a;\nmov.b64 a, {%0,%1};\nst.global.u32 [a], %2;\nst.global.u32 [a+128], %3;\n}" \
                                ::"r"(uox + (s) * 4096 + (t16 >> 2)), "r"(xhi), \
                                  "r"(pack2(ox[0] * dn.y, ox[1] * dn.w)), "r"(pack2(ox[2] * dn.y, ox[3] * dn.w)) : "memory")
#pragma unroll 1
        for (int s2 = 0;; s2 += 2, rp ^= 0x21000)
#pragma unroll
        for (int p = 0; p < 2; p++) {
            const int s = s2 + p;
            const uint32_t ctag = ((s2 >> 1) & 1) ^ 1;
            const uint32_t hb = cb ^ (p * 0x81000), rb = rp ^ (p * 0x11000);
            uint4 k0, k1;
            uint32_t qx0, qx1, ov0, ov1;
            {
                float xa[16], xb[16];
                uint4 m0, n0;
                uint32_t e0, f0;
                uint32_t xp[8];
                wg_fence();
                XMMA(0, 6);
                SF();
                piwait(sb, p, s - 2);
                uint4 pi = xpeer<0>(sb, p ^ 1, t16);
                SF();
                wg_fence();
                XMMA(6, RPOS);
                XMMA(RPOS, RPOS + 4);
                uint32_t a = (p ? rp : rp ^ 0x30000) + t16, e = (p ? rp : rp ^ 0x30000) + (t16 >> 2), ah = xhi, eh = xhi;
                OPQ(a); OPQ(e); OPQ(ah); OPQ(eh);
                SF();
                wg_wait<1>();
                SF();
                PT(11);
                RLOAD();
                SF();
#define QPOS (RPOS >= 32 - NA ? RPOS : RPOS + 4 >= 32 - NA ? RPOS + 4 : 32 - NA)
                if (QPOS > RPOS) {
                    wg_fence();
                    if (QPOS > RPOS + 4) XMMA(RPOS + 4, QPOS);
                    XMMA(QPOS, QPOS + 4);
                    wg_wait<1>();
                    SF();
                }
                xpack<0>(xp, xa);
                xpark<0>(xp, pi, sb, sbw, p ^ 1, t16, KA);
                pi = xpeer<2>(sb, p ^ 1, t16);
                SF();
                if (QPOS + 4 < 32) {
                    wg_fence();
                    XMMA(QPOS + 4, 32);
                    SF();
                }
                wg_wait<0>();
                xpack<2>(xp, xb);
                xpark<2>(xp, pi, sb, sbw, p ^ 1, t16, KA);
                SF();
                PT(12);
                {
                    int it = 0;
                    while (ruse(sb + SM_MEMT + t16, m0, n0, e0, f0)) {
                        RLOAD();
                        if (++it > SPIN_LIMIT) die(it);
                    }
                    PC(22, it + 1);
                }
                PT(13);
                OPQ(KA); OPQ(t16);
                uint32_t acw = hb + (KA & 0xFFFF), ahi = xhi, tg = ctag;
                OPQ(acw); OPQ(ahi); OPQ(tg);
                SF();
                bsync<1, 384>();
                PT(0);
                uint32_t b[8][4];
#pragma unroll
                for (int i = 0; i < 8; i++) {
                    const int pp = i < 2 ? i : i ^ 1;
                    ldsm4t(b[pp], sbm + SM_MEMT + t16 + pp * 512);
                    if (i < 7) MF();
                }
                if (ASF) SF();
                float q[4], k[4];
                const uint32_t aWv = sb + SM_WV + (KB & 0xFFF0);
                uint32_t wv[16 - NA > 0 ? 16 - NA : 1][4];
#define WVLD(n0, n1) _Pragma("unroll") for (int n = (n0); n < (n1) && n < 16 - NA; n++) ldsm4t(wv[n], aWv + n * 2048)
#pragma unroll
                for (int ks = 0; ks < 16; ks++) {
                    const uint32_t b0 = b[ks >> 1][(ks & 1) * 2], b1 = b[ks >> 1][(ks & 1) * 2 + 1];
                    if (ks == 0) {
                        mma16z(q, Wq[0][0], Wq[0][1], Wq[0][2], Wq[0][3], b0, b1);
                        mma16z(k, Wk[0][0], Wk[0][1], Wk[0][2], Wk[0][3], b0, b1);
                    } else {
                        mma16(q, Wq[ks][0], Wq[ks][1], Wq[ks][2], Wq[ks][3], b0, b1);
                        mma16(k, Wk[ks][0], Wk[ks][1], Wk[ks][2], Wk[ks][3], b0, b1);
                    }
                    if (ks == 10 && VPF) { SF(); WVLD(0, VPF); }
                }
                const uint32_t oq0 = settag(pack2(q[0], q[2]), tg), oq1 = settag(pack2(q[1], q[3]), tg);
                const uint32_t ok0 = pack2(k[0], k[2]), ok1 = pack2(k[1], k[3]);
                stg2<XO_CQK>(acw, ahi, oq0, ok0);
                stg2<XO_CQK + 256>(acw, ahi, oq1, ok1);
                SF();
                PT(1);
                int nl = VPF;
#pragma unroll
                for (int rd = 0; rd < 8; rd++) {
                    const int pp = (VORD >> (28 - 4 * rd)) & 7;
                    const uint32_t* a = 2 * pp < NA ? Wv[2 * pp < NA ? 2 * pp : 0] : wv[2 * pp < NA ? 0 : 2 * pp - NA];
                    const uint32_t* c = 2 * pp < NA ? Wv[2 * pp < NA ? 2 * pp + 1 : 0] : wv[2 * pp < NA ? 0 : 2 * pp + 1 - NA];
                    if (rd == 0) {
                        mma16z(q, a[0], a[1], a[2], a[3], b[pp][0], b[pp][1]);
                        mma16z(k, c[0], c[1], c[2], c[3], b[pp][2], b[pp][3]);
                    } else {
                        mma16(q, a[0], a[1], a[2], a[3], b[pp][0], b[pp][1]);
                        mma16(k, c[0], c[1], c[2], c[3], b[pp][2], b[pp][3]);
                    }
                    if (rd == 0) {
                        SF();
                        OPQ(swi);
                        asm volatile("{\n.reg .b64 a;\nmov.b64 a, {%0,%1};\nst.v2.u32 [a], {%2,%3};\nst.v2.u32 [a+256], {%4,%5};\n}"
                                     ::"r"((KA & 0xFFF) + (sb ^ 0x1000000) + SM_TR + 4096 + p * 4096), "r"(swi), "r"(oq0), "r"(ok0), "r"(oq1), "r"(ok1) : "memory");
                        sts64(sb + SM_TR + (KA & 0xFFF), oq0, ok0);
                        sts64(sb + SM_TR + (KA & 0xFFF) + 256, oq1, ok1);
                    }
                    if (rd == 4) KEEP(t16, oq0, oq1, ok0, ok1);
                    if (nl < 16 - NA) {
                        SF();
                        WVLD(nl, nl + (2 * pp < NA ? 1 : 3));
                        nl += 2 * pp < NA ? 1 : 3;
                    } else if (nl < 32) {
                        SF();
                        k0 = lds128(sb + SM_KV + 2048 + (KB >> 16));
                        nl = 32;
                    } else if (nl == 32) {
                        SF();
                        k1 = lds128(sb + SM_KV + 10240 + (KB >> 16));
                        const uint4 qq = lds128(sbw + SM_KV + ((KA >> 16) & 0xFF));
                        qx0 = (t16 & 64) ? qq.y : qq.x;
                        qx1 = (t16 & 64) ? qq.w : qq.z;
                        nl = 33;
                    }
                }
                ov0 = pack2(q[0] + k[0], q[1] + k[1]);
                ov1 = pack2(q[2] + k[2], q[3] + k[3]);
                stg2<XO_CV>(cv + p * 262144 + (t16 >> 1), xhi, settag(ov0, tg), ov1);
                barv<8, 384>();
            }
            OPQ(t16);
            SF();
            PT(2);
            PDUMP();
            {
                const uint32_t a0 = sb + SM_KV;
#define CLOADG() { c2 = ldg4<XO_CQK>((hb ^ 0x1000) + (KA >> 16), xhi); c3 = ldg4<XO_CQK>((hb ^ 0x5000) + (KA >> 16), xhi); }
#define CLOADS() { c0 = lds128(sb + SM_TR + (KA >> 16)); c1 = lds128(sb + SM_TR + 4096 + p * 4096 + (KA >> 16)); }
                uint4 c0, c1, c2, c3, pi;
                float xa[16], xb[16];
                uint32_t xp[8];
                wg_fence();
                XMMA(32, 32 + CPOS);
                XMMA(32 + CPOS, 36 + CPOS);
                wg_wait<1>();
                SF();
                CLOADG();
                SF();
                CLOADS();
                if (KPOS == 0) pi = xpeer<1>(sb, p ^ 1, t16);
                SF();
                wg_fence();
                XMMA(36 + CPOS, 48);
                SF();
                const uint32_t ka[4] = {k0.x, k0.y, k0.z, k0.w}, kb[4] = {k1.x, k1.y, k1.z, k1.w};
                const uint32_t aSp = sb + SM_SP + (KC & 0xFFFF);
                PT(3);
#define SCORES(FIRST) { \
                    const uint32_t qA = hadd2(hadd2(c0.x, c1.x), hadd2(c2.x, c3.x)), qB = hadd2(hadd2(c0.z, c1.z), hadd2(c2.z, c3.z)); \
                    const uint32_t kA = hadd2(hadd2(c0.y, c1.y), hadd2(c2.y, c3.y)), kB = hadd2(hadd2(c0.w, c1.w), hadd2(c2.w, c3.w)); \
                    bad = any_bad(or3(tagx2(c1.x, c1.z, ctag), tagx2(c2.x, c2.z, ctag), tagx2(c3.x, c3.z, ctag))); \
                    float sa[4], sb_[4], sc[4], sd[4], se[4]; \
                    if (FIRST) { SF(); wg_wait<0>(); } \
                    mma16z(sa, ka[0], ka[1], ka[2], ka[3], qA, qB); \
                    mma16z(sb_, kb[0], kb[1], kb[2], kb[3], qA, qB); \
                    mma16z(sc, qA, qx0, qB, qx1, kA, kB); \
                    if (FIRST) { \
                        xpack<1>(xp, xa); \
                        if (KPOS == 0) { xadd(xp, pi); xstore<1>(xp, sb, sbw, p ^ 1, t16, KA); barv<3, 384>(); } \
                        mma16z(sd, ka[0], ka[1], ka[2], ka[3], qx0, qx1); \
                        mma16z(se, kb[0], kb[1], kb[2], kb[3], qx0, qx1); \
                    } \
                    stsm4t(aSp, pack2(sa[0], sa[1]), pack2(sa[2], sa[3]), pack2(sb_[0], sb_[1]), pack2(sb_[2], sb_[3])); \
                    stsm2(aSp + 1024, pack2(sc[0], sc[1]), pack2(sc[2], sc[3])); \
                    if (FIRST) { \
                        stsm4t(aSp + 512, pack2(sd[0], sd[1]), pack2(sd[2], sd[3]), pack2(se[0], se[1]), pack2(se[2], se[3])); \
                        if (KPOS == 0) { KEEP(KD, xp[0], xp[1], xp[2], xp[3]); KEEP(KD, xp[4], xp[5], xp[6], xp[7]); } \
                    } }
                int it = 0;
                bool bad;
                SCORES(true);
                while (__builtin_expect(bad, 0)) {
                    OPQ(KA);
                    CLOADG();
                    CLOADS();
                    SCORES(false);
                    if (++it > SPIN_LIMIT) die(it);
                }
                PC(25, it);
                PT(4);
                bsync<4, 256>();
                uint32_t wo[16][4];
                const uint32_t aWo = sb + SM_WO + (KD & 0xFFFF), aWo1 = sb + SM_WO + ((KD & 0xFFFF) ^ 32);
#define WOLD(n0, n1) _Pragma("unroll") for (int n = (n0); n < (n1) && n < 16; n++) ldsm4t(wo[n], ((n & 1) ? aWo1 : aWo) + (n >> 1) * 2048)
                const bool hi = (t16 & 32) != 0;
                const uint32_t t8 = t16 >> 1;
                uint2 v0, v1, v2, v3;
                uint32_t es;
                {
                    uint32_t am[4], ax[4], a4[2];
                    const uint32_t aSr = sbs + SM_SP + t16;
                    ldsm4t(am, aSr);
                    ldsm4t(ax, aSr + 512);
                    ldsm2t(a4, aSr + 1024);
                    MF();
                    if (KPOS == 1) pi = xpeer<1>(sb, p ^ 1, t16);
                    const uint32_t se = (t16 & 128) ? 0u : ONES, so = se ^ ONES;
                    float hm[4], hx[4], h4[4];
                    mma16z(hm, am[0], am[1], am[2], am[3], se, so);
                    mma16z(hx, ax[0], ax[1], ax[2], ax[3], se, so);
                    mma8z(h4, a4[0], a4[1], ONES);
                    SF();
                    if (KPOS == 1) { xpark<1>(xp, pi, sb, sbw, p ^ 1, t16, KA); barv<3, 384>(); }
                    v0 = lds64(a0 + 4096 + t8); v1 = lds64(a0 + 8192 + t8); v2 = lds64(a0 + 12288 + t8); v3 = lds64(a0 + 16384 + t8);
                    WOLD(0, PF2);
                    float s0 = hi ? hx[0] : hm[0], s1 = hi ? hx[2] : hm[2];
                    const float s2 = hi ? h4[2] : h4[0];
                    s0 = (KB & 1) ? -1.0e9f * 11.313708499f : s0;
                    s1 = (KB & 2) ? -1.0e9f * 11.313708499f : s1;
                    int mi = __float_as_int(fmaxf(fmaxf(s0, s2), s1));
                    mi ^= (mi >> 31) & 0x7FFFFFFF;
                    const int mm = __reduce_max_sync(0xFFFFFFFFu, hi ? (int)0x80000000 : mi), mx = __reduce_max_sync(0xFFFFFFFFu, hi ? mi : (int)0x80000000);
                    SF();
                    WOLD(PF2, PF3);
                    SF();
                    mi = hi ? mx : mm;
                    mi ^= (mi >> 31) & 0x7FFFFFFF;
                    const float c2_ = 0.08838834764831845f * 1.4426950408889634f;
                    const float mc = __int_as_float(mi) * c2_;
                    const float e0 = ex2(fmaf(s0, c2_, -mc)), e1 = ex2(fmaf(s1, c2_, -mc)), e2 = ex2(fmaf(s2, c2_, -mc));
                    sts32(sbp + SM_P + (KC >> 25), pack2(e0, e1));
                    sts16(sbp + SM_P + 128 + ((KC >> 16) & 0xFF), pack2(e2, e2));
                    es = __float_as_uint(fmaf(e2, 0.5f, e0 + e1) + 64.f);
                }
                const uint32_t sm = __reduce_add_sync(0xFFFFFFFFu, hi ? 0u : es), sx = __reduce_add_sync(0xFFFFFFFFu, hi ? es : 0u);
                const uint32_t aPr = sb + SM_P + (KD >> 16);
                PT(5);
                bsync<5, 384>();
                uint32_t pm[4], px[4], p4[2];
                ldsm4(pm, aPr);
                MF();
                const uint2 vs = lds64(sb + SM_VS + t8);
                MF();
                ldsm2(p4, aPr + 128);
                MF();
                ldsm4(px, aPr + 64);
                MF();
                sts32f(sb + SM_DN + w * 8 + ((t16 >> 3) & 4), rcp(__uint_as_float((hi ? sx : sm) - 15u * 0x42800000u) - 64.f));
                MF();
                WOLD(PF3, NPF);
                const uint32_t vm0 = hadd2(ov0, vs.x), vm1 = hadd2(ov1, vs.y);
                float oa[4], ob[4];
                mma16z(oa, v0.x, v0.y, v1.x, v1.y, pm[0], pm[1]);
                mma16z(ob, v2.x, v2.y, v3.x, v3.y, pm[2], pm[3]);
                mma8(oa, vm0, vm1, p4[0]);
                stsm2(sbw + SM_OT + (t16 & 511), pack2(oa[0] + ob[0], oa[1] + ob[1]), pack2(oa[2] + ob[2], oa[3] + ob[3]));
                PT(6);
                SF();
                bsync<6, 256>();
                mma16z(ox, v0.x, v0.y, v1.x, v1.y, px[0], px[1]);
                uint32_t b[4][4];
#define OTLD(pp) ldsm4t(b[pp], sbm + SM_OT + t16 + (pp) * 512)
                OTLD(0);
                MF();
                OTLD(1);
                barv<7, 384>();
                mma16(ox, v2.x, v2.y, v3.x, v3.y, px[2], px[3]);
                mma8(ox, vm0, vm1, p4[1]);
                if (p == 1 && s + 1 == nseg) goto done;
                SF();
                uint32_t ar, ae, ahi = xhi;
                float r[2][4];
#pragma unroll
                for (int ks = 0; ks < 8; ks++) {
                    if (ks == 0) WOLD(NPF, NPF + WPF);
                    if (ks == OPOS) { OTLD(2); MF(); }
                    if (ks == OPOS + 2) { OTLD(3); MF(); }
                    if (ks > 0) WOLD(NPF + WPF + 2 * (ks - 1), NPF + WPF + 2 * ks);
                    if (ks == 5) {
                        OPQ(t16);
                        ar = rb + h1 * 16 + t16; ae = rb + h1 + (t16 >> 2);
                        OPQ(ar); OPQ(ahi); OPQ(ae);
                        dn = lds128f(sb + SM_DN + (t16 & 48));
                    }
#pragma unroll
                    for (int mt = 0; mt < 2; mt++) {
                        const int i = ks * 2 + mt;
                        const uint32_t* a = wo[i];
                        if (i < 2) mma16z(r[mt], a[0], a[1], a[2], a[3], b[ks >> 1][2 * (ks & 1)], b[ks >> 1][2 * (ks & 1) + 1]);
                        else mma16(r[mt], a[0], a[1], a[2], a[3], b[ks >> 1][2 * (ks & 1)], b[ks >> 1][2 * (ks & 1) + 1]);
                    }
                    if (NPF + WPF + 2 * ks < 16 || ks < 5) SF();
                }
                const float r0 = dn.x, r1 = dn.z;
                asm volatile("{\n.reg .b64 a;\nmov.b64 a, {%0,%2};\nred.relaxed.gpu.global.add.noftz.v4.bf16x2 [a], {%3,%4,%5,%6};\n"
                             "mov.b64 a, {%1,%2};\nred.relaxed.gpu.global.add.noftz.bf16x2 [a+32768], %7;\n}"
                             ::"r"(ar), "r"(ae), "r"(ahi), "r"(pack2(r[0][0] * r0, r[0][1] * r1)), "r"(pack2(r[0][2] * r0, r[0][3] * r1)),
                               "r"(pack2(r[1][0] * r0, r[1][1] * r1)), "r"(pack2(r[1][2] * r0, 1.f)), "r"(pack2(r[1][3] * r1, 1.f)) : "memory");
                barv<10, 384>();
            }
            SF();
            PT(10);
            OXSTORE(s);
            OPQALL();
        }
    done:
        dn = lds128f(sb + SM_DN + (t16 & 48));
        OXSTORE(nseg - 1);
        barv<9, 384>();
        g_main(sb, w, role, &tmy);
        if (threadIdx.x == 0) PG(0);
    }
}

template <int SC> DEVI void wg_rs128t(float (&d)[64], const uint32_t (&a)[4], uint64_t db) {
    if (SC) asm volatile("wgmma.mma_async.sync.aligned.m64n128k16.f32.bf16.bf16 "
        "{%0,%1,%2,%3,%4,%5,%6,%7,%8,%9,%10,%11,%12,%13,%14,%15,%16,%17,%18,%19,%20,%21,%22,%23,%24,%25,%26,%27,%28,%29,%30,%31,%32,%33,%34,%35,%36,%37,%38,%39,%40,%41,%42,%43,%44,%45,%46,%47,%48,%49,%50,%51,%52,%53,%54,%55,%56,%57,%58,%59,%60,%61,%62,%63}, "
        "{%64,%65,%66,%67}, %68, 1, 1, 1, 1;"
        : D4(+, 0), D4(+, 4), D4(+, 8), D4(+, 12), D4(+, 16), D4(+, 20), D4(+, 24), D4(+, 28), D4(+, 32), D4(+, 36), D4(+, 40), D4(+, 44), D4(+, 48), D4(+, 52), D4(+, 56), D4(+, 60) : "r"(a[0]), "r"(a[1]), "r"(a[2]), "r"(a[3]), "l"(db));
    else asm volatile("wgmma.mma_async.sync.aligned.m64n128k16.f32.bf16.bf16 "
        "{%0,%1,%2,%3,%4,%5,%6,%7,%8,%9,%10,%11,%12,%13,%14,%15,%16,%17,%18,%19,%20,%21,%22,%23,%24,%25,%26,%27,%28,%29,%30,%31,%32,%33,%34,%35,%36,%37,%38,%39,%40,%41,%42,%43,%44,%45,%46,%47,%48,%49,%50,%51,%52,%53,%54,%55,%56,%57,%58,%59,%60,%61,%62,%63}, "
        "{%64,%65,%66,%67}, %68, 0, 1, 1, 1;"
        : D4(=, 0), D4(=, 4), D4(=, 8), D4(=, 12), D4(=, 16), D4(=, 20), D4(=, 24), D4(=, 28), D4(=, 32), D4(=, 36), D4(=, 40), D4(=, 44), D4(=, 48), D4(=, 52), D4(=, 56), D4(=, 60) : "r"(a[0]), "r"(a[1]), "r"(a[2]), "r"(a[3]), "l"(db));
}
template <int SC> DEVI void wg_rs64t(float (&d)[32], const uint32_t (&a)[4], uint64_t db) {
    if (SC) asm volatile("wgmma.mma_async.sync.aligned.m64n64k16.f32.bf16.bf16 "
        "{%0,%1,%2,%3,%4,%5,%6,%7,%8,%9,%10,%11,%12,%13,%14,%15,%16,%17,%18,%19,%20,%21,%22,%23,%24,%25,%26,%27,%28,%29,%30,%31}, "
        "{%32,%33,%34,%35}, %36, 1, 1, 1, 1;"
        : D4(+, 0), D4(+, 4), D4(+, 8), D4(+, 12), D4(+, 16), D4(+, 20), D4(+, 24), D4(+, 28) : "r"(a[0]), "r"(a[1]), "r"(a[2]), "r"(a[3]), "l"(db));
    else asm volatile("wgmma.mma_async.sync.aligned.m64n64k16.f32.bf16.bf16 "
        "{%0,%1,%2,%3,%4,%5,%6,%7,%8,%9,%10,%11,%12,%13,%14,%15,%16,%17,%18,%19,%20,%21,%22,%23,%24,%25,%26,%27,%28,%29,%30,%31}, "
        "{%32,%33,%34,%35}, %36, 0, 1, 1, 1;"
        : D4(=, 0), D4(=, 4), D4(=, 8), D4(=, 12), D4(=, 16), D4(=, 20), D4(=, 24), D4(=, 28) : "r"(a[0]), "r"(a[1]), "r"(a[2]), "r"(a[3]), "l"(db));
}
template <int SC> DEVI void wg_rs40(float (&d)[20], const uint32_t (&a)[4], uint64_t db) {
    if (SC) asm volatile("wgmma.mma_async.sync.aligned.m64n40k16.f32.bf16.bf16 "
        "{%0,%1,%2,%3,%4,%5,%6,%7,%8,%9,%10,%11,%12,%13,%14,%15,%16,%17,%18,%19}, "
        "{%20,%21,%22,%23}, %24, 1, 1, 1, 0;"
        : D4(+, 0), D4(+, 4), D4(+, 8), D4(+, 12), D4(+, 16) : "r"(a[0]), "r"(a[1]), "r"(a[2]), "r"(a[3]), "l"(db));
    else asm volatile("wgmma.mma_async.sync.aligned.m64n40k16.f32.bf16.bf16 "
        "{%0,%1,%2,%3,%4,%5,%6,%7,%8,%9,%10,%11,%12,%13,%14,%15,%16,%17,%18,%19}, "
        "{%20,%21,%22,%23}, %24, 0, 1, 1, 0;"
        : D4(=, 0), D4(=, 4), D4(=, 8), D4(=, 12), D4(=, 16) : "r"(a[0]), "r"(a[1]), "r"(a[2]), "r"(a[3]), "l"(db));
}
template <int SC> DEVI void wg_rs8(float (&d)[4], const uint32_t (&a)[4], uint64_t db) {
    if (SC) asm volatile("wgmma.mma_async.sync.aligned.m64n8k16.f32.bf16.bf16 "
        "{%0,%1,%2,%3}, "
        "{%4,%5,%6,%7}, %8, 1, 1, 1, 0;"
        : D4(+, 0) : "r"(a[0]), "r"(a[1]), "r"(a[2]), "r"(a[3]), "l"(db));
    else asm volatile("wgmma.mma_async.sync.aligned.m64n8k16.f32.bf16.bf16 "
        "{%0,%1,%2,%3}, "
        "{%4,%5,%6,%7}, %8, 0, 1, 1, 0;"
        : D4(=, 0) : "r"(a[0]), "r"(a[1]), "r"(a[2]), "r"(a[3]), "l"(db));
}
template <int SC> DEVI void wg_ss64a(float (&d)[32], uint64_t da, uint64_t db) {
    if (SC) asm volatile("wgmma.mma_async.sync.aligned.m64n64k16.f32.bf16.bf16 "
        "{%0,%1,%2,%3,%4,%5,%6,%7,%8,%9,%10,%11,%12,%13,%14,%15,%16,%17,%18,%19,%20,%21,%22,%23,%24,%25,%26,%27,%28,%29,%30,%31}, "
        "%32, %33, 1, 1, 1, 1, 0;"
        : D4(+, 0), D4(+, 4), D4(+, 8), D4(+, 12), D4(+, 16), D4(+, 20), D4(+, 24), D4(+, 28) : "l"(da), "l"(db));
    else asm volatile("wgmma.mma_async.sync.aligned.m64n64k16.f32.bf16.bf16 "
        "{%0,%1,%2,%3,%4,%5,%6,%7,%8,%9,%10,%11,%12,%13,%14,%15,%16,%17,%18,%19,%20,%21,%22,%23,%24,%25,%26,%27,%28,%29,%30,%31}, "
        "%32, %33, 0, 1, 1, 1, 0;"
        : D4(=, 0), D4(=, 4), D4(=, 8), D4(=, 12), D4(=, 16), D4(=, 20), D4(=, 24), D4(=, 28) : "l"(da), "l"(db));
}

#define G_ROWS 514
__device__ uint4 g_G[64 * G_ROWS * 8];
__device__ uint4 g_GN[64 * 8];
__device__ uint4 g_WN[1152];
#define FS_F2 196608
#define FS_TB (FS_F2 + 8192)
#define FS_NQ (FS_TB + 16384)
#define FS_BAR (FS_NQ + 128)
#define FS_NY (FS_NQ + 1024 + 128)
#define FS_TOTAL (FS_NQ + 3072)
#define F_THREADS 512

DEVI uint32_t cis(int j) {
    const float a = fmaf(__uint_as_float((((j + 1024) << 12) & 0x7FF000) | 0x3F800000), 6.283185307179586f, -9.42477796076938f);
    return pack2(__cosf(a), __sinf(a));
}
DEVI uint32_t cos2(int j0, int j1) {
    const float f = 6.283185307179586f / 2048.f;
    return pack2(__cosf((float)(((j0 + 1024) & 2047) - 1024) * f), __cosf((float)(((j1 + 1024) & 2047) - 1024) * f));
}
DEVI void twid(int j, float& c, float& s) {
    const float a = (float)(((j + 512) & 1023) - 512) * (6.283185307179586f / 1024.f);
    c = __cosf(a) * (1.f / 1024.f);
    s = __sinf(a) * (1.f / 1024.f);
}
template <bool B> struct Bool { static constexpr bool v = B; };
DEVI uint32_t opq(uint32_t& x, uint32_t zero) { OPQ(x); return x; }
DEVI uint32_t tidx() { uint32_t r; asm volatile("mov.u32 %0, %%tid.x;" : "=r"(r)); return r; }
DEVI void tma4d(uint32_t dst, const CUtensorMap* tm, uint32_t bar, int c0, int c1, int c2, int c3) {
    asm volatile("cp.async.bulk.tensor.4d.shared::cluster.global.mbarrier::complete_tx::bytes [%0], [%1, {%3, %4, %5, %6}], [%2];"
                 ::"r"(dst), "l"(tm), "r"(bar), "r"(c0), "r"(c1), "r"(c2), "r"(c3) : "memory");
}
DEVI void tma3s(const CUtensorMap* tm, uint32_t src, int c0, int c1, int c2) {
    asm volatile("cp.async.bulk.tensor.3d.global.shared::cta.bulk_group [%0, {%2, %3, %4}], [%1];" ::"l"(tm), "r"(src), "r"(c0), "r"(c1), "r"(c2) : "memory");
}
DEVI void tma4s(const CUtensorMap* tm, uint32_t src, int c0, int c1, int c2, int c3) {
    asm volatile("cp.async.bulk.tensor.4d.global.shared::cta.bulk_group [%0, {%2, %3, %4, %5}], [%1];"
                 ::"l"(tm), "r"(src), "r"(c0), "r"(c1), "r"(c2), "r"(c3) : "memory");
}
DEVI void bulk_commit() { asm volatile("cp.async.bulk.commit_group;" ::: "memory"); }
DEVI void fence_async() { asm volatile("fence.proxy.async;" ::: "memory"); }
DEVI void fence_smem() { asm volatile("fence.proxy.async.shared::cta;" ::: "memory"); }
DEVI void wgbar(uint32_t q) { asm volatile("bar.sync %0, 128;" ::"r"(q + 2) : "memory"); }
DEVI void grid_arrive(uint32_t* c, uint32_t n) { asm volatile("fence.proxy.async;\nred.release.gpu.global.inc.u32 [%0], %1;" ::"l"(c), "r"(n - 1) : "memory"); }
DEVI void grid_wait(uint32_t* c) {
    uint32_t v;
    int it = 0;
    do {
        asm volatile("ld.acquire.gpu.global.u32 %0, [%1];" : "=r"(v) : "l"(c) : "memory");
        if (++it > (1 << 22)) die(it);
    } while (v);
    fence_async();
}

template <bool INV, class S1, class S2>
DEVI void fft_rows(uint32_t grp, uint32_t q, const uint32_t (&F)[2][4], const float (&tc)[8], const float (&ts)[8], uint32_t so, float fx, uint32_t nq,
                   S1 sh1, S2 sh2) {
    float d[64];
    const uint64_t db = INV ? mkdesc(grp, 1024, 2048) : (mkdesc(grp, 2048, 512) ^ ((uint64_t)3 << 62));
    wg_fence();
    wg_rs128t<0>(d, F[0], db);
    wg_rs128t<1>(d, F[1], db + (INV ? 256 : 64));
    wg_commit();
    SF();
    sh1();
    float4 ny;
    if (INV) ny = lds128f(nq);
    wg_wait<0>();
    if (INV) { d[0] = fmaf(fx, ny.x, d[0]); d[16] = fmaf(fx, ny.y, d[16]); d[32] = fmaf(fx, ny.z, d[32]); d[48] = fmaf(fx, ny.w, d[48]); }
    uint32_t a[2][4][4];
    float e[2][INV ? 16 : 20];
    const uint64_t df = mkdesc(SB0 + FS_F2, 16, 1024);
#pragma unroll
    for (int s = 0; s < 2; s++) {
#pragma unroll
        for (int i = 0; i < 4; i++)
#pragma unroll
            for (int h = 0; h < 2; h++) {
                const float* x = d + (2 * s + h) * 16 + i * 4;
                a[s][i][h] = pack2(fmaf(x[2], ts[2 * i], x[0] * tc[2 * i]), fmaf(x[3], ts[2 * i + 1], x[1] * tc[2 * i + 1]));
                a[s][i][h + 2] = pack2(fmaf(-x[0], ts[2 * i], x[2] * tc[2 * i]), fmaf(-x[1], ts[2 * i + 1], x[3] * tc[2 * i + 1]));
            }
        wg_fence();
#pragma unroll
        for (int i = 0; i < 4; i++) {
            if constexpr (INV) { if (i == 0) wg_rs32<0>(e[s], a[s][i], df); else wg_rs32<1>(e[s], a[s][i], df + i * 2); }
            else { if (i == 0) wg_rs40<0>(e[s], a[s][i], df); else wg_rs40<1>(e[s], a[s][i], df + i * 2); }
        }
        wg_commit();
    }
    SF();
    sh2();
#pragma unroll
    for (int s = 0; s < 2; s++) {
        if (s == 0) wg_wait<1>(); else wg_wait<0>();
        float* x = e[s];
        if constexpr (!INV) {
            x[0] *= fx; x[1] *= fx; x[2] *= fx; x[3] *= fx;
            if (fx != 1.f) sts64(nq + s * 8, pack2(x[16], 0.f), pack2(x[18], 0.f));
        }
        const uint32_t o = grp + (INV ? so + s * 4096 : so ^ (s * 576));
#pragma unroll
        for (int b = 0; b < 2; b++)
            stsm4t(o + b * (INV ? 1024 : 4096), pack2(x[8 * b], x[8 * b + 1]), pack2(x[8 * b + 2], x[8 * b + 3]), pack2(x[8 * b + 4], x[8 * b + 5]),
                   pack2(x[8 * b + 6], x[8 * b + 7]));
    }
}

template <bool INV>
DEVI void fft_gen(uint32_t a, uint32_t n2) {
    const uint32_t tid = tidx(), x = ((tid >> 4) & 24) + (tid & 3), o = (tid & 4) * 128;
    if (INV) {
        const uint32_t r = (tid & 64) * 16 + (tid & 16) * 32 + (tid & 40) * 8 + n2;
        sts128(a + tid * 16, cis(o - r * x), cis(o - (r + 128) * x), cis(o - r * (x + 4)), cis(o - (r + 128) * (x + 4)));
    } else {
        const uint32_t r = 64 * x + n2, k = ((tid >> 2) & 24) + ((tid >> 3) & 3);
        sts128(a + tid * 16, cis(r * k + o), cis(r * (k + 4) + o), cis((r + 256) * k + o), cis((r + 256) * (k + 4) + o));
    }
}
template <bool INV, class S1>
DEVI void fft_cross(uint32_t buf, uint32_t q, uint32_t fa, uint32_t so, uint32_t nq, float (&n)[4], S1 sh1) {
    uint32_t F[4][4];
#pragma unroll
    for (int s = 0; s < 4; s++) { const uint4 v = lds128(fa + s * 2048); F[s][0] = v.x; F[s][1] = v.y; F[s][2] = v.z; F[s][3] = v.w; }
    float d[64];
    const uint64_t db = mkdesc(buf + q * 2048, 1024, 8192), dn = mkdesc(nq, 16, 1024);
    wg_fence();
#pragma unroll
    for (int s = 0; s < 4; s++) { if (s == 0) wg_rs128t<0>(d, F[s], db); else wg_rs128t<1>(d, F[s], db + s * 1024); }
#pragma unroll
    for (int s = 0; s < 4; s++) { if (s == 0) wg_rs8<0>(n, F[s], dn); else wg_rs8<1>(n, F[s], dn + s * 2); }
    wg_commit();
    SF();
    sh1();
    wg_wait<0>();
#pragma unroll
    for (int b = 0; b < 8; b++) {
        const uint32_t o = INV ? so ^ ((b >> 1) * 288 ^ (b & 1) * 32) : (so ^ ((b & 3) * 32)) + (b >> 2) * 1024;
        stsm4(buf + o, pack2(d[8 * b], d[8 * b + 1]), pack2(d[8 * b + 2], d[8 * b + 3]), pack2(d[8 * b + 4], d[8 * b + 5]), pack2(d[8 * b + 6], d[8 * b + 7]));
    }
}

template <bool ODD>
DEVI void fft_filter(uint32_t aw, const float (&e)[32], const float (&o)[32], uint32_t (&u)[4][4], uint32_t (&v)[4][4]) {
#pragma unroll
    for (int s = 0; s < 4; s++) {
        float y[2][2][4];
#pragma unroll
        for (int c = 0; c < 2; c++) {
            float f[4][2];
#pragma unroll
            for (int i = 0; i < 4; i++) {
                const uint32_t a = aw + (i * 32 + s * 8 + c) * 144, x = lds32(a);
                f[i][0] = ODD ? hi_f(x) : lo_f(x);
                f[i][1] = ODD ? lo_f(lds32(a + 4)) : hi_f(x);
            }
#pragma unroll
            for (int h = 0; h < 2; h++) {
                const int x = 8 * s + 2 * h + c;
                const float ar = e[x] + o[x], ai = e[x + 4] + o[x + 4], br = e[x] - o[x], bi = e[x + 4] - o[x + 4];
                const float yr = fmaf(-ai, f[2][h], ar * f[0][h]), yi = fmaf(ar, f[2][h], ai * f[0][h]);
                y[h][c][0] = fmaf(-bi, f[3][h], fmaf(br, f[1][h], yr));
                y[h][c][1] = fmaf(br, f[3][h], fmaf(bi, f[1][h], yi));
                y[h][c][2] = fmaf(2.f, yr, -y[h][c][0]);
                y[h][c][3] = fmaf(2.f, yi, -y[h][c][1]);
            }
        }
#pragma unroll
        for (int h = 0; h < 2; h++) {
            u[s][h] = pack2(y[h][0][0], y[h][1][0]); u[s][h + 2] = pack2(y[h][0][1], y[h][1][1]);
            v[s][h] = pack2(y[h][0][2], y[h][1][2]); v[s][h + 2] = pack2(y[h][0][3], y[h][1][3]);
        }
    }
}

__global__ void __launch_bounds__(F_THREADS, 1)
post_kernel(const __grid_constant__ CUtensorMap tmx, const __grid_constant__ CUtensorMap tmg1, const __grid_constant__ CUtensorMap tmg2,
           const __grid_constant__ CUtensorMap tmwr, const __grid_constant__ CUtensorMap tmwi, const __grid_constant__ CUtensorMap tmy,
           const bf16* __restrict__ wr, const bf16* __restrict__ wi, uint32_t* cnt, uint32_t zero, int nw) {
    extern __shared__ __align__(1024) uint8_t smem[];
    const uint32_t sb = SB0;
    if (smem_u32(smem) != sb) die(1 << 23);
    const uint32_t tid = threadIdx.x, lane = tid & 31, g = lane >> 2, t = lane & 3, j8 = lane & 7, mat = lane >> 3;
    const uint32_t wi_ = __reduce_max_sync(0xFFFFFFFFu, tid >> 5), q = wi_ >> 2, w = wi_ & 3;
    const int cta = blockIdx.x;
    const int nt = cta < 64 ? (64 - cta + nw - 1) / nw : 0;
    const uint32_t bar = sb + FS_BAR;
    if (tid == 0) {
        for (int i = 0; i < 30; i++) mbar_init(bar + i * 8, i < 3 ? 4 : i < 6 ? 16 : i >= 14 && i < 18 ? 2 : 1);
        asm volatile("fence.mbarrier_init.release.cluster;" ::: "memory");
        fence_smem();
    }
    __syncthreads();
#define FT(n)
    FT(0);
#define N2(p) (2 * ((p) & 31) + ((p) >> 5))
#define WLOAD(tk, part) { \
        const uint32_t wd_ = sb + 131072 + q * 18432 + (part) * 9216, wb_ = bar + 112 + q * 8; \
        mbar_expect(wb_, 9216); \
        if ((tk) < 256) tma3d(wd_, (part) ? &tmwi : &tmwr, wb_, ((tk) & 63) * 64, (tk) >> 6, 0); \
        else asm volatile("cp.async.bulk.shared::cluster.global.mbarrier::complete_tx::bytes [%0], [%1], 9216, [%2];" \
                          ::"r"(wd_), "l"(g_WN + (part) * 576), "r"(wb_) : "memory"); }
#define GROW(tk) ((tk) < 256 ? ((tk) >> 5) * 64 + ((tk) & 7) * 8 + (((tk) >> 3) & 3) * 2 : 512)
#define DLOAD(tk, sl) { mbar_expect(bar + 48 + (sl) * 8, 16384); tma3d(sb + (sl) * 16384, &tmg2, bar + 48 + (sl) * 8, 0, GROW(tk), 0); }
#define IO(c) if (w == 3 && (c) && elect())
#define XLOAD1(i, bb) { const uint32_t xb_ = bar + 144 + (bb) * 32 + q * 8; mbar_expect(xb_, 16384); tma4d(sb + (bb) * 65536 + q * 16384, &tmx, xb_, 0, 0, q * 8, N2(cta + (i) * nw)); }
#define GLOAD3(i, bb) { mbar_expect(bar + (bb) * 8, q ? 16384 : 16512); tma3d(sb + (bb) * 65536 + q * 16384, &tmg1, bar + (bb) * 8, 0, q * 128, cta + (i) * nw); \
        if (q == 0) asm volatile("cp.async.bulk.shared::cluster.global.mbarrier::complete_tx::bytes [%0], [%1], 128, [%2];" \
                                 ::"r"(sb + FS_NQ + (bb) * 1024), "l"(g_GN + (cta + (i) * nw) * 8), "r"(bar + (bb) * 8) : "memory"); }
    for (int i = 0; i < 3; i++) IO(i < nt) XLOAD1(i, i);
    for (uint32_t x = tid; x < 40 * 32; x += 512) {
        const uint32_t n = x >> 5, m2 = mat * 8 + t * 2, ri = g & 1;
        const uint32_t c2 = ((n >> 1) & 1) + ((n >> 3) & 1) * 2 + (n & 4) + (n >> 4) * 8;
        const uint32_t v = cos2(m2 * c2 * 64 + ((n & 1) - ri) * 512, (m2 + 1) * c2 * 64 + ((n & 1) - ri) * 512);
        sts32(sb + FS_F2 + n * 128 + ((g ^ (n & 7)) << 4) + t * 4, n < 32 ? v : n == 32 && ri == 0 ? 0xBF003F00u : 0u);
    }
    float tc[8], ts[8];
    uint32_t F[2][4];
    uint32_t c1 = 16 * (w >> 1) + 2 * g + (w & 1);
#pragma unroll
    for (int i = 0; i < 8; i++) {
        twid(c1 * (8 * (i >> 1) + 2 * t + (i & 1)), tc[i], ts[i]);
        const uint32_t m1 = (i >> 1) * 8 + 2 * t;
        F[i >> 2][i & 3] = cos2(c1 * m1 * 64 + (i & 1) * 512, c1 * (m1 + 1) * 64 + (i & 1) * 512);
    }
    {
        const uint32_t kr = (2 * (mat & 1) + (j8 & 1)) ^ ((j8 >> 2) << 1);
        const uint32_t so1 = ((mat >> 1) + 2 * (j8 >> 2)) * 1024 + kr * 128 + (((((j8 >> 1) & 1) * 4 + w) ^ kr) << 4);
        const uint32_t so2 = (2 * w + (mat & 1)) * 8192 + q * 2048 + j8 * 128 + (((mat >> 1) ^ j8) << 4);
        uint32_t so = so1 << 16 | so2;
        const float fx = (tid & 127) == 0 ? 0.5f : 1.f;
        fft_gen<false>(sb + FS_TB, N2(cta));
        fence_smem();
        bsync<1, 512>();
        FT(1);
        int b = 0, bp = 2, ph = 0;
        if (nt) mwait(bar + 144 + q * 8, 0);
        __syncwarp();
        auto step = [&](auto first, auto last, const int i) {
            const uint32_t p = cta + i * nw, bn = 3 - b - bp, tb = (i & 1) * 8192;
            const uint32_t grp = sb + b * 65536 + q * 16384, nq = sb + FS_NQ + b * 1024 + q * 32;
            auto sa = [&]() {
                if constexpr (!decltype(first)::v) {
                    fence_smem();
                    __syncwarp();
                    if (elect()) mbar_arrive(bar + 24);
                }
                IO(i > 1) {
                    mwait(bar + 32, i & 1);
                    tma3s(&tmg1, sb + bn * 65536 + q * 16384, 0, q * 128, p - 2 * nw);
                    bulk_commit();
                }
            };
            auto sb_ = [&]() { if constexpr (!decltype(first)::v) mwait(bar + 24, (i - 1) & 1); };
            if constexpr (!decltype(last)::v) fft_rows<false>(grp, q, F, tc, ts, opq(so, zero) >> 16, fx, nq, sa, sb_);
            else { sa(); __syncwarp(); sb_(); __syncwarp(); }
            if constexpr (!decltype(first)::v) {
                float n[4];
                fft_cross<false>(sb + bp * 65536, q, sb + FS_TB + 8192 - tb + (((tidx() & 127) ^ (q & 1)) << 4), opq(so, zero) & 0xFFFF, sb + FS_NQ + bp * 1024, n, [&]() {
                    fft_gen<false>(sb + FS_TB + tb, N2(p));
                    IO(i >= 2 && i + 1 < nt) {
                        asm volatile("cp.async.bulk.wait_group.read 0;" ::: "memory");
                        XLOAD1(i + 1, bn);
                    }
                });
                if (q == 0) {
                    const uint32_t x = tidx();
                    bf16* z = (bf16*)(g_G + ((p - nw) * G_ROWS + 512) * 8) + (x & 4) * 16 + ((x >> 2) & 24) + ((x >> 3) & 3);
                    asm volatile("{\n.reg .pred p;\n.reg .b16 a, b;\nsetp.eq.u32 p, %2, 0;\nmov.b32 {a, b}, %1;\n@p st.global.u16 [%0], a;\n@p st.global.u16 [%0+8], b;\n}"
                                 ::"l"(z), "r"(pack2(n[0], n[2])), "r"(x & 3) : "memory");
                }
            }
            if constexpr (!decltype(last)::v) {
                fft_rows<false>(grp + 8192, q, F, tc, ts, opq(so, zero) >> 16, fx, nq + 16, [&]() {
                    if constexpr (!decltype(first)::v) {
                        fence_smem();
                        __syncwarp();
                        if (elect()) mbar_arrive(bar + 32);
                    }
                    if ((w == 1 || w == 2) && elect())
                        asm volatile("cp.async.bulk.prefetch.L2.global [%0], 8208;" ::"l"((w == 1 ? wr : wi) + (p * 4 + q) * 4104) : "memory");
                }, [&]() { if (i + 1 < nt) mwait(bar + 144 + bn * 32 + q * 8, bn ? ph : ph ^ 1); });
                bp = b;
                if (++b == 3) { b = 0; ph ^= 1; }
            }
        };
        if (nt) {
            step(Bool<true>(), Bool<false>(), 0);
#pragma unroll 1
            for (int i = 1; i < nt; i++) step(Bool<false>(), Bool<false>(), i);
            step(Bool<false>(), Bool<true>(), nt);
        }
        for (uint32_t x = cta * 512 + tid; x < 4096; x += nw * 512)
            ((bf16*)g_WN)[(x >> 5) * 72 + (x & 16) + (x & 7) * 2 + ((x >> 3) & 1)] = (x < 2048 ? wr : wi)[(x & 2047) * 513 + 512];
        FT(2);
        fence_async();
        bsync<1, 512>();
        IO(nt) { tma3s(&tmg1, sb + bp * 65536 + q * 16384, 0, q * 128, cta + (nt - 1) * nw); bulk_commit(); }
    }
    for (uint32_t x = tid; x < 128 * 32; x += 512) {
        const uint32_t n = (x >> 5) & 63, a = x & 31, k2 = (n >> 4) * 8 + (n & 7);
        sts32(sb + FS_TB + (x >> 5) * 128 + (((a >> 2) ^ (n & 7)) << 4) + (a & 3) * 4, cis((2 * a + (x >> 11)) * k2 * 32 + (n & 8) * 64));
    }
    fence_smem();
    bsync<1, 512>();
    IO(true) {
        asm volatile("cp.async.bulk.wait_group 0;" ::: "memory");
        grid_arrive(cnt, 4 * nw);
        grid_wait(cnt);
        const int tk = cta + q * nw;
        if (tk <= 256) { DLOAD(tk, q); WLOAD(tk, 0); WLOAD(tk, 1); }
    }
    __syncwarp();
    {
        const uint32_t lo = j8 * 128 + (((2 * w + (mat & 1)) ^ j8) << 4);
        const uint32_t aw = sb + 131072 + q * 18432 + t * 288 + w * 32 + g * 4;
        const uint64_t df = mkdesc(sb + FS_TB, 16, 1024);
        const uint64_t da = mkdesc(sb + q * 16384, 16, 1024);
        const uint32_t buf = sb + 65536 + q * 16384;
        int i = 0, tk = cta + q * nw;
        if (tk <= 256) mwait(bar + 48 + q * 8, 0);
        FT(3);
#pragma unroll 1
        for (; tk <= 256; tk += 4 * nw, i++) {
            const bool more = tk + 4 * nw <= 256;
            float e[32], o[32];
            wg_fence();
#pragma unroll
            for (int s = 0; s < 4; s++) { if (s == 0) wg_ss64a<0>(e, da, df); else wg_ss64a<1>(e, da + s * 128, df + s * 2); }
#pragma unroll
            for (int s = 0; s < 4; s++) { if (s == 0) wg_ss64a<0>(o, da + 512, df + 512); else wg_ss64a<1>(o, da + 512 + s * 128, df + 512 + s * 2); }
            wg_commit();
            SF();
            if (i > 0) {
                fence_smem();
                wgbar(q);
                IO(true) { tma3s(&tmg2, buf, 0, GROW(tk - 4 * nw), 0); bulk_commit(); }
            }
            if (w == 2 && more && elect()) mbar_expect(bar + 48 + q * 8, 16384);
            const int gr = GROW(tk + 4 * nw);
            mwait(bar + 112 + q * 8, i & 1);
            wg_wait<0>();
            if (w == 2 && more && elect()) tma3d(sb + q * 16384, &tmg2, bar + 48 + q * 8, 0, gr, 0);
            uint32_t u[4][4], v[4][4];
            if (tk & 8) fft_filter<true>(aw + (tk & 48) / 4, e, o, u, v);
            else fft_filter<false>(aw + (tk & 48) / 4, e, o, u, v);
            wg_fence();
#pragma unroll
            for (int s = 0; s < 4; s++) { if (s == 0) wg_rs64t<0>(e, u[s], df); else wg_rs64t<1>(e, u[s], df + s * 128); }
#pragma unroll
            for (int s = 0; s < 4; s++) { if (s == 0) wg_rs64t<0>(o, v[s], df + 512); else wg_rs64t<1>(o, v[s], df + 512 + s * 128); }
            wg_commit();
            SF();
            IO(true) asm volatile("cp.async.bulk.wait_group.read 0;" ::: "memory");
            wgbar(q);
            if (more) {
                if ((w == 1 || w == 2) && elect()) WLOAD(tk + 4 * nw, w - 1);
                mwait(bar + 48 + q * 8, (i + 1) & 1);
            }
            wg_wait<0>();
#pragma unroll
            for (int s = 0; s < 4; s++) {
                const uint32_t a = buf + (mat >> 1) * 1024 + lo + s * 2048;
                stsm4t(a, pack2(e[8 * s], e[8 * s + 1]), pack2(e[8 * s + 2], e[8 * s + 3]), pack2(e[8 * s + 4], e[8 * s + 5]), pack2(e[8 * s + 6], e[8 * s + 7]));
                stsm4t(a + 8192, pack2(o[8 * s], o[8 * s + 1]), pack2(o[8 * s + 2], o[8 * s + 3]), pack2(o[8 * s + 4], o[8 * s + 5]), pack2(o[8 * s + 6], o[8 * s + 7]));
            }
            if (tk == 256 && w < 2) {
                uint32_t* z = (uint32_t*)g_GN + t * 32 + w * 16 + g;
#pragma unroll
                for (int s = 0; s < 16; s++) {
                    z[(s >> 1) * 128 + (s & 1) * 8] = pack2(e[2 * s], e[2 * s + 1]);
                    z[(s >> 1) * 128 + (s & 1) * 8 + 1024] = pack2(o[2 * s], o[2 * s + 1]);
                }
                fence_async();
            }
        }
        fence_smem();
        wgbar(q);
        IO(true) {
            if (i > 0) { tma3s(&tmg2, buf, 0, GROW(tk - 4 * nw), 0); bulk_commit(); }
            asm volatile("cp.async.bulk.wait_group 0;" ::: "memory");
            grid_arrive(cnt + 1, 4 * nw);
        }
    }
    FT(4);
    bsync<1, 512>();
    {
        for (uint32_t n = wi_; n < 32; n += 16) {
            const uint32_t cl = (mat >> 1) * 16 + t * 4 + (mat & 1), mh = ((n >> 3) & 1) + (n & 7) * 2 + (n & 16);
            sts32(sb + FS_F2 + n * 128 + ((g ^ (n & 7)) << 4) + t * 4, cos2(cl * mh * 64 + (g & 1) * 512, (cl + 2) * mh * 64 + (g & 1) * 512));
        }
        fence_smem();
        c1 = 8 * w + g;
#pragma unroll
        for (int i = 0; i < 8; i++) {
            twid(-c1 * (16 * (i >> 2) + 4 * t + 2 * (i & 1) + ((i >> 1) & 1)), tc[i], ts[i]);
            F[i >> 2][i & 3] = cis((i & 1) * 512 - c1 * ((i >> 1) * 4 + (t ^ (q & 1))) * 64);
        }
        const uint32_t kr = (j8 & 1) ^ ((j8 >> 2) << 1);
        const uint32_t so2 = ((w >> 1) * 4 + (j8 >> 2) * 2 + (w & 1)) * 8192 + (2 * q + (mat & 1)) * 1024 + kr * 128 + (((((j8 >> 1) & 1) * 4 + (mat >> 1)) ^ kr) << 4);
        const uint32_t so1 = (mat & 1) * 2048 + j8 * 128 + ((((mat >> 1) * 4 + w) ^ j8) << 4);
        uint32_t so = so1 << 16 | so2;
        const float fx = t ? 0.f : (g & 1) ? -1.f : 1.f;
        fft_gen<true>(sb + FS_TB, N2(cta));
        bsync<1, 512>();
        IO(true) grid_wait(cnt + 1);
        for (int i = 0; i < 3; i++) IO(i < nt) GLOAD3(i, i);
        __syncwarp();
        int b = 0, bp = 2, ph = 0;
        auto step = [&](auto first, auto last, const int i) {
            const uint32_t p = cta + i * nw, bn = 3 - b - bp, tb = (i & 1) * 8192;
            const uint32_t grp = sb + bp * 65536 + q * 16384, ny = sb + FS_NY + bp * 128 + q * 32;
            auto sb_ = [&]() { if constexpr (!decltype(last)::v) mwait(bar + b * 8, ph); };
            if constexpr (!decltype(first)::v) {
                fft_rows<true>(grp, q, F, tc, ts, opq(so, zero) >> 16, fx, ny, [&]() {
                    if (i > 1) {
                        fence_smem();
                        wgbar(q);
                        IO(true) { tma4s(&tmy, sb + bn * 65536 + q * 16384, 0, 0, q * 8, N2(p - 2 * nw)); bulk_commit(); }
                    }
                }, sb_);
            } else { sb_(); __syncwarp(); }
            if constexpr (decltype(first)::v) FT(5);
            if constexpr (!decltype(last)::v) {
                float n[4];
                fft_cross<true>(sb + b * 65536, q, sb + FS_TB + tb + (tidx() & 127) * 16, opq(so, zero) & 0xFFFF, sb + FS_NQ + b * 1024, n, [&]() {
                    fft_gen<true>(sb + FS_TB + 8192 - tb, N2(p + nw));
                    IO(i >= 2 && i + 1 < nt) {
                        asm volatile("cp.async.bulk.wait_group.read 0;" ::: "memory");
                        GLOAD3(i + 1, bn);
                    }
                });
                if (q == 0) {
                    const uint32_t x = tidx(), a = sb + FS_NY + b * 128 + (x & 64) + (x & 16) * 2 + ((x & 40) >> 1);
                    if ((x & 7) == 0) { sts32f(a, n[0]); sts32f(a + 8, n[2]); }
                }
            }
            auto sc = [&]() {
                if constexpr (!decltype(last)::v) {
                    fence_smem();
                    __syncwarp();
                    if (elect()) mbar_arrive(bar + 24);
                }
            };
            auto sd = [&]() { if constexpr (!decltype(last)::v) mwait(bar + 24, (nt + i) & 1); };
            if constexpr (!decltype(first)::v) fft_rows<true>(grp + 8192, q, F, tc, ts, opq(so, zero) >> 16, fx, ny + 16, sc, sd);
            else { sc(); __syncwarp(); sd(); __syncwarp(); }
            if constexpr (!decltype(last)::v) {
                bp = b;
                if (++b == 3) { b = 0; ph ^= 1; }
            }
        };
        if (nt) {
            step(Bool<true>(), Bool<false>(), 0);
#pragma unroll 1
            for (int i = 1; i < nt; i++) step(Bool<false>(), Bool<false>(), i);
            step(Bool<false>(), Bool<true>(), nt);
        }
        fence_smem();
        wgbar(q);
        IO(nt) { tma4s(&tmy, sb + bp * 65536 + q * 16384, 0, 0, q * 8, N2(cta + (nt - 1) * nw)); bulk_commit(); }
        FT(6);
        IO(true) asm volatile("cp.async.bulk.wait_group 0;" ::: "memory");
    }
}

typedef CUresult (*EncodeFn)(CUtensorMap*, CUtensorMapDataType, cuuint32_t, void*, const cuuint64_t*, const cuuint64_t*,
                             const cuuint32_t*, const cuuint32_t*, CUtensorMapInterleave, CUtensorMapSwizzle,
                             CUtensorMapL2promotion, CUtensorMapFloatOOBfill);

static void make_map(EncodeFn enc, CUtensorMap* m, const void* ptr, int rank, const cuuint64_t* dims, const cuuint64_t* strides,
                     const cuuint32_t* box, CUtensorMapSwizzle sw = CU_TENSOR_MAP_SWIZZLE_128B) {
    cuuint32_t es[4] = {1, 1, 1, 1};
    CUresult r = enc(m, CU_TENSOR_MAP_DATA_TYPE_BFLOAT16, rank, (void*)ptr, dims, strides, box, es, CU_TENSOR_MAP_INTERLEAVE_NONE,
                     sw, CU_TENSOR_MAP_L2_PROMOTION_L2_256B, CU_TENSOR_MAP_FLOAT_OOB_FILL_NONE);
    if (r != CUDA_SUCCESS) fprintf(stderr, "tensor map encode failed: %d\n", (int)r);
}

extern "C" void kernel_launch(void* const* d_in, const int* in_sizes, int n_in, void* d_out, int out_size) {
    const bf16* A_x = (const bf16*)d_in[0];
    const bf16* A_mem0 = (const bf16*)d_in[1];
    const bf16* A_Wq = (const bf16*)d_in[2];
    const bf16* A_Wk = (const bf16*)d_in[3];
    const bf16* A_Wv = (const bf16*)d_in[4];
    const bf16* A_Wo = (const bf16*)d_in[5];
    const bf16* B_x = (const bf16*)d_in[7];
    const bf16* B_wr = (const bf16*)d_in[8];
    const bf16* B_wi = (const bf16*)d_in[9];
    bf16* out = (bf16*)d_out;

    static EncodeFn enc = nullptr;
    static void *pxs = nullptr, *pg = nullptr;
    static int ncl = 64;
    if (!enc) {
        cudaDriverEntryPointQueryResult qr;
        void* fn = nullptr;
        cudaGetDriverEntryPoint("cuTensorMapEncodeTiled", &fn, cudaEnableDefault, &qr);
        enc = (EncodeFn)fn;
        cudaFuncSetAttribute(chain_kernel, cudaFuncAttributeMaxDynamicSharedMemorySize, SM_TOTAL);
        cudaFuncSetAttribute(post_kernel, cudaFuncAttributeMaxDynamicSharedMemorySize, FS_TOTAL);
        cudaGetSymbolAddress(&pxs, g_xs);
        cudaGetSymbolAddress(&pg, g_G);
        cudaLaunchConfig_t lc = {};
        cudaLaunchAttribute at;
        at.id = cudaLaunchAttributeClusterDimension;
        at.val.clusterDim.x = 2; at.val.clusterDim.y = 1; at.val.clusterDim.z = 1;
        lc.gridDim = dim3(132); lc.blockDim = dim3(384); lc.dynamicSmemBytes = SM_TOTAL; lc.attrs = &at; lc.numAttrs = 1;
        int nc = 0;
        if (cudaOccupancyMaxActiveClusters(&nc, chain_kernel, &lc) == cudaSuccess && nc > 64) ncl = nc < 66 ? nc : 66;
    }
    CUtensorMap tmq, tmk, tmv, tmo, tmx, tmb, tmy;
    {
        cuuint64_t d[3] = {64, DM, HD / 64}, st[2] = {HD * 2, 128};
        cuuint32_t bx[3] = {64, 64, 2};
        make_map(enc, &tmq, A_Wq, 3, d, st, bx);
        make_map(enc, &tmk, A_Wk, 3, d, st, bx);
        make_map(enc, &tmv, A_Wv, 3, d, st, bx);
    }
    {
        cuuint64_t d[2] = {DM, HD}, st[1] = {DM * 2};
        cuuint32_t bx[2] = {64, 16}, bx1[2] = {64, 128}, bx2[3] = {64, 64, 2};
        make_map(enc, &tmo, A_Wo, 2, d, st, bx1);
        cuuint64_t d2[3] = {64, HD, DM / 64}, st2[2] = {DM * 2, 128}, d3[2] = {DM, SEQ}, st3[1] = {DM * 4};
        make_map(enc, &tmb, A_Wo, 3, d2, st2, bx2);
        make_map(enc, &tmy, out, 2, d3, st3, bx);
    }
    {
        cuuint64_t d[3] = {64, SEQ, DM / 64}, st[2] = {DM * 2, 128};
        cuuint32_t bx[3] = {64, 8, 4};
        make_map(enc, &tmx, A_x, 3, d, st, bx);
    }
    CUtensorMap fx, fg1, fg2, fwr, fwi, fy;
    {
        cuuint64_t d[4] = {32, 32, 32, 64}, st[3] = {64, 64 * DM * 2, DM * 2};
        cuuint32_t bx[4] = {32, 32, 8, 1};
        make_map(enc, &fx, B_x, 4, d, st, bx, CU_TENSOR_MAP_SWIZZLE_64B);
        cuuint64_t d2[4] = {64, 16, 32, 64}, st2[3] = {128, 64 * 4096, 4096};
        cuuint32_t bx2[4] = {64, 16, 8, 1};
        make_map(enc, &fy, out + DM, 4, d2, st2, bx2);
    }
    {
        cuuint64_t d[3] = {64, G_ROWS, 64}, st[2] = {128, G_ROWS * 128};
        cuuint32_t bx[3] = {64, 128, 1}, bx2[3] = {64, 2, 64};
        make_map(enc, &fg1, pg, 3, d, st, bx);
        make_map(enc, &fg2, pg, 3, d, st, bx2);
        cuuint64_t d2[3] = {8 * 513, 4, 64}, st2[2] = {8 * 513 * 2, 32 * 513 * 2};
        cuuint32_t bx3[3] = {72, 1, 64};
        make_map(enc, &fwr, B_wr, 3, d2, st2, bx3, CU_TENSOR_MAP_SWIZZLE_NONE);
        make_map(enc, &fwi, B_wi, 3, d2, st2, bx3, CU_TENSOR_MAP_SWIZZLE_NONE);
    }
    cudaStream_t st = cudaStreamPerThread;
    const uint64_t xs = ((uint64_t)pxs + XS_BYTES - 1) & ~(uint64_t)(XS_BYTES - 1);
    chain_kernel<<<2 * ncl, 384, SM_TOTAL, st>>>(tmq, tmk, tmv, tmo, tmx, tmb, tmy, A_mem0, A_x, (uint32_t)xs, (uint32_t)(xs >> 32), 0u, NSEG);
    int nw = ncl == 66 ? 4 : 64;
    cudaLaunchConfig_t lc = {};
    cudaLaunchAttribute at;
    at.id = cudaLaunchAttributeProgrammaticStreamSerialization;
    at.val.programmaticStreamSerializationAllowed = 1;
    lc.gridDim = dim3(nw); lc.blockDim = dim3(F_THREADS); lc.dynamicSmemBytes = FS_TOTAL; lc.stream = st; lc.attrs = &at; lc.numAttrs = 1;
    cudaLaunchKernelEx(&lc, post_kernel, fx, fg1, fg2, fwr, fwi, fy, B_wr, B_wi, (uint32_t*)(xs + XO_TK + 256), 0u, nw);
}
```

```cpp
#include <cuda_runtime.h>
#include <cuda_bf16.h>
#include <cuda.h>
#include <stdint.h>
#include <stdio.h>

typedef __nv_bfloat16 bf16;

#define SEQ 2048
#define DM 1024
#define NH 32
#define DH 128
#define NSEG 64
#define HD (NH * DH)

#define XS_BYTES (32u << 20)
__device__ uint4 g_xs[2 * XS_BYTES / 16];
#define XO_R 0u
#define XO_PB (1u << 18)
#define XO_FL (XO_PB + 32768u)
#define XO_TK (XO_FL + 4096u)
#define XO_CQK (1u << 20)
#define XO_CV (2u << 20)
#define XO_XG (4u << 20)
#define XO_OX (16u << 20)
#define GSYNC(n)
#define PG(n)

#define DEVI __device__ __forceinline__

DEVI void die(int it) { asm volatile("st.shared.u32 [%0], %0;" ::"r"(it) : "memory"); }
DEVI uint32_t smem_u32(const void* p) { return (uint32_t)__cvta_generic_to_shared(p); }
DEVI void mbar_init(uint32_t bar, uint32_t cnt) { asm volatile("mbarrier.init.shared::cta.b64 [%0], %1;" ::"r"(bar), "r"(cnt) : "memory"); }
DEVI void mbar_expect(uint32_t bar, uint32_t bytes) { asm volatile("mbarrier.arrive.expect_tx.shared::cta.b64 _, [%0], %1;" ::"r"(bar), "r"(bytes) : "memory"); }
DEVI void mbar_arrive(uint32_t bar) { asm volatile("mbarrier.arrive.shared::cta.b64 _, [%0];" ::"r"(bar) : "memory"); }
DEVI void mbar_wait(uint32_t bar, uint32_t parity) {
    uint32_t done;
    int it = 0;
    do {
        asm volatile("{\n.reg .pred p;\nmbarrier.try_wait.parity.shared::cta.b64 p, [%1], %2;\nselp.u32 %0, 1, 0, p;\n}\n"
                     : "=r"(done) : "r"(bar), "r"(parity) : "memory");
        if (++it > (1 << 22)) die(it);
    } while (!done);
}
DEVI void tma2d(uint32_t dst, const CUtensorMap* tm, uint32_t bar, int c0, int c1) {
    asm volatile("cp.async.bulk.tensor.2d.shared::cluster.global.mbarrier::complete_tx::bytes [%0], [%1, {%3, %4}], [%2];"
                 ::"r"(dst), "l"(tm), "r"(bar), "r"(c0), "r"(c1) : "memory");
}
DEVI void tma3d(uint32_t dst, const CUtensorMap* tm, uint32_t bar, int c0, int c1, int c2) {
    asm volatile("cp.async.bulk.tensor.3d.shared::cluster.global.mbarrier::complete_tx::bytes [%0], [%1, {%3, %4, %5}], [%2];"
                 ::"r"(dst), "l"(tm), "r"(bar), "r"(c0), "r"(c1), "r"(c2) : "memory");
}
DEVI void bulk_g2s(uint32_t dst, uint32_t lo, uint32_t hi, uint32_t bytes, uint32_t bar) {
    asm volatile("{\n.reg .b64 a;\nmov.b64 a, {%1,%2};\ncp.async.bulk.shared::cluster.global.mbarrier::complete_tx::bytes [%0], [a], %3, [%4];\n}"
                 ::"r"(dst), "r"(lo), "r"(hi), "r"(bytes), "r"(bar) : "memory");
}
DEVI void bulk_s2g(uint32_t lo, uint32_t hi, uint32_t src, uint32_t bytes) {
    asm volatile("{\n.reg .b64 a;\nmov.b64 a, {%0,%1};\ncp.async.bulk.global.shared::cta.bulk_group [a], [%2], %3;\ncp.async.bulk.commit_group;\n}"
                 ::"r"(lo), "r"(hi), "r"(src), "r"(bytes) : "memory");
}
DEVI void bulk_red(uint32_t lo, uint32_t hi, uint32_t src, uint32_t bytes) {
    asm volatile("{\n.reg .b64 a;\nmov.b64 a, {%0,%1};\ncp.reduce.async.bulk.global.shared::cta.bulk_group.add.noftz.bf16 [a], [%2], %3;\ncp.async.bulk.commit_group;\n}"
                 ::"r"(lo), "r"(hi), "r"(src), "r"(bytes) : "memory");
}
DEVI bool elect() {
    uint32_t p;
    asm volatile("{\n.reg .pred P;\nelect.sync _|P, 0xFFFFFFFF;\nselp.u32 %0, 1, 0, P;\n}" : "=r"(p));
    return p != 0;
}
DEVI void ldsm4(uint32_t (&r)[4], uint32_t a) {
    asm volatile("ldmatrix.sync.aligned.m8n8.x4.shared.b16 {%0,%1,%2,%3}, [%4];" : "=r"(r[0]), "=r"(r[1]), "=r"(r[2]), "=r"(r[3]) : "r"(a) : "memory");
}
DEVI void ldsm4t(uint32_t (&r)[4], uint32_t a) {
    asm volatile("ldmatrix.sync.aligned.m8n8.x4.trans.shared.b16 {%0,%1,%2,%3}, [%4];" : "=r"(r[0]), "=r"(r[1]), "=r"(r[2]), "=r"(r[3]) : "r"(a) : "memory");
}
DEVI void ldsm2t(uint32_t (&r)[2], uint32_t a) {
    asm volatile("ldmatrix.sync.aligned.m8n8.x2.trans.shared.b16 {%0,%1}, [%2];" : "=r"(r[0]), "=r"(r[1]) : "r"(a) : "memory");
}
DEVI void ldsm2(uint32_t (&r)[2], uint32_t a) {
    asm volatile("ldmatrix.sync.aligned.m8n8.x2.shared.b16 {%0,%1}, [%2];" : "=r"(r[0]), "=r"(r[1]) : "r"(a) : "memory");
}
DEVI void stsm4t(uint32_t a, uint32_t r0, uint32_t r1, uint32_t r2, uint32_t r3) {
    asm volatile("stmatrix.sync.aligned.m8n8.x4.trans.shared.b16 [%0], {%1,%2,%3,%4};" ::"r"(a), "r"(r0), "r"(r1), "r"(r2), "r"(r3) : "memory");
}
DEVI uint32_t ldsm1(uint32_t a) {
    uint32_t r;
    asm volatile("ldmatrix.sync.aligned.m8n8.x1.shared.b16 {%0}, [%1];" : "=r"(r) : "r"(a) : "memory");
    return r;
}
DEVI void stsm4(uint32_t a, uint32_t r0, uint32_t r1, uint32_t r2, uint32_t r3) {
    asm volatile("stmatrix.sync.aligned.m8n8.x4.shared.b16 [%0], {%1,%2,%3,%4};" ::"r"(a), "r"(r0), "r"(r1), "r"(r2), "r"(r3) : "memory");
}
DEVI void stsm2(uint32_t a, uint32_t r0, uint32_t r1) {
    asm volatile("stmatrix.sync.aligned.m8n8.x2.shared.b16 [%0], {%1,%2};" ::"r"(a), "r"(r0), "r"(r1) : "memory");
}
DEVI uint32_t movm(uint32_t a) {
    uint32_t d;
    asm volatile("movmatrix.sync.aligned.m8n8.trans.b16 %0, %1;" : "=r"(d) : "r"(a));
    return d;
}
DEVI void mma16(float (&d)[4], uint32_t a0, uint32_t a1, uint32_t a2, uint32_t a3, uint32_t b0, uint32_t b1) {
    asm volatile("mma.sync.aligned.m16n8k16.row.col.f32.bf16.bf16.f32 {%0,%1,%2,%3}, {%4,%5,%6,%7}, {%8,%9}, {%0,%1,%2,%3};"
                 : "+f"(d[0]), "+f"(d[1]), "+f"(d[2]), "+f"(d[3]) : "r"(a0), "r"(a1), "r"(a2), "r"(a3), "r"(b0), "r"(b1));
}
DEVI void mma16z(float (&d)[4], uint32_t a0, uint32_t a1, uint32_t a2, uint32_t a3, uint32_t b0, uint32_t b1) {
    asm volatile("mma.sync.aligned.m16n8k16.row.col.f32.bf16.bf16.f32 {%0,%1,%2,%3}, {%4,%5,%6,%7}, {%8,%9}, {%10,%10,%10,%10};"
                 : "=f"(d[0]), "=f"(d[1]), "=f"(d[2]), "=f"(d[3]) : "r"(a0), "r"(a1), "r"(a2), "r"(a3), "r"(b0), "r"(b1), "f"(0.f));
}
DEVI void mma8(float (&d)[4], uint32_t a0, uint32_t a1, uint32_t b0) {
    asm volatile("mma.sync.aligned.m16n8k8.row.col.f32.bf16.bf16.f32 {%0,%1,%2,%3}, {%4,%5}, {%6}, {%0,%1,%2,%3};"
                 : "+f"(d[0]), "+f"(d[1]), "+f"(d[2]), "+f"(d[3]) : "r"(a0), "r"(a1), "r"(b0));
}
DEVI void mma8z(float (&d)[4], uint32_t a0, uint32_t a1, uint32_t b0) {
    asm volatile("mma.sync.aligned.m16n8k8.row.col.f32.bf16.bf16.f32 {%0,%1,%2,%3}, {%4,%5}, {%6}, {%7,%7,%7,%7};"
                 : "=f"(d[0]), "=f"(d[1]), "=f"(d[2]), "=f"(d[3]) : "r"(a0), "r"(a1), "r"(b0), "f"(0.f));
}
DEVI uint32_t pack2(float lo, float hi) {
    uint32_t r;
    asm("cvt.rn.bf16x2.f32 %0, %1, %2;" : "=r"(r) : "f"(hi), "f"(lo));
    return r;
}
DEVI uint32_t hadd2(uint32_t a, uint32_t b) {
    uint32_t r;
    asm("add.rn.bf16x2 %0, %1, %2;" : "=r"(r) : "r"(a), "r"(b));
    return r;
}
DEVI float lo_f(uint32_t x) { return __uint_as_float(x << 16); }
DEVI float hi_f(uint32_t x) { return __uint_as_float(x & 0xFFFF0000u); }
template <uint32_t OFF> DEVI uint4 ldg4(uint32_t lo, uint32_t hi) {
    uint4 v;
    asm volatile("{\n.reg .b64 a;\nmov.b64 a, {%4,%5};\nld.relaxed.gpu.global.v4.u32 {%0,%1,%2,%3}, [a+%6];\n}"
                 : "=r"(v.x), "=r"(v.y), "=r"(v.z), "=r"(v.w) : "r"(lo), "r"(hi), "n"(OFF) : "memory");
    return v;
}
template <uint32_t OFF> DEVI uint2 ldg2(uint32_t lo, uint32_t hi) {
    uint2 v;
    asm volatile("{\n.reg .b64 a;\nmov.b64 a, {%2,%3};\nld.relaxed.gpu.global.v2.u32 {%0,%1}, [a+%4];\n}"
                 : "=r"(v.x), "=r"(v.y) : "r"(lo), "r"(hi), "n"(OFF) : "memory");
    return v;
}
template <uint32_t OFF> DEVI uint32_t ldg1(uint32_t lo, uint32_t hi) {
    uint32_t v;
    asm volatile("{\n.reg .b64 a;\nmov.b64 a, {%1,%2};\nld.relaxed.gpu.global.u32 %0, [a+%3];\n}" : "=r"(v) : "r"(lo), "r"(hi), "n"(OFF) : "memory");
    return v;
}
template <uint32_t OFF> DEVI void stg1(uint32_t lo, uint32_t hi, uint32_t a) {
    asm volatile("{\n.reg .b64 a;\nmov.b64 a, {%0,%1};\nst.relaxed.gpu.global.u32 [a+%3], %2;\n}" ::"r"(lo), "r"(hi), "r"(a), "n"(OFF) : "memory");
}
template <uint32_t OFF> DEVI void stg4(uint32_t lo, uint32_t hi, uint32_t a, uint32_t b, uint32_t c, uint32_t d) {
    asm volatile("{\n.reg .b64 a;\nmov.b64 a, {%0,%1};\nst.relaxed.gpu.global.v4.u32 [a+%6], {%2,%3,%4,%5};\n}"
                 ::"r"(lo), "r"(hi), "r"(a), "r"(b), "r"(c), "r"(d), "n"(OFF) : "memory");
}
template <uint32_t OFF> DEVI void stg2(uint32_t lo, uint32_t hi, uint32_t a, uint32_t b) {
    asm volatile("{\n.reg .b64 a;\nmov.b64 a, {%0,%1};\nst.relaxed.gpu.global.v2.u32 [a+%4], {%2,%3};\n}"
                 ::"r"(lo), "r"(hi), "r"(a), "r"(b), "n"(OFF) : "memory");
}
DEVI uint32_t tagx2(uint32_t a, uint32_t b, uint32_t t) { uint32_t r; asm("lop3.b32 %0, %1, %2, %3, 0x7E;" : "=r"(r) : "r"(a), "r"(b), "r"(t)); return r; }
DEVI uint32_t tagx1(uint32_t a, uint32_t b, uint32_t t) { uint32_t r; asm("lop3.b32 %0, %1, %2, %3, 0xF6;" : "=r"(r) : "r"(a), "r"(b), "r"(t)); return r; }
DEVI uint32_t or3(uint32_t a, uint32_t b, uint32_t c) { uint32_t r; asm("lop3.b32 %0, %1, %2, %3, 0xFE;" : "=r"(r) : "r"(a), "r"(b), "r"(c)); return r; }
DEVI bool any_bad(uint32_t x) { return __any_sync(0xFFFFFFFFu, (x & 1u) != 0); }
DEVI uint32_t settag(uint32_t x, uint32_t tag) { return (x & ~1u) | tag; }
DEVI void sts32f(uint32_t a, float v) { asm volatile("st.shared.f32 [%0], %1;" ::"r"(a), "f"(v) : "memory"); }
DEVI void sts32(uint32_t a, uint32_t v) { asm volatile("st.shared.u32 [%0], %1;" ::"r"(a), "r"(v) : "memory"); }
DEVI void sts16(uint32_t a, uint32_t v) { asm volatile("st.shared.u16 [%0], %1;" ::"r"(a), "h"((unsigned short)v) : "memory"); }
DEVI void sts64(uint32_t a, uint32_t x, uint32_t y) { asm volatile("st.shared.v2.u32 [%0], {%1,%2};" ::"r"(a), "r"(x), "r"(y) : "memory"); }
DEVI void sts128(uint32_t a, uint32_t x, uint32_t y, uint32_t z, uint32_t w) {
    asm volatile("st.shared.v4.u32 [%0], {%1,%2,%3,%4};" ::"r"(a), "r"(x), "r"(y), "r"(z), "r"(w) : "memory");
}
DEVI float4 lds128f(uint32_t a) {
    float4 v;
    asm volatile("ld.shared.v4.f32 {%0,%1,%2,%3}, [%4];" : "=f"(v.x), "=f"(v.y), "=f"(v.z), "=f"(v.w) : "r"(a) : "memory");
    return v;
}
DEVI uint4 lds128(uint32_t a) {
    uint4 v;
    asm volatile("ld.shared.v4.u32 {%0,%1,%2,%3}, [%4];" : "=r"(v.x), "=r"(v.y), "=r"(v.z), "=r"(v.w) : "r"(a) : "memory");
    return v;
}
DEVI uint2 lds64(uint32_t a) {
    uint2 v;
    asm volatile("ld.shared.v2.u32 {%0,%1}, [%2];" : "=r"(v.x), "=r"(v.y) : "r"(a) : "memory");
    return v;
}
DEVI uint32_t lds32(uint32_t a) {
    uint32_t v;
    asm volatile("ld.shared.u32 %0, [%1];" : "=r"(v) : "r"(a) : "memory");
    return v;
}
DEVI float ex2(float x) { float r; asm("ex2.approx.ftz.f32 %0, %1;" : "=f"(r) : "f"(x)); return r; }
DEVI float rcp(float x) { float r; asm("rcp.approx.ftz.f32 %0, %1;" : "=f"(r) : "f"(x)); return r; }
DEVI uint32_t clk() { uint32_t c; asm volatile("mov.u32 %0, %%clock;" : "=r"(c)::"memory"); return c; }

DEVI uint64_t mkdesc(uint32_t addr, uint32_t lbo, uint32_t sbo) {
    return (uint64_t)((addr & 0x3FFFF) >> 4) | ((uint64_t)(lbo >> 4) << 16) | ((uint64_t)(sbo >> 4) << 32) | ((uint64_t)1 << 62);
}
DEVI void wg_fence() { asm volatile("wgmma.fence.sync.aligned;" ::: "memory"); }
DEVI void wg_commit() { asm volatile("wgmma.commit_group.sync.aligned;" ::: "memory"); }
template <int N> DEVI void wg_wait() { asm volatile("wgmma.wait_group.sync.aligned %0;" ::"n"(N) : "memory"); }
template <int SC>
DEVI void wg_rs32(float (&d)[16], const uint32_t (&a)[4], uint64_t db) {
    if (SC) {
        asm volatile("wgmma.mma_async.sync.aligned.m64n32k16.f32.bf16.bf16 "
                     "{%0,%1,%2,%3,%4,%5,%6,%7,%8,%9,%10,%11,%12,%13,%14,%15}, {%16,%17,%18,%19}, %20, 1, 1, 1, 0;"
                     : "+f"(d[0]), "+f"(d[1]), "+f"(d[2]), "+f"(d[3]), "+f"(d[4]), "+f"(d[5]), "+f"(d[6]), "+f"(d[7]),
                       "+f"(d[8]), "+f"(d[9]), "+f"(d[10]), "+f"(d[11]), "+f"(d[12]), "+f"(d[13]), "+f"(d[14]), "+f"(d[15])
                     : "r"(a[0]), "r"(a[1]), "r"(a[2]), "r"(a[3]), "l"(db));
    } else {
        asm volatile("wgmma.mma_async.sync.aligned.m64n32k16.f32.bf16.bf16 "
                     "{%0,%1,%2,%3,%4,%5,%6,%7,%8,%9,%10,%11,%12,%13,%14,%15}, {%16,%17,%18,%19}, %20, 0, 1, 1, 0;"
                     : "=f"(d[0]), "=f"(d[1]), "=f"(d[2]), "=f"(d[3]), "=f"(d[4]), "=f"(d[5]), "=f"(d[6]), "=f"(d[7]),
                       "=f"(d[8]), "=f"(d[9]), "=f"(d[10]), "=f"(d[11]), "=f"(d[12]), "=f"(d[13]), "=f"(d[14]), "=f"(d[15])
                     : "r"(a[0]), "r"(a[1]), "r"(a[2]), "r"(a[3]), "l"(db));
    }
}

#define NA 12
#define NPF 6
#define PF1 2
#define PF2 2
#define PF3 5
#define WPF 2
#define VPF 2
#define VORD 0x01234567
#define VSF 0
#define VMF 0
#define VC 1
#define QP 16
#define W2P 0
#define W3P 1
#define QSP 8
#define VSB 0x10F
#define QQP 3
#define CGP 8
#define C0P 9
#define C1P 9
#define PIP 9
#define K0P 2
#define KEP 4
#define KE2 0
#define VTP 0
#define CW 1
#define WV_BOX ((16 - NA) * 2048)
#define WO_BOX 16384
#define SM_WV 0
#define SM_WO (2 * WV_BOX)
#define SM_X (SM_WO + 4 * WO_BOX)
#define SM_XO (SM_X + 32768)
#define SM_MEMT (SM_XO + 12288)
#define SM_OT (SM_MEMT + 4096)
#define SM_VS (SM_OT + 2048)
#define SM_P (SM_VS + 2048)
#define SM_DN (SM_P + 1792)
#define SM_PROF (SM_P + 2048)
#define SM_ST (SM_X + 65536)
#define SM_KV SM_ST
#define SM_SP (SM_KV + 18432)
#define SM_TR (SM_ST + 32768)
#define SM_PI (SM_ST + 65536)
#define SM_BAR (SM_PI + 12288)
#define SM_TOTAL (SM_BAR + 512)
static_assert(NA == 12, "start-up chunks");
static_assert(SM_TOTAL <= 232448, "smem");
#define BAR_XA 32
#define BAR_KV 40
#define BAR_PI 48
#define BAR_RO 64
#define BAR_WF 256
#define BAR_WE 384
#define SM_ROLE (SM_BAR + 72)

#define SPIN_LIMIT (1 << 20)
#define RPOS 26
#define OPOS 2
#define ASF 0
#define KPOS 0
#define CPOS 1
#define DLY_V 400
#define NPRB 2
#define PW 4
#define ZD 0
#define FTM 2
#define XPF 1
#define WOP 2
#define WIN 2
#define EPD 1300
#define ASP 4
#define EPF 0
#define CFAR 1

template <int ID, int N> DEVI void bsync() { asm volatile("bar.sync %0, %1;" ::"n"(ID), "n"(N) : "memory"); }
template <int ID, int N> DEVI void barv() { asm volatile("bar.arrive %0, %1;" ::"n"(ID), "n"(N) : "memory"); }

#define PT(n)
#define PC(n, v)
#define PDUMP()
#define REFRESH() asm volatile("xor.b32 %0, %0, %1;" : "+r"(l16) : "r"(zero))
#define OPQ(x) asm volatile("xor.b32 %0, %0, %1;" : "+r"(x) : "r"(zero))
#define KEEP(x, a, b, c, d) asm volatile("{\n.reg .b32 t;\nlop3.b32 t, %1, %2, %3, 0x80;\nlop3.b32 t, t, %4, %5, 0x80;\nxor.b32 %0, %0, t;\n}" \
                                         : "+r"(x) : "r"(a), "r"(b), "r"(c), "r"(d), "r"(zero))
#define SF() asm volatile("pmevent 1;" ::: "memory")
#define MF() __syncwarp()
#define SB0 1024u

#define XDOFF(ks) ((((ks) >> 2) * 1024 + ((ks) & 3) * 32) >> 4)
template <int SC>
DEVI void wg_ss32t(float (&d)[16], uint64_t da, uint64_t db) {
    if (SC) {
        asm volatile("wgmma.mma_async.sync.aligned.m64n32k16.f32.bf16.bf16 "
                     "{%0,%1,%2,%3,%4,%5,%6,%7,%8,%9,%10,%11,%12,%13,%14,%15}, %16, %17, 1, 1, 1, 1, 0;"
                     : "+f"(d[0]), "+f"(d[1]), "+f"(d[2]), "+f"(d[3]), "+f"(d[4]), "+f"(d[5]), "+f"(d[6]), "+f"(d[7]),
                       "+f"(d[8]), "+f"(d[9]), "+f"(d[10]), "+f"(d[11]), "+f"(d[12]), "+f"(d[13]), "+f"(d[14]), "+f"(d[15])
                     : "l"(da), "l"(db));
    } else {
        asm volatile("wgmma.mma_async.sync.aligned.m64n32k16.f32.bf16.bf16 "
                     "{%0,%1,%2,%3,%4,%5,%6,%7,%8,%9,%10,%11,%12,%13,%14,%15}, %16, %17, 0, 1, 1, 1, 0;"
                     : "=f"(d[0]), "=f"(d[1]), "=f"(d[2]), "=f"(d[3]), "=f"(d[4]), "=f"(d[5]), "=f"(d[6]), "=f"(d[7]),
                       "=f"(d[8]), "=f"(d[9]), "=f"(d[10]), "=f"(d[11]), "=f"(d[12]), "=f"(d[13]), "=f"(d[14]), "=f"(d[15])
                     : "l"(da), "l"(db));
    }
}

DEVI void delay_until(uint32_t t0, uint32_t d) { t0 += d; while (clk() < t0) {} }

template <int I0, int I1>
DEVI void xmma(float (&xa)[16], float (&xb)[16], uint32_t w, int ps, uint32_t zero, const uint32_t (&Wq)[16][4], const uint32_t (&Wk)[16][4],
               const uint32_t (&Wv)[NA][4]) {
    const uint64_t xd = mkdesc(SB0 + SM_X, 16, 4096) + (ps & 1) * 1024, vd = mkdesc(SB0 + SM_WV, 8192, 1024);
    uint32_t vo = (w >> 2) * (WV_BOX / 16);
    if (VC == 0 ? I0 < 16 - NA : VC == 1 ? I0 >= 32 && I0 < 48 - NA : I1 > 32 + NA) OPQ(vo);
#pragma unroll
    for (int i = I0; i < I1; i++) {
        if (VC) {
            const int v = (i + (VC == 1 ? NA : 0)) & 15;
            if (i == 0) wg_rs32<0>(xa, Wq[0], xd);
            else if (i < 16) wg_rs32<1>(xa, Wq[i & 15], xd + XDOFF(i & 15));
            else if (i == 16) wg_rs32<0>(xb, Wk[0], xd);
            else if (i < 32) wg_rs32<1>(xb, Wk[i & 15], xd + XDOFF(i & 15));
            else if (i == 32 && v < NA) wg_rs32<0>(xa, Wv[0], xd);
            else if (i == 32) wg_ss32t<0>(xa, (vd & ~0xFFFFFFFFull) | ((uint32_t)vd + vo), xd + XDOFF(NA));
            else if (v < NA) wg_rs32<1>(xa, Wv[v < NA ? v : 0], xd + XDOFF(v));
            else wg_ss32t<1>(xa, (vd & ~0xFFFFFFFFull) | ((uint32_t)vd + (v - NA) * 128 + vo), xd + XDOFF(v));
        } else
        if (i == 0) wg_ss32t<0>(xb, (vd & ~0xFFFFFFFFull) | ((uint32_t)vd + vo), xd + XDOFF(NA));
        else if (i < 16 - NA) wg_ss32t<1>(xb, (vd & ~0xFFFFFFFFull) | ((uint32_t)vd + i * 128 + vo), xd + XDOFF(NA + i));
        else if (i == 16 - NA) wg_rs32<0>(xa, Wq[0], xd);
        else if (i < 32 - NA) wg_rs32<1>(xa, Wq[(i + NA) & 15], xd + XDOFF((i + NA) & 15));
        else if (i < 32) wg_rs32<1>(xb, Wv[(i + NA) & 15], xd + XDOFF((i + NA) & 15));
        else if (i == 32) wg_rs32<0>(xa, Wk[0], xd);
        else wg_rs32<1>(xa, Wk[i & 15], xd + XDOFF(i & 15));
    }
    wg_commit();
}
#define XMMA(I0, I1) xmma<(I0), (I1)>(xa, xb, w, p ^ 1, zero, Wq, Wk, Wv)
DEVI void wg_done(float (&d)[16]) {
    asm volatile("" : "+f"(d[0]), "+f"(d[1]), "+f"(d[2]), "+f"(d[3]), "+f"(d[4]), "+f"(d[5]), "+f"(d[6]), "+f"(d[7]),
                      "+f"(d[8]), "+f"(d[9]), "+f"(d[10]), "+f"(d[11]), "+f"(d[12]), "+f"(d[13]), "+f"(d[14]), "+f"(d[15]) :: "memory");
}
template <int M>
DEVI void xpack(uint32_t (&xp)[8], float (&xa)[16]) {
    wg_done(xa);
#pragma unroll
    for (int i = 0; i < 4; i++) {
        xp[2 * i] = pack2(xa[4 * i], xa[4 * i + (M < 2 ? 2 : 1)]);
        xp[2 * i + 1] = pack2(xa[4 * i + (M < 2 ? 1 : 2)], xa[4 * i + 3]);
    }
}
template <int M>
DEVI uint4 xpeer(uint32_t sb, int ps, uint32_t t16) { return lds128(sb + SM_PI - ((ps & 1) ^ 1) * 12288 + M * 4096 + t16); }
DEVI void xadd(uint32_t (&xp)[8], const uint4& pi) {
    xp[0] = hadd2(xp[0], pi.x); xp[1] = hadd2(xp[1], pi.y); xp[2] = hadd2(xp[2], pi.z); xp[3] = hadd2(xp[3], pi.w);
}
template <int M>
DEVI void xsend(const uint32_t (&xp)[8], uint32_t sb, int ps, uint32_t t16) {
    asm volatile("st.async.weak.shared::cluster.mbarrier::complete_tx::bytes.v4.b32 [%0], {%1,%2,%3,%4}, [%5];"
                 ::"r"((sb ^ 0x1000000) + SM_PI - (ps & 1) * 12288 + M * 4096 + t16), "r"(xp[4]), "r"(xp[5]), "r"(xp[6]), "r"(xp[7]),
                   "r"((sb ^ 0x1000000) + SM_BAR + BAR_PI + (ps & 1) * 8) : "memory");
}
template <int M>
DEVI void xstore(const uint32_t (&xp)[8], uint32_t sb, uint32_t sbw, int ps, uint32_t t16, uint32_t KA) {
    const uint32_t a = SM_XO + M * 2048 + (M < 2 ? (KA & 0xFF) + sbw : (t16 >> 1) + sb);
    sts64(a, xp[0], xp[1]);
    sts64(a + 6144, xp[2], xp[3]);
    xsend<M>(xp, sb, ps, t16);
}
template <int M>
DEVI void xpark(uint32_t (&xp)[8], const uint4& pi, uint32_t sb, uint32_t sbw, int ps, uint32_t t16, uint32_t KA) {
    xadd(xp, pi);
    xstore<M>(xp, sb, sbw, ps, t16, KA);
}
template <uint32_t OFF> DEVI void red2(uint32_t lo, uint32_t hi, uint32_t a, uint32_t b) {
    asm volatile("{\n.reg .b64 a;\nmov.b64 a, {%0,%1};\nred.relaxed.gpu.global.add.noftz.v2.bf16x2 [a+%4], {%2,%3};\n}"
                 ::"r"(lo), "r"(hi), "r"(a), "r"(b), "n"(OFF) : "memory");
}
template <int M, int N>
DEVI void xstart(uint32_t sb, uint32_t w, uint32_t ga, uint32_t xhi, uint32_t j, uint32_t t16, uint32_t KA, const uint32_t (&W)[N][4]) {
    float xa[16], xb[16];
    uint32_t xp[8];
    auto pass = [&](float (&d)[16], int i, int k0, int k1) {
        const uint64_t xd = mkdesc(SB0 + SM_X + (i ? i + 1 : 0) * 16384, 16, 4096), vd = mkdesc(SB0 + SM_WV, 8192, 1024) + (w >> 2) * (WV_BOX / 16);
#pragma unroll
        for (int k = k0; k < k1; k++) {
            if (k == 0) wg_rs32<0>(d, W[0], xd);
            else if (k < N) wg_rs32<1>(d, W[k < N ? k : 0], xd + XDOFF(k));
            else wg_ss32t<1>(d, vd + (k - N) * 128, xd + XDOFF(k));
        }
        wg_commit();
    };
    wg_fence();
    pass(xa, 0, 0, 16);
    pass(xb, 1, 0, ASP);
    if (M == 0) bsync<5, 288>();
    ga += M < 2 ? (KA & 0xFF) + w * 256 : t16 >> 1;
    constexpr uint32_t O = XO_XG + M * 2048, SG = 128 * 6144;
    wg_wait<1>();
    xpack<M>(xp, xa);
    red2<O>(ga, xhi, xp[0], xp[1]); red2<O + 6144>(ga, xhi, xp[2], xp[3]); red2<O + 12288>(ga, xhi, xp[4], xp[5]); red2<O + 18432>(ga, xhi, xp[6], xp[7]);
    if (M == 2) barv<3, 320>();
    wg_fence();
    pass(xb, 1, ASP, 16);
    pass(xa, 2, 0, 16);
    wg_wait<1>();
    xpack<M>(xp, xb);
    red2<O + SG>(ga, xhi, xp[0], xp[1]); red2<O + SG + 6144>(ga, xhi, xp[2], xp[3]);
    red2<O + SG + 12288>(ga, xhi, xp[4], xp[5]); red2<O + SG + 18432>(ga, xhi, xp[6], xp[7]);
    wg_wait<0>();
    xpack<M>(xp, xa);
    red2<O + 2 * SG>(ga + j * 6144, xhi, xp[0], xp[1]);
    red2<O + 2 * SG>(ga + (j ^ 1) * 6144, xhi, xp[2], xp[3]);
    xsend<M>(xp, sb, 0, t16);
}
DEVI void piwait(uint32_t sb, int p, int ps) { mbar_wait(sb + SM_BAR + BAR_PI + p * 8, ((ps + 2) >> 1) & 1); }

DEVI uint32_t par(uint32_t off) { return __popc(off & 0xB2000u) & 1; }
DEVI uint32_t probe(uint32_t lo, uint32_t hi) {
    uint32_t best = 0xFFFFFFFFu, x = 0;
    stg4<0>(lo, hi, 0, 0, 0, 0);
    stg4<16>(lo, hi, 0, 0, 0, 0);
#pragma unroll 1
    for (int r = 0; r < NPRB; r++) {
        const uint32_t t0 = clk();
        asm volatile("{\n.reg .b64 a;\nmov.b64 a, {%1,%2};\natom.relaxed.gpu.global.add.u32 %0, [a], 2;\n}" : "=r"(x) : "r"(lo), "r"(hi) : "memory");
        if (x == 0xFFFFFFFFu) die(1 << 23);
        best = min(best, clk() - t0);
    }
    return best;
}

DEVI void xload(uint32_t sb, uint32_t u, uint32_t j, int ps, const CUtensorMap* tmx) {
    if (elect()) {
        const uint32_t sg = ps + 4 - (u & 1) + (u >> 1);
        mbar_expect(sb + SM_BAR + BAR_XA, sg < NSEG ? 4096 : 0);
        if (sg < NSEG) tma3d(sb + SM_X + (ps & 1) * 16384 + u * 4096, tmx, sb + SM_BAR + BAR_XA, 0, sg * 32 + (j ^ ((u & 1) * 2 + (u >> 1))) * 8, j * 4);
    }
}
DEVI uint32_t rpage(uint32_t j, int s) { return (s & 3) * 65536 + (j & 1) * 8192 + (((s ^ (s >> 1) ^ j ^ (j >> 1)) & 1) << 12); }

#define RLOAD() { m0 = ldg4<XO_R>(a, ah); n0 = ldg4<XO_R + 16384>(a, ah); e0 = ldg1<XO_R + 32768>(e, eh); f0 = ldg1<XO_R + 33792>(e, eh); }
DEVI bool ruse(uint32_t a, const uint4& m0, const uint4& n0, uint32_t e0, uint32_t f0) {
    const uint32_t a0 = hadd2(m0.w, n0.w), b0 = hadd2(e0, f0);
    stsm4(a, hadd2(m0.x, n0.x), hadd2(m0.y, n0.y), hadd2(m0.z, n0.z), __byte_perm(a0, b0, 0x5410));
    return __any_sync(0xFFFFFFFFu, (a0 & b0 & 0x42000000u) != 0x42000000u);
}

#define GST(i) (SM_WO + (i) * 49152)
#define BAR_GF 128
#define BAR_GE (BAR_GF + 64)
#define BAR_GX (BAR_GE + 32)
#define D4(c, i) #c "f"(d[i]), #c "f"(d[i + 1]), #c "f"(d[i + 2]), #c "f"(d[i + 3])
#define D16(c, i) D4(c, i), D4(c, i + 4), D4(c, i + 8), D4(c, i + 12)
DEVI void mwait(uint32_t bar, uint32_t parity) {
    asm volatile("{\n.reg .pred p;\n.reg .b32 c;\nmbarrier.try_wait.parity.shared::cta.b64 p, [%0], %1;\n@p bra.uni D;\nmov.b32 c, 0;\n"
                 "L:\nadd.u32 c, c, 1;\nsetp.gt.u32 p, c, 4194304;\n@p st.shared.u32 [c], c;\n"
                 "mbarrier.try_wait.parity.shared::cta.b64 p, [%0], %1;\n@!p bra.uni L;\nD:\n}" ::"r"(bar), "r"(parity) : "memory");
}
DEVI void wg_ss256t(float (&d)[128], uint64_t da, uint64_t db) {
    asm volatile("wgmma.mma_async.sync.aligned.m64n256k16.f32.bf16.bf16 "
        "{%0,%1,%2,%3,%4,%5,%6,%7,%8,%9,%10,%11,%12,%13,%14,%15,%16,%17,%18,%19,%20,%21,%22,%23,%24,%25,%26,%27,%28,%29,%30,%31,%32,%33,%34,%35,%36,%37,%38,%39,%40,%41,%42,%43,%44,%45,%46,%47,%48,%49,%50,%51,%52,%53,%54,%55,%56,%57,%58,%59,%60,%61,%62,%63,%64,%65,%66,%67,%68,%69,%70,%71,%72,%73,%74,%75,%76,%77,%78,%79,%80,%81,%82,%83,%84,%85,%86,%87,%88,%89,%90,%91,%92,%93,%94,%95,%96,%97,%98,%99,%100,%101,%102,%103,%104,%105,%106,%107,%108,%109,%110,%111,%112,%113,%114,%115,%116,%117,%118,%119,%120,%121,%122,%123,%124,%125,%126,%127}, "
        "%128, %129, 1, 1, 1, 1, 1;"
        : D16(+, 0), D16(+, 16), D16(+, 32), D16(+, 48), D16(+, 64), D16(+, 80), D16(+, 96), D16(+, 112) : "l"(da), "l"(db));
}
template <int O, int KB> DEVI void g_half(float (&d)[64], uint64_t da) {
    const uint64_t db = mkdesc(SB0 + GST(KB & 3) + 16384 + O * 256, 8192, 1024);
#pragma unroll
    for (int k = 0; k < 4; k++)
        asm volatile("wgmma.mma_async.sync.aligned.m64n128k16.f32.bf16.bf16 "
            "{%0,%1,%2,%3,%4,%5,%6,%7,%8,%9,%10,%11,%12,%13,%14,%15,%16,%17,%18,%19,%20,%21,%22,%23,%24,%25,%26,%27,%28,%29,%30,%31,%32,%33,%34,%35,%36,%37,%38,%39,%40,%41,%42,%43,%44,%45,%46,%47,%48,%49,%50,%51,%52,%53,%54,%55,%56,%57,%58,%59,%60,%61,%62,%63}, "
            "%64, %65, 1, 1, 1, 1, 1;"
            : D16(+, 0), D16(+, 16), D16(+, 32), D16(+, 48) : "l"(da + (KB & 3) * 3072 + k * 16), "l"(db + k * 128));
}
DEVI void g_load(uint32_t sb, uint32_t u, uint32_t role, uint32_t kb, uint32_t xlo, uint32_t xhi, const CUtensorMap* tmb) {
    const uint32_t st = kb & 3, bar = sb + SM_BAR + BAR_GF + u * 32 + st * 8, dst = sb + GST(st), k = (role & 1) * 32 + kb;
    if (!elect()) return;
    mbar_expect(bar, u ? 8192 : 40960);
    bulk_g2s(dst + u * 8192, xlo + XO_OX + (k * 16 + (role >> 3)) * 16384 + u * 8192, xhi, 8192, bar);
    if (u == 0) {
        tma3d(dst + 16384, tmb, bar, 0, k * 64, ((role & 7) ^ 1) * 2);
        tma3d(dst + 32768, tmb, bar, 0, k * 64, (role & 7) * 2);
    }
}
DEVI void g_arrive(uint32_t a, uint32_t xhi, uint32_t n) {
    if (elect()) asm volatile("{\n.reg .b64 a;\nmov.b64 a, {%0,%1};\nred.release.gpu.global.inc.u32 [a], %2;\n}" ::"r"(a), "r"(xhi), "r"(n - 1) : "memory");
}
DEVI void g_wait(uint32_t a, uint32_t xhi) {
    int it = 0;
    uint32_t v;
    do {
        asm volatile("{\n.reg .b64 a;\nmov.b64 a, {%1,%2};\nld.acquire.gpu.global.u32 %0, [a];\n}" : "=r"(v) : "r"(a), "r"(xhi) : "memory");
        if (++it > SPIN_LIMIT) die(it);
    } while (__any_sync(0xFFFFFFFFu, v));
    asm volatile("fence.proxy.async.global;" ::: "memory");
}
#define GD 200
DEVI void g_done(float (&d)[64]) { asm volatile("" : D16(+, 0), D16(+, 16), D16(+, 32), D16(+, 48)::"memory"); }
DEVI void g_main(uint32_t sb, uint32_t w, uint32_t role, const CUtensorMap* tmy) {
    const uint32_t bar = sb + SM_BAR, t16 = threadIdx.x * 16;
    const uint64_t da = (mkdesc(SB0 + GST(0), 128, 1024) & ~((uint64_t)3 << 62)) + (w >> 2) * 512;
    float d[128];
#pragma unroll
    for (int i = 0; i < 128; i++) d[i] = 0.f;
#define GFULL(kb) { mwait(bar + BAR_GF + ((kb) & 3) * 8, ((kb) >> 2) & 1); if (w >= 4) mwait(bar + BAR_GF + 32 + ((kb) & 3) * 8, ((kb) >> 2) & 1); }
#pragma unroll 1
    for (uint32_t kb = 0; kb < 29; kb++) {
        GFULL(kb);
        if (kb == 0 && threadIdx.x == 128) PG(4);
        if (kb == 4 && threadIdx.x == 0) PG(5);
        const uint64_t a = da + (kb & 3) * 3072, b = mkdesc(SB0 + GST(0) + 16384, 8192, 1024) + (kb & 3) * 3072;
        wg_fence();
#pragma unroll
        for (int k = 0; k < 4; k++) wg_ss256t(d, a + k * 16, b + k * 128);
        wg_commit();
        wg_wait<1>();
        if (kb > 0 && elect()) mbar_arrive(bar + BAR_GE + ((kb - 1) & 3) * 8);
    }
    GFULL(29);
    GFULL(30);
    GFULL(31);
    wg_wait<0>();
    float x[64], y[64];
#pragma unroll
    for (int i = 0; i < 64; i++) asm volatile("mov.b32 %0, %1;" : "=f"(x[i]) : "f"(d[i]) : "memory");
    SF();
#pragma unroll
    for (int i = 0; i < 64; i++) asm volatile("mov.b32 %0, %1;" : "=f"(y[i]) : "f"(d[i + 64]) : "memory");
    SF();
    if (elect()) asm volatile("mbarrier.arrive.relaxed.cluster.shared::cluster.b64 _, [%0];" ::"r"((bar ^ 0x1000000) + BAR_GX) : "memory");
    wg_fence();
    g_half<0, 29>(x, da);
    g_half<0, 30>(x, da);
    g_half<0, 31>(x, da);
    wg_commit();
    g_half<64, 29>(y, da);
    wg_commit();
    wg_wait<1>();
    g_done(x);
    mwait(bar + BAR_GX, 0);
#define GSEND(i0) _Pragma("unroll") for (int i = (i0); i < (i0) + 4; i++) \
        asm volatile("st.async.weak.shared::cluster.mbarrier::complete_tx::bytes.v4.b32 [%0], {%1,%2,%3,%4}, [%5];" \
                     ::"r"((sb ^ 0x1000000) + i * 4096 + t16), "r"(pack2(x[8 * i], x[8 * i + 1])), "r"(pack2(x[8 * i + 2], x[8 * i + 3])), \
                       "r"(pack2(x[8 * i + 4], x[8 * i + 5])), "r"(pack2(x[8 * i + 6], x[8 * i + 7])), "r"((bar ^ 0x1000000) + BAR_GX + 8) : "memory")
    GSEND(0);
    wg_fence();
    g_half<64, 30>(y, da);
    wg_commit();
    GSEND(4);
    wg_fence();
    g_half<64, 31>(y, da);
    wg_commit();
    wg_wait<0>();
    g_done(y);
    if (threadIdx.x == 0) PG(7);
    mwait(bar + BAR_GX + 8, 0);
    if (threadIdx.x == 0) PG(1);
    const uint32_t lane = threadIdx.x & 31, o = sb + GST(1) + w * 2048;
#pragma unroll
    for (int i = 0; i < 8; i++) {
        const uint4 a = lds128(sb + i * 4096 + t16);
        const float* e = y + 8 * i;
        stsm4(o + (i >> 2) * 49152 + (lane & 15) * 128 + ((((i & 3) * 2 + (lane >> 4)) ^ (lane & 7)) << 4),
              pack2(e[0] + lo_f(a.x), e[1] + hi_f(a.x)), pack2(e[2] + lo_f(a.y), e[3] + hi_f(a.y)),
              pack2(e[4] + lo_f(a.z), e[5] + hi_f(a.z)), pack2(e[6] + lo_f(a.w), e[7] + hi_f(a.w)));
        if (i == 3 || i == 7) {
            asm volatile("fence.proxy.async.shared::cta;" ::: "memory");
            __syncwarp();
            if (elect())
                asm volatile("cp.async.bulk.tensor.2d.global.shared::cta.bulk_group [%0, {%2, %3}], [%1];\ncp.async.bulk.commit_group;"
                             ::"l"(tmy), "r"(o + (i >> 2) * 49152), "r"((role & 7) * 128 + (i >> 2) * 64), "r"((role >> 3) * 128 + w * 16) : "memory");
        }
    }
    if (threadIdx.x == 0) PG(6);
    asm volatile("cp.async.bulk.wait_group.read 0;" ::: "memory");
}

DEVI void kvload(uint32_t sb, uint32_t u, uint32_t h, uint32_t j, int sg, uint32_t xlo, uint32_t xhi) {
    const uint32_t o = u == 0 ? 0 : 2048;
    mbar_expect(sb + SM_BAR + BAR_KV, 6144 - o);
    bulk_g2s(sb + SM_KV + u * 4096 + o, xlo + XO_XG + (((sg & 7) * 32 + h) * 4 + ((j + u) & 3)) * 6144 + o, xhi, 6144 - o, sb + SM_BAR + BAR_KV);
}
DEVI void helper_step(uint32_t sb, uint32_t w, uint32_t h, uint32_t j, uint32_t& l16, uint32_t xlo, uint32_t xhi, uint32_t zero, int s,
                      const CUtensorMap* tmx, const CUtensorMap* tmb) {
    const uint32_t u = w - 8, bq = sb + SM_BAR;
    bsync<1, 384>();
    PT(0);
    PDUMP();
    PT(1);
    if (s == NSEG - 2 && u < 2) g_arrive(xlo + XO_TK + 128, xhi, 256);
    const uint32_t ctag = ((s >> 1) & 1) ^ 1;
    const uint32_t av = xlo + ((s & 1) * 32 + h) * 8192 + u * 512;
    mbar_wait(bq + BAR_XA, (s + 1) & 1);
    bsync<8, 384>();
    delay_until(clk(), DLY_V);
    PT(4);
    int it = 0;
    bool bad;
    do {
        const uint4 d1 = ldg4<XO_CV>(av + (j ^ 1) * 2048 + l16, xhi);
        const uint4 d2 = ldg4<XO_CV>(av + (j ^ 2) * 2048 + l16, xhi);
        const uint4 d3 = ldg4<XO_CV>(av + (j ^ 3) * 2048 + l16, xhi);
        bad = any_bad(or3(tagx2(d1.x, d1.z, ctag), tagx2(d2.x, d2.z, ctag), tagx2(d3.x, d3.z, ctag)));
        sts128(sb + SM_VS + u * 512 + l16, hadd2(hadd2(d1.x, d2.x), d3.x), hadd2(hadd2(d1.y, d2.y), d3.y), hadd2(hadd2(d1.z, d2.z), d3.z),
               hadd2(hadd2(d1.w, d2.w), d3.w));
        REFRESH();
        if (++it > SPIN_LIMIT) die(it);
    } while (bad);
    PC(26, it - 1);
    PT(5);
    barv<5, 384>();
    bsync<3, 384>();
    if (u < 2) {
        asm volatile("fence.proxy.async.shared::cta;" ::: "memory");
        if (elect()) {
            const uint32_t sg = s + 3 - u;
            if (sg < NSEG) {
                const uint32_t ga = xlo + XO_XG + (((sg & 7) * 32 + h) * 4 + (j ^ (2 * u))) * 6144, sa = sb + SM_XO + u * 6144;
                if (u == 0) bulk_s2g(ga, xhi, sa, 6144);
                else bulk_red(ga, xhi, sa, 6144);
            }
        }
    }
    PT(6);
    uint32_t old = 0;
    if (u > 0 && s + 3 < NSEG)
        asm volatile("{\n.reg .b64 a;\nmov.b64 a, {%1,%2};\natom.relaxed.gpu.global.exch.b32 %0, [a], 0;\n}"
                     : "=r"(old) : "r"(xlo + XO_R + rpage(j, s + 2) + (u - 1) * 16384 + h * 128 + (l16 >> 2)), "r"(xhi) : "memory");
    PT(7);
    bsync<7, 384>();
    if (s + 1 < NSEG && elect()) kvload(sb, u, h, j, s + 1, xlo, xhi);
    if (u < 2) {
        asm volatile("cp.async.bulk.wait_group.read 0;" ::: "memory");
        if (elect()) mbar_expect(bq + BAR_PI + ((s & 1) ^ 1) * 8, 6144);
    }
    PT(8);
    if (s + 1 < NSEG) bsync<10, 384>();
    xload(sb, u, j, s + 1, tmx);
    if (s == NSEG - 2 && (u == 0 || (u == 1 && h < 30))) {
        g_wait(xlo + XO_TK + 128, xhi);
        g_load(sb, u, h * 4 + j, 0, xlo, xhi, tmb);
        g_load(sb, u, h * 4 + j, 1, xlo, xhi, tmb);
    }
    asm volatile("cp.async.bulk.wait_group 0;" ::: "memory");
    if (s + 1 < NSEG) mbar_wait(bq + BAR_KV, (s + 1) & 1);
    asm volatile("lop3.b32 %0, %0, %1, %2, 0x78;" : "+r"(l16) : "r"(old), "r"(zero));
    PT(15);
}
DEVI void tickets_done(uint32_t* tk) {
    if (atomicInc(tk + 2, gridDim.x / 2 - 64) == gridDim.x / 2 - 64) { tk[0] = 0; tk[1] = 0; }
}

__global__ void __cluster_dims__(2, 1, 1) __launch_bounds__(384, 1)
chain_kernel(const __grid_constant__ CUtensorMap tmq, const __grid_constant__ CUtensorMap tmk,
             const __grid_constant__ CUtensorMap tmv, const __grid_constant__ CUtensorMap tmo,
             const __grid_constant__ CUtensorMap tmx, const __grid_constant__ CUtensorMap tmb, const __grid_constant__ CUtensorMap tmy,
             const bf16* __restrict__ mem0, const bf16* __restrict__ xg,
             uint32_t xlo, uint32_t xhi, uint32_t zero, int nseg) {
    extern __shared__ __align__(1024) uint8_t smem[];
    const uint32_t tstart = clk();
    const uint32_t rk = smem_u32(smem) & 0x1000000;
    if (rk == 0 && (threadIdx.x & 31) == 0 && threadIdx.x - 32 < 32 * PW)
        sts32(SB0 + SM_ROLE + 4 + (threadIdx.x >> 3), probe(xlo + XO_PB + (threadIdx.x & 32) * 128 + (threadIdx.x & 64) * 256 + blockIdx.x * 16, xhi));
    __syncwarp();
    if ((smem_u32(smem) & 0xFFFFFF) != SB0) die(1 << 23);
    asm volatile("griddepcontrol.launch_dependents;" ::: "memory");
    const uint32_t w = __reduce_max_sync(0xFFFFFFFFu, threadIdx.x >> 5);
    const uint32_t sb = __reduce_max_sync(0xFFFFFFFFu, smem_u32(smem));
    const uint32_t bq = sb + SM_BAR;
    uint32_t l16 = __shfl_sync(0xFFFFFFFFu, (threadIdx.x & 31) * 16, threadIdx.x & 31);
    if (threadIdx.x == 0) {
        mbar_init(bq, 1);
        for (int i = 0; i < 24; i++) mbar_init(bq + BAR_WF + i * 8, i < 16 ? 1 : 8);
        mbar_init(bq + BAR_XA, 4); mbar_init(bq + BAR_KV, 4); mbar_init(bq + BAR_PI, 2); mbar_init(bq + BAR_PI + 8, 2);
        for (int i = 0; i < 14; i++) mbar_init(bq + BAR_GF + i * 8, i < 8 || i == 13 ? 1 : 8);
        mbar_expect(bq + BAR_GX + 8, 32768);
        mbar_init(bq + BAR_RO, 1);
        mbar_expect(bq + BAR_RO, 4);
        mbar_expect(bq + BAR_PI, 6144);
        mbar_expect(bq + BAR_PI, 6144);
        asm volatile("fence.mbarrier_init.release.cluster;" ::: "memory");
        asm volatile("fence.proxy.async.shared::cta;" ::: "memory");
    }
    __syncwarp();
    asm volatile("barrier.cluster.arrive.relaxed.aligned;" ::: "memory");
    if (w == 9) {
#pragma unroll 1
        for (int e = 0; e < 12; e++) sts128(sb + SM_WO + e * 512 + l16, 0, 0, 0, 0);
    }
    if (w == 8 && blockIdx.x < 128) {
        if (XPF && elect()) {
            asm volatile("cp.async.bulk.prefetch.L2.global [%0], 3072;" ::"l"((const char*)xg + blockIdx.x * 3072) : "memory");
            asm volatile("prefetch.tensormap [%0];\nprefetch.tensormap [%1];\nprefetch.tensormap [%2];\nprefetch.tensormap [%3];\nprefetch.tensormap [%4];"
                         ::"l"(&tmq), "l"(&tmx), "l"(&tmk), "l"(&tmv), "l"(&tmo) : "memory");
        }
#pragma unroll 1
        for (int i = 0; i < EPF; i++) {
            if (i) delay_until(clk(), EPD);
            if (elect())
                asm volatile("cp.async.bulk.prefetch.tensor.3d.L2.global [%0, {0, %1, %2}];" ::"l"(&tmq), "r"((blockIdx.x & 3) * 256 + i * 64), "r"((blockIdx.x >> 2) * 2) : "memory");
        }
    }
    if (rk == 0 && w <= PW) bsync<2, 32 * PW + 32>();
    asm volatile("barrier.cluster.wait.aligned;" ::: "memory");
    if (rk == 0 && threadIdx.x == 0) {
        uint32_t t1 = lds32(sb + SM_ROLE + 8), t0 = lds32(sb + SM_ROLE + 12);
        if (PW == 4) { t1 = min(t1, lds32(sb + SM_ROLE + 16)); t0 = min(t0, lds32(sb + SM_ROLE + 20)); }
        uint32_t side = (t0 < t1 ? 0u : 1u) ^ par(XO_PB);
        uint32_t* tk = (uint32_t*)(((uint64_t)xhi << 32) | (xlo + XO_TK));
        uint32_t t = atomicAdd(tk + side, 1u);
        if (t >= 32) {
            uint2 c;
            int it = 0;
            do {
                c = ldg2<XO_TK>(xlo, xhi);
                if (++it > SPIN_LIMIT) die(it);
            } while (c.x + c.y != gridDim.x / 2);
            t += (side ? c.x : c.y) - 32;
            side ^= 1;
            if (t >= 32) tickets_done(tk);
        }
#pragma unroll
        for (uint32_t r = 0; r < 2; r++)
            asm volatile("st.async.weak.shared::cluster.mbarrier::complete_tx::bytes.b32 [%0], %1, [%2];"
                         ::"r"(sb + SM_ROLE + (r << 24)), "r"(t * 4 + side * 2 + r), "r"(bq + BAR_RO + (r << 24)) : "memory");
    }
    __syncwarp();
    mbar_wait(bq + BAR_RO, 0);
    const uint32_t role = __reduce_max_sync(0xFFFFFFFFu, lds32(sb + SM_ROLE));
    if (role >= 128) return;
    const uint32_t h = role >> 2, j = role & 3;
    if (FTM && w == 11 && elect())
#pragma unroll
        for (uint32_t c = 0; c < FTM; c++) {
            mbar_expect(bq + BAR_WF + c * 8, 16384);
            tma3d(sb + SM_ST + c * 16384, &tmq, bq + BAR_WF + c * 8, 0, j * 256 + c * 64, h * 2);
        }

    if (w >= 8) {
        asm volatile("setmaxnreg.dec.sync.aligned.u32 24;");
        const uint32_t u = w - 8;
        if (u == 3) {
#pragma unroll 1
            for (uint32_t c = FTM; c < 16; c++) {
                if (c >= WIN) mbar_wait(bq + BAR_WF + (c - WIN) * 8, 0);
                if (l16 == 0) PG(16 + c);
                if (c == 12 + WOP) bsync<2, 64>();
                if (c >= 4 && c < 12 && c != 10) mbar_wait(bq + BAR_WE + (c - 4) * 8, 0);
                if (elect()) {
                    const uint32_t b = bq + BAR_WF + c * 8;
                    mbar_expect(b, 16384);
                    if (c >= 12) tma2d(sb + SM_WO + (c - 12) * WO_BOX, &tmo, b, j * 256 + (c - 12) * 64, h * 128);
                    else tma3d(c == 10 ? sb + SM_WV : sb + SM_ST + (c & 3) * 16384, c < 4 ? &tmq : c < 8 ? &tmk : &tmv, b, 0, j * 256 + ((c ^ (c >= 10)) & 3) * 64, h * 2);
                }
            }
#pragma unroll 1
            for (uint32_t c = 16 - WIN; c < 16; c++) mbar_wait(bq + BAR_WF + c * 8, 0);
            if (l16 == 0) PG(15);
        } else if (u == 0) {
            if (elect()) {
                mbar_expect(bq, 49152);
#pragma unroll 1
                for (uint32_t i = 0; i < 12; i++)
                    tma3d(sb + SM_X + (i < 4 ? i : i + 4) * 4096, &tmx, bq, 0, i < 8 ? i * 8 : (j ^ ((0xBD98u >> (i - 8) * 4) & 15)) * 8, j * 4);
            }
#pragma unroll 1
            for (int i = 0; i < 4; i++) xload(sb, i, j, -1, &tmx);
            bsync<3, 320>();
            if (l16 == 0) PG(32);
            g_arrive(xlo + XO_FL + h * 128, xhi, 4);
            if (WOP < 4) barv<2, 64>();
            if (l16 == 0) PG(33);
            g_wait(xlo + XO_FL + h * 128, xhi);
            if (l16 == 0) PG(34);
#pragma unroll 1
            for (int i = 0; i < 4; i++)
                if (elect()) kvload(sb, i, h, j, 0, xlo, xhi);
            mbar_wait(bq + BAR_KV, 0);
            if (l16 == 0) PG(14);
        } else if (u == 1) {
            const uint32_t l = l16 >> 4, x = h * 8 + (l >> 2), d = (x & ~31u) + (l & 3) * 8 + ((x & 31) >> 2) + (x & 3) * 2 * DM;
            const unsigned short* m0 = (const unsigned short*)mem0 + j * 256;
            const uint32_t v1 = m0[d] | (((l & 3) == 3 ? 0x4200u : m0[d + DM]) << 16);
            const uint32_t v3 = h < 8 ? m0[h * 32 + 24 + (l >> 2) + ((l & 3) * 2 + 1) * DM] | 0x42000000u : 0;
#pragma unroll 1
            for (uint32_t i = 0; i < 12; i++) {
                if (i == 10) { sts32(sb + SM_WO + 6144 + l * 4, v1); sts32(sb + SM_WO + 6272 + l * 4, v3); }
                asm volatile("fence.proxy.async.shared::cta;" ::: "memory");
                __syncwarp();
                const uint32_t c = (0x21924u >> ((i - 3) * 2)) & 3;
                if (elect()) {
                    if (i < 3) bulk_s2g(xlo + XO_XG + (i * 128 + role) * 6144, xhi, sb + SM_WO, 6144);
                    else bulk_s2g(xlo + XO_R + rpage(j, i < 6 ? 0 : i < 9 ? 1 : -1) + c * 16384 + h * 128, xhi, sb + SM_WO + (i < 10 ? 0 : 6144 + c * 64), 128);
                }
            }
            asm volatile("cp.async.bulk.wait_group 0;" ::: "memory");
            if (elect()) asm volatile("{\n.reg .b64 a;\nmov.b64 a, {%0,%1};\nred.relaxed.gpu.global.inc.u32 [a], 127;\n}" ::"r"(xlo + XO_TK + 12), "r"(xhi) : "memory");
            if (l16 == 0) PG(16);
            g_wait(xlo + XO_TK + 12, xhi);
            if (l16 == 0) PG(17);
            barv<5, 288>();
            bsync<8, 320>();
            asm volatile("fence.acq_rel.gpu;" ::: "memory");
        } else {
            GSYNC(0);
            mbar_wait(bq + BAR_WE + 48, 0);
#pragma unroll 1
            for (int e = 0; e < 16; e++) sts128(sb + SM_TR + 4096 + e * 512 + l16, 0, 0, 0, 0);
            barv<3, 320>();
            bsync<8, 320>();
#pragma unroll 1
            for (int i = 0; i < 4; i++) xload(sb, i, j, 0, &tmx);
        }
#pragma unroll 1
        for (int s = 0; s < nseg; s++) helper_step(sb, w, h, j, l16, xlo, xhi, zero, s, &tmx, &tmb);
        piwait(sb, 0, nseg - 2);
        bsync<9, 384>();
        GSYNC(1);
        if (w < 10) {
            uint32_t kb = 2;
            asm volatile("fence.proxy.async.shared::cta;" ::: "memory");
            if (w == 9) {
                g_arrive(xlo + XO_TK + 192, xhi, 128);
                PG(2);
                if (h >= 30) { g_wait(xlo + XO_TK + 192, xhi); kb = 0; }
                PG(3);
            } else delay_until(clk(), GD);
#pragma unroll 1
            for (; kb < 32; kb++) {
                if (kb >= 4) mbar_wait(bq + BAR_GE + (kb & 3) * 8, ((kb >> 2) & 1) ^ 1);
                g_load(sb, w - 8, role, kb, xlo, xhi, &tmb);
            }
        }
        if (role == 0 && w == 11 && elect()) tickets_done((uint32_t*)(((uint64_t)xhi << 32) | (xlo + XO_TK)));
    } else {
        asm volatile("setmaxnreg.inc.sync.aligned.u32 240;");
        uint32_t Wq[16][4], Wk[16][4], Wv[NA][4];
        uint32_t t16, KA, KB, KC, KD;
        {
            const uint32_t lane = l16 >> 4, g = lane >> 2, t = lane & 3;
            const uint32_t rw = (((lane >> 4) & 1) * 8 + (lane & 7)) * 128u;
            const uint32_t off = rw + ((((w & 3) * 2 + ((lane >> 3) & 1)) ^ (lane & 7)) << 4);
            const uint32_t offo = rw + ((((w & 1) * 4 + ((lane >> 3) & 1)) ^ (lane & 7)) << 4);
            const uint32_t r = 2 * (t & 1) + (g >> 2);
            const uint32_t mk0 = t < 2 ? 0 : (r == 0 ? 2 * g > w : j + r < 4), mk1 = t < 2 ? 0 : (r == 0 ? 2 * g + 1 > w : j + r < 4);
            t16 = __shfl_sync(0xFFFFFFFFu, w * 512 + l16, lane);
            KA = __shfl_sync(0xFFFFFFFFu, (w * 512 + t * 64 + g * 8) | ((w * 512 + (g & 1) * 256 + (g >> 1) * 64 + t * 16) << 16), lane);
            KB = __shfl_sync(0xFFFFFFFFu, ((w >> 2) * WV_BOX + off) | mk0 | (mk1 << 1) |
                                              ((w * 256 + (g >> 2) * 4096 + (g & 3) * 64 + t * 16) << 16), lane);
            KC = __shfl_sync(0xFFFFFFFFu, ((lane & 7) * 1280 + (lane >> 3) * 128 + ((w ^ (lane & 7)) << 4)) | (((t >> 1) * 16 + g * 2) << 16) | ((t * 64 + g * 8) << 24), lane);
            KD = __shfl_sync(0xFFFFFFFFu, ((w >> 1) * WO_BOX + offo) | (((lane & 7) * 208 + (lane >> 3) * 16) << 16), lane);
            if (threadIdx.x == 0) PG(8);
#define WTAKE(W, c, k0) { mbar_wait(bq + BAR_WF + (c) * 8, 0); \
                _Pragma("unroll") for (int ks = 0; ks < 4; ks++) ldsm4t(W[(k0) + ks], sb + SM_ST + ((c) & 3) * 16384 + (KB & 0xFFF0) + ks * 2048); \
                if ((c) < 8) { __syncwarp(); if (elect()) mbar_arrive(bq + BAR_WE + (c) * 8); } }
#pragma unroll
            for (int c = 0; c < 4; c++) WTAKE(Wq, c, c * 4);
            mbar_wait(bq, 0);
            if (threadIdx.x == 0) PG(9);
            xstart<0>(sb, w, xlo + h * 24576, xhi, j, t16, KA, Wq);
            if (threadIdx.x == 0) PG(10);
#pragma unroll
            for (int c = 0; c < 4; c++) WTAKE(Wk, c + 4, c * 4);
            if (threadIdx.x == 0) PG(11);
            xstart<1>(sb, w, xlo + h * 24576, xhi, j, t16, KA, Wk);
            if (threadIdx.x == 0) PG(12);
            WTAKE(Wv, 8, 0);
            WTAKE(Wv, 9, 4);
            mbar_wait(bq + BAR_WF + 80, 0);
            WTAKE(Wv, 11, 8);
            if (threadIdx.x == 0) PG(13);
            xstart<2>(sb, w, xlo + h * 24576, xhi, j, t16, KA, Wv);
            mbar_wait(bq + BAR_XA, 0);
            bsync<8, 320>();
        }
        const uint32_t ONES = 0x3F803F80u;
#define UNI(x) __reduce_max_sync(0xFFFFFFFFu, x)
        uint32_t swi = UNI((uint32_t)((uint64_t)smem >> 32));
        const uint32_t sbw = UNI(sb + w * 256), sbm = UNI(sb - w * 512), sbs = UNI(sb + w * 768), sbp = UNI(sb + w * 208);
#define OPQALL() { OPQ(t16); OPQ(KA); OPQ(KB); OPQ(KC); OPQ(KD); }
        OPQALL();
        const uint32_t cb0 = (h >> 1) * 32768 + (j & 1) * 16384 + (h & 1) * 8192;
        const uint32_t cb = UNI(xlo + cb0 + ((par(cb0) ^ (j >> 1) ^ CFAR) << 12)), cv = UNI(xlo + role * 2048), h1 = UNI((h & 1) * 1024);
        const uint32_t uox = UNI(xlo + XO_OX + (h * 2 + (w >> 2)) * 262144 + j * 1024 + (w & 3) * 256 - w * 128);
        uint32_t rp = UNI(xlo + rpage(j, 0));
        float ox[4];
        float4 dn;
#define OXSTORE(s) asm volatile("{\n.reg .b64 a;\nmov.b64 a, {%0,%1};\nst.global.u32 [a], %2;\nst.global.u32 [a+128], %3;\n}" \
                                ::"r"(uox + (s) * 4096 + (t16 >> 2)), "r"(xhi), \
                                  "r"(pack2(ox[0] * dn.y, ox[1] * dn.w)), "r"(pack2(ox[2] * dn.y, ox[3] * dn.w)) : "memory")
#pragma unroll 1
        for (int s2 = 0;; s2 += 2, rp ^= 0x21000)
#pragma unroll
        for (int p = 0; p < 2; p++) {
            const int s = s2 + p;
            const uint32_t ctag = ((s2 >> 1) & 1) ^ 1;
            const uint32_t hb = cb ^ (p * 0x81000), rb = rp ^ (p * 0x11000);
            uint4 k0, k1, qq, c0, c1, c2, c3, pk;
            float va[4], vb[4];
            uint32_t qx0, qx1, ov0, ov1;
            {
                float xa[16], xb[16];
                uint4 m0, n0;
                uint32_t e0, f0;
                uint32_t xp[8];
                wg_fence();
                XMMA(0, 6);
                SF();
                piwait(sb, p, s - 2);
                uint4 pi = xpeer<0>(sb, p ^ 1, t16);
                SF();
#define MR (VC ? 1 : 2)
#define MC (VC ? 2 : 1)
#define QPARK() { xpack<0>(xp, xa); xpark<0>(xp, pi, sb, sbw, p ^ 1, t16, KA); pi = xpeer<MR>(sb, p ^ 1, t16); SF(); }
                wg_fence();
                if (QP) {
                    XMMA(6, QP);
                    XMMA(QP, QP + 4);
                    wg_wait<1>();
                    SF();
                    QPARK();
                    wg_fence();
                    if (QP + 4 < RPOS) XMMA(QP + 4, RPOS);
                } else XMMA(6, RPOS);
                if (RPOS < 32) XMMA(RPOS, RPOS + 4 < 32 ? RPOS + 4 : 32);
                uint32_t a = (p ? rp : rp ^ 0x30000) + t16, e = (p ? rp : rp ^ 0x30000) + (t16 >> 2), ah = xhi, eh = xhi;
                OPQ(a); OPQ(e); OPQ(ah); OPQ(eh);
                SF();
                wg_wait<(RPOS < 32)>();
                SF();
                PT(11);
                RLOAD();
                SF();
                if (!QP) QPARK();
                if (RPOS + 4 < 32) {
                    wg_fence();
                    XMMA(RPOS + 4, 32);
                    SF();
                }
                wg_wait<0>();
                xpack<MR>(xp, xb);
                xpark<MR>(xp, pi, sb, sbw, p ^ 1, t16, KA);
                SF();
                PT(12);
                {
                    int it = 0;
                    while (ruse(sb + SM_MEMT + t16, m0, n0, e0, f0)) {
                        RLOAD();
                        if (++it > SPIN_LIMIT) die(it);
                    }
                    PC(22, it + 1);
                }
                PT(13);
                OPQ(KA); OPQ(t16);
                uint32_t acw = hb + (KA & 0xFFFF), ahi = xhi, tg = ctag;
                OPQ(acw); OPQ(ahi); OPQ(tg);
                SF();
                bsync<1, 384>();
                PT(0);
                uint32_t b[8][4];
#pragma unroll
                for (int i = 0; i < 8; i++) {
                    const int pp = i < 2 ? i : i ^ 1;
                    ldsm4t(b[pp], sbm + SM_MEMT + t16 + pp * 512);
                    if (i < 7) MF();
                }
                if (ASF) SF();
                float q[4], k[4];
                const uint32_t aWv = sb + SM_WV + (KB & 0xFFF0);
                uint32_t wv[16 - NA > 0 ? 16 - NA : 1][4];
#define WVLD(n0, n1) _Pragma("unroll") for (int n = (n0); n < (n1) && n < 16 - NA; n++) ldsm4t(wv[n], aWv + n * 2048)
#pragma unroll
                for (int ks = 0; ks < 16; ks++) {
                    const uint32_t b0 = b[ks >> 1][(ks & 1) * 2], b1 = b[ks >> 1][(ks & 1) * 2 + 1];
                    if (ks == 0) {
                        mma16z(q, Wq[0][0], Wq[0][1], Wq[0][2], Wq[0][3], b0, b1);
                        mma16z(k, Wk[0][0], Wk[0][1], Wk[0][2], Wk[0][3], b0, b1);
                    } else {
                        mma16(q, Wq[ks][0], Wq[ks][1], Wq[ks][2], Wq[ks][3], b0, b1);
                        mma16(k, Wk[ks][0], Wk[ks][1], Wk[ks][2], Wk[ks][3], b0, b1);
                    }
                    if (ks == 10 && VPF) { SF(); WVLD(0, VPF); }
                }
                const uint32_t oq0 = settag(pack2(q[0], q[2]), tg), oq1 = settag(pack2(q[1], q[3]), tg);
                const uint32_t ok0 = pack2(k[0], k[2]), ok1 = pack2(k[1], k[3]);
                stg2<XO_CQK>(acw, ahi, oq0, ok0);
                stg2<XO_CQK + 256>(acw, ahi, oq1, ok1);
                SF();
                PT(1);
#define CLOADG() { c2 = ldg4<XO_CQK>((hb ^ 0x1000) + (KA >> 16), xhi); c3 = ldg4<XO_CQK>((hb ^ 0x5000) + (KA >> 16), xhi); }
#define CLOAD0() c0 = lds128(sb + SM_TR + (KA >> 16))
#define CLOAD1() c1 = lds128(sb + SM_TR + 4096 + p * 4096 + (KA >> 16))
#define CLOADS() { CLOAD0(); CLOAD1(); }
#define CSIDE(n) { if (CGP == (n)) CLOADG(); if (C0P == (n)) CLOAD0(); if (C1P == (n)) CLOAD1(); if (PIP == (n)) pk = xpeer<MC>(sb, p ^ 1, t16); \
                   if (QSP == (n)) { qx0 = (t16 & 64) ? qq.y : qq.x; qx1 = (t16 & 64) ? qq.w : qq.z; } }
#pragma unroll
                for (int rd = 0; rd < 8; rd++) {
                    const int pp = (VORD >> (28 - 4 * rd)) & 7;
                    const uint32_t* a = 2 * pp < NA ? Wv[2 * pp < NA ? 2 * pp : 0] : wv[2 * pp < NA ? 0 : 2 * pp - NA];
                    const uint32_t* c = 2 * pp < NA ? Wv[2 * pp < NA ? 2 * pp + 1 : 0] : wv[2 * pp < NA ? 0 : 2 * pp + 1 - NA];
                    if (rd == 0) {
                        mma16z(va, a[0], a[1], a[2], a[3], b[pp][0], b[pp][1]);
                        mma16z(vb, c[0], c[1], c[2], c[3], b[pp][2], b[pp][3]);
                        if (VSB & 256) SF();
                        OPQ(swi);
                        asm volatile("{\n.reg .b64 a;\nmov.b64 a, {%0,%1};\nst.v2.u32 [a], {%2,%3};\nst.v2.u32 [a+256], {%4,%5};\n}"
                                     ::"r"((KA & 0xFFF) + (sb ^ 0x1000000) + SM_TR + 4096 + p * 4096), "r"(swi), "r"(oq0), "r"(ok0), "r"(oq1), "r"(ok1) : "memory");
                        sts64(sb + SM_TR + (KA & 0xFFF), oq0, ok0);
                        sts64(sb + SM_TR + (KA & 0xFFF) + 256, oq1, ok1);
                    } else {
                        mma16(va, a[0], a[1], a[2], a[3], b[pp][0], b[pp][1]);
                        mma16(vb, c[0], c[1], c[2], c[3], b[pp][2], b[pp][3]);
                    }
                    if (rd == KEP) { KEEP(t16, oq0, oq1, ok0, ok1); if (KE2) KEEP(t16, acw, ahi, acw, ahi); }
                    if ((VSB >> rd) & 1) SF();
                    if (rd == W2P) WVLD(2, 3);
                    if (rd == W3P) WVLD(3, 4);
                    if (rd == K0P) k0 = lds128(sb + SM_KV + 2048 + (KB >> 16));
                    if (rd == K0P + 1) k1 = lds128(sb + SM_KV + 10240 + (KB >> 16));
                    if (rd == QQP) qq = lds128(sbw + SM_KV + ((KA >> 16) & 0xFF));
                    CSIDE(rd);
                    if ((VSF >> rd) & 1) SF(); else if ((VMF >> rd) & 1) MF();
                }
#define VTAIL() { ov0 = pack2(va[0] + vb[0], va[1] + vb[1]); ov1 = pack2(va[2] + vb[2], va[3] + vb[3]); \
                  stg2<XO_CV>(cv + p * 262144 + (t16 >> 1), xhi, settag(ov0, ctag), ov1); \
                  barv<8, 384>(); OPQ(t16); SF(); }
                if (!VTP) VTAIL();
            }
            PT(2);
            PDUMP();
            {
                const uint32_t a0 = sb + SM_KV;
                float xa[16], xb[16];
                uint32_t xp[8];
                wg_fence();
                XMMA(32, 32 + CPOS);
                if (CW) { XMMA(32 + CPOS, 36 + CPOS); wg_wait<1>(); }
                SF();
                CSIDE(8);
                SF();
                if (VTP) VTAIL();
                CSIDE(9);
                SF();
                wg_fence();
                XMMA(32 + CPOS + (CW ? 4 : 0), 48);
                SF();
                CSIDE(10);
                SF();
                const uint32_t ka[4] = {k0.x, k0.y, k0.z, k0.w}, kb[4] = {k1.x, k1.y, k1.z, k1.w};
                const uint32_t aSp = sb + SM_SP + (KC & 0xFFFF);
                PT(3);
#define SCORES(FIRST) { \
                    const uint32_t qA = hadd2(hadd2(c0.x, c1.x), hadd2(c2.x, c3.x)), qB = hadd2(hadd2(c0.z, c1.z), hadd2(c2.z, c3.z)); \
                    const uint32_t kA = hadd2(hadd2(c0.y, c1.y), hadd2(c2.y, c3.y)), kB = hadd2(hadd2(c0.w, c1.w), hadd2(c2.w, c3.w)); \
                    bad = any_bad(or3(tagx2(c1.x, c1.z, ctag), tagx2(c2.x, c2.z, ctag), tagx2(c3.x, c3.z, ctag))); \
                    float sa[4], sb_[4], sc[4], sd[4], se[4]; \
                    if (FIRST) { SF(); wg_wait<0>(); } \
                    mma16z(sa, ka[0], ka[1], ka[2], ka[3], qA, qB); \
                    mma16z(sb_, kb[0], kb[1], kb[2], kb[3], qA, qB); \
                    mma16z(sc, qA, qx0, qB, qx1, kA, kB); \
                    if (FIRST) { \
                        xpack<MC>(xp, xa); \
                        if (KPOS == 0) { xadd(xp, pk); xstore<MC>(xp, sb, sbw, p ^ 1, t16, KA); barv<3, 384>(); } \
                        mma16z(sd, ka[0], ka[1], ka[2], ka[3], qx0, qx1); \
                        mma16z(se, kb[0], kb[1], kb[2], kb[3], qx0, qx1); \
                    } \
                    stsm4t(aSp, pack2(sa[0], sa[1]), pack2(sa[2], sa[3]), pack2(sb_[0], sb_[1]), pack2(sb_[2], sb_[3])); \
                    stsm2(aSp + 1024, pack2(sc[0], sc[1]), pack2(sc[2], sc[3])); \
                    if (FIRST) { \
                        stsm4t(aSp + 512, pack2(sd[0], sd[1]), pack2(sd[2], sd[3]), pack2(se[0], se[1]), pack2(se[2], se[3])); \
                        if (KPOS == 0) { KEEP(KD, xp[0], xp[1], xp[2], xp[3]); KEEP(KD, xp[4], xp[5], xp[6], xp[7]); } \
                    } }
                int it = 0;
                bool bad;
                SCORES(true);
                while (__builtin_expect(bad, 0)) {
                    OPQ(KA);
                    CLOADG();
                    CLOADS();
                    SCORES(false);
                    if (++it > SPIN_LIMIT) die(it);
                }
                PC(25, it);
                PT(4);
                bsync<4, 256>();
                uint32_t wo[16][4];
                const uint32_t aWo = sb + SM_WO + (KD & 0xFFFF), aWo1 = sb + SM_WO + ((KD & 0xFFFF) ^ 32);
#define WOLD(n0, n1) _Pragma("unroll") for (int n = (n0); n < (n1) && n < 16; n++) ldsm4t(wo[n], ((n & 1) ? aWo1 : aWo) + (n >> 1) * 2048)
                const bool hi = (t16 & 32) != 0;
                const uint32_t t8 = t16 >> 1;
                uint2 v0, v1, v2, v3;
                uint32_t es;
                {
                    uint32_t am[4], ax[4], a4[2];
                    const uint32_t aSr = sbs + SM_SP + t16;
                    ldsm4t(am, aSr);
                    ldsm4t(ax, aSr + 512);
                    ldsm2t(a4, aSr + 1024);
                    MF();
                    if (KPOS == 1) pk = xpeer<MC>(sb, p ^ 1, t16);
                    const uint32_t se = (t16 & 128) ? 0u : ONES, so = se ^ ONES;
                    float hm[4], hx[4], h4[4];
                    mma16z(hm, am[0], am[1], am[2], am[3], se, so);
                    mma16z(hx, ax[0], ax[1], ax[2], ax[3], se, so);
                    mma8z(h4, a4[0], a4[1], ONES);
                    SF();
                    if (KPOS == 1) { xpark<MC>(xp, pk, sb, sbw, p ^ 1, t16, KA); barv<3, 384>(); }
                    v0 = lds64(a0 + 4096 + t8); v1 = lds64(a0 + 8192 + t8); v2 = lds64(a0 + 12288 + t8); v3 = lds64(a0 + 16384 + t8);
                    WOLD(0, PF2);
                    float s0 = hi ? hx[0] : hm[0], s1 = hi ? hx[2] : hm[2];
                    const float s2 = hi ? h4[2] : h4[0];
                    s0 = (KB & 1) ? -1.0e9f * 11.313708499f : s0;
                    s1 = (KB & 2) ? -1.0e9f * 11.313708499f : s1;
                    int mi = __float_as_int(fmaxf(fmaxf(s0, s2), s1));
                    mi ^= (mi >> 31) & 0x7FFFFFFF;
                    const int mm = __reduce_max_sync(0xFFFFFFFFu, hi ? (int)0x80000000 : mi), mx = __reduce_max_sync(0xFFFFFFFFu, hi ? mi : (int)0x80000000);
                    SF();
                    WOLD(PF2, PF3);
                    SF();
                    mi = hi ? mx : mm;
                    mi ^= (mi >> 31) & 0x7FFFFFFF;
                    const float c2_ = 0.08838834764831845f * 1.4426950408889634f;
                    const float mc = __int_as_float(mi) * c2_;
                    const float e0 = ex2(fmaf(s0, c2_, -mc)), e1 = ex2(fmaf(s1, c2_, -mc)), e2 = ex2(fmaf(s2, c2_, -mc));
                    sts32(sbp + SM_P + (KC >> 25), pack2(e0, e1));
                    sts16(sbp + SM_P + 128 + ((KC >> 16) & 0xFF), pack2(e2, e2));
                    es = __float_as_uint(fmaf(e2, 0.5f, e0 + e1) + 64.f);
                }
                const uint32_t sm = __reduce_add_sync(0xFFFFFFFFu, hi ? 0u : es), sx = __reduce_add_sync(0xFFFFFFFFu, hi ? es : 0u);
                const uint32_t aPr = sb + SM_P + (KD >> 16);
                PT(5);
                bsync<5, 384>();
                uint32_t pm[4], px[4], p4[2];
                ldsm4(pm, aPr);
                MF();
                const uint2 vs = lds64(sb + SM_VS + t8);
                MF();
                ldsm2(p4, aPr + 128);
                MF();
                ldsm4(px, aPr + 64);
                MF();
                sts32f(sb + SM_DN + w * 8 + ((t16 >> 3) & 4), rcp(__uint_as_float((hi ? sx : sm) - 15u * 0x42800000u) - 64.f));
                MF();
                WOLD(PF3, NPF);
                const uint32_t vm0 = hadd2(ov0, vs.x), vm1 = hadd2(ov1, vs.y);
                float oa[4], ob[4];
                mma16z(oa, v0.x, v0.y, v1.x, v1.y, pm[0], pm[1]);
                mma16z(ob, v2.x, v2.y, v3.x, v3.y, pm[2], pm[3]);
                mma8(oa, vm0, vm1, p4[0]);
                stsm2(sbw + SM_OT + (t16 & 511), pack2(oa[0] + ob[0], oa[1] + ob[1]), pack2(oa[2] + ob[2], oa[3] + ob[3]));
                PT(6);
                SF();
                bsync<6, 256>();
                mma16z(ox, v0.x, v0.y, v1.x, v1.y, px[0], px[1]);
                uint32_t b[4][4];
#define OTLD(pp) ldsm4t(b[pp], sbm + SM_OT + t16 + (pp) * 512)
                OTLD(0);
                MF();
                OTLD(1);
                barv<7, 384>();
                mma16(ox, v2.x, v2.y, v3.x, v3.y, px[2], px[3]);
                mma8(ox, vm0, vm1, p4[1]);
                if (p == 1 && s + 1 == nseg) goto done;
                SF();
                uint32_t ar, ae, ahi = xhi;
                float r[2][4];
#pragma unroll
                for (int ks = 0; ks < 8; ks++) {
                    if (ks == 0) WOLD(NPF, NPF + WPF);
                    if (ks == OPOS) { OTLD(2); MF(); }
                    if (ks == OPOS + 2) { OTLD(3); MF(); }
                    if (ks > 0) WOLD(NPF + WPF + 2 * (ks - 1), NPF + WPF + 2 * ks);
                    if (ks == 5) {
                        OPQ(t16);
                        ar = rb + h1 * 16 + t16; ae = rb + h1 + (t16 >> 2);
                        OPQ(ar); OPQ(ahi); OPQ(ae);
                        dn = lds128f(sb + SM_DN + (t16 & 48));
                    }
#pragma unroll
                    for (int mt = 0; mt < 2; mt++) {
                        const int i = ks * 2 + mt;
                        const uint32_t* a = wo[i];
                        if (i < 2) mma16z(r[mt], a[0], a[1], a[2], a[3], b[ks >> 1][2 * (ks & 1)], b[ks >> 1][2 * (ks & 1) + 1]);
                        else mma16(r[mt], a[0], a[1], a[2], a[3], b[ks >> 1][2 * (ks & 1)], b[ks >> 1][2 * (ks & 1) + 1]);
                    }
                    if (NPF + WPF + 2 * ks < 16 || ks < 5) SF();
                }
                const float r0 = dn.x, r1 = dn.z;
                asm volatile("{\n.reg .b64 a;\nmov.b64 a, {%0,%2};\nred.relaxed.gpu.global.add.noftz.v4.bf16x2 [a], {%3,%4,%5,%6};\n"
                             "mov.b64 a, {%1,%2};\nred.relaxed.gpu.global.add.noftz.bf16x2 [a+32768], %7;\n}"
                             ::"r"(ar), "r"(ae), "r"(ahi), "r"(pack2(r[0][0] * r0, r[0][1] * r1)), "r"(pack2(r[0][2] * r0, r[0][3] * r1)),
                               "r"(pack2(r[1][0] * r0, r[1][1] * r1)), "r"(pack2(r[1][2] * r0, 1.f)), "r"(pack2(r[1][3] * r1, 1.f)) : "memory");
                barv<10, 384>();
            }
            SF();
            PT(10);
            OXSTORE(s);
            OPQALL();
        }
    done:
        dn = lds128f(sb + SM_DN + (t16 & 48));
        OXSTORE(nseg - 1);
        barv<9, 384>();
        g_main(sb, w, role, &tmy);
        if (threadIdx.x == 0) PG(0);
    }
}

template <int SC> DEVI void wg_rs128t(float (&d)[64], const uint32_t (&a)[4], uint64_t db) {
    if (SC) asm volatile("wgmma.mma_async.sync.aligned.m64n128k16.f32.bf16.bf16 "
        "{%0,%1,%2,%3,%4,%5,%6,%7,%8,%9,%10,%11,%12,%13,%14,%15,%16,%17,%18,%19,%20,%21,%22,%23,%24,%25,%26,%27,%28,%29,%30,%31,%32,%33,%34,%35,%36,%37,%38,%39,%40,%41,%42,%43,%44,%45,%46,%47,%48,%49,%50,%51,%52,%53,%54,%55,%56,%57,%58,%59,%60,%61,%62,%63}, "
        "{%64,%65,%66,%67}, %68, 1, 1, 1, 1;"
        : D4(+, 0), D4(+, 4), D4(+, 8), D4(+, 12), D4(+, 16), D4(+, 20), D4(+, 24), D4(+, 28), D4(+, 32), D4(+, 36), D4(+, 40), D4(+, 44), D4(+, 48), D4(+, 52), D4(+, 56), D4(+, 60) : "r"(a[0]), "r"(a[1]), "r"(a[2]), "r"(a[3]), "l"(db));
    else asm volatile("wgmma.mma_async.sync.aligned.m64n128k16.f32.bf16.bf16 "
        "{%0,%1,%2,%3,%4,%5,%6,%7,%8,%9,%10,%11,%12,%13,%14,%15,%16,%17,%18,%19,%20,%21,%22,%23,%24,%25,%26,%27,%28,%29,%30,%31,%32,%33,%34,%35,%36,%37,%38,%39,%40,%41,%42,%43,%44,%45,%46,%47,%48,%49,%50,%51,%52,%53,%54,%55,%56,%57,%58,%59,%60,%61,%62,%63}, "
        "{%64,%65,%66,%67}, %68, 0, 1, 1, 1;"
        : D4(=, 0), D4(=, 4), D4(=, 8), D4(=, 12), D4(=, 16), D4(=, 20), D4(=, 24), D4(=, 28), D4(=, 32), D4(=, 36), D4(=, 40), D4(=, 44), D4(=, 48), D4(=, 52), D4(=, 56), D4(=, 60) : "r"(a[0]), "r"(a[1]), "r"(a[2]), "r"(a[3]), "l"(db));
}
template <int SC> DEVI void wg_rs64t(float (&d)[32], const uint32_t (&a)[4], uint64_t db) {
    if (SC) asm volatile("wgmma.mma_async.sync.aligned.m64n64k16.f32.bf16.bf16 "
        "{%0,%1,%2,%3,%4,%5,%6,%7,%8,%9,%10,%11,%12,%13,%14,%15,%16,%17,%18,%19,%20,%21,%22,%23,%24,%25,%26,%27,%28,%29,%30,%31}, "
        "{%32,%33,%34,%35}, %36, 1, 1, 1, 1;"
        : D4(+, 0), D4(+, 4), D4(+, 8), D4(+, 12), D4(+, 16), D4(+, 20), D4(+, 24), D4(+, 28) : "r"(a[0]), "r"(a[1]), "r"(a[2]), "r"(a[3]), "l"(db));
    else asm volatile("wgmma.mma_async.sync.aligned.m64n64k16.f32.bf16.bf16 "
        "{%0,%1,%2,%3,%4,%5,%6,%7,%8,%9,%10,%11,%12,%13,%14,%15,%16,%17,%18,%19,%20,%21,%22,%23,%24,%25,%26,%27,%28,%29,%30,%31}, "
        "{%32,%33,%34,%35}, %36, 0, 1, 1, 1;"
        : D4(=, 0), D4(=, 4), D4(=, 8), D4(=, 12), D4(=, 16), D4(=, 20), D4(=, 24), D4(=, 28) : "r"(a[0]), "r"(a[1]), "r"(a[2]), "r"(a[3]), "l"(db));
}
template <int SC> DEVI void wg_rs40(float (&d)[20], const uint32_t (&a)[4], uint64_t db) {
    if (SC) asm volatile("wgmma.mma_async.sync.aligned.m64n40k16.f32.bf16.bf16 "
        "{%0,%1,%2,%3,%4,%5,%6,%7,%8,%9,%10,%11,%12,%13,%14,%15,%16,%17,%18,%19}, "
        "{%20,%21,%22,%23}, %24, 1, 1, 1, 0;"
        : D4(+, 0), D4(+, 4), D4(+, 8), D4(+, 12), D4(+, 16) : "r"(a[0]), "r"(a[1]), "r"(a[2]), "r"(a[3]), "l"(db));
    else asm volatile("wgmma.mma_async.sync.aligned.m64n40k16.f32.bf16.bf16 "
        "{%0,%1,%2,%3,%4,%5,%6,%7,%8,%9,%10,%11,%12,%13,%14,%15,%16,%17,%18,%19}, "
        "{%20,%21,%22,%23}, %24, 0, 1, 1, 0;"
        : D4(=, 0), D4(=, 4), D4(=, 8), D4(=, 12), D4(=, 16) : "r"(a[0]), "r"(a[1]), "r"(a[2]), "r"(a[3]), "l"(db));
}
template <int SC> DEVI void wg_rs8(float (&d)[4], const uint32_t (&a)[4], uint64_t db) {
    if (SC) asm volatile("wgmma.mma_async.sync.aligned.m64n8k16.f32.bf16.bf16 "
        "{%0,%1,%2,%3}, "
        "{%4,%5,%6,%7}, %8, 1, 1, 1, 0;"
        : D4(+, 0) : "r"(a[0]), "r"(a[1]), "r"(a[2]), "r"(a[3]), "l"(db));
    else asm volatile("wgmma.mma_async.sync.aligned.m64n8k16.f32.bf16.bf16 "
        "{%0,%1,%2,%3}, "
        "{%4,%5,%6,%7}, %8, 0, 1, 1, 0;"
        : D4(=, 0) : "r"(a[0]), "r"(a[1]), "r"(a[2]), "r"(a[3]), "l"(db));
}
template <int SC> DEVI void wg_ss64a(float (&d)[32], uint64_t da, uint64_t db) {
    if (SC) asm volatile("wgmma.mma_async.sync.aligned.m64n64k16.f32.bf16.bf16 "
        "{%0,%1,%2,%3,%4,%5,%6,%7,%8,%9,%10,%11,%12,%13,%14,%15,%16,%17,%18,%19,%20,%21,%22,%23,%24,%25,%26,%27,%28,%29,%30,%31}, "
        "%32, %33, 1, 1, 1, 1, 0;"
        : D4(+, 0), D4(+, 4), D4(+, 8), D4(+, 12), D4(+, 16), D4(+, 20), D4(+, 24), D4(+, 28) : "l"(da), "l"(db));
    else asm volatile("wgmma.mma_async.sync.aligned.m64n64k16.f32.bf16.bf16 "
        "{%0,%1,%2,%3,%4,%5,%6,%7,%8,%9,%10,%11,%12,%13,%14,%15,%16,%17,%18,%19,%20,%21,%22,%23,%24,%25,%26,%27,%28,%29,%30,%31}, "
        "%32, %33, 0, 1, 1, 1, 0;"
        : D4(=, 0), D4(=, 4), D4(=, 8), D4(=, 12), D4(=, 16), D4(=, 20), D4(=, 24), D4(=, 28) : "l"(da), "l"(db));
}

#define G_ROWS 514
__device__ uint4 g_G[64 * G_ROWS * 8];
__device__ uint4 g_GN[64 * 8];
__device__ uint4 g_WN[1152];
#define FS_F2 196608
#define FS_TB (FS_F2 + 8192)
#define FS_NQ (FS_TB + 16384)
#define FS_BAR (FS_NQ + 128)
#define FS_NY (FS_NQ + 1024 + 128)
#define FS_TOTAL (FS_NQ + 3072)
#define F_THREADS 512

DEVI uint32_t cis(int j) {
    const float a = fmaf(__uint_as_float((((j + 1024) << 12) & 0x7FF000) | 0x3F800000), 6.283185307179586f, -9.42477796076938f);
    return pack2(__cosf(a), __sinf(a));
}
DEVI uint32_t cos2(int j0, int j1) {
    const float f = 6.283185307179586f / 2048.f;
    return pack2(__cosf((float)(((j0 + 1024) & 2047) - 1024) * f), __cosf((float)(((j1 + 1024) & 2047) - 1024) * f));
}
DEVI void twid(int j, float& c, float& s) {
    const float a = (float)(((j + 512) & 1023) - 512) * (6.283185307179586f / 1024.f);
    c = __cosf(a) * (1.f / 1024.f);
    s = __sinf(a) * (1.f / 1024.f);
}
template <bool B> struct Bool { static constexpr bool v = B; };
DEVI uint32_t opq(uint32_t& x, uint32_t zero) { OPQ(x); return x; }
DEVI uint32_t tidx() { uint32_t r; asm volatile("mov.u32 %0, %%tid.x;" : "=r"(r)); return r; }
DEVI void tma4d(uint32_t dst, const CUtensorMap* tm, uint32_t bar, int c0, int c1, int c2, int c3) {
    asm volatile("cp.async.bulk.tensor.4d.shared::cluster.global.mbarrier::complete_tx::bytes [%0], [%1, {%3, %4, %5, %6}], [%2];"
                 ::"r"(dst), "l"(tm), "r"(bar), "r"(c0), "r"(c1), "r"(c2), "r"(c3) : "memory");
}
DEVI void tma3s(const CUtensorMap* tm, uint32_t src, int c0, int c1, int c2) {
    asm volatile("cp.async.bulk.tensor.3d.global.shared::cta.bulk_group [%0, {%2, %3, %4}], [%1];" ::"l"(tm), "r"(src), "r"(c0), "r"(c1), "r"(c2) : "memory");
}
DEVI void tma4s(const CUtensorMap* tm, uint32_t src, int c0, int c1, int c2, int c3) {
    asm volatile("cp.async.bulk.tensor.4d.global.shared::cta.bulk_group [%0, {%2, %3, %4, %5}], [%1];"
                 ::"l"(tm), "r"(src), "r"(c0), "r"(c1), "r"(c2), "r"(c3) : "memory");
}
DEVI void bulk_commit() { asm volatile("cp.async.bulk.commit_group;" ::: "memory"); }
DEVI void fence_async() { asm volatile("fence.proxy.async;" ::: "memory"); }
DEVI void fence_smem() { asm volatile("fence.proxy.async.shared::cta;" ::: "memory"); }
DEVI void wgbar(uint32_t q) { asm volatile("bar.sync %0, 128;" ::"r"(q + 2) : "memory"); }
DEVI void grid_arrive(uint32_t* c, uint32_t n) { asm volatile("fence.proxy.async;\nred.release.gpu.global.inc.u32 [%0], %1;" ::"l"(c), "r"(n - 1) : "memory"); }
DEVI void grid_wait(uint32_t* c) {
    uint32_t v;
    int it = 0;
    do {
        asm volatile("ld.acquire.gpu.global.u32 %0, [%1];" : "=r"(v) : "l"(c) : "memory");
        if (++it > (1 << 22)) die(it);
    } while (v);
    fence_async();
}

template <bool INV, class S1, class S2>
DEVI void fft_rows(uint32_t grp, uint32_t q, const uint32_t (&F)[2][4], const float (&tc)[8], const float (&ts)[8], uint32_t so, float fx, uint32_t nq,
                   S1 sh1, S2 sh2) {
    float d[64];
    const uint64_t db = INV ? mkdesc(grp, 1024, 2048) : (mkdesc(grp, 2048, 512) ^ ((uint64_t)3 << 62));
    wg_fence();
    wg_rs128t<0>(d, F[0], db);
    wg_rs128t<1>(d, F[1], db + (INV ? 256 : 64));
    wg_commit();
    SF();
    sh1();
    float4 ny;
    if (INV) ny = lds128f(nq);
    wg_wait<0>();
    if (INV) { d[0] = fmaf(fx, ny.x, d[0]); d[16] = fmaf(fx, ny.y, d[16]); d[32] = fmaf(fx, ny.z, d[32]); d[48] = fmaf(fx, ny.w, d[48]); }
    uint32_t a[2][4][4];
    float e[2][INV ? 16 : 20];
    const uint64_t df = mkdesc(SB0 + FS_F2, 16, 1024);
#pragma unroll
    for (int s = 0; s < 2; s++) {
#pragma unroll
        for (int i = 0; i < 4; i++)
#pragma unroll
            for (int h = 0; h < 2; h++) {
                const float* x = d + (2 * s + h) * 16 + i * 4;
                a[s][i][h] = pack2(fmaf(x[2], ts[2 * i], x[0] * tc[2 * i]), fmaf(x[3], ts[2 * i + 1], x[1] * tc[2 * i + 1]));
                a[s][i][h + 2] = pack2(fmaf(-x[0], ts[2 * i], x[2] * tc[2 * i]), fmaf(-x[1], ts[2 * i + 1], x[3] * tc[2 * i + 1]));
            }
        wg_fence();
#pragma unroll
        for (int i = 0; i < 4; i++) {
            if constexpr (INV) { if (i == 0) wg_rs32<0>(e[s], a[s][i], df); else wg_rs32<1>(e[s], a[s][i], df + i * 2); }
            else { if (i == 0) wg_rs40<0>(e[s], a[s][i], df); else wg_rs40<1>(e[s], a[s][i], df + i * 2); }
        }
        wg_commit();
    }
    SF();
    sh2();
#pragma unroll
    for (int s = 0; s < 2; s++) {
        if (s == 0) wg_wait<1>(); else wg_wait<0>();
        float* x = e[s];
        if constexpr (!INV) {
            x[0] *= fx; x[1] *= fx; x[2] *= fx; x[3] *= fx;
            if (fx != 1.f) sts64(nq + s * 8, pack2(x[16], 0.f), pack2(x[18], 0.f));
        }
        const uint32_t o = grp + (INV ? so + s * 4096 : so ^ (s * 576));
#pragma unroll
        for (int b = 0; b < 2; b++)
            stsm4t(o + b * (INV ? 1024 : 4096), pack2(x[8 * b], x[8 * b + 1]), pack2(x[8 * b + 2], x[8 * b + 3]), pack2(x[8 * b + 4], x[8 * b + 5]),
                   pack2(x[8 * b + 6], x[8 * b + 7]));
    }
}

template <bool INV>
DEVI void fft_gen(uint32_t a, uint32_t n2) {
    const uint32_t tid = tidx(), x = ((tid >> 4) & 24) + (tid & 3), o = (tid & 4) * 128;
    if (INV) {
        const uint32_t r = (tid & 64) * 16 + (tid & 16) * 32 + (tid & 40) * 8 + n2;
        sts128(a + tid * 16, cis(o - r * x), cis(o - (r + 128) * x), cis(o - r * (x + 4)), cis(o - (r + 128) * (x + 4)));
    } else {
        const uint32_t r = 64 * x + n2, k = ((tid >> 2) & 24) + ((tid >> 3) & 3);
        sts128(a + tid * 16, cis(r * k + o), cis(r * (k + 4) + o), cis((r + 256) * k + o), cis((r + 256) * (k + 4) + o));
    }
}
template <bool INV, class S1>
DEVI void fft_cross(uint32_t buf, uint32_t q, uint32_t fa, uint32_t so, uint32_t nq, float (&n)[4], S1 sh1) {
    uint32_t F[4][4];
#pragma unroll
    for (int s = 0; s < 4; s++) { const uint4 v = lds128(fa + s * 2048); F[s][0] = v.x; F[s][1] = v.y; F[s][2] = v.z; F[s][3] = v.w; }
    float d[64];
    const uint64_t db = mkdesc(buf + q * 2048, 1024, 8192), dn = mkdesc(nq, 16, 1024);
    wg_fence();
#pragma unroll
    for (int s = 0; s < 4; s++) { if (s == 0) wg_rs128t<0>(d, F[s], db); else wg_rs128t<1>(d, F[s], db + s * 1024); }
#pragma unroll
    for (int s = 0; s < 4; s++) { if (s == 0) wg_rs8<0>(n, F[s], dn); else wg_rs8<1>(n, F[s], dn + s * 2); }
    wg_commit();
    SF();
    sh1();
    wg_wait<0>();
#pragma unroll
    for (int b = 0; b < 8; b++) {
        const uint32_t o = INV ? so ^ ((b >> 1) * 288 ^ (b & 1) * 32) : (so ^ ((b & 3) * 32)) + (b >> 2) * 1024;
        stsm4(buf + o, pack2(d[8 * b], d[8 * b + 1]), pack2(d[8 * b + 2], d[8 * b + 3]), pack2(d[8 * b + 4], d[8 * b + 5]), pack2(d[8 * b + 6], d[8 * b + 7]));
    }
}

template <bool ODD>
DEVI void fft_filter(uint32_t aw, const float (&e)[32], const float (&o)[32], uint32_t (&u)[4][4], uint32_t (&v)[4][4]) {
#pragma unroll
    for (int s = 0; s < 4; s++) {
        float y[2][2][4];
#pragma unroll
        for (int c = 0; c < 2; c++) {
            float f[4][2];
#pragma unroll
            for (int i = 0; i < 4; i++) {
                const uint32_t a = aw + (i * 32 + s * 8 + c) * 144, x = lds32(a);
                f[i][0] = ODD ? hi_f(x) : lo_f(x);
                f[i][1] = ODD ? lo_f(lds32(a + 4)) : hi_f(x);
            }
#pragma unroll
            for (int h = 0; h < 2; h++) {
                const int x = 8 * s + 2 * h + c;
                const float ar = e[x] + o[x], ai = e[x + 4] + o[x + 4], br = e[x] - o[x], bi = e[x + 4] - o[x + 4];
                const float yr = fmaf(-ai, f[2][h], ar * f[0][h]), yi = fmaf(ar, f[2][h], ai * f[0][h]);
                y[h][c][0] = fmaf(-bi, f[3][h], fmaf(br, f[1][h], yr));
                y[h][c][1] = fmaf(br, f[3][h], fmaf(bi, f[1][h], yi));
                y[h][c][2] = fmaf(2.f, yr, -y[h][c][0]);
                y[h][c][3] = fmaf(2.f, yi, -y[h][c][1]);
            }
        }
#pragma unroll
        for (int h = 0; h < 2; h++) {
            u[s][h] = pack2(y[h][0][0], y[h][1][0]); u[s][h + 2] = pack2(y[h][0][1], y[h][1][1]);
            v[s][h] = pack2(y[h][0][2], y[h][1][2]); v[s][h + 2] = pack2(y[h][0][3], y[h][1][3]);
        }
    }
}

__global__ void __launch_bounds__(F_THREADS, 1)
post_kernel(const __grid_constant__ CUtensorMap tmx, const __grid_constant__ CUtensorMap tmg1, const __grid_constant__ CUtensorMap tmg2,
           const __grid_constant__ CUtensorMap tmwr, const __grid_constant__ CUtensorMap tmwi, const __grid_constant__ CUtensorMap tmy,
           const bf16* __restrict__ wr, const bf16* __restrict__ wi, uint32_t* cnt, uint32_t zero, int nw) {
    extern __shared__ __align__(1024) uint8_t smem[];
    const uint32_t sb = SB0;
    if (smem_u32(smem) != sb) die(1 << 23);
    const uint32_t tid = threadIdx.x, lane = tid & 31, g = lane >> 2, t = lane & 3, j8 = lane & 7, mat = lane >> 3;
    const uint32_t wi_ = __reduce_max_sync(0xFFFFFFFFu, tid >> 5), q = wi_ >> 2, w = wi_ & 3;
    const int cta = blockIdx.x;
    const int nt = cta < 64 ? (64 - cta + nw - 1) / nw : 0;
    const uint32_t bar = sb + FS_BAR;
    if (tid == 0) {
        for (int i = 0; i < 30; i++) mbar_init(bar + i * 8, i < 3 ? 4 : i < 6 ? 16 : i >= 14 && i < 18 ? 2 : 1);
        asm volatile("fence.mbarrier_init.release.cluster;" ::: "memory");
        fence_smem();
    }
    __syncthreads();
#define FT(n)
    FT(0);
#define N2(p) (2 * ((p) & 31) + ((p) >> 5))
#define WLOAD(tk, part) { \
        const uint32_t wd_ = sb + 131072 + q * 18432 + (part) * 9216, wb_ = bar + 112 + q * 8; \
        mbar_expect(wb_, 9216); \
        if ((tk) < 256) tma3d(wd_, (part) ? &tmwi : &tmwr, wb_, ((tk) & 63) * 64, (tk) >> 6, 0); \
        else asm volatile("cp.async.bulk.shared::cluster.global.mbarrier::complete_tx::bytes [%0], [%1], 9216, [%2];" \
                          ::"r"(wd_), "l"(g_WN + (part) * 576), "r"(wb_) : "memory"); }
#define GROW(tk) ((tk) < 256 ? ((tk) >> 5) * 64 + ((tk) & 7) * 8 + (((tk) >> 3) & 3) * 2 : 512)
#define DLOAD(tk, sl) { mbar_expect(bar + 48 + (sl) * 8, 16384); tma3d(sb + (sl) * 16384, &tmg2, bar + 48 + (sl) * 8, 0, GROW(tk), 0); }
#define IO(c) if (w == 3 && (c) && elect())
#define XLOAD1(i, bb) { const uint32_t xb_ = bar + 144 + (bb) * 32 + q * 8; mbar_expect(xb_, 16384); tma4d(sb + (bb) * 65536 + q * 16384, &tmx, xb_, 0, 0, q * 8, N2(cta + (i) * nw)); }
#define GLOAD3(i, bb) { mbar_expect(bar + (bb) * 8, q ? 16384 : 16512); tma3d(sb + (bb) * 65536 + q * 16384, &tmg1, bar + (bb) * 8, 0, q * 128, cta + (i) * nw); \
        if (q == 0) asm volatile("cp.async.bulk.shared::cluster.global.mbarrier::complete_tx::bytes [%0], [%1], 128, [%2];" \
                                 ::"r"(sb + FS_NQ + (bb) * 1024), "l"(g_GN + (cta + (i) * nw) * 8), "r"(bar + (bb) * 8) : "memory"); }
    for (int i = 0; i < 3; i++) IO(i < nt) XLOAD1(i, i);
    for (uint32_t x = tid; x < 40 * 32; x += 512) {
        const uint32_t n = x >> 5, m2 = mat * 8 + t * 2, ri = g & 1;
        const uint32_t c2 = ((n >> 1) & 1) + ((n >> 3) & 1) * 2 + (n & 4) + (n >> 4) * 8;
        const uint32_t v = cos2(m2 * c2 * 64 + ((n & 1) - ri) * 512, (m2 + 1) * c2 * 64 + ((n & 1) - ri) * 512);
        sts32(sb + FS_F2 + n * 128 + ((g ^ (n & 7)) << 4) + t * 4, n < 32 ? v : n == 32 && ri == 0 ? 0xBF003F00u : 0u);
    }
    float tc[8], ts[8];
    uint32_t F[2][4];
    uint32_t c1 = 16 * (w >> 1) + 2 * g + (w & 1);
#pragma unroll
    for (int i = 0; i < 8; i++) {
        twid(c1 * (8 * (i >> 1) + 2 * t + (i & 1)), tc[i], ts[i]);
        const uint32_t m1 = (i >> 1) * 8 + 2 * t;
        F[i >> 2][i & 3] = cos2(c1 * m1 * 64 + (i & 1) * 512, c1 * (m1 + 1) * 64 + (i & 1) * 512);
    }
    {
        const uint32_t kr = (2 * (mat & 1) + (j8 & 1)) ^ ((j8 >> 2) << 1);
        const uint32_t so1 = ((mat >> 1) + 2 * (j8 >> 2)) * 1024 + kr * 128 + (((((j8 >> 1) & 1) * 4 + w) ^ kr) << 4);
        const uint32_t so2 = (2 * w + (mat & 1)) * 8192 + q * 2048 + j8 * 128 + (((mat >> 1) ^ j8) << 4);
        uint32_t so = so1 << 16 | so2;
        const float fx = (tid & 127) == 0 ? 0.5f : 1.f;
        fft_gen<false>(sb + FS_TB, N2(cta));
        fence_smem();
        bsync<1, 512>();
        FT(1);
        int b = 0, bp = 2, ph = 0;
        if (nt) mwait(bar + 144 + q * 8, 0);
        __syncwarp();
        auto step = [&](auto first, auto last, const int i) {
            const uint32_t p = cta + i * nw, bn = 3 - b - bp, tb = (i & 1) * 8192;
            const uint32_t grp = sb + b * 65536 + q * 16384, nq = sb + FS_NQ + b * 1024 + q * 32;
            auto sa = [&]() {
                if constexpr (!decltype(first)::v) {
                    fence_smem();
                    __syncwarp();
                    if (elect()) mbar_arrive(bar + 24);
                }
                IO(i > 1) {
                    mwait(bar + 32, i & 1);
                    tma3s(&tmg1, sb + bn * 65536 + q * 16384, 0, q * 128, p - 2 * nw);
                    bulk_commit();
                }
            };
            auto sb_ = [&]() { if constexpr (!decltype(first)::v) mwait(bar + 24, (i - 1) & 1); };
            if constexpr (!decltype(last)::v) fft_rows<false>(grp, q, F, tc, ts, opq(so, zero) >> 16, fx, nq, sa, sb_);
            else { sa(); __syncwarp(); sb_(); __syncwarp(); }
            if constexpr (!decltype(first)::v) {
                float n[4];
                fft_cross<false>(sb + bp * 65536, q, sb + FS_TB + 8192 - tb + (((tidx() & 127) ^ (q & 1)) << 4), opq(so, zero) & 0xFFFF, sb + FS_NQ + bp * 1024, n, [&]() {
                    fft_gen<false>(sb + FS_TB + tb, N2(p));
                    IO(i >= 2 && i + 1 < nt) {
                        asm volatile("cp.async.bulk.wait_group.read 0;" ::: "memory");
                        XLOAD1(i + 1, bn);
                    }
                });
                if (q == 0) {
                    const uint32_t x = tidx();
                    bf16* z = (bf16*)(g_G + ((p - nw) * G_ROWS + 512) * 8) + (x & 4) * 16 + ((x >> 2) & 24) + ((x >> 3) & 3);
                    asm volatile("{\n.reg .pred p;\n.reg .b16 a, b;\nsetp.eq.u32 p, %2, 0;\nmov.b32 {a, b}, %1;\n@p st.global.u16 [%0], a;\n@p st.global.u16 [%0+8], b;\n}"
                                 ::"l"(z), "r"(pack2(n[0], n[2])), "r"(x & 3) : "memory");
                }
            }
            if constexpr (!decltype(last)::v) {
                fft_rows<false>(grp + 8192, q, F, tc, ts, opq(so, zero) >> 16, fx, nq + 16, [&]() {
                    if constexpr (!decltype(first)::v) {
                        fence_smem();
                        __syncwarp();
                        if (elect()) mbar_arrive(bar + 32);
                    }
                    if ((w == 1 || w == 2) && elect())
                        asm volatile("cp.async.bulk.prefetch.L2.global [%0], 8208;" ::"l"((w == 1 ? wr : wi) + (p * 4 + q) * 4104) : "memory");
                }, [&]() { if (i + 1 < nt) mwait(bar + 144 + bn * 32 + q * 8, bn ? ph : ph ^ 1); });
                bp = b;
                if (++b == 3) { b = 0; ph ^= 1; }
            }
        };
        if (nt) {
            step(Bool<true>(), Bool<false>(), 0);
#pragma unroll 1
            for (int i = 1; i < nt; i++) step(Bool<false>(), Bool<false>(), i);
            step(Bool<false>(), Bool<true>(), nt);
        }
        for (uint32_t x = cta * 512 + tid; x < 4096; x += nw * 512)
            ((bf16*)g_WN)[(x >> 5) * 72 + (x & 16) + (x & 7) * 2 + ((x >> 3) & 1)] = (x < 2048 ? wr : wi)[(x & 2047) * 513 + 512];
        FT(2);
        fence_async();
        bsync<1, 512>();
        IO(nt) { tma3s(&tmg1, sb + bp * 65536 + q * 16384, 0, q * 128, cta + (nt - 1) * nw); bulk_commit(); }
    }
    for (uint32_t x = tid; x < 128 * 32; x += 512) {
        const uint32_t n = (x >> 5) & 63, a = x & 31, k2 = (n >> 4) * 8 + (n & 7);
        sts32(sb + FS_TB + (x >> 5) * 128 + (((a >> 2) ^ (n & 7)) << 4) + (a & 3) * 4, cis((2 * a + (x >> 11)) * k2 * 32 + (n & 8) * 64));
    }
    fence_smem();
    bsync<1, 512>();
    IO(true) {
        asm volatile("cp.async.bulk.wait_group 0;" ::: "memory");
        grid_arrive(cnt, 4 * nw);
        grid_wait(cnt);
        const int tk = cta + q * nw;
        if (tk <= 256) { DLOAD(tk, q); WLOAD(tk, 0); WLOAD(tk, 1); }
    }
    __syncwarp();
    {
        const uint32_t lo = j8 * 128 + (((2 * w + (mat & 1)) ^ j8) << 4);
        const uint32_t aw = sb + 131072 + q * 18432 + t * 288 + w * 32 + g * 4;
        const uint64_t df = mkdesc(sb + FS_TB, 16, 1024);
        const uint64_t da = mkdesc(sb + q * 16384, 16, 1024);
        const uint32_t buf = sb + 65536 + q * 16384;
        int i = 0, tk = cta + q * nw;
        if (tk <= 256) mwait(bar + 48 + q * 8, 0);
        FT(3);
#pragma unroll 1
        for (; tk <= 256; tk += 4 * nw, i++) {
            const bool more = tk + 4 * nw <= 256;
            float e[32], o[32];
            wg_fence();
#pragma unroll
            for (int s = 0; s < 4; s++) { if (s == 0) wg_ss64a<0>(e, da, df); else wg_ss64a<1>(e, da + s * 128, df + s * 2); }
#pragma unroll
            for (int s = 0; s < 4; s++) { if (s == 0) wg_ss64a<0>(o, da + 512, df + 512); else wg_ss64a<1>(o, da + 512 + s * 128, df + 512 + s * 2); }
            wg_commit();
            SF();
            if (i > 0) {
                fence_smem();
                wgbar(q);
                IO(true) { tma3s(&tmg2, buf, 0, GROW(tk - 4 * nw), 0); bulk_commit(); }
            }
            if (w == 2 && more && elect()) mbar_expect(bar + 48 + q * 8, 16384);
            const int gr = GROW(tk + 4 * nw);
            mwait(bar + 112 + q * 8, i & 1);
            wg_wait<0>();
            if (w == 2 && more && elect()) tma3d(sb + q * 16384, &tmg2, bar + 48 + q * 8, 0, gr, 0);
            uint32_t u[4][4], v[4][4];
            if (tk & 8) fft_filter<true>(aw + (tk & 48) / 4, e, o, u, v);
            else fft_filter<false>(aw + (tk & 48) / 4, e, o, u, v);
            wg_fence();
#pragma unroll
            for (int s = 0; s < 4; s++) { if (s == 0) wg_rs64t<0>(e, u[s], df); else wg_rs64t<1>(e, u[s], df + s * 128); }
#pragma unroll
            for (int s = 0; s < 4; s++) { if (s == 0) wg_rs64t<0>(o, v[s], df + 512); else wg_rs64t<1>(o, v[s], df + 512 + s * 128); }
            wg_commit();
            SF();
            IO(true) asm volatile("cp.async.bulk.wait_group.read 0;" ::: "memory");
            wgbar(q);
            if (more) {
                if ((w == 1 || w == 2) && elect()) WLOAD(tk + 4 * nw, w - 1);
                mwait(bar + 48 + q * 8, (i + 1) & 1);
            }
            wg_wait<0>();
#pragma unroll
            for (int s = 0; s < 4; s++) {
                const uint32_t a = buf + (mat >> 1) * 1024 + lo + s * 2048;
                stsm4t(a, pack2(e[8 * s], e[8 * s + 1]), pack2(e[8 * s + 2], e[8 * s + 3]), pack2(e[8 * s + 4], e[8 * s + 5]), pack2(e[8 * s + 6], e[8 * s + 7]));
                stsm4t(a + 8192, pack2(o[8 * s], o[8 * s + 1]), pack2(o[8 * s + 2], o[8 * s + 3]), pack2(o[8 * s + 4], o[8 * s + 5]), pack2(o[8 * s + 6], o[8 * s + 7]));
            }
            if (tk == 256 && w < 2) {
                uint32_t* z = (uint32_t*)g_GN + t * 32 + w * 16 + g;
#pragma unroll
                for (int s = 0; s < 16; s++) {
                    z[(s >> 1) * 128 + (s & 1) * 8] = pack2(e[2 * s], e[2 * s + 1]);
                    z[(s >> 1) * 128 + (s & 1) * 8 + 1024] = pack2(o[2 * s], o[2 * s + 1]);
                }
                fence_async();
            }
        }
        fence_smem();
        wgbar(q);
        IO(true) {
            if (i > 0) { tma3s(&tmg2, buf, 0, GROW(tk - 4 * nw), 0); bulk_commit(); }
            asm volatile("cp.async.bulk.wait_group 0;" ::: "memory");
            grid_arrive(cnt + 1, 4 * nw);
        }
    }
    FT(4);
    bsync<1, 512>();
    {
        for (uint32_t n = wi_; n < 32; n += 16) {
            const uint32_t cl = (mat >> 1) * 16 + t * 4 + (mat & 1), mh = ((n >> 3) & 1) + (n & 7) * 2 + (n & 16);
            sts32(sb + FS_F2 + n * 128 + ((g ^ (n & 7)) << 4) + t * 4, cos2(cl * mh * 64 + (g & 1) * 512, (cl + 2) * mh * 64 + (g & 1) * 512));
        }
        fence_smem();
        c1 = 8 * w + g;
#pragma unroll
        for (int i = 0; i < 8; i++) {
            twid(-c1 * (16 * (i >> 2) + 4 * t + 2 * (i & 1) + ((i >> 1) & 1)), tc[i], ts[i]);
            F[i >> 2][i & 3] = cis((i & 1) * 512 - c1 * ((i >> 1) * 4 + (t ^ (q & 1))) * 64);
        }
        const uint32_t kr = (j8 & 1) ^ ((j8 >> 2) << 1);
        const uint32_t so2 = ((w >> 1) * 4 + (j8 >> 2) * 2 + (w & 1)) * 8192 + (2 * q + (mat & 1)) * 1024 + kr * 128 + (((((j8 >> 1) & 1) * 4 + (mat >> 1)) ^ kr) << 4);
        const uint32_t so1 = (mat & 1) * 2048 + j8 * 128 + ((((mat >> 1) * 4 + w) ^ j8) << 4);
        uint32_t so = so1 << 16 | so2;
        const float fx = t ? 0.f : (g & 1) ? -1.f : 1.f;
        fft_gen<true>(sb + FS_TB, N2(cta));
        bsync<1, 512>();
        IO(true) grid_wait(cnt + 1);
        for (int i = 0; i < 3; i++) IO(i < nt) GLOAD3(i, i);
        __syncwarp();
        int b = 0, bp = 2, ph = 0;
        auto step = [&](auto first, auto last, const int i) {
            const uint32_t p = cta + i * nw, bn = 3 - b - bp, tb = (i & 1) * 8192;
            const uint32_t grp = sb + bp * 65536 + q * 16384, ny = sb + FS_NY + bp * 128 + q * 32;
            auto sb_ = [&]() { if constexpr (!decltype(last)::v) mwait(bar + b * 8, ph); };
            if constexpr (!decltype(first)::v) {
                fft_rows<true>(grp, q, F, tc, ts, opq(so, zero) >> 16, fx, ny, [&]() {
                    if (i > 1) {
                        fence_smem();
                        wgbar(q);
                        IO(true) { tma4s(&tmy, sb + bn * 65536 + q * 16384, 0, 0, q * 8, N2(p - 2 * nw)); bulk_commit(); }
                    }
                }, sb_);
            } else { sb_(); __syncwarp(); }
            if constexpr (decltype(first)::v) FT(5);
            if constexpr (!decltype(last)::v) {
                float n[4];
                fft_cross<true>(sb + b * 65536, q, sb + FS_TB + tb + (tidx() & 127) * 16, opq(so, zero) & 0xFFFF, sb + FS_NQ + b * 1024, n, [&]() {
                    fft_gen<true>(sb + FS_TB + 8192 - tb, N2(p + nw));
                    IO(i >= 2 && i + 1 < nt) {
                        asm volatile("cp.async.bulk.wait_group.read 0;" ::: "memory");
                        GLOAD3(i + 1, bn);
                    }
                });
                if (q == 0) {
                    const uint32_t x = tidx(), a = sb + FS_NY + b * 128 + (x & 64) + (x & 16) * 2 + ((x & 40) >> 1);
                    if ((x & 7) == 0) { sts32f(a, n[0]); sts32f(a + 8, n[2]); }
                }
            }
            auto sc = [&]() {
                if constexpr (!decltype(last)::v) {
                    fence_smem();
                    __syncwarp();
                    if (elect()) mbar_arrive(bar + 24);
                }
            };
            auto sd = [&]() { if constexpr (!decltype(last)::v) mwait(bar + 24, (nt + i) & 1); };
            if constexpr (!decltype(first)::v) fft_rows<true>(grp + 8192, q, F, tc, ts, opq(so, zero) >> 16, fx, ny + 16, sc, sd);
            else { sc(); __syncwarp(); sd(); __syncwarp(); }
            if constexpr (!decltype(last)::v) {
                bp = b;
                if (++b == 3) { b = 0; ph ^= 1; }
            }
        };
        if (nt) {
            step(Bool<true>(), Bool<false>(), 0);
#pragma unroll 1
            for (int i = 1; i < nt; i++) step(Bool<false>(), Bool<false>(), i);
            step(Bool<false>(), Bool<true>(), nt);
        }
        fence_smem();
        wgbar(q);
        IO(nt) { tma4s(&tmy, sb + bp * 65536 + q * 16384, 0, 0, q * 8, N2(cta + (nt - 1) * nw)); bulk_commit(); }
        FT(6);
        IO(true) asm volatile("cp.async.bulk.wait_group 0;" ::: "memory");
    }
}

typedef CUresult (*EncodeFn)(CUtensorMap*, CUtensorMapDataType, cuuint32_t, void*, const cuuint64_t*, const cuuint64_t*,
                             const cuuint32_t*, const cuuint32_t*, CUtensorMapInterleave, CUtensorMapSwizzle,
                             CUtensorMapL2promotion, CUtensorMapFloatOOBfill);

static void make_map(EncodeFn enc, CUtensorMap* m, const void* ptr, int rank, const cuuint64_t* dims, const cuuint64_t* strides,
                     const cuuint32_t* box, CUtensorMapSwizzle sw = CU_TENSOR_MAP_SWIZZLE_128B) {
    cuuint32_t es[4] = {1, 1, 1, 1};
    CUresult r = enc(m, CU_TENSOR_MAP_DATA_TYPE_BFLOAT16, rank, (void*)ptr, dims, strides, box, es, CU_TENSOR_MAP_INTERLEAVE_NONE,
                     sw, CU_TENSOR_MAP_L2_PROMOTION_L2_256B, CU_TENSOR_MAP_FLOAT_OOB_FILL_NONE);
    if (r != CUDA_SUCCESS) fprintf(stderr, "tensor map encode failed: %d\n", (int)r);
}

extern "C" void kernel_launch(void* const* d_in, const int* in_sizes, int n_in, void* d_out, int out_size) {
    const bf16* A_x = (const bf16*)d_in[0];
    const bf16* A_mem0 = (const bf16*)d_in[1];
    const bf16* A_Wq = (const bf16*)d_in[2];
    const bf16* A_Wk = (const bf16*)d_in[3];
    const bf16* A_Wv = (const bf16*)d_in[4];
    const bf16* A_Wo = (const bf16*)d_in[5];
    const bf16* B_x = (const bf16*)d_in[7];
    const bf16* B_wr = (const bf16*)d_in[8];
    const bf16* B_wi = (const bf16*)d_in[9];
    bf16* out = (bf16*)d_out;

    static EncodeFn enc = nullptr;
    static void *pxs = nullptr, *pg = nullptr;
    static int ncl = 64;
    if (!enc) {
        cudaDriverEntryPointQueryResult qr;
        void* fn = nullptr;
        cudaGetDriverEntryPoint("cuTensorMapEncodeTiled", &fn, cudaEnableDefault, &qr);
        enc = (EncodeFn)fn;
        cudaFuncSetAttribute(chain_kernel, cudaFuncAttributeMaxDynamicSharedMemorySize, SM_TOTAL);
        cudaFuncSetAttribute(post_kernel, cudaFuncAttributeMaxDynamicSharedMemorySize, FS_TOTAL);
        cudaGetSymbolAddress(&pxs, g_xs);
        cudaGetSymbolAddress(&pg, g_G);
        cudaLaunchConfig_t lc = {};
        cudaLaunchAttribute at;
        at.id = cudaLaunchAttributeClusterDimension;
        at.val.clusterDim.x = 2; at.val.clusterDim.y = 1; at.val.clusterDim.z = 1;
        lc.gridDim = dim3(132); lc.blockDim = dim3(384); lc.dynamicSmemBytes = SM_TOTAL; lc.attrs = &at; lc.numAttrs = 1;
        int nc = 0;
        if (cudaOccupancyMaxActiveClusters(&nc, chain_kernel, &lc) == cudaSuccess && nc > 64) ncl = nc < 66 ? nc : 66;
    }
    CUtensorMap tmq, tmk, tmv, tmo, tmx, tmb, tmy;
    {
        cuuint64_t d[3] = {64, DM, HD / 64}, st[2] = {HD * 2, 128};
        cuuint32_t bx[3] = {64, 64, 2};
        make_map(enc, &tmq, A_Wq, 3, d, st, bx);
        make_map(enc, &tmk, A_Wk, 3, d, st, bx);
        make_map(enc, &tmv, A_Wv, 3, d, st, bx);
    }
    {
        cuuint64_t d[2] = {DM, HD}, st[1] = {DM * 2};
        cuuint32_t bx[2] = {64, 16}, bx1[2] = {64, 128}, bx2[3] = {64, 64, 2};
        make_map(enc, &tmo, A_Wo, 2, d, st, bx1);
        cuuint64_t d2[3] = {64, HD, DM / 64}, st2[2] = {DM * 2, 128}, d3[2] = {DM, SEQ}, st3[1] = {DM * 4};
        make_map(enc, &tmb, A_Wo, 3, d2, st2, bx2);
        make_map(enc, &tmy, out, 2, d3, st3, bx);
    }
    {
        cuuint64_t d[3] = {64, SEQ, DM / 64}, st[2] = {DM * 2, 128};
        cuuint32_t bx[3] = {64, 8, 4};
        make_map(enc, &tmx, A_x, 3, d, st, bx);
    }
    CUtensorMap fx, fg1, fg2, fwr, fwi, fy;
    {
        cuuint64_t d[4] = {32, 32, 32, 64}, st[3] = {64, 64 * DM * 2, DM * 2};
        cuuint32_t bx[4] = {32, 32, 8, 1};
        make_map(enc, &fx, B_x, 4, d, st, bx, CU_TENSOR_MAP_SWIZZLE_64B);
        cuuint64_t d2[4] = {64, 16, 32, 64}, st2[3] = {128, 64 * 4096, 4096};
        cuuint32_t bx2[4] = {64, 16, 8, 1};
        make_map(enc, &fy, out + DM, 4, d2, st2, bx2);
    }
    {
        cuuint64_t d[3] = {64, G_ROWS, 64}, st[2] = {128, G_ROWS * 128};
        cuuint32_t bx[3] = {64, 128, 1}, bx2[3] = {64, 2, 64};
        make_map(enc, &fg1, pg, 3, d, st, bx);
        make_map(enc, &fg2, pg, 3, d, st, bx2);
        cuuint64_t d2[3] = {8 * 513, 4, 64}, st2[2] = {8 * 513 * 2, 32 * 513 * 2};
        cuuint32_t bx3[3] = {72, 1, 64};
        make_map(enc, &fwr, B_wr, 3, d2, st2, bx3, CU_TENSOR_MAP_SWIZZLE_NONE);
        make_map(enc, &fwi, B_wi, 3, d2, st2, bx3, CU_TENSOR_MAP_SWIZZLE_NONE);
    }
    cudaStream_t st = cudaStreamPerThread;
    const uint64_t xs = ((uint64_t)pxs + XS_BYTES - 1) & ~(uint64_t)(XS_BYTES - 1);
    chain_kernel<<<2 * ncl, 384, SM_TOTAL, st>>>(tmq, tmk, tmv, tmo, tmx, tmb, tmy, A_mem0, A_x, (uint32_t)xs, (uint32_t)(xs >> 32), 0u, NSEG);
    int nw = ncl == 66 ? 4 : 64;
    cudaLaunchConfig_t lc = {};
    cudaLaunchAttribute at;
    at.id = cudaLaunchAttributeProgrammaticStreamSerialization;
    at.val.programmaticStreamSerializationAllowed = 1;
    lc.gridDim = dim3(nw); lc.blockDim = dim3(F_THREADS); lc.dynamicSmemBytes = FS_TOTAL; lc.stream = st; lc.attrs = &at; lc.numAttrs = 1;
    cudaLaunchKernelEx(&lc, post_kernel, fx, fg1, fg2, fwr, fwi, fy, B_wr, B_wi, (uint32_t*)(xs + XO_TK + 256), 0u, nw);
}
```

```cpp
#include <cuda_runtime.h>
#include <cuda_bf16.h>
#include <cuda.h>
#include <stdint.h>
#include <stdio.h>

typedef __nv_bfloat16 bf16;

#define SEQ 2048
#define DM 1024
#define NH 32
#define DH 128
#define NSEG 64
#define HD (NH * DH)

#define XS_BYTES (32u << 20)
__device__ uint4 g_xs[2 * XS_BYTES / 16];
#define XO_R 0u
#define XO_PB (1u << 18)
#define XO_FL (XO_PB + 32768u)
#define XO_TK (XO_FL + 4096u)
#define XO_CQK (1u << 20)
#define XO_CV (2u << 20)
#define XO_XG (4u << 20)
#define XO_OX (16u << 20)
#define GSYNC(n)
#define PG(n)

#define DEVI __device__ __forceinline__

DEVI void die(int it) { asm volatile("st.shared.u32 [%0], %0;" ::"r"(it) : "memory"); }
DEVI uint32_t smem_u32(const void* p) { return (uint32_t)__cvta_generic_to_shared(p); }
DEVI void mbar_init(uint32_t bar, uint32_t cnt) { asm volatile("mbarrier.init.shared::cta.b64 [%0], %1;" ::"r"(bar), "r"(cnt) : "memory"); }
DEVI void mbar_expect(uint32_t bar, uint32_t bytes) { asm volatile("mbarrier.arrive.expect_tx.shared::cta.b64 _, [%0], %1;" ::"r"(bar), "r"(bytes) : "memory"); }
DEVI void mbar_arrive(uint32_t bar) { asm volatile("mbarrier.arrive.shared::cta.b64 _, [%0];" ::"r"(bar) : "memory"); }
DEVI void mbar_wait(uint32_t bar, uint32_t parity) {
    uint32_t done;
    int it = 0;
    do {
        asm volatile("{\n.reg .pred p;\nmbarrier.try_wait.parity.shared::cta.b64 p, [%1], %2;\nselp.u32 %0, 1, 0, p;\n}\n"
                     : "=r"(done) : "r"(bar), "r"(parity) : "memory");
        if (++it > (1 << 22)) die(it);
    } while (!done);
}
DEVI void tma2d(uint32_t dst, const CUtensorMap* tm, uint32_t bar, int c0, int c1) {
    asm volatile("cp.async.bulk.tensor.2d.shared::cluster.global.mbarrier::complete_tx::bytes [%0], [%1, {%3, %4}], [%2];"
                 ::"r"(dst), "l"(tm), "r"(bar), "r"(c0), "r"(c1) : "memory");
}
DEVI void tma3d(uint32_t dst, const CUtensorMap* tm, uint32_t bar, int c0, int c1, int c2) {
    asm volatile("cp.async.bulk.tensor.3d.shared::cluster.global.mbarrier::complete_tx::bytes [%0], [%1, {%3, %4, %5}], [%2];"
                 ::"r"(dst), "l"(tm), "r"(bar), "r"(c0), "r"(c1), "r"(c2) : "memory");
}
DEVI void bulk_g2s(uint32_t dst, uint32_t lo, uint32_t hi, uint32_t bytes, uint32_t bar) {
    asm volatile("{\n.reg .b64 a;\nmov.b64 a, {%1,%2};\ncp.async.bulk.shared::cluster.global.mbarrier::complete_tx::bytes [%0], [a], %3, [%4];\n}"
                 ::"r"(dst), "r"(lo), "r"(hi), "r"(bytes), "r"(bar) : "memory");
}
DEVI void bulk_s2g(uint32_t lo, uint32_t hi, uint32_t src, uint32_t bytes) {
    asm volatile("{\n.reg .b64 a;\nmov.b64 a, {%0,%1};\ncp.async.bulk.global.shared::cta.bulk_group [a], [%2], %3;\ncp.async.bulk.commit_group;\n}"
                 ::"r"(lo), "r"(hi), "r"(src), "r"(bytes) : "memory");
}
DEVI void bulk_red(uint32_t lo, uint32_t hi, uint32_t src, uint32_t bytes) {
    asm volatile("{\n.reg .b64 a;\nmov.b64 a, {%0,%1};\ncp.reduce.async.bulk.global.shared::cta.bulk_group.add.noftz.bf16 [a], [%2], %3;\ncp.async.bulk.commit_group;\n}"
                 ::"r"(lo), "r"(hi), "r"(src), "r"(bytes) : "memory");
}
DEVI bool elect() {
    uint32_t p;
    asm volatile("{\n.reg .pred P;\nelect.sync _|P, 0xFFFFFFFF;\nselp.u32 %0, 1, 0, P;\n}" : "=r"(p));
    return p != 0;
}
DEVI void ldsm4(uint32_t (&r)[4], uint32_t a) {
    asm volatile("ldmatrix.sync.aligned.m8n8.x4.shared.b16 {%0,%1,%2,%3}, [%4];" : "=r"(r[0]), "=r"(r[1]), "=r"(r[2]), "=r"(r[3]) : "r"(a) : "memory");
}
DEVI void ldsm4t(uint32_t (&r)[4], uint32_t a) {
    asm volatile("ldmatrix.sync.aligned.m8n8.x4.trans.shared.b16 {%0,%1,%2,%3}, [%4];" : "=r"(r[0]), "=r"(r[1]), "=r"(r[2]), "=r"(r[3]) : "r"(a) : "memory");
}
DEVI void ldsm2t(uint32_t (&r)[2], uint32_t a) {
    asm volatile("ldmatrix.sync.aligned.m8n8.x2.trans.shared.b16 {%0,%1}, [%2];" : "=r"(r[0]), "=r"(r[1]) : "r"(a) : "memory");
}
DEVI void ldsm2(uint32_t (&r)[2], uint32_t a) {
    asm volatile("ldmatrix.sync.aligned.m8n8.x2.shared.b16 {%0,%1}, [%2];" : "=r"(r[0]), "=r"(r[1]) : "r"(a) : "memory");
}
DEVI void stsm4t(uint32_t a, uint32_t r0, uint32_t r1, uint32_t r2, uint32_t r3) {
    asm volatile("stmatrix.sync.aligned.m8n8.x4.trans.shared.b16 [%0], {%1,%2,%3,%4};" ::"r"(a), "r"(r0), "r"(r1), "r"(r2), "r"(r3) : "memory");
}
DEVI uint32_t ldsm1(uint32_t a) {
    uint32_t r;
    asm volatile("ldmatrix.sync.aligned.m8n8.x1.shared.b16 {%0}, [%1];" : "=r"(r) : "r"(a) : "memory");
    return r;
}
DEVI void stsm4(uint32_t a, uint32_t r0, uint32_t r1, uint32_t r2, uint32_t r3) {
    asm volatile("stmatrix.sync.aligned.m8n8.x4.shared.b16 [%0], {%1,%2,%3,%4};" ::"r"(a), "r"(r0), "r"(r1), "r"(r2), "r"(r3) : "memory");
}
DEVI void stsm2(uint32_t a, uint32_t r0, uint32_t r1) {
    asm volatile("stmatrix.sync.aligned.m8n8.x2.shared.b16 [%0], {%1,%2};" ::"r"(a), "r"(r0), "r"(r1) : "memory");
}
DEVI uint32_t movm(uint32_t a) {
    uint32_t d;
    asm volatile("movmatrix.sync.aligned.m8n8.trans.b16 %0, %1;" : "=r"(d) : "r"(a));
    return d;
}
DEVI void mma16(float (&d)[4], uint32_t a0, uint32_t a1, uint32_t a2, uint32_t a3, uint32_t b0, uint32_t b1) {
    asm volatile("mma.sync.aligned.m16n8k16.row.col.f32.bf16.bf16.f32 {%0,%1,%2,%3}, {%4,%5,%6,%7}, {%8,%9}, {%0,%1,%2,%3};"
                 : "+f"(d[0]), "+f"(d[1]), "+f"(d[2]), "+f"(d[3]) : "r"(a0), "r"(a1), "r"(a2), "r"(a3), "r"(b0), "r"(b1));
}
DEVI void mma16z(float (&d)[4], uint32_t a0, uint32_t a1, uint32_t a2, uint32_t a3, uint32_t b0, uint32_t b1) {
    asm volatile("mma.sync.aligned.m16n8k16.row.col.f32.bf16.bf16.f32 {%0,%1,%2,%3}, {%4,%5,%6,%7}, {%8,%9}, {%10,%10,%10,%10};"
                 : "=f"(d[0]), "=f"(d[1]), "=f"(d[2]), "=f"(d[3]) : "r"(a0), "r"(a1), "r"(a2), "r"(a3), "r"(b0), "r"(b1), "f"(0.f));
}
DEVI void mma8(float (&d)[4], uint32_t a0, uint32_t a1, uint32_t b0) {
    asm volatile("mma.sync.aligned.m16n8k8.row.col.f32.bf16.bf16.f32 {%0,%1,%2,%3}, {%4,%5}, {%6}, {%0,%1,%2,%3};"
                 : "+f"(d[0]), "+f"(d[1]), "+f"(d[2]), "+f"(d[3]) : "r"(a0), "r"(a1), "r"(b0));
}
DEVI void mma8z(float (&d)[4], uint32_t a0, uint32_t a1, uint32_t b0) {
    asm volatile("mma.sync.aligned.m16n8k8.row.col.f32.bf16.bf16.f32 {%0,%1,%2,%3}, {%4,%5}, {%6}, {%7,%7,%7,%7};"
                 : "=f"(d[0]), "=f"(d[1]), "=f"(d[2]), "=f"(d[3]) : "r"(a0), "r"(a1), "r"(b0), "f"(0.f));
}
DEVI uint32_t pack2(float lo, float hi) {
    uint32_t r;
    asm("cvt.rn.bf16x2.f32 %0, %1, %2;" : "=r"(r) : "f"(hi), "f"(lo));
    return r;
}
DEVI uint32_t hadd2(uint32_t a, uint32_t b) {
    uint32_t r;
    asm("add.rn.bf16x2 %0, %1, %2;" : "=r"(r) : "r"(a), "r"(b));
    return r;
}
DEVI float lo_f(uint32_t x) { return __uint_as_float(x << 16); }
DEVI float hi_f(uint32_t x) { return __uint_as_float(x & 0xFFFF0000u); }
template <uint32_t OFF> DEVI uint4 ldg4(uint32_t lo, uint32_t hi) {
    uint4 v;
    asm volatile("{\n.reg .b64 a;\nmov.b64 a, {%4,%5};\nld.relaxed.gpu.global.v4.u32 {%0,%1,%2,%3}, [a+%6];\n}"
                 : "=r"(v.x), "=r"(v.y), "=r"(v.z), "=r"(v.w) : "r"(lo), "r"(hi), "n"(OFF) : "memory");
    return v;
}
template <uint32_t OFF> DEVI uint2 ldg2(uint32_t lo, uint32_t hi) {
    uint2 v;
    asm volatile("{\n.reg .b64 a;\nmov.b64 a, {%2,%3};\nld.relaxed.gpu.global.v2.u32 {%0,%1}, [a+%4];\n}"
                 : "=r"(v.x), "=r"(v.y) : "r"(lo), "r"(hi), "n"(OFF) : "memory");
    return v;
}
template <uint32_t OFF> DEVI uint32_t ldg1(uint32_t lo, uint32_t hi) {
    uint32_t v;
    asm volatile("{\n.reg .b64 a;\nmov.b64 a, {%1,%2};\nld.relaxed.gpu.global.u32 %0, [a+%3];\n}" : "=r"(v) : "r"(lo), "r"(hi), "n"(OFF) : "memory");
    return v;
}
template <uint32_t OFF> DEVI void stg1(uint32_t lo, uint32_t hi, uint32_t a) {
    asm volatile("{\n.reg .b64 a;\nmov.b64 a, {%0,%1};\nst.relaxed.gpu.global.u32 [a+%3], %2;\n}" ::"r"(lo), "r"(hi), "r"(a), "n"(OFF) : "memory");
}
template <uint32_t OFF> DEVI void stg4(uint32_t lo, uint32_t hi, uint32_t a, uint32_t b, uint32_t c, uint32_t d) {
    asm volatile("{\n.reg .b64 a;\nmov.b64 a, {%0,%1};\nst.relaxed.gpu.global.v4.u32 [a+%6], {%2,%3,%4,%5};\n}"
                 ::"r"(lo), "r"(hi), "r"(a), "r"(b), "r"(c), "r"(d), "n"(OFF) : "memory");
}
template <uint32_t OFF> DEVI void stg2(uint32_t lo, uint32_t hi, uint32_t a, uint32_t b) {
    asm volatile("{\n.reg .b64 a;\nmov.b64 a, {%0,%1};\nst.relaxed.gpu.global.v2.u32 [a+%4], {%2,%3};\n}"
                 ::"r"(lo), "r"(hi), "r"(a), "r"(b), "n"(OFF) : "memory");
}
DEVI uint32_t tagx2(uint32_t a, uint32_t b, uint32_t t) { uint32_t r; asm("lop3.b32 %0, %1, %2, %3, 0x7E;" : "=r"(r) : "r"(a), "r"(b), "r"(t)); return r; }
DEVI uint32_t tagx1(uint32_t a, uint32_t b, uint32_t t) { uint32_t r; asm("lop3.b32 %0, %1, %2, %3, 0xF6;" : "=r"(r) : "r"(a), "r"(b), "r"(t)); return r; }
DEVI uint32_t or3(uint32_t a, uint32_t b, uint32_t c) { uint32_t r; asm("lop3.b32 %0, %1, %2, %3, 0xFE;" : "=r"(r) : "r"(a), "r"(b), "r"(c)); return r; }
DEVI bool any_bad(uint32_t x) { return __any_sync(0xFFFFFFFFu, (x & 1u) != 0); }
DEVI uint32_t settag(uint32_t x, uint32_t tag) { return (x & ~1u) | tag; }
DEVI void sts32f(uint32_t a, float v) { asm volatile("st.shared.f32 [%0], %1;" ::"r"(a), "f"(v) : "memory"); }
DEVI void sts32(uint32_t a, uint32_t v) { asm volatile("st.shared.u32 [%0], %1;" ::"r"(a), "r"(v) : "memory"); }
DEVI void sts16(uint32_t a, uint32_t v) { asm volatile("st.shared.u16 [%0], %1;" ::"r"(a), "h"((unsigned short)v) : "memory"); }
DEVI void sts64(uint32_t a, uint32_t x, uint32_t y) { asm volatile("st.shared.v2.u32 [%0], {%1,%2};" ::"r"(a), "r"(x), "r"(y) : "memory"); }
DEVI void sts128(uint32_t a, uint32_t x, uint32_t y, uint32_t z, uint32_t w) {
    asm volatile("st.shared.v4.u32 [%0], {%1,%2,%3,%4};" ::"r"(a), "r"(x), "r"(y), "r"(z), "r"(w) : "memory");
}
DEVI float4 lds128f(uint32_t a) {
    float4 v;
    asm volatile("ld.shared.v4.f32 {%0,%1,%2,%3}, [%4];" : "=f"(v.x), "=f"(v.y), "=f"(v.z), "=f"(v.w) : "r"(a) : "memory");
    return v;
}
DEVI uint4 lds128(uint32_t a) {
    uint4 v;
    asm volatile("ld.shared.v4.u32 {%0,%1,%2,%3}, [%4];" : "=r"(v.x), "=r"(v.y), "=r"(v.z), "=r"(v.w) : "r"(a) : "memory");
    return v;
}
DEVI uint2 lds64(uint32_t a) {
    uint2 v;
    asm volatile("ld.shared.v2.u32 {%0,%1}, [%2];" : "=r"(v.x), "=r"(v.y) : "r"(a) : "memory");
    return v;
}
DEVI uint32_t lds32(uint32_t a) {
    uint32_t v;
    asm volatile("ld.shared.u32 %0, [%1];" : "=r"(v) : "r"(a) : "memory");
    return v;
}
DEVI float ex2(float x) { float r; asm("ex2.approx.ftz.f32 %0, %1;" : "=f"(r) : "f"(x)); return r; }
DEVI float rcp(float x) { float r; asm("rcp.approx.ftz.f32 %0, %1;" : "=f"(r) : "f"(x)); return r; }
DEVI uint32_t clk() { uint32_t c; asm volatile("mov.u32 %0, %%clock;" : "=r"(c)::"memory"); return c; }

DEVI uint64_t mkdesc(uint32_t addr, uint32_t lbo, uint32_t sbo) {
    return (uint64_t)((addr & 0x3FFFF) >> 4) | ((uint64_t)(lbo >> 4) << 16) | ((uint64_t)(sbo >> 4) << 32) | ((uint64_t)1 << 62);
}
DEVI void wg_fence() { asm volatile("wgmma.fence.sync.aligned;" ::: "memory"); }
DEVI void wg_commit() { asm volatile("wgmma.commit_group.sync.aligned;" ::: "memory"); }
template <int N> DEVI void wg_wait() { asm volatile("wgmma.wait_group.sync.aligned %0;" ::"n"(N) : "memory"); }
template <int SC>
DEVI void wg_rs32(float (&d)[16], const uint32_t (&a)[4], uint64_t db) {
    if (SC) {
        asm volatile("wgmma.mma_async.sync.aligned.m64n32k16.f32.bf16.bf16 "
                     "{%0,%1,%2,%3,%4,%5,%6,%7,%8,%9,%10,%11,%12,%13,%14,%15}, {%16,%17,%18,%19}, %20, 1, 1, 1, 0;"
                     : "+f"(d[0]), "+f"(d[1]), "+f"(d[2]), "+f"(d[3]), "+f"(d[4]), "+f"(d[5]), "+f"(d[6]), "+f"(d[7]),
                       "+f"(d[8]), "+f"(d[9]), "+f"(d[10]), "+f"(d[11]), "+f"(d[12]), "+f"(d[13]), "+f"(d[14]), "+f"(d[15])
                     : "r"(a[0]), "r"(a[1]), "r"(a[2]), "r"(a[3]), "l"(db));
    } else {
        asm volatile("wgmma.mma_async.sync.aligned.m64n32k16.f32.bf16.bf16 "
                     "{%0,%1,%2,%3,%4,%5,%6,%7,%8,%9,%10,%11,%12,%13,%14,%15}, {%16,%17,%18,%19}, %20, 0, 1, 1, 0;"
                     : "=f"(d[0]), "=f"(d[1]), "=f"(d[2]), "=f"(d[3]), "=f"(d[4]), "=f"(d[5]), "=f"(d[6]), "=f"(d[7]),
                       "=f"(d[8]), "=f"(d[9]), "=f"(d[10]), "=f"(d[11]), "=f"(d[12]), "=f"(d[13]), "=f"(d[14]), "=f"(d[15])
                     : "r"(a[0]), "r"(a[1]), "r"(a[2]), "r"(a[3]), "l"(db));
    }
}

#define NA 12
#define NPF 5
#define PF1 2
#define PF2 2
#define PF3 4
#define WPF 2
#define VPF 2
#define VORD 0x01234567
#define VSF 0
#define VMF 0
#define VC 1
#define QP 16
#define W2P 0
#define W3P 1
#define QSP 8
#define VSB 0x10F
#define QQP 3
#define CGP 8
#define C0P 9
#define C1P 9
#define PIP 9
#define K0P 2
#define KEP 4
#define KE2 0
#define VTP 0
#define CW 1
#define WV_BOX ((16 - NA) * 2048)
#define WO_BOX 16384
#define SM_WV 0
#define SM_WO (2 * WV_BOX)
#define SM_X (SM_WO + 4 * WO_BOX)
#define SM_XO (SM_X + 32768)
#define SM_MEMT (SM_XO + 12288)
#define SM_OT (SM_MEMT + 4096)
#define SM_VS (SM_OT + 2048)
#define SM_P (SM_VS + 2048)
#define SM_DN (SM_P + 1792)
#define SM_PROF (SM_P + 2048)
#define SM_ST (SM_X + 65536)
#define SM_KV SM_ST
#define SM_SP (SM_KV + 18432)
#define SM_TR (SM_ST + 32768)
#define SM_PI (SM_ST + 65536)
#define SM_BAR (SM_PI + 12288)
#define SM_TOTAL (SM_BAR + 512)
static_assert(NA == 12, "start-up chunks");
static_assert(SM_TOTAL <= 232448, "smem");
#define BAR_XA 32
#define BAR_KV 40
#define BAR_PI 48
#define BAR_RO 64
#define BAR_WF 256
#define BAR_WE 384
#define SM_ROLE (SM_BAR + 72)

#define SPIN_LIMIT (1 << 20)
#define RPOS 26
#define OPOS 2
#define ASF 0
#define KPOS 0
#define CPOS 1
#define DLY_V 300
#define NPRB 2
#define PW 4
#define ZD 0
#define FTM 2
#define XPF 1
#define WOP 2
#define WIN 2
#define EPD 1300
#define ASP 4
#define EPF 0
#define CFAR 1

template <int ID, int N> DEVI void bsync() { asm volatile("bar.sync %0, %1;" ::"n"(ID), "n"(N) : "memory"); }
template <int ID, int N> DEVI void barv() { asm volatile("bar.arrive %0, %1;" ::"n"(ID), "n"(N) : "memory"); }

#define PT(n)
#define PC(n, v)
#define PDUMP()
#define REFRESH() asm volatile("xor.b32 %0, %0, %1;" : "+r"(l16) : "r"(zero))
#define OPQ(x) asm volatile("xor.b32 %0, %0, %1;" : "+r"(x) : "r"(zero))
#define KEEP(x, a, b, c, d) asm volatile("{\n.reg .b32 t;\nlop3.b32 t, %1, %2, %3, 0x80;\nlop3.b32 t, t, %4, %5, 0x80;\nxor.b32 %0, %0, t;\n}" \
                                         : "+r"(x) : "r"(a), "r"(b), "r"(c), "r"(d), "r"(zero))
#define SF() asm volatile("pmevent 1;" ::: "memory")
#define MF() __syncwarp()
#define SB0 1024u

#define XDOFF(ks) ((((ks) >> 2) * 1024 + ((ks) & 3) * 32) >> 4)
template <int SC>
DEVI void wg_ss32t(float (&d)[16], uint64_t da, uint64_t db) {
    if (SC) {
        asm volatile("wgmma.mma_async.sync.aligned.m64n32k16.f32.bf16.bf16 "
                     "{%0,%1,%2,%3,%4,%5,%6,%7,%8,%9,%10,%11,%12,%13,%14,%15}, %16, %17, 1, 1, 1, 1, 0;"
                     : "+f"(d[0]), "+f"(d[1]), "+f"(d[2]), "+f"(d[3]), "+f"(d[4]), "+f"(d[5]), "+f"(d[6]), "+f"(d[7]),
                       "+f"(d[8]), "+f"(d[9]), "+f"(d[10]), "+f"(d[11]), "+f"(d[12]), "+f"(d[13]), "+f"(d[14]), "+f"(d[15])
                     : "l"(da), "l"(db));
    } else {
        asm volatile("wgmma.mma_async.sync.aligned.m64n32k16.f32.bf16.bf16 "
                     "{%0,%1,%2,%3,%4,%5,%6,%7,%8,%9,%10,%11,%12,%13,%14,%15}, %16, %17, 0, 1, 1, 1, 0;"
                     : "=f"(d[0]), "=f"(d[1]), "=f"(d[2]), "=f"(d[3]), "=f"(d[4]), "=f"(d[5]), "=f"(d[6]), "=f"(d[7]),
                       "=f"(d[8]), "=f"(d[9]), "=f"(d[10]), "=f"(d[11]), "=f"(d[12]), "=f"(d[13]), "=f"(d[14]), "=f"(d[15])
                     : "l"(da), "l"(db));
    }
}

DEVI void delay_until(uint32_t t0, uint32_t d) { while (clk() - t0 < d) {} }

template <int I0, int I1>
DEVI void xmma(float (&xa)[16], float (&xb)[16], uint32_t w, int ps, uint32_t zero, const uint32_t (&Wq)[16][4], const uint32_t (&Wk)[16][4],
               const uint32_t (&Wv)[NA][4]) {
    const uint64_t xd = mkdesc(SB0 + SM_X, 16, 4096) + (ps & 1) * 1024, vd = mkdesc(SB0 + SM_WV, 8192, 1024);
    uint32_t vo = (w >> 2) * (WV_BOX / 16);
    if (VC == 0 ? I0 < 16 - NA : VC == 1 ? I0 >= 32 && I0 < 48 - NA : I1 > 32 + NA) OPQ(vo);
#pragma unroll
    for (int i = I0; i < I1; i++) {
        if (VC) {
            const int v = (i + (VC == 1 ? NA : 0)) & 15;
            if (i == 0) wg_rs32<0>(xa, Wq[0], xd);
            else if (i < 16) wg_rs32<1>(xa, Wq[i & 15], xd + XDOFF(i & 15));
            else if (i == 16) wg_rs32<0>(xb, Wk[0], xd);
            else if (i < 32) wg_rs32<1>(xb, Wk[i & 15], xd + XDOFF(i & 15));
            else if (i == 32 && v < NA) wg_rs32<0>(xa, Wv[0], xd);
            else if (i == 32) wg_ss32t<0>(xa, (vd & ~0xFFFFFFFFull) | ((uint32_t)vd + vo), xd + XDOFF(NA));
            else if (v < NA) wg_rs32<1>(xa, Wv[v < NA ? v : 0], xd + XDOFF(v));
            else wg_ss32t<1>(xa, (vd & ~0xFFFFFFFFull) | ((uint32_t)vd + (v - NA) * 128 + vo), xd + XDOFF(v));
        } else
        if (i == 0) wg_ss32t<0>(xb, (vd & ~0xFFFFFFFFull) | ((uint32_t)vd + vo), xd + XDOFF(NA));
        else if (i < 16 - NA) wg_ss32t<1>(xb, (vd & ~0xFFFFFFFFull) | ((uint32_t)vd + i * 128 + vo), xd + XDOFF(NA + i));
        else if (i == 16 - NA) wg_rs32<0>(xa, Wq[0], xd);
        else if (i < 32 - NA) wg_rs32<1>(xa, Wq[(i + NA) & 15], xd + XDOFF((i + NA) & 15));
        else if (i < 32) wg_rs32<1>(xb, Wv[(i + NA) & 15], xd + XDOFF((i + NA) & 15));
        else if (i == 32) wg_rs32<0>(xa, Wk[0], xd);
        else wg_rs32<1>(xa, Wk[i & 15], xd + XDOFF(i & 15));
    }
    wg_commit();
}
#define XMMA(I0, I1) xmma<(I0), (I1)>(xa, xb, w, p ^ 1, zero, Wq, Wk, Wv)
DEVI void wg_done(float (&d)[16]) {
    asm volatile("" : "+f"(d[0]), "+f"(d[1]), "+f"(d[2]), "+f"(d[3]), "+f"(d[4]), "+f"(d[5]), "+f"(d[6]), "+f"(d[7]),
                      "+f"(d[8]), "+f"(d[9]), "+f"(d[10]), "+f"(d[11]), "+f"(d[12]), "+f"(d[13]), "+f"(d[14]), "+f"(d[15]) :: "memory");
}
template <int M>
DEVI void xpack(uint32_t (&xp)[8], float (&xa)[16]) {
    wg_done(xa);
#pragma unroll
    for (int i = 0; i < 4; i++) {
        xp[2 * i] = pack2(xa[4 * i], xa[4 * i + (M < 2 ? 2 : 1)]);
        xp[2 * i + 1] = pack2(xa[4 * i + (M < 2 ? 1 : 2)], xa[4 * i + 3]);
    }
}
template <int M>
DEVI uint4 xpeer(uint32_t sb, int ps, uint32_t t16) { return lds128(sb + SM_PI - ((ps & 1) ^ 1) * 12288 + M * 4096 + t16); }
DEVI void xadd(uint32_t (&xp)[8], const uint4& pi) {
    xp[0] = hadd2(xp[0], pi.x); xp[1] = hadd2(xp[1], pi.y); xp[2] = hadd2(xp[2], pi.z); xp[3] = hadd2(xp[3], pi.w);
}
template <int M>
DEVI void xsend(const uint32_t (&xp)[8], uint32_t sb, int ps, uint32_t t16) {
    asm volatile("st.async.weak.shared::cluster.mbarrier::complete_tx::bytes.v4.b32 [%0], {%1,%2,%3,%4}, [%5];"
                 ::"r"((sb ^ 0x1000000) + SM_PI - (ps & 1) * 12288 + M * 4096 + t16), "r"(xp[4]), "r"(xp[5]), "r"(xp[6]), "r"(xp[7]),
                   "r"((sb ^ 0x1000000) + SM_BAR + BAR_PI + (ps & 1) * 8) : "memory");
}
template <int M>
DEVI void xstore(const uint32_t (&xp)[8], uint32_t sb, uint32_t sbw, int ps, uint32_t t16, uint32_t KA) {
    const uint32_t a = SM_XO + M * 2048 + (M < 2 ? (KA & 0xFF) + sbw : (t16 >> 1) + sb);
    sts64(a, xp[0], xp[1]);
    sts64(a + 6144, xp[2], xp[3]);
    xsend<M>(xp, sb, ps, t16);
}
template <int M>
DEVI void xpark(uint32_t (&xp)[8], const uint4& pi, uint32_t sb, uint32_t sbw, int ps, uint32_t t16, uint32_t KA) {
    xadd(xp, pi);
    xstore<M>(xp, sb, sbw, ps, t16, KA);
}
template <uint32_t OFF> DEVI void red2(uint32_t lo, uint32_t hi, uint32_t a, uint32_t b) {
    asm volatile("{\n.reg .b64 a;\nmov.b64 a, {%0,%1};\nred.relaxed.gpu.global.add.noftz.v2.bf16x2 [a+%4], {%2,%3};\n}"
                 ::"r"(lo), "r"(hi), "r"(a), "r"(b), "n"(OFF) : "memory");
}
template <int M, int N>
DEVI void xstart(uint32_t sb, uint32_t w, uint32_t ga, uint32_t xhi, uint32_t j, uint32_t t16, uint32_t KA, const uint32_t (&W)[N][4]) {
    float xa[16], xb[16];
    uint32_t xp[8];
    auto pass = [&](float (&d)[16], int i, int k0, int k1) {
        const uint64_t xd = mkdesc(SB0 + SM_X + (i ? i + 1 : 0) * 16384, 16, 4096), vd = mkdesc(SB0 + SM_WV, 8192, 1024) + (w >> 2) * (WV_BOX / 16);
#pragma unroll
        for (int k = k0; k < k1; k++) {
            if (k == 0) wg_rs32<0>(d, W[0], xd);
            else if (k < N) wg_rs32<1>(d, W[k < N ? k : 0], xd + XDOFF(k));
            else wg_ss32t<1>(d, vd + (k - N) * 128, xd + XDOFF(k));
        }
        wg_commit();
    };
    wg_fence();
    pass(xa, 0, 0, 16);
    pass(xb, 1, 0, ASP);
    if (M == 0) bsync<5, 288>();
    ga += M < 2 ? (KA & 0xFF) + w * 256 : t16 >> 1;
    constexpr uint32_t O = XO_XG + M * 2048, SG = 128 * 6144;
    wg_wait<1>();
    xpack<M>(xp, xa);
    red2<O>(ga, xhi, xp[0], xp[1]); red2<O + 6144>(ga, xhi, xp[2], xp[3]); red2<O + 12288>(ga, xhi, xp[4], xp[5]); red2<O + 18432>(ga, xhi, xp[6], xp[7]);
    if (M == 2) barv<3, 320>();
    wg_fence();
    pass(xb, 1, ASP, 16);
    pass(xa, 2, 0, 16);
    wg_wait<1>();
    xpack<M>(xp, xb);
    red2<O + SG>(ga, xhi, xp[0], xp[1]); red2<O + SG + 6144>(ga, xhi, xp[2], xp[3]);
    red2<O + SG + 12288>(ga, xhi, xp[4], xp[5]); red2<O + SG + 18432>(ga, xhi, xp[6], xp[7]);
    wg_wait<0>();
    xpack<M>(xp, xa);
    red2<O + 2 * SG>(ga + j * 6144, xhi, xp[0], xp[1]);
    red2<O + 2 * SG>(ga + (j ^ 1) * 6144, xhi, xp[2], xp[3]);
    xsend<M>(xp, sb, 0, t16);
}
DEVI void piwait(uint32_t sb, int p, int ps) { mbar_wait(sb + SM_BAR + BAR_PI + p * 8, ((ps + 2) >> 1) & 1); }

DEVI uint32_t par(uint32_t off) { return __popc(off & 0xB2000u) & 1; }
DEVI uint32_t probe(uint32_t lo, uint32_t hi) {
    uint32_t best = 0xFFFFFFFFu, x = 0;
    stg4<0>(lo, hi, 0, 0, 0, 0);
    stg4<16>(lo, hi, 0, 0, 0, 0);
#pragma unroll 1
    for (int r = 0; r < NPRB; r++) {
        const uint32_t t0 = clk();
        asm volatile("{\n.reg .b64 a;\nmov.b64 a, {%1,%2};\natom.relaxed.gpu.global.add.u32 %0, [a], 2;\n}" : "=r"(x) : "r"(lo), "r"(hi) : "memory");
        if (x == 0xFFFFFFFFu) die(1 << 23);
        best = min(best, clk() - t0);
    }
    return best;
}

DEVI void xload(uint32_t sb, uint32_t u, uint32_t j, int ps, const CUtensorMap* tmx) {
    if (elect()) {
        const uint32_t sg = ps + 4 - (u & 1) + (u >> 1);
        mbar_expect(sb + SM_BAR + BAR_XA, sg < NSEG ? 4096 : 0);
        if (sg < NSEG) tma3d(sb + SM_X + (ps & 1) * 16384 + u * 4096, tmx, sb + SM_BAR + BAR_XA, 0, sg * 32 + (j ^ ((u & 1) * 2 + (u >> 1))) * 8, j * 4);
    }
}
DEVI uint32_t rpage(uint32_t j, int s) { return (s & 3) * 65536 + (j & 1) * 8192 + (((s ^ (s >> 1) ^ j ^ (j >> 1)) & 1) << 12); }

#define RLOAD() { m0 = ldg4<XO_R>(a, ah); n0 = ldg4<XO_R + 16384>(a, ah); e0 = ldg1<XO_R + 32768>(e, eh); f0 = ldg1<XO_R + 33792>(e, eh); }
DEVI bool ruse(uint32_t a, const uint4& m0, const uint4& n0, uint32_t e0, uint32_t f0) {
    const uint32_t a0 = hadd2(m0.w, n0.w), b0 = hadd2(e0, f0);
    stsm4(a, hadd2(m0.x, n0.x), hadd2(m0.y, n0.y), hadd2(m0.z, n0.z), __byte_perm(a0, b0, 0x5410));
    return __any_sync(0xFFFFFFFFu, (a0 & b0 & 0x42000000u) != 0x42000000u);
}

#define GST(i) (SM_WO + (i) * 49152)
#define BAR_GF 128
#define BAR_GE (BAR_GF + 64)
#define BAR_GX (BAR_GE + 32)
#define D4(c, i) #c "f"(d[i]), #c "f"(d[i + 1]), #c "f"(d[i + 2]), #c "f"(d[i + 3])
#define D16(c, i) D4(c, i), D4(c, i + 4), D4(c, i + 8), D4(c, i + 12)
DEVI void mwait(uint32_t bar, uint32_t parity) {
    asm volatile("{\n.reg .pred p;\n.reg .b32 c;\nmbarrier.try_wait.parity.shared::cta.b64 p, [%0], %1;\n@p bra.uni D;\nmov.b32 c, 0;\n"
                 "L:\nadd.u32 c, c, 1;\nsetp.gt.u32 p, c, 4194304;\n@p st.shared.u32 [c], c;\n"
                 "mbarrier.try_wait.parity.shared::cta.b64 p, [%0], %1;\n@!p bra.uni L;\nD:\n}" ::"r"(bar), "r"(parity) : "memory");
}
DEVI void wg_ss256t(float (&d)[128], uint64_t da, uint64_t db) {
    asm volatile("wgmma.mma_async.sync.aligned.m64n256k16.f32.bf16.bf16 "
        "{%0,%1,%2,%3,%4,%5,%6,%7,%8,%9,%10,%11,%12,%13,%14,%15,%16,%17,%18,%19,%20,%21,%22,%23,%24,%25,%26,%27,%28,%29,%30,%31,%32,%33,%34,%35,%36,%37,%38,%39,%40,%41,%42,%43,%44,%45,%46,%47,%48,%49,%50,%51,%52,%53,%54,%55,%56,%57,%58,%59,%60,%61,%62,%63,%64,%65,%66,%67,%68,%69,%70,%71,%72,%73,%74,%75,%76,%77,%78,%79,%80,%81,%82,%83,%84,%85,%86,%87,%88,%89,%90,%91,%92,%93,%94,%95,%96,%97,%98,%99,%100,%101,%102,%103,%104,%105,%106,%107,%108,%109,%110,%111,%112,%113,%114,%115,%116,%117,%118,%119,%120,%121,%122,%123,%124,%125,%126,%127}, "
        "%128, %129, 1, 1, 1, 1, 1;"
        : D16(+, 0), D16(+, 16), D16(+, 32), D16(+, 48), D16(+, 64), D16(+, 80), D16(+, 96), D16(+, 112) : "l"(da), "l"(db));
}
template <int O, int KB> DEVI void g_half(float (&d)[64], uint64_t da) {
    const uint64_t db = mkdesc(SB0 + GST(KB & 3) + 16384 + O * 256, 8192, 1024);
#pragma unroll
    for (int k = 0; k < 4; k++)
        asm volatile("wgmma.mma_async.sync.aligned.m64n128k16.f32.bf16.bf16 "
            "{%0,%1,%2,%3,%4,%5,%6,%7,%8,%9,%10,%11,%12,%13,%14,%15,%16,%17,%18,%19,%20,%21,%22,%23,%24,%25,%26,%27,%28,%29,%30,%31,%32,%33,%34,%35,%36,%37,%38,%39,%40,%41,%42,%43,%44,%45,%46,%47,%48,%49,%50,%51,%52,%53,%54,%55,%56,%57,%58,%59,%60,%61,%62,%63}, "
            "%64, %65, 1, 1, 1, 1, 1;"
            : D16(+, 0), D16(+, 16), D16(+, 32), D16(+, 48) : "l"(da + (KB & 3) * 3072 + k * 16), "l"(db + k * 128));
}
DEVI void g_load(uint32_t sb, uint32_t u, uint32_t role, uint32_t kb, uint32_t xlo, uint32_t xhi, const CUtensorMap* tmb) {
    const uint32_t st = kb & 3, bar = sb + SM_BAR + BAR_GF + u * 32 + st * 8, dst = sb + GST(st), k = (role & 1) * 32 + kb;
    if (!elect()) return;
    mbar_expect(bar, u ? 8192 : 40960);
    bulk_g2s(dst + u * 8192, xlo + XO_OX + (k * 16 + (role >> 3)) * 16384 + u * 8192, xhi, 8192, bar);
    if (u == 0) {
        tma3d(dst + 16384, tmb, bar, 0, k * 64, ((role & 7) ^ 1) * 2);
        tma3d(dst + 32768, tmb, bar, 0, k * 64, (role & 7) * 2);
    }
}
DEVI void g_arrive(uint32_t a, uint32_t xhi, uint32_t n) {
    if (elect()) asm volatile("{\n.reg .b64 a;\nmov.b64 a, {%0,%1};\nred.release.gpu.global.inc.u32 [a], %2;\n}" ::"r"(a), "r"(xhi), "r"(n - 1) : "memory");
}
DEVI void g_wait(uint32_t a, uint32_t xhi) {
    int it = 0;
    uint32_t v;
    do {
        asm volatile("{\n.reg .b64 a;\nmov.b64 a, {%1,%2};\nld.acquire.gpu.global.u32 %0, [a];\n}" : "=r"(v) : "r"(a), "r"(xhi) : "memory");
        if (++it > SPIN_LIMIT) die(it);
    } while (__any_sync(0xFFFFFFFFu, v));
    asm volatile("fence.proxy.async.global;" ::: "memory");
}
#define SE 2
#define DLY_S 0
#define VX 1
#define VH 1
#define VD 1
#define SM_VP (SM_TR + 12288)
#define JV(h, j) (VH < 2 ? (j) ^ ((par((h) * 8192) ^ VH) << 1) : (j))
#define SEU 0
#define VA 0
#define VLP 0
#define VCP 1
#define B3 0
#define GD 200
#define GE 1
#define GH 1
#define GS 1
#define GP 1
DEVI void g_done(float (&d)[64]) { asm volatile("" : D16(+, 0), D16(+, 16), D16(+, 32), D16(+, 48)::"memory"); }
DEVI void g_main(uint32_t sb, uint32_t w, uint32_t role, const CUtensorMap* tmy, void* out) {
    const uint32_t bar = sb + SM_BAR, t16 = threadIdx.x * 16;
    const uint64_t da = (mkdesc(SB0 + GST(0), 128, 1024) & ~((uint64_t)3 << 62)) + (w >> 2) * 512;
    float d[128];
#pragma unroll
    for (int i = 0; i < 128; i++) d[i] = 0.f;
#define GFULL(kb) { mwait(bar + BAR_GF + ((kb) & 3) * 8, ((kb) >> 2) & 1); if (w >= 4) mwait(bar + BAR_GF + 32 + ((kb) & 3) * 8, ((kb) >> 2) & 1); }
#pragma unroll 1
    for (uint32_t kb = 0; kb < (GE ? 28 : 29); kb++) {
        GFULL(kb);
        if (kb == 0 && threadIdx.x == 128) PG(4);
        if (kb == 4 && threadIdx.x == 0) PG(5);
        const uint64_t a = da + (kb & 3) * 3072, b = mkdesc(SB0 + GST(0) + 16384, 8192, 1024) + (kb & 3) * 3072;
        wg_fence();
#pragma unroll
        for (int k = 0; k < 4; k++) wg_ss256t(d, a + k * 16, b + k * 128);
        wg_commit();
        wg_wait<1>();
        if (kb > 0 && elect()) mbar_arrive(bar + BAR_GE + ((kb - 1) & 3) * 8);
    }
    if (GE) { GFULL(28); }
    else { GFULL(29); GFULL(30); GFULL(31); }
    wg_wait<0>();
    if (GE && elect()) mbar_arrive(bar + BAR_GE + 24);
    float x[64], y[64];
#pragma unroll
    for (int i = 0; i < 64; i++) asm volatile("mov.b32 %0, %1;" : "=f"(x[i]) : "f"(d[i]) : "memory");
    SF();
#pragma unroll
    for (int i = 0; i < 64; i++) asm volatile("mov.b32 %0, %1;" : "=f"(y[i]) : "f"(d[i + 64]) : "memory");
    SF();
#define GFREE() if (elect()) asm volatile("mbarrier.arrive.relaxed.cluster.shared::cluster.b64 _, [%0];" ::"r"((bar ^ 0x1000000) + BAR_GX) : "memory")
#define GSW(i) ((i) * 4096 + (GE && (i) >= 4 ? GST(0) : 0))
#define GSEND(i0) _Pragma("unroll") for (int i = (i0); i < (i0) + 4; i++) \
        asm volatile("st.async.weak.shared::cluster.mbarrier::complete_tx::bytes.v4.b32 [%0], {%1,%2,%3,%4}, [%5];" \
                     ::"r"((sb ^ 0x1000000) + GSW(i) + t16), "r"(pack2(x[8 * i], x[8 * i + 1])), "r"(pack2(x[8 * i + 2], x[8 * i + 3])), \
                       "r"(pack2(x[8 * i + 4], x[8 * i + 5])), "r"(pack2(x[8 * i + 6], x[8 * i + 7])), "r"((bar ^ 0x1000000) + BAR_GX + 8) : "memory")
    if (GE) {
        wg_fence();
        g_half<0, 28>(x, da);
        wg_commit();
        GFULL(29);
        wg_fence();
        g_half<0, 29>(x, da);
        wg_commit();
        GFULL(30);
        wg_fence();
        g_half<0, 30>(x, da);
        wg_commit();
        GFULL(31);
        wg_fence();
        g_half<0, 31>(x, da);
        wg_commit();
        g_half<64, 28>(y, da);
        if (GE == 2) g_half<64, 29>(y, da);
        wg_commit();
        wg_wait<1>();
        g_done(x);
        GFREE();
        GSEND(0);
        wg_fence();
        if (GE != 2) g_half<64, 29>(y, da);
        if (GE != 1) g_half<64, 30>(y, da);
        wg_commit();
        mwait(bar + BAR_GX, 0);
        GSEND(4);
        wg_fence();
        if (GE == 1) g_half<64, 30>(y, da);
        g_half<64, 31>(y, da);
        wg_commit();
        mwait(bar + BAR_GX + 8, 0);
        if (threadIdx.x == 0) PG(1);
#pragma unroll
        for (int i = 0; i < 8; i++) {
            const uint4 a = lds128(sb + GSW(i) + t16);
            float* e = x + 8 * i;
            e[0] = lo_f(a.x); e[1] = hi_f(a.x); e[2] = lo_f(a.y); e[3] = hi_f(a.y); e[4] = lo_f(a.z); e[5] = hi_f(a.z); e[6] = lo_f(a.w); e[7] = hi_f(a.w);
        }
        g_done(x);
        SF();
        wg_wait<0>();
        g_done(y);
        if (threadIdx.x == 0) PG(7);
    } else {
        GFREE();
        wg_fence();
        g_half<0, 29>(x, da);
        g_half<0, 30>(x, da);
        g_half<0, 31>(x, da);
        wg_commit();
        g_half<64, 29>(y, da);
        wg_commit();
        wg_wait<1>();
        g_done(x);
        mwait(bar + BAR_GX, 0);
        GSEND(0);
        wg_fence();
        g_half<64, 30>(y, da);
        wg_commit();
        GSEND(4);
        wg_fence();
        g_half<64, 31>(y, da);
        wg_commit();
        wg_wait<0>();
        g_done(y);
        if (threadIdx.x == 0) PG(7);
        mwait(bar + BAR_GX + 8, 0);
        if (threadIdx.x == 0) PG(1);
    }
    const uint32_t lane = threadIdx.x & 31, o = sb + GST(1) + w * 2048;
    char* go = (char*)out + ((role >> 3) * 128 + w * 16 + (lane >> 3)) * 4096 + (role & 7) * 256 + (lane & 7) * 16;
#pragma unroll
    for (int i = 0; i < 8; i++) {
        float* e = y + 8 * i;
        if (GE) {
#pragma unroll
            for (int n = 0; n < 8; n++) e[n] += x[8 * i + n];
        } else {
            const uint4 a = lds128(sb + i * 4096 + t16);
            e[0] += lo_f(a.x); e[1] += hi_f(a.x); e[2] += lo_f(a.y); e[3] += hi_f(a.y); e[4] += lo_f(a.z); e[5] += hi_f(a.z); e[6] += lo_f(a.w); e[7] += hi_f(a.w);
        }
        stsm4(o + (i >> 2) * 49152 + (lane & 15) * 128 + ((((i & 3) * 2 + (lane >> 4)) ^ (lane & 7)) << 4),
              pack2(e[0], e[1]), pack2(e[2], e[3]), pack2(e[4], e[5]), pack2(e[6], e[7]));
        if (i == 3 || i == 7) {
            if (GS) {
                __syncwarp();
#pragma unroll
                for (int m = 0; m < 4; m++)
                    *(uint4*)(go + m * 16384 + (i >> 2) * 128) =
                        lds128(o + (i >> 2) * 49152 + m * 512 + (lane >> 3) * 128 + (((lane & 7) ^ ((m & 1) * 4 + (lane >> 3))) << 4));
            } else {
                asm volatile("fence.proxy.async.shared::cta;" ::: "memory");
                __syncwarp();
                if (elect())
                    asm volatile("cp.async.bulk.tensor.2d.global.shared::cta.bulk_group [%0, {%2, %3}], [%1];\ncp.async.bulk.commit_group;"
                                 ::"l"(tmy), "r"(o + (i >> 2) * 49152), "r"((role & 7) * 128 + (i >> 2) * 64), "r"((role >> 3) * 128 + w * 16) : "memory");
            }
        }
    }
    if (threadIdx.x == 0) PG(6);
    if (!GS) asm volatile("cp.async.bulk.wait_group.read 0;" ::: "memory");
}

DEVI void kvload(uint32_t sb, uint32_t u, uint32_t h, uint32_t j, int sg, uint32_t xlo, uint32_t xhi) {
    const uint32_t o = u == 0 ? 0 : 2048;
    mbar_expect(sb + SM_BAR + BAR_KV, 6144 - o);
    bulk_g2s(sb + SM_KV + u * 4096 + o, xlo + XO_XG + (((sg & 7) * 32 + h) * 4 + ((j + u) & 3)) * 6144 + o, xhi, 6144 - o, sb + SM_BAR + BAR_KV);
}
DEVI void helper_step(uint32_t sb, uint32_t w, uint32_t h, uint32_t j, uint32_t& l16, uint32_t xlo, uint32_t xhi, uint32_t zero, int s,
                      const CUtensorMap* tmx, const CUtensorMap* tmb) {
    const uint32_t u = w - 8, bq = sb + SM_BAR;
    bsync<1, 384>();
    PT(0);
    PDUMP();
    PT(1);
    if (s == NSEG - 2 && u < 2) g_arrive(xlo + XO_TK + 128, xhi, 256);
    const bool gl = u == 0 || (u == 1 && h < 30);
    if (GP == 1 && s == NSEG - 1 && gl) g_load(sb, u, h * 4 + j, 1, xlo, xhi, tmb);
    const uint32_t ctag = ((s >> 1) & 1) ^ 1;
    const uint32_t av = xlo + ((s & 1) * 32 + h) * 8192 + u * 512;
    mbar_wait(bq + BAR_XA, (s + 1) & 1);
    if (B3 == 8) barv<5, 384>();
    bsync<8, 384>();
    const uint32_t t8 = clk(), gs = xlo + XO_XG + ((((s + 3) & 7) * 32 + h) * 4 + j) * 6144;
    const bool se = B3 % 8 == 0 && SE && u == SEU && s + 3 < NSEG;
    if (se) {
        asm volatile("fence.proxy.async.shared::cta;" ::: "memory");
        if (SE == 1 && elect()) bulk_s2g(gs, xhi, sb + SM_XO, 4096);
    }
    if (B3 != 6 || u || SE == 2) delay_until(t8, DLY_V);
    if (se && SE == 2 && elect()) bulk_s2g(gs, xhi, sb + SM_XO, 4096);
    PT(4);
    int it = 0;
    uint4 d1, d2, d3;
    uint2 e1, e2, e3;
    const uint32_t ae = av - u * 512 + (u & 1) * 256;
    const uint32_t jv = JV(h, j);
#define VLOAD() { if (!VD) d1 = ldg4<XO_CV>(av + (jv ^ 1) * 2048 + l16, xhi); \
        d2 = ldg4<XO_CV>(av + (jv ^ 2) * 2048 + l16, xhi); d3 = ldg4<XO_CV>(av + (jv ^ 3) * 2048 + l16, xhi); \
        if (B3 == 6 && VX) { if (!VD) e1 = ldg2<XO_CV>(ae + (jv ^ 1) * 2048 + (l16 >> 1), xhi); \
                       e2 = ldg2<XO_CV>(ae + (jv ^ 2) * 2048 + (l16 >> 1), xhi); e3 = ldg2<XO_CV>(ae + (jv ^ 3) * 2048 + (l16 >> 1), xhi); } \
        if (VD) { d1 = lds128(sb + SM_VP + (s & 1) * 2048 + u * 512 + l16); \
                  if (B3 == 6 && VX) e1 = lds64(sb + SM_VP + (s & 1) * 2048 + (u & 1) * 256 + (l16 >> 1)); } }
#define XSEND(F, C) if (u < 2) { \
        if (F) asm volatile("fence.proxy.async.shared::cta;" ::: "memory"); \
        if ((C) && elect()) { \
            const uint32_t sg = s + 3 - u; \
            if (sg < NSEG) { \
                const uint32_t ga = xlo + XO_XG + (((sg & 7) * 32 + h) * 4 + (j ^ (2 * u))) * 6144, sa = sb + SM_XO + u * 6144; \
                if (u == 0) bulk_s2g(ga + (SE ? 4096 : 0), xhi, sa + (SE ? 4096 : 0), SE ? 2048 : 6144); \
                else bulk_red(ga, xhi, sa, 6144); \
            } \
        } \
    }
    if (B3 == 8) {
        bsync<3, 384>();
        if (DLY_S) delay_until(clk(), DLY_S);
        XSEND(true, true);
    } else if (B3 == 6 && u == 0) {
        const uint32_t ga = xlo + XO_XG + ((((s + 3) & 7) * 32 + h) * 4 + j) * 6144, o = SE == 1 || SE == 2 ? 4096 : 0;
        if (o) {
            asm volatile("fence.proxy.async.shared::cta;" ::: "memory");
            if (s + 3 < NSEG && elect()) bulk_s2g(ga, xhi, sb + SM_XO, o);
        }
        bsync<3, 288>();
        if (DLY_S) delay_until(clk(), DLY_S);
        asm volatile("fence.proxy.async.shared::cta;" ::: "memory");
        if (elect()) {
            if (SE == 3 && s + 3 < NSEG) bulk_s2g(ga + o, xhi, sb + SM_XO + o, 6144 - o);
            if (s + 2 < NSEG) bulk_red(xlo + XO_XG + ((((s + 2) & 7) * 32 + h) * 4 + (j ^ 2)) * 6144, xhi, sb + SM_XO + 6144, 6144);
            if (SE != 3 && s + 3 < NSEG) bulk_s2g(ga + o, xhi, sb + SM_XO + o, 6144 - o);
        }
    } else {
    if (B3 == 6) VLOAD();
    if (B3 && B3 < 6) {
        VLOAD();
        bsync<B3 == 2 ? 4 : 3, 384>();
        XSEND(true, B3 < 3 || B3 == 5 || (B3 == 4 && u == 0));
    }
    while (true) {
        if (B3 % 7 == 0) VLOAD();
        if (se && SE == 3 && it == 0 && elect()) bulk_s2g(gs, xhi, sb + SM_XO, 4096);
        uint32_t tg = or3(tagx2(d1.x, d1.z, ctag), tagx2(d2.x, d2.z, ctag), tagx2(d3.x, d3.z, ctag));
        if (B3 == 6 && VX) tg = or3(tg, tagx2(e1.x, e2.x, ctag), e3.x ^ ctag);
        const bool bad = any_bad(tg);
        if (B3 == 6 && VX) sts64(sb + SM_VS + (u & 1) * 256 + (l16 >> 1), hadd2(hadd2(e1.x, e2.x), e3.x), hadd2(hadd2(e1.y, e2.y), e3.y));
        sts128(sb + SM_VS + u * 512 + l16, hadd2(hadd2(d1.x, d2.x), d3.x), hadd2(hadd2(d1.y, d2.y), d3.y), hadd2(hadd2(d1.z, d2.z), d3.z),
               hadd2(hadd2(d1.w, d2.w), d3.w));
        if (VA) asm volatile("{\n.reg .pred p;\nsetp.eq.u32 p, %0, 0;\n@p bar.arrive 5, 384;\n}" ::"r"((uint32_t)bad) : "memory");
        if (B3 % 7 == 0) REFRESH();
        if (!bad) break;
        if (B3 % 7) { REFRESH(); VLOAD(); }
        if (++it > SPIN_LIMIT) die(it);
    }
    PC(26, it);
    PT(5);
    if (!VA) barv<5, B3 == 6 ? 352 : 384>();
    }
    if (B3 % 7 == 0) {
        bsync<3, 384>();
        XSEND(true, true);
    }
    if (B3 == 3 || B3 == 4) XSEND(false, B3 == 3 || u == 1);
    PT(6);
    uint32_t old = 0;
    if (u > 0 && s + 3 < NSEG)
        asm volatile("{\n.reg .b64 a;\nmov.b64 a, {%1,%2};\natom.relaxed.gpu.global.exch.b32 %0, [a], 0;\n}"
                     : "=r"(old) : "r"(xlo + XO_R + rpage(j, s + 2) + (u - 1) * 16384 + h * 128 + (l16 >> 2)), "r"(xhi) : "memory");
    PT(7);
    bsync<7, 384>();
    if (s + 1 < NSEG && elect()) kvload(sb, u, h, j, s + 1, xlo, xhi);
    if (u < (B3 == 6 ? 1 : 2)) {
        asm volatile("cp.async.bulk.wait_group.read 0;" ::: "memory");
        if (elect()) {
            mbar_expect(bq + BAR_PI + ((s & 1) ^ 1) * 8, 6144);
            if (B3 == 6) mbar_expect(bq + BAR_PI + ((s & 1) ^ 1) * 8, 6144);
        }
    }
    PT(8);
    if (GP && s == NSEG - 2 && gl) g_wait(xlo + XO_TK + 128, xhi);
    if (s + 1 < NSEG) bsync<10, 384>();
    xload(sb, u, j, s + 1, tmx);
    if (s == NSEG - 2 && gl) {
        if (!GP) g_wait(xlo + XO_TK + 128, xhi);
        g_load(sb, u, h * 4 + j, 0, xlo, xhi, tmb);
        if (GP == 0 || GP == 3) g_load(sb, u, h * 4 + j, 1, xlo, xhi, tmb);
    }
    asm volatile("cp.async.bulk.wait_group 0;" ::: "memory");
    if (s + 1 < NSEG) mbar_wait(bq + BAR_KV, (s + 1) & 1);
    asm volatile("lop3.b32 %0, %0, %1, %2, 0x78;" : "+r"(l16) : "r"(old), "r"(zero));
    PT(15);
}
DEVI void tickets_done(uint32_t* tk) {
    if (atomicInc(tk + 2, gridDim.x / 2 - 64) == gridDim.x / 2 - 64) { tk[0] = 0; tk[1] = 0; }
}

__global__ void __cluster_dims__(2, 1, 1) __launch_bounds__(384, 1)
chain_kernel(const __grid_constant__ CUtensorMap tmq, const __grid_constant__ CUtensorMap tmk,
             const __grid_constant__ CUtensorMap tmv, const __grid_constant__ CUtensorMap tmo,
             const __grid_constant__ CUtensorMap tmx, const __grid_constant__ CUtensorMap tmb, const __grid_constant__ CUtensorMap tmy,
             const bf16* __restrict__ mem0, const bf16* __restrict__ xg,
             uint32_t xlo, uint32_t xhi, uint32_t zero, int nseg, bf16* __restrict__ out) {
    extern __shared__ __align__(1024) uint8_t smem[];
    const uint32_t tstart = clk();
    const uint32_t rk = smem_u32(smem) & 0x1000000;
    if (rk == 0 && (threadIdx.x & 31) == 0 && threadIdx.x - 32 < 32 * PW)
        sts32(SB0 + SM_ROLE + 4 + (threadIdx.x >> 3), probe(xlo + XO_PB + (threadIdx.x & 32) * 128 + (threadIdx.x & 64) * 256 + blockIdx.x * 16, xhi));
    __syncwarp();
    if ((smem_u32(smem) & 0xFFFFFF) != SB0) die(1 << 23);
    asm volatile("griddepcontrol.launch_dependents;" ::: "memory");
    const uint32_t w = __reduce_max_sync(0xFFFFFFFFu, threadIdx.x >> 5);
    const uint32_t sb = __reduce_max_sync(0xFFFFFFFFu, smem_u32(smem));
    const uint32_t bq = sb + SM_BAR;
    uint32_t l16 = __shfl_sync(0xFFFFFFFFu, (threadIdx.x & 31) * 16, threadIdx.x & 31);
    if (threadIdx.x == 0) {
        mbar_init(bq, 1);
        for (int i = 0; i < 24; i++) mbar_init(bq + BAR_WF + i * 8, i < 16 ? 1 : 8);
        mbar_init(bq + BAR_XA, 4); mbar_init(bq + BAR_KV, 4); mbar_init(bq + BAR_PI, 2); mbar_init(bq + BAR_PI + 8, 2);
        for (int i = 0; i < 14; i++) mbar_init(bq + BAR_GF + i * 8, i < 8 || i == 13 ? 1 : 8);
        mbar_expect(bq + BAR_GX + 8, 32768);
        mbar_init(bq + BAR_RO, 1);
        mbar_expect(bq + BAR_RO, 4);
        mbar_expect(bq + BAR_PI, 6144);
        mbar_expect(bq + BAR_PI, 6144);
        asm volatile("fence.mbarrier_init.release.cluster;" ::: "memory");
        asm volatile("fence.proxy.async.shared::cta;" ::: "memory");
    }
    __syncwarp();
    asm volatile("barrier.cluster.arrive.relaxed.aligned;" ::: "memory");
    if (w == 9) {
#pragma unroll 1
        for (int e = 0; e < 12; e++) sts128(sb + SM_WO + e * 512 + l16, 0, 0, 0, 0);
    }
    if (w == 8 && blockIdx.x < 128) {
        if (XPF && elect()) {
            asm volatile("cp.async.bulk.prefetch.L2.global [%0], 3072;" ::"l"((const char*)xg + blockIdx.x * 3072) : "memory");
            asm volatile("prefetch.tensormap [%0];\nprefetch.tensormap [%1];\nprefetch.tensormap [%2];\nprefetch.tensormap [%3];\nprefetch.tensormap [%4];"
                         ::"l"(&tmq), "l"(&tmx), "l"(&tmk), "l"(&tmv), "l"(&tmo) : "memory");
        }
#pragma unroll 1
        for (int i = 0; i < EPF; i++) {
            if (i) delay_until(clk(), EPD);
            if (elect())
                asm volatile("cp.async.bulk.prefetch.tensor.3d.L2.global [%0, {0, %1, %2}];" ::"l"(&tmq), "r"((blockIdx.x & 3) * 256 + i * 64), "r"((blockIdx.x >> 2) * 2) : "memory");
        }
    }
    if (rk == 0 && w <= PW) bsync<2, 32 * PW + 32>();
    asm volatile("barrier.cluster.wait.aligned;" ::: "memory");
    if (rk == 0 && threadIdx.x == 0) {
        uint32_t t1 = lds32(sb + SM_ROLE + 8), t0 = lds32(sb + SM_ROLE + 12);
        if (PW == 4) { t1 = min(t1, lds32(sb + SM_ROLE + 16)); t0 = min(t0, lds32(sb + SM_ROLE + 20)); }
        uint32_t side = (t0 < t1 ? 0u : 1u) ^ par(XO_PB);
        uint32_t* tk = (uint32_t*)(((uint64_t)xhi << 32) | (xlo + XO_TK));
        uint32_t t = atomicAdd(tk + side, 1u);
        if (t >= 32) {
            uint2 c;
            int it = 0;
            do {
                c = ldg2<XO_TK>(xlo, xhi);
                if (++it > SPIN_LIMIT) die(it);
            } while (c.x + c.y != gridDim.x / 2);
            t += (side ? c.x : c.y) - 32;
            side ^= 1;
            if (t >= 32) tickets_done(tk);
        }
#pragma unroll
        for (uint32_t r = 0; r < 2; r++)
            asm volatile("st.async.weak.shared::cluster.mbarrier::complete_tx::bytes.b32 [%0], %1, [%2];"
                         ::"r"(sb + SM_ROLE + (r << 24)), "r"(t * 4 + side * 2 + r), "r"(bq + BAR_RO + (r << 24)) : "memory");
    }
    __syncwarp();
    mbar_wait(bq + BAR_RO, 0);
    const uint32_t role = __reduce_max_sync(0xFFFFFFFFu, lds32(sb + SM_ROLE));
    if (role >= 128) return;
    const uint32_t h = role >> 2, j = role & 3;
    if (FTM && w == 11 && elect())
#pragma unroll
        for (uint32_t c = 0; c < FTM; c++) {
            mbar_expect(bq + BAR_WF + c * 8, 16384);
            tma3d(sb + SM_ST + c * 16384, &tmq, bq + BAR_WF + c * 8, 0, j * 256 + c * 64, h * 2);
        }

    if (w >= 8) {
        asm volatile("setmaxnreg.dec.sync.aligned.u32 24;");
        const uint32_t u = w - 8;
        if (u == 3) {
#pragma unroll 1
            for (uint32_t c = FTM; c < 16; c++) {
                if (c >= WIN) mbar_wait(bq + BAR_WF + (c - WIN) * 8, 0);
                if (l16 == 0) PG(16 + c);
                if (c == 12 + WOP) bsync<2, 64>();
                if (c >= 4 && c < 12 && c != 10) mbar_wait(bq + BAR_WE + (c - 4) * 8, 0);
                if (elect()) {
                    const uint32_t b = bq + BAR_WF + c * 8;
                    mbar_expect(b, 16384);
                    if (c >= 12) tma2d(sb + SM_WO + (c - 12) * WO_BOX, &tmo, b, j * 256 + (c - 12) * 64, h * 128);
                    else tma3d(c == 10 ? sb + SM_WV : sb + SM_ST + (c & 3) * 16384, c < 4 ? &tmq : c < 8 ? &tmk : &tmv, b, 0, j * 256 + ((c ^ (c >= 10)) & 3) * 64, h * 2);
                }
            }
#pragma unroll 1
            for (uint32_t c = 16 - WIN; c < 16; c++) mbar_wait(bq + BAR_WF + c * 8, 0);
            if (l16 == 0) PG(15);
        } else if (u == 0) {
            if (elect()) {
                mbar_expect(bq, 49152);
#pragma unroll 1
                for (uint32_t i = 0; i < 12; i++)
                    tma3d(sb + SM_X + (i < 4 ? i : i + 4) * 4096, &tmx, bq, 0, i < 8 ? i * 8 : (j ^ ((0xBD98u >> (i - 8) * 4) & 15)) * 8, j * 4);
            }
#pragma unroll 1
            for (int i = 0; i < 4; i++) xload(sb, i, j, -1, &tmx);
            bsync<3, 320>();
            if (l16 == 0) PG(32);
            if (GH && j == 0 && elect()) asm volatile("{\n.reg .b64 a;\nmov.b64 a, {%0,%1};\nred.relaxed.gpu.global.inc.u32 [a+64], 4;\n}" ::"r"(xlo + XO_FL + h * 128), "r"(xhi) : "memory");
            __syncwarp();
            g_arrive(xlo + XO_FL + h * 128, xhi, 4);
            if (WOP < 4) barv<2, 64>();
            if (l16 == 0) PG(33);
            g_wait(xlo + XO_FL + h * 128, xhi);
            if (l16 == 0) PG(34);
#pragma unroll 1
            for (int i = 0; i < 4; i++)
                if (elect()) kvload(sb, i, h, j, 0, xlo, xhi);
            mbar_wait(bq + BAR_KV, 0);
            if (l16 == 0) PG(14);
        } else if (u == 1) {
            const uint32_t l = l16 >> 4, x = h * 8 + (l >> 2), d = (x & ~31u) + (l & 3) * 8 + ((x & 31) >> 2) + (x & 3) * 2 * DM;
            const unsigned short* m0 = (const unsigned short*)mem0 + j * 256;
            const uint32_t v1 = m0[d] | (((l & 3) == 3 ? 0x4200u : m0[d + DM]) << 16);
            const uint32_t v3 = h < 8 ? m0[h * 32 + 24 + (l >> 2) + ((l & 3) * 2 + 1) * DM] | 0x42000000u : 0;
#pragma unroll 1
            for (uint32_t i = 0; i < 12; i++) {
                if (i == 10) { sts32(sb + SM_WO + 6144 + l * 4, v1); sts32(sb + SM_WO + 6272 + l * 4, v3); }
                asm volatile("fence.proxy.async.shared::cta;" ::: "memory");
                __syncwarp();
                const uint32_t c = (0x21924u >> ((i - 3) * 2)) & 3;
                if (elect()) {
                    if (i < 3) bulk_s2g(xlo + XO_XG + (i * 128 + role) * 6144, xhi, sb + SM_WO, 6144);
                    else bulk_s2g(xlo + XO_R + rpage(j, i < 6 ? 0 : i < 9 ? 1 : -1) + c * 16384 + h * 128, xhi, sb + SM_WO + (i < 10 ? 0 : 6144 + c * 64), 128);
                }
            }
            asm volatile("cp.async.bulk.wait_group 0;" ::: "memory");
            if (elect()) asm volatile("{\n.reg .b64 a;\nmov.b64 a, {%0,%1};\nred.relaxed.gpu.global.inc.u32 [a], 127;\n}" ::"r"(xlo + XO_TK + 12), "r"(xhi) : "memory");
            if (l16 == 0) PG(16);
            g_wait(xlo + XO_TK + 12, xhi);
            if (l16 == 0) PG(17);
            barv<5, 288>();
            bsync<8, 320>();
            asm volatile("fence.acq_rel.gpu;" ::: "memory");
        } else {
            GSYNC(0);
            mbar_wait(bq + BAR_WE + 48, 0);
#pragma unroll 1
            for (int e = 0; e < 24; e++) sts128(sb + SM_TR + 4096 + e * 512 + l16, 0, 0, 0, 0);
            barv<3, 320>();
            bsync<8, 320>();
#pragma unroll 1
            for (int i = 0; i < 4; i++) xload(sb, i, j, 0, &tmx);
        }
#pragma unroll 1
        for (int s = 0; s < nseg; s++) helper_step(sb, w, h, j, l16, xlo, xhi, zero, s, &tmx, &tmb);
        piwait(sb, 0, nseg - 2);
        bsync<9, 384>();
        GSYNC(1);
        if (!GS && w == 11 && elect()) asm volatile("prefetch.tensormap [%0];" ::"l"(&tmy) : "memory");
        if (GH && w == 10) { g_arrive(xlo + XO_FL + h * 128 + 64, xhi, 5); PG(2); }
        if (w < 10) {
            uint32_t kb = 2, heads = 0;
            asm volatile("fence.proxy.async.shared::cta;" ::: "memory");
            if (GH) {
                if (w == 9 && h >= 30) { kb = 0; heads = 0xFFFF; }
                else delay_until(clk(), GD);
            } else if (w == 9) {
                g_arrive(xlo + XO_TK + 192, xhi, 128);
                PG(2);
                if (h >= 30) { g_wait(xlo + XO_TK + 192, xhi); kb = 0; }
                PG(3);
            } else delay_until(clk(), GD);
#pragma unroll 1
            for (; kb < 32; kb++) {
                if (kb >= 4) mbar_wait(bq + BAR_GE + (kb & 3) * 8, ((kb >> 2) & 1) ^ 1);
                if (GH && ((heads >> (kb >> 1)) & 1)) {
                    int it = 0;
                    do {
                        uint32_t v;
                        asm volatile("{\n.reg .b64 a;\nmov.b64 a, {%1,%2};\nld.acquire.gpu.global.u32 %0, [a+64];\n}"
                                     : "=r"(v) : "r"(xlo + XO_FL + (role & 1) * 2048 + (l16 & 255) * 8), "r"(xhi) : "memory");
                        heads = __ballot_sync(0xFFFFFFFFu, v != 0);
                        if (++it > SPIN_LIMIT) die(it);
                    } while ((heads >> (kb >> 1)) & 1);
                    asm volatile("fence.proxy.async.global;" ::: "memory");
                    if (kb == 0) PG(3);
                }
                g_load(sb, w - 8, role, kb, xlo, xhi, &tmb);
            }
        }
        if (role == 0 && w == 11 && elect()) tickets_done((uint32_t*)(((uint64_t)xhi << 32) | (xlo + XO_TK)));
    } else {
        asm volatile("setmaxnreg.inc.sync.aligned.u32 240;");
        uint32_t Wq[16][4], Wk[16][4], Wv[NA][4];
        uint32_t t16, KA, KB, KC, KD;
        {
            const uint32_t lane = l16 >> 4, g = lane >> 2, t = lane & 3;
            const uint32_t rw = (((lane >> 4) & 1) * 8 + (lane & 7)) * 128u;
            const uint32_t off = rw + ((((w & 3) * 2 + ((lane >> 3) & 1)) ^ (lane & 7)) << 4);
            const uint32_t offo = rw + ((((w & 1) * 4 + ((lane >> 3) & 1)) ^ (lane & 7)) << 4);
            const uint32_t r = 2 * (t & 1) + (g >> 2);
            const uint32_t mk0 = t < 2 ? 0 : (r == 0 ? 2 * g > w : j + r < 4), mk1 = t < 2 ? 0 : (r == 0 ? 2 * g + 1 > w : j + r < 4);
            t16 = __shfl_sync(0xFFFFFFFFu, w * 512 + l16, lane);
            KA = __shfl_sync(0xFFFFFFFFu, (w * 512 + t * 64 + g * 8) | ((w * 512 + (g & 1) * 256 + (g >> 1) * 64 + t * 16) << 16), lane);
            KB = __shfl_sync(0xFFFFFFFFu, ((w >> 2) * WV_BOX + off) | mk0 | (mk1 << 1) |
                                              ((w * 256 + (g >> 2) * 4096 + (g & 3) * 64 + t * 16) << 16), lane);
            KC = __shfl_sync(0xFFFFFFFFu, ((lane & 7) * 1280 + (lane >> 3) * 128 + ((w ^ (lane & 7)) << 4)) | (((t >> 1) * 16 + g * 2) << 16) | ((t * 64 + g * 8) << 24), lane);
            KD = __shfl_sync(0xFFFFFFFFu, ((w >> 1) * WO_BOX + offo) | (((lane & 7) * 208 + (lane >> 3) * 16) << 16), lane);
            if (threadIdx.x == 0) PG(8);
#define WTAKE(W, c, k0) { mbar_wait(bq + BAR_WF + (c) * 8, 0); \
                _Pragma("unroll") for (int ks = 0; ks < 4; ks++) ldsm4t(W[(k0) + ks], sb + SM_ST + ((c) & 3) * 16384 + (KB & 0xFFF0) + ks * 2048); \
                if ((c) < 8) { __syncwarp(); if (elect()) mbar_arrive(bq + BAR_WE + (c) * 8); } }
#pragma unroll
            for (int c = 0; c < 4; c++) WTAKE(Wq, c, c * 4);
            mbar_wait(bq, 0);
            if (threadIdx.x == 0) PG(9);
            xstart<0>(sb, w, xlo + h * 24576, xhi, j, t16, KA, Wq);
            if (threadIdx.x == 0) PG(10);
#pragma unroll
            for (int c = 0; c < 4; c++) WTAKE(Wk, c + 4, c * 4);
            if (threadIdx.x == 0) PG(11);
            xstart<1>(sb, w, xlo + h * 24576, xhi, j, t16, KA, Wk);
            if (threadIdx.x == 0) PG(12);
            WTAKE(Wv, 8, 0);
            WTAKE(Wv, 9, 4);
            mbar_wait(bq + BAR_WF + 80, 0);
            WTAKE(Wv, 11, 8);
            if (threadIdx.x == 0) PG(13);
            xstart<2>(sb, w, xlo + h * 24576, xhi, j, t16, KA, Wv);
            mbar_wait(bq + BAR_XA, 0);
            bsync<8, 320>();
        }
        const uint32_t ONES = 0x3F803F80u;
#define UNI(x) __reduce_max_sync(0xFFFFFFFFu, x)
        uint32_t swi = UNI((uint32_t)((uint64_t)smem >> 32));
        const uint32_t sbw = UNI(sb + w * 256), sbm = UNI(sb - w * 512), sbs = UNI(sb + w * 768), sbp = UNI(sb + w * 208);
#define OPQALL() { OPQ(t16); OPQ(KA); OPQ(KB); OPQ(KC); OPQ(KD); }
        OPQALL();
        const uint32_t cb0 = (h >> 1) * 32768 + (j & 1) * 16384 + (h & 1) * 8192;
        const uint32_t cb = UNI(xlo + cb0 + ((par(cb0) ^ (j >> 1) ^ CFAR) << 12)), cv = UNI(xlo + h * 8192 + JV(h, j) * 2048), h1 = UNI((h & 1) * 1024);
        const uint32_t uox = UNI(xlo + XO_OX + (h * 2 + (w >> 2)) * 262144 + j * 1024 + (w & 3) * 256 - w * 128);
        uint32_t rp = UNI(xlo + rpage(j, 0));
        float ox[4];
        float4 dn;
#define OXSTORE(s) asm volatile("{\n.reg .b64 a;\nmov.b64 a, {%0,%1};\nst.global.u32 [a], %2;\nst.global.u32 [a+128], %3;\n}" \
                                ::"r"(uox + (s) * 4096 + (t16 >> 2)), "r"(xhi), \
                                  "r"(pack2(ox[0] * dn.y, ox[1] * dn.w)), "r"(pack2(ox[2] * dn.y, ox[3] * dn.w)) : "memory")
#pragma unroll 1
        for (int s2 = 0;; s2 += 2, rp ^= 0x21000)
#pragma unroll
        for (int p = 0; p < 2; p++) {
            const int s = s2 + p;
            const uint32_t ctag = ((s2 >> 1) & 1) ^ 1;
            const uint32_t hb = cb ^ (p * 0x81000), rb = rp ^ (p * 0x11000);
            uint4 k0, k1, qq, c0, c1, c2, c3, pk;
            float va[4], vb[4];
            uint32_t qx0, qx1, ov0, ov1;
            {
                float xa[16], xb[16];
                uint4 m0, n0;
                uint32_t e0, f0;
                uint32_t xp[8];
                wg_fence();
                XMMA(0, 6);
                SF();
                piwait(sb, p, s - 2);
                uint4 pi = xpeer<0>(sb, p ^ 1, t16);
                SF();
#define MR (VC ? 1 : 2)
#define MC (VC ? 2 : 1)
#define QPARK() { xpack<0>(xp, xa); xpark<0>(xp, pi, sb, sbw, p ^ 1, t16, KA); pi = xpeer<MR>(sb, p ^ 1, t16); SF(); }
                wg_fence();
                if (QP) {
                    XMMA(6, QP);
                    XMMA(QP, QP + 4);
                    wg_wait<1>();
                    SF();
                    QPARK();
                    wg_fence();
                    if (QP + 4 < RPOS) XMMA(QP + 4, RPOS);
                } else XMMA(6, RPOS);
                if (RPOS < 32) XMMA(RPOS, RPOS + 4 < 32 ? RPOS + 4 : 32);
                uint32_t a = (p ? rp : rp ^ 0x30000) + t16, e = (p ? rp : rp ^ 0x30000) + (t16 >> 2), ah = xhi, eh = xhi;
                OPQ(a); OPQ(e); OPQ(ah); OPQ(eh);
                SF();
                wg_wait<(RPOS < 32)>();
                SF();
                PT(11);
                RLOAD();
                SF();
                if (!QP) QPARK();
                if (RPOS + 4 < 32) {
                    wg_fence();
                    XMMA(RPOS + 4, 32);
                    SF();
                }
                wg_wait<0>();
                xpack<MR>(xp, xb);
                xpark<MR>(xp, pi, sb, sbw, p ^ 1, t16, KA);
                SF();
                PT(12);
                {
                    int it = 0;
                    while (ruse(sb + SM_MEMT + t16, m0, n0, e0, f0)) {
                        RLOAD();
                        if (++it > SPIN_LIMIT) die(it);
                    }
                    PC(22, it + 1);
                }
                PT(13);
                OPQ(KA); OPQ(t16);
                uint32_t acw = hb + (KA & 0xFFFF), ahi = xhi, tg = ctag;
                OPQ(acw); OPQ(ahi); OPQ(tg);
                SF();
                bsync<1, 384>();
                PT(0);
                uint32_t b[8][4];
#pragma unroll
                for (int i = 0; i < 8; i++) {
                    const int pp = i < 2 ? i : i ^ 1;
                    ldsm4t(b[pp], sbm + SM_MEMT + t16 + pp * 512);
                    if (i < 7) MF();
                }
                if (ASF) SF();
                float q[4], k[4];
                const uint32_t aWv = sb + SM_WV + (KB & 0xFFF0);
                uint32_t wv[16 - NA > 0 ? 16 - NA : 1][4];
#define WVLD(n0, n1) _Pragma("unroll") for (int n = (n0); n < (n1) && n < 16 - NA; n++) ldsm4t(wv[n], aWv + n * 2048)
#pragma unroll
                for (int ks = 0; ks < 16; ks++) {
                    const uint32_t b0 = b[ks >> 1][(ks & 1) * 2], b1 = b[ks >> 1][(ks & 1) * 2 + 1];
                    if (ks == 0) {
                        mma16z(q, Wq[0][0], Wq[0][1], Wq[0][2], Wq[0][3], b0, b1);
                        mma16z(k, Wk[0][0], Wk[0][1], Wk[0][2], Wk[0][3], b0, b1);
                    } else {
                        mma16(q, Wq[ks][0], Wq[ks][1], Wq[ks][2], Wq[ks][3], b0, b1);
                        mma16(k, Wk[ks][0], Wk[ks][1], Wk[ks][2], Wk[ks][3], b0, b1);
                    }
                    if (ks == 10 && VPF) { SF(); WVLD(0, VPF); }
                }
                const uint32_t oq0 = settag(pack2(q[0], q[2]), tg), oq1 = settag(pack2(q[1], q[3]), tg);
                const uint32_t ok0 = pack2(k[0], k[2]), ok1 = pack2(k[1], k[3]);
                stg2<XO_CQK>(acw, ahi, oq0, ok0);
                stg2<XO_CQK + 256>(acw, ahi, oq1, ok1);
                SF();
                PT(1);
#define CLOADG() { c2 = ldg4<XO_CQK>((hb ^ 0x1000) + (KA >> 16), xhi); c3 = ldg4<XO_CQK>((hb ^ 0x5000) + (KA >> 16), xhi); }
#define CLOAD0() c0 = lds128(sb + SM_TR + (KA >> 16))
#define CLOAD1() c1 = lds128(sb + SM_TR + 4096 + p * 4096 + (KA >> 16))
#define CLOADS() { CLOAD0(); CLOAD1(); }
#define CSIDE(n) { if (CGP == (n)) CLOADG(); if (C0P == (n)) CLOAD0(); if (C1P == (n)) CLOAD1(); if (PIP == (n)) pk = xpeer<MC>(sb, p ^ 1, t16); \
                   if (QSP == (n)) { qx0 = (t16 & 64) ? qq.y : qq.x; qx1 = (t16 & 64) ? qq.w : qq.z; } }
#pragma unroll
                for (int rd = 0; rd < 8; rd++) {
                    const int pp = (VORD >> (28 - 4 * rd)) & 7;
                    const uint32_t* a = 2 * pp < NA ? Wv[2 * pp < NA ? 2 * pp : 0] : wv[2 * pp < NA ? 0 : 2 * pp - NA];
                    const uint32_t* c = 2 * pp < NA ? Wv[2 * pp < NA ? 2 * pp + 1 : 0] : wv[2 * pp < NA ? 0 : 2 * pp + 1 - NA];
                    if (rd == 0) {
                        mma16z(va, a[0], a[1], a[2], a[3], b[pp][0], b[pp][1]);
                        mma16z(vb, c[0], c[1], c[2], c[3], b[pp][2], b[pp][3]);
                        if (VSB & 256) SF();
                        OPQ(swi);
                        asm volatile("{\n.reg .b64 a;\nmov.b64 a, {%0,%1};\nst.v2.u32 [a], {%2,%3};\nst.v2.u32 [a+256], {%4,%5};\n}"
                                     ::"r"((KA & 0xFFF) + (sb ^ 0x1000000) + SM_TR + 4096 + p * 4096), "r"(swi), "r"(oq0), "r"(ok0), "r"(oq1), "r"(ok1) : "memory");
                        sts64(sb + SM_TR + (KA & 0xFFF), oq0, ok0);
                        sts64(sb + SM_TR + (KA & 0xFFF) + 256, oq1, ok1);
                    } else {
                        mma16(va, a[0], a[1], a[2], a[3], b[pp][0], b[pp][1]);
                        mma16(vb, c[0], c[1], c[2], c[3], b[pp][2], b[pp][3]);
                    }
                    if (rd == KEP) { KEEP(t16, oq0, oq1, ok0, ok1); if (KE2) KEEP(t16, acw, ahi, acw, ahi); }
                    if ((VSB >> rd) & 1) SF();
                    if (rd == W2P) WVLD(2, 3);
                    if (rd == W3P) WVLD(3, 4);
                    if (rd == K0P) k0 = lds128(sb + SM_KV + 2048 + (KB >> 16));
                    if (rd == K0P + 1) k1 = lds128(sb + SM_KV + 10240 + (KB >> 16));
                    if (rd == QQP) qq = lds128(sbw + SM_KV + ((KA >> 16) & 0xFF));
                    CSIDE(rd);
                    if ((VSF >> rd) & 1) SF(); else if ((VMF >> rd) & 1) MF();
                }
#define VTAIL() { ov0 = pack2(va[0] + vb[0], va[1] + vb[1]); ov1 = pack2(va[2] + vb[2], va[3] + vb[3]); \
                  stg2<XO_CV>(cv + p * 262144 + (t16 >> 1), xhi, settag(ov0, ctag), ov1); \
                  if (VD) asm volatile("{\n.reg .b64 a;\nmov.b64 a, {%0,%1};\nst.v2.u32 [a], {%2,%3};\n}" \
                                     ::"r"((t16 >> 1) + (sb ^ 0x1000000) + SM_VP + p * 2048), "r"(swi), "r"(settag(ov0, ctag)), "r"(ov1) : "memory"); \
                  barv<8, 384>(); OPQ(t16); SF(); }
                if (!VTP) VTAIL();
            }
            PT(2);
            PDUMP();
            {
                const uint32_t a0 = sb + SM_KV;
                float xa[16], xb[16];
                uint32_t xp[8];
                wg_fence();
                XMMA(32, 32 + CPOS);
                if (CW) { XMMA(32 + CPOS, 36 + CPOS); wg_wait<1>(); }
                SF();
                CSIDE(8);
                SF();
                if (VTP) VTAIL();
                CSIDE(9);
                SF();
                wg_fence();
                XMMA(32 + CPOS + (CW ? 4 : 0), 48);
                SF();
                uint2 u1, u2, u3;
#define ULOADG() { u2 = ldg2<XO_CV>((cv ^ 4096) + p * 262144 + (t16 >> 1), xhi); u3 = ldg2<XO_CV>((cv ^ 6144) + p * 262144 + (t16 >> 1), xhi); }
#define ULOADS() u1 = lds64(sb + SM_VP + p * 2048 + (t16 >> 1))
#define UCHECK() { int it = 0; \
                   while (__builtin_expect(any_bad(tagx1(tagx2(u2.x, u3.x, ctag), u1.x, ctag)), 0)) { OPQ(t16); ULOADG(); ULOADS(); if (++it > SPIN_LIMIT) die(it); } \
                   PC(26, it); }
                CSIDE(10);
                if (B3 == 8 && VLP == 2) ULOADG();
                SF();
                const uint32_t ka[4] = {k0.x, k0.y, k0.z, k0.w}, kb[4] = {k1.x, k1.y, k1.z, k1.w};
                const uint32_t aSp = sb + SM_SP + (KC & 0xFFFF);
                PT(3);
#define BAR3() asm volatile("{\n.reg .pred p;\nsetp.eq.u32 p, %0, 0;\n@p bar.arrive 3, %1;\n}" ::"r"((uint32_t)bad), "n"(B3 == 6 ? 288 : 384) : "memory")
#define SCORES(FIRST) { \
                    const uint32_t qA = hadd2(hadd2(c0.x, c1.x), hadd2(c2.x, c3.x)), qB = hadd2(hadd2(c0.z, c1.z), hadd2(c2.z, c3.z)); \
                    const uint32_t kA = hadd2(hadd2(c0.y, c1.y), hadd2(c2.y, c3.y)), kB = hadd2(hadd2(c0.w, c1.w), hadd2(c2.w, c3.w)); \
                    bad = any_bad(or3(tagx2(c1.x, c1.z, ctag), tagx2(c2.x, c2.z, ctag), tagx2(c3.x, c3.z, ctag))); \
                    float sa[4], sb_[4], sc[4], sd[4], se[4]; \
                    if (FIRST) { SF(); if (B3 == 8 && VLP == 3) ULOADG(); wg_wait<0>(); } \
                    mma16z(sa, ka[0], ka[1], ka[2], ka[3], qA, qB); \
                    mma16z(sb_, kb[0], kb[1], kb[2], kb[3], qA, qB); \
                    mma16z(sc, qA, qx0, qB, qx1, kA, kB); \
                    if (FIRST) { \
                        xpack<MC>(xp, xa); \
                        if (KPOS == 0) { xadd(xp, pk); xstore<MC>(xp, sb, sbw, p ^ 1, t16, KA); if (B3 >= 5) BAR3(); else if (!B3 || B3 >= 3) barv<3, 384>(); } \
                        mma16z(sd, ka[0], ka[1], ka[2], ka[3], qx0, qx1); \
                        mma16z(se, kb[0], kb[1], kb[2], kb[3], qx0, qx1); \
                    } \
                    stsm4t(aSp, pack2(sa[0], sa[1]), pack2(sa[2], sa[3]), pack2(sb_[0], sb_[1]), pack2(sb_[2], sb_[3])); \
                    stsm2(aSp + 1024, pack2(sc[0], sc[1]), pack2(sc[2], sc[3])); \
                    if (FIRST) { \
                        stsm4t(aSp + 512, pack2(sd[0], sd[1]), pack2(sd[2], sd[3]), pack2(se[0], se[1]), pack2(se[2], se[3])); \
                        if (KPOS == 0) { KEEP(KD, xp[0], xp[1], xp[2], xp[3]); KEEP(KD, xp[4], xp[5], xp[6], xp[7]); } \
                    } }
                int it = 0;
                bool bad;
                SCORES(true);
                while (__builtin_expect(bad, 0)) {
                    OPQ(KA);
                    CLOADG();
                    CLOADS();
                    SCORES(false);
                    if (B3 >= 5) BAR3();
                    if (++it > SPIN_LIMIT) die(it);
                }
                PC(25, it);
                PT(4);
                if (B3 == 8 && VLP == 0) ULOADG();
                if (B3 == 1) barv<3, 384>();
                bsync<4, B3 == 2 ? 384 : 256>();
                uint32_t wo[16][4];
                const uint32_t aWo = sb + SM_WO + (KD & 0xFFFF), aWo1 = sb + SM_WO + ((KD & 0xFFFF) ^ 32);
#define WOLD(n0, n1) _Pragma("unroll") for (int n = (n0); n < (n1) && n < 16; n++) ldsm4t(wo[n], ((n & 1) ? aWo1 : aWo) + (n >> 1) * 2048)
                const bool hi = (t16 & 32) != 0;
                const uint32_t t8 = t16 >> 1;
                uint2 v0, v1, v2, v3;
                uint32_t es;
                {
                    uint32_t am[4], ax[4], a4[2];
                    const uint32_t aSr = sbs + SM_SP + t16;
                    ldsm4t(am, aSr);
                    ldsm4t(ax, aSr + 512);
                    ldsm2t(a4, aSr + 1024);
                    MF();
                    if (B3 == 8 && VLP == 1) ULOADG();
                    if (KPOS == 1) pk = xpeer<MC>(sb, p ^ 1, t16);
                    const uint32_t se = (t16 & 128) ? 0u : ONES, so = se ^ ONES;
                    float hm[4], hx[4], h4[4];
                    mma16z(hm, am[0], am[1], am[2], am[3], se, so);
                    mma16z(hx, ax[0], ax[1], ax[2], ax[3], se, so);
                    mma8z(h4, a4[0], a4[1], ONES);
                    SF();
                    if (KPOS == 1) { xpark<MC>(xp, pk, sb, sbw, p ^ 1, t16, KA); barv<3, 384>(); }
                    v0 = lds64(a0 + 4096 + t8); v1 = lds64(a0 + 8192 + t8); v2 = lds64(a0 + 12288 + t8); v3 = lds64(a0 + 16384 + t8);
                    if (B3 == 8) ULOADS();
                    WOLD(0, PF2);
                    float s0 = hi ? hx[0] : hm[0], s1 = hi ? hx[2] : hm[2];
                    const float s2 = hi ? h4[2] : h4[0];
                    s0 = (KB & 1) ? -1.0e9f * 11.313708499f : s0;
                    s1 = (KB & 2) ? -1.0e9f * 11.313708499f : s1;
                    int mi = __float_as_int(fmaxf(fmaxf(s0, s2), s1));
                    mi ^= (mi >> 31) & 0x7FFFFFFF;
                    const int mm = __reduce_max_sync(0xFFFFFFFFu, hi ? (int)0x80000000 : mi), mx = __reduce_max_sync(0xFFFFFFFFu, hi ? mi : (int)0x80000000);
                    SF();
                    WOLD(PF2, PF3);
                    SF();
                    mi = hi ? mx : mm;
                    mi ^= (mi >> 31) & 0x7FFFFFFF;
                    const float c2_ = 0.08838834764831845f * 1.4426950408889634f;
                    const float mc = __int_as_float(mi) * c2_;
                    const float e0 = ex2(fmaf(s0, c2_, -mc)), e1 = ex2(fmaf(s1, c2_, -mc)), e2 = ex2(fmaf(s2, c2_, -mc));
                    sts32(sbp + SM_P + (KC >> 25), pack2(e0, e1));
                    sts16(sbp + SM_P + 128 + ((KC >> 16) & 0xFF), pack2(e2, e2));
                    es = __float_as_uint(fmaf(e2, 0.5f, e0 + e1) + 64.f);
                }
                const uint32_t sm = __reduce_add_sync(0xFFFFFFFFu, hi ? 0u : es), sx = __reduce_add_sync(0xFFFFFFFFu, hi ? es : 0u);
                const uint32_t aPr = sb + SM_P + (KD >> 16);
                if (B3 == 8 && VCP == 0) UCHECK();
                PT(5);
                bsync<5, B3 == 6 ? 352 : 384>();
                uint32_t pm[4], px[4], p4[2];
                ldsm4(pm, aPr);
                MF();
                uint2 vs;
                if (B3 != 8) { vs = lds64(sb + SM_VS + t8); MF(); }
                ldsm2(p4, aPr + 128);
                MF();
                ldsm4(px, aPr + 64);
                MF();
                sts32f(sb + SM_DN + w * 8 + ((t16 >> 3) & 4), rcp(__uint_as_float((hi ? sx : sm) - 15u * 0x42800000u) - 64.f));
                MF();
                if (B3 == 8 && VCP == 2) UCHECK();
                WOLD(PF3, NPF);
                if (B3 == 8 && VCP == 1) UCHECK();
                if (B3 == 8) { ov0 = hadd2(ov0, u1.x); ov1 = hadd2(ov1, u1.y); vs.x = hadd2(u2.x, u3.x); vs.y = hadd2(u2.y, u3.y); }
                const uint32_t vm0 = hadd2(ov0, vs.x), vm1 = hadd2(ov1, vs.y);
                float oa[4], ob[4];
                mma16z(oa, v0.x, v0.y, v1.x, v1.y, pm[0], pm[1]);
                mma16z(ob, v2.x, v2.y, v3.x, v3.y, pm[2], pm[3]);
                mma8(oa, vm0, vm1, p4[0]);
                stsm2(sbw + SM_OT + (t16 & 511), pack2(oa[0] + ob[0], oa[1] + ob[1]), pack2(oa[2] + ob[2], oa[3] + ob[3]));
                PT(6);
                SF();
                bsync<6, 256>();
                mma16z(ox, v0.x, v0.y, v1.x, v1.y, px[0], px[1]);
                uint32_t b[4][4];
#define OTLD(pp) ldsm4t(b[pp], sbm + SM_OT + t16 + (pp) * 512)
                OTLD(0);
                MF();
                OTLD(1);
                barv<7, 384>();
                mma16(ox, v2.x, v2.y, v3.x, v3.y, px[2], px[3]);
                mma8(ox, vm0, vm1, p4[1]);
                if (p == 1 && s + 1 == nseg) goto done;
                SF();
                uint32_t ar, ae, ahi = xhi;
                float r[2][4];
#pragma unroll
                for (int ks = 0; ks < 8; ks++) {
                    if (ks == 0) WOLD(NPF, NPF + WPF);
                    if (ks == OPOS) { OTLD(2); MF(); }
                    if (ks == OPOS + 2) { OTLD(3); MF(); }
                    if (ks > 0) WOLD(NPF + WPF + 2 * (ks - 1), NPF + WPF + 2 * ks);
                    if (ks == 5) {
                        OPQ(t16);
                        ar = rb + h1 * 16 + t16; ae = rb + h1 + (t16 >> 2);
                        OPQ(ar); OPQ(ahi); OPQ(ae);
                        dn = lds128f(sb + SM_DN + (t16 & 48));
                    }
#pragma unroll
                    for (int mt = 0; mt < 2; mt++) {
                        const int i = ks * 2 + mt;
                        const uint32_t* a = wo[i];
                        if (i < 2) mma16z(r[mt], a[0], a[1], a[2], a[3], b[ks >> 1][2 * (ks & 1)], b[ks >> 1][2 * (ks & 1) + 1]);
                        else mma16(r[mt], a[0], a[1], a[2], a[3], b[ks >> 1][2 * (ks & 1)], b[ks >> 1][2 * (ks & 1) + 1]);
                    }
                    if (NPF + WPF + 2 * ks < 16 || ks < 5) SF();
                }
                const float r0 = dn.x, r1 = dn.z;
                asm volatile("{\n.reg .b64 a;\nmov.b64 a, {%0,%2};\nred.relaxed.gpu.global.add.noftz.v4.bf16x2 [a], {%3,%4,%5,%6};\n"
                             "mov.b64 a, {%1,%2};\nred.relaxed.gpu.global.add.noftz.bf16x2 [a+32768], %7;\n}"
                             ::"r"(ar), "r"(ae), "r"(ahi), "r"(pack2(r[0][0] * r0, r[0][1] * r1)), "r"(pack2(r[0][2] * r0, r[0][3] * r1)),
                               "r"(pack2(r[1][0] * r0, r[1][1] * r1)), "r"(pack2(r[1][2] * r0, 1.f)), "r"(pack2(r[1][3] * r1, 1.f)) : "memory");
                barv<10, 384>();
            }
            SF();
            PT(10);
            OXSTORE(s);
            OPQALL();
        }
    done:
        dn = lds128f(sb + SM_DN + (t16 & 48));
        OXSTORE(nseg - 1);
        barv<9, 384>();
        g_main(sb, w, role, &tmy, out);
        if (threadIdx.x == 0) PG(0);
    }
}

template <int SC> DEVI void wg_rs128t(float (&d)[64], const uint32_t (&a)[4], uint64_t db) {
    if (SC) asm volatile("wgmma.mma_async.sync.aligned.m64n128k16.f32.bf16.bf16 "
        "{%0,%1,%2,%3,%4,%5,%6,%7,%8,%9,%10,%11,%12,%13,%14,%15,%16,%17,%18,%19,%20,%21,%22,%23,%24,%25,%26,%27,%28,%29,%30,%31,%32,%33,%34,%35,%36,%37,%38,%39,%40,%41,%42,%43,%44,%45,%46,%47,%48,%49,%50,%51,%52,%53,%54,%55,%56,%57,%58,%59,%60,%61,%62,%63}, "
        "{%64,%65,%66,%67}, %68, 1, 1, 1, 1;"
        : D4(+, 0), D4(+, 4), D4(+, 8), D4(+, 12), D4(+, 16), D4(+, 20), D4(+, 24), D4(+, 28), D4(+, 32), D4(+, 36), D4(+, 40), D4(+, 44), D4(+, 48), D4(+, 52), D4(+, 56), D4(+, 60) : "r"(a[0]), "r"(a[1]), "r"(a[2]), "r"(a[3]), "l"(db));
    else asm volatile("wgmma.mma_async.sync.aligned.m64n128k16.f32.bf16.bf16 "
        "{%0,%1,%2,%3,%4,%5,%6,%7,%8,%9,%10,%11,%12,%13,%14,%15,%16,%17,%18,%19,%20,%21,%22,%23,%24,%25,%26,%27,%28,%29,%30,%31,%32,%33,%34,%35,%36,%37,%38,%39,%40,%41,%42,%43,%44,%45,%46,%47,%48,%49,%50,%51,%52,%53,%54,%55,%56,%57,%58,%59,%60,%61,%62,%63}, "
        "{%64,%65,%66,%67}, %68, 0, 1, 1, 1;"
        : D4(=, 0), D4(=, 4), D4(=, 8), D4(=, 12), D4(=, 16), D4(=, 20), D4(=, 24), D4(=, 28), D4(=, 32), D4(=, 36), D4(=, 40), D4(=, 44), D4(=, 48), D4(=, 52), D4(=, 56), D4(=, 60) : "r"(a[0]), "r"(a[1]), "r"(a[2]), "r"(a[3]), "l"(db));
}
template <int SC> DEVI void wg_rs64t(float (&d)[32], const uint32_t (&a)[4], uint64_t db) {
    if (SC) asm volatile("wgmma.mma_async.sync.aligned.m64n64k16.f32.bf16.bf16 "
        "{%0,%1,%2,%3,%4,%5,%6,%7,%8,%9,%10,%11,%12,%13,%14,%15,%16,%17,%18,%19,%20,%21,%22,%23,%24,%25,%26,%27,%28,%29,%30,%31}, "
        "{%32,%33,%34,%35}, %36, 1, 1, 1, 1;"
        : D4(+, 0), D4(+, 4), D4(+, 8), D4(+, 12), D4(+, 16), D4(+, 20), D4(+, 24), D4(+, 28) : "r"(a[0]), "r"(a[1]), "r"(a[2]), "r"(a[3]), "l"(db));
    else asm volatile("wgmma.mma_async.sync.aligned.m64n64k16.f32.bf16.bf16 "
        "{%0,%1,%2,%3,%4,%5,%6,%7,%8,%9,%10,%11,%12,%13,%14,%15,%16,%17,%18,%19,%20,%21,%22,%23,%24,%25,%26,%27,%28,%29,%30,%31}, "
        "{%32,%33,%34,%35}, %36, 0, 1, 1, 1;"
        : D4(=, 0), D4(=, 4), D4(=, 8), D4(=, 12), D4(=, 16), D4(=, 20), D4(=, 24), D4(=, 28) : "r"(a[0]), "r"(a[1]), "r"(a[2]), "r"(a[3]), "l"(db));
}
template <int SC> DEVI void wg_rs40(float (&d)[20], const uint32_t (&a)[4], uint64_t db) {
    if (SC) asm volatile("wgmma.mma_async.sync.aligned.m64n40k16.f32.bf16.bf16 "
        "{%0,%1,%2,%3,%4,%5,%6,%7,%8,%9,%10,%11,%12,%13,%14,%15,%16,%17,%18,%19}, "
        "{%20,%21,%22,%23}, %24, 1, 1, 1, 0;"
        : D4(+, 0), D4(+, 4), D4(+, 8), D4(+, 12), D4(+, 16) : "r"(a[0]), "r"(a[1]), "r"(a[2]), "r"(a[3]), "l"(db));
    else asm volatile("wgmma.mma_async.sync.aligned.m64n40k16.f32.bf16.bf16 "
        "{%0,%1,%2,%3,%4,%5,%6,%7,%8,%9,%10,%11,%12,%13,%14,%15,%16,%17,%18,%19}, "
        "{%20,%21,%22,%23}, %24, 0, 1, 1, 0;"
        : D4(=, 0), D4(=, 4), D4(=, 8), D4(=, 12), D4(=, 16) : "r"(a[0]), "r"(a[1]), "r"(a[2]), "r"(a[3]), "l"(db));
}
template <int SC> DEVI void wg_rs8(float (&d)[4], const uint32_t (&a)[4], uint64_t db) {
    if (SC) asm volatile("wgmma.mma_async.sync.aligned.m64n8k16.f32.bf16.bf16 "
        "{%0,%1,%2,%3}, "
        "{%4,%5,%6,%7}, %8, 1, 1, 1, 0;"
        : D4(+, 0) : "r"(a[0]), "r"(a[1]), "r"(a[2]), "r"(a[3]), "l"(db));
    else asm volatile("wgmma.mma_async.sync.aligned.m64n8k16.f32.bf16.bf16 "
        "{%0,%1,%2,%3}, "
        "{%4,%5,%6,%7}, %8, 0, 1, 1, 0;"
        : D4(=, 0) : "r"(a[0]), "r"(a[1]), "r"(a[2]), "r"(a[3]), "l"(db));
}
template <int SC> DEVI void wg_ss64a(float (&d)[32], uint64_t da, uint64_t db) {
    if (SC) asm volatile("wgmma.mma_async.sync.aligned.m64n64k16.f32.bf16.bf16 "
        "{%0,%1,%2,%3,%4,%5,%6,%7,%8,%9,%10,%11,%12,%13,%14,%15,%16,%17,%18,%19,%20,%21,%22,%23,%24,%25,%26,%27,%28,%29,%30,%31}, "
        "%32, %33, 1, 1, 1, 1, 0;"
        : D4(+, 0), D4(+, 4), D4(+, 8), D4(+, 12), D4(+, 16), D4(+, 20), D4(+, 24), D4(+, 28) : "l"(da), "l"(db));
    else asm volatile("wgmma.mma_async.sync.aligned.m64n64k16.f32.bf16.bf16 "
        "{%0,%1,%2,%3,%4,%5,%6,%7,%8,%9,%10,%11,%12,%13,%14,%15,%16,%17,%18,%19,%20,%21,%22,%23,%24,%25,%26,%27,%28,%29,%30,%31}, "
        "%32, %33, 0, 1, 1, 1, 0;"
        : D4(=, 0), D4(=, 4), D4(=, 8), D4(=, 12), D4(=, 16), D4(=, 20), D4(=, 24), D4(=, 28) : "l"(da), "l"(db));
}

#define G_ROWS 514
__device__ uint4 g_G[64 * G_ROWS * 8];
__device__ uint4 g_GN[64 * 8];
__device__ uint4 g_WN[1152];
#define FS_F2 196608
#define FS_TB (FS_F2 + 8192)
#define FS_NQ (FS_TB + 16384)
#define FS_BAR (FS_NQ + 128)
#define FS_NY (FS_NQ + 1024 + 128)
#define FS_TOTAL (FS_NQ + 3072)
#define F_THREADS 512

DEVI uint32_t cis(int j) {
    const float a = fmaf(__uint_as_float((((j + 1024) << 12) & 0x7FF000) | 0x3F800000), 6.283185307179586f, -9.42477796076938f);
    return pack2(__cosf(a), __sinf(a));
}
DEVI uint32_t cos2(int j0, int j1) {
    const float f = 6.283185307179586f / 2048.f;
    return pack2(__cosf((float)(((j0 + 1024) & 2047) - 1024) * f), __cosf((float)(((j1 + 1024) & 2047) - 1024) * f));
}
DEVI void twid(int j, float& c, float& s) {
    const float a = (float)(((j + 512) & 1023) - 512) * (6.283185307179586f / 1024.f);
    c = __cosf(a) * (1.f / 1024.f);
    s = __sinf(a) * (1.f / 1024.f);
}
template <bool B> struct Bool { static constexpr bool v = B; };
DEVI uint32_t opq(uint32_t& x, uint32_t zero) { OPQ(x); return x; }
DEVI uint32_t tidx() { uint32_t r; asm volatile("mov.u32 %0, %%tid.x;" : "=r"(r)); return r; }
DEVI void tma4d(uint32_t dst, const CUtensorMap* tm, uint32_t bar, int c0, int c1, int c2, int c3) {
    asm volatile("cp.async.bulk.tensor.4d.shared::cluster.global.mbarrier::complete_tx::bytes [%0], [%1, {%3, %4, %5, %6}], [%2];"
                 ::"r"(dst), "l"(tm), "r"(bar), "r"(c0), "r"(c1), "r"(c2), "r"(c3) : "memory");
}
DEVI void tma3s(const CUtensorMap* tm, uint32_t src, int c0, int c1, int c2) {
    asm volatile("cp.async.bulk.tensor.3d.global.shared::cta.bulk_group [%0, {%2, %3, %4}], [%1];" ::"l"(tm), "r"(src), "r"(c0), "r"(c1), "r"(c2) : "memory");
}
DEVI void tma4s(const CUtensorMap* tm, uint32_t src, int c0, int c1, int c2, int c3) {
    asm volatile("cp.async.bulk.tensor.4d.global.shared::cta.bulk_group [%0, {%2, %3, %4, %5}], [%1];"
                 ::"l"(tm), "r"(src), "r"(c0), "r"(c1), "r"(c2), "r"(c3) : "memory");
}
DEVI void bulk_commit() { asm volatile("cp.async.bulk.commit_group;" ::: "memory"); }
DEVI void fence_async() { asm volatile("fence.proxy.async;" ::: "memory"); }
DEVI void fence_smem() { asm volatile("fence.proxy.async.shared::cta;" ::: "memory"); }
DEVI void wgbar(uint32_t q) { asm volatile("bar.sync %0, 128;" ::"r"(q + 2) : "memory"); }
DEVI void grid_arrive(uint32_t* c, uint32_t n) { asm volatile("fence.proxy.async;\nred.release.gpu.global.inc.u32 [%0], %1;" ::"l"(c), "r"(n - 1) : "memory"); }
DEVI void grid_wait(uint32_t* c) {
    uint32_t v;
    int it = 0;
    do {
        asm volatile("ld.acquire.gpu.global.u32 %0, [%1];" : "=r"(v) : "l"(c) : "memory");
        if (++it > (1 << 22)) die(it);
    } while (v);
    fence_async();
}

template <bool INV, class S1, class S2>
DEVI void fft_rows(uint32_t grp, uint32_t q, const uint32_t (&F)[2][4], const float (&tc)[8], const float (&ts)[8], uint32_t so, float fx, uint32_t nq,
                   S1 sh1, S2 sh2) {
    float d[64];
    const uint64_t db = INV ? mkdesc(grp, 1024, 2048) : (mkdesc(grp, 2048, 512) ^ ((uint64_t)3 << 62));
    wg_fence();
    wg_rs128t<0>(d, F[0], db);
    wg_rs128t<1>(d, F[1], db + (INV ? 256 : 64));
    wg_commit();
    SF();
    sh1();
    float4 ny;
    if (INV) ny = lds128f(nq);
    wg_wait<0>();
    if (INV) { d[0] = fmaf(fx, ny.x, d[0]); d[16] = fmaf(fx, ny.y, d[16]); d[32] = fmaf(fx, ny.z, d[32]); d[48] = fmaf(fx, ny.w, d[48]); }
    uint32_t a[2][4][4];
    float e[2][INV ? 16 : 20];
    const uint64_t df = mkdesc(SB0 + FS_F2, 16, 1024);
#pragma unroll
    for (int s = 0; s < 2; s++) {
#pragma unroll
        for (int i = 0; i < 4; i++)
#pragma unroll
            for (int h = 0; h < 2; h++) {
                const float* x = d + (2 * s + h) * 16 + i * 4;
                a[s][i][h] = pack2(fmaf(x[2], ts[2 * i], x[0] * tc[2 * i]), fmaf(x[3], ts[2 * i + 1], x[1] * tc[2 * i + 1]));
                a[s][i][h + 2] = pack2(fmaf(-x[0], ts[2 * i], x[2] * tc[2 * i]), fmaf(-x[1], ts[2 * i + 1], x[3] * tc[2 * i + 1]));
            }
        wg_fence();
#pragma unroll
        for (int i = 0; i < 4; i++) {
            if constexpr (INV) { if (i == 0) wg_rs32<0>(e[s], a[s][i], df); else wg_rs32<1>(e[s], a[s][i], df + i * 2); }
            else { if (i == 0) wg_rs40<0>(e[s], a[s][i], df); else wg_rs40<1>(e[s], a[s][i], df + i * 2); }
        }
        wg_commit();
    }
    SF();
    sh2();
#pragma unroll
    for (int s = 0; s < 2; s++) {
        if (s == 0) wg_wait<1>(); else wg_wait<0>();
        float* x = e[s];
        if constexpr (!INV) {
            x[0] *= fx; x[1] *= fx; x[2] *= fx; x[3] *= fx;
            if (fx != 1.f) sts64(nq + s * 8, pack2(x[16], 0.f), pack2(x[18], 0.f));
        }
        const uint32_t o = grp + (INV ? so + s * 4096 : so ^ (s * 576));
#pragma unroll
        for (int b = 0; b < 2; b++)
            stsm4t(o + b * (INV ? 1024 : 4096), pack2(x[8 * b], x[8 * b + 1]), pack2(x[8 * b + 2], x[8 * b + 3]), pack2(x[8 * b + 4], x[8 * b + 5]),
                   pack2(x[8 * b + 6], x[8 * b + 7]));
    }
}

template <bool INV>
DEVI void fft_gen(uint32_t a, uint32_t n2) {
    const uint32_t tid = tidx(), x = ((tid >> 4) & 24) + (tid & 3), o = (tid & 4) * 128;
    if (INV) {
        const uint32_t r = (tid & 64) * 16 + (tid & 16) * 32 + (tid & 40) * 8 + n2;
        sts128(a + tid * 16, cis(o - r * x), cis(o - (r + 128) * x), cis(o - r * (x + 4)), cis(o - (r + 128) * (x + 4)));
    } else {
        const uint32_t r = 64 * x + n2, k = ((tid >> 2) & 24) + ((tid >> 3) & 3);
        sts128(a + tid * 16, cis(r * k + o), cis(r * (k + 4) + o), cis((r + 256) * k + o), cis((r + 256) * (k + 4) + o));
    }
}
template <bool INV, class S1>
DEVI void fft_cross(uint32_t buf, uint32_t q, uint32_t fa, uint32_t so, uint32_t nq, float (&n)[4], S1 sh1) {
    uint32_t F[4][4];
#pragma unroll
    for (int s = 0; s < 4; s++) { const uint4 v = lds128(fa + s * 2048); F[s][0] = v.x; F[s][1] = v.y; F[s][2] = v.z; F[s][3] = v.w; }
    float d[64];
    const uint64_t db = mkdesc(buf + q * 2048, 1024, 8192), dn = mkdesc(nq, 16, 1024);
    wg_fence();
#pragma unroll
    for (int s = 0; s < 4; s++) { if (s == 0) wg_rs128t<0>(d, F[s], db); else wg_rs128t<1>(d, F[s], db + s * 1024); }
#pragma unroll
    for (int s = 0; s < 4; s++) { if (s == 0) wg_rs8<0>(n, F[s], dn); else wg_rs8<1>(n, F[s], dn + s * 2); }
    wg_commit();
    SF();
    sh1();
    wg_wait<0>();
#pragma unroll
    for (int b = 0; b < 8; b++) {
        const uint32_t o = INV ? so ^ ((b >> 1) * 288 ^ (b & 1) * 32) : (so ^ ((b & 3) * 32)) + (b >> 2) * 1024;
        stsm4(buf + o, pack2(d[8 * b], d[8 * b + 1]), pack2(d[8 * b + 2], d[8 * b + 3]), pack2(d[8 * b + 4], d[8 * b + 5]), pack2(d[8 * b + 6], d[8 * b + 7]));
    }
}

template <bool ODD>
DEVI void fft_filter(uint32_t aw, const float (&e)[32], const float (&o)[32], uint32_t (&u)[4][4], uint32_t (&v)[4][4]) {
#pragma unroll
    for (int s = 0; s < 4; s++) {
        float y[2][2][4];
#pragma unroll
        for (int c = 0; c < 2; c++) {
            float f[4][2];
#pragma unroll
            for (int i = 0; i < 4; i++) {
                const uint32_t a = aw + (i * 32 + s * 8 + c) * 144, x = lds32(a);
                f[i][0] = ODD ? hi_f(x) : lo_f(x);
                f[i][1] = ODD ? lo_f(lds32(a + 4)) : hi_f(x);
            }
#pragma unroll
            for (int h = 0; h < 2; h++) {
                const int x = 8 * s + 2 * h + c;
                const float ar = e[x] + o[x], ai = e[x + 4] + o[x + 4], br = e[x] - o[x], bi = e[x + 4] - o[x + 4];
                const float yr = fmaf(-ai, f[2][h], ar * f[0][h]), yi = fmaf(ar, f[2][h], ai * f[0][h]);
                y[h][c][0] = fmaf(-bi, f[3][h], fmaf(br, f[1][h], yr));
                y[h][c][1] = fmaf(br, f[3][h], fmaf(bi, f[1][h], yi));
                y[h][c][2] = fmaf(2.f, yr, -y[h][c][0]);
                y[h][c][3] = fmaf(2.f, yi, -y[h][c][1]);
            }
        }
#pragma unroll
        for (int h = 0; h < 2; h++) {
            u[s][h] = pack2(y[h][0][0], y[h][1][0]); u[s][h + 2] = pack2(y[h][0][1], y[h][1][1]);
            v[s][h] = pack2(y[h][0][2], y[h][1][2]); v[s][h + 2] = pack2(y[h][0][3], y[h][1][3]);
        }
    }
}

__global__ void __launch_bounds__(F_THREADS, 1)
post_kernel(const __grid_constant__ CUtensorMap tmx, const __grid_constant__ CUtensorMap tmg1, const __grid_constant__ CUtensorMap tmg2,
           const __grid_constant__ CUtensorMap tmwr, const __grid_constant__ CUtensorMap tmwi, const __grid_constant__ CUtensorMap tmy,
           const bf16* __restrict__ wr, const bf16* __restrict__ wi, uint32_t* cnt, uint32_t zero, int nw) {
    extern __shared__ __align__(1024) uint8_t smem[];
    const uint32_t sb = SB0;
    if (smem_u32(smem) != sb) die(1 << 23);
    const uint32_t tid = threadIdx.x, lane = tid & 31, g = lane >> 2, t = lane & 3, j8 = lane & 7, mat = lane >> 3;
    const uint32_t wi_ = __reduce_max_sync(0xFFFFFFFFu, tid >> 5), q = wi_ >> 2, w = wi_ & 3;
    const int cta = blockIdx.x;
    const int nt = cta < 64 ? (64 - cta + nw - 1) / nw : 0;
    const uint32_t bar = sb + FS_BAR;
    if (tid == 0) {
        for (int i = 0; i < 30; i++) mbar_init(bar + i * 8, i < 3 ? 4 : i < 6 ? 16 : i >= 14 && i < 18 ? 2 : 1);
        asm volatile("fence.mbarrier_init.release.cluster;" ::: "memory");
        fence_smem();
    }
    __syncthreads();
#define FT(n)
    FT(0);
#define N2(p) (2 * ((p) & 31) + ((p) >> 5))
#define WLOAD(tk, part) { \
        const uint32_t wd_ = sb + 131072 + q * 18432 + (part) * 9216, wb_ = bar + 112 + q * 8; \
        mbar_expect(wb_, 9216); \
        if ((tk) < 256) tma3d(wd_, (part) ? &tmwi : &tmwr, wb_, ((tk) & 63) * 64, (tk) >> 6, 0); \
        else asm volatile("cp.async.bulk.shared::cluster.global.mbarrier::complete_tx::bytes [%0], [%1], 9216, [%2];" \
                          ::"r"(wd_), "l"(g_WN + (part) * 576), "r"(wb_) : "memory"); }
#define GROW(tk) ((tk) < 256 ? ((tk) >> 5) * 64 + ((tk) & 7) * 8 + (((tk) >> 3) & 3) * 2 : 512)
#define DLOAD(tk, sl) { mbar_expect(bar + 48 + (sl) * 8, 16384); tma3d(sb + (sl) * 16384, &tmg2, bar + 48 + (sl) * 8, 0, GROW(tk), 0); }
#define IO(c) if (w == 3 && (c) && elect())
#define XLOAD1(i, bb) { const uint32_t xb_ = bar + 144 + (bb) * 32 + q * 8; mbar_expect(xb_, 16384); tma4d(sb + (bb) * 65536 + q * 16384, &tmx, xb_, 0, 0, q * 8, N2(cta + (i) * nw)); }
#define GLOAD3(i, bb) { mbar_expect(bar + (bb) * 8, q ? 16384 : 16512); tma3d(sb + (bb) * 65536 + q * 16384, &tmg1, bar + (bb) * 8, 0, q * 128, cta + (i) * nw); \
        if (q == 0) asm volatile("cp.async.bulk.shared::cluster.global.mbarrier::complete_tx::bytes [%0], [%1], 128, [%2];" \
                                 ::"r"(sb + FS_NQ + (bb) * 1024), "l"(g_GN + (cta + (i) * nw) * 8), "r"(bar + (bb) * 8) : "memory"); }
    for (int i = 0; i < 3; i++) IO(i < nt) XLOAD1(i, i);
    for (uint32_t x = tid; x < 40 * 32; x += 512) {
        const uint32_t n = x >> 5, m2 = mat * 8 + t * 2, ri = g & 1;
        const uint32_t c2 = ((n >> 1) & 1) + ((n >> 3) & 1) * 2 + (n & 4) + (n >> 4) * 8;
        const uint32_t v = cos2(m2 * c2 * 64 + ((n & 1) - ri) * 512, (m2 + 1) * c2 * 64 + ((n & 1) - ri) * 512);
        sts32(sb + FS_F2 + n * 128 + ((g ^ (n & 7)) << 4) + t * 4, n < 32 ? v : n == 32 && ri == 0 ? 0xBF003F00u : 0u);
    }
    float tc[8], ts[8];
    uint32_t F[2][4];
    uint32_t c1 = 16 * (w >> 1) + 2 * g + (w & 1);
#pragma unroll
    for (int i = 0; i < 8; i++) {
        twid(c1 * (8 * (i >> 1) + 2 * t + (i & 1)), tc[i], ts[i]);
        const uint32_t m1 = (i >> 1) * 8 + 2 * t;
        F[i >> 2][i & 3] = cos2(c1 * m1 * 64 + (i & 1) * 512, c1 * (m1 + 1) * 64 + (i & 1) * 512);
    }
    {
        const uint32_t kr = (2 * (mat & 1) + (j8 & 1)) ^ ((j8 >> 2) << 1);
        const uint32_t so1 = ((mat >> 1) + 2 * (j8 >> 2)) * 1024 + kr * 128 + (((((j8 >> 1) & 1) * 4 + w) ^ kr) << 4);
        const uint32_t so2 = (2 * w + (mat & 1)) * 8192 + q * 2048 + j8 * 128 + (((mat >> 1) ^ j8) << 4);
        uint32_t so = so1 << 16 | so2;
        const float fx = (tid & 127) == 0 ? 0.5f : 1.f;
        fft_gen<false>(sb + FS_TB, N2(cta));
        fence_smem();
        bsync<1, 512>();
        FT(1);
        int b = 0, bp = 2, ph = 0;
        if (nt) mwait(bar + 144 + q * 8, 0);
        __syncwarp();
        auto step = [&](auto first, auto last, const int i) {
            const uint32_t p = cta + i * nw, bn = 3 - b - bp, tb = (i & 1) * 8192;
            const uint32_t grp = sb + b * 65536 + q * 16384, nq = sb + FS_NQ + b * 1024 + q * 32;
            auto sa = [&]() {
                if constexpr (!decltype(first)::v) {
                    fence_smem();
                    __syncwarp();
                    if (elect()) mbar_arrive(bar + 24);
                }
                IO(i > 1) {
                    mwait(bar + 32, i & 1);
                    tma3s(&tmg1, sb + bn * 65536 + q * 16384, 0, q * 128, p - 2 * nw);
                    bulk_commit();
                }
            };
            auto sb_ = [&]() { if constexpr (!decltype(first)::v) mwait(bar + 24, (i - 1) & 1); };
            if constexpr (!decltype(last)::v) fft_rows<false>(grp, q, F, tc, ts, opq(so, zero) >> 16, fx, nq, sa, sb_);
            else { sa(); __syncwarp(); sb_(); __syncwarp(); }
            if constexpr (!decltype(first)::v) {
                float n[4];
                fft_cross<false>(sb + bp * 65536, q, sb + FS_TB + 8192 - tb + (((tidx() & 127) ^ (q & 1)) << 4), opq(so, zero) & 0xFFFF, sb + FS_NQ + bp * 1024, n, [&]() {
                    fft_gen<false>(sb + FS_TB + tb, N2(p));
                    IO(i >= 2 && i + 1 < nt) {
                        asm volatile("cp.async.bulk.wait_group.read 0;" ::: "memory");
                        XLOAD1(i + 1, bn);
                    }
                });
                if (q == 0) {
                    const uint32_t x = tidx();
                    bf16* z = (bf16*)(g_G + ((p - nw) * G_ROWS + 512) * 8) + (x & 4) * 16 + ((x >> 2) & 24) + ((x >> 3) & 3);
                    asm volatile("{\n.reg .pred p;\n.reg .b16 a, b;\nsetp.eq.u32 p, %2, 0;\nmov.b32 {a, b}, %1;\n@p st.global.u16 [%0], a;\n@p st.global.u16 [%0+8], b;\n}"
                                 ::"l"(z), "r"(pack2(n[0], n[2])), "r"(x & 3) : "memory");
                }
            }
            if constexpr (!decltype(last)::v) {
                fft_rows<false>(grp + 8192, q, F, tc, ts, opq(so, zero) >> 16, fx, nq + 16, [&]() {
                    if constexpr (!decltype(first)::v) {
                        fence_smem();
                        __syncwarp();
                        if (elect()) mbar_arrive(bar + 32);
                    }
                    if ((w == 1 || w == 2) && elect())
                        asm volatile("cp.async.bulk.prefetch.L2.global [%0], 8208;" ::"l"((w == 1 ? wr : wi) + (p * 4 + q) * 4104) : "memory");
                }, [&]() { if (i + 1 < nt) mwait(bar + 144 + bn * 32 + q * 8, bn ? ph : ph ^ 1); });
                bp = b;
                if (++b == 3) { b = 0; ph ^= 1; }
            }
        };
        if (nt) {
            step(Bool<true>(), Bool<false>(), 0);
#pragma unroll 1
            for (int i = 1; i < nt; i++) step(Bool<false>(), Bool<false>(), i);
            step(Bool<false>(), Bool<true>(), nt);
        }
        for (uint32_t x = cta * 512 + tid; x < 4096; x += nw * 512)
            ((bf16*)g_WN)[(x >> 5) * 72 + (x & 16) + (x & 7) * 2 + ((x >> 3) & 1)] = (x < 2048 ? wr : wi)[(x & 2047) * 513 + 512];
        FT(2);
        fence_async();
        bsync<1, 512>();
        IO(nt) { tma3s(&tmg1, sb + bp * 65536 + q * 16384, 0, q * 128, cta + (nt - 1) * nw); bulk_commit(); }
    }
    for (uint32_t x = tid; x < 128 * 32; x += 512) {
        const uint32_t n = (x >> 5) & 63, a = x & 31, k2 = (n >> 4) * 8 + (n & 7);
        sts32(sb + FS_TB + (x >> 5) * 128 + (((a >> 2) ^ (n & 7)) << 4) + (a & 3) * 4, cis((2 * a + (x >> 11)) * k2 * 32 + (n & 8) * 64));
    }
    fence_smem();
    bsync<1, 512>();
    IO(true) {
        asm volatile("cp.async.bulk.wait_group 0;" ::: "memory");
        grid_arrive(cnt, 4 * nw);
        grid_wait(cnt);
        const int tk = cta + q * nw;
        if (tk <= 256) { DLOAD(tk, q); WLOAD(tk, 0); WLOAD(tk, 1); }
    }
    __syncwarp();
    {
        const uint32_t lo = j8 * 128 + (((2 * w + (mat & 1)) ^ j8) << 4);
        const uint32_t aw = sb + 131072 + q * 18432 + t * 288 + w * 32 + g * 4;
        const uint64_t df = mkdesc(sb + FS_TB, 16, 1024);
        const uint64_t da = mkdesc(sb + q * 16384, 16, 1024);
        const uint32_t buf = sb + 65536 + q * 16384;
        int i = 0, tk = cta + q * nw;
        if (tk <= 256) mwait(bar + 48 + q * 8, 0);
        FT(3);
#pragma unroll 1
        for (; tk <= 256; tk += 4 * nw, i++) {
            const bool more = tk + 4 * nw <= 256;
            float e[32], o[32];
            wg_fence();
#pragma unroll
            for (int s = 0; s < 4; s++) { if (s == 0) wg_ss64a<0>(e, da, df); else wg_ss64a<1>(e, da + s * 128, df + s * 2); }
#pragma unroll
            for (int s = 0; s < 4; s++) { if (s == 0) wg_ss64a<0>(o, da + 512, df + 512); else wg_ss64a<1>(o, da + 512 + s * 128, df + 512 + s * 2); }
            wg_commit();
            SF();
            if (i > 0) {
                fence_smem();
                wgbar(q);
                IO(true) { tma3s(&tmg2, buf, 0, GROW(tk - 4 * nw), 0); bulk_commit(); }
            }
            if (w == 2 && more && elect()) mbar_expect(bar + 48 + q * 8, 16384);
            const int gr = GROW(tk + 4 * nw);
            mwait(bar + 112 + q * 8, i & 1);
            wg_wait<0>();
            if (w == 2 && more && elect()) tma3d(sb + q * 16384, &tmg2, bar + 48 + q * 8, 0, gr, 0);
            uint32_t u[4][4], v[4][4];
            if (tk & 8) fft_filter<true>(aw + (tk & 48) / 4, e, o, u, v);
            else fft_filter<false>(aw + (tk & 48) / 4, e, o, u, v);
            wg_fence();
#pragma unroll
            for (int s = 0; s < 4; s++) { if (s == 0) wg_rs64t<0>(e, u[s], df); else wg_rs64t<1>(e, u[s], df + s * 128); }
#pragma unroll
            for (int s = 0; s < 4; s++) { if (s == 0) wg_rs64t<0>(o, v[s], df + 512); else wg_rs64t<1>(o, v[s], df + 512 + s * 128); }
            wg_commit();
            SF();
            IO(true) asm volatile("cp.async.bulk.wait_group.read 0;" ::: "memory");
            wgbar(q);
            if (more) {
                if ((w == 1 || w == 2) && elect()) WLOAD(tk + 4 * nw, w - 1);
                mwait(bar + 48 + q * 8, (i + 1) & 1);
            }
            wg_wait<0>();
#pragma unroll
            for (int s = 0; s < 4; s++) {
                const uint32_t a = buf + (mat >> 1) * 1024 + lo + s * 2048;
                stsm4t(a, pack2(e[8 * s], e[8 * s + 1]), pack2(e[8 * s + 2], e[8 * s + 3]), pack2(e[8 * s + 4], e[8 * s + 5]), pack2(e[8 * s + 6], e[8 * s + 7]));
                stsm4t(a + 8192, pack2(o[8 * s], o[8 * s + 1]), pack2(o[8 * s + 2], o[8 * s + 3]), pack2(o[8 * s + 4], o[8 * s + 5]), pack2(o[8 * s + 6], o[8 * s + 7]));
            }
            if (tk == 256 && w < 2) {
                uint32_t* z = (uint32_t*)g_GN + t * 32 + w * 16 + g;
#pragma unroll
                for (int s = 0; s < 16; s++) {
                    z[(s >> 1) * 128 + (s & 1) * 8] = pack2(e[2 * s], e[2 * s + 1]);
                    z[(s >> 1) * 128 + (s & 1) * 8 + 1024] = pack2(o[2 * s], o[2 * s + 1]);
                }
                fence_async();
            }
        }
        fence_smem();
        wgbar(q);
        IO(true) {
            if (i > 0) { tma3s(&tmg2, buf, 0, GROW(tk - 4 * nw), 0); bulk_commit(); }
            asm volatile("cp.async.bulk.wait_group 0;" ::: "memory");
            grid_arrive(cnt + 1, 4 * nw);
        }
    }
    FT(4);
    bsync<1, 512>();
    {
        for (uint32_t n = wi_; n < 32; n += 16) {
            const uint32_t cl = (mat >> 1) * 16 + t * 4 + (mat & 1), mh = ((n >> 3) & 1) + (n & 7) * 2 + (n & 16);
            sts32(sb + FS_F2 + n * 128 + ((g ^ (n & 7)) << 4) + t * 4, cos2(cl * mh * 64 + (g & 1) * 512, (cl + 2) * mh * 64 + (g & 1) * 512));
        }
        fence_smem();
        c1 = 8 * w + g;
#pragma unroll
        for (int i = 0; i < 8; i++) {
            twid(-c1 * (16 * (i >> 2) + 4 * t + 2 * (i & 1) + ((i >> 1) & 1)), tc[i], ts[i]);
            F[i >> 2][i & 3] = cis((i & 1) * 512 - c1 * ((i >> 1) * 4 + (t ^ (q & 1))) * 64);
        }
        const uint32_t kr = (j8 & 1) ^ ((j8 >> 2) << 1);
        const uint32_t so2 = ((w >> 1) * 4 + (j8 >> 2) * 2 + (w & 1)) * 8192 + (2 * q + (mat & 1)) * 1024 + kr * 128 + (((((j8 >> 1) & 1) * 4 + (mat >> 1)) ^ kr) << 4);
        const uint32_t so1 = (mat & 1) * 2048 + j8 * 128 + ((((mat >> 1) * 4 + w) ^ j8) << 4);
        uint32_t so = so1 << 16 | so2;
        const float fx = t ? 0.f : (g & 1) ? -1.f : 1.f;
        fft_gen<true>(sb + FS_TB, N2(cta));
        bsync<1, 512>();
        IO(true) grid_wait(cnt + 1);
        for (int i = 0; i < 3; i++) IO(i < nt) GLOAD3(i, i);
        __syncwarp();
        int b = 0, bp = 2, ph = 0;
        auto step = [&](auto first, auto last, const int i) {
            const uint32_t p = cta + i * nw, bn = 3 - b - bp, tb = (i & 1) * 8192;
            const uint32_t grp = sb + bp * 65536 + q * 16384, ny = sb + FS_NY + bp * 128 + q * 32;
            auto sb_ = [&]() { if constexpr (!decltype(last)::v) mwait(bar + b * 8, ph); };
            if constexpr (!decltype(first)::v) {
                fft_rows<true>(grp, q, F, tc, ts, opq(so, zero) >> 16, fx, ny, [&]() {
                    if (i > 1) {
                        fence_smem();
                        wgbar(q);
                        IO(true) { tma4s(&tmy, sb + bn * 65536 + q * 16384, 0, 0, q * 8, N2(p - 2 * nw)); bulk_commit(); }
                    }
                }, sb_);
            } else { sb_(); __syncwarp(); }
            if constexpr (decltype(first)::v) FT(5);
            if constexpr (!decltype(last)::v) {
                float n[4];
                fft_cross<true>(sb + b * 65536, q, sb + FS_TB + tb + (tidx() & 127) * 16, opq(so, zero) & 0xFFFF, sb + FS_NQ + b * 1024, n, [&]() {
                    fft_gen<true>(sb + FS_TB + 8192 - tb, N2(p + nw));
                    IO(i >= 2 && i + 1 < nt) {
                        asm volatile("cp.async.bulk.wait_group.read 0;" ::: "memory");
                        GLOAD3(i + 1, bn);
                    }
                });
                if (q == 0) {
                    const uint32_t x = tidx(), a = sb + FS_NY + b * 128 + (x & 64) + (x & 16) * 2 + ((x & 40) >> 1);
                    if ((x & 7) == 0) { sts32f(a, n[0]); sts32f(a + 8, n[2]); }
                }
            }
            auto sc = [&]() {
                if constexpr (!decltype(last)::v) {
                    fence_smem();
                    __syncwarp();
                    if (elect()) mbar_arrive(bar + 24);
                }
            };
            auto sd = [&]() { if constexpr (!decltype(last)::v) mwait(bar + 24, (nt + i) & 1); };
            if constexpr (!decltype(first)::v) fft_rows<true>(grp + 8192, q, F, tc, ts, opq(so, zero) >> 16, fx, ny + 16, sc, sd);
            else { sc(); __syncwarp(); sd(); __syncwarp(); }
            if constexpr (!decltype(last)::v) {
                bp = b;
                if (++b == 3) { b = 0; ph ^= 1; }
            }
        };
        if (nt) {
            step(Bool<true>(), Bool<false>(), 0);
#pragma unroll 1
            for (int i = 1; i < nt; i++) step(Bool<false>(), Bool<false>(), i);
            step(Bool<false>(), Bool<true>(), nt);
        }
        fence_smem();
        wgbar(q);
        IO(nt) { tma4s(&tmy, sb + bp * 65536 + q * 16384, 0, 0, q * 8, N2(cta + (nt - 1) * nw)); bulk_commit(); }
        FT(6);
        IO(true) asm volatile("cp.async.bulk.wait_group 0;" ::: "memory");
    }
}

typedef CUresult (*EncodeFn)(CUtensorMap*, CUtensorMapDataType, cuuint32_t, void*, const cuuint64_t*, const cuuint64_t*,
                             const cuuint32_t*, const cuuint32_t*, CUtensorMapInterleave, CUtensorMapSwizzle,
                             CUtensorMapL2promotion, CUtensorMapFloatOOBfill);

static void make_map(EncodeFn enc, CUtensorMap* m, const void* ptr, int rank, const cuuint64_t* dims, const cuuint64_t* strides,
                     const cuuint32_t* box, CUtensorMapSwizzle sw = CU_TENSOR_MAP_SWIZZLE_128B) {
    cuuint32_t es[4] = {1, 1, 1, 1};
    CUresult r = enc(m, CU_TENSOR_MAP_DATA_TYPE_BFLOAT16, rank, (void*)ptr, dims, strides, box, es, CU_TENSOR_MAP_INTERLEAVE_NONE,
                     sw, CU_TENSOR_MAP_L2_PROMOTION_L2_256B, CU_TENSOR_MAP_FLOAT_OOB_FILL_NONE);
    if (r != CUDA_SUCCESS) fprintf(stderr, "tensor map encode failed: %d\n", (int)r);
}

extern "C" void kernel_launch(void* const* d_in, const int* in_sizes, int n_in, void* d_out, int out_size) {
    const bf16* A_x = (const bf16*)d_in[0];
    const bf16* A_mem0 = (const bf16*)d_in[1];
    const bf16* A_Wq = (const bf16*)d_in[2];
    const bf16* A_Wk = (const bf16*)d_in[3];
    const bf16* A_Wv = (const bf16*)d_in[4];
    const bf16* A_Wo = (const bf16*)d_in[5];
    const bf16* B_x = (const bf16*)d_in[7];
    const bf16* B_wr = (const bf16*)d_in[8];
    const bf16* B_wi = (const bf16*)d_in[9];
    bf16* out = (bf16*)d_out;

    static EncodeFn enc = nullptr;
    static void *pxs = nullptr, *pg = nullptr;
    static int ncl = 64;
    if (!enc) {
        cudaDriverEntryPointQueryResult qr;
        void* fn = nullptr;
        cudaGetDriverEntryPoint("cuTensorMapEncodeTiled", &fn, cudaEnableDefault, &qr);
        enc = (EncodeFn)fn;
        cudaFuncSetAttribute(chain_kernel, cudaFuncAttributeMaxDynamicSharedMemorySize, SM_TOTAL);
        cudaFuncSetAttribute(post_kernel, cudaFuncAttributeMaxDynamicSharedMemorySize, FS_TOTAL);
        cudaGetSymbolAddress(&pxs, g_xs);
        cudaGetSymbolAddress(&pg, g_G);
        cudaLaunchConfig_t lc = {};
        cudaLaunchAttribute at;
        at.id = cudaLaunchAttributeClusterDimension;
        at.val.clusterDim.x = 2; at.val.clusterDim.y = 1; at.val.clusterDim.z = 1;
        lc.gridDim = dim3(132); lc.blockDim = dim3(384); lc.dynamicSmemBytes = SM_TOTAL; lc.attrs = &at; lc.numAttrs = 1;
        int nc = 0;
        if (cudaOccupancyMaxActiveClusters(&nc, chain_kernel, &lc) == cudaSuccess && nc > 64) ncl = nc < 66 ? nc : 66;
    }
    CUtensorMap tmq, tmk, tmv, tmo, tmx, tmb, tmy;
    {
        cuuint64_t d[3] = {64, DM, HD / 64}, st[2] = {HD * 2, 128};
        cuuint32_t bx[3] = {64, 64, 2};
        make_map(enc, &tmq, A_Wq, 3, d, st, bx);
        make_map(enc, &tmk, A_Wk, 3, d, st, bx);
        make_map(enc, &tmv, A_Wv, 3, d, st, bx);
    }
    {
        cuuint64_t d[2] = {DM, HD}, st[1] = {DM * 2};
        cuuint32_t bx[2] = {64, 16}, bx1[2] = {64, 128}, bx2[3] = {64, 64, 2};
        make_map(enc, &tmo, A_Wo, 2, d, st, bx1);
        cuuint64_t d2[3] = {64, HD, DM / 64}, st2[2] = {DM * 2, 128}, d3[2] = {DM, SEQ}, st3[1] = {DM * 4};
        make_map(enc, &tmb, A_Wo, 3, d2, st2, bx2);
        make_map(enc, &tmy, out, 2, d3, st3, bx);
    }
    {
        cuuint64_t d[3] = {64, SEQ, DM / 64}, st[2] = {DM * 2, 128};
        cuuint32_t bx[3] = {64, 8, 4};
        make_map(enc, &tmx, A_x, 3, d, st, bx);
    }
    CUtensorMap fx, fg1, fg2, fwr, fwi, fy;
    {
        cuuint64_t d[4] = {32, 32, 32, 64}, st[3] = {64, 64 * DM * 2, DM * 2};
        cuuint32_t bx[4] = {32, 32, 8, 1};
        make_map(enc, &fx, B_x, 4, d, st, bx, CU_TENSOR_MAP_SWIZZLE_64B);
        cuuint64_t d2[4] = {64, 16, 32, 64}, st2[3] = {128, 64 * 4096, 4096};
        cuuint32_t bx2[4] = {64, 16, 8, 1};
        make_map(enc, &fy, out + DM, 4, d2, st2, bx2);
    }
    {
        cuuint64_t d[3] = {64, G_ROWS, 64}, st[2] = {128, G_ROWS * 128};
        cuuint32_t bx[3] = {64, 128, 1}, bx2[3] = {64, 2, 64};
        make_map(enc, &fg1, pg, 3, d, st, bx);
        make_map(enc, &fg2, pg, 3, d, st, bx2);
        cuuint64_t d2[3] = {8 * 513, 4, 64}, st2[2] = {8 * 513 * 2, 32 * 513 * 2};
        cuuint32_t bx3[3] = {72, 1, 64};
        make_map(enc, &fwr, B_wr, 3, d2, st2, bx3, CU_TENSOR_MAP_SWIZZLE_NONE);
        make_map(enc, &fwi, B_wi, 3, d2, st2, bx3, CU_TENSOR_MAP_SWIZZLE_NONE);
    }
    cudaStream_t st = cudaStreamPerThread;
    const uint64_t xs = ((uint64_t)pxs + XS_BYTES - 1) & ~(uint64_t)(XS_BYTES - 1);
    chain_kernel<<<2 * ncl, 384, SM_TOTAL, st>>>(tmq, tmk, tmv, tmo, tmx, tmb, tmy, A_mem0, A_x, (uint32_t)xs, (uint32_t)(xs >> 32), 0u, NSEG, out);
    int nw = ncl == 66 ? 4 : 64;
    cudaLaunchConfig_t lc = {};
    cudaLaunchAttribute at;
    at.id = cudaLaunchAttributeProgrammaticStreamSerialization;
    at.val.programmaticStreamSerializationAllowed = 1;
    lc.gridDim = dim3(nw); lc.blockDim = dim3(F_THREADS); lc.dynamicSmemBytes = FS_TOTAL; lc.stream = st; lc.attrs = &at; lc.numAttrs = 1;
    cudaLaunchKernelEx(&lc, post_kernel, fx, fg1, fg2, fwr, fwi, fy, B_wr, B_wi, (uint32_t*)(xs + XO_TK + 256), 0u, nw);
}
```

```cpp
#include <cuda_runtime.h>
#include <cuda_bf16.h>
#include <cuda.h>
#include <stdint.h>
#include <stdio.h>

typedef __nv_bfloat16 bf16;

#define SEQ 2048
#define DM 1024
#define NH 32
#define DH 128
#define NSEG 64
#define HD (NH * DH)

#define XS_BYTES (32u << 20)
__device__ uint4 g_xs[2 * XS_BYTES / 16];
#define XO_R 0u
#define XO_PB (1u << 18)
#define XO_FL (XO_PB + 32768u)
#define XO_TK (XO_FL + 4096u)
#define XO_CQK (1u << 20)
#define XO_CV (2u << 20)
#define XO_XG (4u << 20)
#define XO_OX (16u << 20)
#define GSYNC(n)
#define PG(n)

#define DEVI __device__ __forceinline__

DEVI void die(int it) { asm volatile("st.shared.u32 [%0], %0;" ::"r"(it) : "memory"); }
DEVI uint32_t smem_u32(const void* p) { return (uint32_t)__cvta_generic_to_shared(p); }
DEVI void mbar_init(uint32_t bar, uint32_t cnt) { asm volatile("mbarrier.init.shared::cta.b64 [%0], %1;" ::"r"(bar), "r"(cnt) : "memory"); }
DEVI void mbar_expect(uint32_t bar, uint32_t bytes) { asm volatile("mbarrier.arrive.expect_tx.shared::cta.b64 _, [%0], %1;" ::"r"(bar), "r"(bytes) : "memory"); }
DEVI void mbar_arrive(uint32_t bar) { asm volatile("mbarrier.arrive.shared::cta.b64 _, [%0];" ::"r"(bar) : "memory"); }
DEVI void mbar_wait(uint32_t bar, uint32_t parity) {
    uint32_t done;
    int it = 0;
    do {
        asm volatile("{\n.reg .pred p;\nmbarrier.try_wait.parity.shared::cta.b64 p, [%1], %2;\nselp.u32 %0, 1, 0, p;\n}\n"
                     : "=r"(done) : "r"(bar), "r"(parity) : "memory");
        if (++it > (1 << 22)) die(it);
    } while (!done);
}
DEVI void tma2d(uint32_t dst, const CUtensorMap* tm, uint32_t bar, int c0, int c1) {
    asm volatile("cp.async.bulk.tensor.2d.shared::cluster.global.mbarrier::complete_tx::bytes [%0], [%1, {%3, %4}], [%2];"
                 ::"r"(dst), "l"(tm), "r"(bar), "r"(c0), "r"(c1) : "memory");
}
DEVI void tma3d(uint32_t dst, const CUtensorMap* tm, uint32_t bar, int c0, int c1, int c2) {
    asm volatile("cp.async.bulk.tensor.3d.shared::cluster.global.mbarrier::complete_tx::bytes [%0], [%1, {%3, %4, %5}], [%2];"
                 ::"r"(dst), "l"(tm), "r"(bar), "r"(c0), "r"(c1), "r"(c2) : "memory");
}
DEVI void bulk_g2s(uint32_t dst, uint32_t lo, uint32_t hi, uint32_t bytes, uint32_t bar) {
    asm volatile("{\n.reg .b64 a;\nmov.b64 a, {%1,%2};\ncp.async.bulk.shared::cluster.global.mbarrier::complete_tx::bytes [%0], [a], %3, [%4];\n}"
                 ::"r"(dst), "r"(lo), "r"(hi), "r"(bytes), "r"(bar) : "memory");
}
DEVI void bulk_s2g(uint32_t lo, uint32_t hi, uint32_t src, uint32_t bytes) {
    asm volatile("{\n.reg .b64 a;\nmov.b64 a, {%0,%1};\ncp.async.bulk.global.shared::cta.bulk_group [a], [%2], %3;\ncp.async.bulk.commit_group;\n}"
                 ::"r"(lo), "r"(hi), "r"(src), "r"(bytes) : "memory");
}
DEVI void bulk_red(uint32_t lo, uint32_t hi, uint32_t src, uint32_t bytes) {
    asm volatile("{\n.reg .b64 a;\nmov.b64 a, {%0,%1};\ncp.reduce.async.bulk.global.shared::cta.bulk_group.add.noftz.bf16 [a], [%2], %3;\ncp.async.bulk.commit_group;\n}"
                 ::"r"(lo), "r"(hi), "r"(src), "r"(bytes) : "memory");
}
DEVI bool elect() {
    uint32_t p;
    asm volatile("{\n.reg .pred P;\nelect.sync _|P, 0xFFFFFFFF;\nselp.u32 %0, 1, 0, P;\n}" : "=r"(p));
    return p != 0;
}
DEVI void ldsm4(uint32_t (&r)[4], uint32_t a) {
    asm volatile("ldmatrix.sync.aligned.m8n8.x4.shared.b16 {%0,%1,%2,%3}, [%4];" : "=r"(r[0]), "=r"(r[1]), "=r"(r[2]), "=r"(r[3]) : "r"(a) : "memory");
}
DEVI void ldsm4t(uint32_t (&r)[4], uint32_t a) {
    asm volatile("ldmatrix.sync.aligned.m8n8.x4.trans.shared.b16 {%0,%1,%2,%3}, [%4];" : "=r"(r[0]), "=r"(r[1]), "=r"(r[2]), "=r"(r[3]) : "r"(a) : "memory");
}
DEVI void ldsm2t(uint32_t (&r)[2], uint32_t a) {
    asm volatile("ldmatrix.sync.aligned.m8n8.x2.trans.shared.b16 {%0,%1}, [%2];" : "=r"(r[0]), "=r"(r[1]) : "r"(a) : "memory");
}
DEVI void ldsm2(uint32_t (&r)[2], uint32_t a) {
    asm volatile("ldmatrix.sync.aligned.m8n8.x2.shared.b16 {%0,%1}, [%2];" : "=r"(r[0]), "=r"(r[1]) : "r"(a) : "memory");
}
DEVI void stsm4t(uint32_t a, uint32_t r0, uint32_t r1, uint32_t r2, uint32_t r3) {
    asm volatile("stmatrix.sync.aligned.m8n8.x4.trans.shared.b16 [%0], {%1,%2,%3,%4};" ::"r"(a), "r"(r0), "r"(r1), "r"(r2), "r"(r3) : "memory");
}
DEVI uint32_t ldsm1(uint32_t a) {
    uint32_t r;
    asm volatile("ldmatrix.sync.aligned.m8n8.x1.shared.b16 {%0}, [%1];" : "=r"(r) : "r"(a) : "memory");
    return r;
}
DEVI void stsm4(uint32_t a, uint32_t r0, uint32_t r1, uint32_t r2, uint32_t r3) {
    asm volatile("stmatrix.sync.aligned.m8n8.x4.shared.b16 [%0], {%1,%2,%3,%4};" ::"r"(a), "r"(r0), "r"(r1), "r"(r2), "r"(r3) : "memory");
}
DEVI void stsm2(uint32_t a, uint32_t r0, uint32_t r1) {
    asm volatile("stmatrix.sync.aligned.m8n8.x2.shared.b16 [%0], {%1,%2};" ::"r"(a), "r"(r0), "r"(r1) : "memory");
}
DEVI uint32_t movm(uint32_t a) {
    uint32_t d;
    asm volatile("movmatrix.sync.aligned.m8n8.trans.b16 %0, %1;" : "=r"(d) : "r"(a));
    return d;
}
DEVI void mma16(float (&d)[4], uint32_t a0, uint32_t a1, uint32_t a2, uint32_t a3, uint32_t b0, uint32_t b1) {
    asm volatile("mma.sync.aligned.m16n8k16.row.col.f32.bf16.bf16.f32 {%0,%1,%2,%3}, {%4,%5,%6,%7}, {%8,%9}, {%0,%1,%2,%3};"
                 : "+f"(d[0]), "+f"(d[1]), "+f"(d[2]), "+f"(d[3]) : "r"(a0), "r"(a1), "r"(a2), "r"(a3), "r"(b0), "r"(b1));
}
DEVI void mma16z(float (&d)[4], uint32_t a0, uint32_t a1, uint32_t a2, uint32_t a3, uint32_t b0, uint32_t b1) {
    asm volatile("mma.sync.aligned.m16n8k16.row.col.f32.bf16.bf16.f32 {%0,%1,%2,%3}, {%4,%5,%6,%7}, {%8,%9}, {%10,%10,%10,%10};"
                 : "=f"(d[0]), "=f"(d[1]), "=f"(d[2]), "=f"(d[3]) : "r"(a0), "r"(a1), "r"(a2), "r"(a3), "r"(b0), "r"(b1), "f"(0.f));
}
DEVI void mma8(float (&d)[4], uint32_t a0, uint32_t a1, uint32_t b0) {
    asm volatile("mma.sync.aligned.m16n8k8.row.col.f32.bf16.bf16.f32 {%0,%1,%2,%3}, {%4,%5}, {%6}, {%0,%1,%2,%3};"
                 : "+f"(d[0]), "+f"(d[1]), "+f"(d[2]), "+f"(d[3]) : "r"(a0), "r"(a1), "r"(b0));
}
DEVI void mma8z(float (&d)[4], uint32_t a0, uint32_t a1, uint32_t b0) {
    asm volatile("mma.sync.aligned.m16n8k8.row.col.f32.bf16.bf16.f32 {%0,%1,%2,%3}, {%4,%5}, {%6}, {%7,%7,%7,%7};"
                 : "=f"(d[0]), "=f"(d[1]), "=f"(d[2]), "=f"(d[3]) : "r"(a0), "r"(a1), "r"(b0), "f"(0.f));
}
DEVI uint32_t pack2(float lo, float hi) {
    uint32_t r;
    asm("cvt.rn.bf16x2.f32 %0, %1, %2;" : "=r"(r) : "f"(hi), "f"(lo));
    return r;
}
DEVI uint32_t hadd2(uint32_t a, uint32_t b) {
    uint32_t r;
    asm("add.rn.bf16x2 %0, %1, %2;" : "=r"(r) : "r"(a), "r"(b));
    return r;
}
DEVI float lo_f(uint32_t x) { return __uint_as_float(x << 16); }
DEVI float hi_f(uint32_t x) { return __uint_as_float(x & 0xFFFF0000u); }
template <uint32_t OFF> DEVI uint4 ldg4(uint32_t lo, uint32_t hi) {
    uint4 v;
    asm volatile("{\n.reg .b64 a;\nmov.b64 a, {%4,%5};\nld.relaxed.gpu.global.v4.u32 {%0,%1,%2,%3}, [a+%6];\n}"
                 : "=r"(v.x), "=r"(v.y), "=r"(v.z), "=r"(v.w) : "r"(lo), "r"(hi), "n"(OFF) : "memory");
    return v;
}
template <uint32_t OFF> DEVI uint2 ldg2(uint32_t lo, uint32_t hi) {
    uint2 v;
    asm volatile("{\n.reg .b64 a;\nmov.b64 a, {%2,%3};\nld.relaxed.gpu.global.v2.u32 {%0,%1}, [a+%4];\n}"
                 : "=r"(v.x), "=r"(v.y) : "r"(lo), "r"(hi), "n"(OFF) : "memory");
    return v;
}
template <uint32_t OFF> DEVI uint32_t ldg1(uint32_t lo, uint32_t hi) {
    uint32_t v;
    asm volatile("{\n.reg .b64 a;\nmov.b64 a, {%1,%2};\nld.relaxed.gpu.global.u32 %0, [a+%3];\n}" : "=r"(v) : "r"(lo), "r"(hi), "n"(OFF) : "memory");
    return v;
}
template <uint32_t OFF> DEVI void stg1(uint32_t lo, uint32_t hi, uint32_t a) {
    asm volatile("{\n.reg .b64 a;\nmov.b64 a, {%0,%1};\nst.relaxed.gpu.global.u32 [a+%3], %2;\n}" ::"r"(lo), "r"(hi), "r"(a), "n"(OFF) : "memory");
}
template <uint32_t OFF> DEVI void stg4(uint32_t lo, uint32_t hi, uint32_t a, uint32_t b, uint32_t c, uint32_t d) {
    asm volatile("{\n.reg .b64 a;\nmov.b64 a, {%0,%1};\nst.relaxed.gpu.global.v4.u32 [a+%6], {%2,%3,%4,%5};\n}"
                 ::"r"(lo), "r"(hi), "r"(a), "r"(b), "r"(c), "r"(d), "n"(OFF) : "memory");
}
template <uint32_t OFF> DEVI void stg2(uint32_t lo, uint32_t hi, uint32_t a, uint32_t b) {
    asm volatile("{\n.reg .b64 a;\nmov.b64 a, {%0,%1};\nst.relaxed.gpu.global.v2.u32 [a+%4], {%2,%3};\n}"
                 ::"r"(lo), "r"(hi), "r"(a), "r"(b), "n"(OFF) : "memory");
}
DEVI uint32_t tagx2(uint32_t a, uint32_t b, uint32_t t) { uint32_t r; asm("lop3.b32 %0, %1, %2, %3, 0x7E;" : "=r"(r) : "r"(a), "r"(b), "r"(t)); return r; }
DEVI uint32_t tagx1(uint32_t a, uint32_t b, uint32_t t) { uint32_t r; asm("lop3.b32 %0, %1, %2, %3, 0xF6;" : "=r"(r) : "r"(a), "r"(b), "r"(t)); return r; }
DEVI uint32_t or3(uint32_t a, uint32_t b, uint32_t c) { uint32_t r; asm("lop3.b32 %0, %1, %2, %3, 0xFE;" : "=r"(r) : "r"(a), "r"(b), "r"(c)); return r; }
DEVI bool any_bad(uint32_t x) { return __any_sync(0xFFFFFFFFu, (x & 1u) != 0); }
DEVI uint32_t settag(uint32_t x, uint32_t tag) { return (x & ~1u) | tag; }
DEVI void sts32f(uint32_t a, float v) { asm volatile("st.shared.f32 [%0], %1;" ::"r"(a), "f"(v) : "memory"); }
DEVI void sts32(uint32_t a, uint32_t v) { asm volatile("st.shared.u32 [%0], %1;" ::"r"(a), "r"(v) : "memory"); }
DEVI void sts16(uint32_t a, uint32_t v) { asm volatile("st.shared.u16 [%0], %1;" ::"r"(a), "h"((unsigned short)v) : "memory"); }
DEVI void sts64(uint32_t a, uint32_t x, uint32_t y) { asm volatile("st.shared.v2.u32 [%0], {%1,%2};" ::"r"(a), "r"(x), "r"(y) : "memory"); }
DEVI void sts128(uint32_t a, uint32_t x, uint32_t y, uint32_t z, uint32_t w) {
    asm volatile("st.shared.v4.u32 [%0], {%1,%2,%3,%4};" ::"r"(a), "r"(x), "r"(y), "r"(z), "r"(w) : "memory");
}
DEVI float4 lds128f(uint32_t a) {
    float4 v;
    asm volatile("ld.shared.v4.f32 {%0,%1,%2,%3}, [%4];" : "=f"(v.x), "=f"(v.y), "=f"(v.z), "=f"(v.w) : "r"(a) : "memory");
    return v;
}
DEVI uint4 lds128(uint32_t a) {
    uint4 v;
    asm volatile("ld.shared.v4.u32 {%0,%1,%2,%3}, [%4];" : "=r"(v.x), "=r"(v.y), "=r"(v.z), "=r"(v.w) : "r"(a) : "memory");
    return v;
}
DEVI uint2 lds64(uint32_t a) {
    uint2 v;
    asm volatile("ld.shared.v2.u32 {%0,%1}, [%2];" : "=r"(v.x), "=r"(v.y) : "r"(a) : "memory");
    return v;
}
DEVI uint32_t lds32(uint32_t a) {
    uint32_t v;
    asm volatile("ld.shared.u32 %0, [%1];" : "=r"(v) : "r"(a) : "memory");
    return v;
}
DEVI float ex2(float x) { float r; asm("ex2.approx.ftz.f32 %0, %1;" : "=f"(r) : "f"(x)); return r; }
DEVI float rcp(float x) { float r; asm("rcp.approx.ftz.f32 %0, %1;" : "=f"(r) : "f"(x)); return r; }
DEVI uint32_t clk() { uint32_t c; asm volatile("mov.u32 %0, %%clock;" : "=r"(c)::"memory"); return c; }

DEVI uint64_t mkdesc(uint32_t addr, uint32_t lbo, uint32_t sbo) {
    return (uint64_t)((addr & 0x3FFFF) >> 4) | ((uint64_t)(lbo >> 4) << 16) | ((uint64_t)(sbo >> 4) << 32) | ((uint64_t)1 << 62);
}
DEVI void wg_fence() { asm volatile("wgmma.fence.sync.aligned;" ::: "memory"); }
DEVI void wg_commit() { asm volatile("wgmma.commit_group.sync.aligned;" ::: "memory"); }
template <int N> DEVI void wg_wait() { asm volatile("wgmma.wait_group.sync.aligned %0;" ::"n"(N) : "memory"); }
template <int SC>
DEVI void wg_rs32(float (&d)[16], const uint32_t (&a)[4], uint64_t db) {
    if (SC) {
        asm volatile("wgmma.mma_async.sync.aligned.m64n32k16.f32.bf16.bf16 "
                     "{%0,%1,%2,%3,%4,%5,%6,%7,%8,%9,%10,%11,%12,%13,%14,%15}, {%16,%17,%18,%19}, %20, 1, 1, 1, 0;"
                     : "+f"(d[0]), "+f"(d[1]), "+f"(d[2]), "+f"(d[3]), "+f"(d[4]), "+f"(d[5]), "+f"(d[6]), "+f"(d[7]),
                       "+f"(d[8]), "+f"(d[9]), "+f"(d[10]), "+f"(d[11]), "+f"(d[12]), "+f"(d[13]), "+f"(d[14]), "+f"(d[15])
                     : "r"(a[0]), "r"(a[1]), "r"(a[2]), "r"(a[3]), "l"(db));
    } else {
        asm volatile("wgmma.mma_async.sync.aligned.m64n32k16.f32.bf16.bf16 "
                     "{%0,%1,%2,%3,%4,%5,%6,%7,%8,%9,%10,%11,%12,%13,%14,%15}, {%16,%17,%18,%19}, %20, 0, 1, 1, 0;"
                     : "=f"(d[0]), "=f"(d[1]), "=f"(d[2]), "=f"(d[3]), "=f"(d[4]), "=f"(d[5]), "=f"(d[6]), "=f"(d[7]),
                       "=f"(d[8]), "=f"(d[9]), "=f"(d[10]), "=f"(d[11]), "=f"(d[12]), "=f"(d[13]), "=f"(d[14]), "=f"(d[15])
                     : "r"(a[0]), "r"(a[1]), "r"(a[2]), "r"(a[3]), "l"(db));
    }
}

#define NA 12
#define NPF 6
#define PF1 2
#define PF2 2
#define PF3 4
#define WPF 2
#define VPF 2
#define VORD 0x01234567
#define VSF 0
#define VMF 0
#define VC 1
#define QP 16
#define W2P 0
#define W3P 1
#define QSP 12
#define VSB 0x10F
#define QQP 3
#define CGP 8
#define C0P 9
#define C1P 9
#define PIP 10
#define K0P 2
#define KEP 4
#define KE2 0
#define VTP 0
#define CW 1
#define WV_BOX ((16 - NA) * 2048)
#define WO_BOX 16384
#define SM_WV 0
#define SM_WO (2 * WV_BOX)
#define SM_X (SM_WO + 4 * WO_BOX)
#define SM_XO (SM_X + 32768)
#define SM_MEMT (SM_XO + 12288)
#define SM_OT (SM_MEMT + 4096)
#define SM_VS (SM_OT + 2048)
#define SM_P (SM_VS + 2048)
#define SM_DN (SM_P + 1792)
#define SM_PROF (SM_P + 2048)
#define SM_ST (SM_X + 65536)
#define SM_KV SM_ST
#define SM_SP (SM_KV + 18432)
#define SM_TR (SM_ST + 32768)
#define SM_PI (SM_ST + 65536)
#define SM_BAR (SM_PI + 12288)
#define SM_TOTAL (SM_BAR + 512)
static_assert(NA == 12, "start-up chunks");
static_assert(SM_TOTAL <= 232448, "smem");
#define BAR_XA 32
#define BAR_KV 40
#define BAR_PI 48
#define BAR_RO 64
#define BAR_WF 256
#define BAR_WE 384
#define SM_ROLE (SM_BAR + 72)

#define SPIN_LIMIT (1 << 20)
#define RPOS 26
#define OPOS 2
#define ASF 0
#define KPOS 0
#define CPOS 4
#define DLY_V 380
#define NPRB 2
#define PW 4
#define ZD 0
#define FTM 2
#define XPF 1
#define WOP 2
#define WIN 2
#define EPD 1300
#define ASP 4
#define EPF 0
#define CFAR 1

template <int ID, int N> DEVI void bsync() { asm volatile("bar.sync %0, %1;" ::"n"(ID), "n"(N) : "memory"); }
template <int ID, int N> DEVI void barv() { asm volatile("bar.arrive %0, %1;" ::"n"(ID), "n"(N) : "memory"); }

#define PT(n)
#define PC(n, v)
#define PDUMP()
#define REFRESH() asm volatile("xor.b32 %0, %0, %1;" : "+r"(l16) : "r"(zero))
#define OPQ(x) asm volatile("xor.b32 %0, %0, %1;" : "+r"(x) : "r"(zero))
#define KEEP(x, a, b, c, d) asm volatile("{\n.reg .b32 t;\nlop3.b32 t, %1, %2, %3, 0x80;\nlop3.b32 t, t, %4, %5, 0x80;\nxor.b32 %0, %0, t;\n}" \
                                         : "+r"(x) : "r"(a), "r"(b), "r"(c), "r"(d), "r"(zero))
#define SF() asm volatile("pmevent 1;" ::: "memory")
#define MF() __syncwarp()
#define SB0 1024u

#define XDOFF(ks) ((((ks) >> 2) * 1024 + ((ks) & 3) * 32) >> 4)
template <int SC>
DEVI void wg_ss32t(float (&d)[16], uint64_t da, uint64_t db) {
    if (SC) {
        asm volatile("wgmma.mma_async.sync.aligned.m64n32k16.f32.bf16.bf16 "
                     "{%0,%1,%2,%3,%4,%5,%6,%7,%8,%9,%10,%11,%12,%13,%14,%15}, %16, %17, 1, 1, 1, 1, 0;"
                     : "+f"(d[0]), "+f"(d[1]), "+f"(d[2]), "+f"(d[3]), "+f"(d[4]), "+f"(d[5]), "+f"(d[6]), "+f"(d[7]),
                       "+f"(d[8]), "+f"(d[9]), "+f"(d[10]), "+f"(d[11]), "+f"(d[12]), "+f"(d[13]), "+f"(d[14]), "+f"(d[15])
                     : "l"(da), "l"(db));
    } else {
        asm volatile("wgmma.mma_async.sync.aligned.m64n32k16.f32.bf16.bf16 "
                     "{%0,%1,%2,%3,%4,%5,%6,%7,%8,%9,%10,%11,%12,%13,%14,%15}, %16, %17, 0, 1, 1, 1, 0;"
                     : "=f"(d[0]), "=f"(d[1]), "=f"(d[2]), "=f"(d[3]), "=f"(d[4]), "=f"(d[5]), "=f"(d[6]), "=f"(d[7]),
                       "=f"(d[8]), "=f"(d[9]), "=f"(d[10]), "=f"(d[11]), "=f"(d[12]), "=f"(d[13]), "=f"(d[14]), "=f"(d[15])
                     : "l"(da), "l"(db));
    }
}

DEVI void delay_until(uint32_t t0, uint32_t d) { while (clk() - t0 < d) {} }

#define VR 2
#define CW2 4
template <int I0, int I1>
DEVI void xmma(float (&xa)[16], float (&xb)[16], uint32_t w, int ps, uint32_t zero, const uint32_t (&Wq)[16][4], const uint32_t (&Wk)[16][4],
               const uint32_t (&Wv)[NA][4], const uint32_t (&wv)[16 - NA][4]) {
    const uint64_t xd = mkdesc(SB0 + SM_X, 16, 4096) + (ps & 1) * 1024, vd = mkdesc(SB0 + SM_WV, 8192, 1024);
    uint32_t vo = (w >> 2) * (WV_BOX / 16);
    if (VR ? false : VC == 0 ? I0 < 16 - NA : VC == 1 ? I0 >= 32 && I0 < 48 - NA : I1 > 32 + NA) OPQ(vo);
#pragma unroll
    for (int i = I0; i < I1; i++) {
        if (VC) {
            const int v = (i + (VC == 1 ? NA : 0)) & 15;
            if (i == 0) wg_rs32<0>(xa, Wq[0], xd);
            else if (i < 16) wg_rs32<1>(xa, Wq[i & 15], xd + XDOFF(i & 15));
            else if (i == 16) wg_rs32<0>(xb, Wk[0], xd);
            else if (i < 32) wg_rs32<1>(xb, Wk[i & 15], xd + XDOFF(i & 15));
            else if (i == 32 && v < NA) wg_rs32<0>(xa, Wv[0], xd);
            else if (VR && i == 32) wg_rs32<0>(xa, wv[0], xd + XDOFF(NA));
            else if (VR && v >= NA) wg_rs32<1>(xa, wv[v >= NA ? v - NA : 0], xd + XDOFF(v));
            else if (i == 32) wg_ss32t<0>(xa, (vd & ~0xFFFFFFFFull) | ((uint32_t)vd + vo), xd + XDOFF(NA));
            else if (v < NA) wg_rs32<1>(xa, Wv[v < NA ? v : 0], xd + XDOFF(v));
            else wg_ss32t<1>(xa, (vd & ~0xFFFFFFFFull) | ((uint32_t)vd + (v - NA) * 128 + vo), xd + XDOFF(v));
        } else
        if (i == 0) wg_ss32t<0>(xb, (vd & ~0xFFFFFFFFull) | ((uint32_t)vd + vo), xd + XDOFF(NA));
        else if (i < 16 - NA) wg_ss32t<1>(xb, (vd & ~0xFFFFFFFFull) | ((uint32_t)vd + i * 128 + vo), xd + XDOFF(NA + i));
        else if (i == 16 - NA) wg_rs32<0>(xa, Wq[0], xd);
        else if (i < 32 - NA) wg_rs32<1>(xa, Wq[(i + NA) & 15], xd + XDOFF((i + NA) & 15));
        else if (i < 32) wg_rs32<1>(xb, Wv[(i + NA) & 15], xd + XDOFF((i + NA) & 15));
        else if (i == 32) wg_rs32<0>(xa, Wk[0], xd);
        else wg_rs32<1>(xa, Wk[i & 15], xd + XDOFF(i & 15));
    }
    wg_commit();
}
#define XMMA(I0, I1) xmma<(I0), (I1)>(xa, xb, w, p ^ 1, zero, Wq, Wk, Wv, wv)
DEVI void wg_done(float (&d)[16]) {
    asm volatile("" : "+f"(d[0]), "+f"(d[1]), "+f"(d[2]), "+f"(d[3]), "+f"(d[4]), "+f"(d[5]), "+f"(d[6]), "+f"(d[7]),
                      "+f"(d[8]), "+f"(d[9]), "+f"(d[10]), "+f"(d[11]), "+f"(d[12]), "+f"(d[13]), "+f"(d[14]), "+f"(d[15]) :: "memory");
}
template <int M>
DEVI void xpack(uint32_t (&xp)[8], float (&xa)[16]) {
    wg_done(xa);
#pragma unroll
    for (int i = 0; i < 4; i++) {
        xp[2 * i] = pack2(xa[4 * i], xa[4 * i + (M < 2 ? 2 : 1)]);
        xp[2 * i + 1] = pack2(xa[4 * i + (M < 2 ? 1 : 2)], xa[4 * i + 3]);
    }
}
template <int M>
DEVI uint4 xpeer(uint32_t sb, int ps, uint32_t t16) { return lds128(sb + SM_PI - ((ps & 1) ^ 1) * 12288 + M * 4096 + t16); }
DEVI void xadd(uint32_t (&xp)[8], const uint4& pi) {
    xp[0] = hadd2(xp[0], pi.x); xp[1] = hadd2(xp[1], pi.y); xp[2] = hadd2(xp[2], pi.z); xp[3] = hadd2(xp[3], pi.w);
}
template <int M>
DEVI void xsend(const uint32_t (&xp)[8], uint32_t sb, int ps, uint32_t t16) {
    asm volatile("st.async.weak.shared::cluster.mbarrier::complete_tx::bytes.v4.b32 [%0], {%1,%2,%3,%4}, [%5];"
                 ::"r"((sb ^ 0x1000000) + SM_PI - (ps & 1) * 12288 + M * 4096 + t16), "r"(xp[4]), "r"(xp[5]), "r"(xp[6]), "r"(xp[7]),
                   "r"((sb ^ 0x1000000) + SM_BAR + BAR_PI + (ps & 1) * 8) : "memory");
}
template <int M>
DEVI void xstore(const uint32_t (&xp)[8], uint32_t sb, uint32_t sbw, int ps, uint32_t t16, uint32_t KA) {
    const uint32_t a = SM_XO + M * 2048 + (M < 2 ? (KA & 0xFF) + sbw : (t16 >> 1) + sb);
    sts64(a, xp[0], xp[1]);
    sts64(a + 6144, xp[2], xp[3]);
    xsend<M>(xp, sb, ps, t16);
}
template <int M>
DEVI void xpark(uint32_t (&xp)[8], const uint4& pi, uint32_t sb, uint32_t sbw, int ps, uint32_t t16, uint32_t KA) {
    xadd(xp, pi);
    xstore<M>(xp, sb, sbw, ps, t16, KA);
}
template <uint32_t OFF> DEVI void red2(uint32_t lo, uint32_t hi, uint32_t a, uint32_t b) {
    asm volatile("{\n.reg .b64 a;\nmov.b64 a, {%0,%1};\nred.relaxed.gpu.global.add.noftz.v2.bf16x2 [a+%4], {%2,%3};\n}"
                 ::"r"(lo), "r"(hi), "r"(a), "r"(b), "n"(OFF) : "memory");
}
template <int M, int N>
DEVI void xstart(uint32_t sb, uint32_t w, uint32_t ga, uint32_t xhi, uint32_t j, uint32_t t16, uint32_t KA, const uint32_t (&W)[N][4]) {
    float xa[16], xb[16];
    uint32_t xp[8];
    auto pass = [&](float (&d)[16], int i, int k0, int k1) {
        const uint64_t xd = mkdesc(SB0 + SM_X + (i ? i + 1 : 0) * 16384, 16, 4096), vd = mkdesc(SB0 + SM_WV, 8192, 1024) + (w >> 2) * (WV_BOX / 16);
#pragma unroll
        for (int k = k0; k < k1; k++) {
            if (k == 0) wg_rs32<0>(d, W[0], xd);
            else if (k < N) wg_rs32<1>(d, W[k < N ? k : 0], xd + XDOFF(k));
            else wg_ss32t<1>(d, vd + (k - N) * 128, xd + XDOFF(k));
        }
        wg_commit();
    };
    wg_fence();
    pass(xa, 0, 0, 16);
    pass(xb, 1, 0, ASP);
    if (M == 0) bsync<5, 288>();
    ga += M < 2 ? (KA & 0xFF) + w * 256 : t16 >> 1;
    constexpr uint32_t O = XO_XG + M * 2048, SG = 128 * 6144;
    wg_wait<1>();
    xpack<M>(xp, xa);
    red2<O>(ga, xhi, xp[0], xp[1]); red2<O + 6144>(ga, xhi, xp[2], xp[3]); red2<O + 12288>(ga, xhi, xp[4], xp[5]); red2<O + 18432>(ga, xhi, xp[6], xp[7]);
    if (M == 2) barv<3, 320>();
    wg_fence();
    pass(xb, 1, ASP, 16);
    pass(xa, 2, 0, 16);
    wg_wait<1>();
    xpack<M>(xp, xb);
    red2<O + SG>(ga, xhi, xp[0], xp[1]); red2<O + SG + 6144>(ga, xhi, xp[2], xp[3]);
    red2<O + SG + 12288>(ga, xhi, xp[4], xp[5]); red2<O + SG + 18432>(ga, xhi, xp[6], xp[7]);
    wg_wait<0>();
    xpack<M>(xp, xa);
    red2<O + 2 * SG>(ga + j * 6144, xhi, xp[0], xp[1]);
    red2<O + 2 * SG>(ga + (j ^ 1) * 6144, xhi, xp[2], xp[3]);
    xsend<M>(xp, sb, 0, t16);
}
DEVI void piwait(uint32_t sb, int p, int ps) { mbar_wait(sb + SM_BAR + BAR_PI + p * 8, ((ps + 2) >> 1) & 1); }

DEVI uint32_t par(uint32_t off) { return __popc(off & 0xB2000u) & 1; }
DEVI uint32_t probe(uint32_t lo, uint32_t hi) {
    uint32_t best = 0xFFFFFFFFu, x = 0;
    stg4<0>(lo, hi, 0, 0, 0, 0);
    stg4<16>(lo, hi, 0, 0, 0, 0);
#pragma unroll 1
    for (int r = 0; r < NPRB; r++) {
        const uint32_t t0 = clk();
        asm volatile("{\n.reg .b64 a;\nmov.b64 a, {%1,%2};\natom.relaxed.gpu.global.add.u32 %0, [a], 2;\n}" : "=r"(x) : "r"(lo), "r"(hi) : "memory");
        if (x == 0xFFFFFFFFu) die(1 << 23);
        best = min(best, clk() - t0);
    }
    return best;
}

DEVI void xload(uint32_t sb, uint32_t u, uint32_t j, int ps, const CUtensorMap* tmx) {
    if (elect()) {
        const uint32_t sg = ps + 4 - (u & 1) + (u >> 1);
        mbar_expect(sb + SM_BAR + BAR_XA, sg < NSEG ? 4096 : 0);
        if (sg < NSEG) tma3d(sb + SM_X + (ps & 1) * 16384 + u * 4096, tmx, sb + SM_BAR + BAR_XA, 0, sg * 32 + (j ^ ((u & 1) * 2 + (u >> 1))) * 8, j * 4);
    }
}
DEVI uint32_t rpage(uint32_t j, int s) { return (s & 3) * 65536 + (j & 1) * 8192 + (((s ^ (s >> 1) ^ j ^ (j >> 1)) & 1) << 12); }

#define RLOAD() { m0 = ldg4<XO_R>(a, ah); n0 = ldg4<XO_R + 16384>(a, ah); e0 = ldg1<XO_R + 32768>(e, eh); f0 = ldg1<XO_R + 33792>(e, eh); }
DEVI bool ruse(uint32_t a, const uint4& m0, const uint4& n0, uint32_t e0, uint32_t f0) {
    const uint32_t a0 = hadd2(m0.w, n0.w), b0 = hadd2(e0, f0);
    stsm4(a, hadd2(m0.x, n0.x), hadd2(m0.y, n0.y), hadd2(m0.z, n0.z), __byte_perm(a0, b0, 0x5410));
    return __any_sync(0xFFFFFFFFu, (a0 & b0 & 0x42000000u) != 0x42000000u);
}

#define GST(i) (SM_WO + (i) * 49152)
#define BAR_GF 128
#define BAR_GE (BAR_GF + 64)
#define BAR_GX (BAR_GE + 32)
#define D4(c, i) #c "f"(d[i]), #c "f"(d[i + 1]), #c "f"(d[i + 2]), #c "f"(d[i + 3])
#define D16(c, i) D4(c, i), D4(c, i + 4), D4(c, i + 8), D4(c, i + 12)
DEVI void mwait(uint32_t bar, uint32_t parity) {
    asm volatile("{\n.reg .pred p;\n.reg .b32 c;\nmbarrier.try_wait.parity.shared::cta.b64 p, [%0], %1;\n@p bra.uni D;\nmov.b32 c, 0;\n"
                 "L:\nadd.u32 c, c, 1;\nsetp.gt.u32 p, c, 4194304;\n@p st.shared.u32 [c], c;\n"
                 "mbarrier.try_wait.parity.shared::cta.b64 p, [%0], %1;\n@!p bra.uni L;\nD:\n}" ::"r"(bar), "r"(parity) : "memory");
}
DEVI void wg_ss256t(float (&d)[128], uint64_t da, uint64_t db) {
    asm volatile("wgmma.mma_async.sync.aligned.m64n256k16.f32.bf16.bf16 "
        "{%0,%1,%2,%3,%4,%5,%6,%7,%8,%9,%10,%11,%12,%13,%14,%15,%16,%17,%18,%19,%20,%21,%22,%23,%24,%25,%26,%27,%28,%29,%30,%31,%32,%33,%34,%35,%36,%37,%38,%39,%40,%41,%42,%43,%44,%45,%46,%47,%48,%49,%50,%51,%52,%53,%54,%55,%56,%57,%58,%59,%60,%61,%62,%63,%64,%65,%66,%67,%68,%69,%70,%71,%72,%73,%74,%75,%76,%77,%78,%79,%80,%81,%82,%83,%84,%85,%86,%87,%88,%89,%90,%91,%92,%93,%94,%95,%96,%97,%98,%99,%100,%101,%102,%103,%104,%105,%106,%107,%108,%109,%110,%111,%112,%113,%114,%115,%116,%117,%118,%119,%120,%121,%122,%123,%124,%125,%126,%127}, "
        "%128, %129, 1, 1, 1, 1, 1;"
        : D16(+, 0), D16(+, 16), D16(+, 32), D16(+, 48), D16(+, 64), D16(+, 80), D16(+, 96), D16(+, 112) : "l"(da), "l"(db));
}
template <int O, int KB> DEVI void g_half(float (&d)[64], uint64_t da) {
    const uint64_t db = mkdesc(SB0 + GST(KB & 3) + 16384 + O * 256, 8192, 1024);
#pragma unroll
    for (int k = 0; k < 4; k++)
        asm volatile("wgmma.mma_async.sync.aligned.m64n128k16.f32.bf16.bf16 "
            "{%0,%1,%2,%3,%4,%5,%6,%7,%8,%9,%10,%11,%12,%13,%14,%15,%16,%17,%18,%19,%20,%21,%22,%23,%24,%25,%26,%27,%28,%29,%30,%31,%32,%33,%34,%35,%36,%37,%38,%39,%40,%41,%42,%43,%44,%45,%46,%47,%48,%49,%50,%51,%52,%53,%54,%55,%56,%57,%58,%59,%60,%61,%62,%63}, "
            "%64, %65, 1, 1, 1, 1, 1;"
            : D16(+, 0), D16(+, 16), D16(+, 32), D16(+, 48) : "l"(da + (KB & 3) * 3072 + k * 16), "l"(db + k * 128));
}
DEVI void g_load(uint32_t sb, uint32_t u, uint32_t role, uint32_t kb, uint32_t xlo, uint32_t xhi, const CUtensorMap* tmb) {
    const uint32_t st = kb & 3, bar = sb + SM_BAR + BAR_GF + u * 32 + st * 8, dst = sb + GST(st), k = (role & 1) * 32 + kb;
    if (!elect()) return;
    mbar_expect(bar, u ? 8192 : 40960);
    bulk_g2s(dst + u * 8192, xlo + XO_OX + (k * 16 + (role >> 3)) * 16384 + u * 8192, xhi, 8192, bar);
    if (u == 0) {
        tma3d(dst + 16384, tmb, bar, 0, k * 64, ((role & 7) ^ 1) * 2);
        tma3d(dst + 32768, tmb, bar, 0, k * 64, (role & 7) * 2);
    }
}
DEVI void g_arrive(uint32_t a, uint32_t xhi, uint32_t n) {
    if (elect()) asm volatile("{\n.reg .b64 a;\nmov.b64 a, {%0,%1};\nred.release.gpu.global.inc.u32 [a], %2;\n}" ::"r"(a), "r"(xhi), "r"(n - 1) : "memory");
}
DEVI void g_wait(uint32_t a, uint32_t xhi) {
    int it = 0;
    uint32_t v;
    do {
        asm volatile("{\n.reg .b64 a;\nmov.b64 a, {%1,%2};\nld.acquire.gpu.global.u32 %0, [a];\n}" : "=r"(v) : "r"(a), "r"(xhi) : "memory");
        if (++it > SPIN_LIMIT) die(it);
    } while (__any_sync(0xFFFFFFFFu, v));
    asm volatile("fence.proxy.async.global;" ::: "memory");
}
#define SE 2
#define DLY_S 0
#define VX 1
#define VH 1
#define VD 1
#define SM_VP (SM_TR + 12288)
#define JV(h, j) (VH < 2 ? (j) ^ ((par((h) * 8192) ^ VH) << 1) : (j))
#define SEU 0
#define VA 0
#define VLP 0
#define VCP 1
#define SEED 0
#define VB 0
#define RCP 0
#define XLP 0
#define B3 0
#define GD 200
#define GE 1
#define GH 1
#define GS 1
#define GP 1
DEVI void g_done(float (&d)[64]) { asm volatile("" : D16(+, 0), D16(+, 16), D16(+, 32), D16(+, 48)::"memory"); }
DEVI void g_main(uint32_t sb, uint32_t w, uint32_t role, const CUtensorMap* tmy, void* out) {
    const uint32_t bar = sb + SM_BAR, t16 = threadIdx.x * 16;
    const uint64_t da = (mkdesc(SB0 + GST(0), 128, 1024) & ~((uint64_t)3 << 62)) + (w >> 2) * 512;
    float d[128];
#pragma unroll
    for (int i = 0; i < 128; i++) d[i] = 0.f;
#define GFULL(kb) { mwait(bar + BAR_GF + ((kb) & 3) * 8, ((kb) >> 2) & 1); if (w >= 4) mwait(bar + BAR_GF + 32 + ((kb) & 3) * 8, ((kb) >> 2) & 1); }
#pragma unroll 1
    for (uint32_t kb = 0; kb < (GE ? 28 : 29); kb++) {
        GFULL(kb);
        if (kb == 0 && threadIdx.x == 128) PG(4);
        if (kb == 4 && threadIdx.x == 0) PG(5);
        const uint64_t a = da + (kb & 3) * 3072, b = mkdesc(SB0 + GST(0) + 16384, 8192, 1024) + (kb & 3) * 3072;
        wg_fence();
#pragma unroll
        for (int k = 0; k < 4; k++) wg_ss256t(d, a + k * 16, b + k * 128);
        wg_commit();
        wg_wait<1>();
        if (kb > 0 && elect()) mbar_arrive(bar + BAR_GE + ((kb - 1) & 3) * 8);
    }
    if (GE) { GFULL(28); }
    else { GFULL(29); GFULL(30); GFULL(31); }
    wg_wait<0>();
    if (GE && elect()) mbar_arrive(bar + BAR_GE + 24);
    float x[64], y[64];
#pragma unroll
    for (int i = 0; i < 64; i++) asm volatile("mov.b32 %0, %1;" : "=f"(x[i]) : "f"(d[i]) : "memory");
    SF();
#pragma unroll
    for (int i = 0; i < 64; i++) asm volatile("mov.b32 %0, %1;" : "=f"(y[i]) : "f"(d[i + 64]) : "memory");
    SF();
#define GFREE() if (elect()) asm volatile("mbarrier.arrive.relaxed.cluster.shared::cluster.b64 _, [%0];" ::"r"((bar ^ 0x1000000) + BAR_GX) : "memory")
#define GSW(i) ((i) * 4096 + (GE && (i) >= 4 ? GST(0) : 0))
#define GSEND(i0) _Pragma("unroll") for (int i = (i0); i < (i0) + 4; i++) \
        asm volatile("st.async.weak.shared::cluster.mbarrier::complete_tx::bytes.v4.b32 [%0], {%1,%2,%3,%4}, [%5];" \
                     ::"r"((sb ^ 0x1000000) + GSW(i) + t16), "r"(pack2(x[8 * i], x[8 * i + 1])), "r"(pack2(x[8 * i + 2], x[8 * i + 3])), \
                       "r"(pack2(x[8 * i + 4], x[8 * i + 5])), "r"(pack2(x[8 * i + 6], x[8 * i + 7])), "r"((bar ^ 0x1000000) + BAR_GX + 8) : "memory")
    if (GE) {
        wg_fence();
        g_half<0, 28>(x, da);
        wg_commit();
        GFULL(29);
        wg_fence();
        g_half<0, 29>(x, da);
        wg_commit();
        GFULL(30);
        wg_fence();
        g_half<0, 30>(x, da);
        wg_commit();
        GFULL(31);
        wg_fence();
        g_half<0, 31>(x, da);
        wg_commit();
        g_half<64, 28>(y, da);
        if (GE == 2) g_half<64, 29>(y, da);
        wg_commit();
        wg_wait<1>();
        g_done(x);
        GFREE();
        GSEND(0);
        wg_fence();
        if (GE != 2) g_half<64, 29>(y, da);
        if (GE != 1) g_half<64, 30>(y, da);
        wg_commit();
        mwait(bar + BAR_GX, 0);
        GSEND(4);
        wg_fence();
        if (GE == 1) g_half<64, 30>(y, da);
        g_half<64, 31>(y, da);
        wg_commit();
        mwait(bar + BAR_GX + 8, 0);
        if (threadIdx.x == 0) PG(1);
#pragma unroll
        for (int i = 0; i < 8; i++) {
            const uint4 a = lds128(sb + GSW(i) + t16);
            float* e = x + 8 * i;
            e[0] = lo_f(a.x); e[1] = hi_f(a.x); e[2] = lo_f(a.y); e[3] = hi_f(a.y); e[4] = lo_f(a.z); e[5] = hi_f(a.z); e[6] = lo_f(a.w); e[7] = hi_f(a.w);
        }
        g_done(x);
        SF();
        wg_wait<0>();
        g_done(y);
        if (threadIdx.x == 0) PG(7);
    } else {
        GFREE();
        wg_fence();
        g_half<0, 29>(x, da);
        g_half<0, 30>(x, da);
        g_half<0, 31>(x, da);
        wg_commit();
        g_half<64, 29>(y, da);
        wg_commit();
        wg_wait<1>();
        g_done(x);
        mwait(bar + BAR_GX, 0);
        GSEND(0);
        wg_fence();
        g_half<64, 30>(y, da);
        wg_commit();
        GSEND(4);
        wg_fence();
        g_half<64, 31>(y, da);
        wg_commit();
        wg_wait<0>();
        g_done(y);
        if (threadIdx.x == 0) PG(7);
        mwait(bar + BAR_GX + 8, 0);
        if (threadIdx.x == 0) PG(1);
    }
    const uint32_t lane = threadIdx.x & 31, o = sb + GST(1) + w * 2048;
    char* go = (char*)out + ((role >> 3) * 128 + w * 16 + (lane >> 3)) * 4096 + (role & 7) * 256 + (lane & 7) * 16;
#pragma unroll
    for (int i = 0; i < 8; i++) {
        float* e = y + 8 * i;
        if (GE) {
#pragma unroll
            for (int n = 0; n < 8; n++) e[n] += x[8 * i + n];
        } else {
            const uint4 a = lds128(sb + i * 4096 + t16);
            e[0] += lo_f(a.x); e[1] += hi_f(a.x); e[2] += lo_f(a.y); e[3] += hi_f(a.y); e[4] += lo_f(a.z); e[5] += hi_f(a.z); e[6] += lo_f(a.w); e[7] += hi_f(a.w);
        }
        stsm4(o + (i >> 2) * 49152 + (lane & 15) * 128 + ((((i & 3) * 2 + (lane >> 4)) ^ (lane & 7)) << 4),
              pack2(e[0], e[1]), pack2(e[2], e[3]), pack2(e[4], e[5]), pack2(e[6], e[7]));
        if (i == 3 || i == 7) {
            if (GS) {
                __syncwarp();
#pragma unroll
                for (int m = 0; m < 4; m++)
                    *(uint4*)(go + m * 16384 + (i >> 2) * 128) =
                        lds128(o + (i >> 2) * 49152 + m * 512 + (lane >> 3) * 128 + (((lane & 7) ^ ((m & 1) * 4 + (lane >> 3))) << 4));
            } else {
                asm volatile("fence.proxy.async.shared::cta;" ::: "memory");
                __syncwarp();
                if (elect())
                    asm volatile("cp.async.bulk.tensor.2d.global.shared::cta.bulk_group [%0, {%2, %3}], [%1];\ncp.async.bulk.commit_group;"
                                 ::"l"(tmy), "r"(o + (i >> 2) * 49152), "r"((role & 7) * 128 + (i >> 2) * 64), "r"((role >> 3) * 128 + w * 16) : "memory");
            }
        }
    }
    if (threadIdx.x == 0) PG(6);
    if (!GS) asm volatile("cp.async.bulk.wait_group.read 0;" ::: "memory");
}

DEVI void kvload(uint32_t sb, uint32_t u, uint32_t h, uint32_t j, int sg, uint32_t xlo, uint32_t xhi) {
    const uint32_t o = u == 0 ? 0 : 2048;
    mbar_expect(sb + SM_BAR + BAR_KV, 6144 - o);
    bulk_g2s(sb + SM_KV + u * 4096 + o, xlo + XO_XG + (((sg & 7) * 32 + h) * 4 + ((j + u) & 3)) * 6144 + o, xhi, 6144 - o, sb + SM_BAR + BAR_KV);
}
DEVI void helper_step(uint32_t sb, uint32_t w, uint32_t h, uint32_t j, uint32_t& l16, uint32_t xlo, uint32_t xhi, uint32_t zero, int s,
                      const CUtensorMap* tmx, const CUtensorMap* tmb) {
    const uint32_t u = w - 8, bq = sb + SM_BAR;
    bsync<1, 384>();
    PT(0);
    PDUMP();
    PT(1);
    if (s == NSEG - 2 && u < 2) g_arrive(xlo + XO_TK + 128, xhi, 256);
    uint32_t old = 0;
#define RCLEAR(n) if (RCP == (n) && u > 0 && s + 3 < NSEG) \
        asm volatile("{\n.reg .b64 a;\nmov.b64 a, {%1,%2};\natom.relaxed.gpu.global.exch.b32 %0, [a], 0;\n}" \
                     : "=r"(old) : "r"(xlo + XO_R + rpage(j, s + 2) + (u - 1) * 16384 + h * 128 + (l16 >> 2)), "r"(xhi) : "memory");
    RCLEAR(1);
    const bool gl = u == 0 || (u == 1 && h < 30);
    if (GP == 1 && s == NSEG - 1 && gl) g_load(sb, u, h * 4 + j, 1, xlo, xhi, tmb);
    const uint32_t ctag = ((s >> 1) & 1) ^ 1;
    const uint32_t av = xlo + ((s & 1) * 32 + h) * 8192 + u * 512;
    mbar_wait(bq + BAR_XA, (s + 1) & 1);
    if (B3 == 8) barv<5, 384>();
    bsync<8, 384>();
    const uint32_t t8 = clk(), gs = xlo + XO_XG + ((((s + 3) & 7) * 32 + h) * 4 + j) * 6144;
    RCLEAR(2);
    const bool se = B3 % 8 == 0 && SE && u == SEU && s + 3 < NSEG;
    if (se) {
        asm volatile("fence.proxy.async.shared::cta;" ::: "memory");
        if (SE == 1 && elect()) bulk_s2g(gs, xhi, sb + SM_XO, 4096);
    }
    if (B3 != 6 || u || SE == 2) delay_until(t8, DLY_V);
    if (se && SE == 2 && elect()) bulk_s2g(gs, xhi, sb + SM_XO, 4096);
    PT(4);
    int it = 0;
    uint4 d1, d2, d3;
    uint2 e1, e2, e3;
    const uint32_t ae = av - u * 512 + (u & 1) * 256;
    const uint32_t jv = JV(h, j);
#define VLOAD() { if (!VD) d1 = ldg4<XO_CV>(av + (jv ^ 1) * 2048 + l16, xhi); \
        d2 = ldg4<XO_CV>(av + (jv ^ 2) * 2048 + l16, xhi); d3 = ldg4<XO_CV>(av + (jv ^ 3) * 2048 + l16, xhi); \
        if (B3 == 6 && VX) { if (!VD) e1 = ldg2<XO_CV>(ae + (jv ^ 1) * 2048 + (l16 >> 1), xhi); \
                       e2 = ldg2<XO_CV>(ae + (jv ^ 2) * 2048 + (l16 >> 1), xhi); e3 = ldg2<XO_CV>(ae + (jv ^ 3) * 2048 + (l16 >> 1), xhi); } \
        if (VD) { d1 = lds128(sb + SM_VP + (s & 1) * 2048 + u * 512 + l16); \
                  if (B3 == 6 && VX) e1 = lds64(sb + SM_VP + (s & 1) * 2048 + (u & 1) * 256 + (l16 >> 1)); } }
#define XSEND(F, C) if (u < 2) { \
        if (F) asm volatile("fence.proxy.async.shared::cta;" ::: "memory"); \
        if ((C) && elect()) { \
            const uint32_t sg = s + 3 - u; \
            if (sg < NSEG) { \
                const uint32_t ga = xlo + XO_XG + (((sg & 7) * 32 + h) * 4 + (j ^ (2 * u))) * 6144, sa = sb + SM_XO + u * 6144; \
                if (u == 0) bulk_s2g(ga + (SE ? 4096 : 0), xhi, sa + (SE ? 4096 : 0), SE ? 2048 : 6144); \
                else bulk_red(ga, xhi, sa, 6144); \
            } \
        } \
    }
    if (B3 == 8) {
        bsync<3, 384>();
        if (DLY_S) delay_until(clk(), DLY_S);
        XSEND(true, true);
    } else if (B3 == 6 && u == 0) {
        const uint32_t ga = xlo + XO_XG + ((((s + 3) & 7) * 32 + h) * 4 + j) * 6144, o = SE == 1 || SE == 2 ? 4096 : 0;
        if (o) {
            asm volatile("fence.proxy.async.shared::cta;" ::: "memory");
            if (s + 3 < NSEG && elect()) bulk_s2g(ga, xhi, sb + SM_XO, o);
        }
        bsync<3, 288>();
        if (DLY_S) delay_until(clk(), DLY_S);
        asm volatile("fence.proxy.async.shared::cta;" ::: "memory");
        if (elect()) {
            if (SE == 3 && s + 3 < NSEG) bulk_s2g(ga + o, xhi, sb + SM_XO + o, 6144 - o);
            if (s + 2 < NSEG) bulk_red(xlo + XO_XG + ((((s + 2) & 7) * 32 + h) * 4 + (j ^ 2)) * 6144, xhi, sb + SM_XO + 6144, 6144);
            if (SE != 3 && s + 3 < NSEG) bulk_s2g(ga + o, xhi, sb + SM_XO + o, 6144 - o);
        }
    } else {
    if (B3 == 6) VLOAD();
    if (B3 && B3 < 6) {
        VLOAD();
        bsync<B3 == 2 ? 4 : 3, 384>();
        XSEND(true, B3 < 3 || B3 == 5 || (B3 == 4 && u == 0));
    }
    while (true) {
        if (B3 % 7 == 0) VLOAD();
        if (se && SE == 3 && it == 0 && elect()) bulk_s2g(gs, xhi, sb + SM_XO, 4096);
        uint32_t tg = or3(tagx2(d1.x, d1.z, ctag), tagx2(d2.x, d2.z, ctag), tagx2(d3.x, d3.z, ctag));
        if (B3 == 6 && VX) tg = or3(tg, tagx2(e1.x, e2.x, ctag), e3.x ^ ctag);
        const bool bad = any_bad(tg);
        if (B3 == 6 && VX) sts64(sb + SM_VS + (u & 1) * 256 + (l16 >> 1), hadd2(hadd2(e1.x, e2.x), e3.x), hadd2(hadd2(e1.y, e2.y), e3.y));
        sts128(sb + SM_VS + u * 512 + l16, hadd2(hadd2(d1.x, d2.x), d3.x), hadd2(hadd2(d1.y, d2.y), d3.y), hadd2(hadd2(d1.z, d2.z), d3.z),
               hadd2(hadd2(d1.w, d2.w), d3.w));
        if (VA) asm volatile("{\n.reg .pred p;\nsetp.eq.u32 p, %0, 0;\n@p bar.arrive 5, 384;\n}" ::"r"((uint32_t)bad) : "memory");
        if (B3 % 7 == 0) REFRESH();
        if (!bad) break;
        if (B3 % 7) { REFRESH(); VLOAD(); }
        if (++it > SPIN_LIMIT) die(it);
    }
    PC(26, it);
    PT(5);
    if (VB) barv<11, 384>();
    else if (!VA) barv<5, B3 == 6 ? 352 : 384>();
    }
    if (B3 % 7 == 0) {
        bsync<3, 384>();
        XSEND(true, true);
    }
    if (B3 == 3 || B3 == 4) XSEND(false, B3 == 3 || u == 1);
    PT(6);
    RCLEAR(0);
    PT(7);
    bsync<7, 384>();
    if (s + 1 < NSEG && elect()) kvload(sb, u, h, j, s + 1, xlo, xhi);
    RCLEAR(3);
    if (XLP == 1) xload(sb, u, j, s + 1, tmx);
    if (u < (B3 == 6 ? 1 : 2)) {
        asm volatile("cp.async.bulk.wait_group.read 0;" ::: "memory");
        if (elect()) {
            mbar_expect(bq + BAR_PI + ((s & 1) ^ 1) * 8, 6144);
            if (B3 == 6) mbar_expect(bq + BAR_PI + ((s & 1) ^ 1) * 8, 6144);
        }
    }
    PT(8);
    if (GP && s == NSEG - 2 && gl) g_wait(xlo + XO_TK + 128, xhi);
    if (s + 1 < NSEG) bsync<10, 384>();
    if (XLP == 0) xload(sb, u, j, s + 1, tmx);
    RCLEAR(4);
    if (s == NSEG - 2 && gl) {
        if (!GP) g_wait(xlo + XO_TK + 128, xhi);
        g_load(sb, u, h * 4 + j, 0, xlo, xhi, tmb);
        if (GP == 0 || GP == 3) g_load(sb, u, h * 4 + j, 1, xlo, xhi, tmb);
    }
    asm volatile("cp.async.bulk.wait_group 0;" ::: "memory");
    if (s + 1 < NSEG) mbar_wait(bq + BAR_KV, (s + 1) & 1);
    asm volatile("lop3.b32 %0, %0, %1, %2, 0x78;" : "+r"(l16) : "r"(old), "r"(zero));
    PT(15);
}
DEVI void tickets_done(uint32_t* tk) {
    if (atomicInc(tk + 2, gridDim.x / 2 - 64) == gridDim.x / 2 - 64) { tk[0] = 0; tk[1] = 0; }
}

__global__ void __cluster_dims__(2, 1, 1) __launch_bounds__(384, 1)
chain_kernel(const __grid_constant__ CUtensorMap tmq, const __grid_constant__ CUtensorMap tmk,
             const __grid_constant__ CUtensorMap tmv, const __grid_constant__ CUtensorMap tmo,
             const __grid_constant__ CUtensorMap tmx, const __grid_constant__ CUtensorMap tmb, const __grid_constant__ CUtensorMap tmy,
             const bf16* __restrict__ mem0, const bf16* __restrict__ xg,
             uint32_t xlo, uint32_t xhi, uint32_t zero, int nseg, bf16* __restrict__ out) {
    extern __shared__ __align__(1024) uint8_t smem[];
    const uint32_t tstart = clk();
    const uint32_t rk = smem_u32(smem) & 0x1000000;
    if (rk == 0 && (threadIdx.x & 31) == 0 && threadIdx.x - 32 < 32 * PW)
        sts32(SB0 + SM_ROLE + 4 + (threadIdx.x >> 3), probe(xlo + XO_PB + (threadIdx.x & 32) * 128 + (threadIdx.x & 64) * 256 + blockIdx.x * 16, xhi));
    __syncwarp();
    if ((smem_u32(smem) & 0xFFFFFF) != SB0) die(1 << 23);
    asm volatile("griddepcontrol.launch_dependents;" ::: "memory");
    const uint32_t w = __reduce_max_sync(0xFFFFFFFFu, threadIdx.x >> 5);
    const uint32_t sb = __reduce_max_sync(0xFFFFFFFFu, smem_u32(smem));
    const uint32_t bq = sb + SM_BAR;
    uint32_t l16 = __shfl_sync(0xFFFFFFFFu, (threadIdx.x & 31) * 16, threadIdx.x & 31);
    if (threadIdx.x == 0) {
        mbar_init(bq, 1);
        for (int i = 0; i < 24; i++) mbar_init(bq + BAR_WF + i * 8, i < 16 ? 1 : 8);
        mbar_init(bq + BAR_XA, 4); mbar_init(bq + BAR_KV, 4); mbar_init(bq + BAR_PI, 2); mbar_init(bq + BAR_PI + 8, 2);
        for (int i = 0; i < 14; i++) mbar_init(bq + BAR_GF + i * 8, i < 8 || i == 13 ? 1 : 8);
        mbar_expect(bq + BAR_GX + 8, 32768);
        mbar_init(bq + BAR_RO, 1);
        mbar_expect(bq + BAR_RO, 4);
        mbar_expect(bq + BAR_PI, 6144);
        mbar_expect(bq + BAR_PI, 6144);
        asm volatile("fence.mbarrier_init.release.cluster;" ::: "memory");
        asm volatile("fence.proxy.async.shared::cta;" ::: "memory");
    }
    __syncwarp();
    asm volatile("barrier.cluster.arrive.relaxed.aligned;" ::: "memory");
    if (w == 9) {
#pragma unroll 1
        for (int e = 0; e < 12; e++) sts128(sb + SM_WO + e * 512 + l16, 0, 0, 0, 0);
    }
    if (w == 8 && blockIdx.x < 128) {
        if (XPF && elect()) {
            asm volatile("cp.async.bulk.prefetch.L2.global [%0], 3072;" ::"l"((const char*)xg + blockIdx.x * 3072) : "memory");
            asm volatile("prefetch.tensormap [%0];\nprefetch.tensormap [%1];\nprefetch.tensormap [%2];\nprefetch.tensormap [%3];\nprefetch.tensormap [%4];"
                         ::"l"(&tmq), "l"(&tmx), "l"(&tmk), "l"(&tmv), "l"(&tmo) : "memory");
        }
#pragma unroll 1
        for (int i = 0; i < EPF; i++) {
            if (i) delay_until(clk(), EPD);
            if (elect())
                asm volatile("cp.async.bulk.prefetch.tensor.3d.L2.global [%0, {0, %1, %2}];" ::"l"(&tmq), "r"((blockIdx.x & 3) * 256 + i * 64), "r"((blockIdx.x >> 2) * 2) : "memory");
        }
    }
    if (rk == 0 && w <= PW) bsync<2, 32 * PW + 32>();
    asm volatile("barrier.cluster.wait.aligned;" ::: "memory");
    if (rk == 0 && threadIdx.x == 0) {
        uint32_t t1 = lds32(sb + SM_ROLE + 8), t0 = lds32(sb + SM_ROLE + 12);
        if (PW == 4) { t1 = min(t1, lds32(sb + SM_ROLE + 16)); t0 = min(t0, lds32(sb + SM_ROLE + 20)); }
        uint32_t side = (t0 < t1 ? 0u : 1u) ^ par(XO_PB);
        uint32_t* tk = (uint32_t*)(((uint64_t)xhi << 32) | (xlo + XO_TK));
        uint32_t t = atomicAdd(tk + side, 1u);
        if (t >= 32) {
            uint2 c;
            int it = 0;
            do {
                c = ldg2<XO_TK>(xlo, xhi);
                if (++it > SPIN_LIMIT) die(it);
            } while (c.x + c.y != gridDim.x / 2);
            t += (side ? c.x : c.y) - 32;
            side ^= 1;
            if (t >= 32) tickets_done(tk);
        }
#pragma unroll
        for (uint32_t r = 0; r < 2; r++)
            asm volatile("st.async.weak.shared::cluster.mbarrier::complete_tx::bytes.b32 [%0], %1, [%2];"
                         ::"r"(sb + SM_ROLE + (r << 24)), "r"(t * 4 + side * 2 + r), "r"(bq + BAR_RO + (r << 24)) : "memory");
    }
    __syncwarp();
    mbar_wait(bq + BAR_RO, 0);
    const uint32_t role = __reduce_max_sync(0xFFFFFFFFu, lds32(sb + SM_ROLE));
    if (role >= 128) return;
    const uint32_t h = role >> 2, j = role & 3;
    if (FTM && w == 11 && elect())
#pragma unroll
        for (uint32_t c = 0; c < FTM; c++) {
            mbar_expect(bq + BAR_WF + c * 8, 16384);
            tma3d(sb + SM_ST + c * 16384, &tmq, bq + BAR_WF + c * 8, 0, j * 256 + c * 64, h * 2);
        }

    if (w >= 8) {
        asm volatile("setmaxnreg.dec.sync.aligned.u32 24;");
        const uint32_t u = w - 8;
        if (u == 3) {
#pragma unroll 1
            for (uint32_t c = FTM; c < 16; c++) {
                if (c >= WIN) mbar_wait(bq + BAR_WF + (c - WIN) * 8, 0);
                if (l16 == 0) PG(16 + c);
                if (c == 12 + WOP) bsync<2, 64>();
                if (c >= 4 && c < 12 && c != 10) mbar_wait(bq + BAR_WE + (c - 4) * 8, 0);
                if (elect()) {
                    const uint32_t b = bq + BAR_WF + c * 8;
                    mbar_expect(b, 16384);
                    if (c >= 12) tma2d(sb + SM_WO + (c - 12) * WO_BOX, &tmo, b, j * 256 + (c - 12) * 64, h * 128);
                    else tma3d(c == 10 ? sb + SM_WV : sb + SM_ST + (c & 3) * 16384, c < 4 ? &tmq : c < 8 ? &tmk : &tmv, b, 0, j * 256 + ((c ^ (c >= 10)) & 3) * 64, h * 2);
                }
            }
#pragma unroll 1
            for (uint32_t c = 16 - WIN; c < 16; c++) mbar_wait(bq + BAR_WF + c * 8, 0);
            if (l16 == 0) PG(15);
        } else if (u == 0) {
            if (elect()) {
                mbar_expect(bq, 49152);
#pragma unroll 1
                for (uint32_t i = 0; i < 12; i++)
                    tma3d(sb + SM_X + (i < 4 ? i : i + 4) * 4096, &tmx, bq, 0, i < 8 ? i * 8 : (j ^ ((0xBD98u >> (i - 8) * 4) & 15)) * 8, j * 4);
            }
#pragma unroll 1
            for (int i = 0; i < 4; i++) xload(sb, i, j, -1, &tmx);
            bsync<3, 320>();
            if (l16 == 0) PG(32);
            if (GH && j == 0 && elect()) asm volatile("{\n.reg .b64 a;\nmov.b64 a, {%0,%1};\nred.relaxed.gpu.global.inc.u32 [a+64], 4;\n}" ::"r"(xlo + XO_FL + h * 128), "r"(xhi) : "memory");
            __syncwarp();
            g_arrive(xlo + XO_FL + h * 128, xhi, 4);
            if (WOP < 4) barv<2, 64>();
            if (l16 == 0) PG(33);
            g_wait(xlo + XO_FL + h * 128, xhi);
            if (l16 == 0) PG(34);
#pragma unroll 1
            for (int i = 0; i < 4; i++)
                if (elect()) kvload(sb, i, h, j, 0, xlo, xhi);
            mbar_wait(bq + BAR_KV, 0);
            if (l16 == 0) PG(14);
        } else if (u == 1) {
            const uint32_t l = l16 >> 4, x = h * 8 + (l >> 2), d = (x & ~31u) + (l & 3) * 8 + ((x & 31) >> 2) + (x & 3) * 2 * DM;
            const unsigned short* m0 = (const unsigned short*)mem0 + j * 256;
            const uint32_t v1 = m0[d] | (((l & 3) == 3 ? 0x4200u : m0[d + DM]) << 16);
            const uint32_t v3 = h < 8 ? m0[h * 32 + 24 + (l >> 2) + ((l & 3) * 2 + 1) * DM] | 0x42000000u : 0;
#pragma unroll 1
            for (uint32_t i = 0; i < 12; i++) {
                if (i == 10) { sts32(sb + SM_WO + 6144 + l * 4, v1); sts32(sb + SM_WO + 6272 + l * 4, v3); }
                asm volatile("fence.proxy.async.shared::cta;" ::: "memory");
                __syncwarp();
                const uint32_t c = (0x21924u >> ((i - 3) * 2)) & 3;
                if (elect()) {
                    if (i < 3) bulk_s2g(xlo + XO_XG + (i * 128 + role) * 6144, xhi, sb + SM_WO, 6144);
                    else bulk_s2g(xlo + XO_R + rpage(j, i < 6 ? 0 : i < 9 ? 1 : -1) + c * 16384 + h * 128, xhi, sb + SM_WO + (i < 10 ? 0 : 6144 + c * 64), 128);
                }
            }
            asm volatile("cp.async.bulk.wait_group 0;" ::: "memory");
            if (elect()) asm volatile("{\n.reg .b64 a;\nmov.b64 a, {%0,%1};\nred.relaxed.gpu.global.inc.u32 [a], 127;\n}" ::"r"(xlo + XO_TK + 12), "r"(xhi) : "memory");
            if (l16 == 0) PG(16);
            g_wait(xlo + XO_TK + 12, xhi);
            if (l16 == 0) PG(17);
            barv<5, 288>();
            bsync<8, 320>();
            asm volatile("fence.acq_rel.gpu;" ::: "memory");
        } else {
            GSYNC(0);
            mbar_wait(bq + BAR_WE + 48, 0);
#pragma unroll 1
            for (int e = 0; e < 24; e++) sts128(sb + SM_TR + 4096 + e * 512 + l16, 0, 0, 0, 0);
            barv<3, 320>();
            bsync<8, 320>();
#pragma unroll 1
            for (int i = 0; i < 4; i++) xload(sb, i, j, 0, &tmx);
        }
#pragma unroll 1
        for (int s = 0; s < nseg; s++) helper_step(sb, w, h, j, l16, xlo, xhi, zero, s, &tmx, &tmb);
        piwait(sb, 0, nseg - 2);
        bsync<9, 384>();
        GSYNC(1);
        if (!GS && w == 11 && elect()) asm volatile("prefetch.tensormap [%0];" ::"l"(&tmy) : "memory");
        if (GH && w == 10) { g_arrive(xlo + XO_FL + h * 128 + 64, xhi, 5); PG(2); }
        if (w < 10) {
            uint32_t kb = 2, heads = 0;
            asm volatile("fence.proxy.async.shared::cta;" ::: "memory");
            if (GH) {
                if (w == 9 && h >= 30) { kb = 0; heads = 0xFFFF; }
                else delay_until(clk(), GD);
            } else if (w == 9) {
                g_arrive(xlo + XO_TK + 192, xhi, 128);
                PG(2);
                if (h >= 30) { g_wait(xlo + XO_TK + 192, xhi); kb = 0; }
                PG(3);
            } else delay_until(clk(), GD);
#pragma unroll 1
            for (; kb < 32; kb++) {
                if (kb >= 4) mbar_wait(bq + BAR_GE + (kb & 3) * 8, ((kb >> 2) & 1) ^ 1);
                if (GH && ((heads >> (kb >> 1)) & 1)) {
                    int it = 0;
                    do {
                        uint32_t v;
                        asm volatile("{\n.reg .b64 a;\nmov.b64 a, {%1,%2};\nld.acquire.gpu.global.u32 %0, [a+64];\n}"
                                     : "=r"(v) : "r"(xlo + XO_FL + (role & 1) * 2048 + (l16 & 255) * 8), "r"(xhi) : "memory");
                        heads = __ballot_sync(0xFFFFFFFFu, v != 0);
                        if (++it > SPIN_LIMIT) die(it);
                    } while ((heads >> (kb >> 1)) & 1);
                    asm volatile("fence.proxy.async.global;" ::: "memory");
                    if (kb == 0) PG(3);
                }
                g_load(sb, w - 8, role, kb, xlo, xhi, &tmb);
            }
        }
        if (role == 0 && w == 11 && elect()) tickets_done((uint32_t*)(((uint64_t)xhi << 32) | (xlo + XO_TK)));
    } else {
        asm volatile("setmaxnreg.inc.sync.aligned.u32 240;");
        uint32_t Wq[16][4], Wk[16][4], Wv[NA][4];
        uint32_t t16, KA, KB, KC, KD;
        {
            const uint32_t lane = l16 >> 4, g = lane >> 2, t = lane & 3;
            const uint32_t rw = (((lane >> 4) & 1) * 8 + (lane & 7)) * 128u;
            const uint32_t off = rw + ((((w & 3) * 2 + ((lane >> 3) & 1)) ^ (lane & 7)) << 4);
            const uint32_t offo = rw + ((((w & 1) * 4 + ((lane >> 3) & 1)) ^ (lane & 7)) << 4);
            const uint32_t r = 2 * (t & 1) + (g >> 2);
            const uint32_t mk0 = t < 2 ? 0 : (r == 0 ? 2 * g > w : j + r < 4), mk1 = t < 2 ? 0 : (r == 0 ? 2 * g + 1 > w : j + r < 4);
            t16 = __shfl_sync(0xFFFFFFFFu, w * 512 + l16, lane);
            KA = __shfl_sync(0xFFFFFFFFu, (w * 512 + t * 64 + g * 8) | ((w * 512 + (g & 1) * 256 + (g >> 1) * 64 + t * 16) << 16), lane);
            KB = __shfl_sync(0xFFFFFFFFu, ((w >> 2) * WV_BOX + off) | mk0 | (mk1 << 1) |
                                              ((w * 256 + (g >> 2) * 4096 + (g & 3) * 64 + t * 16) << 16), lane);
            KC = __shfl_sync(0xFFFFFFFFu, ((lane & 7) * 1280 + (lane >> 3) * 128 + ((w ^ (lane & 7)) << 4)) | (((t >> 1) * 16 + g * 2) << 16) | ((t * 64 + g * 8) << 24), lane);
            KD = __shfl_sync(0xFFFFFFFFu, ((w >> 1) * WO_BOX + offo) | (((lane & 7) * 208 + (lane >> 3) * 16) << 16), lane);
            if (threadIdx.x == 0) PG(8);
#define WTAKE(W, c, k0) { mbar_wait(bq + BAR_WF + (c) * 8, 0); \
                _Pragma("unroll") for (int ks = 0; ks < 4; ks++) ldsm4t(W[(k0) + ks], sb + SM_ST + ((c) & 3) * 16384 + (KB & 0xFFF0) + ks * 2048); \
                if ((c) < 8) { __syncwarp(); if (elect()) mbar_arrive(bq + BAR_WE + (c) * 8); } }
#pragma unroll
            for (int c = 0; c < 4; c++) WTAKE(Wq, c, c * 4);
            mbar_wait(bq, 0);
            if (threadIdx.x == 0) PG(9);
            xstart<0>(sb, w, xlo + h * 24576, xhi, j, t16, KA, Wq);
            if (threadIdx.x == 0) PG(10);
#pragma unroll
            for (int c = 0; c < 4; c++) WTAKE(Wk, c + 4, c * 4);
            if (threadIdx.x == 0) PG(11);
            xstart<1>(sb, w, xlo + h * 24576, xhi, j, t16, KA, Wk);
            if (threadIdx.x == 0) PG(12);
            WTAKE(Wv, 8, 0);
            WTAKE(Wv, 9, 4);
            mbar_wait(bq + BAR_WF + 80, 0);
            WTAKE(Wv, 11, 8);
            if (threadIdx.x == 0) PG(13);
            xstart<2>(sb, w, xlo + h * 24576, xhi, j, t16, KA, Wv);
            mbar_wait(bq + BAR_XA, 0);
            bsync<8, 320>();
        }
        const uint32_t ONES = 0x3F803F80u;
#define UNI(x) __reduce_max_sync(0xFFFFFFFFu, x)
        uint32_t swi = UNI((uint32_t)((uint64_t)smem >> 32));
        const uint32_t sbw = UNI(sb + w * 256), sbm = UNI(sb - w * 512), sbs = UNI(sb + w * 768), sbp = UNI(sb + w * 208);
#define OPQALL() { OPQ(t16); OPQ(KA); OPQ(KB); OPQ(KC); OPQ(KD); }
        OPQALL();
        if (SEED & 1) OPQ(Wq[0][0]);
        if (SEED & 2) OPQ(Wq[5][1]);
        if (SEED & 4) OPQ(Wk[0][0]);
        if (SEED & 8) OPQ(Wk[15][2]);
        if (SEED & 16) OPQ(Wv[0][0]);
        if (SEED & 32) OPQ(Wv[7][3]);
        const uint32_t cb0 = (h >> 1) * 32768 + (j & 1) * 16384 + (h & 1) * 8192;
        const uint32_t cb = UNI(xlo + cb0 + ((par(cb0) ^ (j >> 1) ^ CFAR) << 12)), cv = UNI(xlo + h * 8192 + JV(h, j) * 2048), h1 = UNI((h & 1) * 1024);
        const uint32_t uox = UNI(xlo + XO_OX + (h * 2 + (w >> 2)) * 262144 + j * 1024 + (w & 3) * 256 - w * 128);
        uint32_t rp = UNI(xlo + rpage(j, 0));
        float ox[4];
        float4 dn;
#define OXSTORE(s) asm volatile("{\n.reg .b64 a;\nmov.b64 a, {%0,%1};\nst.global.u32 [a], %2;\nst.global.u32 [a+128], %3;\n}" \
                                ::"r"(uox + (s) * 4096 + (t16 >> 2)), "r"(xhi), \
                                  "r"(pack2(ox[0] * dn.y, ox[1] * dn.w)), "r"(pack2(ox[2] * dn.y, ox[3] * dn.w)) : "memory")
#pragma unroll 1
        for (int s2 = 0;; s2 += 2, rp ^= 0x21000)
#pragma unroll
        for (int p = 0; p < 2; p++) {
            const int s = s2 + p;
            const uint32_t ctag = ((s2 >> 1) & 1) ^ 1;
            const uint32_t hb = cb ^ (p * 0x81000), rb = rp ^ (p * 0x11000);
            uint4 k0, k1, qq, c0, c1, c2, c3, pk;
            float va[4], vb[4];
            uint32_t qx0, qx1, ov0, ov1, wv[16 - NA][4];
            {
                float xa[16], xb[16];
                uint4 m0, n0;
                uint32_t e0, f0;
                uint32_t xp[8];
                wg_fence();
                XMMA(0, 6);
                SF();
                piwait(sb, p, s - 2);
                uint4 pi = xpeer<0>(sb, p ^ 1, t16);
                SF();
#define MR (VC ? 1 : 2)
#define MC (VC ? 2 : 1)
#define QPARK() { xpack<0>(xp, xa); xpark<0>(xp, pi, sb, sbw, p ^ 1, t16, KA); pi = xpeer<MR>(sb, p ^ 1, t16); SF(); }
                wg_fence();
                if (QP) {
                    XMMA(6, QP);
                    XMMA(QP, QP + 4);
                    wg_wait<1>();
                    SF();
                    QPARK();
                    wg_fence();
                    if (QP + 4 < RPOS) XMMA(QP + 4, RPOS);
                } else XMMA(6, RPOS);
                if (RPOS < 32) XMMA(RPOS, RPOS + 4 < 32 ? RPOS + 4 : 32);
                uint32_t a = (p ? rp : rp ^ 0x30000) + t16, e = (p ? rp : rp ^ 0x30000) + (t16 >> 2), ah = xhi, eh = xhi;
                OPQ(a); OPQ(e); OPQ(ah); OPQ(eh);
                SF();
                wg_wait<(RPOS < 32)>();
                SF();
                PT(11);
                RLOAD();
                SF();
                if (!QP) QPARK();
                if (RPOS + 4 < 32) {
                    wg_fence();
                    XMMA(RPOS + 4, 32);
                    SF();
                }
                wg_wait<0>();
                xpack<MR>(xp, xb);
                xpark<MR>(xp, pi, sb, sbw, p ^ 1, t16, KA);
                SF();
                PT(12);
                {
                    int it = 0;
                    while (ruse(sb + SM_MEMT + t16, m0, n0, e0, f0)) {
                        RLOAD();
                        if (++it > SPIN_LIMIT) die(it);
                    }
                    PC(22, it + 1);
                }
                PT(13);
                OPQ(KA); OPQ(t16);
                uint32_t acw = hb + (KA & 0xFFFF), ahi = xhi, tg = ctag;
                OPQ(acw); OPQ(ahi); OPQ(tg);
                SF();
                bsync<1, 384>();
                PT(0);
                uint32_t b[8][4];
#pragma unroll
                for (int i = 0; i < 8; i++) {
                    const int pp = i < 2 ? i : i ^ 1;
                    ldsm4t(b[pp], sbm + SM_MEMT + t16 + pp * 512);
                    if (i < 7) MF();
                }
                if (ASF) SF();
                float q[4], k[4];
                const uint32_t aWv = sb + SM_WV + (KB & 0xFFF0);
#define WVLD(n0, n1) _Pragma("unroll") for (int n = (n0); n < (n1) && n < 16 - NA; n++) ldsm4t(wv[n], aWv + n * 2048)
#pragma unroll
                for (int ks = 0; ks < 16; ks++) {
                    const uint32_t b0 = b[ks >> 1][(ks & 1) * 2], b1 = b[ks >> 1][(ks & 1) * 2 + 1];
                    if (ks == 0) {
                        mma16z(q, Wq[0][0], Wq[0][1], Wq[0][2], Wq[0][3], b0, b1);
                        mma16z(k, Wk[0][0], Wk[0][1], Wk[0][2], Wk[0][3], b0, b1);
                    } else {
                        mma16(q, Wq[ks][0], Wq[ks][1], Wq[ks][2], Wq[ks][3], b0, b1);
                        mma16(k, Wk[ks][0], Wk[ks][1], Wk[ks][2], Wk[ks][3], b0, b1);
                    }
                    if (ks == 10 && VPF) { SF(); WVLD(0, VPF); }
                }
                const uint32_t oq0 = settag(pack2(q[0], q[2]), tg), oq1 = settag(pack2(q[1], q[3]), tg);
                const uint32_t ok0 = pack2(k[0], k[2]), ok1 = pack2(k[1], k[3]);
                stg2<XO_CQK>(acw, ahi, oq0, ok0);
                stg2<XO_CQK + 256>(acw, ahi, oq1, ok1);
                SF();
                PT(1);
#define CLOADG() { c2 = ldg4<XO_CQK>((hb ^ 0x1000) + (KA >> 16), xhi); c3 = ldg4<XO_CQK>((hb ^ 0x5000) + (KA >> 16), xhi); }
#define CLOAD0() c0 = lds128(sb + SM_TR + (KA >> 16))
#define CLOAD1() c1 = lds128(sb + SM_TR + 4096 + p * 4096 + (KA >> 16))
#define CLOADS() { CLOAD0(); CLOAD1(); }
#define CSIDE(n) { if (CGP == (n)) CLOADG(); if (C0P == (n)) CLOAD0(); if (C1P == (n)) CLOAD1(); if (PIP == (n)) pk = xpeer<MC>(sb, p ^ 1, t16); \
                   if (QSP == (n)) { qx0 = (t16 & 64) ? qq.y : qq.x; qx1 = (t16 & 64) ? qq.w : qq.z; } }
#pragma unroll
                for (int rd = 0; rd < 8; rd++) {
                    const int pp = (VORD >> (28 - 4 * rd)) & 7;
                    const uint32_t* a = 2 * pp < NA ? Wv[2 * pp < NA ? 2 * pp : 0] : wv[2 * pp < NA ? 0 : 2 * pp - NA];
                    const uint32_t* c = 2 * pp < NA ? Wv[2 * pp < NA ? 2 * pp + 1 : 0] : wv[2 * pp < NA ? 0 : 2 * pp + 1 - NA];
                    if (rd == 0) {
                        mma16z(va, a[0], a[1], a[2], a[3], b[pp][0], b[pp][1]);
                        mma16z(vb, c[0], c[1], c[2], c[3], b[pp][2], b[pp][3]);
                        if (VSB & 256) SF();
                        OPQ(swi);
                        asm volatile("{\n.reg .b64 a;\nmov.b64 a, {%0,%1};\nst.v2.u32 [a], {%2,%3};\nst.v2.u32 [a+256], {%4,%5};\n}"
                                     ::"r"((KA & 0xFFF) + (sb ^ 0x1000000) + SM_TR + 4096 + p * 4096), "r"(swi), "r"(oq0), "r"(ok0), "r"(oq1), "r"(ok1) : "memory");
                        sts64(sb + SM_TR + (KA & 0xFFF), oq0, ok0);
                        sts64(sb + SM_TR + (KA & 0xFFF) + 256, oq1, ok1);
                    } else {
                        mma16(va, a[0], a[1], a[2], a[3], b[pp][0], b[pp][1]);
                        mma16(vb, c[0], c[1], c[2], c[3], b[pp][2], b[pp][3]);
                    }
                    if (rd == KEP) { KEEP(t16, oq0, oq1, ok0, ok1); if (KE2) KEEP(t16, acw, ahi, acw, ahi); }
                    if ((VSB >> rd) & 1) SF();
                    if (rd == W2P) WVLD(2, 3);
                    if (rd == W3P) WVLD(3, 4);
                    if (rd == K0P) k0 = lds128(sb + SM_KV + 2048 + (KB >> 16));
                    if (rd == K0P + 1) k1 = lds128(sb + SM_KV + 10240 + (KB >> 16));
                    if (rd == QQP) qq = lds128(sbw + SM_KV + ((KA >> 16) & 0xFF));
                    CSIDE(rd);
                    if ((VSF >> rd) & 1) SF(); else if ((VMF >> rd) & 1) MF();
                }
#define VTAIL() { ov0 = pack2(va[0] + vb[0], va[1] + vb[1]); ov1 = pack2(va[2] + vb[2], va[3] + vb[3]); \
                  stg2<XO_CV>(cv + p * 262144 + (t16 >> 1), xhi, settag(ov0, ctag), ov1); \
                  if (VD) asm volatile("{\n.reg .b64 a;\nmov.b64 a, {%0,%1};\nst.v2.u32 [a], {%2,%3};\n}" \
                                     ::"r"((t16 >> 1) + (sb ^ 0x1000000) + SM_VP + p * 2048), "r"(swi), "r"(settag(ov0, ctag)), "r"(ov1) : "memory"); \
                  barv<8, 384>(); OPQ(t16); SF(); }
                if (!VTP) VTAIL();
            }
            PT(2);
            PDUMP();
            {
                const uint32_t a0 = sb + SM_KV;
                float xa[16], xb[16];
                uint32_t xp[8];
                if (CGP == 12 || QSP == 12) { CSIDE(12); SF(); }
                wg_fence();
                XMMA(32, 32 + CPOS);
                if (CGP == 13) { SF(); CSIDE(13); SF(); wg_fence(); }
                if (VR == 1) { XMMA(32 + CPOS, 36); XMMA(36, 36 + CW2); wg_wait<2>(); }
                else if (CW) { XMMA(32 + CPOS, 36 + CPOS); wg_wait<1>(); }
                SF();
                CSIDE(8);
                SF();
                if (VR == 1) { wg_wait<1>(); SF(); }
                if (VTP) VTAIL();
                CSIDE(9);
                SF();
                wg_fence();
                XMMA(VR == 1 ? 36 + CW2 : 32 + CPOS + (CW ? 4 : 0), 48);
                SF();
                uint2 u1, u2, u3;
#define ULOADG() { u2 = ldg2<XO_CV>((cv ^ 4096) + p * 262144 + (t16 >> 1), xhi); u3 = ldg2<XO_CV>((cv ^ 6144) + p * 262144 + (t16 >> 1), xhi); }
#define ULOADS() u1 = lds64(sb + SM_VP + p * 2048 + (t16 >> 1))
#define UCHECK() { int it = 0; \
                   while (__builtin_expect(any_bad(tagx1(tagx2(u2.x, u3.x, ctag), u1.x, ctag)), 0)) { OPQ(t16); ULOADG(); ULOADS(); if (++it > SPIN_LIMIT) die(it); } \
                   PC(26, it); }
                CSIDE(10);
                if (B3 == 8 && VLP == 2) ULOADG();
                SF();
                const uint32_t ka[4] = {k0.x, k0.y, k0.z, k0.w}, kb[4] = {k1.x, k1.y, k1.z, k1.w};
                const uint32_t aSp = sb + SM_SP + (KC & 0xFFFF);
                PT(3);
#define BAR3() asm volatile("{\n.reg .pred p;\nsetp.eq.u32 p, %0, 0;\n@p bar.arrive 3, %1;\n}" ::"r"((uint32_t)bad), "n"(B3 == 6 ? 288 : 384) : "memory")
#define SCORES(FIRST) { \
                    const uint32_t qA = hadd2(hadd2(c0.x, c1.x), hadd2(c2.x, c3.x)), qB = hadd2(hadd2(c0.z, c1.z), hadd2(c2.z, c3.z)); \
                    const uint32_t kA = hadd2(hadd2(c0.y, c1.y), hadd2(c2.y, c3.y)), kB = hadd2(hadd2(c0.w, c1.w), hadd2(c2.w, c3.w)); \
                    bad = any_bad(or3(tagx2(c1.x, c1.z, ctag), tagx2(c2.x, c2.z, ctag), tagx2(c3.x, c3.z, ctag))); \
                    float sa[4], sb_[4], sc[4], sd[4], se[4]; \
                    if (FIRST) { SF(); if (B3 == 8 && VLP == 3) ULOADG(); CSIDE(11); wg_wait<0>(); } \
                    mma16z(sa, ka[0], ka[1], ka[2], ka[3], qA, qB); \
                    mma16z(sb_, kb[0], kb[1], kb[2], kb[3], qA, qB); \
                    mma16z(sc, qA, qx0, qB, qx1, kA, kB); \
                    if (FIRST) { \
                        xpack<MC>(xp, xa); \
                        if (KPOS == 0) { xadd(xp, pk); xstore<MC>(xp, sb, sbw, p ^ 1, t16, KA); if (B3 >= 5) BAR3(); else if (!B3 || B3 >= 3) barv<3, 384>(); } \
                        mma16z(sd, ka[0], ka[1], ka[2], ka[3], qx0, qx1); \
                        mma16z(se, kb[0], kb[1], kb[2], kb[3], qx0, qx1); \
                    } \
                    stsm4t(aSp, pack2(sa[0], sa[1]), pack2(sa[2], sa[3]), pack2(sb_[0], sb_[1]), pack2(sb_[2], sb_[3])); \
                    stsm2(aSp + 1024, pack2(sc[0], sc[1]), pack2(sc[2], sc[3])); \
                    if (FIRST) { \
                        stsm4t(aSp + 512, pack2(sd[0], sd[1]), pack2(sd[2], sd[3]), pack2(se[0], se[1]), pack2(se[2], se[3])); \
                        if (KPOS == 0) { KEEP(KD, xp[0], xp[1], xp[2], xp[3]); KEEP(KD, xp[4], xp[5], xp[6], xp[7]); } \
                    } }
                int it = 0;
                bool bad;
                SCORES(true);
                while (__builtin_expect(bad, 0)) {
                    OPQ(KA);
                    CLOADG();
                    CLOADS();
                    SCORES(false);
                    if (B3 >= 5) BAR3();
                    if (++it > SPIN_LIMIT) die(it);
                }
                PC(25, it);
                PT(4);
                if (B3 == 8 && VLP == 0) ULOADG();
                if (B3 == 1) barv<3, 384>();
                bsync<4, B3 == 2 ? 384 : 256>();
                uint32_t wo[16][4];
                const uint32_t aWo = sb + SM_WO + (KD & 0xFFFF), aWo1 = sb + SM_WO + ((KD & 0xFFFF) ^ 32);
#define WOLD(n0, n1) _Pragma("unroll") for (int n = (n0); n < (n1) && n < 16; n++) ldsm4t(wo[n], ((n & 1) ? aWo1 : aWo) + (n >> 1) * 2048)
                const bool hi = (t16 & 32) != 0;
                const uint32_t t8 = t16 >> 1;
                uint2 v0, v1, v2, v3;
                uint32_t es;
                {
                    uint32_t am[4], ax[4], a4[2];
                    const uint32_t aSr = sbs + SM_SP + t16;
                    ldsm4t(am, aSr);
                    ldsm4t(ax, aSr + 512);
                    ldsm2t(a4, aSr + 1024);
                    MF();
                    if (B3 == 8 && VLP == 1) ULOADG();
                    if (KPOS == 1) pk = xpeer<MC>(sb, p ^ 1, t16);
                    const uint32_t se = (t16 & 128) ? 0u : ONES, so = se ^ ONES;
                    float hm[4], hx[4], h4[4];
                    mma16z(hm, am[0], am[1], am[2], am[3], se, so);
                    mma16z(hx, ax[0], ax[1], ax[2], ax[3], se, so);
                    mma8z(h4, a4[0], a4[1], ONES);
                    SF();
                    if (KPOS == 1) { xpark<MC>(xp, pk, sb, sbw, p ^ 1, t16, KA); barv<3, 384>(); }
                    v0 = lds64(a0 + 4096 + t8); v1 = lds64(a0 + 8192 + t8); v2 = lds64(a0 + 12288 + t8); v3 = lds64(a0 + 16384 + t8);
                    if (B3 == 8) ULOADS();
                    WOLD(0, PF2);
                    float s0 = hi ? hx[0] : hm[0], s1 = hi ? hx[2] : hm[2];
                    const float s2 = hi ? h4[2] : h4[0];
                    s0 = (KB & 1) ? -1.0e9f * 11.313708499f : s0;
                    s1 = (KB & 2) ? -1.0e9f * 11.313708499f : s1;
                    int mi = __float_as_int(fmaxf(fmaxf(s0, s2), s1));
                    mi ^= (mi >> 31) & 0x7FFFFFFF;
                    const int mm = __reduce_max_sync(0xFFFFFFFFu, hi ? (int)0x80000000 : mi), mx = __reduce_max_sync(0xFFFFFFFFu, hi ? mi : (int)0x80000000);
                    SF();
                    WOLD(PF2, PF3);
                    SF();
                    mi = hi ? mx : mm;
                    mi ^= (mi >> 31) & 0x7FFFFFFF;
                    const float c2_ = 0.08838834764831845f * 1.4426950408889634f;
                    const float mc = __int_as_float(mi) * c2_;
                    const float e0 = ex2(fmaf(s0, c2_, -mc)), e1 = ex2(fmaf(s1, c2_, -mc)), e2 = ex2(fmaf(s2, c2_, -mc));
                    sts32(sbp + SM_P + (KC >> 25), pack2(e0, e1));
                    sts16(sbp + SM_P + 128 + ((KC >> 16) & 0xFF), pack2(e2, e2));
                    es = __float_as_uint(fmaf(e2, 0.5f, e0 + e1) + 64.f);
                }
                const uint32_t sm = __reduce_add_sync(0xFFFFFFFFu, hi ? 0u : es), sx = __reduce_add_sync(0xFFFFFFFFu, hi ? es : 0u);
                const uint32_t aPr = sb + SM_P + (KD >> 16);
                if (B3 == 8 && VCP == 0) UCHECK();
                PT(5);
                bsync<5, VB ? 256 : B3 == 6 ? 352 : 384>();
                uint32_t pm[4], px[4], p4[2];
                ldsm4(pm, aPr);
                MF();
                uint2 vs;
                #define VGET(n) if (VB == (n)) { if (VB) bsync<11, 384>(); vs = lds64(sb + SM_VS + t8); MF(); }
                if (B3 != 8) { VGET(0); VGET(1); }
                ldsm2(p4, aPr + 128);
                MF();
                VGET(2);
                ldsm4(px, aPr + 64);
                MF();
                VGET(3);
                sts32f(sb + SM_DN + w * 8 + ((t16 >> 3) & 4), rcp(__uint_as_float((hi ? sx : sm) - 15u * 0x42800000u) - 64.f));
                MF();
                if (B3 == 8 && VCP == 2) UCHECK();
                WOLD(PF3, NPF);
                if (B3 == 8 && VCP == 1) UCHECK();
                if (B3 == 8) { ov0 = hadd2(ov0, u1.x); ov1 = hadd2(ov1, u1.y); vs.x = hadd2(u2.x, u3.x); vs.y = hadd2(u2.y, u3.y); }
                const uint32_t vm0 = hadd2(ov0, vs.x), vm1 = hadd2(ov1, vs.y);
                float oa[4], ob[4];
                mma16z(oa, v0.x, v0.y, v1.x, v1.y, pm[0], pm[1]);
                mma16z(ob, v2.x, v2.y, v3.x, v3.y, pm[2], pm[3]);
                mma8(oa, vm0, vm1, p4[0]);
                stsm2(sbw + SM_OT + (t16 & 511), pack2(oa[0] + ob[0], oa[1] + ob[1]), pack2(oa[2] + ob[2], oa[3] + ob[3]));
                PT(6);
                SF();
                bsync<6, 256>();
                mma16z(ox, v0.x, v0.y, v1.x, v1.y, px[0], px[1]);
                uint32_t b[4][4];
#define OTLD(pp) ldsm4t(b[pp], sbm + SM_OT + t16 + (pp) * 512)
                OTLD(0);
                MF();
                OTLD(1);
                barv<7, 384>();
                mma16(ox, v2.x, v2.y, v3.x, v3.y, px[2], px[3]);
                mma8(ox, vm0, vm1, p4[1]);
                if (p == 1 && s + 1 == nseg) goto done;
                SF();
                uint32_t ar, ae, ahi = xhi;
                float r[2][4];
#pragma unroll
                for (int ks = 0; ks < 8; ks++) {
                    if (ks == 0) WOLD(NPF, NPF + WPF);
                    if (ks == OPOS) { OTLD(2); MF(); }
                    if (ks == OPOS + 2) { OTLD(3); MF(); }
                    if (ks > 0) WOLD(NPF + WPF + 2 * (ks - 1), NPF + WPF + 2 * ks);
                    if (ks == 5) {
                        OPQ(t16);
                        ar = rb + h1 * 16 + t16; ae = rb + h1 + (t16 >> 2);
                        OPQ(ar); OPQ(ahi); OPQ(ae);
                        dn = lds128f(sb + SM_DN + (t16 & 48));
                    }
#pragma unroll
                    for (int mt = 0; mt < 2; mt++) {
                        const int i = ks * 2 + mt;
                        const uint32_t* a = wo[i];
                        if (i < 2) mma16z(r[mt], a[0], a[1], a[2], a[3], b[ks >> 1][2 * (ks & 1)], b[ks >> 1][2 * (ks & 1) + 1]);
                        else mma16(r[mt], a[0], a[1], a[2], a[3], b[ks >> 1][2 * (ks & 1)], b[ks >> 1][2 * (ks & 1) + 1]);
                    }
                    if (NPF + WPF + 2 * ks < 16 || ks < 5) SF();
                }
                const float r0 = dn.x, r1 = dn.z;
                asm volatile("{\n.reg .b64 a;\nmov.b64 a, {%0,%2};\nred.relaxed.gpu.global.add.noftz.v4.bf16x2 [a], {%3,%4,%5,%6};\n"
                             "mov.b64 a, {%1,%2};\nred.relaxed.gpu.global.add.noftz.bf16x2 [a+32768], %7;\n}"
                             ::"r"(ar), "r"(ae), "r"(ahi), "r"(pack2(r[0][0] * r0, r[0][1] * r1)), "r"(pack2(r[0][2] * r0, r[0][3] * r1)),
                               "r"(pack2(r[1][0] * r0, r[1][1] * r1)), "r"(pack2(r[1][2] * r0, 1.f)), "r"(pack2(r[1][3] * r1, 1.f)) : "memory");
                barv<10, 384>();
            }
            SF();
            PT(10);
            OXSTORE(s);
            OPQALL();
        }
    done:
        dn = lds128f(sb + SM_DN + (t16 & 48));
        OXSTORE(nseg - 1);
        barv<9, 384>();
        g_main(sb, w, role, &tmy, out);
        if (threadIdx.x == 0) PG(0);
    }
}

template <int SC> DEVI void wg_rs128t(float (&d)[64], const uint32_t (&a)[4], uint64_t db) {
    if (SC) asm volatile("wgmma.mma_async.sync.aligned.m64n128k16.f32.bf16.bf16 "
        "{%0,%1,%2,%3,%4,%5,%6,%7,%8,%9,%10,%11,%12,%13,%14,%15,%16,%17,%18,%19,%20,%21,%22,%23,%24,%25,%26,%27,%28,%29,%30,%31,%32,%33,%34,%35,%36,%37,%38,%39,%40,%41,%42,%43,%44,%45,%46,%47,%48,%49,%50,%51,%52,%53,%54,%55,%56,%57,%58,%59,%60,%61,%62,%63}, "
        "{%64,%65,%66,%67}, %68, 1, 1, 1, 1;"
        : D4(+, 0), D4(+, 4), D4(+, 8), D4(+, 12), D4(+, 16), D4(+, 20), D4(+, 24), D4(+, 28), D4(+, 32), D4(+, 36), D4(+, 40), D4(+, 44), D4(+, 48), D4(+, 52), D4(+, 56), D4(+, 60) : "r"(a[0]), "r"(a[1]), "r"(a[2]), "r"(a[3]), "l"(db));
    else asm volatile("wgmma.mma_async.sync.aligned.m64n128k16.f32.bf16.bf16 "
        "{%0,%1,%2,%3,%4,%5,%6,%7,%8,%9,%10,%11,%12,%13,%14,%15,%16,%17,%18,%19,%20,%21,%22,%23,%24,%25,%26,%27,%28,%29,%30,%31,%32,%33,%34,%35,%36,%37,%38,%39,%40,%41,%42,%43,%44,%45,%46,%47,%48,%49,%50,%51,%52,%53,%54,%55,%56,%57,%58,%59,%60,%61,%62,%63}, "
        "{%64,%65,%66,%67}, %68, 0, 1, 1, 1;"
        : D4(=, 0), D4(=, 4), D4(=, 8), D4(=, 12), D4(=, 16), D4(=, 20), D4(=, 24), D4(=, 28), D4(=, 32), D4(=, 36), D4(=, 40), D4(=, 44), D4(=, 48), D4(=, 52), D4(=, 56), D4(=, 60) : "r"(a[0]), "r"(a[1]), "r"(a[2]), "r"(a[3]), "l"(db));
}
template <int SC> DEVI void wg_rs64t(float (&d)[32], const uint32_t (&a)[4], uint64_t db) {
    if (SC) asm volatile("wgmma.mma_async.sync.aligned.m64n64k16.f32.bf16.bf16 "
        "{%0,%1,%2,%3,%4,%5,%6,%7,%8,%9,%10,%11,%12,%13,%14,%15,%16,%17,%18,%19,%20,%21,%22,%23,%24,%25,%26,%27,%28,%29,%30,%31}, "
        "{%32,%33,%34,%35}, %36, 1, 1, 1, 1;"
        : D4(+, 0), D4(+, 4), D4(+, 8), D4(+, 12), D4(+, 16), D4(+, 20), D4(+, 24), D4(+, 28) : "r"(a[0]), "r"(a[1]), "r"(a[2]), "r"(a[3]), "l"(db));
    else asm volatile("wgmma.mma_async.sync.aligned.m64n64k16.f32.bf16.bf16 "
        "{%0,%1,%2,%3,%4,%5,%6,%7,%8,%9,%10,%11,%12,%13,%14,%15,%16,%17,%18,%19,%20,%21,%22,%23,%24,%25,%26,%27,%28,%29,%30,%31}, "
        "{%32,%33,%34,%35}, %36, 0, 1, 1, 1;"
        : D4(=, 0), D4(=, 4), D4(=, 8), D4(=, 12), D4(=, 16), D4(=, 20), D4(=, 24), D4(=, 28) : "r"(a[0]), "r"(a[1]), "r"(a[2]), "r"(a[3]), "l"(db));
}
template <int SC> DEVI void wg_rs40(float (&d)[20], const uint32_t (&a)[4], uint64_t db) {
    if (SC) asm volatile("wgmma.mma_async.sync.aligned.m64n40k16.f32.bf16.bf16 "
        "{%0,%1,%2,%3,%4,%5,%6,%7,%8,%9,%10,%11,%12,%13,%14,%15,%16,%17,%18,%19}, "
        "{%20,%21,%22,%23}, %24, 1, 1, 1, 0;"
        : D4(+, 0), D4(+, 4), D4(+, 8), D4(+, 12), D4(+, 16) : "r"(a[0]), "r"(a[1]), "r"(a[2]), "r"(a[3]), "l"(db));
    else asm volatile("wgmma.mma_async.sync.aligned.m64n40k16.f32.bf16.bf16 "
        "{%0,%1,%2,%3,%4,%5,%6,%7,%8,%9,%10,%11,%12,%13,%14,%15,%16,%17,%18,%19}, "
        "{%20,%21,%22,%23}, %24, 0, 1, 1, 0;"
        : D4(=, 0), D4(=, 4), D4(=, 8), D4(=, 12), D4(=, 16) : "r"(a[0]), "r"(a[1]), "r"(a[2]), "r"(a[3]), "l"(db));
}
template <int SC> DEVI void wg_rs8(float (&d)[4], const uint32_t (&a)[4], uint64_t db) {
    if (SC) asm volatile("wgmma.mma_async.sync.aligned.m64n8k16.f32.bf16.bf16 "
        "{%0,%1,%2,%3}, "
        "{%4,%5,%6,%7}, %8, 1, 1, 1, 0;"
        : D4(+, 0) : "r"(a[0]), "r"(a[1]), "r"(a[2]), "r"(a[3]), "l"(db));
    else asm volatile("wgmma.mma_async.sync.aligned.m64n8k16.f32.bf16.bf16 "
        "{%0,%1,%2,%3}, "
        "{%4,%5,%6,%7}, %8, 0, 1, 1, 0;"
        : D4(=, 0) : "r"(a[0]), "r"(a[1]), "r"(a[2]), "r"(a[3]), "l"(db));
}
template <int SC> DEVI void wg_ss64a(float (&d)[32], uint64_t da, uint64_t db) {
    if (SC) asm volatile("wgmma.mma_async.sync.aligned.m64n64k16.f32.bf16.bf16 "
        "{%0,%1,%2,%3,%4,%5,%6,%7,%8,%9,%10,%11,%12,%13,%14,%15,%16,%17,%18,%19,%20,%21,%22,%23,%24,%25,%26,%27,%28,%29,%30,%31}, "
        "%32, %33, 1, 1, 1, 1, 0;"
        : D4(+, 0), D4(+, 4), D4(+, 8), D4(+, 12), D4(+, 16), D4(+, 20), D4(+, 24), D4(+, 28) : "l"(da), "l"(db));
    else asm volatile("wgmma.mma_async.sync.aligned.m64n64k16.f32.bf16.bf16 "
        "{%0,%1,%2,%3,%4,%5,%6,%7,%8,%9,%10,%11,%12,%13,%14,%15,%16,%17,%18,%19,%20,%21,%22,%23,%24,%25,%26,%27,%28,%29,%30,%31}, "
        "%32, %33, 0, 1, 1, 1, 0;"
        : D4(=, 0), D4(=, 4), D4(=, 8), D4(=, 12), D4(=, 16), D4(=, 20), D4(=, 24), D4(=, 28) : "l"(da), "l"(db));
}

#define G_ROWS 514
__device__ uint4 g_G[64 * G_ROWS * 8];
__device__ uint4 g_GN[64 * 8];
__device__ uint4 g_WN[1152];
#define FS_F2 196608
#define FS_TB (FS_F2 + 8192)
#define FS_NQ (FS_TB + 16384)
#define FS_BAR (FS_NQ + 128)
#define FS_NY (FS_NQ + 1024 + 128)
#define FS_TOTAL (FS_NQ + 3072)
#define F_THREADS 512

DEVI uint32_t cis(int j) {
    const float a = fmaf(__uint_as_float((((j + 1024) << 12) & 0x7FF000) | 0x3F800000), 6.283185307179586f, -9.42477796076938f);
    return pack2(__cosf(a), __sinf(a));
}
DEVI uint32_t cos2(int j0, int j1) {
    const float f = 6.283185307179586f / 2048.f;
    return pack2(__cosf((float)(((j0 + 1024) & 2047) - 1024) * f), __cosf((float)(((j1 + 1024) & 2047) - 1024) * f));
}
DEVI void twid(int j, float& c, float& s) {
    const float a = (float)(((j + 512) & 1023) - 512) * (6.283185307179586f / 1024.f);
    c = __cosf(a) * (1.f / 1024.f);
    s = __sinf(a) * (1.f / 1024.f);
}
template <bool B> struct Bool { static constexpr bool v = B; };
DEVI uint32_t opq(uint32_t& x, uint32_t zero) { OPQ(x); return x; }
DEVI uint32_t tidx() { uint32_t r; asm volatile("mov.u32 %0, %%tid.x;" : "=r"(r)); return r; }
DEVI void tma4d(uint32_t dst, const CUtensorMap* tm, uint32_t bar, int c0, int c1, int c2, int c3) {
    asm volatile("cp.async.bulk.tensor.4d.shared::cluster.global.mbarrier::complete_tx::bytes [%0], [%1, {%3, %4, %5, %6}], [%2];"
                 ::"r"(dst), "l"(tm), "r"(bar), "r"(c0), "r"(c1), "r"(c2), "r"(c3) : "memory");
}
DEVI void tma3s(const CUtensorMap* tm, uint32_t src, int c0, int c1, int c2) {
    asm volatile("cp.async.bulk.tensor.3d.global.shared::cta.bulk_group [%0, {%2, %3, %4}], [%1];" ::"l"(tm), "r"(src), "r"(c0), "r"(c1), "r"(c2) : "memory");
}
DEVI void tma4s(const CUtensorMap* tm, uint32_t src, int c0, int c1, int c2, int c3) {
    asm volatile("cp.async.bulk.tensor.4d.global.shared::cta.bulk_group [%0, {%2, %3, %4, %5}], [%1];"
                 ::"l"(tm), "r"(src), "r"(c0), "r"(c1), "r"(c2), "r"(c3) : "memory");
}
DEVI void bulk_commit() { asm volatile("cp.async.bulk.commit_group;" ::: "memory"); }
DEVI void fence_async() { asm volatile("fence.proxy.async;" ::: "memory"); }
DEVI void fence_smem() { asm volatile("fence.proxy.async.shared::cta;" ::: "memory"); }
DEVI void wgbar(uint32_t q) { asm volatile("bar.sync %0, 128;" ::"r"(q + 2) : "memory"); }
DEVI void grid_arrive(uint32_t* c, uint32_t n) { asm volatile("fence.proxy.async;\nred.release.gpu.global.inc.u32 [%0], %1;" ::"l"(c), "r"(n - 1) : "memory"); }
DEVI void grid_wait(uint32_t* c) {
    uint32_t v;
    int it = 0;
    do {
        asm volatile("ld.acquire.gpu.global.u32 %0, [%1];" : "=r"(v) : "l"(c) : "memory");
        if (++it > (1 << 22)) die(it);
    } while (v);
    fence_async();
}

template <bool INV, class S1, class S2>
DEVI void fft_rows(uint32_t grp, uint32_t q, const uint32_t (&F)[2][4], const float (&tc)[8], const float (&ts)[8], uint32_t so, float fx, uint32_t nq,
                   S1 sh1, S2 sh2) {
    float d[64];
    const uint64_t db = INV ? mkdesc(grp, 1024, 2048) : (mkdesc(grp, 2048, 512) ^ ((uint64_t)3 << 62));
    wg_fence();
    wg_rs128t<0>(d, F[0], db);
    wg_rs128t<1>(d, F[1], db + (INV ? 256 : 64));
    wg_commit();
    SF();
    sh1();
    float4 ny;
    if (INV) ny = lds128f(nq);
    wg_wait<0>();
    if (INV) { d[0] = fmaf(fx, ny.x, d[0]); d[16] = fmaf(fx, ny.y, d[16]); d[32] = fmaf(fx, ny.z, d[32]); d[48] = fmaf(fx, ny.w, d[48]); }
    uint32_t a[2][4][4];
    float e[2][INV ? 16 : 20];
    const uint64_t df = mkdesc(SB0 + FS_F2, 16, 1024);
#pragma unroll
    for (int s = 0; s < 2; s++) {
#pragma unroll
        for (int i = 0; i < 4; i++)
#pragma unroll
            for (int h = 0; h < 2; h++) {
                const float* x = d + (2 * s + h) * 16 + i * 4;
                a[s][i][h] = pack2(fmaf(x[2], ts[2 * i], x[0] * tc[2 * i]), fmaf(x[3], ts[2 * i + 1], x[1] * tc[2 * i + 1]));
                a[s][i][h + 2] = pack2(fmaf(-x[0], ts[2 * i], x[2] * tc[2 * i]), fmaf(-x[1], ts[2 * i + 1], x[3] * tc[2 * i + 1]));
            }
        wg_fence();
#pragma unroll
        for (int i = 0; i < 4; i++) {
            if constexpr (INV) { if (i == 0) wg_rs32<0>(e[s], a[s][i], df); else wg_rs32<1>(e[s], a[s][i], df + i * 2); }
            else { if (i == 0) wg_rs40<0>(e[s], a[s][i], df); else wg_rs40<1>(e[s], a[s][i], df + i * 2); }
        }
        wg_commit();
    }
    SF();
    sh2();
#pragma unroll
    for (int s = 0; s < 2; s++) {
        if (s == 0) wg_wait<1>(); else wg_wait<0>();
        float* x = e[s];
        if constexpr (!INV) {
            x[0] *= fx; x[1] *= fx; x[2] *= fx; x[3] *= fx;
            if (fx != 1.f) sts64(nq + s * 8, pack2(x[16], 0.f), pack2(x[18], 0.f));
        }
        const uint32_t o = grp + (INV ? so + s * 4096 : so ^ (s * 576));
#pragma unroll
        for (int b = 0; b < 2; b++)
            stsm4t(o + b * (INV ? 1024 : 4096), pack2(x[8 * b], x[8 * b + 1]), pack2(x[8 * b + 2], x[8 * b + 3]), pack2(x[8 * b + 4], x[8 * b + 5]),
                   pack2(x[8 * b + 6], x[8 * b + 7]));
    }
}

template <bool INV>
DEVI void fft_gen(uint32_t a, uint32_t n2) {
    const uint32_t tid = tidx(), x = ((tid >> 4) & 24) + (tid & 3), o = (tid & 4) * 128;
    if (INV) {
        const uint32_t r = (tid & 64) * 16 + (tid & 16) * 32 + (tid & 40) * 8 + n2;
        sts128(a + tid * 16, cis(o - r * x), cis(o - (r + 128) * x), cis(o - r * (x + 4)), cis(o - (r + 128) * (x + 4)));
    } else {
        const uint32_t r = 64 * x + n2, k = ((tid >> 2) & 24) + ((tid >> 3) & 3);
        sts128(a + tid * 16, cis(r * k + o), cis(r * (k + 4) + o), cis((r + 256) * k + o), cis((r + 256) * (k + 4) + o));
    }
}
template <bool INV, class S1>
DEVI void fft_cross(uint32_t buf, uint32_t q, uint32_t fa, uint32_t so, uint32_t nq, float (&n)[4], S1 sh1) {
    uint32_t F[4][4];
#pragma unroll
    for (int s = 0; s < 4; s++) { const uint4 v = lds128(fa + s * 2048); F[s][0] = v.x; F[s][1] = v.y; F[s][2] = v.z; F[s][3] = v.w; }
    float d[64];
    const uint64_t db = mkdesc(buf + q * 2048, 1024, 8192), dn = mkdesc(nq, 16, 1024);
    wg_fence();
#pragma unroll
    for (int s = 0; s < 4; s++) { if (s == 0) wg_rs128t<0>(d, F[s], db); else wg_rs128t<1>(d, F[s], db + s * 1024); }
#pragma unroll
    for (int s = 0; s < 4; s++) { if (s == 0) wg_rs8<0>(n, F[s], dn); else wg_rs8<1>(n, F[s], dn + s * 2); }
    wg_commit();
    SF();
    sh1();
    wg_wait<0>();
#pragma unroll
    for (int b = 0; b < 8; b++) {
        const uint32_t o = INV ? so ^ ((b >> 1) * 288 ^ (b & 1) * 32) : (so ^ ((b & 3) * 32)) + (b >> 2) * 1024;
        stsm4(buf + o, pack2(d[8 * b], d[8 * b + 1]), pack2(d[8 * b + 2], d[8 * b + 3]), pack2(d[8 * b + 4], d[8 * b + 5]), pack2(d[8 * b + 6], d[8 * b + 7]));
    }
}

template <bool ODD>
DEVI void fft_filter(uint32_t aw, const float (&e)[32], const float (&o)[32], uint32_t (&u)[4][4], uint32_t (&v)[4][4]) {
#pragma unroll
    for (int s = 0; s < 4; s++) {
        float y[2][2][4];
#pragma unroll
        for (int c = 0; c < 2; c++) {
            float f[4][2];
#pragma unroll
            for (int i = 0; i < 4; i++) {
                const uint32_t a = aw + (i * 32 + s * 8 + c) * 144, x = lds32(a);
                f[i][0] = ODD ? hi_f(x) : lo_f(x);
                f[i][1] = ODD ? lo_f(lds32(a + 4)) : hi_f(x);
            }
#pragma unroll
            for (int h = 0; h < 2; h++) {
                const int x = 8 * s + 2 * h + c;
                const float ar = e[x] + o[x], ai = e[x + 4] + o[x + 4], br = e[x] - o[x], bi = e[x + 4] - o[x + 4];
                const float yr = fmaf(-ai, f[2][h], ar * f[0][h]), yi = fmaf(ar, f[2][h], ai * f[0][h]);
                y[h][c][0] = fmaf(-bi, f[3][h], fmaf(br, f[1][h], yr));
                y[h][c][1] = fmaf(br, f[3][h], fmaf(bi, f[1][h], yi));
                y[h][c][2] = fmaf(2.f, yr, -y[h][c][0]);
                y[h][c][3] = fmaf(2.f, yi, -y[h][c][1]);
            }
        }
#pragma unroll
        for (int h = 0; h < 2; h++) {
            u[s][h] = pack2(y[h][0][0], y[h][1][0]); u[s][h + 2] = pack2(y[h][0][1], y[h][1][1]);
            v[s][h] = pack2(y[h][0][2], y[h][1][2]); v[s][h + 2] = pack2(y[h][0][3], y[h][1][3]);
        }
    }
}

__global__ void __launch_bounds__(F_THREADS, 1)
post_kernel(const __grid_constant__ CUtensorMap tmx, const __grid_constant__ CUtensorMap tmg1, const __grid_constant__ CUtensorMap tmg2,
           const __grid_constant__ CUtensorMap tmwr, const __grid_constant__ CUtensorMap tmwi, const __grid_constant__ CUtensorMap tmy,
           const bf16* __restrict__ wr, const bf16* __restrict__ wi, uint32_t* cnt, uint32_t zero, int nw) {
    extern __shared__ __align__(1024) uint8_t smem[];
    const uint32_t sb = SB0;
    if (smem_u32(smem) != sb) die(1 << 23);
    const uint32_t tid = threadIdx.x, lane = tid & 31, g = lane >> 2, t = lane & 3, j8 = lane & 7, mat = lane >> 3;
    const uint32_t wi_ = __reduce_max_sync(0xFFFFFFFFu, tid >> 5), q = wi_ >> 2, w = wi_ & 3;
    const int cta = blockIdx.x;
    const int nt = cta < 64 ? (64 - cta + nw - 1) / nw : 0;
    const uint32_t bar = sb + FS_BAR;
    if (tid == 0) {
        for (int i = 0; i < 30; i++) mbar_init(bar + i * 8, i < 3 ? 4 : i < 6 ? 16 : i >= 14 && i < 18 ? 2 : 1);
        asm volatile("fence.mbarrier_init.release.cluster;" ::: "memory");
        fence_smem();
    }
    __syncthreads();
#define FT(n)
    FT(0);
#define N2(p) (2 * ((p) & 31) + ((p) >> 5))
#define WLOAD(tk, part) { \
        const uint32_t wd_ = sb + 131072 + q * 18432 + (part) * 9216, wb_ = bar + 112 + q * 8; \
        mbar_expect(wb_, 9216); \
        if ((tk) < 256) tma3d(wd_, (part) ? &tmwi : &tmwr, wb_, ((tk) & 63) * 64, (tk) >> 6, 0); \
        else asm volatile("cp.async.bulk.shared::cluster.global.mbarrier::complete_tx::bytes [%0], [%1], 9216, [%2];" \
                          ::"r"(wd_), "l"(g_WN + (part) * 576), "r"(wb_) : "memory"); }
#define GROW(tk) ((tk) < 256 ? ((tk) >> 5) * 64 + ((tk) & 7) * 8 + (((tk) >> 3) & 3) * 2 : 512)
#define DLOAD(tk, sl) { mbar_expect(bar + 48 + (sl) * 8, 16384); tma3d(sb + (sl) * 16384, &tmg2, bar + 48 + (sl) * 8, 0, GROW(tk), 0); }
#define IO(c) if (w == 3 && (c) && elect())
#define XLOAD1(i, bb) { const uint32_t xb_ = bar + 144 + (bb) * 32 + q * 8; mbar_expect(xb_, 16384); tma4d(sb + (bb) * 65536 + q * 16384, &tmx, xb_, 0, 0, q * 8, N2(cta + (i) * nw)); }
#define GLOAD3(i, bb) { mbar_expect(bar + (bb) * 8, q ? 16384 : 16512); tma3d(sb + (bb) * 65536 + q * 16384, &tmg1, bar + (bb) * 8, 0, q * 128, cta + (i) * nw); \
        if (q == 0) asm volatile("cp.async.bulk.shared::cluster.global.mbarrier::complete_tx::bytes [%0], [%1], 128, [%2];" \
                                 ::"r"(sb + FS_NQ + (bb) * 1024), "l"(g_GN + (cta + (i) * nw) * 8), "r"(bar + (bb) * 8) : "memory"); }
    for (int i = 0; i < 3; i++) IO(i < nt) XLOAD1(i, i);
    for (uint32_t x = tid; x < 40 * 32; x += 512) {
        const uint32_t n = x >> 5, m2 = mat * 8 + t * 2, ri = g & 1;
        const uint32_t c2 = ((n >> 1) & 1) + ((n >> 3) & 1) * 2 + (n & 4) + (n >> 4) * 8;
        const uint32_t v = cos2(m2 * c2 * 64 + ((n & 1) - ri) * 512, (m2 + 1) * c2 * 64 + ((n & 1) - ri) * 512);
        sts32(sb + FS_F2 + n * 128 + ((g ^ (n & 7)) << 4) + t * 4, n < 32 ? v : n == 32 && ri == 0 ? 0xBF003F00u : 0u);
    }
    float tc[8], ts[8];
    uint32_t F[2][4];
    uint32_t c1 = 16 * (w >> 1) + 2 * g + (w & 1);
#pragma unroll
    for (int i = 0; i < 8; i++) {
        twid(c1 * (8 * (i >> 1) + 2 * t + (i & 1)), tc[i], ts[i]);
        const uint32_t m1 = (i >> 1) * 8 + 2 * t;
        F[i >> 2][i & 3] = cos2(c1 * m1 * 64 + (i & 1) * 512, c1 * (m1 + 1) * 64 + (i & 1) * 512);
    }
    {
        const uint32_t kr = (2 * (mat & 1) + (j8 & 1)) ^ ((j8 >> 2) << 1);
        const uint32_t so1 = ((mat >> 1) + 2 * (j8 >> 2)) * 1024 + kr * 128 + (((((j8 >> 1) & 1) * 4 + w) ^ kr) << 4);
        const uint32_t so2 = (2 * w + (mat & 1)) * 8192 + q * 2048 + j8 * 128 + (((mat >> 1) ^ j8) << 4);
        uint32_t so = so1 << 16 | so2;
        const float fx = (tid & 127) == 0 ? 0.5f : 1.f;
        fft_gen<false>(sb + FS_TB, N2(cta));
        fence_smem();
        bsync<1, 512>();
        FT(1);
        int b = 0, bp = 2, ph = 0;
        if (nt) mwait(bar + 144 + q * 8, 0);
        __syncwarp();
        auto step = [&](auto first, auto last, const int i) {
            const uint32_t p = cta + i * nw, bn = 3 - b - bp, tb = (i & 1) * 8192;
            const uint32_t grp = sb + b * 65536 + q * 16384, nq = sb + FS_NQ + b * 1024 + q * 32;
            auto sa = [&]() {
                if constexpr (!decltype(first)::v) {
                    fence_smem();
                    __syncwarp();
                    if (elect()) mbar_arrive(bar + 24);
                }
                IO(i > 1) {
                    mwait(bar + 32, i & 1);
                    tma3s(&tmg1, sb + bn * 65536 + q * 16384, 0, q * 128, p - 2 * nw);
                    bulk_commit();
                }
            };
            auto sb_ = [&]() { if constexpr (!decltype(first)::v) mwait(bar + 24, (i - 1) & 1); };
            if constexpr (!decltype(last)::v) fft_rows<false>(grp, q, F, tc, ts, opq(so, zero) >> 16, fx, nq, sa, sb_);
            else { sa(); __syncwarp(); sb_(); __syncwarp(); }
            if constexpr (!decltype(first)::v) {
                float n[4];
                fft_cross<false>(sb + bp * 65536, q, sb + FS_TB + 8192 - tb + (((tidx() & 127) ^ (q & 1)) << 4), opq(so, zero) & 0xFFFF, sb + FS_NQ + bp * 1024, n, [&]() {
                    fft_gen<false>(sb + FS_TB + tb, N2(p));
                    IO(i >= 2 && i + 1 < nt) {
                        asm volatile("cp.async.bulk.wait_group.read 0;" ::: "memory");
                        XLOAD1(i + 1, bn);
                    }
                });
                if (q == 0) {
                    const uint32_t x = tidx();
                    bf16* z = (bf16*)(g_G + ((p - nw) * G_ROWS + 512) * 8) + (x & 4) * 16 + ((x >> 2) & 24) + ((x >> 3) & 3);
                    asm volatile("{\n.reg .pred p;\n.reg .b16 a, b;\nsetp.eq.u32 p, %2, 0;\nmov.b32 {a, b}, %1;\n@p st.global.u16 [%0], a;\n@p st.global.u16 [%0+8], b;\n}"
                                 ::"l"(z), "r"(pack2(n[0], n[2])), "r"(x & 3) : "memory");
                }
            }
            if constexpr (!decltype(last)::v) {
                fft_rows<false>(grp + 8192, q, F, tc, ts, opq(so, zero) >> 16, fx, nq + 16, [&]() {
                    if constexpr (!decltype(first)::v) {
                        fence_smem();
                        __syncwarp();
                        if (elect()) mbar_arrive(bar + 32);
                    }
                    if ((w == 1 || w == 2) && elect())
                        asm volatile("cp.async.bulk.prefetch.L2.global [%0], 8208;" ::"l"((w == 1 ? wr : wi) + (p * 4 + q) * 4104) : "memory");
                }, [&]() { if (i + 1 < nt) mwait(bar + 144 + bn * 32 + q * 8, bn ? ph : ph ^ 1); });
                bp = b;
                if (++b == 3) { b = 0; ph ^= 1; }
            }
        };
        if (nt) {
            step(Bool<true>(), Bool<false>(), 0);
#pragma unroll 1
            for (int i = 1; i < nt; i++) step(Bool<false>(), Bool<false>(), i);
            step(Bool<false>(), Bool<true>(), nt);
        }
        for (uint32_t x = cta * 512 + tid; x < 4096; x += nw * 512)
            ((bf16*)g_WN)[(x >> 5) * 72 + (x & 16) + (x & 7) * 2 + ((x >> 3) & 1)] = (x < 2048 ? wr : wi)[(x & 2047) * 513 + 512];
        FT(2);
        fence_async();
        bsync<1, 512>();
        IO(nt) { tma3s(&tmg1, sb + bp * 65536 + q * 16384, 0, q * 128, cta + (nt - 1) * nw); bulk_commit(); }
    }
    for (uint32_t x = tid; x < 128 * 32; x += 512) {
        const uint32_t n = (x >> 5) & 63, a = x & 31, k2 = (n >> 4) * 8 + (n & 7);
        sts32(sb + FS_TB + (x >> 5) * 128 + (((a >> 2) ^ (n & 7)) << 4) + (a & 3) * 4, cis((2 * a + (x >> 11)) * k2 * 32 + (n & 8) * 64));
    }
    fence_smem();
    bsync<1, 512>();
    IO(true) {
        asm volatile("cp.async.bulk.wait_group 0;" ::: "memory");
        grid_arrive(cnt, 4 * nw);
        grid_wait(cnt);
        const int tk = cta + q * nw;
        if (tk <= 256) { DLOAD(tk, q); WLOAD(tk, 0); WLOAD(tk, 1); }
    }
    __syncwarp();
    {
        const uint32_t lo = j8 * 128 + (((2 * w + (mat & 1)) ^ j8) << 4);
        const uint32_t aw = sb + 131072 + q * 18432 + t * 288 + w * 32 + g * 4;
        const uint64_t df = mkdesc(sb + FS_TB, 16, 1024);
        const uint64_t da = mkdesc(sb + q * 16384, 16, 1024);
        const uint32_t buf = sb + 65536 + q * 16384;
        int i = 0, tk = cta + q * nw;
        if (tk <= 256) mwait(bar + 48 + q * 8, 0);
        FT(3);
#pragma unroll 1
        for (; tk <= 256; tk += 4 * nw, i++) {
            const bool more = tk + 4 * nw <= 256;
            float e[32], o[32];
            wg_fence();
#pragma unroll
            for (int s = 0; s < 4; s++) { if (s == 0) wg_ss64a<0>(e, da, df); else wg_ss64a<1>(e, da + s * 128, df + s * 2); }
#pragma unroll
            for (int s = 0; s < 4; s++) { if (s == 0) wg_ss64a<0>(o, da + 512, df + 512); else wg_ss64a<1>(o, da + 512 + s * 128, df + 512 + s * 2); }
            wg_commit();
            SF();
            if (i > 0) {
                fence_smem();
                wgbar(q);
                IO(true) { tma3s(&tmg2, buf, 0, GROW(tk - 4 * nw), 0); bulk_commit(); }
            }
            if (w == 2 && more && elect()) mbar_expect(bar + 48 + q * 8, 16384);
            const int gr = GROW(tk + 4 * nw);
            mwait(bar + 112 + q * 8, i & 1);
            wg_wait<0>();
            if (w == 2 && more && elect()) tma3d(sb + q * 16384, &tmg2, bar + 48 + q * 8, 0, gr, 0);
            uint32_t u[4][4], v[4][4];
            if (tk & 8) fft_filter<true>(aw + (tk & 48) / 4, e, o, u, v);
            else fft_filter<false>(aw + (tk & 48) / 4, e, o, u, v);
            wg_fence();
#pragma unroll
            for (int s = 0; s < 4; s++) { if (s == 0) wg_rs64t<0>(e, u[s], df); else wg_rs64t<1>(e, u[s], df + s * 128); }
#pragma unroll
            for (int s = 0; s < 4; s++) { if (s == 0) wg_rs64t<0>(o, v[s], df + 512); else wg_rs64t<1>(o, v[s], df + 512 + s * 128); }
            wg_commit();
            SF();
            IO(true) asm volatile("cp.async.bulk.wait_group.read 0;" ::: "memory");
            wgbar(q);
            if (more) {
                if ((w == 1 || w == 2) && elect()) WLOAD(tk + 4 * nw, w - 1);
                mwait(bar + 48 + q * 8, (i + 1) & 1);
            }
            wg_wait<0>();
#pragma unroll
            for (int s = 0; s < 4; s++) {
                const uint32_t a = buf + (mat >> 1) * 1024 + lo + s * 2048;
                stsm4t(a, pack2(e[8 * s], e[8 * s + 1]), pack2(e[8 * s + 2], e[8 * s + 3]), pack2(e[8 * s + 4], e[8 * s + 5]), pack2(e[8 * s + 6], e[8 * s + 7]));
                stsm4t(a + 8192, pack2(o[8 * s], o[8 * s + 1]), pack2(o[8 * s + 2], o[8 * s + 3]), pack2(o[8 * s + 4], o[8 * s + 5]), pack2(o[8 * s + 6], o[8 * s + 7]));
            }
            if (tk == 256 && w < 2) {
                uint32_t* z = (uint32_t*)g_GN + t * 32 + w * 16 + g;
#pragma unroll
                for (int s = 0; s < 16; s++) {
                    z[(s >> 1) * 128 + (s & 1) * 8] = pack2(e[2 * s], e[2 * s + 1]);
                    z[(s >> 1) * 128 + (s & 1) * 8 + 1024] = pack2(o[2 * s], o[2 * s + 1]);
                }
                fence_async();
            }
        }
        fence_smem();
        wgbar(q);
        IO(true) {
            if (i > 0) { tma3s(&tmg2, buf, 0, GROW(tk - 4 * nw), 0); bulk_commit(); }
            asm volatile("cp.async.bulk.wait_group 0;" ::: "memory");
            grid_arrive(cnt + 1, 4 * nw);
        }
    }
    FT(4);
    bsync<1, 512>();
    {
        for (uint32_t n = wi_; n < 32; n += 16) {
            const uint32_t cl = (mat >> 1) * 16 + t * 4 + (mat & 1), mh = ((n >> 3) & 1) + (n & 7) * 2 + (n & 16);
            sts32(sb + FS_F2 + n * 128 + ((g ^ (n & 7)) << 4) + t * 4, cos2(cl * mh * 64 + (g & 1) * 512, (cl + 2) * mh * 64 + (g & 1) * 512));
        }
        fence_smem();
        c1 = 8 * w + g;
#pragma unroll
        for (int i = 0; i < 8; i++) {
            twid(-c1 * (16 * (i >> 2) + 4 * t + 2 * (i & 1) + ((i >> 1) & 1)), tc[i], ts[i]);
            F[i >> 2][i & 3] = cis((i & 1) * 512 - c1 * ((i >> 1) * 4 + (t ^ (q & 1))) * 64);
        }
        const uint32_t kr = (j8 & 1) ^ ((j8 >> 2) << 1);
        const uint32_t so2 = ((w >> 1) * 4 + (j8 >> 2) * 2 + (w & 1)) * 8192 + (2 * q + (mat & 1)) * 1024 + kr * 128 + (((((j8 >> 1) & 1) * 4 + (mat >> 1)) ^ kr) << 4);
        const uint32_t so1 = (mat & 1) * 2048 + j8 * 128 + ((((mat >> 1) * 4 + w) ^ j8) << 4);
        uint32_t so = so1 << 16 | so2;
        const float fx = t ? 0.f : (g & 1) ? -1.f : 1.f;
        fft_gen<true>(sb + FS_TB, N2(cta));
        bsync<1, 512>();
        IO(true) grid_wait(cnt + 1);
        for (int i = 0; i < 3; i++) IO(i < nt) GLOAD3(i, i);
        __syncwarp();
        int b = 0, bp = 2, ph = 0;
        auto step = [&](auto first, auto last, const int i) {
            const uint32_t p = cta + i * nw, bn = 3 - b - bp, tb = (i & 1) * 8192;
            const uint32_t grp = sb + bp * 65536 + q * 16384, ny = sb + FS_NY + bp * 128 + q * 32;
            auto sb_ = [&]() { if constexpr (!decltype(last)::v) mwait(bar + b * 8, ph); };
            if constexpr (!decltype(first)::v) {
                fft_rows<true>(grp, q, F, tc, ts, opq(so, zero) >> 16, fx, ny, [&]() {
                    if (i > 1) {
                        fence_smem();
                        wgbar(q);
                        IO(true) { tma4s(&tmy, sb + bn * 65536 + q * 16384, 0, 0, q * 8, N2(p - 2 * nw)); bulk_commit(); }
                    }
                }, sb_);
            } else { sb_(); __syncwarp(); }
            if constexpr (decltype(first)::v) FT(5);
            if constexpr (!decltype(last)::v) {
                float n[4];
                fft_cross<true>(sb + b * 65536, q, sb + FS_TB + tb + (tidx() & 127) * 16, opq(so, zero) & 0xFFFF, sb + FS_NQ + b * 1024, n, [&]() {
                    fft_gen<true>(sb + FS_TB + 8192 - tb, N2(p + nw));
                    IO(i >= 2 && i + 1 < nt) {
                        asm volatile("cp.async.bulk.wait_group.read 0;" ::: "memory");
                        GLOAD3(i + 1, bn);
                    }
                });
                if (q == 0) {
                    const uint32_t x = tidx(), a = sb + FS_NY + b * 128 + (x & 64) + (x & 16) * 2 + ((x & 40) >> 1);
                    if ((x & 7) == 0) { sts32f(a, n[0]); sts32f(a + 8, n[2]); }
                }
            }
            auto sc = [&]() {
                if constexpr (!decltype(last)::v) {
                    fence_smem();
                    __syncwarp();
                    if (elect()) mbar_arrive(bar + 24);
                }
            };
            auto sd = [&]() { if constexpr (!decltype(last)::v) mwait(bar + 24, (nt + i) & 1); };
            if constexpr (!decltype(first)::v) fft_rows<true>(grp + 8192, q, F, tc, ts, opq(so, zero) >> 16, fx, ny + 16, sc, sd);
            else { sc(); __syncwarp(); sd(); __syncwarp(); }
            if constexpr (!decltype(last)::v) {
                bp = b;
                if (++b == 3) { b = 0; ph ^= 1; }
            }
        };
        if (nt) {
            step(Bool<true>(), Bool<false>(), 0);
#pragma unroll 1
            for (int i = 1; i < nt; i++) step(Bool<false>(), Bool<false>(), i);
            step(Bool<false>(), Bool<true>(), nt);
        }
        fence_smem();
        wgbar(q);
        IO(nt) { tma4s(&tmy, sb + bp * 65536 + q * 16384, 0, 0, q * 8, N2(cta + (nt - 1) * nw)); bulk_commit(); }
        FT(6);
        IO(true) asm volatile("cp.async.bulk.wait_group 0;" ::: "memory");
    }
}

typedef CUresult (*EncodeFn)(CUtensorMap*, CUtensorMapDataType, cuuint32_t, void*, const cuuint64_t*, const cuuint64_t*,
                             const cuuint32_t*, const cuuint32_t*, CUtensorMapInterleave, CUtensorMapSwizzle,
                             CUtensorMapL2promotion, CUtensorMapFloatOOBfill);

static void make_map(EncodeFn enc, CUtensorMap* m, const void* ptr, int rank, const cuuint64_t* dims, const cuuint64_t* strides,
                     const cuuint32_t* box, CUtensorMapSwizzle sw = CU_TENSOR_MAP_SWIZZLE_128B) {
    cuuint32_t es[4] = {1, 1, 1, 1};
    CUresult r = enc(m, CU_TENSOR_MAP_DATA_TYPE_BFLOAT16, rank, (void*)ptr, dims, strides, box, es, CU_TENSOR_MAP_INTERLEAVE_NONE,
                     sw, CU_TENSOR_MAP_L2_PROMOTION_L2_256B, CU_TENSOR_MAP_FLOAT_OOB_FILL_NONE);
    if (r != CUDA_SUCCESS) fprintf(stderr, "tensor map encode failed: %d\n", (int)r);
}

extern "C" void kernel_launch(void* const* d_in, const int* in_sizes, int n_in, void* d_out, int out_size) {
    const bf16* A_x = (const bf16*)d_in[0];
    const bf16* A_mem0 = (const bf16*)d_in[1];
    const bf16* A_Wq = (const bf16*)d_in[2];
    const bf16* A_Wk = (const bf16*)d_in[3];
    const bf16* A_Wv = (const bf16*)d_in[4];
    const bf16* A_Wo = (const bf16*)d_in[5];
    const bf16* B_x = (const bf16*)d_in[7];
    const bf16* B_wr = (const bf16*)d_in[8];
    const bf16* B_wi = (const bf16*)d_in[9];
    bf16* out = (bf16*)d_out;

    static EncodeFn enc = nullptr;
    static void *pxs = nullptr, *pg = nullptr;
    static int ncl = 64;
    if (!enc) {
        cudaDriverEntryPointQueryResult qr;
        void* fn = nullptr;
        cudaGetDriverEntryPoint("cuTensorMapEncodeTiled", &fn, cudaEnableDefault, &qr);
        enc = (EncodeFn)fn;
        cudaFuncSetAttribute(chain_kernel, cudaFuncAttributeMaxDynamicSharedMemorySize, SM_TOTAL);
        cudaFuncSetAttribute(post_kernel, cudaFuncAttributeMaxDynamicSharedMemorySize, FS_TOTAL);
        cudaGetSymbolAddress(&pxs, g_xs);
        cudaGetSymbolAddress(&pg, g_G);
        cudaLaunchConfig_t lc = {};
        cudaLaunchAttribute at;
        at.id = cudaLaunchAttributeClusterDimension;
        at.val.clusterDim.x = 2; at.val.clusterDim.y = 1; at.val.clusterDim.z = 1;
        lc.gridDim = dim3(132); lc.blockDim = dim3(384); lc.dynamicSmemBytes = SM_TOTAL; lc.attrs = &at; lc.numAttrs = 1;
        int nc = 0;
        if (cudaOccupancyMaxActiveClusters(&nc, chain_kernel, &lc) == cudaSuccess && nc > 64) ncl = nc < 66 ? nc : 66;
    }
    CUtensorMap tmq, tmk, tmv, tmo, tmx, tmb, tmy;
    {
        cuuint64_t d[3] = {64, DM, HD / 64}, st[2] = {HD * 2, 128};
        cuuint32_t bx[3] = {64, 64, 2};
        make_map(enc, &tmq, A_Wq, 3, d, st, bx);
        make_map(enc, &tmk, A_Wk, 3, d, st, bx);
        make_map(enc, &tmv, A_Wv, 3, d, st, bx);
    }
    {
        cuuint64_t d[2] = {DM, HD}, st[1] = {DM * 2};
        cuuint32_t bx[2] = {64, 16}, bx1[2] = {64, 128}, bx2[3] = {64, 64, 2};
        make_map(enc, &tmo, A_Wo, 2, d, st, bx1);
        cuuint64_t d2[3] = {64, HD, DM / 64}, st2[2] = {DM * 2, 128}, d3[2] = {DM, SEQ}, st3[1] = {DM * 4};
        make_map(enc, &tmb, A_Wo, 3, d2, st2, bx2);
        make_map(enc, &tmy, out, 2, d3, st3, bx);
    }
    {
        cuuint64_t d[3] = {64, SEQ, DM / 64}, st[2] = {DM * 2, 128};
        cuuint32_t bx[3] = {64, 8, 4};
        make_map(enc, &tmx, A_x, 3, d, st, bx);
    }
    CUtensorMap fx, fg1, fg2, fwr, fwi, fy;
    {
        cuuint64_t d[4] = {32, 32, 32, 64}, st[3] = {64, 64 * DM * 2, DM * 2};
        cuuint32_t bx[4] = {32, 32, 8, 1};
        make_map(enc, &fx, B_x, 4, d, st, bx, CU_TENSOR_MAP_SWIZZLE_64B);
        cuuint64_t d2[4] = {64, 16, 32, 64}, st2[3] = {128, 64 * 4096, 4096};
        cuuint32_t bx2[4] = {64, 16, 8, 1};
        make_map(enc, &fy, out + DM, 4, d2, st2, bx2);
    }
    {
        cuuint64_t d[3] = {64, G_ROWS, 64}, st[2] = {128, G_ROWS * 128};
        cuuint32_t bx[3] = {64, 128, 1}, bx2[3] = {64, 2, 64};
        make_map(enc, &fg1, pg, 3, d, st, bx);
        make_map(enc, &fg2, pg, 3, d, st, bx2);
        cuuint64_t d2[3] = {8 * 513, 4, 64}, st2[2] = {8 * 513 * 2, 32 * 513 * 2};
        cuuint32_t bx3[3] = {72, 1, 64};
        make_map(enc, &fwr, B_wr, 3, d2, st2, bx3, CU_TENSOR_MAP_SWIZZLE_NONE);
        make_map(enc, &fwi, B_wi, 3, d2, st2, bx3, CU_TENSOR_MAP_SWIZZLE_NONE);
    }
    cudaStream_t st = cudaStreamPerThread;
    const uint64_t xs = ((uint64_t)pxs + XS_BYTES - 1) & ~(uint64_t)(XS_BYTES - 1);
    chain_kernel<<<2 * ncl, 384, SM_TOTAL, st>>>(tmq, tmk, tmv, tmo, tmx, tmb, tmy, A_mem0, A_x, (uint32_t)xs, (uint32_t)(xs >> 32), 0u, NSEG, out);
    int nw = ncl == 66 ? 4 : 64;
    cudaLaunchConfig_t lc = {};
    cudaLaunchAttribute at;
    at.id = cudaLaunchAttributeProgrammaticStreamSerialization;
    at.val.programmaticStreamSerializationAllowed = 1;
    lc.gridDim = dim3(nw); lc.blockDim = dim3(F_THREADS); lc.dynamicSmemBytes = FS_TOTAL; lc.stream = st; lc.attrs = &at; lc.numAttrs = 1;
    cudaLaunchKernelEx(&lc, post_kernel, fx, fg1, fg2, fwr, fwi, fy, B_wr, B_wi, (uint32_t*)(xs + XO_TK + 256), 0u, nw);
}
```

```cpp
#include <cuda_runtime.h>
#include <cuda_bf16.h>
#include <cuda.h>
#include <stdint.h>
#include <stdio.h>

typedef __nv_bfloat16 bf16;

#define SEQ 2048
#define DM 1024
#define NH 32
#define DH 128
#define NSEG 64
#define HD (NH * DH)

#define XS_BYTES (32u << 20)
__device__ uint4 g_xs[2 * XS_BYTES / 16];
#define XO_R 0u
#define XO_PB (1u << 18)
#define XO_FL (XO_PB + 32768u)
#define XO_TK (XO_FL + 4096u)
#define XO_CQK (1u << 20)
#define XO_CV (2u << 20)
#define XO_XG (4u << 20)
#define XO_OX (16u << 20)
#define GSYNC(n)
#define PG(n)

#define DEVI __device__ __forceinline__

DEVI void die(int it) { asm volatile("st.shared.u32 [%0], %0;" ::"r"(it) : "memory"); }
DEVI uint32_t smem_u32(const void* p) { return (uint32_t)__cvta_generic_to_shared(p); }
DEVI void mbar_init(uint32_t bar, uint32_t cnt) { asm volatile("mbarrier.init.shared::cta.b64 [%0], %1;" ::"r"(bar), "r"(cnt) : "memory"); }
DEVI void mbar_expect(uint32_t bar, uint32_t bytes) { asm volatile("mbarrier.arrive.expect_tx.shared::cta.b64 _, [%0], %1;" ::"r"(bar), "r"(bytes) : "memory"); }
DEVI void mbar_arrive(uint32_t bar) { asm volatile("mbarrier.arrive.shared::cta.b64 _, [%0];" ::"r"(bar) : "memory"); }
DEVI void mbar_wait(uint32_t bar, uint32_t parity) {
    uint32_t done;
    int it = 0;
    do {
        asm volatile("{\n.reg .pred p;\nmbarrier.try_wait.parity.shared::cta.b64 p, [%1], %2;\nselp.u32 %0, 1, 0, p;\n}\n"
                     : "=r"(done) : "r"(bar), "r"(parity) : "memory");
        if (++it > (1 << 22)) die(it);
    } while (!done);
}
DEVI void tma2d(uint32_t dst, const CUtensorMap* tm, uint32_t bar, int c0, int c1) {
    asm volatile("cp.async.bulk.tensor.2d.shared::cluster.global.mbarrier::complete_tx::bytes [%0], [%1, {%3, %4}], [%2];"
                 ::"r"(dst), "l"(tm), "r"(bar), "r"(c0), "r"(c1) : "memory");
}
DEVI void tma3d(uint32_t dst, const CUtensorMap* tm, uint32_t bar, int c0, int c1, int c2) {
    asm volatile("cp.async.bulk.tensor.3d.shared::cluster.global.mbarrier::complete_tx::bytes [%0], [%1, {%3, %4, %5}], [%2];"
                 ::"r"(dst), "l"(tm), "r"(bar), "r"(c0), "r"(c1), "r"(c2) : "memory");
}
DEVI void bulk_g2s(uint32_t dst, uint32_t lo, uint32_t hi, uint32_t bytes, uint32_t bar) {
    asm volatile("{\n.reg .b64 a;\nmov.b64 a, {%1,%2};\ncp.async.bulk.shared::cluster.global.mbarrier::complete_tx::bytes [%0], [a], %3, [%4];\n}"
                 ::"r"(dst), "r"(lo), "r"(hi), "r"(bytes), "r"(bar) : "memory");
}
DEVI void bulk_s2g(uint32_t lo, uint32_t hi, uint32_t src, uint32_t bytes) {
    asm volatile("{\n.reg .b64 a;\nmov.b64 a, {%0,%1};\ncp.async.bulk.global.shared::cta.bulk_group [a], [%2], %3;\ncp.async.bulk.commit_group;\n}"
                 ::"r"(lo), "r"(hi), "r"(src), "r"(bytes) : "memory");
}
DEVI void bulk_red(uint32_t lo, uint32_t hi, uint32_t src, uint32_t bytes) {
    asm volatile("{\n.reg .b64 a;\nmov.b64 a, {%0,%1};\ncp.reduce.async.bulk.global.shared::cta.bulk_group.add.noftz.bf16 [a], [%2], %3;\ncp.async.bulk.commit_group;\n}"
                 ::"r"(lo), "r"(hi), "r"(src), "r"(bytes) : "memory");
}
DEVI bool elect() {
    uint32_t p;
    asm volatile("{\n.reg .pred P;\nelect.sync _|P, 0xFFFFFFFF;\nselp.u32 %0, 1, 0, P;\n}" : "=r"(p));
    return p != 0;
}
DEVI void ldsm4(uint32_t (&r)[4], uint32_t a) {
    asm volatile("ldmatrix.sync.aligned.m8n8.x4.shared.b16 {%0,%1,%2,%3}, [%4];" : "=r"(r[0]), "=r"(r[1]), "=r"(r[2]), "=r"(r[3]) : "r"(a) : "memory");
}
DEVI void ldsm4t(uint32_t (&r)[4], uint32_t a) {
    asm volatile("ldmatrix.sync.aligned.m8n8.x4.trans.shared.b16 {%0,%1,%2,%3}, [%4];" : "=r"(r[0]), "=r"(r[1]), "=r"(r[2]), "=r"(r[3]) : "r"(a) : "memory");
}
DEVI void ldsm2t(uint32_t (&r)[2], uint32_t a) {
    asm volatile("ldmatrix.sync.aligned.m8n8.x2.trans.shared.b16 {%0,%1}, [%2];" : "=r"(r[0]), "=r"(r[1]) : "r"(a) : "memory");
}
DEVI void ldsm2(uint32_t (&r)[2], uint32_t a) {
    asm volatile("ldmatrix.sync.aligned.m8n8.x2.shared.b16 {%0,%1}, [%2];" : "=r"(r[0]), "=r"(r[1]) : "r"(a) : "memory");
}
DEVI void stsm4t(uint32_t a, uint32_t r0, uint32_t r1, uint32_t r2, uint32_t r3) {
    asm volatile("stmatrix.sync.aligned.m8n8.x4.trans.shared.b16 [%0], {%1,%2,%3,%4};" ::"r"(a), "r"(r0), "r"(r1), "r"(r2), "r"(r3) : "memory");
}
DEVI uint32_t ldsm1(uint32_t a) {
    uint32_t r;
    asm volatile("ldmatrix.sync.aligned.m8n8.x1.shared.b16 {%0}, [%1];" : "=r"(r) : "r"(a) : "memory");
    return r;
}
DEVI void stsm4(uint32_t a, uint32_t r0, uint32_t r1, uint32_t r2, uint32_t r3) {
    asm volatile("stmatrix.sync.aligned.m8n8.x4.shared.b16 [%0], {%1,%2,%3,%4};" ::"r"(a), "r"(r0), "r"(r1), "r"(r2), "r"(r3) : "memory");
}
DEVI void stsm2(uint32_t a, uint32_t r0, uint32_t r1) {
    asm volatile("stmatrix.sync.aligned.m8n8.x2.shared.b16 [%0], {%1,%2};" ::"r"(a), "r"(r0), "r"(r1) : "memory");
}
DEVI uint32_t movm(uint32_t a) {
    uint32_t d;
    asm volatile("movmatrix.sync.aligned.m8n8.trans.b16 %0, %1;" : "=r"(d) : "r"(a));
    return d;
}
DEVI void mma16(float (&d)[4], uint32_t a0, uint32_t a1, uint32_t a2, uint32_t a3, uint32_t b0, uint32_t b1) {
    asm volatile("mma.sync.aligned.m16n8k16.row.col.f32.bf16.bf16.f32 {%0,%1,%2,%3}, {%4,%5,%6,%7}, {%8,%9}, {%0,%1,%2,%3};"
                 : "+f"(d[0]), "+f"(d[1]), "+f"(d[2]), "+f"(d[3]) : "r"(a0), "r"(a1), "r"(a2), "r"(a3), "r"(b0), "r"(b1));
}
DEVI void mma16z(float (&d)[4], uint32_t a0, uint32_t a1, uint32_t a2, uint32_t a3, uint32_t b0, uint32_t b1) {
    asm volatile("mma.sync.aligned.m16n8k16.row.col.f32.bf16.bf16.f32 {%0,%1,%2,%3}, {%4,%5,%6,%7}, {%8,%9}, {%10,%10,%10,%10};"
                 : "=f"(d[0]), "=f"(d[1]), "=f"(d[2]), "=f"(d[3]) : "r"(a0), "r"(a1), "r"(a2), "r"(a3), "r"(b0), "r"(b1), "f"(0.f));
}
DEVI void mma8(float (&d)[4], uint32_t a0, uint32_t a1, uint32_t b0) {
    asm volatile("mma.sync.aligned.m16n8k8.row.col.f32.bf16.bf16.f32 {%0,%1,%2,%3}, {%4,%5}, {%6}, {%0,%1,%2,%3};"
                 : "+f"(d[0]), "+f"(d[1]), "+f"(d[2]), "+f"(d[3]) : "r"(a0), "r"(a1), "r"(b0));
}
DEVI void mma8z(float (&d)[4], uint32_t a0, uint32_t a1, uint32_t b0) {
    asm volatile("mma.sync.aligned.m16n8k8.row.col.f32.bf16.bf16.f32 {%0,%1,%2,%3}, {%4,%5}, {%6}, {%7,%7,%7,%7};"
                 : "=f"(d[0]), "=f"(d[1]), "=f"(d[2]), "=f"(d[3]) : "r"(a0), "r"(a1), "r"(b0), "f"(0.f));
}
DEVI uint32_t pack2(float lo, float hi) {
    uint32_t r;
    asm("cvt.rn.bf16x2.f32 %0, %1, %2;" : "=r"(r) : "f"(hi), "f"(lo));
    return r;
}
DEVI uint32_t hadd2(uint32_t a, uint32_t b) {
    uint32_t r;
    asm("add.rn.bf16x2 %0, %1, %2;" : "=r"(r) : "r"(a), "r"(b));
    return r;
}
DEVI float lo_f(uint32_t x) { return __uint_as_float(x << 16); }
DEVI float hi_f(uint32_t x) { return __uint_as_float(x & 0xFFFF0000u); }
template <uint32_t OFF> DEVI uint4 ldg4(uint32_t lo, uint32_t hi) {
    uint4 v;
    asm volatile("{\n.reg .b64 a;\nmov.b64 a, {%4,%5};\nld.relaxed.gpu.global.v4.u32 {%0,%1,%2,%3}, [a+%6];\n}"
                 : "=r"(v.x), "=r"(v.y), "=r"(v.z), "=r"(v.w) : "r"(lo), "r"(hi), "n"(OFF) : "memory");
    return v;
}
template <uint32_t OFF> DEVI uint2 ldg2(uint32_t lo, uint32_t hi) {
    uint2 v;
    asm volatile("{\n.reg .b64 a;\nmov.b64 a, {%2,%3};\nld.relaxed.gpu.global.v2.u32 {%0,%1}, [a+%4];\n}"
                 : "=r"(v.x), "=r"(v.y) : "r"(lo), "r"(hi), "n"(OFF) : "memory");
    return v;
}
template <uint32_t OFF> DEVI uint32_t ldg1(uint32_t lo, uint32_t hi) {
    uint32_t v;
    asm volatile("{\n.reg .b64 a;\nmov.b64 a, {%1,%2};\nld.relaxed.gpu.global.u32 %0, [a+%3];\n}" : "=r"(v) : "r"(lo), "r"(hi), "n"(OFF) : "memory");
    return v;
}
template <uint32_t OFF> DEVI void stg1(uint32_t lo, uint32_t hi, uint32_t a) {
    asm volatile("{\n.reg .b64 a;\nmov.b64 a, {%0,%1};\nst.relaxed.gpu.global.u32 [a+%3], %2;\n}" ::"r"(lo), "r"(hi), "r"(a), "n"(OFF) : "memory");
}
template <uint32_t OFF> DEVI void stg4(uint32_t lo, uint32_t hi, uint32_t a, uint32_t b, uint32_t c, uint32_t d) {
    asm volatile("{\n.reg .b64 a;\nmov.b64 a, {%0,%1};\nst.relaxed.gpu.global.v4.u32 [a+%6], {%2,%3,%4,%5};\n}"
                 ::"r"(lo), "r"(hi), "r"(a), "r"(b), "r"(c), "r"(d), "n"(OFF) : "memory");
}
template <uint32_t OFF> DEVI void stg2(uint32_t lo, uint32_t hi, uint32_t a, uint32_t b) {
    asm volatile("{\n.reg .b64 a;\nmov.b64 a, {%0,%1};\nst.relaxed.gpu.global.v2.u32 [a+%4], {%2,%3};\n}"
                 ::"r"(lo), "r"(hi), "r"(a), "r"(b), "n"(OFF) : "memory");
}
DEVI uint32_t tagx2(uint32_t a, uint32_t b, uint32_t t) { uint32_t r; asm("lop3.b32 %0, %1, %2, %3, 0x7E;" : "=r"(r) : "r"(a), "r"(b), "r"(t)); return r; }
DEVI uint32_t tagx1(uint32_t a, uint32_t b, uint32_t t) { uint32_t r; asm("lop3.b32 %0, %1, %2, %3, 0xF6;" : "=r"(r) : "r"(a), "r"(b), "r"(t)); return r; }
DEVI uint32_t or3(uint32_t a, uint32_t b, uint32_t c) { uint32_t r; asm("lop3.b32 %0, %1, %2, %3, 0xFE;" : "=r"(r) : "r"(a), "r"(b), "r"(c)); return r; }
DEVI bool any_bad(uint32_t x) { return __any_sync(0xFFFFFFFFu, (x & 1u) != 0); }
DEVI uint32_t settag(uint32_t x, uint32_t tag) { return (x & ~1u) | tag; }
DEVI void sts32f(uint32_t a, float v) { asm volatile("st.shared.f32 [%0], %1;" ::"r"(a), "f"(v) : "memory"); }
DEVI void sts32(uint32_t a, uint32_t v) { asm volatile("st.shared.u32 [%0], %1;" ::"r"(a), "r"(v) : "memory"); }
DEVI void sts16(uint32_t a, uint32_t v) { asm volatile("st.shared.u16 [%0], %1;" ::"r"(a), "h"((unsigned short)v) : "memory"); }
DEVI void sts64(uint32_t a, uint32_t x, uint32_t y) { asm volatile("st.shared.v2.u32 [%0], {%1,%2};" ::"r"(a), "r"(x), "r"(y) : "memory"); }
DEVI void sts128(uint32_t a, uint32_t x, uint32_t y, uint32_t z, uint32_t w) {
    asm volatile("st.shared.v4.u32 [%0], {%1,%2,%3,%4};" ::"r"(a), "r"(x), "r"(y), "r"(z), "r"(w) : "memory");
}
DEVI float4 lds128f(uint32_t a) {
    float4 v;
    asm volatile("ld.shared.v4.f32 {%0,%1,%2,%3}, [%4];" : "=f"(v.x), "=f"(v.y), "=f"(v.z), "=f"(v.w) : "r"(a) : "memory");
    return v;
}
DEVI uint4 lds128(uint32_t a) {
    uint4 v;
    asm volatile("ld.shared.v4.u32 {%0,%1,%2,%3}, [%4];" : "=r"(v.x), "=r"(v.y), "=r"(v.z), "=r"(v.w) : "r"(a) : "memory");
    return v;
}
DEVI uint2 lds64(uint32_t a) {
    uint2 v;
    asm volatile("ld.shared.v2.u32 {%0,%1}, [%2];" : "=r"(v.x), "=r"(v.y) : "r"(a) : "memory");
    return v;
}
DEVI uint32_t lds32(uint32_t a) {
    uint32_t v;
    asm volatile("ld.shared.u32 %0, [%1];" : "=r"(v) : "r"(a) : "memory");
    return v;
}
DEVI float ex2(float x) { float r; asm("ex2.approx.ftz.f32 %0, %1;" : "=f"(r) : "f"(x)); return r; }
DEVI float rcp(float x) { float r; asm("rcp.approx.ftz.f32 %0, %1;" : "=f"(r) : "f"(x)); return r; }
DEVI uint32_t clk() { uint32_t c; asm volatile("mov.u32 %0, %%clock;" : "=r"(c)::"memory"); return c; }

DEVI uint64_t mkdesc(uint32_t addr, uint32_t lbo, uint32_t sbo) {
    return (uint64_t)((addr & 0x3FFFF) >> 4) | ((uint64_t)(lbo >> 4) << 16) | ((uint64_t)(sbo >> 4) << 32) | ((uint64_t)1 << 62);
}
DEVI void wg_fence() { asm volatile("wgmma.fence.sync.aligned;" ::: "memory"); }
DEVI void wg_commit() { asm volatile("wgmma.commit_group.sync.aligned;" ::: "memory"); }
template <int N> DEVI void wg_wait() { asm volatile("wgmma.wait_group.sync.aligned %0;" ::"n"(N) : "memory"); }
template <int SC>
DEVI void wg_rs32(float (&d)[16], const uint32_t (&a)[4], uint64_t db) {
    if (SC) {
        asm volatile("wgmma.mma_async.sync.aligned.m64n32k16.f32.bf16.bf16 "
                     "{%0,%1,%2,%3,%4,%5,%6,%7,%8,%9,%10,%11,%12,%13,%14,%15}, {%16,%17,%18,%19}, %20, 1, 1, 1, 0;"
                     : "+f"(d[0]), "+f"(d[1]), "+f"(d[2]), "+f"(d[3]), "+f"(d[4]), "+f"(d[5]), "+f"(d[6]), "+f"(d[7]),
                       "+f"(d[8]), "+f"(d[9]), "+f"(d[10]), "+f"(d[11]), "+f"(d[12]), "+f"(d[13]), "+f"(d[14]), "+f"(d[15])
                     : "r"(a[0]), "r"(a[1]), "r"(a[2]), "r"(a[3]), "l"(db));
    } else {
        asm volatile("wgmma.mma_async.sync.aligned.m64n32k16.f32.bf16.bf16 "
                     "{%0,%1,%2,%3,%4,%5,%6,%7,%8,%9,%10,%11,%12,%13,%14,%15}, {%16,%17,%18,%19}, %20, 0, 1, 1, 0;"
                     : "=f"(d[0]), "=f"(d[1]), "=f"(d[2]), "=f"(d[3]), "=f"(d[4]), "=f"(d[5]), "=f"(d[6]), "=f"(d[7]),
                       "=f"(d[8]), "=f"(d[9]), "=f"(d[10]), "=f"(d[11]), "=f"(d[12]), "=f"(d[13]), "=f"(d[14]), "=f"(d[15])
                     : "r"(a[0]), "r"(a[1]), "r"(a[2]), "r"(a[3]), "l"(db));
    }
}

#define NA 12
#define NPF 6
#define PF1 2
#define PF2 2
#define PF3 4
#define WPF 2
#define VPF 2
#define VORD 0x01234567
#define VSF 0
#define VMF 0
#define VC 1
#define QP 16
#define W2P 0
#define W3P 1
#define QSP 12
#define VSB 0x10F
#define QQP 3
#define CGP 8
#define C0P 9
#define C1P 9
#define PIP 10
#define K0P 2
#define KEP 4
#define KE2 0
#define VTP 0
#define CW 1
#define WV_BOX ((16 - NA) * 2048)
#define WO_BOX 16384
#define SM_WV 0
#define SM_WO (2 * WV_BOX)
#define SM_X (SM_WO + 4 * WO_BOX)
#define SM_XO (SM_X + 32768)
#define SM_MEMT (SM_XO + 12288)
#define SM_OT (SM_MEMT + 4096)
#define SM_VS (SM_OT + 2048)
#define SM_P (SM_VS + 2048)
#define SM_DN (SM_P + 1792)
#define SM_PROF (SM_P + 2048)
#define SM_ST (SM_X + 65536)
#define SM_KV SM_ST
#define SM_SP (SM_KV + 18432)
#define SM_TR (SM_ST + 32768)
#define SM_PI (SM_ST + 65536)
#define SM_BAR (SM_PI + 12288)
#define SM_TOTAL (SM_BAR + 512)
static_assert(NA == 12, "start-up chunks");
static_assert(SM_TOTAL <= 232448, "smem");
#define BAR_XA 32
#define BAR_KV 40
#define BAR_PI 48
#define BAR_RO 64
#define BAR_WF 256
#define BAR_WE 384
#define SM_ROLE (SM_BAR + 72)

#define SPIN_LIMIT (1 << 20)
#define RPOS 26
#define OPOS 2
#define ASF 0
#define KPOS 0
#define CPOS 4
#define DLY_V 350
#define NPRB 2
#define PW 4
#define ZD 0
#define FTM 2
#define XPF 1
#define WOP 2
#define WIN 2
#define EPD 1300
#define ASP 4
#define EPF 0
#define CFAR 1

template <int ID, int N> DEVI void bsync() { asm volatile("bar.sync %0, %1;" ::"n"(ID), "n"(N) : "memory"); }
template <int ID, int N> DEVI void barv() { asm volatile("bar.arrive %0, %1;" ::"n"(ID), "n"(N) : "memory"); }

#define PT(n)
#define PC(n, v)
#define PDUMP()
#define REFRESH() asm volatile("xor.b32 %0, %0, %1;" : "+r"(l16) : "r"(zero))
#define OPQ(x) asm volatile("xor.b32 %0, %0, %1;" : "+r"(x) : "r"(zero))
#define KEEP(x, a, b, c, d) asm volatile("{\n.reg .b32 t;\nlop3.b32 t, %1, %2, %3, 0x80;\nlop3.b32 t, t, %4, %5, 0x80;\nxor.b32 %0, %0, t;\n}" \
                                         : "+r"(x) : "r"(a), "r"(b), "r"(c), "r"(d), "r"(zero))
#define SF() asm volatile("pmevent 1;" ::: "memory")
#define MF() __syncwarp()
#define SB0 1024u

#define XDOFF(ks) ((((ks) >> 2) * 1024 + ((ks) & 3) * 32) >> 4)
template <int SC>
DEVI void wg_ss32t(float (&d)[16], uint64_t da, uint64_t db) {
    if (SC) {
        asm volatile("wgmma.mma_async.sync.aligned.m64n32k16.f32.bf16.bf16 "
                     "{%0,%1,%2,%3,%4,%5,%6,%7,%8,%9,%10,%11,%12,%13,%14,%15}, %16, %17, 1, 1, 1, 1, 0;"
                     : "+f"(d[0]), "+f"(d[1]), "+f"(d[2]), "+f"(d[3]), "+f"(d[4]), "+f"(d[5]), "+f"(d[6]), "+f"(d[7]),
                       "+f"(d[8]), "+f"(d[9]), "+f"(d[10]), "+f"(d[11]), "+f"(d[12]), "+f"(d[13]), "+f"(d[14]), "+f"(d[15])
                     : "l"(da), "l"(db));
    } else {
        asm volatile("wgmma.mma_async.sync.aligned.m64n32k16.f32.bf16.bf16 "
                     "{%0,%1,%2,%3,%4,%5,%6,%7,%8,%9,%10,%11,%12,%13,%14,%15}, %16, %17, 0, 1, 1, 1, 0;"
                     : "=f"(d[0]), "=f"(d[1]), "=f"(d[2]), "=f"(d[3]), "=f"(d[4]), "=f"(d[5]), "=f"(d[6]), "=f"(d[7]),
                       "=f"(d[8]), "=f"(d[9]), "=f"(d[10]), "=f"(d[11]), "=f"(d[12]), "=f"(d[13]), "=f"(d[14]), "=f"(d[15])
                     : "l"(da), "l"(db));
    }
}

DEVI void delay_until(uint32_t t0, uint32_t d) { while (clk() - t0 < d) {} }

#define VR 2
#define CW2 4
template <int I0, int I1>
DEVI void xmma(float (&xa)[16], float (&xb)[16], uint32_t w, int ps, uint32_t zero, const uint32_t (&Wq)[16][4], const uint32_t (&Wk)[16][4],
               const uint32_t (&Wv)[NA][4], const uint32_t (&wv)[16 - NA][4]) {
    const uint64_t xd = mkdesc(SB0 + SM_X, 16, 4096) + (ps & 1) * 1024, vd = mkdesc(SB0 + SM_WV, 8192, 1024);
    uint32_t vo = (w >> 2) * (WV_BOX / 16);
    if (VR ? false : VC == 0 ? I0 < 16 - NA : VC == 1 ? I0 >= 32 && I0 < 48 - NA : I1 > 32 + NA) OPQ(vo);
#pragma unroll
    for (int i = I0; i < I1; i++) {
        if (VC) {
            const int v = (i + (VC == 1 ? NA : 0)) & 15;
            if (i == 0) wg_rs32<0>(xa, Wq[0], xd);
            else if (i < 16) wg_rs32<1>(xa, Wq[i & 15], xd + XDOFF(i & 15));
            else if (i == 16) wg_rs32<0>(xb, Wk[0], xd);
            else if (i < 32) wg_rs32<1>(xb, Wk[i & 15], xd + XDOFF(i & 15));
            else if (i == 32 && v < NA) wg_rs32<0>(xa, Wv[0], xd);
            else if (VR && i == 32) wg_rs32<0>(xa, wv[0], xd + XDOFF(NA));
            else if (VR && v >= NA) wg_rs32<1>(xa, wv[v >= NA ? v - NA : 0], xd + XDOFF(v));
            else if (i == 32) wg_ss32t<0>(xa, (vd & ~0xFFFFFFFFull) | ((uint32_t)vd + vo), xd + XDOFF(NA));
            else if (v < NA) wg_rs32<1>(xa, Wv[v < NA ? v : 0], xd + XDOFF(v));
            else wg_ss32t<1>(xa, (vd & ~0xFFFFFFFFull) | ((uint32_t)vd + (v - NA) * 128 + vo), xd + XDOFF(v));
        } else
        if (i == 0) wg_ss32t<0>(xb, (vd & ~0xFFFFFFFFull) | ((uint32_t)vd + vo), xd + XDOFF(NA));
        else if (i < 16 - NA) wg_ss32t<1>(xb, (vd & ~0xFFFFFFFFull) | ((uint32_t)vd + i * 128 + vo), xd + XDOFF(NA + i));
        else if (i == 16 - NA) wg_rs32<0>(xa, Wq[0], xd);
        else if (i < 32 - NA) wg_rs32<1>(xa, Wq[(i + NA) & 15], xd + XDOFF((i + NA) & 15));
        else if (i < 32) wg_rs32<1>(xb, Wv[(i + NA) & 15], xd + XDOFF((i + NA) & 15));
        else if (i == 32) wg_rs32<0>(xa, Wk[0], xd);
        else wg_rs32<1>(xa, Wk[i & 15], xd + XDOFF(i & 15));
    }
    wg_commit();
}
#define XMMA(I0, I1) xmma<(I0), (I1)>(xa, xb, w, p ^ 1, zero, Wq, Wk, Wv, wv)
DEVI void wg_done(float (&d)[16]) {
    asm volatile("" : "+f"(d[0]), "+f"(d[1]), "+f"(d[2]), "+f"(d[3]), "+f"(d[4]), "+f"(d[5]), "+f"(d[6]), "+f"(d[7]),
                      "+f"(d[8]), "+f"(d[9]), "+f"(d[10]), "+f"(d[11]), "+f"(d[12]), "+f"(d[13]), "+f"(d[14]), "+f"(d[15]) :: "memory");
}
template <int M>
DEVI void xpack(uint32_t (&xp)[8], float (&xa)[16]) {
    wg_done(xa);
#pragma unroll
    for (int i = 0; i < 4; i++) {
        xp[2 * i] = pack2(xa[4 * i], xa[4 * i + (M < 2 ? 2 : 1)]);
        xp[2 * i + 1] = pack2(xa[4 * i + (M < 2 ? 1 : 2)], xa[4 * i + 3]);
    }
}
template <int M>
DEVI uint4 xpeer(uint32_t sb, int ps, uint32_t t16) { return lds128(sb + SM_PI - ((ps & 1) ^ 1) * 12288 + M * 4096 + t16); }
DEVI void xadd(uint32_t (&xp)[8], const uint4& pi) {
    xp[0] = hadd2(xp[0], pi.x); xp[1] = hadd2(xp[1], pi.y); xp[2] = hadd2(xp[2], pi.z); xp[3] = hadd2(xp[3], pi.w);
}
template <int M>
DEVI void xsend(const uint32_t (&xp)[8], uint32_t sb, int ps, uint32_t t16) {
    asm volatile("st.async.weak.shared::cluster.mbarrier::complete_tx::bytes.v4.b32 [%0], {%1,%2,%3,%4}, [%5];"
                 ::"r"((sb ^ 0x1000000) + SM_PI - (ps & 1) * 12288 + M * 4096 + t16), "r"(xp[4]), "r"(xp[5]), "r"(xp[6]), "r"(xp[7]),
                   "r"((sb ^ 0x1000000) + SM_BAR + BAR_PI + (ps & 1) * 8) : "memory");
}
template <int M>
DEVI void xstore(const uint32_t (&xp)[8], uint32_t sb, uint32_t sbw, int ps, uint32_t t16, uint32_t KA) {
    const uint32_t a = SM_XO + M * 2048 + (M < 2 ? (KA & 0xFF) + sbw : (t16 >> 1) + sb);
    sts64(a, xp[0], xp[1]);
    sts64(a + 6144, xp[2], xp[3]);
    xsend<M>(xp, sb, ps, t16);
}
template <int M>
DEVI void xpark(uint32_t (&xp)[8], const uint4& pi, uint32_t sb, uint32_t sbw, int ps, uint32_t t16, uint32_t KA) {
    xadd(xp, pi);
    xstore<M>(xp, sb, sbw, ps, t16, KA);
}
template <uint32_t OFF> DEVI void red2(uint32_t lo, uint32_t hi, uint32_t a, uint32_t b) {
    asm volatile("{\n.reg .b64 a;\nmov.b64 a, {%0,%1};\nred.relaxed.gpu.global.add.noftz.v2.bf16x2 [a+%4], {%2,%3};\n}"
                 ::"r"(lo), "r"(hi), "r"(a), "r"(b), "n"(OFF) : "memory");
}
template <int M, int N>
DEVI void xstart(uint32_t sb, uint32_t w, uint32_t ga, uint32_t xhi, uint32_t j, uint32_t t16, uint32_t KA, const uint32_t (&W)[N][4]) {
    float xa[16], xb[16];
    uint32_t xp[8];
    auto pass = [&](float (&d)[16], int i, int k0, int k1) {
        const uint64_t xd = mkdesc(SB0 + SM_X + (i ? i + 1 : 0) * 16384, 16, 4096), vd = mkdesc(SB0 + SM_WV, 8192, 1024) + (w >> 2) * (WV_BOX / 16);
#pragma unroll
        for (int k = k0; k < k1; k++) {
            if (k == 0) wg_rs32<0>(d, W[0], xd);
            else if (k < N) wg_rs32<1>(d, W[k < N ? k : 0], xd + XDOFF(k));
            else wg_ss32t<1>(d, vd + (k - N) * 128, xd + XDOFF(k));
        }
        wg_commit();
    };
    wg_fence();
    pass(xa, 0, 0, 16);
    pass(xb, 1, 0, ASP);
    if (M == 0) bsync<5, 288>();
    ga += M < 2 ? (KA & 0xFF) + w * 256 : t16 >> 1;
    constexpr uint32_t O = XO_XG + M * 2048, SG = 128 * 6144;
    wg_wait<1>();
    xpack<M>(xp, xa);
    red2<O>(ga, xhi, xp[0], xp[1]); red2<O + 6144>(ga, xhi, xp[2], xp[3]); red2<O + 12288>(ga, xhi, xp[4], xp[5]); red2<O + 18432>(ga, xhi, xp[6], xp[7]);
    if (M == 2) barv<3, 320>();
    wg_fence();
    pass(xb, 1, ASP, 16);
    pass(xa, 2, 0, 16);
    wg_wait<1>();
    xpack<M>(xp, xb);
    red2<O + SG>(ga, xhi, xp[0], xp[1]); red2<O + SG + 6144>(ga, xhi, xp[2], xp[3]);
    red2<O + SG + 12288>(ga, xhi, xp[4], xp[5]); red2<O + SG + 18432>(ga, xhi, xp[6], xp[7]);
    wg_wait<0>();
    xpack<M>(xp, xa);
    red2<O + 2 * SG>(ga + j * 6144, xhi, xp[0], xp[1]);
    red2<O + 2 * SG>(ga + (j ^ 1) * 6144, xhi, xp[2], xp[3]);
    xsend<M>(xp, sb, 0, t16);
}
DEVI void piwait(uint32_t sb, int p, int ps) { mbar_wait(sb + SM_BAR + BAR_PI + p * 8, ((ps + 2) >> 1) & 1); }

DEVI uint32_t par(uint32_t off) { return __popc(off & 0xB2000u) & 1; }
DEVI uint32_t probe(uint32_t lo, uint32_t hi) {
    uint32_t best = 0xFFFFFFFFu, x = 0;
    stg4<0>(lo, hi, 0, 0, 0, 0);
    stg4<16>(lo, hi, 0, 0, 0, 0);
#pragma unroll 1
    for (int r = 0; r < NPRB; r++) {
        const uint32_t t0 = clk();
        asm volatile("{\n.reg .b64 a;\nmov.b64 a, {%1,%2};\natom.relaxed.gpu.global.add.u32 %0, [a], 2;\n}" : "=r"(x) : "r"(lo), "r"(hi) : "memory");
        if (x == 0xFFFFFFFFu) die(1 << 23);
        best = min(best, clk() - t0);
    }
    return best;
}

DEVI void xload(uint32_t sb, uint32_t u, uint32_t j, int ps, const CUtensorMap* tmx) {
    if (elect()) {
        const uint32_t sg = ps + 4 - (u & 1) + (u >> 1);
        mbar_expect(sb + SM_BAR + BAR_XA, sg < NSEG ? 4096 : 0);
        if (sg < NSEG) tma3d(sb + SM_X + (ps & 1) * 16384 + u * 4096, tmx, sb + SM_BAR + BAR_XA, 0, sg * 32 + (j ^ ((u & 1) * 2 + (u >> 1))) * 8, j * 4);
    }
}
DEVI uint32_t rpage(uint32_t j, int s) { return (s & 3) * 65536 + (j & 1) * 8192 + (((s ^ (s >> 1) ^ j ^ (j >> 1)) & 1) << 12); }

#define RLOAD() { m0 = ldg4<XO_R>(a, ah); n0 = ldg4<XO_R + 16384>(a, ah); e0 = ldg1<XO_R + 32768>(e, eh); f0 = ldg1<XO_R + 33792>(e, eh); }
DEVI bool ruse(uint32_t a, const uint4& m0, const uint4& n0, uint32_t e0, uint32_t f0) {
    const uint32_t a0 = hadd2(m0.w, n0.w), b0 = hadd2(e0, f0);
    stsm4(a, hadd2(m0.x, n0.x), hadd2(m0.y, n0.y), hadd2(m0.z, n0.z), __byte_perm(a0, b0, 0x5410));
    return __any_sync(0xFFFFFFFFu, (a0 & b0 & 0x42000000u) != 0x42000000u);
}

#define GST(i) (SM_WO + (i) * 49152)
#define BAR_GF 128
#define BAR_GE (BAR_GF + 64)
#define BAR_GX (BAR_GE + 32)
#define D4(c, i) #c "f"(d[i]), #c "f"(d[i + 1]), #c "f"(d[i + 2]), #c "f"(d[i + 3])
#define D16(c, i) D4(c, i), D4(c, i + 4), D4(c, i + 8), D4(c, i + 12)
DEVI void mwait(uint32_t bar, uint32_t parity) {
    asm volatile("{\n.reg .pred p;\n.reg .b32 c;\nmbarrier.try_wait.parity.shared::cta.b64 p, [%0], %1;\n@p bra.uni D;\nmov.b32 c, 0;\n"
                 "L:\nadd.u32 c, c, 1;\nsetp.gt.u32 p, c, 4194304;\n@p st.shared.u32 [c], c;\n"
                 "mbarrier.try_wait.parity.shared::cta.b64 p, [%0], %1;\n@!p bra.uni L;\nD:\n}" ::"r"(bar), "r"(parity) : "memory");
}
DEVI void wg_ss256t(float (&d)[128], uint64_t da, uint64_t db) {
    asm volatile("wgmma.mma_async.sync.aligned.m64n256k16.f32.bf16.bf16 "
        "{%0,%1,%2,%3,%4,%5,%6,%7,%8,%9,%10,%11,%12,%13,%14,%15,%16,%17,%18,%19,%20,%21,%22,%23,%24,%25,%26,%27,%28,%29,%30,%31,%32,%33,%34,%35,%36,%37,%38,%39,%40,%41,%42,%43,%44,%45,%46,%47,%48,%49,%50,%51,%52,%53,%54,%55,%56,%57,%58,%59,%60,%61,%62,%63,%64,%65,%66,%67,%68,%69,%70,%71,%72,%73,%74,%75,%76,%77,%78,%79,%80,%81,%82,%83,%84,%85,%86,%87,%88,%89,%90,%91,%92,%93,%94,%95,%96,%97,%98,%99,%100,%101,%102,%103,%104,%105,%106,%107,%108,%109,%110,%111,%112,%113,%114,%115,%116,%117,%118,%119,%120,%121,%122,%123,%124,%125,%126,%127}, "
        "%128, %129, 1, 1, 1, 1, 1;"
        : D16(+, 0), D16(+, 16), D16(+, 32), D16(+, 48), D16(+, 64), D16(+, 80), D16(+, 96), D16(+, 112) : "l"(da), "l"(db));
}
template <int O, int KB> DEVI void g_half(float (&d)[64], uint64_t da) {
    const uint64_t db = mkdesc(SB0 + GST(KB & 3) + 16384 + O * 256, 8192, 1024);
#pragma unroll
    for (int k = 0; k < 4; k++)
        asm volatile("wgmma.mma_async.sync.aligned.m64n128k16.f32.bf16.bf16 "
            "{%0,%1,%2,%3,%4,%5,%6,%7,%8,%9,%10,%11,%12,%13,%14,%15,%16,%17,%18,%19,%20,%21,%22,%23,%24,%25,%26,%27,%28,%29,%30,%31,%32,%33,%34,%35,%36,%37,%38,%39,%40,%41,%42,%43,%44,%45,%46,%47,%48,%49,%50,%51,%52,%53,%54,%55,%56,%57,%58,%59,%60,%61,%62,%63}, "
            "%64, %65, 1, 1, 1, 1, 1;"
            : D16(+, 0), D16(+, 16), D16(+, 32), D16(+, 48) : "l"(da + (KB & 3) * 3072 + k * 16), "l"(db + k * 128));
}
DEVI void g_load(uint32_t sb, uint32_t u, uint32_t role, uint32_t kb, uint32_t xlo, uint32_t xhi, const CUtensorMap* tmb) {
    const uint32_t st = kb & 3, bar = sb + SM_BAR + BAR_GF + u * 32 + st * 8, dst = sb + GST(st), k = (role & 1) * 32 + kb;
    if (!elect()) return;
    mbar_expect(bar, u ? 8192 : 40960);
    bulk_g2s(dst + u * 8192, xlo + XO_OX + (k * 16 + (role >> 3)) * 16384 + u * 8192, xhi, 8192, bar);
    if (u == 0) {
        tma3d(dst + 16384, tmb, bar, 0, k * 64, ((role & 7) ^ 1) * 2);
        tma3d(dst + 32768, tmb, bar, 0, k * 64, (role & 7) * 2);
    }
}
DEVI void g_arrive(uint32_t a, uint32_t xhi, uint32_t n) {
    if (elect()) asm volatile("{\n.reg .b64 a;\nmov.b64 a, {%0,%1};\nred.release.gpu.global.inc.u32 [a], %2;\n}" ::"r"(a), "r"(xhi), "r"(n - 1) : "memory");
}
DEVI void g_wait(uint32_t a, uint32_t xhi) {
    int it = 0;
    uint32_t v;
    do {
        asm volatile("{\n.reg .b64 a;\nmov.b64 a, {%1,%2};\nld.acquire.gpu.global.u32 %0, [a];\n}" : "=r"(v) : "r"(a), "r"(xhi) : "memory");
        if (++it > SPIN_LIMIT) die(it);
    } while (__any_sync(0xFFFFFFFFu, v));
    asm volatile("fence.proxy.async.global;" ::: "memory");
}
#define SE 2
#define DLY_S 0
#define VX 1
#define VH 1
#define VD 1
#define SM_VP (SM_TR + 12288)
#define JV(h, j) (VH < 2 ? (j) ^ ((par((h) * 8192) ^ VH) << 1) : (j))
#define SEU 0
#define VA 0
#define VLP 0
#define VCP 1
#define SEED 0
#define VB 0
#define RCP 0
#define XLP 0
#define RE 0
#define DLY_E 300
#define DLY_T 200
#define B3 0
#define GD 200
#define GE 1
#define GH 1
#define GS 1
#define GP 1
DEVI void g_done(float (&d)[64]) { asm volatile("" : D16(+, 0), D16(+, 16), D16(+, 32), D16(+, 48)::"memory"); }
DEVI void g_main(uint32_t sb, uint32_t w, uint32_t role, const CUtensorMap* tmy, void* out) {
    const uint32_t bar = sb + SM_BAR, t16 = threadIdx.x * 16;
    const uint64_t da = (mkdesc(SB0 + GST(0), 128, 1024) & ~((uint64_t)3 << 62)) + (w >> 2) * 512;
    float d[128];
#pragma unroll
    for (int i = 0; i < 128; i++) d[i] = 0.f;
#define GFULL(kb) { mwait(bar + BAR_GF + ((kb) & 3) * 8, ((kb) >> 2) & 1); if (w >= 4) mwait(bar + BAR_GF + 32 + ((kb) & 3) * 8, ((kb) >> 2) & 1); }
#pragma unroll 1
    for (uint32_t kb = 0; kb < (GE ? 28 : 29); kb++) {
        GFULL(kb);
        if (kb == 0 && threadIdx.x == 128) PG(4);
        if (kb == 4 && threadIdx.x == 0) PG(5);
        const uint64_t a = da + (kb & 3) * 3072, b = mkdesc(SB0 + GST(0) + 16384, 8192, 1024) + (kb & 3) * 3072;
        wg_fence();
#pragma unroll
        for (int k = 0; k < 4; k++) wg_ss256t(d, a + k * 16, b + k * 128);
        wg_commit();
        wg_wait<1>();
        if (kb > 0 && elect()) mbar_arrive(bar + BAR_GE + ((kb - 1) & 3) * 8);
    }
    if (GE) { GFULL(28); }
    else { GFULL(29); GFULL(30); GFULL(31); }
    wg_wait<0>();
    if (GE && elect()) mbar_arrive(bar + BAR_GE + 24);
    float x[64], y[64];
#pragma unroll
    for (int i = 0; i < 64; i++) asm volatile("mov.b32 %0, %1;" : "=f"(x[i]) : "f"(d[i]) : "memory");
    SF();
#pragma unroll
    for (int i = 0; i < 64; i++) asm volatile("mov.b32 %0, %1;" : "=f"(y[i]) : "f"(d[i + 64]) : "memory");
    SF();
#define GFREE() if (elect()) asm volatile("mbarrier.arrive.relaxed.cluster.shared::cluster.b64 _, [%0];" ::"r"((bar ^ 0x1000000) + BAR_GX) : "memory")
#define GSW(i) ((i) * 4096 + (GE && (i) >= 4 ? GST(0) : 0))
#define GSEND(i0) _Pragma("unroll") for (int i = (i0); i < (i0) + 4; i++) \
        asm volatile("st.async.weak.shared::cluster.mbarrier::complete_tx::bytes.v4.b32 [%0], {%1,%2,%3,%4}, [%5];" \
                     ::"r"((sb ^ 0x1000000) + GSW(i) + t16), "r"(pack2(x[8 * i], x[8 * i + 1])), "r"(pack2(x[8 * i + 2], x[8 * i + 3])), \
                       "r"(pack2(x[8 * i + 4], x[8 * i + 5])), "r"(pack2(x[8 * i + 6], x[8 * i + 7])), "r"((bar ^ 0x1000000) + BAR_GX + 8) : "memory")
    if (GE) {
        wg_fence();
        g_half<0, 28>(x, da);
        wg_commit();
        GFULL(29);
        wg_fence();
        g_half<0, 29>(x, da);
        wg_commit();
        GFULL(30);
        wg_fence();
        g_half<0, 30>(x, da);
        wg_commit();
        GFULL(31);
        wg_fence();
        g_half<0, 31>(x, da);
        wg_commit();
        g_half<64, 28>(y, da);
        if (GE == 2) g_half<64, 29>(y, da);
        wg_commit();
        wg_wait<1>();
        g_done(x);
        GFREE();
        GSEND(0);
        wg_fence();
        if (GE != 2) g_half<64, 29>(y, da);
        if (GE != 1) g_half<64, 30>(y, da);
        wg_commit();
        mwait(bar + BAR_GX, 0);
        GSEND(4);
        wg_fence();
        if (GE == 1) g_half<64, 30>(y, da);
        g_half<64, 31>(y, da);
        wg_commit();
        mwait(bar + BAR_GX + 8, 0);
        if (threadIdx.x == 0) PG(1);
#pragma unroll
        for (int i = 0; i < 8; i++) {
            const uint4 a = lds128(sb + GSW(i) + t16);
            float* e = x + 8 * i;
            e[0] = lo_f(a.x); e[1] = hi_f(a.x); e[2] = lo_f(a.y); e[3] = hi_f(a.y); e[4] = lo_f(a.z); e[5] = hi_f(a.z); e[6] = lo_f(a.w); e[7] = hi_f(a.w);
        }
        g_done(x);
        SF();
        wg_wait<0>();
        g_done(y);
        if (threadIdx.x == 0) PG(7);
    } else {
        GFREE();
        wg_fence();
        g_half<0, 29>(x, da);
        g_half<0, 30>(x, da);
        g_half<0, 31>(x, da);
        wg_commit();
        g_half<64, 29>(y, da);
        wg_commit();
        wg_wait<1>();
        g_done(x);
        mwait(bar + BAR_GX, 0);
        GSEND(0);
        wg_fence();
        g_half<64, 30>(y, da);
        wg_commit();
        GSEND(4);
        wg_fence();
        g_half<64, 31>(y, da);
        wg_commit();
        wg_wait<0>();
        g_done(y);
        if (threadIdx.x == 0) PG(7);
        mwait(bar + BAR_GX + 8, 0);
        if (threadIdx.x == 0) PG(1);
    }
    const uint32_t lane = threadIdx.x & 31, o = sb + GST(1) + w * 2048;
    char* go = (char*)out + ((role >> 3) * 128 + w * 16 + (lane >> 3)) * 4096 + (role & 7) * 256 + (lane & 7) * 16;
#pragma unroll
    for (int i = 0; i < 8; i++) {
        float* e = y + 8 * i;
        if (GE) {
#pragma unroll
            for (int n = 0; n < 8; n++) e[n] += x[8 * i + n];
        } else {
            const uint4 a = lds128(sb + i * 4096 + t16);
            e[0] += lo_f(a.x); e[1] += hi_f(a.x); e[2] += lo_f(a.y); e[3] += hi_f(a.y); e[4] += lo_f(a.z); e[5] += hi_f(a.z); e[6] += lo_f(a.w); e[7] += hi_f(a.w);
        }
        stsm4(o + (i >> 2) * 49152 + (lane & 15) * 128 + ((((i & 3) * 2 + (lane >> 4)) ^ (lane & 7)) << 4),
              pack2(e[0], e[1]), pack2(e[2], e[3]), pack2(e[4], e[5]), pack2(e[6], e[7]));
        if (i == 3 || i == 7) {
            if (GS) {
                __syncwarp();
#pragma unroll
                for (int m = 0; m < 4; m++)
                    *(uint4*)(go + m * 16384 + (i >> 2) * 128) =
                        lds128(o + (i >> 2) * 49152 + m * 512 + (lane >> 3) * 128 + (((lane & 7) ^ ((m & 1) * 4 + (lane >> 3))) << 4));
            } else {
                asm volatile("fence.proxy.async.shared::cta;" ::: "memory");
                __syncwarp();
                if (elect())
                    asm volatile("cp.async.bulk.tensor.2d.global.shared::cta.bulk_group [%0, {%2, %3}], [%1];\ncp.async.bulk.commit_group;"
                                 ::"l"(tmy), "r"(o + (i >> 2) * 49152), "r"((role & 7) * 128 + (i >> 2) * 64), "r"((role >> 3) * 128 + w * 16) : "memory");
            }
        }
    }
    if (threadIdx.x == 0) PG(6);
    if (!GS) asm volatile("cp.async.bulk.wait_group.read 0;" ::: "memory");
}

DEVI void kvload(uint32_t sb, uint32_t u, uint32_t h, uint32_t j, int sg, uint32_t xlo, uint32_t xhi) {
    const uint32_t o = u == 0 ? 0 : 2048;
    mbar_expect(sb + SM_BAR + BAR_KV, 6144 - o);
    bulk_g2s(sb + SM_KV + u * 4096 + o, xlo + XO_XG + (((sg & 7) * 32 + h) * 4 + ((j + u) & 3)) * 6144 + o, xhi, 6144 - o, sb + SM_BAR + BAR_KV);
}
DEVI void helper_step(uint32_t sb, uint32_t w, uint32_t h, uint32_t j, uint32_t& l16, uint32_t xlo, uint32_t xhi, uint32_t zero, int s,
                      const CUtensorMap* tmx, const CUtensorMap* tmb) {
    const uint32_t u = w - 8, bq = sb + SM_BAR;
    bsync<1, 384>();
    PT(0);
    PDUMP();
    PT(1);
    if (s == NSEG - 2 && u < 2) g_arrive(xlo + XO_TK + 128, xhi, 256);
    uint32_t old = 0;
#define RCLEAR(n) if (RCP == (n) && u > 0 && s + 3 < NSEG) \
        asm volatile("{\n.reg .b64 a;\nmov.b64 a, {%1,%2};\natom.relaxed.gpu.global.exch.b32 %0, [a], 0;\n}" \
                     : "=r"(old) : "r"(xlo + XO_R + rpage(j, s + 2) + (u - 1) * 16384 + h * 128 + (l16 >> 2)), "r"(xhi) : "memory");
    RCLEAR(1);
    const bool gl = u == 0 || (u == 1 && h < 30);
    if (GP == 1 && s == NSEG - 1 && gl) g_load(sb, u, h * 4 + j, 1, xlo, xhi, tmb);
    const uint32_t ctag = ((s >> 1) & 1) ^ 1;
    const uint32_t av = xlo + ((s & 1) * 32 + h) * 8192 + u * 512;
    mbar_wait(bq + BAR_XA, (s + 1) & 1);
    if (B3 == 8) barv<5, 384>();
    bsync<8, 384>();
    const uint32_t t8 = clk(), gs = xlo + XO_XG + ((((s + 3) & 7) * 32 + h) * 4 + j) * 6144;
    RCLEAR(2);
    const bool se = B3 % 8 == 0 && SE && u == SEU && s + 3 < NSEG;
    uint32_t tv = ctag ^ 1, ro = 0;
    if (se) {
        asm volatile("fence.proxy.async.shared::cta;" ::: "memory");
        if (SE == 4) delay_until(t8, DLY_E);
        if ((SE == 1 || SE == 4) && elect()) bulk_s2g(gs, xhi, sb + SM_XO, 4096);
    } else if (RE && u == 1 && s + 2 < NSEG) {
        asm volatile("fence.proxy.async.shared::cta;" ::: "memory");
        const uint32_t cb0 = (h >> 1) * 32768 + (j & 1) * 16384 + (h & 1) * 8192;
        delay_until(t8, DLY_T);
        tv = ldg1<XO_CQK>((xlo + cb0 + ((par(cb0) ^ (j >> 1) ^ CFAR ^ 1) << 12)) ^ ((s & 1) * 0x81000), xhi);
        SF();
    }
    if (B3 != 6 || u || SE == 2) delay_until(t8, DLY_V);
    if (se && SE == 2 && elect()) bulk_s2g(gs, xhi, sb + SM_XO, 4096);
    PT(4);
    int it = 0;
    uint4 d1, d2, d3;
    uint2 e1, e2, e3;
    const uint32_t ae = av - u * 512 + (u & 1) * 256;
    const uint32_t jv = JV(h, j);
#define VLOAD() { if (!VD) d1 = ldg4<XO_CV>(av + (jv ^ 1) * 2048 + l16, xhi); \
        d2 = ldg4<XO_CV>(av + (jv ^ 2) * 2048 + l16, xhi); d3 = ldg4<XO_CV>(av + (jv ^ 3) * 2048 + l16, xhi); \
        if (B3 == 6 && VX) { if (!VD) e1 = ldg2<XO_CV>(ae + (jv ^ 1) * 2048 + (l16 >> 1), xhi); \
                       e2 = ldg2<XO_CV>(ae + (jv ^ 2) * 2048 + (l16 >> 1), xhi); e3 = ldg2<XO_CV>(ae + (jv ^ 3) * 2048 + (l16 >> 1), xhi); } \
        if (VD) { d1 = lds128(sb + SM_VP + (s & 1) * 2048 + u * 512 + l16); \
                  if (B3 == 6 && VX) e1 = lds64(sb + SM_VP + (s & 1) * 2048 + (u & 1) * 256 + (l16 >> 1)); } }
#define XSEND(F, C) if (u < 2) { \
        if (F) asm volatile("fence.proxy.async.shared::cta;" ::: "memory"); \
        if ((C) && elect()) { \
            const uint32_t sg = s + 3 - u; \
            if (sg < NSEG) { \
                const uint32_t ga = xlo + XO_XG + (((sg & 7) * 32 + h) * 4 + (j ^ (2 * u))) * 6144, sa = sb + SM_XO + u * 6144; \
                if (u == 0) bulk_s2g(ga + (SE ? 4096 : 0), xhi, sa + (SE ? 4096 : 0), SE ? 2048 : 6144); \
                else bulk_red(ga + ro, xhi, sa + ro, 6144 - ro); \
            } \
        } \
    }
    if (B3 == 8) {
        bsync<3, 384>();
        if (DLY_S) delay_until(clk(), DLY_S);
        XSEND(true, true);
    } else if (B3 == 6 && u == 0) {
        const uint32_t ga = xlo + XO_XG + ((((s + 3) & 7) * 32 + h) * 4 + j) * 6144, o = SE == 1 || SE == 2 ? 4096 : 0;
        if (o) {
            asm volatile("fence.proxy.async.shared::cta;" ::: "memory");
            if (s + 3 < NSEG && elect()) bulk_s2g(ga, xhi, sb + SM_XO, o);
        }
        bsync<3, 288>();
        if (DLY_S) delay_until(clk(), DLY_S);
        asm volatile("fence.proxy.async.shared::cta;" ::: "memory");
        if (elect()) {
            if (SE == 3 && s + 3 < NSEG) bulk_s2g(ga + o, xhi, sb + SM_XO + o, 6144 - o);
            if (s + 2 < NSEG) bulk_red(xlo + XO_XG + ((((s + 2) & 7) * 32 + h) * 4 + (j ^ 2)) * 6144, xhi, sb + SM_XO + 6144, 6144);
            if (SE != 3 && s + 3 < NSEG) bulk_s2g(ga + o, xhi, sb + SM_XO + o, 6144 - o);
        }
    } else {
    if (B3 == 6) VLOAD();
    if (B3 && B3 < 6) {
        VLOAD();
        bsync<B3 == 2 ? 4 : 3, 384>();
        XSEND(true, B3 < 3 || B3 == 5 || (B3 == 4 && u == 0));
    }
    while (true) {
        if (B3 % 7 == 0) VLOAD();
        if (RE && it == 0) {
            SF();
            if (!any_bad(tv ^ ctag)) {
                if (elect()) bulk_red(xlo + XO_XG + ((((s + 2) & 7) * 32 + h) * 4 + (j ^ 2)) * 6144, xhi, sb + SM_XO + 6144, 4096);
                ro = 4096;
            }
        }
        if (se && SE == 3 && it == 0 && elect()) bulk_s2g(gs, xhi, sb + SM_XO, 4096);
        uint32_t tg = or3(tagx2(d1.x, d1.z, ctag), tagx2(d2.x, d2.z, ctag), tagx2(d3.x, d3.z, ctag));
        if (B3 == 6 && VX) tg = or3(tg, tagx2(e1.x, e2.x, ctag), e3.x ^ ctag);
        const bool bad = any_bad(tg);
        if (B3 == 6 && VX) sts64(sb + SM_VS + (u & 1) * 256 + (l16 >> 1), hadd2(hadd2(e1.x, e2.x), e3.x), hadd2(hadd2(e1.y, e2.y), e3.y));
        sts128(sb + SM_VS + u * 512 + l16, hadd2(hadd2(d1.x, d2.x), d3.x), hadd2(hadd2(d1.y, d2.y), d3.y), hadd2(hadd2(d1.z, d2.z), d3.z),
               hadd2(hadd2(d1.w, d2.w), d3.w));
        if (VA) asm volatile("{\n.reg .pred p;\nsetp.eq.u32 p, %0, 0;\n@p bar.arrive 5, 384;\n}" ::"r"((uint32_t)bad) : "memory");
        if (B3 % 7 == 0) REFRESH();
        if (!bad) break;
        if (B3 % 7) { REFRESH(); VLOAD(); }
        if (++it > SPIN_LIMIT) die(it);
    }
    PC(26, it);
    PT(5);
    if (VB) barv<11, 384>();
    else if (!VA) barv<5, B3 == 6 ? 352 : 384>();
    }
    if (B3 % 7 == 0) {
        bsync<3, 384>();
        XSEND(true, true);
    }
    if (B3 == 3 || B3 == 4) XSEND(false, B3 == 3 || u == 1);
    PT(6);
    RCLEAR(0);
    PT(7);
    bsync<7, 384>();
    if (s + 1 < NSEG && elect()) kvload(sb, u, h, j, s + 1, xlo, xhi);
    RCLEAR(3);
    if (XLP == 1) xload(sb, u, j, s + 1, tmx);
    if (u < (B3 == 6 ? 1 : 2)) {
        asm volatile("cp.async.bulk.wait_group.read 0;" ::: "memory");
        if (elect()) {
            mbar_expect(bq + BAR_PI + ((s & 1) ^ 1) * 8, 6144);
            if (B3 == 6) mbar_expect(bq + BAR_PI + ((s & 1) ^ 1) * 8, 6144);
        }
    }
    PT(8);
    if (GP && s == NSEG - 2 && gl) g_wait(xlo + XO_TK + 128, xhi);
    if (s + 1 < NSEG) bsync<10, 384>();
    if (XLP == 0) xload(sb, u, j, s + 1, tmx);
    RCLEAR(4);
    if (s == NSEG - 2 && gl) {
        if (!GP) g_wait(xlo + XO_TK + 128, xhi);
        g_load(sb, u, h * 4 + j, 0, xlo, xhi, tmb);
        if (GP == 0 || GP == 3) g_load(sb, u, h * 4 + j, 1, xlo, xhi, tmb);
    }
    asm volatile("cp.async.bulk.wait_group 0;" ::: "memory");
    if (s + 1 < NSEG) mbar_wait(bq + BAR_KV, (s + 1) & 1);
    asm volatile("lop3.b32 %0, %0, %1, %2, 0x78;" : "+r"(l16) : "r"(old), "r"(zero));
    PT(15);
}
DEVI void tickets_done(uint32_t* tk) {
    if (atomicInc(tk + 2, gridDim.x / 2 - 64) == gridDim.x / 2 - 64) { tk[0] = 0; tk[1] = 0; }
}

__global__ void __cluster_dims__(2, 1, 1) __launch_bounds__(384, 1)
chain_kernel(const __grid_constant__ CUtensorMap tmq, const __grid_constant__ CUtensorMap tmk,
             const __grid_constant__ CUtensorMap tmv, const __grid_constant__ CUtensorMap tmo,
             const __grid_constant__ CUtensorMap tmx, const __grid_constant__ CUtensorMap tmb, const __grid_constant__ CUtensorMap tmy,
             const bf16* __restrict__ mem0, const bf16* __restrict__ xg,
             uint32_t xlo, uint32_t xhi, uint32_t zero, int nseg, bf16* __restrict__ out) {
    extern __shared__ __align__(1024) uint8_t smem[];
    const uint32_t tstart = clk();
    const uint32_t rk = smem_u32(smem) & 0x1000000;
    if (rk == 0 && (threadIdx.x & 31) == 0 && threadIdx.x - 32 < 32 * PW)
        sts32(SB0 + SM_ROLE + 4 + (threadIdx.x >> 3), probe(xlo + XO_PB + (threadIdx.x & 32) * 128 + (threadIdx.x & 64) * 256 + blockIdx.x * 16, xhi));
    __syncwarp();
    if ((smem_u32(smem) & 0xFFFFFF) != SB0) die(1 << 23);
    asm volatile("griddepcontrol.launch_dependents;" ::: "memory");
    const uint32_t w = __reduce_max_sync(0xFFFFFFFFu, threadIdx.x >> 5);
    const uint32_t sb = __reduce_max_sync(0xFFFFFFFFu, smem_u32(smem));
    const uint32_t bq = sb + SM_BAR;
    uint32_t l16 = __shfl_sync(0xFFFFFFFFu, (threadIdx.x & 31) * 16, threadIdx.x & 31);
    if (threadIdx.x == 0) {
        mbar_init(bq, 1);
        for (int i = 0; i < 24; i++) mbar_init(bq + BAR_WF + i * 8, i < 16 ? 1 : 8);
        mbar_init(bq + BAR_XA, 4); mbar_init(bq + BAR_KV, 4); mbar_init(bq + BAR_PI, 2); mbar_init(bq + BAR_PI + 8, 2);
        for (int i = 0; i < 14; i++) mbar_init(bq + BAR_GF + i * 8, i < 8 || i == 13 ? 1 : 8);
        mbar_expect(bq + BAR_GX + 8, 32768);
        mbar_init(bq + BAR_RO, 1);
        mbar_expect(bq + BAR_RO, 4);
        mbar_expect(bq + BAR_PI, 6144);
        mbar_expect(bq + BAR_PI, 6144);
        asm volatile("fence.mbarrier_init.release.cluster;" ::: "memory");
        asm volatile("fence.proxy.async.shared::cta;" ::: "memory");
    }
    __syncwarp();
    asm volatile("barrier.cluster.arrive.relaxed.aligned;" ::: "memory");
    if (w == 9) {
#pragma unroll 1
        for (int e = 0; e < 12; e++) sts128(sb + SM_WO + e * 512 + l16, 0, 0, 0, 0);
    }
    if (w == 8 && blockIdx.x < 128) {
        if (XPF && elect()) {
            asm volatile("cp.async.bulk.prefetch.L2.global [%0], 3072;" ::"l"((const char*)xg + blockIdx.x * 3072) : "memory");
            asm volatile("prefetch.tensormap [%0];\nprefetch.tensormap [%1];\nprefetch.tensormap [%2];\nprefetch.tensormap [%3];\nprefetch.tensormap [%4];"
                         ::"l"(&tmq), "l"(&tmx), "l"(&tmk), "l"(&tmv), "l"(&tmo) : "memory");
        }
#pragma unroll 1
        for (int i = 0; i < EPF; i++) {
            if (i) delay_until(clk(), EPD);
            if (elect())
                asm volatile("cp.async.bulk.prefetch.tensor.3d.L2.global [%0, {0, %1, %2}];" ::"l"(&tmq), "r"((blockIdx.x & 3) * 256 + i * 64), "r"((blockIdx.x >> 2) * 2) : "memory");
        }
    }
    if (rk == 0 && w <= PW) bsync<2, 32 * PW + 32>();
    asm volatile("barrier.cluster.wait.aligned;" ::: "memory");
    if (rk == 0 && threadIdx.x == 0) {
        uint32_t t1 = lds32(sb + SM_ROLE + 8), t0 = lds32(sb + SM_ROLE + 12);
        if (PW == 4) { t1 = min(t1, lds32(sb + SM_ROLE + 16)); t0 = min(t0, lds32(sb + SM_ROLE + 20)); }
        uint32_t side = (t0 < t1 ? 0u : 1u) ^ par(XO_PB);
        uint32_t* tk = (uint32_t*)(((uint64_t)xhi << 32) | (xlo + XO_TK));
        uint32_t t = atomicAdd(tk + side, 1u);
        if (t >= 32) {
            uint2 c;
            int it = 0;
            do {
                c = ldg2<XO_TK>(xlo, xhi);
                if (++it > SPIN_LIMIT) die(it);
            } while (c.x + c.y != gridDim.x / 2);
            t += (side ? c.x : c.y) - 32;
            side ^= 1;
            if (t >= 32) tickets_done(tk);
        }
#pragma unroll
        for (uint32_t r = 0; r < 2; r++)
            asm volatile("st.async.weak.shared::cluster.mbarrier::complete_tx::bytes.b32 [%0], %1, [%2];"
                         ::"r"(sb + SM_ROLE + (r << 24)), "r"(t * 4 + side * 2 + r), "r"(bq + BAR_RO + (r << 24)) : "memory");
    }
    __syncwarp();
    mbar_wait(bq + BAR_RO, 0);
    const uint32_t role = __reduce_max_sync(0xFFFFFFFFu, lds32(sb + SM_ROLE));
    if (role >= 128) return;
    const uint32_t h = role >> 2, j = role & 3;
    if (FTM && w == 11 && elect())
#pragma unroll
        for (uint32_t c = 0; c < FTM; c++) {
            mbar_expect(bq + BAR_WF + c * 8, 16384);
            tma3d(sb + SM_ST + c * 16384, &tmq, bq + BAR_WF + c * 8, 0, j * 256 + c * 64, h * 2);
        }

    if (w >= 8) {
        asm volatile("setmaxnreg.dec.sync.aligned.u32 24;");
        const uint32_t u = w - 8;
        if (u == 3) {
#pragma unroll 1
            for (uint32_t c = FTM; c < 16; c++) {
                if (c >= WIN) mbar_wait(bq + BAR_WF + (c - WIN) * 8, 0);
                if (l16 == 0) PG(16 + c);
                if (c == 12 + WOP) bsync<2, 64>();
                if (c >= 4 && c < 12 && c != 10) mbar_wait(bq + BAR_WE + (c - 4) * 8, 0);
                if (elect()) {
                    const uint32_t b = bq + BAR_WF + c * 8;
                    mbar_expect(b, 16384);
                    if (c >= 12) tma2d(sb + SM_WO + (c - 12) * WO_BOX, &tmo, b, j * 256 + (c - 12) * 64, h * 128);
                    else tma3d(c == 10 ? sb + SM_WV : sb + SM_ST + (c & 3) * 16384, c < 4 ? &tmq : c < 8 ? &tmk : &tmv, b, 0, j * 256 + ((c ^ (c >= 10)) & 3) * 64, h * 2);
                }
            }
#pragma unroll 1
            for (uint32_t c = 16 - WIN; c < 16; c++) mbar_wait(bq + BAR_WF + c * 8, 0);
            if (l16 == 0) PG(15);
        } else if (u == 0) {
            if (elect()) {
                mbar_expect(bq, 49152);
#pragma unroll 1
                for (uint32_t i = 0; i < 12; i++)
                    tma3d(sb + SM_X + (i < 4 ? i : i + 4) * 4096, &tmx, bq, 0, i < 8 ? i * 8 : (j ^ ((0xBD98u >> (i - 8) * 4) & 15)) * 8, j * 4);
            }
#pragma unroll 1
            for (int i = 0; i < 4; i++) xload(sb, i, j, -1, &tmx);
            bsync<3, 320>();
            if (l16 == 0) PG(32);
            if (GH && j == 0 && elect()) asm volatile("{\n.reg .b64 a;\nmov.b64 a, {%0,%1};\nred.relaxed.gpu.global.inc.u32 [a+64], 4;\n}" ::"r"(xlo + XO_FL + h * 128), "r"(xhi) : "memory");
            __syncwarp();
            g_arrive(xlo + XO_FL + h * 128, xhi, 4);
            if (WOP < 4) barv<2, 64>();
            if (l16 == 0) PG(33);
            g_wait(xlo + XO_FL + h * 128, xhi);
            if (l16 == 0) PG(34);
#pragma unroll 1
            for (int i = 0; i < 4; i++)
                if (elect()) kvload(sb, i, h, j, 0, xlo, xhi);
            mbar_wait(bq + BAR_KV, 0);
            if (l16 == 0) PG(14);
        } else if (u == 1) {
            const uint32_t l = l16 >> 4, x = h * 8 + (l >> 2), d = (x & ~31u) + (l & 3) * 8 + ((x & 31) >> 2) + (x & 3) * 2 * DM;
            const unsigned short* m0 = (const unsigned short*)mem0 + j * 256;
            const uint32_t v1 = m0[d] | (((l & 3) == 3 ? 0x4200u : m0[d + DM]) << 16);
            const uint32_t v3 = h < 8 ? m0[h * 32 + 24 + (l >> 2) + ((l & 3) * 2 + 1) * DM] | 0x42000000u : 0;
#pragma unroll 1
            for (uint32_t i = 0; i < 12; i++) {
                if (i == 10) { sts32(sb + SM_WO + 6144 + l * 4, v1); sts32(sb + SM_WO + 6272 + l * 4, v3); }
                asm volatile("fence.proxy.async.shared::cta;" ::: "memory");
                __syncwarp();
                const uint32_t c = (0x21924u >> ((i - 3) * 2)) & 3;
                if (elect()) {
                    if (i < 3) bulk_s2g(xlo + XO_XG + (i * 128 + role) * 6144, xhi, sb + SM_WO, 6144);
                    else bulk_s2g(xlo + XO_R + rpage(j, i < 6 ? 0 : i < 9 ? 1 : -1) + c * 16384 + h * 128, xhi, sb + SM_WO + (i < 10 ? 0 : 6144 + c * 64), 128);
                }
            }
            asm volatile("cp.async.bulk.wait_group 0;" ::: "memory");
            if (elect()) asm volatile("{\n.reg .b64 a;\nmov.b64 a, {%0,%1};\nred.relaxed.gpu.global.inc.u32 [a], 127;\n}" ::"r"(xlo + XO_TK + 12), "r"(xhi) : "memory");
            if (l16 == 0) PG(16);
            g_wait(xlo + XO_TK + 12, xhi);
            if (l16 == 0) PG(17);
            barv<5, 288>();
            bsync<8, 320>();
            asm volatile("fence.acq_rel.gpu;" ::: "memory");
        } else {
            GSYNC(0);
            mbar_wait(bq + BAR_WE + 48, 0);
#pragma unroll 1
            for (int e = 0; e < 24; e++) sts128(sb + SM_TR + 4096 + e * 512 + l16, 0, 0, 0, 0);
            barv<3, 320>();
            bsync<8, 320>();
#pragma unroll 1
            for (int i = 0; i < 4; i++) xload(sb, i, j, 0, &tmx);
        }
#pragma unroll 1
        for (int s = 0; s < nseg; s++) helper_step(sb, w, h, j, l16, xlo, xhi, zero, s, &tmx, &tmb);
        piwait(sb, 0, nseg - 2);
        bsync<9, 384>();
        GSYNC(1);
        if (!GS && w == 11 && elect()) asm volatile("prefetch.tensormap [%0];" ::"l"(&tmy) : "memory");
        if (GH && w == 10) { g_arrive(xlo + XO_FL + h * 128 + 64, xhi, 5); PG(2); }
        if (w < 10) {
            uint32_t kb = 2, heads = 0;
            asm volatile("fence.proxy.async.shared::cta;" ::: "memory");
            if (GH) {
                if (w == 9 && h >= 30) { kb = 0; heads = 0xFFFF; }
                else delay_until(clk(), GD);
            } else if (w == 9) {
                g_arrive(xlo + XO_TK + 192, xhi, 128);
                PG(2);
                if (h >= 30) { g_wait(xlo + XO_TK + 192, xhi); kb = 0; }
                PG(3);
            } else delay_until(clk(), GD);
#pragma unroll 1
            for (; kb < 32; kb++) {
                if (kb >= 4) mbar_wait(bq + BAR_GE + (kb & 3) * 8, ((kb >> 2) & 1) ^ 1);
                if (GH && ((heads >> (kb >> 1)) & 1)) {
                    int it = 0;
                    do {
                        uint32_t v;
                        asm volatile("{\n.reg .b64 a;\nmov.b64 a, {%1,%2};\nld.acquire.gpu.global.u32 %0, [a+64];\n}"
                                     : "=r"(v) : "r"(xlo + XO_FL + (role & 1) * 2048 + (l16 & 255) * 8), "r"(xhi) : "memory");
                        heads = __ballot_sync(0xFFFFFFFFu, v != 0);
                        if (++it > SPIN_LIMIT) die(it);
                    } while ((heads >> (kb >> 1)) & 1);
                    asm volatile("fence.proxy.async.global;" ::: "memory");
                    if (kb == 0) PG(3);
                }
                g_load(sb, w - 8, role, kb, xlo, xhi, &tmb);
            }
        }
        if (role == 0 && w == 11 && elect()) tickets_done((uint32_t*)(((uint64_t)xhi << 32) | (xlo + XO_TK)));
    } else {
        asm volatile("setmaxnreg.inc.sync.aligned.u32 240;");
        uint32_t Wq[16][4], Wk[16][4], Wv[NA][4];
        uint32_t t16, KA, KB, KC, KD;
        {
            const uint32_t lane = l16 >> 4, g = lane >> 2, t = lane & 3;
            const uint32_t rw = (((lane >> 4) & 1) * 8 + (lane & 7)) * 128u;
            const uint32_t off = rw + ((((w & 3) * 2 + ((lane >> 3) & 1)) ^ (lane & 7)) << 4);
            const uint32_t offo = rw + ((((w & 1) * 4 + ((lane >> 3) & 1)) ^ (lane & 7)) << 4);
            const uint32_t r = 2 * (t & 1) + (g >> 2);
            const uint32_t mk0 = t < 2 ? 0 : (r == 0 ? 2 * g > w : j + r < 4), mk1 = t < 2 ? 0 : (r == 0 ? 2 * g + 1 > w : j + r < 4);
            t16 = __shfl_sync(0xFFFFFFFFu, w * 512 + l16, lane);
            KA = __shfl_sync(0xFFFFFFFFu, (w * 512 + t * 64 + g * 8) | ((w * 512 + (g & 1) * 256 + (g >> 1) * 64 + t * 16) << 16), lane);
            KB = __shfl_sync(0xFFFFFFFFu, ((w >> 2) * WV_BOX + off) | mk0 | (mk1 << 1) |
                                              ((w * 256 + (g >> 2) * 4096 + (g & 3) * 64 + t * 16) << 16), lane);
            KC = __shfl_sync(0xFFFFFFFFu, ((lane & 7) * 1280 + (lane >> 3) * 128 + ((w ^ (lane & 7)) << 4)) | (((t >> 1) * 16 + g * 2) << 16) | ((t * 64 + g * 8) << 24), lane);
            KD = __shfl_sync(0xFFFFFFFFu, ((w >> 1) * WO_BOX + offo) | (((lane & 7) * 208 + (lane >> 3) * 16) << 16), lane);
            if (threadIdx.x == 0) PG(8);
#define WTAKE(W, c, k0) { mbar_wait(bq + BAR_WF + (c) * 8, 0); \
                _Pragma("unroll") for (int ks = 0; ks < 4; ks++) ldsm4t(W[(k0) + ks], sb + SM_ST + ((c) & 3) * 16384 + (KB & 0xFFF0) + ks * 2048); \
                if ((c) < 8) { __syncwarp(); if (elect()) mbar_arrive(bq + BAR_WE + (c) * 8); } }
#pragma unroll
            for (int c = 0; c < 4; c++) WTAKE(Wq, c, c * 4);
            mbar_wait(bq, 0);
            if (threadIdx.x == 0) PG(9);
            xstart<0>(sb, w, xlo + h * 24576, xhi, j, t16, KA, Wq);
            if (threadIdx.x == 0) PG(10);
#pragma unroll
            for (int c = 0; c < 4; c++) WTAKE(Wk, c + 4, c * 4);
            if (threadIdx.x == 0) PG(11);
            xstart<1>(sb, w, xlo + h * 24576, xhi, j, t16, KA, Wk);
            if (threadIdx.x == 0) PG(12);
            WTAKE(Wv, 8, 0);
            WTAKE(Wv, 9, 4);
            mbar_wait(bq + BAR_WF + 80, 0);
            WTAKE(Wv, 11, 8);
            if (threadIdx.x == 0) PG(13);
            xstart<2>(sb, w, xlo + h * 24576, xhi, j, t16, KA, Wv);
            mbar_wait(bq + BAR_XA, 0);
            bsync<8, 320>();
        }
        const uint32_t ONES = 0x3F803F80u;
#define UNI(x) __reduce_max_sync(0xFFFFFFFFu, x)
        uint32_t swi = UNI((uint32_t)((uint64_t)smem >> 32));
        const uint32_t sbw = UNI(sb + w * 256), sbm = UNI(sb - w * 512), sbs = UNI(sb + w * 768), sbp = UNI(sb + w * 208);
#define OPQALL() { OPQ(t16); OPQ(KA); OPQ(KB); OPQ(KC); OPQ(KD); }
        OPQALL();
        if (SEED & 1) OPQ(Wq[0][0]);
        if (SEED & 2) OPQ(Wq[5][1]);
        if (SEED & 4) OPQ(Wk[0][0]);
        if (SEED & 8) OPQ(Wk[15][2]);
        if (SEED & 16) OPQ(Wv[0][0]);
        if (SEED & 32) OPQ(Wv[7][3]);
        const uint32_t cb0 = (h >> 1) * 32768 + (j & 1) * 16384 + (h & 1) * 8192;
        const uint32_t cb = UNI(xlo + cb0 + ((par(cb0) ^ (j >> 1) ^ CFAR) << 12)), cv = UNI(xlo + h * 8192 + JV(h, j) * 2048), h1 = UNI((h & 1) * 1024);
        const uint32_t uox = UNI(xlo + XO_OX + (h * 2 + (w >> 2)) * 262144 + j * 1024 + (w & 3) * 256 - w * 128);
        uint32_t rp = UNI(xlo + rpage(j, 0));
        float ox[4];
        float4 dn;
#define OXSTORE(s) asm volatile("{\n.reg .b64 a;\nmov.b64 a, {%0,%1};\nst.global.u32 [a], %2;\nst.global.u32 [a+128], %3;\n}" \
                                ::"r"(uox + (s) * 4096 + (t16 >> 2)), "r"(xhi), \
                                  "r"(pack2(ox[0] * dn.y, ox[1] * dn.w)), "r"(pack2(ox[2] * dn.y, ox[3] * dn.w)) : "memory")
#pragma unroll 1
        for (int s2 = 0;; s2 += 2, rp ^= 0x21000)
#pragma unroll
        for (int p = 0; p < 2; p++) {
            const int s = s2 + p;
            const uint32_t ctag = ((s2 >> 1) & 1) ^ 1;
            const uint32_t hb = cb ^ (p * 0x81000), rb = rp ^ (p * 0x11000);
            uint4 k0, k1, qq, c0, c1, c2, c3, pk;
            float va[4], vb[4];
            uint32_t qx0, qx1, ov0, ov1, wv[16 - NA][4];
            {
                float xa[16], xb[16];
                uint4 m0, n0;
                uint32_t e0, f0;
                uint32_t xp[8];
                wg_fence();
                XMMA(0, 6);
                SF();
                piwait(sb, p, s - 2);
                uint4 pi = xpeer<0>(sb, p ^ 1, t16);
                SF();
#define MR (VC ? 1 : 2)
#define MC (VC ? 2 : 1)
#define QPARK() { xpack<0>(xp, xa); xpark<0>(xp, pi, sb, sbw, p ^ 1, t16, KA); pi = xpeer<MR>(sb, p ^ 1, t16); SF(); }
                wg_fence();
                if (QP) {
                    XMMA(6, QP);
                    XMMA(QP, QP + 4);
                    wg_wait<1>();
                    SF();
                    QPARK();
                    wg_fence();
                    if (QP + 4 < RPOS) XMMA(QP + 4, RPOS);
                } else XMMA(6, RPOS);
                if (RPOS < 32) XMMA(RPOS, RPOS + 4 < 32 ? RPOS + 4 : 32);
                uint32_t a = (p ? rp : rp ^ 0x30000) + t16, e = (p ? rp : rp ^ 0x30000) + (t16 >> 2), ah = xhi, eh = xhi;
                OPQ(a); OPQ(e); OPQ(ah); OPQ(eh);
                SF();
                wg_wait<(RPOS < 32)>();
                SF();
                PT(11);
                RLOAD();
                SF();
                if (!QP) QPARK();
                if (RPOS + 4 < 32) {
                    wg_fence();
                    XMMA(RPOS + 4, 32);
                    SF();
                }
                wg_wait<0>();
                xpack<MR>(xp, xb);
                xpark<MR>(xp, pi, sb, sbw, p ^ 1, t16, KA);
                SF();
                PT(12);
                {
                    int it = 0;
                    while (ruse(sb + SM_MEMT + t16, m0, n0, e0, f0)) {
                        RLOAD();
                        if (++it > SPIN_LIMIT) die(it);
                    }
                    PC(22, it + 1);
                }
                PT(13);
                OPQ(KA); OPQ(t16);
                uint32_t acw = hb + (KA & 0xFFFF), ahi = xhi, tg = ctag;
                OPQ(acw); OPQ(ahi); OPQ(tg);
                SF();
                bsync<1, 384>();
                PT(0);
                uint32_t b[8][4];
#pragma unroll
                for (int i = 0; i < 8; i++) {
                    const int pp = i < 2 ? i : i ^ 1;
                    ldsm4t(b[pp], sbm + SM_MEMT + t16 + pp * 512);
                    if (i < 7) MF();
                }
                if (ASF) SF();
                float q[4], k[4];
                const uint32_t aWv = sb + SM_WV + (KB & 0xFFF0);
#define WVLD(n0, n1) _Pragma("unroll") for (int n = (n0); n < (n1) && n < 16 - NA; n++) ldsm4t(wv[n], aWv + n * 2048)
#pragma unroll
                for (int ks = 0; ks < 16; ks++) {
                    const uint32_t b0 = b[ks >> 1][(ks & 1) * 2], b1 = b[ks >> 1][(ks & 1) * 2 + 1];
                    if (ks == 0) {
                        mma16z(q, Wq[0][0], Wq[0][1], Wq[0][2], Wq[0][3], b0, b1);
                        mma16z(k, Wk[0][0], Wk[0][1], Wk[0][2], Wk[0][3], b0, b1);
                    } else {
                        mma16(q, Wq[ks][0], Wq[ks][1], Wq[ks][2], Wq[ks][3], b0, b1);
                        mma16(k, Wk[ks][0], Wk[ks][1], Wk[ks][2], Wk[ks][3], b0, b1);
                    }
                    if (ks == 10 && VPF) { SF(); WVLD(0, VPF); }
                }
                const uint32_t oq0 = settag(pack2(q[0], q[2]), tg), oq1 = settag(pack2(q[1], q[3]), tg);
                const uint32_t ok0 = pack2(k[0], k[2]), ok1 = pack2(k[1], k[3]);
                stg2<XO_CQK>(acw, ahi, oq0, ok0);
                stg2<XO_CQK + 256>(acw, ahi, oq1, ok1);
                SF();
                PT(1);
#define CLOADG() { c2 = ldg4<XO_CQK>((hb ^ 0x1000) + (KA >> 16), xhi); c3 = ldg4<XO_CQK>((hb ^ 0x5000) + (KA >> 16), xhi); }
#define CLOAD0() c0 = lds128(sb + SM_TR + (KA >> 16))
#define CLOAD1() c1 = lds128(sb + SM_TR + 4096 + p * 4096 + (KA >> 16))
#define CLOADS() { CLOAD0(); CLOAD1(); }
#define CSIDE(n) { if (CGP == (n)) CLOADG(); if (C0P == (n)) CLOAD0(); if (C1P == (n)) CLOAD1(); if (PIP == (n)) pk = xpeer<MC>(sb, p ^ 1, t16); \
                   if (QSP == (n)) { qx0 = (t16 & 64) ? qq.y : qq.x; qx1 = (t16 & 64) ? qq.w : qq.z; } }
#pragma unroll
                for (int rd = 0; rd < 8; rd++) {
                    const int pp = (VORD >> (28 - 4 * rd)) & 7;
                    const uint32_t* a = 2 * pp < NA ? Wv[2 * pp < NA ? 2 * pp : 0] : wv[2 * pp < NA ? 0 : 2 * pp - NA];
                    const uint32_t* c = 2 * pp < NA ? Wv[2 * pp < NA ? 2 * pp + 1 : 0] : wv[2 * pp < NA ? 0 : 2 * pp + 1 - NA];
                    if (rd == 0) {
                        mma16z(va, a[0], a[1], a[2], a[3], b[pp][0], b[pp][1]);
                        mma16z(vb, c[0], c[1], c[2], c[3], b[pp][2], b[pp][3]);
                        if (VSB & 256) SF();
                        OPQ(swi);
                        asm volatile("{\n.reg .b64 a;\nmov.b64 a, {%0,%1};\nst.v2.u32 [a], {%2,%3};\nst.v2.u32 [a+256], {%4,%5};\n}"
                                     ::"r"((KA & 0xFFF) + (sb ^ 0x1000000) + SM_TR + 4096 + p * 4096), "r"(swi), "r"(oq0), "r"(ok0), "r"(oq1), "r"(ok1) : "memory");
                        sts64(sb + SM_TR + (KA & 0xFFF), oq0, ok0);
                        sts64(sb + SM_TR + (KA & 0xFFF) + 256, oq1, ok1);
                    } else {
                        mma16(va, a[0], a[1], a[2], a[3], b[pp][0], b[pp][1]);
                        mma16(vb, c[0], c[1], c[2], c[3], b[pp][2], b[pp][3]);
                    }
                    if (rd == KEP) { KEEP(t16, oq0, oq1, ok0, ok1); if (KE2) KEEP(t16, acw, ahi, acw, ahi); }
                    if ((VSB >> rd) & 1) SF();
                    if (rd == W2P) WVLD(2, 3);
                    if (rd == W3P) WVLD(3, 4);
                    if (rd == K0P) k0 = lds128(sb + SM_KV + 2048 + (KB >> 16));
                    if (rd == K0P + 1) k1 = lds128(sb + SM_KV + 10240 + (KB >> 16));
                    if (rd == QQP) qq = lds128(sbw + SM_KV + ((KA >> 16) & 0xFF));
                    CSIDE(rd);
                    if ((VSF >> rd) & 1) SF(); else if ((VMF >> rd) & 1) MF();
                }
#define VTAIL() { ov0 = pack2(va[0] + vb[0], va[1] + vb[1]); ov1 = pack2(va[2] + vb[2], va[3] + vb[3]); \
                  stg2<XO_CV>(cv + p * 262144 + (t16 >> 1), xhi, settag(ov0, ctag), ov1); \
                  if (VD) asm volatile("{\n.reg .b64 a;\nmov.b64 a, {%0,%1};\nst.v2.u32 [a], {%2,%3};\n}" \
                                     ::"r"((t16 >> 1) + (sb ^ 0x1000000) + SM_VP + p * 2048), "r"(swi), "r"(settag(ov0, ctag)), "r"(ov1) : "memory"); \
                  barv<8, 384>(); OPQ(t16); SF(); }
                if (!VTP) VTAIL();
            }
            PT(2);
            PDUMP();
            {
                const uint32_t a0 = sb + SM_KV;
                float xa[16], xb[16];
                uint32_t xp[8];
                if (CGP == 12 || QSP == 12) { CSIDE(12); SF(); }
                wg_fence();
                XMMA(32, 32 + CPOS);
                if (CGP == 13) { SF(); CSIDE(13); SF(); wg_fence(); }
                if (VR == 1) { XMMA(32 + CPOS, 36); XMMA(36, 36 + CW2); wg_wait<2>(); }
                else if (CW) { XMMA(32 + CPOS, 36 + CPOS); wg_wait<1>(); }
                SF();
                CSIDE(8);
                SF();
                if (VR == 1) { wg_wait<1>(); SF(); }
                if (VTP) VTAIL();
                CSIDE(9);
                SF();
                wg_fence();
                XMMA(VR == 1 ? 36 + CW2 : 32 + CPOS + (CW ? 4 : 0), 48);
                SF();
                uint2 u1, u2, u3;
#define ULOADG() { u2 = ldg2<XO_CV>((cv ^ 4096) + p * 262144 + (t16 >> 1), xhi); u3 = ldg2<XO_CV>((cv ^ 6144) + p * 262144 + (t16 >> 1), xhi); }
#define ULOADS() u1 = lds64(sb + SM_VP + p * 2048 + (t16 >> 1))
#define UCHECK() { int it = 0; \
                   while (__builtin_expect(any_bad(tagx1(tagx2(u2.x, u3.x, ctag), u1.x, ctag)), 0)) { OPQ(t16); ULOADG(); ULOADS(); if (++it > SPIN_LIMIT) die(it); } \
                   PC(26, it); }
                CSIDE(10);
                if (B3 == 8 && VLP == 2) ULOADG();
                SF();
                const uint32_t ka[4] = {k0.x, k0.y, k0.z, k0.w}, kb[4] = {k1.x, k1.y, k1.z, k1.w};
                const uint32_t aSp = sb + SM_SP + (KC & 0xFFFF);
                PT(3);
#define BAR3() asm volatile("{\n.reg .pred p;\nsetp.eq.u32 p, %0, 0;\n@p bar.arrive 3, %1;\n}" ::"r"((uint32_t)bad), "n"(B3 == 6 ? 288 : 384) : "memory")
#define SCORES(FIRST) { \
                    const uint32_t qA = hadd2(hadd2(c0.x, c1.x), hadd2(c2.x, c3.x)), qB = hadd2(hadd2(c0.z, c1.z), hadd2(c2.z, c3.z)); \
                    const uint32_t kA = hadd2(hadd2(c0.y, c1.y), hadd2(c2.y, c3.y)), kB = hadd2(hadd2(c0.w, c1.w), hadd2(c2.w, c3.w)); \
                    bad = any_bad(or3(tagx2(c1.x, c1.z, ctag), tagx2(c2.x, c2.z, ctag), tagx2(c3.x, c3.z, ctag))); \
                    float sa[4], sb_[4], sc[4], sd[4], se[4]; \
                    if (FIRST) { SF(); if (B3 == 8 && VLP == 3) ULOADG(); CSIDE(11); wg_wait<0>(); } \
                    mma16z(sa, ka[0], ka[1], ka[2], ka[3], qA, qB); \
                    mma16z(sb_, kb[0], kb[1], kb[2], kb[3], qA, qB); \
                    mma16z(sc, qA, qx0, qB, qx1, kA, kB); \
                    if (FIRST) { \
                        xpack<MC>(xp, xa); \
                        if (KPOS == 0) { xadd(xp, pk); xstore<MC>(xp, sb, sbw, p ^ 1, t16, KA); if (B3 >= 5) BAR3(); else if (!B3 || B3 >= 3) barv<3, 384>(); } \
                        mma16z(sd, ka[0], ka[1], ka[2], ka[3], qx0, qx1); \
                        mma16z(se, kb[0], kb[1], kb[2], kb[3], qx0, qx1); \
                    } \
                    stsm4t(aSp, pack2(sa[0], sa[1]), pack2(sa[2], sa[3]), pack2(sb_[0], sb_[1]), pack2(sb_[2], sb_[3])); \
                    stsm2(aSp + 1024, pack2(sc[0], sc[1]), pack2(sc[2], sc[3])); \
                    if (FIRST) { \
                        stsm4t(aSp + 512, pack2(sd[0], sd[1]), pack2(sd[2], sd[3]), pack2(se[0], se[1]), pack2(se[2], se[3])); \
                        if (KPOS == 0) { KEEP(KD, xp[0], xp[1], xp[2], xp[3]); KEEP(KD, xp[4], xp[5], xp[6], xp[7]); } \
                    } }
                int it = 0;
                bool bad;
                SCORES(true);
                while (__builtin_expect(bad, 0)) {
                    OPQ(KA);
                    CLOADG();
                    CLOADS();
                    SCORES(false);
                    if (B3 >= 5) BAR3();
                    if (++it > SPIN_LIMIT) die(it);
                }
                PC(25, it);
                PT(4);
                if (B3 == 8 && VLP == 0) ULOADG();
                if (B3 == 1) barv<3, 384>();
                bsync<4, B3 == 2 ? 384 : 256>();
                uint32_t wo[16][4];
                const uint32_t aWo = sb + SM_WO + (KD & 0xFFFF), aWo1 = sb + SM_WO + ((KD & 0xFFFF) ^ 32);
#define WOLD(n0, n1) _Pragma("unroll") for (int n = (n0); n < (n1) && n < 16; n++) ldsm4t(wo[n], ((n & 1) ? aWo1 : aWo) + (n >> 1) * 2048)
                const bool hi = (t16 & 32) != 0;
                const uint32_t t8 = t16 >> 1;
                uint2 v0, v1, v2, v3;
                uint32_t es;
                {
                    uint32_t am[4], ax[4], a4[2];
                    const uint32_t aSr = sbs + SM_SP + t16;
                    ldsm4t(am, aSr);
                    ldsm4t(ax, aSr + 512);
                    ldsm2t(a4, aSr + 1024);
                    MF();
                    if (B3 == 8 && VLP == 1) ULOADG();
                    if (KPOS == 1) pk = xpeer<MC>(sb, p ^ 1, t16);
                    const uint32_t se = (t16 & 128) ? 0u : ONES, so = se ^ ONES;
                    float hm[4], hx[4], h4[4];
                    mma16z(hm, am[0], am[1], am[2], am[3], se, so);
                    mma16z(hx, ax[0], ax[1], ax[2], ax[3], se, so);
                    mma8z(h4, a4[0], a4[1], ONES);
                    SF();
                    if (KPOS == 1) { xpark<MC>(xp, pk, sb, sbw, p ^ 1, t16, KA); barv<3, 384>(); }
                    v0 = lds64(a0 + 4096 + t8); v1 = lds64(a0 + 8192 + t8); v2 = lds64(a0 + 12288 + t8); v3 = lds64(a0 + 16384 + t8);
                    if (B3 == 8) ULOADS();
                    WOLD(0, PF2);
                    float s0 = hi ? hx[0] : hm[0], s1 = hi ? hx[2] : hm[2];
                    const float s2 = hi ? h4[2] : h4[0];
                    s0 = (KB & 1) ? -1.0e9f * 11.313708499f : s0;
                    s1 = (KB & 2) ? -1.0e9f * 11.313708499f : s1;
                    int mi = __float_as_int(fmaxf(fmaxf(s0, s2), s1));
                    mi ^= (mi >> 31) & 0x7FFFFFFF;
                    const int mm = __reduce_max_sync(0xFFFFFFFFu, hi ? (int)0x80000000 : mi), mx = __reduce_max_sync(0xFFFFFFFFu, hi ? mi : (int)0x80000000);
                    SF();
                    WOLD(PF2, PF3);
                    SF();
                    mi = hi ? mx : mm;
                    mi ^= (mi >> 31) & 0x7FFFFFFF;
                    const float c2_ = 0.08838834764831845f * 1.4426950408889634f;
                    const float mc = __int_as_float(mi) * c2_;
                    const float e0 = ex2(fmaf(s0, c2_, -mc)), e1 = ex2(fmaf(s1, c2_, -mc)), e2 = ex2(fmaf(s2, c2_, -mc));
                    sts32(sbp + SM_P + (KC >> 25), pack2(e0, e1));
                    sts16(sbp + SM_P + 128 + ((KC >> 16) & 0xFF), pack2(e2, e2));
                    es = __float_as_uint(fmaf(e2, 0.5f, e0 + e1) + 64.f);
                }
                const uint32_t sm = __reduce_add_sync(0xFFFFFFFFu, hi ? 0u : es), sx = __reduce_add_sync(0xFFFFFFFFu, hi ? es : 0u);
                const uint32_t aPr = sb + SM_P + (KD >> 16);
                if (B3 == 8 && VCP == 0) UCHECK();
                PT(5);
                bsync<5, VB ? 256 : B3 == 6 ? 352 : 384>();
                uint32_t pm[4], px[4], p4[2];
                ldsm4(pm, aPr);
                MF();
                uint2 vs;
                #define VGET(n) if (VB == (n)) { if (VB) bsync<11, 384>(); vs = lds64(sb + SM_VS + t8); MF(); }
                if (B3 != 8) { VGET(0); VGET(1); }
                ldsm2(p4, aPr + 128);
                MF();
                VGET(2);
                ldsm4(px, aPr + 64);
                MF();
                VGET(3);
                sts32f(sb + SM_DN + w * 8 + ((t16 >> 3) & 4), rcp(__uint_as_float((hi ? sx : sm) - 15u * 0x42800000u) - 64.f));
                MF();
                if (B3 == 8 && VCP == 2) UCHECK();
                WOLD(PF3, NPF);
                if (B3 == 8 && VCP == 1) UCHECK();
                if (B3 == 8) { ov0 = hadd2(ov0, u1.x); ov1 = hadd2(ov1, u1.y); vs.x = hadd2(u2.x, u3.x); vs.y = hadd2(u2.y, u3.y); }
                const uint32_t vm0 = hadd2(ov0, vs.x), vm1 = hadd2(ov1, vs.y);
                float oa[4], ob[4];
                mma16z(oa, v0.x, v0.y, v1.x, v1.y, pm[0], pm[1]);
                mma16z(ob, v2.x, v2.y, v3.x, v3.y, pm[2], pm[3]);
                mma8(oa, vm0, vm1, p4[0]);
                stsm2(sbw + SM_OT + (t16 & 511), pack2(oa[0] + ob[0], oa[1] + ob[1]), pack2(oa[2] + ob[2], oa[3] + ob[3]));
                PT(6);
                SF();
                bsync<6, 256>();
                mma16z(ox, v0.x, v0.y, v1.x, v1.y, px[0], px[1]);
                uint32_t b[4][4];
#define OTLD(pp) ldsm4t(b[pp], sbm + SM_OT + t16 + (pp) * 512)
                OTLD(0);
                MF();
                OTLD(1);
                barv<7, 384>();
                mma16(ox, v2.x, v2.y, v3.x, v3.y, px[2], px[3]);
                mma8(ox, vm0, vm1, p4[1]);
                if (p == 1 && s + 1 == nseg) goto done;
                SF();
                uint32_t ar, ae, ahi = xhi;
                float r[2][4];
#pragma unroll
                for (int ks = 0; ks < 8; ks++) {
                    if (ks == 0) WOLD(NPF, NPF + WPF);
                    if (ks == OPOS) { OTLD(2); MF(); }
                    if (ks == OPOS + 2) { OTLD(3); MF(); }
                    if (ks > 0) WOLD(NPF + WPF + 2 * (ks - 1), NPF + WPF + 2 * ks);
                    if (ks == 5) {
                        OPQ(t16);
                        ar = rb + h1 * 16 + t16; ae = rb + h1 + (t16 >> 2);
                        OPQ(ar); OPQ(ahi); OPQ(ae);
                        dn = lds128f(sb + SM_DN + (t16 & 48));
                    }
#pragma unroll
                    for (int mt = 0; mt < 2; mt++) {
                        const int i = ks * 2 + mt;
                        const uint32_t* a = wo[i];
                        if (i < 2) mma16z(r[mt], a[0], a[1], a[2], a[3], b[ks >> 1][2 * (ks & 1)], b[ks >> 1][2 * (ks & 1) + 1]);
                        else mma16(r[mt], a[0], a[1], a[2], a[3], b[ks >> 1][2 * (ks & 1)], b[ks >> 1][2 * (ks & 1) + 1]);
                    }
                    if (NPF + WPF + 2 * ks < 16 || ks < 5) SF();
                }
                const float r0 = dn.x, r1 = dn.z;
                asm volatile("{\n.reg .b64 a;\nmov.b64 a, {%0,%2};\nred.relaxed.gpu.global.add.noftz.v4.bf16x2 [a], {%3,%4,%5,%6};\n"
                             "mov.b64 a, {%1,%2};\nred.relaxed.gpu.global.add.noftz.bf16x2 [a+32768], %7;\n}"
                             ::"r"(ar), "r"(ae), "r"(ahi), "r"(pack2(r[0][0] * r0, r[0][1] * r1)), "r"(pack2(r[0][2] * r0, r[0][3] * r1)),
                               "r"(pack2(r[1][0] * r0, r[1][1] * r1)), "r"(pack2(r[1][2] * r0, 1.f)), "r"(pack2(r[1][3] * r1, 1.f)) : "memory");
                barv<10, 384>();
            }
            SF();
            PT(10);
            OXSTORE(s);
            OPQALL();
        }
    done:
        dn = lds128f(sb + SM_DN + (t16 & 48));
        OXSTORE(nseg - 1);
        barv<9, 384>();
        g_main(sb, w, role, &tmy, out);
        if (threadIdx.x == 0) PG(0);
    }
}

template <int SC> DEVI void wg_rs128t(float (&d)[64], const uint32_t (&a)[4], uint64_t db) {
    if (SC) asm volatile("wgmma.mma_async.sync.aligned.m64n128k16.f32.bf16.bf16 "
        "{%0,%1,%2,%3,%4,%5,%6,%7,%8,%9,%10,%11,%12,%13,%14,%15,%16,%17,%18,%19,%20,%21,%22,%23,%24,%25,%26,%27,%28,%29,%30,%31,%32,%33,%34,%35,%36,%37,%38,%39,%40,%41,%42,%43,%44,%45,%46,%47,%48,%49,%50,%51,%52,%53,%54,%55,%56,%57,%58,%59,%60,%61,%62,%63}, "
        "{%64,%65,%66,%67}, %68, 1, 1, 1, 1;"
        : D4(+, 0), D4(+, 4), D4(+, 8), D4(+, 12), D4(+, 16), D4(+, 20), D4(+, 24), D4(+, 28), D4(+, 32), D4(+, 36), D4(+, 40), D4(+, 44), D4(+, 48), D4(+, 52), D4(+, 56), D4(+, 60) : "r"(a[0]), "r"(a[1]), "r"(a[2]), "r"(a[3]), "l"(db));
    else asm volatile("wgmma.mma_async.sync.aligned.m64n128k16.f32.bf16.bf16 "
        "{%0,%1,%2,%3,%4,%5,%6,%7,%8,%9,%10,%11,%12,%13,%14,%15,%16,%17,%18,%19,%20,%21,%22,%23,%24,%25,%26,%27,%28,%29,%30,%31,%32,%33,%34,%35,%36,%37,%38,%39,%40,%41,%42,%43,%44,%45,%46,%47,%48,%49,%50,%51,%52,%53,%54,%55,%56,%57,%58,%59,%60,%61,%62,%63}, "
        "{%64,%65,%66,%67}, %68, 0, 1, 1, 1;"
        : D4(=, 0), D4(=, 4), D4(=, 8), D4(=, 12), D4(=, 16), D4(=, 20), D4(=, 24), D4(=, 28), D4(=, 32), D4(=, 36), D4(=, 40), D4(=, 44), D4(=, 48), D4(=, 52), D4(=, 56), D4(=, 60) : "r"(a[0]), "r"(a[1]), "r"(a[2]), "r"(a[3]), "l"(db));
}
template <int SC> DEVI void wg_rs64t(float (&d)[32], const uint32_t (&a)[4], uint64_t db) {
    if (SC) asm volatile("wgmma.mma_async.sync.aligned.m64n64k16.f32.bf16.bf16 "
        "{%0,%1,%2,%3,%4,%5,%6,%7,%8,%9,%10,%11,%12,%13,%14,%15,%16,%17,%18,%19,%20,%21,%22,%23,%24,%25,%26,%27,%28,%29,%30,%31}, "
        "{%32,%33,%34,%35}, %36, 1, 1, 1, 1;"
        : D4(+, 0), D4(+, 4), D4(+, 8), D4(+, 12), D4(+, 16), D4(+, 20), D4(+, 24), D4(+, 28) : "r"(a[0]), "r"(a[1]), "r"(a[2]), "r"(a[3]), "l"(db));
    else asm volatile("wgmma.mma_async.sync.aligned.m64n64k16.f32.bf16.bf16 "
        "{%0,%1,%2,%3,%4,%5,%6,%7,%8,%9,%10,%11,%12,%13,%14,%15,%16,%17,%18,%19,%20,%21,%22,%23,%24,%25,%26,%27,%28,%29,%30,%31}, "
        "{%32,%33,%34,%35}, %36, 0, 1, 1, 1;"
        : D4(=, 0), D4(=, 4), D4(=, 8), D4(=, 12), D4(=, 16), D4(=, 20), D4(=, 24), D4(=, 28) : "r"(a[0]), "r"(a[1]), "r"(a[2]), "r"(a[3]), "l"(db));
}
template <int SC> DEVI void wg_rs40(float (&d)[20], const uint32_t (&a)[4], uint64_t db) {
    if (SC) asm volatile("wgmma.mma_async.sync.aligned.m64n40k16.f32.bf16.bf16 "
        "{%0,%1,%2,%3,%4,%5,%6,%7,%8,%9,%10,%11,%12,%13,%14,%15,%16,%17,%18,%19}, "
        "{%20,%21,%22,%23}, %24, 1, 1, 1, 0;"
        : D4(+, 0), D4(+, 4), D4(+, 8), D4(+, 12), D4(+, 16) : "r"(a[0]), "r"(a[1]), "r"(a[2]), "r"(a[3]), "l"(db));
    else asm volatile("wgmma.mma_async.sync.aligned.m64n40k16.f32.bf16.bf16 "
        "{%0,%1,%2,%3,%4,%5,%6,%7,%8,%9,%10,%11,%12,%13,%14,%15,%16,%17,%18,%19}, "
        "{%20,%21,%22,%23}, %24, 0, 1, 1, 0;"
        : D4(=, 0), D4(=, 4), D4(=, 8), D4(=, 12), D4(=, 16) : "r"(a[0]), "r"(a[1]), "r"(a[2]), "r"(a[3]), "l"(db));
}
template <int SC> DEVI void wg_rs8(float (&d)[4], const uint32_t (&a)[4], uint64_t db) {
    if (SC) asm volatile("wgmma.mma_async.sync.aligned.m64n8k16.f32.bf16.bf16 "
        "{%0,%1,%2,%3}, "
        "{%4,%5,%6,%7}, %8, 1, 1, 1, 0;"
        : D4(+, 0) : "r"(a[0]), "r"(a[1]), "r"(a[2]), "r"(a[3]), "l"(db));
    else asm volatile("wgmma.mma_async.sync.aligned.m64n8k16.f32.bf16.bf16 "
        "{%0,%1,%2,%3}, "
        "{%4,%5,%6,%7}, %8, 0, 1, 1, 0;"
        : D4(=, 0) : "r"(a[0]), "r"(a[1]), "r"(a[2]), "r"(a[3]), "l"(db));
}
template <int SC> DEVI void wg_ss64a(float (&d)[32], uint64_t da, uint64_t db) {
    if (SC) asm volatile("wgmma.mma_async.sync.aligned.m64n64k16.f32.bf16.bf16 "
        "{%0,%1,%2,%3,%4,%5,%6,%7,%8,%9,%10,%11,%12,%13,%14,%15,%16,%17,%18,%19,%20,%21,%22,%23,%24,%25,%26,%27,%28,%29,%30,%31}, "
        "%32, %33, 1, 1, 1, 1, 0;"
        : D4(+, 0), D4(+, 4), D4(+, 8), D4(+, 12), D4(+, 16), D4(+, 20), D4(+, 24), D4(+, 28) : "l"(da), "l"(db));
    else asm volatile("wgmma.mma_async.sync.aligned.m64n64k16.f32.bf16.bf16 "
        "{%0,%1,%2,%3,%4,%5,%6,%7,%8,%9,%10,%11,%12,%13,%14,%15,%16,%17,%18,%19,%20,%21,%22,%23,%24,%25,%26,%27,%28,%29,%30,%31}, "
        "%32, %33, 0, 1, 1, 1, 0;"
        : D4(=, 0), D4(=, 4), D4(=, 8), D4(=, 12), D4(=, 16), D4(=, 20), D4(=, 24), D4(=, 28) : "l"(da), "l"(db));
}

#define G_ROWS 514
__device__ uint4 g_G[64 * G_ROWS * 8];
__device__ uint4 g_GN[64 * 8];
__device__ uint4 g_WN[1152];
#define FS_F2 196608
#define FS_TB (FS_F2 + 8192)
#define FS_NQ (FS_TB + 16384)
#define FS_BAR (FS_NQ + 128)
#define FS_NY (FS_NQ + 1024 + 128)
#define FS_TOTAL (FS_NQ + 3072)
#define F_THREADS 512

DEVI uint32_t cis(int j) {
    const float a = fmaf(__uint_as_float((((j + 1024) << 12) & 0x7FF000) | 0x3F800000), 6.283185307179586f, -9.42477796076938f);
    return pack2(__cosf(a), __sinf(a));
}
DEVI uint32_t cos2(int j0, int j1) {
    const float f = 6.283185307179586f / 2048.f;
    return pack2(__cosf((float)(((j0 + 1024) & 2047) - 1024) * f), __cosf((float)(((j1 + 1024) & 2047) - 1024) * f));
}
DEVI void twid(int j, float& c, float& s) {
    const float a = (float)(((j + 512) & 1023) - 512) * (6.283185307179586f / 1024.f);
    c = __cosf(a) * (1.f / 1024.f);
    s = __sinf(a) * (1.f / 1024.f);
}
template <bool B> struct Bool { static constexpr bool v = B; };
DEVI uint32_t opq(uint32_t& x, uint32_t zero) { OPQ(x); return x; }
DEVI uint32_t tidx() { uint32_t r; asm volatile("mov.u32 %0, %%tid.x;" : "=r"(r)); return r; }
DEVI void tma4d(uint32_t dst, const CUtensorMap* tm, uint32_t bar, int c0, int c1, int c2, int c3) {
    asm volatile("cp.async.bulk.tensor.4d.shared::cluster.global.mbarrier::complete_tx::bytes [%0], [%1, {%3, %4, %5, %6}], [%2];"
                 ::"r"(dst), "l"(tm), "r"(bar), "r"(c0), "r"(c1), "r"(c2), "r"(c3) : "memory");
}
DEVI void tma3s(const CUtensorMap* tm, uint32_t src, int c0, int c1, int c2) {
    asm volatile("cp.async.bulk.tensor.3d.global.shared::cta.bulk_group [%0, {%2, %3, %4}], [%1];" ::"l"(tm), "r"(src), "r"(c0), "r"(c1), "r"(c2) : "memory");
}
DEVI void tma4s(const CUtensorMap* tm, uint32_t src, int c0, int c1, int c2, int c3) {
    asm volatile("cp.async.bulk.tensor.4d.global.shared::cta.bulk_group [%0, {%2, %3, %4, %5}], [%1];"
                 ::"l"(tm), "r"(src), "r"(c0), "r"(c1), "r"(c2), "r"(c3) : "memory");
}
DEVI void bulk_commit() { asm volatile("cp.async.bulk.commit_group;" ::: "memory"); }
DEVI void fence_async() { asm volatile("fence.proxy.async;" ::: "memory"); }
DEVI void fence_smem() { asm volatile("fence.proxy.async.shared::cta;" ::: "memory"); }
DEVI void wgbar(uint32_t q) { asm volatile("bar.sync %0, 128;" ::"r"(q + 2) : "memory"); }
DEVI void grid_arrive(uint32_t* c, uint32_t n) { asm volatile("fence.proxy.async;\nred.release.gpu.global.inc.u32 [%0], %1;" ::"l"(c), "r"(n - 1) : "memory"); }
DEVI void grid_wait(uint32_t* c) {
    uint32_t v;
    int it = 0;
    do {
        asm volatile("ld.acquire.gpu.global.u32 %0, [%1];" : "=r"(v) : "l"(c) : "memory");
        if (++it > (1 << 22)) die(it);
    } while (v);
    fence_async();
}

template <bool INV, class S1, class S2>
DEVI void fft_rows(uint32_t grp, uint32_t q, const uint32_t (&F)[2][4], const float (&tc)[8], const float (&ts)[8], uint32_t so, float fx, uint32_t nq,
                   S1 sh1, S2 sh2) {
    float d[64];
    const uint64_t db = INV ? mkdesc(grp, 1024, 2048) : (mkdesc(grp, 2048, 512) ^ ((uint64_t)3 << 62));
    wg_fence();
    wg_rs128t<0>(d, F[0], db);
    wg_rs128t<1>(d, F[1], db + (INV ? 256 : 64));
    wg_commit();
    SF();
    sh1();
    float4 ny;
    if (INV) ny = lds128f(nq);
    wg_wait<0>();
    if (INV) { d[0] = fmaf(fx, ny.x, d[0]); d[16] = fmaf(fx, ny.y, d[16]); d[32] = fmaf(fx, ny.z, d[32]); d[48] = fmaf(fx, ny.w, d[48]); }
    uint32_t a[2][4][4];
    float e[2][INV ? 16 : 20];
    const uint64_t df = mkdesc(SB0 + FS_F2, 16, 1024);
#pragma unroll
    for (int s = 0; s < 2; s++) {
#pragma unroll
        for (int i = 0; i < 4; i++)
#pragma unroll
            for (int h = 0; h < 2; h++) {
                const float* x = d + (2 * s + h) * 16 + i * 4;
                a[s][i][h] = pack2(fmaf(x[2], ts[2 * i], x[0] * tc[2 * i]), fmaf(x[3], ts[2 * i + 1], x[1] * tc[2 * i + 1]));
                a[s][i][h + 2] = pack2(fmaf(-x[0], ts[2 * i], x[2] * tc[2 * i]), fmaf(-x[1], ts[2 * i + 1], x[3] * tc[2 * i + 1]));
            }
        wg_fence();
#pragma unroll
        for (int i = 0; i < 4; i++) {
            if constexpr (INV) { if (i == 0) wg_rs32<0>(e[s], a[s][i], df); else wg_rs32<1>(e[s], a[s][i], df + i * 2); }
            else { if (i == 0) wg_rs40<0>(e[s], a[s][i], df); else wg_rs40<1>(e[s], a[s][i], df + i * 2); }
        }
        wg_commit();
    }
    SF();
    sh2();
#pragma unroll
    for (int s = 0; s < 2; s++) {
        if (s == 0) wg_wait<1>(); else wg_wait<0>();
        float* x = e[s];
        if constexpr (!INV) {
            x[0] *= fx; x[1] *= fx; x[2] *= fx; x[3] *= fx;
            if (fx != 1.f) sts64(nq + s * 8, pack2(x[16], 0.f), pack2(x[18], 0.f));
        }
        const uint32_t o = grp + (INV ? so + s * 4096 : so ^ (s * 576));
#pragma unroll
        for (int b = 0; b < 2; b++)
            stsm4t(o + b * (INV ? 1024 : 4096), pack2(x[8 * b], x[8 * b + 1]), pack2(x[8 * b + 2], x[8 * b + 3]), pack2(x[8 * b + 4], x[8 * b + 5]),
                   pack2(x[8 * b + 6], x[8 * b + 7]));
    }
}

template <bool INV>
DEVI void fft_gen(uint32_t a, uint32_t n2) {
    const uint32_t tid = tidx(), x = ((tid >> 4) & 24) + (tid & 3), o = (tid & 4) * 128;
    if (INV) {
        const uint32_t r = (tid & 64) * 16 + (tid & 16) * 32 + (tid & 40) * 8 + n2;
        sts128(a + tid * 16, cis(o - r * x), cis(o - (r + 128) * x), cis(o - r * (x + 4)), cis(o - (r + 128) * (x + 4)));
    } else {
        const uint32_t r = 64 * x + n2, k = ((tid >> 2) & 24) + ((tid >> 3) & 3);
        sts128(a + tid * 16, cis(r * k + o), cis(r * (k + 4) + o), cis((r + 256) * k + o), cis((r + 256) * (k + 4) + o));
    }
}
template <bool INV, class S1>
DEVI void fft_cross(uint32_t buf, uint32_t q, uint32_t fa, uint32_t so, uint32_t nq, float (&n)[4], S1 sh1) {
    uint32_t F[4][4];
#pragma unroll
    for (int s = 0; s < 4; s++) { const uint4 v = lds128(fa + s * 2048); F[s][0] = v.x; F[s][1] = v.y; F[s][2] = v.z; F[s][3] = v.w; }
    float d[64];
    const uint64_t db = mkdesc(buf + q * 2048, 1024, 8192), dn = mkdesc(nq, 16, 1024);
    wg_fence();
#pragma unroll
    for (int s = 0; s < 4; s++) { if (s == 0) wg_rs128t<0>(d, F[s], db); else wg_rs128t<1>(d, F[s], db + s * 1024); }
#pragma unroll
    for (int s = 0; s < 4; s++) { if (s == 0) wg_rs8<0>(n, F[s], dn); else wg_rs8<1>(n, F[s], dn + s * 2); }
    wg_commit();
    SF();
    sh1();
    wg_wait<0>();
#pragma unroll
    for (int b = 0; b < 8; b++) {
        const uint32_t o = INV ? so ^ ((b >> 1) * 288 ^ (b & 1) * 32) : (so ^ ((b & 3) * 32)) + (b >> 2) * 1024;
        stsm4(buf + o, pack2(d[8 * b], d[8 * b + 1]), pack2(d[8 * b + 2], d[8 * b + 3]), pack2(d[8 * b + 4], d[8 * b + 5]), pack2(d[8 * b + 6], d[8 * b + 7]));
    }
}

template <bool ODD>
DEVI void fft_filter(uint32_t aw, const float (&e)[32], const float (&o)[32], uint32_t (&u)[4][4], uint32_t (&v)[4][4]) {
#pragma unroll
    for (int s = 0; s < 4; s++) {
        float y[2][2][4];
#pragma unroll
        for (int c = 0; c < 2; c++) {
            float f[4][2];
#pragma unroll
            for (int i = 0; i < 4; i++) {
                const uint32_t a = aw + (i * 32 + s * 8 + c) * 144, x = lds32(a);
                f[i][0] = ODD ? hi_f(x) : lo_f(x);
                f[i][1] = ODD ? lo_f(lds32(a + 4)) : hi_f(x);
            }
#pragma unroll
            for (int h = 0; h < 2; h++) {
                const int x = 8 * s + 2 * h + c;
                const float ar = e[x] + o[x], ai = e[x + 4] + o[x + 4], br = e[x] - o[x], bi = e[x + 4] - o[x + 4];
                const float yr = fmaf(-ai, f[2][h], ar * f[0][h]), yi = fmaf(ar, f[2][h], ai * f[0][h]);
                y[h][c][0] = fmaf(-bi, f[3][h], fmaf(br, f[1][h], yr));
                y[h][c][1] = fmaf(br, f[3][h], fmaf(bi, f[1][h], yi));
                y[h][c][2] = fmaf(2.f, yr, -y[h][c][0]);
                y[h][c][3] = fmaf(2.f, yi, -y[h][c][1]);
            }
        }
#pragma unroll
        for (int h = 0; h < 2; h++) {
            u[s][h] = pack2(y[h][0][0], y[h][1][0]); u[s][h + 2] = pack2(y[h][0][1], y[h][1][1]);
            v[s][h] = pack2(y[h][0][2], y[h][1][2]); v[s][h + 2] = pack2(y[h][0][3], y[h][1][3]);
        }
    }
}

__global__ void __launch_bounds__(F_THREADS, 1)
post_kernel(const __grid_constant__ CUtensorMap tmx, const __grid_constant__ CUtensorMap tmg1, const __grid_constant__ CUtensorMap tmg2,
           const __grid_constant__ CUtensorMap tmwr, const __grid_constant__ CUtensorMap tmwi, const __grid_constant__ CUtensorMap tmy,
           const bf16* __restrict__ wr, const bf16* __restrict__ wi, uint32_t* cnt, uint32_t zero, int nw) {
    extern __shared__ __align__(1024) uint8_t smem[];
    const uint32_t sb = SB0;
    if (smem_u32(smem) != sb) die(1 << 23);
    const uint32_t tid = threadIdx.x, lane = tid & 31, g = lane >> 2, t = lane & 3, j8 = lane & 7, mat = lane >> 3;
    const uint32_t wi_ = __reduce_max_sync(0xFFFFFFFFu, tid >> 5), q = wi_ >> 2, w = wi_ & 3;
    const int cta = blockIdx.x;
    const int nt = cta < 64 ? (64 - cta + nw - 1) / nw : 0;
    const uint32_t bar = sb + FS_BAR;
    if (tid == 0) {
        for (int i = 0; i < 30; i++) mbar_init(bar + i * 8, i < 3 ? 4 : i < 6 ? 16 : i >= 14 && i < 18 ? 2 : 1);
        asm volatile("fence.mbarrier_init.release.cluster;" ::: "memory");
        fence_smem();
    }
    __syncthreads();
#define FT(n)
    FT(0);
#define N2(p) (2 * ((p) & 31) + ((p) >> 5))
#define WLOAD(tk, part) { \
        const uint32_t wd_ = sb + 131072 + q * 18432 + (part) * 9216, wb_ = bar + 112 + q * 8; \
        mbar_expect(wb_, 9216); \
        if ((tk) < 256) tma3d(wd_, (part) ? &tmwi : &tmwr, wb_, ((tk) & 63) * 64, (tk) >> 6, 0); \
        else asm volatile("cp.async.bulk.shared::cluster.global.mbarrier::complete_tx::bytes [%0], [%1], 9216, [%2];" \
                          ::"r"(wd_), "l"(g_WN + (part) * 576), "r"(wb_) : "memory"); }
#define GROW(tk) ((tk) < 256 ? ((tk) >> 5) * 64 + ((tk) & 7) * 8 + (((tk) >> 3) & 3) * 2 : 512)
#define DLOAD(tk, sl) { mbar_expect(bar + 48 + (sl) * 8, 16384); tma3d(sb + (sl) * 16384, &tmg2, bar + 48 + (sl) * 8, 0, GROW(tk), 0); }
#define IO(c) if (w == 3 && (c) && elect())
#define XLOAD1(i, bb) { const uint32_t xb_ = bar + 144 + (bb) * 32 + q * 8; mbar_expect(xb_, 16384); tma4d(sb + (bb) * 65536 + q * 16384, &tmx, xb_, 0, 0, q * 8, N2(cta + (i) * nw)); }
#define GLOAD3(i, bb) { mbar_expect(bar + (bb) * 8, q ? 16384 : 16512); tma3d(sb + (bb) * 65536 + q * 16384, &tmg1, bar + (bb) * 8, 0, q * 128, cta + (i) * nw); \
        if (q == 0) asm volatile("cp.async.bulk.shared::cluster.global.mbarrier::complete_tx::bytes [%0], [%1], 128, [%2];" \
                                 ::"r"(sb + FS_NQ + (bb) * 1024), "l"(g_GN + (cta + (i) * nw) * 8), "r"(bar + (bb) * 8) : "memory"); }
    for (int i = 0; i < 3; i++) IO(i < nt) XLOAD1(i, i);
    for (uint32_t x = tid; x < 40 * 32; x += 512) {
        const uint32_t n = x >> 5, m2 = mat * 8 + t * 2, ri = g & 1;
        const uint32_t c2 = ((n >> 1) & 1) + ((n >> 3) & 1) * 2 + (n & 4) + (n >> 4) * 8;
        const uint32_t v = cos2(m2 * c2 * 64 + ((n & 1) - ri) * 512, (m2 + 1) * c2 * 64 + ((n & 1) - ri) * 512);
        sts32(sb + FS_F2 + n * 128 + ((g ^ (n & 7)) << 4) + t * 4, n < 32 ? v : n == 32 && ri == 0 ? 0xBF003F00u : 0u);
    }
    float tc[8], ts[8];
    uint32_t F[2][4];
    uint32_t c1 = 16 * (w >> 1) + 2 * g + (w & 1);
#pragma unroll
    for (int i = 0; i < 8; i++) {
        twid(c1 * (8 * (i >> 1) + 2 * t + (i & 1)), tc[i], ts[i]);
        const uint32_t m1 = (i >> 1) * 8 + 2 * t;
        F[i >> 2][i & 3] = cos2(c1 * m1 * 64 + (i & 1) * 512, c1 * (m1 + 1) * 64 + (i & 1) * 512);
    }
    {
        const uint32_t kr = (2 * (mat & 1) + (j8 & 1)) ^ ((j8 >> 2) << 1);
        const uint32_t so1 = ((mat >> 1) + 2 * (j8 >> 2)) * 1024 + kr * 128 + (((((j8 >> 1) & 1) * 4 + w) ^ kr) << 4);
        const uint32_t so2 = (2 * w + (mat & 1)) * 8192 + q * 2048 + j8 * 128 + (((mat >> 1) ^ j8) << 4);
        uint32_t so = so1 << 16 | so2;
        const float fx = (tid & 127) == 0 ? 0.5f : 1.f;
        fft_gen<false>(sb + FS_TB, N2(cta));
        fence_smem();
        bsync<1, 512>();
        FT(1);
        int b = 0, bp = 2, ph = 0;
        if (nt) mwait(bar + 144 + q * 8, 0);
        __syncwarp();
        auto step = [&](auto first, auto last, const int i) {
            const uint32_t p = cta + i * nw, bn = 3 - b - bp, tb = (i & 1) * 8192;
            const uint32_t grp = sb + b * 65536 + q * 16384, nq = sb + FS_NQ + b * 1024 + q * 32;
            auto sa = [&]() {
                if constexpr (!decltype(first)::v) {
                    fence_smem();
                    __syncwarp();
                    if (elect()) mbar_arrive(bar + 24);
                }
                IO(i > 1) {
                    mwait(bar + 32, i & 1);
                    tma3s(&tmg1, sb + bn * 65536 + q * 16384, 0, q * 128, p - 2 * nw);
                    bulk_commit();
                }
            };
            auto sb_ = [&]() { if constexpr (!decltype(first)::v) mwait(bar + 24, (i - 1) & 1); };
            if constexpr (!decltype(last)::v) fft_rows<false>(grp, q, F, tc, ts, opq(so, zero) >> 16, fx, nq, sa, sb_);
            else { sa(); __syncwarp(); sb_(); __syncwarp(); }
            if constexpr (!decltype(first)::v) {
                float n[4];
                fft_cross<false>(sb + bp * 65536, q, sb + FS_TB + 8192 - tb + (((tidx() & 127) ^ (q & 1)) << 4), opq(so, zero) & 0xFFFF, sb + FS_NQ + bp * 1024, n, [&]() {
                    fft_gen<false>(sb + FS_TB + tb, N2(p));
                    IO(i >= 2 && i + 1 < nt) {
                        asm volatile("cp.async.bulk.wait_group.read 0;" ::: "memory");
                        XLOAD1(i + 1, bn);
                    }
                });
                if (q == 0) {
                    const uint32_t x = tidx();
                    bf16* z = (bf16*)(g_G + ((p - nw) * G_ROWS + 512) * 8) + (x & 4) * 16 + ((x >> 2) & 24) + ((x >> 3) & 3);
                    asm volatile("{\n.reg .pred p;\n.reg .b16 a, b;\nsetp.eq.u32 p, %2, 0;\nmov.b32 {a, b}, %1;\n@p st.global.u16 [%0], a;\n@p st.global.u16 [%0+8], b;\n}"
                                 ::"l"(z), "r"(pack2(n[0], n[2])), "r"(x & 3) : "memory");
                }
            }
            if constexpr (!decltype(last)::v) {
                fft_rows<false>(grp + 8192, q, F, tc, ts, opq(so, zero) >> 16, fx, nq + 16, [&]() {
                    if constexpr (!decltype(first)::v) {
                        fence_smem();
                        __syncwarp();
                        if (elect()) mbar_arrive(bar + 32);
                    }
                    if ((w == 1 || w == 2) && elect())
                        asm volatile("cp.async.bulk.prefetch.L2.global [%0], 8208;" ::"l"((w == 1 ? wr : wi) + (p * 4 + q) * 4104) : "memory");
                }, [&]() { if (i + 1 < nt) mwait(bar + 144 + bn * 32 + q * 8, bn ? ph : ph ^ 1); });
                bp = b;
                if (++b == 3) { b = 0; ph ^= 1; }
            }
        };
        if (nt) {
            step(Bool<true>(), Bool<false>(), 0);
#pragma unroll 1
            for (int i = 1; i < nt; i++) step(Bool<false>(), Bool<false>(), i);
            step(Bool<false>(), Bool<true>(), nt);
        }
        for (uint32_t x = cta * 512 + tid; x < 4096; x += nw * 512)
            ((bf16*)g_WN)[(x >> 5) * 72 + (x & 16) + (x & 7) * 2 + ((x >> 3) & 1)] = (x < 2048 ? wr : wi)[(x & 2047) * 513 + 512];
        FT(2);
        fence_async();
        bsync<1, 512>();
        IO(nt) { tma3s(&tmg1, sb + bp * 65536 + q * 16384, 0, q * 128, cta + (nt - 1) * nw); bulk_commit(); }
    }
    for (uint32_t x = tid; x < 128 * 32; x += 512) {
        const uint32_t n = (x >> 5) & 63, a = x & 31, k2 = (n >> 4) * 8 + (n & 7);
        sts32(sb + FS_TB + (x >> 5) * 128 + (((a >> 2) ^ (n & 7)) << 4) + (a & 3) * 4, cis((2 * a + (x >> 11)) * k2 * 32 + (n & 8) * 64));
    }
    fence_smem();
    bsync<1, 512>();
    IO(true) {
        asm volatile("cp.async.bulk.wait_group 0;" ::: "memory");
        grid_arrive(cnt, 4 * nw);
        grid_wait(cnt);
        const int tk = cta + q * nw;
        if (tk <= 256) { DLOAD(tk, q); WLOAD(tk, 0); WLOAD(tk, 1); }
    }
    __syncwarp();
    {
        const uint32_t lo = j8 * 128 + (((2 * w + (mat & 1)) ^ j8) << 4);
        const uint32_t aw = sb + 131072 + q * 18432 + t * 288 + w * 32 + g * 4;
        const uint64_t df = mkdesc(sb + FS_TB, 16, 1024);
        const uint64_t da = mkdesc(sb + q * 16384, 16, 1024);
        const uint32_t buf = sb + 65536 + q * 16384;
        int i = 0, tk = cta + q * nw;
        if (tk <= 256) mwait(bar + 48 + q * 8, 0);
        FT(3);
#pragma unroll 1
        for (; tk <= 256; tk += 4 * nw, i++) {
            const bool more = tk + 4 * nw <= 256;
            float e[32], o[32];
            wg_fence();
#pragma unroll
            for (int s = 0; s < 4; s++) { if (s == 0) wg_ss64a<0>(e, da, df); else wg_ss64a<1>(e, da + s * 128, df + s * 2); }
#pragma unroll
            for (int s = 0; s < 4; s++) { if (s == 0) wg_ss64a<0>(o, da + 512, df + 512); else wg_ss64a<1>(o, da + 512 + s * 128, df + 512 + s * 2); }
            wg_commit();
            SF();
            if (i > 0) {
                fence_smem();
                wgbar(q);
                IO(true) { tma3s(&tmg2, buf, 0, GROW(tk - 4 * nw), 0); bulk_commit(); }
            }
            if (w == 2 && more && elect()) mbar_expect(bar + 48 + q * 8, 16384);
            const int gr = GROW(tk + 4 * nw);
            mwait(bar + 112 + q * 8, i & 1);
            wg_wait<0>();
            if (w == 2 && more && elect()) tma3d(sb + q * 16384, &tmg2, bar + 48 + q * 8, 0, gr, 0);
            uint32_t u[4][4], v[4][4];
            if (tk & 8) fft_filter<true>(aw + (tk & 48) / 4, e, o, u, v);
            else fft_filter<false>(aw + (tk & 48) / 4, e, o, u, v);
            wg_fence();
#pragma unroll
            for (int s = 0; s < 4; s++) { if (s == 0) wg_rs64t<0>(e, u[s], df); else wg_rs64t<1>(e, u[s], df + s * 128); }
#pragma unroll
            for (int s = 0; s < 4; s++) { if (s == 0) wg_rs64t<0>(o, v[s], df + 512); else wg_rs64t<1>(o, v[s], df + 512 + s * 128); }
            wg_commit();
            SF();
            IO(true) asm volatile("cp.async.bulk.wait_group.read 0;" ::: "memory");
            wgbar(q);
            if (more) {
                if ((w == 1 || w == 2) && elect()) WLOAD(tk + 4 * nw, w - 1);
                mwait(bar + 48 + q * 8, (i + 1) & 1);
            }
            wg_wait<0>();
#pragma unroll
            for (int s = 0; s < 4; s++) {
                const uint32_t a = buf + (mat >> 1) * 1024 + lo + s * 2048;
                stsm4t(a, pack2(e[8 * s], e[8 * s + 1]), pack2(e[8 * s + 2], e[8 * s + 3]), pack2(e[8 * s + 4], e[8 * s + 5]), pack2(e[8 * s + 6], e[8 * s + 7]));
                stsm4t(a + 8192, pack2(o[8 * s], o[8 * s + 1]), pack2(o[8 * s + 2], o[8 * s + 3]), pack2(o[8 * s + 4], o[8 * s + 5]), pack2(o[8 * s + 6], o[8 * s + 7]));
            }
            if (tk == 256 && w < 2) {
                uint32_t* z = (uint32_t*)g_GN + t * 32 + w * 16 + g;
#pragma unroll
                for (int s = 0; s < 16; s++) {
                    z[(s >> 1) * 128 + (s & 1) * 8] = pack2(e[2 * s], e[2 * s + 1]);
                    z[(s >> 1) * 128 + (s & 1) * 8 + 1024] = pack2(o[2 * s], o[2 * s + 1]);
                }
                fence_async();
            }
        }
        fence_smem();
        wgbar(q);
        IO(true) {
            if (i > 0) { tma3s(&tmg2, buf, 0, GROW(tk - 4 * nw), 0); bulk_commit(); }
            asm volatile("cp.async.bulk.wait_group 0;" ::: "memory");
            grid_arrive(cnt + 1, 4 * nw);
        }
    }
    FT(4);
    bsync<1, 512>();
    {
        for (uint32_t n = wi_; n < 32; n += 16) {
            const uint32_t cl = (mat >> 1) * 16 + t * 4 + (mat & 1), mh = ((n >> 3) & 1) + (n & 7) * 2 + (n & 16);
            sts32(sb + FS_F2 + n * 128 + ((g ^ (n & 7)) << 4) + t * 4, cos2(cl * mh * 64 + (g & 1) * 512, (cl + 2) * mh * 64 + (g & 1) * 512));
        }
        fence_smem();
        c1 = 8 * w + g;
#pragma unroll
        for (int i = 0; i < 8; i++) {
            twid(-c1 * (16 * (i >> 2) + 4 * t + 2 * (i & 1) + ((i >> 1) & 1)), tc[i], ts[i]);
            F[i >> 2][i & 3] = cis((i & 1) * 512 - c1 * ((i >> 1) * 4 + (t ^ (q & 1))) * 64);
        }
        const uint32_t kr = (j8 & 1) ^ ((j8 >> 2) << 1);
        const uint32_t so2 = ((w >> 1) * 4 + (j8 >> 2) * 2 + (w & 1)) * 8192 + (2 * q + (mat & 1)) * 1024 + kr * 128 + (((((j8 >> 1) & 1) * 4 + (mat >> 1)) ^ kr) << 4);
        const uint32_t so1 = (mat & 1) * 2048 + j8 * 128 + ((((mat >> 1) * 4 + w) ^ j8) << 4);
        uint32_t so = so1 << 16 | so2;
        const float fx = t ? 0.f : (g & 1) ? -1.f : 1.f;
        fft_gen<true>(sb + FS_TB, N2(cta));
        bsync<1, 512>();
        IO(true) grid_wait(cnt + 1);
        for (int i = 0; i < 3; i++) IO(i < nt) GLOAD3(i, i);
        __syncwarp();
        int b = 0, bp = 2, ph = 0;
        auto step = [&](auto first, auto last, const int i) {
            const uint32_t p = cta + i * nw, bn = 3 - b - bp, tb = (i & 1) * 8192;
            const uint32_t grp = sb + bp * 65536 + q * 16384, ny = sb + FS_NY + bp * 128 + q * 32;
            auto sb_ = [&]() { if constexpr (!decltype(last)::v) mwait(bar + b * 8, ph); };
            if constexpr (!decltype(first)::v) {
                fft_rows<true>(grp, q, F, tc, ts, opq(so, zero) >> 16, fx, ny, [&]() {
                    if (i > 1) {
                        fence_smem();
                        wgbar(q);
                        IO(true) { tma4s(&tmy, sb + bn * 65536 + q * 16384, 0, 0, q * 8, N2(p - 2 * nw)); bulk_commit(); }
                    }
                }, sb_);
            } else { sb_(); __syncwarp(); }
            if constexpr (decltype(first)::v) FT(5);
            if constexpr (!decltype(last)::v) {
                float n[4];
                fft_cross<true>(sb + b * 65536, q, sb + FS_TB + tb + (tidx() & 127) * 16, opq(so, zero) & 0xFFFF, sb + FS_NQ + b * 1024, n, [&]() {
                    fft_gen<true>(sb + FS_TB + 8192 - tb, N2(p + nw));
                    IO(i >= 2 && i + 1 < nt) {
                        asm volatile("cp.async.bulk.wait_group.read 0;" ::: "memory");
                        GLOAD3(i + 1, bn);
                    }
                });
                if (q == 0) {
                    const uint32_t x = tidx(), a = sb + FS_NY + b * 128 + (x & 64) + (x & 16) * 2 + ((x & 40) >> 1);
                    if ((x & 7) == 0) { sts32f(a, n[0]); sts32f(a + 8, n[2]); }
                }
            }
            auto sc = [&]() {
                if constexpr (!decltype(last)::v) {
                    fence_smem();
                    __syncwarp();
                    if (elect()) mbar_arrive(bar + 24);
                }
            };
            auto sd = [&]() { if constexpr (!decltype(last)::v) mwait(bar + 24, (nt + i) & 1); };
            if constexpr (!decltype(first)::v) fft_rows<true>(grp + 8192, q, F, tc, ts, opq(so, zero) >> 16, fx, ny + 16, sc, sd);
            else { sc(); __syncwarp(); sd(); __syncwarp(); }
            if constexpr (!decltype(last)::v) {
                bp = b;
                if (++b == 3) { b = 0; ph ^= 1; }
            }
        };
        if (nt) {
            step(Bool<true>(), Bool<false>(), 0);
#pragma unroll 1
            for (int i = 1; i < nt; i++) step(Bool<false>(), Bool<false>(), i);
            step(Bool<false>(), Bool<true>(), nt);
        }
        fence_smem();
        wgbar(q);
        IO(nt) { tma4s(&tmy, sb + bp * 65536 + q * 16384, 0, 0, q * 8, N2(cta + (nt - 1) * nw)); bulk_commit(); }
        FT(6);
        IO(true) asm volatile("cp.async.bulk.wait_group 0;" ::: "memory");
    }
}

typedef CUresult (*EncodeFn)(CUtensorMap*, CUtensorMapDataType, cuuint32_t, void*, const cuuint64_t*, const cuuint64_t*,
                             const cuuint32_t*, const cuuint32_t*, CUtensorMapInterleave, CUtensorMapSwizzle,
                             CUtensorMapL2promotion, CUtensorMapFloatOOBfill);

static void make_map(EncodeFn enc, CUtensorMap* m, const void* ptr, int rank, const cuuint64_t* dims, const cuuint64_t* strides,
                     const cuuint32_t* box, CUtensorMapSwizzle sw = CU_TENSOR_MAP_SWIZZLE_128B) {
    cuuint32_t es[4] = {1, 1, 1, 1};
    CUresult r = enc(m, CU_TENSOR_MAP_DATA_TYPE_BFLOAT16, rank, (void*)ptr, dims, strides, box, es, CU_TENSOR_MAP_INTERLEAVE_NONE,
                     sw, CU_TENSOR_MAP_L2_PROMOTION_L2_256B, CU_TENSOR_MAP_FLOAT_OOB_FILL_NONE);
    if (r != CUDA_SUCCESS) fprintf(stderr, "tensor map encode failed: %d\n", (int)r);
}

extern "C" void kernel_launch(void* const* d_in, const int* in_sizes, int n_in, void* d_out, int out_size) {
    const bf16* A_x = (const bf16*)d_in[0];
    const bf16* A_mem0 = (const bf16*)d_in[1];
    const bf16* A_Wq = (const bf16*)d_in[2];
    const bf16* A_Wk = (const bf16*)d_in[3];
    const bf16* A_Wv = (const bf16*)d_in[4];
    const bf16* A_Wo = (const bf16*)d_in[5];
    const bf16* B_x = (const bf16*)d_in[7];
    const bf16* B_wr = (const bf16*)d_in[8];
    const bf16* B_wi = (const bf16*)d_in[9];
    bf16* out = (bf16*)d_out;

    static EncodeFn enc = nullptr;
    static void *pxs = nullptr, *pg = nullptr;
    static int ncl = 64;
    if (!enc) {
        cudaDriverEntryPointQueryResult qr;
        void* fn = nullptr;
        cudaGetDriverEntryPoint("cuTensorMapEncodeTiled", &fn, cudaEnableDefault, &qr);
        enc = (EncodeFn)fn;
        cudaFuncSetAttribute(chain_kernel, cudaFuncAttributeMaxDynamicSharedMemorySize, SM_TOTAL);
        cudaFuncSetAttribute(post_kernel, cudaFuncAttributeMaxDynamicSharedMemorySize, FS_TOTAL);
        cudaGetSymbolAddress(&pxs, g_xs);
        cudaGetSymbolAddress(&pg, g_G);
        cudaLaunchConfig_t lc = {};
        cudaLaunchAttribute at;
        at.id = cudaLaunchAttributeClusterDimension;
        at.val.clusterDim.x = 2; at.val.clusterDim.y = 1; at.val.clusterDim.z = 1;
        lc.gridDim = dim3(132); lc.blockDim = dim3(384); lc.dynamicSmemBytes = SM_TOTAL; lc.attrs = &at; lc.numAttrs = 1;
        int nc = 0;
        if (cudaOccupancyMaxActiveClusters(&nc, chain_kernel, &lc) == cudaSuccess && nc > 64) ncl = nc < 66 ? nc : 66;
    }
    CUtensorMap tmq, tmk, tmv, tmo, tmx, tmb, tmy;
    {
        cuuint64_t d[3] = {64, DM, HD / 64}, st[2] = {HD * 2, 128};
        cuuint32_t bx[3] = {64, 64, 2};
        make_map(enc, &tmq, A_Wq, 3, d, st, bx);
        make_map(enc, &tmk, A_Wk, 3, d, st, bx);
        make_map(enc, &tmv, A_Wv, 3, d, st, bx);
    }
    {
        cuuint64_t d[2] = {DM, HD}, st[1] = {DM * 2};
        cuuint32_t bx[2] = {64, 16}, bx1[2] = {64, 128}, bx2[3] = {64, 64, 2};
        make_map(enc, &tmo, A_Wo, 2, d, st, bx1);
        cuuint64_t d2[3] = {64, HD, DM / 64}, st2[2] = {DM * 2, 128}, d3[2] = {DM, SEQ}, st3[1] = {DM * 4};
        make_map(enc, &tmb, A_Wo, 3, d2, st2, bx2);
        make_map(enc, &tmy, out, 2, d3, st3, bx);
    }
    {
        cuuint64_t d[3] = {64, SEQ, DM / 64}, st[2] = {DM * 2, 128};
        cuuint32_t bx[3] = {64, 8, 4};
        make_map(enc, &tmx, A_x, 3, d, st, bx);
    }
    CUtensorMap fx, fg1, fg2, fwr, fwi, fy;
    {
        cuuint64_t d[4] = {32, 32, 32, 64}, st[3] = {64, 64 * DM * 2, DM * 2};
        cuuint32_t bx[4] = {32, 32, 8, 1};
        make_map(enc, &fx, B_x, 4, d, st, bx, CU_TENSOR_MAP_SWIZZLE_64B);
        cuuint64_t d2[4] = {64, 16, 32, 64}, st2[3] = {128, 64 * 4096, 4096};
        cuuint32_t bx2[4] = {64, 16, 8, 1};
        make_map(enc, &fy, out + DM, 4, d2, st2, bx2);
    }
    {
        cuuint64_t d[3] = {64, G_ROWS, 64}, st[2] = {128, G_ROWS * 128};
        cuuint32_t bx[3] = {64, 128, 1}, bx2[3] = {64, 2, 64};
        make_map(enc, &fg1, pg, 3, d, st, bx);
        make_map(enc, &fg2, pg, 3, d, st, bx2);
        cuuint64_t d2[3] = {8 * 513, 4, 64}, st2[2] = {8 * 513 * 2, 32 * 513 * 2};
        cuuint32_t bx3[3] = {72, 1, 64};
        make_map(enc, &fwr, B_wr, 3, d2, st2, bx3, CU_TENSOR_MAP_SWIZZLE_NONE);
        make_map(enc, &fwi, B_wi, 3, d2, st2, bx3, CU_TENSOR_MAP_SWIZZLE_NONE);
    }
    cudaStream_t st = cudaStreamPerThread;
    const uint64_t xs = ((uint64_t)pxs + XS_BYTES - 1) & ~(uint64_t)(XS_BYTES - 1);
    chain_kernel<<<2 * ncl, 384, SM_TOTAL, st>>>(tmq, tmk, tmv, tmo, tmx, tmb, tmy, A_mem0, A_x, (uint32_t)xs, (uint32_t)(xs >> 32), 0u, NSEG, out);
    int nw = ncl == 66 ? 4 : 64;
    cudaLaunchConfig_t lc = {};
    cudaLaunchAttribute at;
    at.id = cudaLaunchAttributeProgrammaticStreamSerialization;
    at.val.programmaticStreamSerializationAllowed = 1;
    lc.gridDim = dim3(nw); lc.blockDim = dim3(F_THREADS); lc.dynamicSmemBytes = FS_TOTAL; lc.stream = st; lc.attrs = &at; lc.numAttrs = 1;
    cudaLaunchKernelEx(&lc, post_kernel, fx, fg1, fg2, fwr, fwi, fy, B_wr, B_wi, (uint32_t*)(xs + XO_TK + 256), 0u, nw);
}
```

```cpp
#include <cuda_runtime.h>
#include <cuda_bf16.h>
#include <cuda.h>
#include <stdint.h>
#include <stdio.h>

typedef __nv_bfloat16 bf16;

#define SEQ 2048
#define DM 1024
#define NH 32
#define DH 128
#define NSEG 64
#define HD (NH * DH)

#define XS_BYTES (32u << 20)
__device__ uint4 g_xs[2 * XS_BYTES / 16];
#define XO_R 0u
#define XO_PB (1u << 18)
#define XO_FL (XO_PB + 32768u)
#define XO_TK (XO_FL + 4096u)
#define XO_CQK (1u << 20)
#define XO_CV (2u << 20)
#define XO_XG (4u << 20)
#define XO_OX (16u << 20)
#define GSYNC(n)
#define PG(n)

#define DEVI __device__ __forceinline__

DEVI void die(int it) { asm volatile("st.shared.u32 [%0], %0;" ::"r"(it) : "memory"); }
DEVI uint32_t smem_u32(const void* p) { return (uint32_t)__cvta_generic_to_shared(p); }
DEVI void mbar_init(uint32_t bar, uint32_t cnt) { asm volatile("mbarrier.init.shared::cta.b64 [%0], %1;" ::"r"(bar), "r"(cnt) : "memory"); }
DEVI void mbar_expect(uint32_t bar, uint32_t bytes) { asm volatile("mbarrier.arrive.expect_tx.shared::cta.b64 _, [%0], %1;" ::"r"(bar), "r"(bytes) : "memory"); }
DEVI void mbar_arrive(uint32_t bar) { asm volatile("mbarrier.arrive.shared::cta.b64 _, [%0];" ::"r"(bar) : "memory"); }
DEVI void mbar_wait(uint32_t bar, uint32_t parity) {
    uint32_t done;
    int it = 0;
    do {
        asm volatile("{\n.reg .pred p;\nmbarrier.try_wait.parity.shared::cta.b64 p, [%1], %2;\nselp.u32 %0, 1, 0, p;\n}\n"
                     : "=r"(done) : "r"(bar), "r"(parity) : "memory");
        if (++it > (1 << 22)) die(it);
    } while (!done);
}
DEVI void tma2d(uint32_t dst, const CUtensorMap* tm, uint32_t bar, int c0, int c1) {
    asm volatile("cp.async.bulk.tensor.2d.shared::cluster.global.mbarrier::complete_tx::bytes [%0], [%1, {%3, %4}], [%2];"
                 ::"r"(dst), "l"(tm), "r"(bar), "r"(c0), "r"(c1) : "memory");
}
DEVI void tma3d(uint32_t dst, const CUtensorMap* tm, uint32_t bar, int c0, int c1, int c2) {
    asm volatile("cp.async.bulk.tensor.3d.shared::cluster.global.mbarrier::complete_tx::bytes [%0], [%1, {%3, %4, %5}], [%2];"
                 ::"r"(dst), "l"(tm), "r"(bar), "r"(c0), "r"(c1), "r"(c2) : "memory");
}
DEVI void bulk_g2s(uint32_t dst, uint32_t lo, uint32_t hi, uint32_t bytes, uint32_t bar) {
    asm volatile("{\n.reg .b64 a;\nmov.b64 a, {%1,%2};\ncp.async.bulk.shared::cluster.global.mbarrier::complete_tx::bytes [%0], [a], %3, [%4];\n}"
                 ::"r"(dst), "r"(lo), "r"(hi), "r"(bytes), "r"(bar) : "memory");
}
DEVI void bulk_s2g(uint32_t lo, uint32_t hi, uint32_t src, uint32_t bytes) {
    asm volatile("{\n.reg .b64 a;\nmov.b64 a, {%0,%1};\ncp.async.bulk.global.shared::cta.bulk_group [a], [%2], %3;\ncp.async.bulk.commit_group;\n}"
                 ::"r"(lo), "r"(hi), "r"(src), "r"(bytes) : "memory");
}
DEVI void bulk_red(uint32_t lo, uint32_t hi, uint32_t src, uint32_t bytes) {
    asm volatile("{\n.reg .b64 a;\nmov.b64 a, {%0,%1};\ncp.reduce.async.bulk.global.shared::cta.bulk_group.add.noftz.bf16 [a], [%2], %3;\ncp.async.bulk.commit_group;\n}"
                 ::"r"(lo), "r"(hi), "r"(src), "r"(bytes) : "memory");
}
DEVI bool elect() {
    uint32_t p;
    asm volatile("{\n.reg .pred P;\nelect.sync _|P, 0xFFFFFFFF;\nselp.u32 %0, 1, 0, P;\n}" : "=r"(p));
    return p != 0;
}
DEVI void ldsm4(uint32_t (&r)[4], uint32_t a) {
    asm volatile("ldmatrix.sync.aligned.m8n8.x4.shared.b16 {%0,%1,%2,%3}, [%4];" : "=r"(r[0]), "=r"(r[1]), "=r"(r[2]), "=r"(r[3]) : "r"(a) : "memory");
}
DEVI void ldsm4t(uint32_t (&r)[4], uint32_t a) {
    asm volatile("ldmatrix.sync.aligned.m8n8.x4.trans.shared.b16 {%0,%1,%2,%3}, [%4];" : "=r"(r[0]), "=r"(r[1]), "=r"(r[2]), "=r"(r[3]) : "r"(a) : "memory");
}
DEVI void ldsm2t(uint32_t (&r)[2], uint32_t a) {
    asm volatile("ldmatrix.sync.aligned.m8n8.x2.trans.shared.b16 {%0,%1}, [%2];" : "=r"(r[0]), "=r"(r[1]) : "r"(a) : "memory");
}
DEVI void ldsm2(uint32_t (&r)[2], uint32_t a) {
    asm volatile("ldmatrix.sync.aligned.m8n8.x2.shared.b16 {%0,%1}, [%2];" : "=r"(r[0]), "=r"(r[1]) : "r"(a) : "memory");
}
DEVI void stsm4t(uint32_t a, uint32_t r0, uint32_t r1, uint32_t r2, uint32_t r3) {
    asm volatile("stmatrix.sync.aligned.m8n8.x4.trans.shared.b16 [%0], {%1,%2,%3,%4};" ::"r"(a), "r"(r0), "r"(r1), "r"(r2), "r"(r3) : "memory");
}
DEVI uint32_t ldsm1(uint32_t a) {
    uint32_t r;
    asm volatile("ldmatrix.sync.aligned.m8n8.x1.shared.b16 {%0}, [%1];" : "=r"(r) : "r"(a) : "memory");
    return r;
}
DEVI void stsm4(uint32_t a, uint32_t r0, uint32_t r1, uint32_t r2, uint32_t r3) {
    asm volatile("stmatrix.sync.aligned.m8n8.x4.shared.b16 [%0], {%1,%2,%3,%4};" ::"r"(a), "r"(r0), "r"(r1), "r"(r2), "r"(r3) : "memory");
}
DEVI void stsm2(uint32_t a, uint32_t r0, uint32_t r1) {
    asm volatile("stmatrix.sync.aligned.m8n8.x2.shared.b16 [%0], {%1,%2};" ::"r"(a), "r"(r0), "r"(r1) : "memory");
}
DEVI uint32_t movm(uint32_t a) {
    uint32_t d;
    asm volatile("movmatrix.sync.aligned.m8n8.trans.b16 %0, %1;" : "=r"(d) : "r"(a));
    return d;
}
DEVI void mma16(float (&d)[4], uint32_t a0, uint32_t a1, uint32_t a2, uint32_t a3, uint32_t b0, uint32_t b1) {
    asm volatile("mma.sync.aligned.m16n8k16.row.col.f32.bf16.bf16.f32 {%0,%1,%2,%3}, {%4,%5,%6,%7}, {%8,%9}, {%0,%1,%2,%3};"
                 : "+f"(d[0]), "+f"(d[1]), "+f"(d[2]), "+f"(d[3]) : "r"(a0), "r"(a1), "r"(a2), "r"(a3), "r"(b0), "r"(b1));
}
DEVI void mma16z(float (&d)[4], uint32_t a0, uint32_t a1, uint32_t a2, uint32_t a3, uint32_t b0, uint32_t b1) {
    asm volatile("mma.sync.aligned.m16n8k16.row.col.f32.bf16.bf16.f32 {%0,%1,%2,%3}, {%4,%5,%6,%7}, {%8,%9}, {%10,%10,%10,%10};"
                 : "=f"(d[0]), "=f"(d[1]), "=f"(d[2]), "=f"(d[3]) : "r"(a0), "r"(a1), "r"(a2), "r"(a3), "r"(b0), "r"(b1), "f"(0.f));
}
DEVI void mma8(float (&d)[4], uint32_t a0, uint32_t a1, uint32_t b0) {
    asm volatile("mma.sync.aligned.m16n8k8.row.col.f32.bf16.bf16.f32 {%0,%1,%2,%3}, {%4,%5}, {%6}, {%0,%1,%2,%3};"
                 : "+f"(d[0]), "+f"(d[1]), "+f"(d[2]), "+f"(d[3]) : "r"(a0), "r"(a1), "r"(b0));
}
DEVI void mma8z(float (&d)[4], uint32_t a0, uint32_t a1, uint32_t b0) {
    asm volatile("mma.sync.aligned.m16n8k8.row.col.f32.bf16.bf16.f32 {%0,%1,%2,%3}, {%4,%5}, {%6}, {%7,%7,%7,%7};"
                 : "=f"(d[0]), "=f"(d[1]), "=f"(d[2]), "=f"(d[3]) : "r"(a0), "r"(a1), "r"(b0), "f"(0.f));
}
DEVI uint32_t pack2(float lo, float hi) {
    uint32_t r;
    asm("cvt.rn.bf16x2.f32 %0, %1, %2;" : "=r"(r) : "f"(hi), "f"(lo));
    return r;
}
DEVI uint32_t hadd2(uint32_t a, uint32_t b) {
    uint32_t r;
    asm("add.rn.bf16x2 %0, %1, %2;" : "=r"(r) : "r"(a), "r"(b));
    return r;
}
DEVI float lo_f(uint32_t x) { return __uint_as_float(x << 16); }
DEVI float hi_f(uint32_t x) { return __uint_as_float(x & 0xFFFF0000u); }
template <uint32_t OFF> DEVI uint4 ldg4(uint32_t lo, uint32_t hi) {
    uint4 v;
    asm volatile("{\n.reg .b64 a;\nmov.b64 a, {%4,%5};\nld.relaxed.gpu.global.v4.u32 {%0,%1,%2,%3}, [a+%6];\n}"
                 : "=r"(v.x), "=r"(v.y), "=r"(v.z), "=r"(v.w) : "r"(lo), "r"(hi), "n"(OFF) : "memory");
    return v;
}
template <uint32_t OFF> DEVI uint2 ldg2(uint32_t lo, uint32_t hi) {
    uint2 v;
    asm volatile("{\n.reg .b64 a;\nmov.b64 a, {%2,%3};\nld.relaxed.gpu.global.v2.u32 {%0,%1}, [a+%4];\n}"
                 : "=r"(v.x), "=r"(v.y) : "r"(lo), "r"(hi), "n"(OFF) : "memory");
    return v;
}
template <uint32_t OFF> DEVI uint32_t ldg1(uint32_t lo, uint32_t hi) {
    uint32_t v;
    asm volatile("{\n.reg .b64 a;\nmov.b64 a, {%1,%2};\nld.relaxed.gpu.global.u32 %0, [a+%3];\n}" : "=r"(v) : "r"(lo), "r"(hi), "n"(OFF) : "memory");
    return v;
}
template <uint32_t OFF> DEVI void stg1(uint32_t lo, uint32_t hi, uint32_t a) {
    asm volatile("{\n.reg .b64 a;\nmov.b64 a, {%0,%1};\nst.relaxed.gpu.global.u32 [a+%3], %2;\n}" ::"r"(lo), "r"(hi), "r"(a), "n"(OFF) : "memory");
}
template <uint32_t OFF> DEVI void stg4(uint32_t lo, uint32_t hi, uint32_t a, uint32_t b, uint32_t c, uint32_t d) {
    asm volatile("{\n.reg .b64 a;\nmov.b64 a, {%0,%1};\nst.relaxed.gpu.global.v4.u32 [a+%6], {%2,%3,%4,%5};\n}"
                 ::"r"(lo), "r"(hi), "r"(a), "r"(b), "r"(c), "r"(d), "n"(OFF) : "memory");
}
template <uint32_t OFF> DEVI void stg2(uint32_t lo, uint32_t hi, uint32_t a, uint32_t b) {
    asm volatile("{\n.reg .b64 a;\nmov.b64 a, {%0,%1};\nst.relaxed.gpu.global.v2.u32 [a+%4], {%2,%3};\n}"
                 ::"r"(lo), "r"(hi), "r"(a), "r"(b), "n"(OFF) : "memory");
}
DEVI uint32_t tagx2(uint32_t a, uint32_t b, uint32_t t) { uint32_t r; asm("lop3.b32 %0, %1, %2, %3, 0x7E;" : "=r"(r) : "r"(a), "r"(b), "r"(t)); return r; }
DEVI uint32_t tagx1(uint32_t a, uint32_t b, uint32_t t) { uint32_t r; asm("lop3.b32 %0, %1, %2, %3, 0xF6;" : "=r"(r) : "r"(a), "r"(b), "r"(t)); return r; }
DEVI uint32_t or3(uint32_t a, uint32_t b, uint32_t c) { uint32_t r; asm("lop3.b32 %0, %1, %2, %3, 0xFE;" : "=r"(r) : "r"(a), "r"(b), "r"(c)); return r; }
DEVI bool any_bad(uint32_t x) { return __any_sync(0xFFFFFFFFu, (x & 1u) != 0); }
DEVI uint32_t settag(uint32_t x, uint32_t tag) { return (x & ~1u) | tag; }
DEVI void sts32f(uint32_t a, float v) { asm volatile("st.shared.f32 [%0], %1;" ::"r"(a), "f"(v) : "memory"); }
DEVI void sts32(uint32_t a, uint32_t v) { asm volatile("st.shared.u32 [%0], %1;" ::"r"(a), "r"(v) : "memory"); }
DEVI void sts16(uint32_t a, uint32_t v) { asm volatile("st.shared.u16 [%0], %1;" ::"r"(a), "h"((unsigned short)v) : "memory"); }
DEVI void sts64(uint32_t a, uint32_t x, uint32_t y) { asm volatile("st.shared.v2.u32 [%0], {%1,%2};" ::"r"(a), "r"(x), "r"(y) : "memory"); }
DEVI void sts128(uint32_t a, uint32_t x, uint32_t y, uint32_t z, uint32_t w) {
    asm volatile("st.shared.v4.u32 [%0], {%1,%2,%3,%4};" ::"r"(a), "r"(x), "r"(y), "r"(z), "r"(w) : "memory");
}
DEVI float4 lds128f(uint32_t a) {
    float4 v;
    asm volatile("ld.shared.v4.f32 {%0,%1,%2,%3}, [%4];" : "=f"(v.x), "=f"(v.y), "=f"(v.z), "=f"(v.w) : "r"(a) : "memory");
    return v;
}
DEVI uint4 lds128(uint32_t a) {
    uint4 v;
    asm volatile("ld.shared.v4.u32 {%0,%1,%2,%3}, [%4];" : "=r"(v.x), "=r"(v.y), "=r"(v.z), "=r"(v.w) : "r"(a) : "memory");
    return v;
}
DEVI uint2 lds64(uint32_t a) {
    uint2 v;
    asm volatile("ld.shared.v2.u32 {%0,%1}, [%2];" : "=r"(v.x), "=r"(v.y) : "r"(a) : "memory");
    return v;
}
DEVI uint32_t lds32(uint32_t a) {
    uint32_t v;
    asm volatile("ld.shared.u32 %0, [%1];" : "=r"(v) : "r"(a) : "memory");
    return v;
}
DEVI float ex2(float x) { float r; asm("ex2.approx.ftz.f32 %0, %1;" : "=f"(r) : "f"(x)); return r; }
DEVI float rcp(float x) { float r; asm("rcp.approx.ftz.f32 %0, %1;" : "=f"(r) : "f"(x)); return r; }
DEVI uint32_t clk() { uint32_t c; asm volatile("mov.u32 %0, %%clock;" : "=r"(c)::"memory"); return c; }

DEVI uint64_t mkdesc(uint32_t addr, uint32_t lbo, uint32_t sbo) {
    return (uint64_t)((addr & 0x3FFFF) >> 4) | ((uint64_t)(lbo >> 4) << 16) | ((uint64_t)(sbo >> 4) << 32) | ((uint64_t)1 << 62);
}
DEVI void wg_fence() { asm volatile("wgmma.fence.sync.aligned;" ::: "memory"); }
DEVI void wg_commit() { asm volatile("wgmma.commit_group.sync.aligned;" ::: "memory"); }
template <int N> DEVI void wg_wait() { asm volatile("wgmma.wait_group.sync.aligned %0;" ::"n"(N) : "memory"); }
template <int SC>
DEVI void wg_rs32(float (&d)[16], const uint32_t (&a)[4], uint64_t db) {
    if (SC) {
        asm volatile("wgmma.mma_async.sync.aligned.m64n32k16.f32.bf16.bf16 "
                     "{%0,%1,%2,%3,%4,%5,%6,%7,%8,%9,%10,%11,%12,%13,%14,%15}, {%16,%17,%18,%19}, %20, 1, 1, 1, 0;"
                     : "+f"(d[0]), "+f"(d[1]), "+f"(d[2]), "+f"(d[3]), "+f"(d[4]), "+f"(d[5]), "+f"(d[6]), "+f"(d[7]),
                       "+f"(d[8]), "+f"(d[9]), "+f"(d[10]), "+f"(d[11]), "+f"(d[12]), "+f"(d[13]), "+f"(d[14]), "+f"(d[15])
                     : "r"(a[0]), "r"(a[1]), "r"(a[2]), "r"(a[3]), "l"(db));
    } else {
        asm volatile("wgmma.mma_async.sync.aligned.m64n32k16.f32.bf16.bf16 "
                     "{%0,%1,%2,%3,%4,%5,%6,%7,%8,%9,%10,%11,%12,%13,%14,%15}, {%16,%17,%18,%19}, %20, 0, 1, 1, 0;"
                     : "=f"(d[0]), "=f"(d[1]), "=f"(d[2]), "=f"(d[3]), "=f"(d[4]), "=f"(d[5]), "=f"(d[6]), "=f"(d[7]),
                       "=f"(d[8]), "=f"(d[9]), "=f"(d[10]), "=f"(d[11]), "=f"(d[12]), "=f"(d[13]), "=f"(d[14]), "=f"(d[15])
                     : "r"(a[0]), "r"(a[1]), "r"(a[2]), "r"(a[3]), "l"(db));
    }
}

#define NA 12
#define NPF 6
#define PF1 2
#define PF2 2
#define PF3 4
#define WPF 2
#define VPF 2
#define VORD 0x01234567
#define VSF 0
#define VMF 0
#define VC 1
#define QP 16
#define W2P 0
#define W3P 1
#define QSP 12
#define VSB 0x10F
#define QQP 3
#define CGP 8
#define C0P 9
#define C1P 9
#define PIP 10
#define K0P 2
#define KEP 4
#define KE2 0
#define VTP 0
#define CW 1
#define WV_BOX ((16 - NA) * 2048)
#define WO_BOX 16384
#define SM_WV 0
#define SM_WO (2 * WV_BOX)
#define SM_X (SM_WO + 4 * WO_BOX)
#define SM_XO (SM_X + 32768)
#define SM_MEMT (SM_XO + 12288)
#define SM_OT (SM_MEMT + 4096)
#define SM_VS (SM_OT + 2048)
#define SM_P (SM_VS + 2048)
#define SM_DN (SM_P + 1792)
#define SM_PROF (SM_P + 2048)
#define SM_ST (SM_X + 65536)
#define SM_KV SM_ST
#define SM_SP (SM_KV + 18432)
#define SM_TR (SM_ST + 32768)
#define SM_PI (SM_ST + 65536)
#define SM_BAR (SM_PI + 12288)
#define SM_TOTAL (SM_BAR + 512)
static_assert(NA == 12, "start-up chunks");
static_assert(SM_TOTAL <= 232448, "smem");
#define BAR_XA 32
#define BAR_KV 40
#define BAR_PI 48
#define BAR_RO 64
#define BAR_WF 256
#define BAR_WE 384
#define SM_ROLE (SM_BAR + 72)

#define SPIN_LIMIT (1 << 20)
#define RPOS 26
#define OPOS 2
#define ASF 0
#define KPOS 0
#define CPOS 4
#define DLY_V 350
#define NPRB 2
#define PW 4
#define ZD 0
#define FTM 2
#define XPF 1
#define WOP 2
#define WIN 2
#define EPD 1300
#define ASP 4
#define EPF 0
#define CFAR 1

template <int ID, int N> DEVI void bsync() { asm volatile("bar.sync %0, %1;" ::"n"(ID), "n"(N) : "memory"); }
template <int ID, int N> DEVI void barv() { asm volatile("bar.arrive %0, %1;" ::"n"(ID), "n"(N) : "memory"); }

#define PT(n)
#define PC(n, v)
#define PDUMP()
#define REFRESH() asm volatile("xor.b32 %0, %0, %1;" : "+r"(l16) : "r"(zero))
#define OPQ(x) asm volatile("xor.b32 %0, %0, %1;" : "+r"(x) : "r"(zero))
#define KEEP(x, a, b, c, d) asm volatile("{\n.reg .b32 t;\nlop3.b32 t, %1, %2, %3, 0x80;\nlop3.b32 t, t, %4, %5, 0x80;\nxor.b32 %0, %0, t;\n}" \
                                         : "+r"(x) : "r"(a), "r"(b), "r"(c), "r"(d), "r"(zero))
#define SF() asm volatile("pmevent 1;" ::: "memory")
#define MF() __syncwarp()
#define SB0 1024u

#define XDOFF(ks) ((((ks) >> 2) * 1024 + ((ks) & 3) * 32) >> 4)
template <int SC>
DEVI void wg_ss32t(float (&d)[16], uint64_t da, uint64_t db) {
    if (SC) {
        asm volatile("wgmma.mma_async.sync.aligned.m64n32k16.f32.bf16.bf16 "
                     "{%0,%1,%2,%3,%4,%5,%6,%7,%8,%9,%10,%11,%12,%13,%14,%15}, %16, %17, 1, 1, 1, 1, 0;"
                     : "+f"(d[0]), "+f"(d[1]), "+f"(d[2]), "+f"(d[3]), "+f"(d[4]), "+f"(d[5]), "+f"(d[6]), "+f"(d[7]),
                       "+f"(d[8]), "+f"(d[9]), "+f"(d[10]), "+f"(d[11]), "+f"(d[12]), "+f"(d[13]), "+f"(d[14]), "+f"(d[15])
                     : "l"(da), "l"(db));
    } else {
        asm volatile("wgmma.mma_async.sync.aligned.m64n32k16.f32.bf16.bf16 "
                     "{%0,%1,%2,%3,%4,%5,%6,%7,%8,%9,%10,%11,%12,%13,%14,%15}, %16, %17, 0, 1, 1, 1, 0;"
                     : "=f"(d[0]), "=f"(d[1]), "=f"(d[2]), "=f"(d[3]), "=f"(d[4]), "=f"(d[5]), "=f"(d[6]), "=f"(d[7]),
                       "=f"(d[8]), "=f"(d[9]), "=f"(d[10]), "=f"(d[11]), "=f"(d[12]), "=f"(d[13]), "=f"(d[14]), "=f"(d[15])
                     : "l"(da), "l"(db));
    }
}

DEVI void delay_until(uint32_t t0, uint32_t d) { while (clk() - t0 < d) {} }

#define VR 2
#define CW2 4
template <int I0, int I1>
DEVI void xmma(float (&xa)[16], float (&xb)[16], uint32_t w, int ps, uint32_t zero, const uint32_t (&Wq)[16][4], const uint32_t (&Wk)[16][4],
               const uint32_t (&Wv)[NA][4], const uint32_t (&wv)[16 - NA][4]) {
    const uint64_t xd = mkdesc(SB0 + SM_X, 16, 4096) + (ps & 1) * 1024, vd = mkdesc(SB0 + SM_WV, 8192, 1024);
    uint32_t vo = (w >> 2) * (WV_BOX / 16);
    if (VR ? false : VC == 0 ? I0 < 16 - NA : VC == 1 ? I0 >= 32 && I0 < 48 - NA : I1 > 32 + NA) OPQ(vo);
#pragma unroll
    for (int i = I0; i < I1; i++) {
        if (VC) {
            const int v = (i + (VC == 1 ? NA : 0)) & 15;
            if (i == 0) wg_rs32<0>(xa, Wq[0], xd);
            else if (i < 16) wg_rs32<1>(xa, Wq[i & 15], xd + XDOFF(i & 15));
            else if (i == 16) wg_rs32<0>(xb, Wk[0], xd);
            else if (i < 32) wg_rs32<1>(xb, Wk[i & 15], xd + XDOFF(i & 15));
            else if (i == 32 && v < NA) wg_rs32<0>(xa, Wv[0], xd);
            else if (VR && i == 32) wg_rs32<0>(xa, wv[0], xd + XDOFF(NA));
            else if (VR && v >= NA) wg_rs32<1>(xa, wv[v >= NA ? v - NA : 0], xd + XDOFF(v));
            else if (i == 32) wg_ss32t<0>(xa, (vd & ~0xFFFFFFFFull) | ((uint32_t)vd + vo), xd + XDOFF(NA));
            else if (v < NA) wg_rs32<1>(xa, Wv[v < NA ? v : 0], xd + XDOFF(v));
            else wg_ss32t<1>(xa, (vd & ~0xFFFFFFFFull) | ((uint32_t)vd + (v - NA) * 128 + vo), xd + XDOFF(v));
        } else
        if (i == 0) wg_ss32t<0>(xb, (vd & ~0xFFFFFFFFull) | ((uint32_t)vd + vo), xd + XDOFF(NA));
        else if (i < 16 - NA) wg_ss32t<1>(xb, (vd & ~0xFFFFFFFFull) | ((uint32_t)vd + i * 128 + vo), xd + XDOFF(NA + i));
        else if (i == 16 - NA) wg_rs32<0>(xa, Wq[0], xd);
        else if (i < 32 - NA) wg_rs32<1>(xa, Wq[(i + NA) & 15], xd + XDOFF((i + NA) & 15));
        else if (i < 32) wg_rs32<1>(xb, Wv[(i + NA) & 15], xd + XDOFF((i + NA) & 15));
        else if (i == 32) wg_rs32<0>(xa, Wk[0], xd);
        else wg_rs32<1>(xa, Wk[i & 15], xd + XDOFF(i & 15));
    }
    wg_commit();
}
#define XMMA(I0, I1) xmma<(I0), (I1)>(xa, xb, w, p ^ 1, zero, Wq, Wk, Wv, wv)
DEVI void wg_done(float (&d)[16]) {
    asm volatile("" : "+f"(d[0]), "+f"(d[1]), "+f"(d[2]), "+f"(d[3]), "+f"(d[4]), "+f"(d[5]), "+f"(d[6]), "+f"(d[7]),
                      "+f"(d[8]), "+f"(d[9]), "+f"(d[10]), "+f"(d[11]), "+f"(d[12]), "+f"(d[13]), "+f"(d[14]), "+f"(d[15]) :: "memory");
}
template <int M>
DEVI void xpack(uint32_t (&xp)[8], float (&xa)[16]) {
    wg_done(xa);
#pragma unroll
    for (int i = 0; i < 4; i++) {
        xp[2 * i] = pack2(xa[4 * i], xa[4 * i + (M < 2 ? 2 : 1)]);
        xp[2 * i + 1] = pack2(xa[4 * i + (M < 2 ? 1 : 2)], xa[4 * i + 3]);
    }
}
template <int M>
DEVI uint4 xpeer(uint32_t sb, int ps, uint32_t t16) { return lds128(sb + SM_PI - ((ps & 1) ^ 1) * 12288 + M * 4096 + t16); }
DEVI void xadd(uint32_t (&xp)[8], const uint4& pi) {
    xp[0] = hadd2(xp[0], pi.x); xp[1] = hadd2(xp[1], pi.y); xp[2] = hadd2(xp[2], pi.z); xp[3] = hadd2(xp[3], pi.w);
}
template <int M>
DEVI void xsend(const uint32_t (&xp)[8], uint32_t sb, int ps, uint32_t t16) {
    asm volatile("st.async.weak.shared::cluster.mbarrier::complete_tx::bytes.v4.b32 [%0], {%1,%2,%3,%4}, [%5];"
                 ::"r"((sb ^ 0x1000000) + SM_PI - (ps & 1) * 12288 + M * 4096 + t16), "r"(xp[4]), "r"(xp[5]), "r"(xp[6]), "r"(xp[7]),
                   "r"((sb ^ 0x1000000) + SM_BAR + BAR_PI + (ps & 1) * 8) : "memory");
}
template <int M>
DEVI void xstore(const uint32_t (&xp)[8], uint32_t sb, uint32_t sbw, int ps, uint32_t t16, uint32_t KA) {
    const uint32_t a = SM_XO + M * 2048 + (M < 2 ? (KA & 0xFF) + sbw : (t16 >> 1) + sb);
    sts64(a, xp[0], xp[1]);
    sts64(a + 6144, xp[2], xp[3]);
    xsend<M>(xp, sb, ps, t16);
}
template <int M>
DEVI void xpark(uint32_t (&xp)[8], const uint4& pi, uint32_t sb, uint32_t sbw, int ps, uint32_t t16, uint32_t KA) {
    xadd(xp, pi);
    xstore<M>(xp, sb, sbw, ps, t16, KA);
}
template <uint32_t OFF> DEVI void red2(uint32_t lo, uint32_t hi, uint32_t a, uint32_t b) {
    asm volatile("{\n.reg .b64 a;\nmov.b64 a, {%0,%1};\nred.relaxed.gpu.global.add.noftz.v2.bf16x2 [a+%4], {%2,%3};\n}"
                 ::"r"(lo), "r"(hi), "r"(a), "r"(b), "n"(OFF) : "memory");
}
template <int M, int N>
DEVI void xstart(uint32_t sb, uint32_t w, uint32_t ga, uint32_t xhi, uint32_t j, uint32_t t16, uint32_t KA, const uint32_t (&W)[N][4]) {
    float xa[16], xb[16];
    uint32_t xp[8];
    auto pass = [&](float (&d)[16], int i, int k0, int k1) {
        const uint64_t xd = mkdesc(SB0 + SM_X + (i ? i + 1 : 0) * 16384, 16, 4096), vd = mkdesc(SB0 + SM_WV, 8192, 1024) + (w >> 2) * (WV_BOX / 16);
#pragma unroll
        for (int k = k0; k < k1; k++) {
            if (k == 0) wg_rs32<0>(d, W[0], xd);
            else if (k < N) wg_rs32<1>(d, W[k < N ? k : 0], xd + XDOFF(k));
            else wg_ss32t<1>(d, vd + (k - N) * 128, xd + XDOFF(k));
        }
        wg_commit();
    };
    wg_fence();
    pass(xa, 0, 0, 16);
    pass(xb, 1, 0, ASP);
    if (M == 0) bsync<5, 288>();
    ga += M < 2 ? (KA & 0xFF) + w * 256 : t16 >> 1;
    constexpr uint32_t O = XO_XG + M * 2048, SG = 128 * 6144;
    wg_wait<1>();
    xpack<M>(xp, xa);
    red2<O>(ga, xhi, xp[0], xp[1]); red2<O + 6144>(ga, xhi, xp[2], xp[3]); red2<O + 12288>(ga, xhi, xp[4], xp[5]); red2<O + 18432>(ga, xhi, xp[6], xp[7]);
    if (M == 2) barv<3, 320>();
    wg_fence();
    pass(xb, 1, ASP, 16);
    pass(xa, 2, 0, 16);
    wg_wait<1>();
    xpack<M>(xp, xb);
    red2<O + SG>(ga, xhi, xp[0], xp[1]); red2<O + SG + 6144>(ga, xhi, xp[2], xp[3]);
    red2<O + SG + 12288>(ga, xhi, xp[4], xp[5]); red2<O + SG + 18432>(ga, xhi, xp[6], xp[7]);
    wg_wait<0>();
    xpack<M>(xp, xa);
    red2<O + 2 * SG>(ga + j * 6144, xhi, xp[0], xp[1]);
    red2<O + 2 * SG>(ga + (j ^ 1) * 6144, xhi, xp[2], xp[3]);
    xsend<M>(xp, sb, 0, t16);
}
DEVI void piwait(uint32_t sb, int p, int ps) { mbar_wait(sb + SM_BAR + BAR_PI + p * 8, ((ps + 2) >> 1) & 1); }

DEVI uint32_t par(uint32_t off) { return __popc(off & 0xB2000u) & 1; }
DEVI uint32_t probe(uint32_t lo, uint32_t hi) {
    uint32_t best = 0xFFFFFFFFu, x = 0;
    stg4<0>(lo, hi, 0, 0, 0, 0);
    stg4<16>(lo, hi, 0, 0, 0, 0);
#pragma unroll 1
    for (int r = 0; r < NPRB; r++) {
        const uint32_t t0 = clk();
        asm volatile("{\n.reg .b64 a;\nmov.b64 a, {%1,%2};\natom.relaxed.gpu.global.add.u32 %0, [a], 2;\n}" : "=r"(x) : "r"(lo), "r"(hi) : "memory");
        if (x == 0xFFFFFFFFu) die(1 << 23);
        best = min(best, clk() - t0);
    }
    return best;
}

DEVI void xload(uint32_t sb, uint32_t u, uint32_t j, int ps, const CUtensorMap* tmx) {
    if (elect()) {
        const uint32_t sg = ps + 4 - (u & 1) + (u >> 1);
        mbar_expect(sb + SM_BAR + BAR_XA, sg < NSEG ? 4096 : 0);
        if (sg < NSEG) tma3d(sb + SM_X + (ps & 1) * 16384 + u * 4096, tmx, sb + SM_BAR + BAR_XA, 0, sg * 32 + (j ^ ((u & 1) * 2 + (u >> 1))) * 8, j * 4);
    }
}
DEVI uint32_t rpage(uint32_t j, int s) { return (s & 3) * 65536 + (j & 1) * 8192 + (((s ^ (s >> 1) ^ j ^ (j >> 1)) & 1) << 12); }

#define RLOAD() { m0 = ldg4<XO_R>(a, ah); n0 = ldg4<XO_R + 16384>(a, ah); e0 = ldg1<XO_R + 32768>(e, eh); f0 = ldg1<XO_R + 33792>(e, eh); }
DEVI bool ruse(uint32_t a, const uint4& m0, const uint4& n0, uint32_t e0, uint32_t f0) {
    const uint32_t a0 = hadd2(m0.w, n0.w), b0 = hadd2(e0, f0);
    stsm4(a, hadd2(m0.x, n0.x), hadd2(m0.y, n0.y), hadd2(m0.z, n0.z), __byte_perm(a0, b0, 0x5410));
    return __any_sync(0xFFFFFFFFu, (a0 & b0 & 0x42000000u) != 0x42000000u);
}

#define GST(i) (SM_WO + (i) * 49152)
#define BAR_GF 128
#define BAR_GE (BAR_GF + 64)
#define BAR_GX (BAR_GE + 32)
#define D4(c, i) #c "f"(d[i]), #c "f"(d[i + 1]), #c "f"(d[i + 2]), #c "f"(d[i + 3])
#define D16(c, i) D4(c, i), D4(c, i + 4), D4(c, i + 8), D4(c, i + 12)
DEVI void mwait(uint32_t bar, uint32_t parity) {
    asm volatile("{\n.reg .pred p;\n.reg .b32 c;\nmbarrier.try_wait.parity.shared::cta.b64 p, [%0], %1;\n@p bra.uni D;\nmov.b32 c, 0;\n"
                 "L:\nadd.u32 c, c, 1;\nsetp.gt.u32 p, c, 4194304;\n@p st.shared.u32 [c], c;\n"
                 "mbarrier.try_wait.parity.shared::cta.b64 p, [%0], %1;\n@!p bra.uni L;\nD:\n}" ::"r"(bar), "r"(parity) : "memory");
}
DEVI void wg_ss256t(float (&d)[128], uint64_t da, uint64_t db) {
    asm volatile("wgmma.mma_async.sync.aligned.m64n256k16.f32.bf16.bf16 "
        "{%0,%1,%2,%3,%4,%5,%6,%7,%8,%9,%10,%11,%12,%13,%14,%15,%16,%17,%18,%19,%20,%21,%22,%23,%24,%25,%26,%27,%28,%29,%30,%31,%32,%33,%34,%35,%36,%37,%38,%39,%40,%41,%42,%43,%44,%45,%46,%47,%48,%49,%50,%51,%52,%53,%54,%55,%56,%57,%58,%59,%60,%61,%62,%63,%64,%65,%66,%67,%68,%69,%70,%71,%72,%73,%74,%75,%76,%77,%78,%79,%80,%81,%82,%83,%84,%85,%86,%87,%88,%89,%90,%91,%92,%93,%94,%95,%96,%97,%98,%99,%100,%101,%102,%103,%104,%105,%106,%107,%108,%109,%110,%111,%112,%113,%114,%115,%116,%117,%118,%119,%120,%121,%122,%123,%124,%125,%126,%127}, "
        "%128, %129, 1, 1, 1, 1, 1;"
        : D16(+, 0), D16(+, 16), D16(+, 32), D16(+, 48), D16(+, 64), D16(+, 80), D16(+, 96), D16(+, 112) : "l"(da), "l"(db));
}
template <int O, int KB> DEVI void g_half(float (&d)[64], uint64_t da) {
    const uint64_t db = mkdesc(SB0 + GST(KB & 3) + 16384 + O * 256, 8192, 1024);
#pragma unroll
    for (int k = 0; k < 4; k++)
        asm volatile("wgmma.mma_async.sync.aligned.m64n128k16.f32.bf16.bf16 "
            "{%0,%1,%2,%3,%4,%5,%6,%7,%8,%9,%10,%11,%12,%13,%14,%15,%16,%17,%18,%19,%20,%21,%22,%23,%24,%25,%26,%27,%28,%29,%30,%31,%32,%33,%34,%35,%36,%37,%38,%39,%40,%41,%42,%43,%44,%45,%46,%47,%48,%49,%50,%51,%52,%53,%54,%55,%56,%57,%58,%59,%60,%61,%62,%63}, "
            "%64, %65, 1, 1, 1, 1, 1;"
            : D16(+, 0), D16(+, 16), D16(+, 32), D16(+, 48) : "l"(da + (KB & 3) * 3072 + k * 16), "l"(db + k * 128));
}
DEVI void g_load(uint32_t sb, uint32_t u, uint32_t role, uint32_t kb, uint32_t xlo, uint32_t xhi, const CUtensorMap* tmb) {
    const uint32_t st = kb & 3, bar = sb + SM_BAR + BAR_GF + u * 32 + st * 8, dst = sb + GST(st), k = (role & 1) * 32 + kb;
    if (!elect()) return;
    mbar_expect(bar, u ? 8192 : 40960);
    bulk_g2s(dst + u * 8192, xlo + XO_OX + (k * 16 + (role >> 3)) * 16384 + u * 8192, xhi, 8192, bar);
    if (u == 0) {
        tma3d(dst + 16384, tmb, bar, 0, k * 64, ((role & 7) ^ 1) * 2);
        tma3d(dst + 32768, tmb, bar, 0, k * 64, (role & 7) * 2);
    }
}
DEVI void g_arrive(uint32_t a, uint32_t xhi, uint32_t n) {
    if (elect()) asm volatile("{\n.reg .b64 a;\nmov.b64 a, {%0,%1};\nred.release.gpu.global.inc.u32 [a], %2;\n}" ::"r"(a), "r"(xhi), "r"(n - 1) : "memory");
}
DEVI void g_wait(uint32_t a, uint32_t xhi) {
    int it = 0;
    uint32_t v;
    do {
        asm volatile("{\n.reg .b64 a;\nmov.b64 a, {%1,%2};\nld.acquire.gpu.global.u32 %0, [a];\n}" : "=r"(v) : "r"(a), "r"(xhi) : "memory");
        if (++it > SPIN_LIMIT) die(it);
    } while (__any_sync(0xFFFFFFFFu, v));
    asm volatile("fence.proxy.async.global;" ::: "memory");
}
#define SE 2
#define DLY_S 0
#define VX 1
#define VH 1
#define VD 1
#define SM_VP (SM_TR + 12288)
#define JV(h, j) (VH < 2 ? (j) ^ ((par((h) * 8192) ^ VH) << 1) : (j))
#define SEU 0
#define VA 0
#define VLP 0
#define VCP 1
#define SEED 0
#define VB 0
#define RCP 0
#define XLP 0
#define RE 0
#define DLY_E 300
#define DLY_T 200
#define RDW 0
#define APH 0
#define B3 0
#define GD 400
#define GE 3
#define GH 1
#define GS 1
#define GP 0
DEVI void g_done(float (&d)[64]) { asm volatile("" : D16(+, 0), D16(+, 16), D16(+, 32), D16(+, 48)::"memory"); }
DEVI void g_main(uint32_t sb, uint32_t w, uint32_t role, const CUtensorMap* tmy, void* out) {
    const uint32_t bar = sb + SM_BAR, t16 = threadIdx.x * 16;
    const uint64_t da = (mkdesc(SB0 + GST(0), 128, 1024) & ~((uint64_t)3 << 62)) + (w >> 2) * 512;
    float d[128];
#pragma unroll
    for (int i = 0; i < 128; i++) d[i] = 0.f;
#define GFULL(kb) { mwait(bar + BAR_GF + ((kb) & 3) * 8, ((kb) >> 2) & 1); if (w >= 4) mwait(bar + BAR_GF + 32 + ((kb) & 3) * 8, ((kb) >> 2) & 1); }
#pragma unroll 1
    for (uint32_t kb = 0; kb < (GE ? 28 : 29); kb++) {
        GFULL(kb);
        if (kb == 0 && threadIdx.x == 128) PG(4);
        if (kb == 4 && threadIdx.x == 0) PG(5);
        const uint64_t a = da + (kb & 3) * 3072, b = mkdesc(SB0 + GST(0) + 16384, 8192, 1024) + (kb & 3) * 3072;
        wg_fence();
#pragma unroll
        for (int k = 0; k < 4; k++) wg_ss256t(d, a + k * 16, b + k * 128);
        wg_commit();
        wg_wait<1>();
        if (kb > 0 && elect()) mbar_arrive(bar + BAR_GE + ((kb - 1) & 3) * 8);
    }
    if (GE) { GFULL(28); }
    else { GFULL(29); GFULL(30); GFULL(31); }
    wg_wait<0>();
    if (GE && elect()) mbar_arrive(bar + BAR_GE + 24);
    float x[64], y[64];
#pragma unroll
    for (int i = 0; i < 64; i++) asm volatile("mov.b32 %0, %1;" : "=f"(x[i]) : "f"(d[i]) : "memory");
    SF();
#pragma unroll
    for (int i = 0; i < 64; i++) asm volatile("mov.b32 %0, %1;" : "=f"(y[i]) : "f"(d[i + 64]) : "memory");
    SF();
#define GFREE() if (elect()) asm volatile("mbarrier.arrive.relaxed.cluster.shared::cluster.b64 _, [%0];" ::"r"((bar ^ 0x1000000) + BAR_GX) : "memory")
#define GSW(i) ((i) * 4096 + (GE && (i) >= 4 ? GST(0) : 0))
#define GSEND(i0) _Pragma("unroll") for (int i = (i0); i < (i0) + 4; i++) \
        asm volatile("st.async.weak.shared::cluster.mbarrier::complete_tx::bytes.v4.b32 [%0], {%1,%2,%3,%4}, [%5];" \
                     ::"r"((sb ^ 0x1000000) + GSW(i) + t16), "r"(pack2(x[8 * i], x[8 * i + 1])), "r"(pack2(x[8 * i + 2], x[8 * i + 3])), \
                       "r"(pack2(x[8 * i + 4], x[8 * i + 5])), "r"(pack2(x[8 * i + 6], x[8 * i + 7])), "r"((bar ^ 0x1000000) + BAR_GX + 8) : "memory")
    if (GE) {
        wg_fence();
        g_half<0, 28>(x, da);
        wg_commit();
        GFULL(29);
        wg_fence();
        g_half<0, 29>(x, da);
        wg_commit();
        GFULL(30);
        wg_fence();
        g_half<0, 30>(x, da);
        wg_commit();
        GFULL(31);
        wg_fence();
        g_half<0, 31>(x, da);
        wg_commit();
        g_half<64, 28>(y, da);
        if (GE == 2) g_half<64, 29>(y, da);
        wg_commit();
        wg_wait<1>();
        g_done(x);
        GFREE();
        GSEND(0);
        wg_fence();
        if (GE != 2) g_half<64, 29>(y, da);
        if (GE != 1) g_half<64, 30>(y, da);
        wg_commit();
        mwait(bar + BAR_GX, 0);
        GSEND(4);
        wg_fence();
        if (GE == 1) g_half<64, 30>(y, da);
        g_half<64, 31>(y, da);
        wg_commit();
        mwait(bar + BAR_GX + 8, 0);
        if (threadIdx.x == 0) PG(1);
#pragma unroll
        for (int i = 0; i < 8; i++) {
            const uint4 a = lds128(sb + GSW(i) + t16);
            float* e = x + 8 * i;
            e[0] = lo_f(a.x); e[1] = hi_f(a.x); e[2] = lo_f(a.y); e[3] = hi_f(a.y); e[4] = lo_f(a.z); e[5] = hi_f(a.z); e[6] = lo_f(a.w); e[7] = hi_f(a.w);
        }
        g_done(x);
        SF();
        wg_wait<0>();
        g_done(y);
        if (threadIdx.x == 0) PG(7);
    } else {
        GFREE();
        wg_fence();
        g_half<0, 29>(x, da);
        g_half<0, 30>(x, da);
        g_half<0, 31>(x, da);
        wg_commit();
        g_half<64, 29>(y, da);
        wg_commit();
        wg_wait<1>();
        g_done(x);
        mwait(bar + BAR_GX, 0);
        GSEND(0);
        wg_fence();
        g_half<64, 30>(y, da);
        wg_commit();
        GSEND(4);
        wg_fence();
        g_half<64, 31>(y, da);
        wg_commit();
        wg_wait<0>();
        g_done(y);
        if (threadIdx.x == 0) PG(7);
        mwait(bar + BAR_GX + 8, 0);
        if (threadIdx.x == 0) PG(1);
    }
    const uint32_t lane = threadIdx.x & 31, o = sb + GST(1) + w * 2048;
    char* go = (char*)out + ((role >> 3) * 128 + w * 16 + (lane >> 3)) * 4096 + (role & 7) * 256 + (lane & 7) * 16;
#pragma unroll
    for (int i = 0; i < 8; i++) {
        float* e = y + 8 * i;
        if (GE) {
#pragma unroll
            for (int n = 0; n < 8; n++) e[n] += x[8 * i + n];
        } else {
            const uint4 a = lds128(sb + i * 4096 + t16);
            e[0] += lo_f(a.x); e[1] += hi_f(a.x); e[2] += lo_f(a.y); e[3] += hi_f(a.y); e[4] += lo_f(a.z); e[5] += hi_f(a.z); e[6] += lo_f(a.w); e[7] += hi_f(a.w);
        }
        stsm4(o + (i >> 2) * 49152 + (lane & 15) * 128 + ((((i & 3) * 2 + (lane >> 4)) ^ (lane & 7)) << 4),
              pack2(e[0], e[1]), pack2(e[2], e[3]), pack2(e[4], e[5]), pack2(e[6], e[7]));
        if (i == 3 || i == 7) {
            if (GS) {
                __syncwarp();
#pragma unroll
                for (int m = 0; m < 4; m++)
                    *(uint4*)(go + m * 16384 + (i >> 2) * 128) =
                        lds128(o + (i >> 2) * 49152 + m * 512 + (lane >> 3) * 128 + (((lane & 7) ^ ((m & 1) * 4 + (lane >> 3))) << 4));
            } else {
                asm volatile("fence.proxy.async.shared::cta;" ::: "memory");
                __syncwarp();
                if (elect())
                    asm volatile("cp.async.bulk.tensor.2d.global.shared::cta.bulk_group [%0, {%2, %3}], [%1];\ncp.async.bulk.commit_group;"
                                 ::"l"(tmy), "r"(o + (i >> 2) * 49152), "r"((role & 7) * 128 + (i >> 2) * 64), "r"((role >> 3) * 128 + w * 16) : "memory");
            }
        }
    }
    if (threadIdx.x == 0) PG(6);
    if (!GS) asm volatile("cp.async.bulk.wait_group.read 0;" ::: "memory");
}

DEVI void kvload(uint32_t sb, uint32_t u, uint32_t h, uint32_t j, int sg, uint32_t xlo, uint32_t xhi) {
    const uint32_t o = u == 0 ? 0 : 2048;
    mbar_expect(sb + SM_BAR + BAR_KV, 6144 - o);
    bulk_g2s(sb + SM_KV + u * 4096 + o, xlo + XO_XG + (((sg & 7) * 32 + h) * 4 + ((j + u) & 3)) * 6144 + o, xhi, 6144 - o, sb + SM_BAR + BAR_KV);
}
DEVI void helper_step(uint32_t sb, uint32_t w, uint32_t h, uint32_t j, uint32_t& l16, uint32_t xlo, uint32_t xhi, uint32_t zero, int s,
                      const CUtensorMap* tmx, const CUtensorMap* tmb) {
    const uint32_t u = w - 8, bq = sb + SM_BAR;
    bsync<1, 384>();
    PT(0);
    PDUMP();
    PT(1);
    if (s == NSEG - 2 && u < 2) g_arrive(xlo + XO_TK + 128, xhi, 256);
    uint32_t old = 0;
#define RCLEAR(n) if (RCP == (n) && u > 0 && s + 3 < NSEG) \
        asm volatile("{\n.reg .b64 a;\nmov.b64 a, {%1,%2};\natom.relaxed.gpu.global.exch.b32 %0, [a], 0;\n}" \
                     : "=r"(old) : "r"(xlo + XO_R + rpage(j, s + 2) + (u - 1) * 16384 + h * 128 + (l16 >> 2)), "r"(xhi) : "memory");
    RCLEAR(1);
    const bool gl = u == 0 || (u == 1 && h < 30);
    if (GP == 1 && s == NSEG - 1 && gl) g_load(sb, u, h * 4 + j, 1, xlo, xhi, tmb);
    const uint32_t ctag = ((s >> 1) & 1) ^ 1;
    const uint32_t av = xlo + ((s & 1) * 32 + h) * 8192 + u * 512;
    mbar_wait(bq + BAR_XA, (s + 1) & 1);
    if (B3 == 8) barv<5, 384>();
    bsync<8, 384>();
    const uint32_t t8 = clk(), gs = xlo + XO_XG + ((((s + 3) & 7) * 32 + h) * 4 + j) * 6144;
    RCLEAR(2);
    const bool se = B3 % 8 == 0 && SE && u == SEU && s + 3 < NSEG;
    uint32_t tv = ctag ^ 1, ro = 0;
    if (se) {
        asm volatile("fence.proxy.async.shared::cta;" ::: "memory");
        if (SE == 4) delay_until(t8, DLY_E);
        if ((SE == 1 || SE == 4) && elect()) bulk_s2g(gs, xhi, sb + SM_XO, 4096);
    } else if (RE && u == 1 && s + 2 < NSEG) {
        asm volatile("fence.proxy.async.shared::cta;" ::: "memory");
        const uint32_t cb0 = (h >> 1) * 32768 + (j & 1) * 16384 + (h & 1) * 8192;
        delay_until(t8, DLY_T);
        tv = ldg1<XO_CQK>((xlo + cb0 + ((par(cb0) ^ (j >> 1) ^ CFAR ^ 1) << 12)) ^ ((s & 1) * 0x81000), xhi);
        SF();
    }
    if (B3 != 6 || u || SE == 2) delay_until(t8, DLY_V);
    if (se && SE == 2 && elect()) bulk_s2g(gs, xhi, sb + SM_XO, 4096);
    PT(4);
    int it = 0;
    uint4 d1, d2, d3;
    uint2 e1, e2, e3;
    const uint32_t ae = av - u * 512 + (u & 1) * 256;
    const uint32_t jv = JV(h, j);
#define VLOAD() { if (!VD) d1 = ldg4<XO_CV>(av + (jv ^ 1) * 2048 + l16, xhi); \
        d2 = ldg4<XO_CV>(av + (jv ^ 2) * 2048 + l16, xhi); d3 = ldg4<XO_CV>(av + (jv ^ 3) * 2048 + l16, xhi); \
        if (B3 == 6 && VX) { if (!VD) e1 = ldg2<XO_CV>(ae + (jv ^ 1) * 2048 + (l16 >> 1), xhi); \
                       e2 = ldg2<XO_CV>(ae + (jv ^ 2) * 2048 + (l16 >> 1), xhi); e3 = ldg2<XO_CV>(ae + (jv ^ 3) * 2048 + (l16 >> 1), xhi); } \
        if (VD) { d1 = lds128(sb + SM_VP + (s & 1) * 2048 + u * 512 + l16); \
                  if (B3 == 6 && VX) e1 = lds64(sb + SM_VP + (s & 1) * 2048 + (u & 1) * 256 + (l16 >> 1)); } }
#define XSEND(F, C) if (u < 2) { \
        if (F) asm volatile("fence.proxy.async.shared::cta;" ::: "memory"); \
        if ((C) && elect()) { \
            const uint32_t sg = s + 3 - u; \
            if (sg < NSEG) { \
                const uint32_t ga = xlo + XO_XG + (((sg & 7) * 32 + h) * 4 + (j ^ (2 * u))) * 6144, sa = sb + SM_XO + u * 6144; \
                if (u == 0) bulk_s2g(ga + (SE ? 4096 : 0), xhi, sa + (SE ? 4096 : 0), SE ? 2048 : 6144); \
                else bulk_red(ga + ro, xhi, sa + ro, 6144 - ro); \
            } \
        } \
    }
    if (B3 == 8) {
        bsync<3, 384>();
        if (DLY_S) delay_until(clk(), DLY_S);
        XSEND(true, true);
    } else if (B3 == 6 && u == 0) {
        const uint32_t ga = xlo + XO_XG + ((((s + 3) & 7) * 32 + h) * 4 + j) * 6144, o = SE == 1 || SE == 2 ? 4096 : 0;
        if (o) {
            asm volatile("fence.proxy.async.shared::cta;" ::: "memory");
            if (s + 3 < NSEG && elect()) bulk_s2g(ga, xhi, sb + SM_XO, o);
        }
        bsync<3, 288>();
        if (DLY_S) delay_until(clk(), DLY_S);
        asm volatile("fence.proxy.async.shared::cta;" ::: "memory");
        if (elect()) {
            if (SE == 3 && s + 3 < NSEG) bulk_s2g(ga + o, xhi, sb + SM_XO + o, 6144 - o);
            if (s + 2 < NSEG) bulk_red(xlo + XO_XG + ((((s + 2) & 7) * 32 + h) * 4 + (j ^ 2)) * 6144, xhi, sb + SM_XO + 6144, 6144);
            if (SE != 3 && s + 3 < NSEG) bulk_s2g(ga + o, xhi, sb + SM_XO + o, 6144 - o);
        }
    } else {
    if (B3 == 6) VLOAD();
    if (B3 && B3 < 6) {
        VLOAD();
        bsync<B3 == 2 ? 4 : 3, 384>();
        XSEND(true, B3 < 3 || B3 == 5 || (B3 == 4 && u == 0));
    }
    while (true) {
        if (B3 % 7 == 0) VLOAD();
        if (RE && it == 0) {
            SF();
            if (!any_bad(tv ^ ctag)) {
                if (elect()) bulk_red(xlo + XO_XG + ((((s + 2) & 7) * 32 + h) * 4 + (j ^ 2)) * 6144, xhi, sb + SM_XO + 6144, 4096);
                ro = 4096;
            }
        }
        if (se && SE == 3 && it == 0 && elect()) bulk_s2g(gs, xhi, sb + SM_XO, 4096);
        uint32_t tg = or3(tagx2(d1.x, d1.z, ctag), tagx2(d2.x, d2.z, ctag), tagx2(d3.x, d3.z, ctag));
        if (B3 == 6 && VX) tg = or3(tg, tagx2(e1.x, e2.x, ctag), e3.x ^ ctag);
        const bool bad = any_bad(tg);
        if (B3 == 6 && VX) sts64(sb + SM_VS + (u & 1) * 256 + (l16 >> 1), hadd2(hadd2(e1.x, e2.x), e3.x), hadd2(hadd2(e1.y, e2.y), e3.y));
        sts128(sb + SM_VS + u * 512 + l16, hadd2(hadd2(d1.x, d2.x), d3.x), hadd2(hadd2(d1.y, d2.y), d3.y), hadd2(hadd2(d1.z, d2.z), d3.z),
               hadd2(hadd2(d1.w, d2.w), d3.w));
        if (VA) asm volatile("{\n.reg .pred p;\nsetp.eq.u32 p, %0, 0;\n@p bar.arrive 5, 384;\n}" ::"r"((uint32_t)bad) : "memory");
        if (B3 % 7 == 0) REFRESH();
        if (!bad) break;
        if (B3 % 7) { REFRESH(); VLOAD(); }
        if (++it > SPIN_LIMIT) die(it);
    }
    PC(26, it);
    PT(5);
    if (VB) barv<11, 384>();
    else if (!VA) barv<5, B3 == 6 ? 352 : 384>();
    }
    if (B3 % 7 == 0) {
        bsync<3, 384>();
        XSEND(true, true);
    }
    if (B3 == 3 || B3 == 4) XSEND(false, B3 == 3 || u == 1);
    PT(6);
    RCLEAR(0);
    PT(7);
    bsync<7, 384>();
    if (s + 1 < NSEG && elect()) kvload(sb, u, h, j, s + 1, xlo, xhi);
    RCLEAR(3);
    if (XLP == 1) xload(sb, u, j, s + 1, tmx);
    if (u < (B3 == 6 ? 1 : 2)) {
        asm volatile("cp.async.bulk.wait_group.read 0;" ::: "memory");
        if (elect()) {
            mbar_expect(bq + BAR_PI + ((s & 1) ^ 1) * 8, 6144);
            if (B3 == 6) mbar_expect(bq + BAR_PI + ((s & 1) ^ 1) * 8, 6144);
        }
    }
    PT(8);
    if (GP && s == NSEG - 2 && gl) g_wait(xlo + XO_TK + 128, xhi);
    if (s + 1 < NSEG) bsync<10, 384>();
    if (XLP == 0) xload(sb, u, j, s + 1, tmx);
    RCLEAR(4);
    if (s == NSEG - 2 && gl) {
        if (!GP) g_wait(xlo + XO_TK + 128, xhi);
        g_load(sb, u, h * 4 + j, 0, xlo, xhi, tmb);
        if (GP == 0 || GP == 3) g_load(sb, u, h * 4 + j, 1, xlo, xhi, tmb);
    }
    asm volatile("cp.async.bulk.wait_group 0;" ::: "memory");
    if (s + 1 < NSEG) mbar_wait(bq + BAR_KV, (s + 1) & 1);
    asm volatile("lop3.b32 %0, %0, %1, %2, 0x78;" : "+r"(l16) : "r"(old), "r"(zero));
    PT(15);
}
DEVI void tickets_done(uint32_t* tk) {
    if (atomicInc(tk + 2, gridDim.x / 2 - 64) == gridDim.x / 2 - 64) { tk[0] = 0; tk[1] = 0; }
}

__global__ void __cluster_dims__(2, 1, 1) __launch_bounds__(384, 1)
chain_kernel(const __grid_constant__ CUtensorMap tmq, const __grid_constant__ CUtensorMap tmk,
             const __grid_constant__ CUtensorMap tmv, const __grid_constant__ CUtensorMap tmo,
             const __grid_constant__ CUtensorMap tmx, const __grid_constant__ CUtensorMap tmb, const __grid_constant__ CUtensorMap tmy,
             const bf16* __restrict__ mem0, const bf16* __restrict__ xg,
             uint32_t xlo, uint32_t xhi, uint32_t zero, int nseg, bf16* __restrict__ out) {
    extern __shared__ __align__(1024) uint8_t smem[];
    const uint32_t tstart = clk();
    const uint32_t rk = smem_u32(smem) & 0x1000000;
    if (rk == 0 && (threadIdx.x & 31) == 0 && threadIdx.x - 32 < 32 * PW)
        sts32(SB0 + SM_ROLE + 4 + (threadIdx.x >> 3), probe(xlo + XO_PB + (threadIdx.x & 32) * 128 + (threadIdx.x & 64) * 256 + blockIdx.x * 16, xhi));
    __syncwarp();
    if ((smem_u32(smem) & 0xFFFFFF) != SB0) die(1 << 23);
    asm volatile("griddepcontrol.launch_dependents;" ::: "memory");
    const uint32_t w = __reduce_max_sync(0xFFFFFFFFu, threadIdx.x >> 5);
    const uint32_t sb = __reduce_max_sync(0xFFFFFFFFu, smem_u32(smem));
    const uint32_t bq = sb + SM_BAR;
    uint32_t l16 = __shfl_sync(0xFFFFFFFFu, (threadIdx.x & 31) * 16, threadIdx.x & 31);
    if (threadIdx.x == 0) {
        mbar_init(bq, 1);
        for (int i = 0; i < 24; i++) mbar_init(bq + BAR_WF + i * 8, i < 16 ? 1 : 8);
        mbar_init(bq + BAR_XA, 4); mbar_init(bq + BAR_KV, 4); mbar_init(bq + BAR_PI, 2); mbar_init(bq + BAR_PI + 8, 2);
        for (int i = 0; i < 14; i++) mbar_init(bq + BAR_GF + i * 8, i < 8 || i == 13 ? 1 : 8);
        mbar_expect(bq + BAR_GX + 8, 32768);
        mbar_init(bq + BAR_RO, 1);
        mbar_expect(bq + BAR_RO, 4);
        mbar_expect(bq + BAR_PI, 6144);
        mbar_expect(bq + BAR_PI, 6144);
        asm volatile("fence.mbarrier_init.release.cluster;" ::: "memory");
        asm volatile("fence.proxy.async.shared::cta;" ::: "memory");
    }
    __syncwarp();
    asm volatile("barrier.cluster.arrive.relaxed.aligned;" ::: "memory");
    if (w == 9) {
#pragma unroll 1
        for (int e = 0; e < 12; e++) sts128(sb + SM_WO + e * 512 + l16, 0, 0, 0, 0);
    }
    if (w == 8 && blockIdx.x < 128) {
        if (XPF && elect()) {
            asm volatile("cp.async.bulk.prefetch.L2.global [%0], 3072;" ::"l"((const char*)xg + blockIdx.x * 3072) : "memory");
            asm volatile("prefetch.tensormap [%0];\nprefetch.tensormap [%1];\nprefetch.tensormap [%2];\nprefetch.tensormap [%3];\nprefetch.tensormap [%4];"
                         ::"l"(&tmq), "l"(&tmx), "l"(&tmk), "l"(&tmv), "l"(&tmo) : "memory");
        }
#pragma unroll 1
        for (int i = 0; i < EPF; i++) {
            if (i) delay_until(clk(), EPD);
            if (elect())
                asm volatile("cp.async.bulk.prefetch.tensor.3d.L2.global [%0, {0, %1, %2}];" ::"l"(&tmq), "r"((blockIdx.x & 3) * 256 + i * 64), "r"((blockIdx.x >> 2) * 2) : "memory");
        }
    }
    if (rk == 0 && w <= PW) bsync<2, 32 * PW + 32>();
    asm volatile("barrier.cluster.wait.aligned;" ::: "memory");
    if (rk == 0 && threadIdx.x == 0) {
        uint32_t t1 = lds32(sb + SM_ROLE + 8), t0 = lds32(sb + SM_ROLE + 12);
        if (PW == 4) { t1 = min(t1, lds32(sb + SM_ROLE + 16)); t0 = min(t0, lds32(sb + SM_ROLE + 20)); }
        uint32_t side = (t0 < t1 ? 0u : 1u) ^ par(XO_PB);
        uint32_t* tk = (uint32_t*)(((uint64_t)xhi << 32) | (xlo + XO_TK));
        uint32_t t = atomicAdd(tk + side, 1u);
        if (t >= 32) {
            uint2 c;
            int it = 0;
            do {
                c = ldg2<XO_TK>(xlo, xhi);
                if (++it > SPIN_LIMIT) die(it);
            } while (c.x + c.y != gridDim.x / 2);
            t += (side ? c.x : c.y) - 32;
            side ^= 1;
            if (t >= 32) tickets_done(tk);
        }
#pragma unroll
        for (uint32_t r = 0; r < 2; r++)
            asm volatile("st.async.weak.shared::cluster.mbarrier::complete_tx::bytes.b32 [%0], %1, [%2];"
                         ::"r"(sb + SM_ROLE + (r << 24)), "r"(t * 4 + side * 2 + r), "r"(bq + BAR_RO + (r << 24)) : "memory");
    }
    __syncwarp();
    mbar_wait(bq + BAR_RO, 0);
    const uint32_t role = __reduce_max_sync(0xFFFFFFFFu, lds32(sb + SM_ROLE));
    if (role >= 128) return;
    const uint32_t h = role >> 2, j = role & 3;
    if (FTM && w == 11 && elect())
#pragma unroll
        for (uint32_t c = 0; c < FTM; c++) {
            mbar_expect(bq + BAR_WF + c * 8, 16384);
            tma3d(sb + SM_ST + c * 16384, &tmq, bq + BAR_WF + c * 8, 0, j * 256 + c * 64, h * 2);
        }

    if (w >= 8) {
        asm volatile("setmaxnreg.dec.sync.aligned.u32 24;");
        const uint32_t u = w - 8;
        if (u == 3) {
#pragma unroll 1
            for (uint32_t c = FTM; c < 16; c++) {
                if (c >= WIN) mbar_wait(bq + BAR_WF + (c - WIN) * 8, 0);
                if (l16 == 0) PG(16 + c);
                if (c == 12 + WOP) bsync<2, 64>();
                if (c >= 4 && c < 12 && c != 10) mbar_wait(bq + BAR_WE + (c - 4) * 8, 0);
                if (elect()) {
                    const uint32_t b = bq + BAR_WF + c * 8;
                    mbar_expect(b, 16384);
                    if (c >= 12) tma2d(sb + SM_WO + (c - 12) * WO_BOX, &tmo, b, j * 256 + (c - 12) * 64, h * 128);
                    else tma3d(c == 10 ? sb + SM_WV : sb + SM_ST + (c & 3) * 16384, c < 4 ? &tmq : c < 8 ? &tmk : &tmv, b, 0, j * 256 + ((c ^ (c >= 10)) & 3) * 64, h * 2);
                }
            }
#pragma unroll 1
            for (uint32_t c = 16 - WIN; c < 16; c++) mbar_wait(bq + BAR_WF + c * 8, 0);
            if (l16 == 0) PG(15);
        } else if (u == 0) {
            if (elect()) {
                mbar_expect(bq, 49152);
#pragma unroll 1
                for (uint32_t i = 0; i < 12; i++)
                    tma3d(sb + SM_X + (i < 4 ? i : i + 4) * 4096, &tmx, bq, 0, i < 8 ? i * 8 : (j ^ ((0xBD98u >> (i - 8) * 4) & 15)) * 8, j * 4);
            }
#pragma unroll 1
            for (int i = 0; i < 4; i++) xload(sb, i, j, -1, &tmx);
            bsync<3, 320>();
            if (l16 == 0) PG(32);
            if (GH && j == 0 && elect()) asm volatile("{\n.reg .b64 a;\nmov.b64 a, {%0,%1};\nred.relaxed.gpu.global.inc.u32 [a+64], 4;\n}" ::"r"(xlo + XO_FL + h * 128), "r"(xhi) : "memory");
            __syncwarp();
            g_arrive(xlo + XO_FL + h * 128, xhi, 4);
            if (WOP < 4) barv<2, 64>();
            if (l16 == 0) PG(33);
            g_wait(xlo + XO_FL + h * 128, xhi);
            if (l16 == 0) PG(34);
#pragma unroll 1
            for (int i = 0; i < 4; i++)
                if (elect()) kvload(sb, i, h, j, 0, xlo, xhi);
            mbar_wait(bq + BAR_KV, 0);
            if (l16 == 0) PG(14);
        } else if (u == 1) {
            const uint32_t l = l16 >> 4, x = h * 8 + (l >> 2), d = (x & ~31u) + (l & 3) * 8 + ((x & 31) >> 2) + (x & 3) * 2 * DM;
            const unsigned short* m0 = (const unsigned short*)mem0 + j * 256;
            const uint32_t v1 = m0[d] | (((l & 3) == 3 ? 0x4200u : m0[d + DM]) << 16);
            const uint32_t v3 = h < 8 ? m0[h * 32 + 24 + (l >> 2) + ((l & 3) * 2 + 1) * DM] | 0x42000000u : 0;
#pragma unroll 1
            for (uint32_t i = 0; i < 12; i++) {
                if (i == 10) { sts32(sb + SM_WO + 6144 + l * 4, v1); sts32(sb + SM_WO + 6272 + l * 4, v3); }
                asm volatile("fence.proxy.async.shared::cta;" ::: "memory");
                __syncwarp();
                const uint32_t c = (0x21924u >> ((i - 3) * 2)) & 3;
                if (elect()) {
                    if (i < 3) bulk_s2g(xlo + XO_XG + (i * 128 + role) * 6144, xhi, sb + SM_WO, 6144);
                    else bulk_s2g(xlo + XO_R + rpage(j, i < 6 ? 0 : i < 9 ? 1 : -1) + c * 16384 + h * 128, xhi, sb + SM_WO + (i < 10 ? 0 : 6144 + c * 64), 128);
                }
            }
            asm volatile("cp.async.bulk.wait_group 0;" ::: "memory");
            if (elect()) asm volatile("{\n.reg .b64 a;\nmov.b64 a, {%0,%1};\nred.relaxed.gpu.global.inc.u32 [a], 127;\n}" ::"r"(xlo + XO_TK + 12), "r"(xhi) : "memory");
            if (l16 == 0) PG(16);
            g_wait(xlo + XO_TK + 12, xhi);
            if (l16 == 0) PG(17);
            barv<5, 288>();
            bsync<8, 320>();
            asm volatile("fence.acq_rel.gpu;" ::: "memory");
        } else {
            GSYNC(0);
            mbar_wait(bq + BAR_WE + 48, 0);
#pragma unroll 1
            for (int e = 0; e < 24; e++) sts128(sb + SM_TR + 4096 + e * 512 + l16, 0, 0, 0, 0);
            barv<3, 320>();
            bsync<8, 320>();
#pragma unroll 1
            for (int i = 0; i < 4; i++) xload(sb, i, j, 0, &tmx);
        }
#pragma unroll 1
        for (int s = 0; s < nseg; s++) helper_step(sb, w, h, j, l16, xlo, xhi, zero, s, &tmx, &tmb);
        piwait(sb, 0, nseg - 2);
        bsync<9, 384>();
        GSYNC(1);
        if (!GS && w == 11 && elect()) asm volatile("prefetch.tensormap [%0];" ::"l"(&tmy) : "memory");
        if (GH && w == 10) { g_arrive(xlo + XO_FL + h * 128 + 64, xhi, 5); PG(2); }
        if (w < 10) {
            uint32_t kb = 2, heads = 0;
            asm volatile("fence.proxy.async.shared::cta;" ::: "memory");
            if (GH) {
                if (w == 9 && h >= 30) { kb = 0; heads = 0xFFFF; }
                else delay_until(clk(), GD);
            } else if (w == 9) {
                g_arrive(xlo + XO_TK + 192, xhi, 128);
                PG(2);
                if (h >= 30) { g_wait(xlo + XO_TK + 192, xhi); kb = 0; }
                PG(3);
            } else delay_until(clk(), GD);
#pragma unroll 1
            for (; kb < 32; kb++) {
                if (kb >= 4) mbar_wait(bq + BAR_GE + (kb & 3) * 8, ((kb >> 2) & 1) ^ 1);
                if (GH && ((heads >> (kb >> 1)) & 1)) {
                    int it = 0;
                    do {
                        uint32_t v;
                        asm volatile("{\n.reg .b64 a;\nmov.b64 a, {%1,%2};\nld.acquire.gpu.global.u32 %0, [a+64];\n}"
                                     : "=r"(v) : "r"(xlo + XO_FL + (role & 1) * 2048 + (l16 & 255) * 8), "r"(xhi) : "memory");
                        heads = __ballot_sync(0xFFFFFFFFu, v != 0);
                        if (++it > SPIN_LIMIT) die(it);
                    } while ((heads >> (kb >> 1)) & 1);
                    asm volatile("fence.proxy.async.global;" ::: "memory");
                    if (kb == 0) PG(3);
                }
                g_load(sb, w - 8, role, kb, xlo, xhi, &tmb);
            }
        }
        if (role == 0 && w == 11 && elect()) tickets_done((uint32_t*)(((uint64_t)xhi << 32) | (xlo + XO_TK)));
    } else {
        asm volatile("setmaxnreg.inc.sync.aligned.u32 240;");
        uint32_t Wq[16][4], Wk[16][4], Wv[NA][4];
        uint32_t t16, KA, KB, KC, KD;
        {
            const uint32_t lane = l16 >> 4, g = lane >> 2, t = lane & 3;
            const uint32_t rw = (((lane >> 4) & 1) * 8 + (lane & 7)) * 128u;
            const uint32_t off = rw + ((((w & 3) * 2 + ((lane >> 3) & 1)) ^ (lane & 7)) << 4);
            const uint32_t offo = rw + ((((w & 1) * 4 + ((lane >> 3) & 1)) ^ (lane & 7)) << 4);
            const uint32_t r = 2 * (t & 1) + (g >> 2);
            const uint32_t mk0 = t < 2 ? 0 : (r == 0 ? 2 * g > w : j + r < 4), mk1 = t < 2 ? 0 : (r == 0 ? 2 * g + 1 > w : j + r < 4);
            t16 = __shfl_sync(0xFFFFFFFFu, w * 512 + l16, lane);
            KA = __shfl_sync(0xFFFFFFFFu, (w * 512 + t * 64 + g * 8) | ((w * 512 + (g & 1) * 256 + (g >> 1) * 64 + t * 16) << 16), lane);
            KB = __shfl_sync(0xFFFFFFFFu, ((w >> 2) * WV_BOX + off) | mk0 | (mk1 << 1) |
                                              ((w * 256 + (g >> 2) * 4096 + (g & 3) * 64 + t * 16) << 16), lane);
            KC = __shfl_sync(0xFFFFFFFFu, ((lane & 7) * 1280 + (lane >> 3) * 128 + ((w ^ (lane & 7)) << 4)) | (((t >> 1) * 16 + g * 2) << 16) | ((t * 64 + g * 8) << 24), lane);
            KD = __shfl_sync(0xFFFFFFFFu, ((w >> 1) * WO_BOX + offo) | (((lane & 7) * 208 + (lane >> 3) * 16) << 16), lane);
            if (threadIdx.x == 0) PG(8);
#define WTAKE(W, c, k0) { mbar_wait(bq + BAR_WF + (c) * 8, 0); \
                _Pragma("unroll") for (int ks = 0; ks < 4; ks++) ldsm4t(W[(k0) + ks], sb + SM_ST + ((c) & 3) * 16384 + (KB & 0xFFF0) + ks * 2048); \
                if ((c) < 8) { __syncwarp(); if (elect()) mbar_arrive(bq + BAR_WE + (c) * 8); } }
#pragma unroll
            for (int c = 0; c < 4; c++) WTAKE(Wq, c, c * 4);
            mbar_wait(bq, 0);
            if (threadIdx.x == 0) PG(9);
            xstart<0>(sb, w, xlo + h * 24576, xhi, j, t16, KA, Wq);
            if (threadIdx.x == 0) PG(10);
#pragma unroll
            for (int c = 0; c < 4; c++) WTAKE(Wk, c + 4, c * 4);
            if (threadIdx.x == 0) PG(11);
            xstart<1>(sb, w, xlo + h * 24576, xhi, j, t16, KA, Wk);
            if (threadIdx.x == 0) PG(12);
            WTAKE(Wv, 8, 0);
            WTAKE(Wv, 9, 4);
            mbar_wait(bq + BAR_WF + 80, 0);
            WTAKE(Wv, 11, 8);
            if (threadIdx.x == 0) PG(13);
            xstart<2>(sb, w, xlo + h * 24576, xhi, j, t16, KA, Wv);
            mbar_wait(bq + BAR_XA, 0);
            bsync<8, 320>();
        }
        const uint32_t ONES = 0x3F803F80u;
#define UNI(x) __reduce_max_sync(0xFFFFFFFFu, x)
        uint32_t swi = UNI((uint32_t)((uint64_t)smem >> 32));
        const uint32_t sbw = UNI(sb + w * 256), sbm = UNI(sb - w * 512), sbs = UNI(sb + w * 768), sbp = UNI(sb + w * 208);
#define OPQALL() { OPQ(t16); OPQ(KA); OPQ(KB); OPQ(KC); OPQ(KD); }
        OPQALL();
        if (SEED & 1) OPQ(Wq[0][0]);
        if (SEED & 2) OPQ(Wq[5][1]);
        if (SEED & 4) OPQ(Wk[0][0]);
        if (SEED & 8) OPQ(Wk[15][2]);
        if (SEED & 16) OPQ(Wv[0][0]);
        if (SEED & 32) OPQ(Wv[7][3]);
        const uint32_t cb0 = (h >> 1) * 32768 + (j & 1) * 16384 + (h & 1) * 8192;
        const uint32_t cb = UNI(xlo + cb0 + ((par(cb0) ^ (j >> 1) ^ CFAR) << 12)), cv = UNI(xlo + h * 8192 + JV(h, j) * 2048), h1 = UNI((h & 1) * 1024);
        const uint32_t uox = UNI(xlo + XO_OX + (h * 2 + (w >> 2)) * 262144 + j * 1024 + (w & 3) * 256 - w * 128);
        uint32_t rp = UNI(xlo + rpage(j, 0));
        float ox[4];
        float4 dn;
#define OXSTORE(s) asm volatile("{\n.reg .b64 a;\nmov.b64 a, {%0,%1};\nst.global.u32 [a], %2;\nst.global.u32 [a+128], %3;\n}" \
                                ::"r"(uox + (s) * 4096 + (t16 >> 2)), "r"(xhi), \
                                  "r"(pack2(ox[0] * dn.y, ox[1] * dn.w)), "r"(pack2(ox[2] * dn.y, ox[3] * dn.w)) : "memory")
#pragma unroll 1
        for (int s2 = 0;; s2 += 2, rp ^= 0x21000)
#pragma unroll
        for (int p = 0; p < 2; p++) {
            const int s = s2 + p;
            const uint32_t ctag = ((s2 >> 1) & 1) ^ 1;
            const uint32_t hb = cb ^ (p * 0x81000), rb = rp ^ (p * 0x11000);
            uint4 k0, k1, qq, c0, c1, c2, c3, pk;
            float va[4], vb[4];
            uint32_t qx0, qx1, ov0, ov1, wv[16 - NA][4];
            {
                float xa[16], xb[16];
                uint4 m0, n0;
                uint32_t e0, f0;
                uint32_t xp[8];
                wg_fence();
                XMMA(0, 6);
                SF();
                piwait(sb, p, s - 2);
                uint4 pi = xpeer<0>(sb, p ^ 1, t16);
                SF();
#define MR (VC ? 1 : 2)
#define MC (VC ? 2 : 1)
#define QPARK() { xpack<0>(xp, xa); xpark<0>(xp, pi, sb, sbw, p ^ 1, t16, KA); pi = xpeer<MR>(sb, p ^ 1, t16); SF(); }
                wg_fence();
                if (QP) {
                    XMMA(6, QP);
                    XMMA(QP, QP + 4);
                    wg_wait<1>();
                    SF();
                    QPARK();
                    wg_fence();
                    if (QP + 4 < RPOS) XMMA(QP + 4, RPOS);
                } else XMMA(6, RPOS);
                if (RPOS < 32) XMMA(RPOS, RPOS + 4 < 32 ? RPOS + 4 : 32);
                uint32_t a = (p ? rp : rp ^ 0x30000) + t16, e = (p ? rp : rp ^ 0x30000) + (t16 >> 2), ah = xhi, eh = xhi;
                OPQ(a); OPQ(e); OPQ(ah); OPQ(eh);
                SF();
                wg_wait<(RPOS < 32)>();
                SF();
                PT(11);
                RLOAD();
                SF();
                if (!QP) QPARK();
                if (RPOS + 4 < 32) {
                    wg_fence();
                    XMMA(RPOS + 4, 32);
                    SF();
                }
                wg_wait<0>();
                xpack<MR>(xp, xb);
                xpark<MR>(xp, pi, sb, sbw, p ^ 1, t16, KA);
                uint32_t acw, ahi, tg;
#define APREP() { OPQ(KA); if (!APH) OPQ(t16); acw = hb + (KA & 0xFFFF); ahi = xhi; tg = ctag; OPQ(acw); OPQ(ahi); OPQ(tg); }
                if (APH == 3) SF();
                if (APH) APREP();
                if (APH >= 2) OPQ(t16);
                SF();
                PT(12);
                {
                    int it = 0;
                    if (RDW) {
                        bool rb_;
#pragma unroll 1
                        do {
                            rb_ = ruse(sb + SM_MEMT + t16, m0, n0, e0, f0);
                            if (RDW == 2) MF();
                            if (RDW == 3) SF();
                            asm volatile("{\n.reg .pred p, q;\n.reg .b64 a, e;\nsetp.ne.u32 p, %15, 0;\nmov.b64 a, {%11,%12};\nmov.b64 e, {%13,%14};\n"
                                         "@p ld.relaxed.gpu.global.v4.u32 {%0,%1,%2,%3}, [a];\n@p ld.relaxed.gpu.global.v4.u32 {%4,%5,%6,%7}, [a+16384];\n"
                                         "@p ld.relaxed.gpu.global.u32 %8, [e+32768];\n@p ld.relaxed.gpu.global.u32 %9, [e+33792];\n"
                                         "add.u32 %10, %10, 1;\nsetp.gt.u32 q, %10, 1048576;\n@q st.shared.u32 [%10], %10;\n}"
                                         : "+r"(m0.x), "+r"(m0.y), "+r"(m0.z), "+r"(m0.w), "+r"(n0.x), "+r"(n0.y), "+r"(n0.z), "+r"(n0.w), "+r"(e0), "+r"(f0), "+r"(it)
                                         : "r"(a), "r"(ah), "r"(e), "r"(eh), "r"((uint32_t)rb_) : "memory");
                        } while (rb_);
                    } else
                    while (ruse(sb + SM_MEMT + t16, m0, n0, e0, f0)) {
                        RLOAD();
                        if (++it > SPIN_LIMIT) die(it);
                    }
                    PC(22, it + 1);
                }
                PT(13);
                if (APH == 1) OPQ(t16);
                if (!APH) APREP();
                if (APH < 2) SF();
                bsync<1, 384>();
                PT(0);
                uint32_t b[8][4];
#pragma unroll
                for (int i = 0; i < 8; i++) {
                    const int pp = i < 2 ? i : i ^ 1;
                    ldsm4t(b[pp], sbm + SM_MEMT + t16 + pp * 512);
                    if (i < 7) MF();
                }
                if (ASF) SF();
                float q[4], k[4];
                const uint32_t aWv = sb + SM_WV + (KB & 0xFFF0);
#define WVLD(n0, n1) _Pragma("unroll") for (int n = (n0); n < (n1) && n < 16 - NA; n++) ldsm4t(wv[n], aWv + n * 2048)
#pragma unroll
                for (int ks = 0; ks < 16; ks++) {
                    const uint32_t b0 = b[ks >> 1][(ks & 1) * 2], b1 = b[ks >> 1][(ks & 1) * 2 + 1];
                    if (ks == 0) {
                        mma16z(q, Wq[0][0], Wq[0][1], Wq[0][2], Wq[0][3], b0, b1);
                        mma16z(k, Wk[0][0], Wk[0][1], Wk[0][2], Wk[0][3], b0, b1);
                    } else {
                        mma16(q, Wq[ks][0], Wq[ks][1], Wq[ks][2], Wq[ks][3], b0, b1);
                        mma16(k, Wk[ks][0], Wk[ks][1], Wk[ks][2], Wk[ks][3], b0, b1);
                    }
                    if (ks == 10 && VPF) { SF(); WVLD(0, VPF); }
                }
                const uint32_t oq0 = settag(pack2(q[0], q[2]), tg), oq1 = settag(pack2(q[1], q[3]), tg);
                const uint32_t ok0 = pack2(k[0], k[2]), ok1 = pack2(k[1], k[3]);
                stg2<XO_CQK>(acw, ahi, oq0, ok0);
                stg2<XO_CQK + 256>(acw, ahi, oq1, ok1);
                SF();
                PT(1);
#define CLOADG() { c2 = ldg4<XO_CQK>((hb ^ 0x1000) + (KA >> 16), xhi); c3 = ldg4<XO_CQK>((hb ^ 0x5000) + (KA >> 16), xhi); }
#define CLOAD0() c0 = lds128(sb + SM_TR + (KA >> 16))
#define CLOAD1() c1 = lds128(sb + SM_TR + 4096 + p * 4096 + (KA >> 16))
#define CLOADS() { CLOAD0(); CLOAD1(); }
#define CSIDE(n) { if (CGP == (n)) CLOADG(); if (C0P == (n)) CLOAD0(); if (C1P == (n)) CLOAD1(); if (PIP == (n)) pk = xpeer<MC>(sb, p ^ 1, t16); \
                   if (QSP == (n)) { qx0 = (t16 & 64) ? qq.y : qq.x; qx1 = (t16 & 64) ? qq.w : qq.z; } }
#pragma unroll
                for (int rd = 0; rd < 8; rd++) {
                    const int pp = (VORD >> (28 - 4 * rd)) & 7;
                    const uint32_t* a = 2 * pp < NA ? Wv[2 * pp < NA ? 2 * pp : 0] : wv[2 * pp < NA ? 0 : 2 * pp - NA];
                    const uint32_t* c = 2 * pp < NA ? Wv[2 * pp < NA ? 2 * pp + 1 : 0] : wv[2 * pp < NA ? 0 : 2 * pp + 1 - NA];
                    if (rd == 0) {
                        mma16z(va, a[0], a[1], a[2], a[3], b[pp][0], b[pp][1]);
                        mma16z(vb, c[0], c[1], c[2], c[3], b[pp][2], b[pp][3]);
                        if (VSB & 256) SF();
                        OPQ(swi);
                        asm volatile("{\n.reg .b64 a;\nmov.b64 a, {%0,%1};\nst.v2.u32 [a], {%2,%3};\nst.v2.u32 [a+256], {%4,%5};\n}"
                                     ::"r"((KA & 0xFFF) + (sb ^ 0x1000000) + SM_TR + 4096 + p * 4096), "r"(swi), "r"(oq0), "r"(ok0), "r"(oq1), "r"(ok1) : "memory");
                        sts64(sb + SM_TR + (KA & 0xFFF), oq0, ok0);
                        sts64(sb + SM_TR + (KA & 0xFFF) + 256, oq1, ok1);
                    } else {
                        mma16(va, a[0], a[1], a[2], a[3], b[pp][0], b[pp][1]);
                        mma16(vb, c[0], c[1], c[2], c[3], b[pp][2], b[pp][3]);
                    }
                    if (rd == KEP) { KEEP(t16, oq0, oq1, ok0, ok1); if (KE2) KEEP(t16, acw, ahi, acw, ahi); }
                    if ((VSB >> rd) & 1) SF();
                    if (rd == W2P) WVLD(2, 3);
                    if (rd == W3P) WVLD(3, 4);
                    if (rd == K0P) k0 = lds128(sb + SM_KV + 2048 + (KB >> 16));
                    if (rd == K0P + 1) k1 = lds128(sb + SM_KV + 10240 + (KB >> 16));
                    if (rd == QQP) qq = lds128(sbw + SM_KV + ((KA >> 16) & 0xFF));
                    CSIDE(rd);
                    if ((VSF >> rd) & 1) SF(); else if ((VMF >> rd) & 1) MF();
                }
#define VTAIL() { ov0 = pack2(va[0] + vb[0], va[1] + vb[1]); ov1 = pack2(va[2] + vb[2], va[3] + vb[3]); \
                  stg2<XO_CV>(cv + p * 262144 + (t16 >> 1), xhi, settag(ov0, ctag), ov1); \
                  if (VD) asm volatile("{\n.reg .b64 a;\nmov.b64 a, {%0,%1};\nst.v2.u32 [a], {%2,%3};\n}" \
                                     ::"r"((t16 >> 1) + (sb ^ 0x1000000) + SM_VP + p * 2048), "r"(swi), "r"(settag(ov0, ctag)), "r"(ov1) : "memory"); \
                  barv<8, 384>(); OPQ(t16); SF(); }
                if (!VTP) VTAIL();
            }
            PT(2);
            PDUMP();
            {
                const uint32_t a0 = sb + SM_KV;
                float xa[16], xb[16];
                uint32_t xp[8];
                if (CGP == 12 || QSP == 12) { CSIDE(12); SF(); }
                wg_fence();
                XMMA(32, 32 + CPOS);
                if (CGP == 13) { SF(); CSIDE(13); SF(); wg_fence(); }
                if (VR == 1) { XMMA(32 + CPOS, 36); XMMA(36, 36 + CW2); wg_wait<2>(); }
                else if (CW) { XMMA(32 + CPOS, 36 + CPOS); wg_wait<1>(); }
                SF();
                CSIDE(8);
                SF();
                if (VR == 1) { wg_wait<1>(); SF(); }
                if (VTP) VTAIL();
                CSIDE(9);
                SF();
                wg_fence();
                XMMA(VR == 1 ? 36 + CW2 : 32 + CPOS + (CW ? 4 : 0), 48);
                SF();
                uint2 u1, u2, u3;
#define ULOADG() { u2 = ldg2<XO_CV>((cv ^ 4096) + p * 262144 + (t16 >> 1), xhi); u3 = ldg2<XO_CV>((cv ^ 6144) + p * 262144 + (t16 >> 1), xhi); }
#define ULOADS() u1 = lds64(sb + SM_VP + p * 2048 + (t16 >> 1))
#define UCHECK() { int it = 0; \
                   while (__builtin_expect(any_bad(tagx1(tagx2(u2.x, u3.x, ctag), u1.x, ctag)), 0)) { OPQ(t16); ULOADG(); ULOADS(); if (++it > SPIN_LIMIT) die(it); } \
                   PC(26, it); }
                CSIDE(10);
                if (B3 == 8 && VLP == 2) ULOADG();
                SF();
                const uint32_t ka[4] = {k0.x, k0.y, k0.z, k0.w}, kb[4] = {k1.x, k1.y, k1.z, k1.w};
                const uint32_t aSp = sb + SM_SP + (KC & 0xFFFF);
                PT(3);
#define BAR3() asm volatile("{\n.reg .pred p;\nsetp.eq.u32 p, %0, 0;\n@p bar.arrive 3, %1;\n}" ::"r"((uint32_t)bad), "n"(B3 == 6 ? 288 : 384) : "memory")
#define SCORES(FIRST) { \
                    const uint32_t qA = hadd2(hadd2(c0.x, c1.x), hadd2(c2.x, c3.x)), qB = hadd2(hadd2(c0.z, c1.z), hadd2(c2.z, c3.z)); \
                    const uint32_t kA = hadd2(hadd2(c0.y, c1.y), hadd2(c2.y, c3.y)), kB = hadd2(hadd2(c0.w, c1.w), hadd2(c2.w, c3.w)); \
                    bad = any_bad(or3(tagx2(c1.x, c1.z, ctag), tagx2(c2.x, c2.z, ctag), tagx2(c3.x, c3.z, ctag))); \
                    float sa[4], sb_[4], sc[4], sd[4], se[4]; \
                    if (FIRST) { SF(); if (B3 == 8 && VLP == 3) ULOADG(); CSIDE(11); wg_wait<0>(); } \
                    mma16z(sa, ka[0], ka[1], ka[2], ka[3], qA, qB); \
                    mma16z(sb_, kb[0], kb[1], kb[2], kb[3], qA, qB); \
                    mma16z(sc, qA, qx0, qB, qx1, kA, kB); \
                    if (FIRST) { \
                        xpack<MC>(xp, xa); \
                        if (KPOS == 0) { xadd(xp, pk); xstore<MC>(xp, sb, sbw, p ^ 1, t16, KA); if (B3 >= 5) BAR3(); else if (!B3 || B3 >= 3) barv<3, 384>(); } \
                        mma16z(sd, ka[0], ka[1], ka[2], ka[3], qx0, qx1); \
                        mma16z(se, kb[0], kb[1], kb[2], kb[3], qx0, qx1); \
                    } \
                    stsm4t(aSp, pack2(sa[0], sa[1]), pack2(sa[2], sa[3]), pack2(sb_[0], sb_[1]), pack2(sb_[2], sb_[3])); \
                    stsm2(aSp + 1024, pack2(sc[0], sc[1]), pack2(sc[2], sc[3])); \
                    if (FIRST) { \
                        stsm4t(aSp + 512, pack2(sd[0], sd[1]), pack2(sd[2], sd[3]), pack2(se[0], se[1]), pack2(se[2], se[3])); \
                        if (KPOS == 0) { KEEP(KD, xp[0], xp[1], xp[2], xp[3]); KEEP(KD, xp[4], xp[5], xp[6], xp[7]); } \
                    } }
                int it = 0;
                bool bad;
                SCORES(true);
                while (__builtin_expect(bad, 0)) {
                    OPQ(KA);
                    CLOADG();
                    CLOADS();
                    SCORES(false);
                    if (B3 >= 5) BAR3();
                    if (++it > SPIN_LIMIT) die(it);
                }
                PC(25, it);
                PT(4);
                if (B3 == 8 && VLP == 0) ULOADG();
                if (B3 == 1) barv<3, 384>();
                bsync<4, B3 == 2 ? 384 : 256>();
                uint32_t wo[16][4];
                const uint32_t aWo = sb + SM_WO + (KD & 0xFFFF), aWo1 = sb + SM_WO + ((KD & 0xFFFF) ^ 32);
#define WOLD(n0, n1) _Pragma("unroll") for (int n = (n0); n < (n1) && n < 16; n++) ldsm4t(wo[n], ((n & 1) ? aWo1 : aWo) + (n >> 1) * 2048)
                const bool hi = (t16 & 32) != 0;
                const uint32_t t8 = t16 >> 1;
                uint2 v0, v1, v2, v3;
                uint32_t es;
                {
                    uint32_t am[4], ax[4], a4[2];
                    const uint32_t aSr = sbs + SM_SP + t16;
                    ldsm4t(am, aSr);
                    ldsm4t(ax, aSr + 512);
                    ldsm2t(a4, aSr + 1024);
                    MF();
                    if (B3 == 8 && VLP == 1) ULOADG();
                    if (KPOS == 1) pk = xpeer<MC>(sb, p ^ 1, t16);
                    const uint32_t se = (t16 & 128) ? 0u : ONES, so = se ^ ONES;
                    float hm[4], hx[4], h4[4];
                    mma16z(hm, am[0], am[1], am[2], am[3], se, so);
                    mma16z(hx, ax[0], ax[1], ax[2], ax[3], se, so);
                    mma8z(h4, a4[0], a4[1], ONES);
                    SF();
                    if (KPOS == 1) { xpark<MC>(xp, pk, sb, sbw, p ^ 1, t16, KA); barv<3, 384>(); }
                    v0 = lds64(a0 + 4096 + t8); v1 = lds64(a0 + 8192 + t8); v2 = lds64(a0 + 12288 + t8); v3 = lds64(a0 + 16384 + t8);
                    if (B3 == 8) ULOADS();
                    WOLD(0, PF2);
                    float s0 = hi ? hx[0] : hm[0], s1 = hi ? hx[2] : hm[2];
                    const float s2 = hi ? h4[2] : h4[0];
                    s0 = (KB & 1) ? -1.0e9f * 11.313708499f : s0;
                    s1 = (KB & 2) ? -1.0e9f * 11.313708499f : s1;
                    int mi = __float_as_int(fmaxf(fmaxf(s0, s2), s1));
                    mi ^= (mi >> 31) & 0x7FFFFFFF;
                    const int mm = __reduce_max_sync(0xFFFFFFFFu, hi ? (int)0x80000000 : mi), mx = __reduce_max_sync(0xFFFFFFFFu, hi ? mi : (int)0x80000000);
                    SF();
                    WOLD(PF2, PF3);
                    SF();
                    mi = hi ? mx : mm;
                    mi ^= (mi >> 31) & 0x7FFFFFFF;
                    const float c2_ = 0.08838834764831845f * 1.4426950408889634f;
                    const float mc = __int_as_float(mi) * c2_;
                    const float e0 = ex2(fmaf(s0, c2_, -mc)), e1 = ex2(fmaf(s1, c2_, -mc)), e2 = ex2(fmaf(s2, c2_, -mc));
                    sts32(sbp + SM_P + (KC >> 25), pack2(e0, e1));
                    sts16(sbp + SM_P + 128 + ((KC >> 16) & 0xFF), pack2(e2, e2));
                    es = __float_as_uint(fmaf(e2, 0.5f, e0 + e1) + 64.f);
                }
                const uint32_t sm = __reduce_add_sync(0xFFFFFFFFu, hi ? 0u : es), sx = __reduce_add_sync(0xFFFFFFFFu, hi ? es : 0u);
                const uint32_t aPr = sb + SM_P + (KD >> 16);
                if (B3 == 8 && VCP == 0) UCHECK();
                PT(5);
                bsync<5, VB ? 256 : B3 == 6 ? 352 : 384>();
                uint32_t pm[4], px[4], p4[2];
                ldsm4(pm, aPr);
                MF();
                uint2 vs;
                #define VGET(n) if (VB == (n)) { if (VB) bsync<11, 384>(); vs = lds64(sb + SM_VS + t8); MF(); }
                if (B3 != 8) { VGET(0); VGET(1); }
                ldsm2(p4, aPr + 128);
                MF();
                VGET(2);
                ldsm4(px, aPr + 64);
                MF();
                VGET(3);
                sts32f(sb + SM_DN + w * 8 + ((t16 >> 3) & 4), rcp(__uint_as_float((hi ? sx : sm) - 15u * 0x42800000u) - 64.f));
                MF();
                if (B3 == 8 && VCP == 2) UCHECK();
                WOLD(PF3, NPF);
                if (B3 == 8 && VCP == 1) UCHECK();
                if (B3 == 8) { ov0 = hadd2(ov0, u1.x); ov1 = hadd2(ov1, u1.y); vs.x = hadd2(u2.x, u3.x); vs.y = hadd2(u2.y, u3.y); }
                const uint32_t vm0 = hadd2(ov0, vs.x), vm1 = hadd2(ov1, vs.y);
                float oa[4], ob[4];
                mma16z(oa, v0.x, v0.y, v1.x, v1.y, pm[0], pm[1]);
                mma16z(ob, v2.x, v2.y, v3.x, v3.y, pm[2], pm[3]);
                mma8(oa, vm0, vm1, p4[0]);
                stsm2(sbw + SM_OT + (t16 & 511), pack2(oa[0] + ob[0], oa[1] + ob[1]), pack2(oa[2] + ob[2], oa[3] + ob[3]));
                PT(6);
                SF();
                bsync<6, 256>();
                mma16z(ox, v0.x, v0.y, v1.x, v1.y, px[0], px[1]);
                uint32_t b[4][4];
#define OTLD(pp) ldsm4t(b[pp], sbm + SM_OT + t16 + (pp) * 512)
                OTLD(0);
                MF();
                OTLD(1);
                barv<7, 384>();
                mma16(ox, v2.x, v2.y, v3.x, v3.y, px[2], px[3]);
                mma8(ox, vm0, vm1, p4[1]);
                if (p == 1 && s + 1 == nseg) goto done;
                SF();
                uint32_t ar, ae, ahi = xhi;
                float r[2][4];
#pragma unroll
                for (int ks = 0; ks < 8; ks++) {
                    if (ks == 0) WOLD(NPF, NPF + WPF);
                    if (ks == OPOS) { OTLD(2); MF(); }
                    if (ks == OPOS + 2) { OTLD(3); MF(); }
                    if (ks > 0) WOLD(NPF + WPF + 2 * (ks - 1), NPF + WPF + 2 * ks);
                    if (ks == 5) {
                        OPQ(t16);
                        ar = rb + h1 * 16 + t16; ae = rb + h1 + (t16 >> 2);
                        OPQ(ar); OPQ(ahi); OPQ(ae);
                        dn = lds128f(sb + SM_DN + (t16 & 48));
                    }
#pragma unroll
                    for (int mt = 0; mt < 2; mt++) {
                        const int i = ks * 2 + mt;
                        const uint32_t* a = wo[i];
                        if (i < 2) mma16z(r[mt], a[0], a[1], a[2], a[3], b[ks >> 1][2 * (ks & 1)], b[ks >> 1][2 * (ks & 1) + 1]);
                        else mma16(r[mt], a[0], a[1], a[2], a[3], b[ks >> 1][2 * (ks & 1)], b[ks >> 1][2 * (ks & 1) + 1]);
                    }
                    if (NPF + WPF + 2 * ks < 16 || ks < 5) SF();
                }
                const float r0 = dn.x, r1 = dn.z;
                asm volatile("{\n.reg .b64 a;\nmov.b64 a, {%0,%2};\nred.relaxed.gpu.global.add.noftz.v4.bf16x2 [a], {%3,%4,%5,%6};\n"
                             "mov.b64 a, {%1,%2};\nred.relaxed.gpu.global.add.noftz.bf16x2 [a+32768], %7;\n}"
                             ::"r"(ar), "r"(ae), "r"(ahi), "r"(pack2(r[0][0] * r0, r[0][1] * r1)), "r"(pack2(r[0][2] * r0, r[0][3] * r1)),
                               "r"(pack2(r[1][0] * r0, r[1][1] * r1)), "r"(pack2(r[1][2] * r0, 1.f)), "r"(pack2(r[1][3] * r1, 1.f)) : "memory");
                barv<10, 384>();
            }
            SF();
            PT(10);
            OXSTORE(s);
            OPQALL();
        }
    done:
        dn = lds128f(sb + SM_DN + (t16 & 48));
        OXSTORE(nseg - 1);
        barv<9, 384>();
        g_main(sb, w, role, &tmy, out);
        if (threadIdx.x == 0) PG(0);
    }
}

template <int SC> DEVI void wg_rs128t(float (&d)[64], const uint32_t (&a)[4], uint64_t db) {
    if (SC) asm volatile("wgmma.mma_async.sync.aligned.m64n128k16.f32.bf16.bf16 "
        "{%0,%1,%2,%3,%4,%5,%6,%7,%8,%9,%10,%11,%12,%13,%14,%15,%16,%17,%18,%19,%20,%21,%22,%23,%24,%25,%26,%27,%28,%29,%30,%31,%32,%33,%34,%35,%36,%37,%38,%39,%40,%41,%42,%43,%44,%45,%46,%47,%48,%49,%50,%51,%52,%53,%54,%55,%56,%57,%58,%59,%60,%61,%62,%63}, "
        "{%64,%65,%66,%67}, %68, 1, 1, 1, 1;"
        : D4(+, 0), D4(+, 4), D4(+, 8), D4(+, 12), D4(+, 16), D4(+, 20), D4(+, 24), D4(+, 28), D4(+, 32), D4(+, 36), D4(+, 40), D4(+, 44), D4(+, 48), D4(+, 52), D4(+, 56), D4(+, 60) : "r"(a[0]), "r"(a[1]), "r"(a[2]), "r"(a[3]), "l"(db));
    else asm volatile("wgmma.mma_async.sync.aligned.m64n128k16.f32.bf16.bf16 "
        "{%0,%1,%2,%3,%4,%5,%6,%7,%8,%9,%10,%11,%12,%13,%14,%15,%16,%17,%18,%19,%20,%21,%22,%23,%24,%25,%26,%27,%28,%29,%30,%31,%32,%33,%34,%35,%36,%37,%38,%39,%40,%41,%42,%43,%44,%45,%46,%47,%48,%49,%50,%51,%52,%53,%54,%55,%56,%57,%58,%59,%60,%61,%62,%63}, "
        "{%64,%65,%66,%67}, %68, 0, 1, 1, 1;"
        : D4(=, 0), D4(=, 4), D4(=, 8), D4(=, 12), D4(=, 16), D4(=, 20), D4(=, 24), D4(=, 28), D4(=, 32), D4(=, 36), D4(=, 40), D4(=, 44), D4(=, 48), D4(=, 52), D4(=, 56), D4(=, 60) : "r"(a[0]), "r"(a[1]), "r"(a[2]), "r"(a[3]), "l"(db));
}
template <int SC> DEVI void wg_rs64t(float (&d)[32], const uint32_t (&a)[4], uint64_t db) {
    if (SC) asm volatile("wgmma.mma_async.sync.aligned.m64n64k16.f32.bf16.bf16 "
        "{%0,%1,%2,%3,%4,%5,%6,%7,%8,%9,%10,%11,%12,%13,%14,%15,%16,%17,%18,%19,%20,%21,%22,%23,%24,%25,%26,%27,%28,%29,%30,%31}, "
        "{%32,%33,%34,%35}, %36, 1, 1, 1, 1;"
        : D4(+, 0), D4(+, 4), D4(+, 8), D4(+, 12), D4(+, 16), D4(+, 20), D4(+, 24), D4(+, 28) : "r"(a[0]), "r"(a[1]), "r"(a[2]), "r"(a[3]), "l"(db));
    else asm volatile("wgmma.mma_async.sync.aligned.m64n64k16.f32.bf16.bf16 "
        "{%0,%1,%2,%3,%4,%5,%6,%7,%8,%9,%10,%11,%12,%13,%14,%15,%16,%17,%18,%19,%20,%21,%22,%23,%24,%25,%26,%27,%28,%29,%30,%31}, "
        "{%32,%33,%34,%35}, %36, 0, 1, 1, 1;"
        : D4(=, 0), D4(=, 4), D4(=, 8), D4(=, 12), D4(=, 16), D4(=, 20), D4(=, 24), D4(=, 28) : "r"(a[0]), "r"(a[1]), "r"(a[2]), "r"(a[3]), "l"(db));
}
template <int SC> DEVI void wg_rs40(float (&d)[20], const uint32_t (&a)[4], uint64_t db) {
    if (SC) asm volatile("wgmma.mma_async.sync.aligned.m64n40k16.f32.bf16.bf16 "
        "{%0,%1,%2,%3,%4,%5,%6,%7,%8,%9,%10,%11,%12,%13,%14,%15,%16,%17,%18,%19}, "
        "{%20,%21,%22,%23}, %24, 1, 1, 1, 0;"
        : D4(+, 0), D4(+, 4), D4(+, 8), D4(+, 12), D4(+, 16) : "r"(a[0]), "r"(a[1]), "r"(a[2]), "r"(a[3]), "l"(db));
    else asm volatile("wgmma.mma_async.sync.aligned.m64n40k16.f32.bf16.bf16 "
        "{%0,%1,%2,%3,%4,%5,%6,%7,%8,%9,%10,%11,%12,%13,%14,%15,%16,%17,%18,%19}, "
        "{%20,%21,%22,%23}, %24, 0, 1, 1, 0;"
        : D4(=, 0), D4(=, 4), D4(=, 8), D4(=, 12), D4(=, 16) : "r"(a[0]), "r"(a[1]), "r"(a[2]), "r"(a[3]), "l"(db));
}
template <int SC> DEVI void wg_rs8(float (&d)[4], const uint32_t (&a)[4], uint64_t db) {
    if (SC) asm volatile("wgmma.mma_async.sync.aligned.m64n8k16.f32.bf16.bf16 "
        "{%0,%1,%2,%3}, "
        "{%4,%5,%6,%7}, %8, 1, 1, 1, 0;"
        : D4(+, 0) : "r"(a[0]), "r"(a[1]), "r"(a[2]), "r"(a[3]), "l"(db));
    else asm volatile("wgmma.mma_async.sync.aligned.m64n8k16.f32.bf16.bf16 "
        "{%0,%1,%2,%3}, "
        "{%4,%5,%6,%7}, %8, 0, 1, 1, 0;"
        : D4(=, 0) : "r"(a[0]), "r"(a[1]), "r"(a[2]), "r"(a[3]), "l"(db));
}
template <int SC> DEVI void wg_ss64a(float (&d)[32], uint64_t da, uint64_t db) {
    if (SC) asm volatile("wgmma.mma_async.sync.aligned.m64n64k16.f32.bf16.bf16 "
        "{%0,%1,%2,%3,%4,%5,%6,%7,%8,%9,%10,%11,%12,%13,%14,%15,%16,%17,%18,%19,%20,%21,%22,%23,%24,%25,%26,%27,%28,%29,%30,%31}, "
        "%32, %33, 1, 1, 1, 1, 0;"
        : D4(+, 0), D4(+, 4), D4(+, 8), D4(+, 12), D4(+, 16), D4(+, 20), D4(+, 24), D4(+, 28) : "l"(da), "l"(db));
    else asm volatile("wgmma.mma_async.sync.aligned.m64n64k16.f32.bf16.bf16 "
        "{%0,%1,%2,%3,%4,%5,%6,%7,%8,%9,%10,%11,%12,%13,%14,%15,%16,%17,%18,%19,%20,%21,%22,%23,%24,%25,%26,%27,%28,%29,%30,%31}, "
        "%32, %33, 0, 1, 1, 1, 0;"
        : D4(=, 0), D4(=, 4), D4(=, 8), D4(=, 12), D4(=, 16), D4(=, 20), D4(=, 24), D4(=, 28) : "l"(da), "l"(db));
}

#define G_ROWS 514
__device__ uint4 g_G[64 * G_ROWS * 8];
__device__ uint4 g_GN[64 * 8];
__device__ uint4 g_WN[1152];
#define FS_F2 196608
#define FS_TB (FS_F2 + 8192)
#define FS_NQ (FS_TB + 16384)
#define FS_BAR (FS_NQ + 128)
#define FS_NY (FS_NQ + 1024 + 128)
#define FS_TOTAL (FS_NQ + 3072)
#define F_THREADS 512

DEVI uint32_t cis(int j) {
    const float a = fmaf(__uint_as_float((((j + 1024) << 12) & 0x7FF000) | 0x3F800000), 6.283185307179586f, -9.42477796076938f);
    return pack2(__cosf(a), __sinf(a));
}
DEVI uint32_t cos2(int j0, int j1) {
    const float f = 6.283185307179586f / 2048.f;
    return pack2(__cosf((float)(((j0 + 1024) & 2047) - 1024) * f), __cosf((float)(((j1 + 1024) & 2047) - 1024) * f));
}
DEVI void twid(int j, float& c, float& s) {
    const float a = (float)(((j + 512) & 1023) - 512) * (6.283185307179586f / 1024.f);
    c = __cosf(a) * (1.f / 1024.f);
    s = __sinf(a) * (1.f / 1024.f);
}
template <bool B> struct Bool { static constexpr bool v = B; };
DEVI uint32_t opq(uint32_t& x, uint32_t zero) { OPQ(x); return x; }
DEVI uint32_t tidx() { uint32_t r; asm volatile("mov.u32 %0, %%tid.x;" : "=r"(r)); return r; }
DEVI void tma4d(uint32_t dst, const CUtensorMap* tm, uint32_t bar, int c0, int c1, int c2, int c3) {
    asm volatile("cp.async.bulk.tensor.4d.shared::cluster.global.mbarrier::complete_tx::bytes [%0], [%1, {%3, %4, %5, %6}], [%2];"
                 ::"r"(dst), "l"(tm), "r"(bar), "r"(c0), "r"(c1), "r"(c2), "r"(c3) : "memory");
}
DEVI void tma3s(const CUtensorMap* tm, uint32_t src, int c0, int c1, int c2) {
    asm volatile("cp.async.bulk.tensor.3d.global.shared::cta.bulk_group [%0, {%2, %3, %4}], [%1];" ::"l"(tm), "r"(src), "r"(c0), "r"(c1), "r"(c2) : "memory");
}
DEVI void tma4s(const CUtensorMap* tm, uint32_t src, int c0, int c1, int c2, int c3) {
    asm volatile("cp.async.bulk.tensor.4d.global.shared::cta.bulk_group [%0, {%2, %3, %4, %5}], [%1];"
                 ::"l"(tm), "r"(src), "r"(c0), "r"(c1), "r"(c2), "r"(c3) : "memory");
}
DEVI void bulk_commit() { asm volatile("cp.async.bulk.commit_group;" ::: "memory"); }
DEVI void fence_async() { asm volatile("fence.proxy.async;" ::: "memory"); }
DEVI void fence_smem() { asm volatile("fence.proxy.async.shared::cta;" ::: "memory"); }
DEVI void wgbar(uint32_t q) { asm volatile("bar.sync %0, 128;" ::"r"(q + 2) : "memory"); }
DEVI void grid_arrive(uint32_t* c, uint32_t n) { asm volatile("fence.proxy.async;\nred.release.gpu.global.inc.u32 [%0], %1;" ::"l"(c), "r"(n - 1) : "memory"); }
DEVI void grid_wait(uint32_t* c) {
    uint32_t v;
    int it = 0;
    do {
        asm volatile("ld.acquire.gpu.global.u32 %0, [%1];" : "=r"(v) : "l"(c) : "memory");
        if (++it > (1 << 22)) die(it);
    } while (v);
    fence_async();
}

template <bool INV, class S1, class S2>
DEVI void fft_rows(uint32_t grp, uint32_t q, const uint32_t (&F)[2][4], const float (&tc)[8], const float (&ts)[8], uint32_t so, float fx, uint32_t nq,
                   S1 sh1, S2 sh2) {
    float d[64];
    const uint64_t db = INV ? mkdesc(grp, 1024, 2048) : (mkdesc(grp, 2048, 512) ^ ((uint64_t)3 << 62));
    wg_fence();
    wg_rs128t<0>(d, F[0], db);
    wg_rs128t<1>(d, F[1], db + (INV ? 256 : 64));
    wg_commit();
    SF();
    sh1();
    float4 ny;
    if (INV) ny = lds128f(nq);
    wg_wait<0>();
    if (INV) { d[0] = fmaf(fx, ny.x, d[0]); d[16] = fmaf(fx, ny.y, d[16]); d[32] = fmaf(fx, ny.z, d[32]); d[48] = fmaf(fx, ny.w, d[48]); }
    uint32_t a[2][4][4];
    float e[2][INV ? 16 : 20];
    const uint64_t df = mkdesc(SB0 + FS_F2, 16, 1024);
#pragma unroll
    for (int s = 0; s < 2; s++) {
#pragma unroll
        for (int i = 0; i < 4; i++)
#pragma unroll
            for (int h = 0; h < 2; h++) {
                const float* x = d + (2 * s + h) * 16 + i * 4;
                a[s][i][h] = pack2(fmaf(x[2], ts[2 * i], x[0] * tc[2 * i]), fmaf(x[3], ts[2 * i + 1], x[1] * tc[2 * i + 1]));
                a[s][i][h + 2] = pack2(fmaf(-x[0], ts[2 * i], x[2] * tc[2 * i]), fmaf(-x[1], ts[2 * i + 1], x[3] * tc[2 * i + 1]));
            }
        wg_fence();
#pragma unroll
        for (int i = 0; i < 4; i++) {
            if constexpr (INV) { if (i == 0) wg_rs32<0>(e[s], a[s][i], df); else wg_rs32<1>(e[s], a[s][i], df + i * 2); }
            else { if (i == 0) wg_rs40<0>(e[s], a[s][i], df); else wg_rs40<1>(e[s], a[s][i], df + i * 2); }
        }
        wg_commit();
    }
    SF();
    sh2();
#pragma unroll
    for (int s = 0; s < 2; s++) {
        if (s == 0) wg_wait<1>(); else wg_wait<0>();
        float* x = e[s];
        if constexpr (!INV) {
            x[0] *= fx; x[1] *= fx; x[2] *= fx; x[3] *= fx;
            if (fx != 1.f) sts64(nq + s * 8, pack2(x[16], 0.f), pack2(x[18], 0.f));
        }
        const uint32_t o = grp + (INV ? so + s * 4096 : so ^ (s * 576));
#pragma unroll
        for (int b = 0; b < 2; b++)
            stsm4t(o + b * (INV ? 1024 : 4096), pack2(x[8 * b], x[8 * b + 1]), pack2(x[8 * b + 2], x[8 * b + 3]), pack2(x[8 * b + 4], x[8 * b + 5]),
                   pack2(x[8 * b + 6], x[8 * b + 7]));
    }
}

template <bool INV>
DEVI void fft_gen(uint32_t a, uint32_t n2) {
    const uint32_t tid = tidx(), x = ((tid >> 4) & 24) + (tid & 3), o = (tid & 4) * 128;
    if (INV) {
        const uint32_t r = (tid & 64) * 16 + (tid & 16) * 32 + (tid & 40) * 8 + n2;
        sts128(a + tid * 16, cis(o - r * x), cis(o - (r + 128) * x), cis(o - r * (x + 4)), cis(o - (r + 128) * (x + 4)));
    } else {
        const uint32_t r = 64 * x + n2, k = ((tid >> 2) & 24) + ((tid >> 3) & 3);
        sts128(a + tid * 16, cis(r * k + o), cis(r * (k + 4) + o), cis((r + 256) * k + o), cis((r + 256) * (k + 4) + o));
    }
}
template <bool INV, class S1>
DEVI void fft_cross(uint32_t buf, uint32_t q, uint32_t fa, uint32_t so, uint32_t nq, float (&n)[4], S1 sh1) {
    uint32_t F[4][4];
#pragma unroll
    for (int s = 0; s < 4; s++) { const uint4 v = lds128(fa + s * 2048); F[s][0] = v.x; F[s][1] = v.y; F[s][2] = v.z; F[s][3] = v.w; }
    float d[64];
    const uint64_t db = mkdesc(buf + q * 2048, 1024, 8192), dn = mkdesc(nq, 16, 1024);
    wg_fence();
#pragma unroll
    for (int s = 0; s < 4; s++) { if (s == 0) wg_rs128t<0>(d, F[s], db); else wg_rs128t<1>(d, F[s], db + s * 1024); }
#pragma unroll
    for (int s = 0; s < 4; s++) { if (s == 0) wg_rs8<0>(n, F[s], dn); else wg_rs8<1>(n, F[s], dn + s * 2); }
    wg_commit();
    SF();
    sh1();
    wg_wait<0>();
#pragma unroll
    for (int b = 0; b < 8; b++) {
        const uint32_t o = INV ? so ^ ((b >> 1) * 288 ^ (b & 1) * 32) : (so ^ ((b & 3) * 32)) + (b >> 2) * 1024;
        stsm4(buf + o, pack2(d[8 * b], d[8 * b + 1]), pack2(d[8 * b + 2], d[8 * b + 3]), pack2(d[8 * b + 4], d[8 * b + 5]), pack2(d[8 * b + 6], d[8 * b + 7]));
    }
}

template <bool ODD>
DEVI void fft_filter(uint32_t aw, const float (&e)[32], const float (&o)[32], uint32_t (&u)[4][4], uint32_t (&v)[4][4]) {
#pragma unroll
    for (int s = 0; s < 4; s++) {
        float y[2][2][4];
#pragma unroll
        for (int c = 0; c < 2; c++) {
            float f[4][2];
#pragma unroll
            for (int i = 0; i < 4; i++) {
                const uint32_t a = aw + (i * 32 + s * 8 + c) * 144, x = lds32(a);
                f[i][0] = ODD ? hi_f(x) : lo_f(x);
                f[i][1] = ODD ? lo_f(lds32(a + 4)) : hi_f(x);
            }
#pragma unroll
            for (int h = 0; h < 2; h++) {
                const int x = 8 * s + 2 * h + c;
                const float ar = e[x] + o[x], ai = e[x + 4] + o[x + 4], br = e[x] - o[x], bi = e[x + 4] - o[x + 4];
                const float yr = fmaf(-ai, f[2][h], ar * f[0][h]), yi = fmaf(ar, f[2][h], ai * f[0][h]);
                y[h][c][0] = fmaf(-bi, f[3][h], fmaf(br, f[1][h], yr));
                y[h][c][1] = fmaf(br, f[3][h], fmaf(bi, f[1][h], yi));
                y[h][c][2] = fmaf(2.f, yr, -y[h][c][0]);
                y[h][c][3] = fmaf(2.f, yi, -y[h][c][1]);
            }
        }
#pragma unroll
        for (int h = 0; h < 2; h++) {
            u[s][h] = pack2(y[h][0][0], y[h][1][0]); u[s][h + 2] = pack2(y[h][0][1], y[h][1][1]);
            v[s][h] = pack2(y[h][0][2], y[h][1][2]); v[s][h + 2] = pack2(y[h][0][3], y[h][1][3]);
        }
    }
}

__global__ void __launch_bounds__(F_THREADS, 1)
post_kernel(const __grid_constant__ CUtensorMap tmx, const __grid_constant__ CUtensorMap tmg1, const __grid_constant__ CUtensorMap tmg2,
           const __grid_constant__ CUtensorMap tmwr, const __grid_constant__ CUtensorMap tmwi, const __grid_constant__ CUtensorMap tmy,
           const bf16* __restrict__ wr, const bf16* __restrict__ wi, uint32_t* cnt, uint32_t zero, int nw) {
    extern __shared__ __align__(1024) uint8_t smem[];
    const uint32_t sb = SB0;
    if (smem_u32(smem) != sb) die(1 << 23);
    const uint32_t tid = threadIdx.x, lane = tid & 31, g = lane >> 2, t = lane & 3, j8 = lane & 7, mat = lane >> 3;
    const uint32_t wi_ = __reduce_max_sync(0xFFFFFFFFu, tid >> 5), q = wi_ >> 2, w = wi_ & 3;
    const int cta = blockIdx.x;
    const int nt = cta < 64 ? (64 - cta + nw - 1) / nw : 0;
    const uint32_t bar = sb + FS_BAR;
    if (tid == 0) {
        for (int i = 0; i < 30; i++) mbar_init(bar + i * 8, i < 3 ? 4 : i < 6 ? 16 : i >= 14 && i < 18 ? 2 : 1);
        asm volatile("fence.mbarrier_init.release.cluster;" ::: "memory");
        fence_smem();
    }
    __syncthreads();
#define FT(n)
    FT(0);
#define N2(p) (2 * ((p) & 31) + ((p) >> 5))
#define WLOAD(tk, part) { \
        const uint32_t wd_ = sb + 131072 + q * 18432 + (part) * 9216, wb_ = bar + 112 + q * 8; \
        mbar_expect(wb_, 9216); \
        if ((tk) < 256) tma3d(wd_, (part) ? &tmwi : &tmwr, wb_, ((tk) & 63) * 64, (tk) >> 6, 0); \
        else asm volatile("cp.async.bulk.shared::cluster.global.mbarrier::complete_tx::bytes [%0], [%1], 9216, [%2];" \
                          ::"r"(wd_), "l"(g_WN + (part) * 576), "r"(wb_) : "memory"); }
#define GROW(tk) ((tk) < 256 ? ((tk) >> 5) * 64 + ((tk) & 7) * 8 + (((tk) >> 3) & 3) * 2 : 512)
#define DLOAD(tk, sl) { mbar_expect(bar + 48 + (sl) * 8, 16384); tma3d(sb + (sl) * 16384, &tmg2, bar + 48 + (sl) * 8, 0, GROW(tk), 0); }
#define IO(c) if (w == 3 && (c) && elect())
#define XLOAD1(i, bb) { const uint32_t xb_ = bar + 144 + (bb) * 32 + q * 8; mbar_expect(xb_, 16384); tma4d(sb + (bb) * 65536 + q * 16384, &tmx, xb_, 0, 0, q * 8, N2(cta + (i) * nw)); }
#define GLOAD3(i, bb) { mbar_expect(bar + (bb) * 8, q ? 16384 : 16512); tma3d(sb + (bb) * 65536 + q * 16384, &tmg1, bar + (bb) * 8, 0, q * 128, cta + (i) * nw); \
        if (q == 0) asm volatile("cp.async.bulk.shared::cluster.global.mbarrier::complete_tx::bytes [%0], [%1], 128, [%2];" \
                                 ::"r"(sb + FS_NQ + (bb) * 1024), "l"(g_GN + (cta + (i) * nw) * 8), "r"(bar + (bb) * 8) : "memory"); }
    for (int i = 0; i < 3; i++) IO(i < nt) XLOAD1(i, i);
    for (uint32_t x = tid; x < 40 * 32; x += 512) {
        const uint32_t n = x >> 5, m2 = mat * 8 + t * 2, ri = g & 1;
        const uint32_t c2 = ((n >> 1) & 1) + ((n >> 3) & 1) * 2 + (n & 4) + (n >> 4) * 8;
        const uint32_t v = cos2(m2 * c2 * 64 + ((n & 1) - ri) * 512, (m2 + 1) * c2 * 64 + ((n & 1) - ri) * 512);
        sts32(sb + FS_F2 + n * 128 + ((g ^ (n & 7)) << 4) + t * 4, n < 32 ? v : n == 32 && ri == 0 ? 0xBF003F00u : 0u);
    }
    float tc[8], ts[8];
    uint32_t F[2][4];
    uint32_t c1 = 16 * (w >> 1) + 2 * g + (w & 1);
#pragma unroll
    for (int i = 0; i < 8; i++) {
        twid(c1 * (8 * (i >> 1) + 2 * t + (i & 1)), tc[i], ts[i]);
        const uint32_t m1 = (i >> 1) * 8 + 2 * t;
        F[i >> 2][i & 3] = cos2(c1 * m1 * 64 + (i & 1) * 512, c1 * (m1 + 1) * 64 + (i & 1) * 512);
    }
    {
        const uint32_t kr = (2 * (mat & 1) + (j8 & 1)) ^ ((j8 >> 2) << 1);
        const uint32_t so1 = ((mat >> 1) + 2 * (j8 >> 2)) * 1024 + kr * 128 + (((((j8 >> 1) & 1) * 4 + w) ^ kr) << 4);
        const uint32_t so2 = (2 * w + (mat & 1)) * 8192 + q * 2048 + j8 * 128 + (((mat >> 1) ^ j8) << 4);
        uint32_t so = so1 << 16 | so2;
        const float fx = (tid & 127) == 0 ? 0.5f : 1.f;
        fft_gen<false>(sb + FS_TB, N2(cta));
        fence_smem();
        bsync<1, 512>();
        FT(1);
        int b = 0, bp = 2, ph = 0;
        if (nt) mwait(bar + 144 + q * 8, 0);
        __syncwarp();
        auto step = [&](auto first, auto last, const int i) {
            const uint32_t p = cta + i * nw, bn = 3 - b - bp, tb = (i & 1) * 8192;
            const uint32_t grp = sb + b * 65536 + q * 16384, nq = sb + FS_NQ + b * 1024 + q * 32;
            auto sa = [&]() {
                if constexpr (!decltype(first)::v) {
                    fence_smem();
                    __syncwarp();
                    if (elect()) mbar_arrive(bar + 24);
                }
                IO(i > 1) {
                    mwait(bar + 32, i & 1);
                    tma3s(&tmg1, sb + bn * 65536 + q * 16384, 0, q * 128, p - 2 * nw);
                    bulk_commit();
                }
            };
            auto sb_ = [&]() { if constexpr (!decltype(first)::v) mwait(bar + 24, (i - 1) & 1); };
            if constexpr (!decltype(last)::v) fft_rows<false>(grp, q, F, tc, ts, opq(so, zero) >> 16, fx, nq, sa, sb_);
            else { sa(); __syncwarp(); sb_(); __syncwarp(); }
            if constexpr (!decltype(first)::v) {
                float n[4];
                fft_cross<false>(sb + bp * 65536, q, sb + FS_TB + 8192 - tb + (((tidx() & 127) ^ (q & 1)) << 4), opq(so, zero) & 0xFFFF, sb + FS_NQ + bp * 1024, n, [&]() {
                    fft_gen<false>(sb + FS_TB + tb, N2(p));
                    IO(i >= 2 && i + 1 < nt) {
                        asm volatile("cp.async.bulk.wait_group.read 0;" ::: "memory");
                        XLOAD1(i + 1, bn);
                    }
                });
                if (q == 0) {
                    const uint32_t x = tidx();
                    bf16* z = (bf16*)(g_G + ((p - nw) * G_ROWS + 512) * 8) + (x & 4) * 16 + ((x >> 2) & 24) + ((x >> 3) & 3);
                    asm volatile("{\n.reg .pred p;\n.reg .b16 a, b;\nsetp.eq.u32 p, %2, 0;\nmov.b32 {a, b}, %1;\n@p st.global.u16 [%0], a;\n@p st.global.u16 [%0+8], b;\n}"
                                 ::"l"(z), "r"(pack2(n[0], n[2])), "r"(x & 3) : "memory");
                }
            }
            if constexpr (!decltype(last)::v) {
                fft_rows<false>(grp + 8192, q, F, tc, ts, opq(so, zero) >> 16, fx, nq + 16, [&]() {
                    if constexpr (!decltype(first)::v) {
                        fence_smem();
                        __syncwarp();
                        if (elect()) mbar_arrive(bar + 32);
                    }
                    if ((w == 1 || w == 2) && elect())
                        asm volatile("cp.async.bulk.prefetch.L2.global [%0], 8208;" ::"l"((w == 1 ? wr : wi) + (p * 4 + q) * 4104) : "memory");
                }, [&]() { if (i + 1 < nt) mwait(bar + 144 + bn * 32 + q * 8, bn ? ph : ph ^ 1); });
                bp = b;
                if (++b == 3) { b = 0; ph ^= 1; }
            }
        };
        if (nt) {
            step(Bool<true>(), Bool<false>(), 0);
#pragma unroll 1
            for (int i = 1; i < nt; i++) step(Bool<false>(), Bool<false>(), i);
            step(Bool<false>(), Bool<true>(), nt);
        }
        for (uint32_t x = cta * 512 + tid; x < 4096; x += nw * 512)
            ((bf16*)g_WN)[(x >> 5) * 72 + (x & 16) + (x & 7) * 2 + ((x >> 3) & 1)] = (x < 2048 ? wr : wi)[(x & 2047) * 513 + 512];
        FT(2);
        fence_async();
        bsync<1, 512>();
        IO(nt) { tma3s(&tmg1, sb + bp * 65536 + q * 16384, 0, q * 128, cta + (nt - 1) * nw); bulk_commit(); }
    }
    for (uint32_t x = tid; x < 128 * 32; x += 512) {
        const uint32_t n = (x >> 5) & 63, a = x & 31, k2 = (n >> 4) * 8 + (n & 7);
        sts32(sb + FS_TB + (x >> 5) * 128 + (((a >> 2) ^ (n & 7)) << 4) + (a & 3) * 4, cis((2 * a + (x >> 11)) * k2 * 32 + (n & 8) * 64));
    }
    fence_smem();
    bsync<1, 512>();
    IO(true) {
        asm volatile("cp.async.bulk.wait_group 0;" ::: "memory");
        grid_arrive(cnt, 4 * nw);
        grid_wait(cnt);
        const int tk = cta + q * nw;
        if (tk <= 256) { DLOAD(tk, q); WLOAD(tk, 0); WLOAD(tk, 1); }
    }
    __syncwarp();
    {
        const uint32_t lo = j8 * 128 + (((2 * w + (mat & 1)) ^ j8) << 4);
        const uint32_t aw = sb + 131072 + q * 18432 + t * 288 + w * 32 + g * 4;
        const uint64_t df = mkdesc(sb + FS_TB, 16, 1024);
        const uint64_t da = mkdesc(sb + q * 16384, 16, 1024);
        const uint32_t buf = sb + 65536 + q * 16384;
        int i = 0, tk = cta + q * nw;
        if (tk <= 256) mwait(bar + 48 + q * 8, 0);
        FT(3);
#pragma unroll 1
        for (; tk <= 256; tk += 4 * nw, i++) {
            const bool more = tk + 4 * nw <= 256;
            float e[32], o[32];
            wg_fence();
#pragma unroll
            for (int s = 0; s < 4; s++) { if (s == 0) wg_ss64a<0>(e, da, df); else wg_ss64a<1>(e, da + s * 128, df + s * 2); }
#pragma unroll
            for (int s = 0; s < 4; s++) { if (s == 0) wg_ss64a<0>(o, da + 512, df + 512); else wg_ss64a<1>(o, da + 512 + s * 128, df + 512 + s * 2); }
            wg_commit();
            SF();
            if (i > 0) {
                fence_smem();
                wgbar(q);
                IO(true) { tma3s(&tmg2, buf, 0, GROW(tk - 4 * nw), 0); bulk_commit(); }
            }
            if (w == 2 && more && elect()) mbar_expect(bar + 48 + q * 8, 16384);
            const int gr = GROW(tk + 4 * nw);
            mwait(bar + 112 + q * 8, i & 1);
            wg_wait<0>();
            if (w == 2 && more && elect()) tma3d(sb + q * 16384, &tmg2, bar + 48 + q * 8, 0, gr, 0);
            uint32_t u[4][4], v[4][4];
            if (tk & 8) fft_filter<true>(aw + (tk & 48) / 4, e, o, u, v);
            else fft_filter<false>(aw + (tk & 48) / 4, e, o, u, v);
            wg_fence();
#pragma unroll
            for (int s = 0; s < 4; s++) { if (s == 0) wg_rs64t<0>(e, u[s], df); else wg_rs64t<1>(e, u[s], df + s * 128); }
#pragma unroll
            for (int s = 0; s < 4; s++) { if (s == 0) wg_rs64t<0>(o, v[s], df + 512); else wg_rs64t<1>(o, v[s], df + 512 + s * 128); }
            wg_commit();
            SF();
            IO(true) asm volatile("cp.async.bulk.wait_group.read 0;" ::: "memory");
            wgbar(q);
            if (more) {
                if ((w == 1 || w == 2) && elect()) WLOAD(tk + 4 * nw, w - 1);
                mwait(bar + 48 + q * 8, (i + 1) & 1);
            }
            wg_wait<0>();
#pragma unroll
            for (int s = 0; s < 4; s++) {
                const uint32_t a = buf + (mat >> 1) * 1024 + lo + s * 2048;
                stsm4t(a, pack2(e[8 * s], e[8 * s + 1]), pack2(e[8 * s + 2], e[8 * s + 3]), pack2(e[8 * s + 4], e[8 * s + 5]), pack2(e[8 * s + 6], e[8 * s + 7]));
                stsm4t(a + 8192, pack2(o[8 * s], o[8 * s + 1]), pack2(o[8 * s + 2], o[8 * s + 3]), pack2(o[8 * s + 4], o[8 * s + 5]), pack2(o[8 * s + 6], o[8 * s + 7]));
            }
            if (tk == 256 && w < 2) {
                uint32_t* z = (uint32_t*)g_GN + t * 32 + w * 16 + g;
#pragma unroll
                for (int s = 0; s < 16; s++) {
                    z[(s >> 1) * 128 + (s & 1) * 8] = pack2(e[2 * s], e[2 * s + 1]);
                    z[(s >> 1) * 128 + (s & 1) * 8 + 1024] = pack2(o[2 * s], o[2 * s + 1]);
                }
                fence_async();
            }
        }
        fence_smem();
        wgbar(q);
        IO(true) {
            if (i > 0) { tma3s(&tmg2, buf, 0, GROW(tk - 4 * nw), 0); bulk_commit(); }
            asm volatile("cp.async.bulk.wait_group 0;" ::: "memory");
            grid_arrive(cnt + 1, 4 * nw);
        }
    }
    FT(4);
    bsync<1, 512>();
    {
        for (uint32_t n = wi_; n < 32; n += 16) {
            const uint32_t cl = (mat >> 1) * 16 + t * 4 + (mat & 1), mh = ((n >> 3) & 1) + (n & 7) * 2 + (n & 16);
            sts32(sb + FS_F2 + n * 128 + ((g ^ (n & 7)) << 4) + t * 4, cos2(cl * mh * 64 + (g & 1) * 512, (cl + 2) * mh * 64 + (g & 1) * 512));
        }
        fence_smem();
        c1 = 8 * w + g;
#pragma unroll
        for (int i = 0; i < 8; i++) {
            twid(-c1 * (16 * (i >> 2) + 4 * t + 2 * (i & 1) + ((i >> 1) & 1)), tc[i], ts[i]);
            F[i >> 2][i & 3] = cis((i & 1) * 512 - c1 * ((i >> 1) * 4 + (t ^ (q & 1))) * 64);
        }
        const uint32_t kr = (j8 & 1) ^ ((j8 >> 2) << 1);
        const uint32_t so2 = ((w >> 1) * 4 + (j8 >> 2) * 2 + (w & 1)) * 8192 + (2 * q + (mat & 1)) * 1024 + kr * 128 + (((((j8 >> 1) & 1) * 4 + (mat >> 1)) ^ kr) << 4);
        const uint32_t so1 = (mat & 1) * 2048 + j8 * 128 + ((((mat >> 1) * 4 + w) ^ j8) << 4);
        uint32_t so = so1 << 16 | so2;
        const float fx = t ? 0.f : (g & 1) ? -1.f : 1.f;
        fft_gen<true>(sb + FS_TB, N2(cta));
        bsync<1, 512>();
        IO(true) grid_wait(cnt + 1);
        for (int i = 0; i < 3; i++) IO(i < nt) GLOAD3(i, i);
        __syncwarp();
        int b = 0, bp = 2, ph = 0;
        auto step = [&](auto first, auto last, const int i) {
            const uint32_t p = cta + i * nw, bn = 3 - b - bp, tb = (i & 1) * 8192;
            const uint32_t grp = sb + bp * 65536 + q * 16384, ny = sb + FS_NY + bp * 128 + q * 32;
            auto sb_ = [&]() { if constexpr (!decltype(last)::v) mwait(bar + b * 8, ph); };
            if constexpr (!decltype(first)::v) {
                fft_rows<true>(grp, q, F, tc, ts, opq(so, zero) >> 16, fx, ny, [&]() {
                    if (i > 1) {
                        fence_smem();
                        wgbar(q);
                        IO(true) { tma4s(&tmy, sb + bn * 65536 + q * 16384, 0, 0, q * 8, N2(p - 2 * nw)); bulk_commit(); }
                    }
                }, sb_);
            } else { sb_(); __syncwarp(); }
            if constexpr (decltype(first)::v) FT(5);
            if constexpr (!decltype(last)::v) {
                float n[4];
                fft_cross<true>(sb + b * 65536, q, sb + FS_TB + tb + (tidx() & 127) * 16, opq(so, zero) & 0xFFFF, sb + FS_NQ + b * 1024, n, [&]() {
                    fft_gen<true>(sb + FS_TB + 8192 - tb, N2(p + nw));
                    IO(i >= 2 && i + 1 < nt) {
                        asm volatile("cp.async.bulk.wait_group.read 0;" ::: "memory");
                        GLOAD3(i + 1, bn);
                    }
                });
                if (q == 0) {
                    const uint32_t x = tidx(), a = sb + FS_NY + b * 128 + (x & 64) + (x & 16) * 2 + ((x & 40) >> 1);
                    if ((x & 7) == 0) { sts32f(a, n[0]); sts32f(a + 8, n[2]); }
                }
            }
            auto sc = [&]() {
                if constexpr (!decltype(last)::v) {
                    fence_smem();
                    __syncwarp();
                    if (elect()) mbar_arrive(bar + 24);
                }
            };
            auto sd = [&]() { if constexpr (!decltype(last)::v) mwait(bar + 24, (nt + i) & 1); };
            if constexpr (!decltype(first)::v) fft_rows<true>(grp + 8192, q, F, tc, ts, opq(so, zero) >> 16, fx, ny + 16, sc, sd);
            else { sc(); __syncwarp(); sd(); __syncwarp(); }
            if constexpr (!decltype(last)::v) {
                bp = b;
                if (++b == 3) { b = 0; ph ^= 1; }
            }
        };
        if (nt) {
            step(Bool<true>(), Bool<false>(), 0);
#pragma unroll 1
            for (int i = 1; i < nt; i++) step(Bool<false>(), Bool<false>(), i);
            step(Bool<false>(), Bool<true>(), nt);
        }
        fence_smem();
        wgbar(q);
        IO(nt) { tma4s(&tmy, sb + bp * 65536 + q * 16384, 0, 0, q * 8, N2(cta + (nt - 1) * nw)); bulk_commit(); }
        FT(6);
        IO(true) asm volatile("cp.async.bulk.wait_group 0;" ::: "memory");
    }
}

typedef CUresult (*EncodeFn)(CUtensorMap*, CUtensorMapDataType, cuuint32_t, void*, const cuuint64_t*, const cuuint64_t*,
                             const cuuint32_t*, const cuuint32_t*, CUtensorMapInterleave, CUtensorMapSwizzle,
                             CUtensorMapL2promotion, CUtensorMapFloatOOBfill);

static void make_map(EncodeFn enc, CUtensorMap* m, const void* ptr, int rank, const cuuint64_t* dims, const cuuint64_t* strides,
                     const cuuint32_t* box, CUtensorMapSwizzle sw = CU_TENSOR_MAP_SWIZZLE_128B) {
    cuuint32_t es[4] = {1, 1, 1, 1};
    CUresult r = enc(m, CU_TENSOR_MAP_DATA_TYPE_BFLOAT16, rank, (void*)ptr, dims, strides, box, es, CU_TENSOR_MAP_INTERLEAVE_NONE,
                     sw, CU_TENSOR_MAP_L2_PROMOTION_L2_256B, CU_TENSOR_MAP_FLOAT_OOB_FILL_NONE);
    if (r != CUDA_SUCCESS) fprintf(stderr, "tensor map encode failed: %d\n", (int)r);
}

extern "C" void kernel_launch(void* const* d_in, const int* in_sizes, int n_in, void* d_out, int out_size) {
    const bf16* A_x = (const bf16*)d_in[0];
    const bf16* A_mem0 = (const bf16*)d_in[1];
    const bf16* A_Wq = (const bf16*)d_in[2];
    const bf16* A_Wk = (const bf16*)d_in[3];
    const bf16* A_Wv = (const bf16*)d_in[4];
    const bf16* A_Wo = (const bf16*)d_in[5];
    const bf16* B_x = (const bf16*)d_in[7];
    const bf16* B_wr = (const bf16*)d_in[8];
    const bf16* B_wi = (const bf16*)d_in[9];
    bf16* out = (bf16*)d_out;

    static EncodeFn enc = nullptr;
    static void *pxs = nullptr, *pg = nullptr;
    static int ncl = 64;
    if (!enc) {
        cudaDriverEntryPointQueryResult qr;
        void* fn = nullptr;
        cudaGetDriverEntryPoint("cuTensorMapEncodeTiled", &fn, cudaEnableDefault, &qr);
        enc = (EncodeFn)fn;
        cudaFuncSetAttribute(chain_kernel, cudaFuncAttributeMaxDynamicSharedMemorySize, SM_TOTAL);
        cudaFuncSetAttribute(post_kernel, cudaFuncAttributeMaxDynamicSharedMemorySize, FS_TOTAL);
        cudaGetSymbolAddress(&pxs, g_xs);
        cudaGetSymbolAddress(&pg, g_G);
        cudaLaunchConfig_t lc = {};
        cudaLaunchAttribute at;
        at.id = cudaLaunchAttributeClusterDimension;
        at.val.clusterDim.x = 2; at.val.clusterDim.y = 1; at.val.clusterDim.z = 1;
        lc.gridDim = dim3(132); lc.blockDim = dim3(384); lc.dynamicSmemBytes = SM_TOTAL; lc.attrs = &at; lc.numAttrs = 1;
        int nc = 0;
        if (cudaOccupancyMaxActiveClusters(&nc, chain_kernel, &lc) == cudaSuccess && nc > 64) ncl = nc < 66 ? nc : 66;
    }
    CUtensorMap tmq, tmk, tmv, tmo, tmx, tmb, tmy;
    {
        cuuint64_t d[3] = {64, DM, HD / 64}, st[2] = {HD * 2, 128};
        cuuint32_t bx[3] = {64, 64, 2};
        make_map(enc, &tmq, A_Wq, 3, d, st, bx);
        make_map(enc, &tmk, A_Wk, 3, d, st, bx);
        make_map(enc, &tmv, A_Wv, 3, d, st, bx);
    }
    {
        cuuint64_t d[2] = {DM, HD}, st[1] = {DM * 2};
        cuuint32_t bx[2] = {64, 16}, bx1[2] = {64, 128}, bx2[3] = {64, 64, 2};
        make_map(enc, &tmo, A_Wo, 2, d, st, bx1);
        cuuint64_t d2[3] = {64, HD, DM / 64}, st2[2] = {DM * 2, 128}, d3[2] = {DM, SEQ}, st3[1] = {DM * 4};
        make_map(enc, &tmb, A_Wo, 3, d2, st2, bx2);
        make_map(enc, &tmy, out, 2, d3, st3, bx);
    }
    {
        cuuint64_t d[3] = {64, SEQ, DM / 64}, st[2] = {DM * 2, 128};
        cuuint32_t bx[3] = {64, 8, 4};
        make_map(enc, &tmx, A_x, 3, d, st, bx);
    }
    CUtensorMap fx, fg1, fg2, fwr, fwi, fy;
    {
        cuuint64_t d[4] = {32, 32, 32, 64}, st[3] = {64, 64 * DM * 2, DM * 2};
        cuuint32_t bx[4] = {32, 32, 8, 1};
        make_map(enc, &fx, B_x, 4, d, st, bx, CU_TENSOR_MAP_SWIZZLE_64B);
        cuuint64_t d2[4] = {64, 16, 32, 64}, st2[3] = {128, 64 * 4096, 4096};
        cuuint32_t bx2[4] = {64, 16, 8, 1};
        make_map(enc, &fy, out + DM, 4, d2, st2, bx2);
    }
    {
        cuuint64_t d[3] = {64, G_ROWS, 64}, st[2] = {128, G_ROWS * 128};
        cuuint32_t bx[3] = {64, 128, 1}, bx2[3] = {64, 2, 64};
        make_map(enc, &fg1, pg, 3, d, st, bx);
        make_map(enc, &fg2, pg, 3, d, st, bx2);
        cuuint64_t d2[3] = {8 * 513, 4, 64}, st2[2] = {8 * 513 * 2, 32 * 513 * 2};
        cuuint32_t bx3[3] = {72, 1, 64};
        make_map(enc, &fwr, B_wr, 3, d2, st2, bx3, CU_TENSOR_MAP_SWIZZLE_NONE);
        make_map(enc, &fwi, B_wi, 3, d2, st2, bx3, CU_TENSOR_MAP_SWIZZLE_NONE);
    }
    cudaStream_t st = cudaStreamPerThread;
    const uint64_t xs = ((uint64_t)pxs + XS_BYTES - 1) & ~(uint64_t)(XS_BYTES - 1);
    chain_kernel<<<2 * ncl, 384, SM_TOTAL, st>>>(tmq, tmk, tmv, tmo, tmx, tmb, tmy, A_mem0, A_x, (uint32_t)xs, (uint32_t)(xs >> 32), 0u, NSEG, out);
    int nw = ncl == 66 ? 4 : 64;
    cudaLaunchConfig_t lc = {};
    cudaLaunchAttribute at;
    at.id = cudaLaunchAttributeProgrammaticStreamSerialization;
    at.val.programmaticStreamSerializationAllowed = 1;
    lc.gridDim = dim3(nw); lc.blockDim = dim3(F_THREADS); lc.dynamicSmemBytes = FS_TOTAL; lc.stream = st; lc.attrs = &at; lc.numAttrs = 1;
    cudaLaunchKernelEx(&lc, post_kernel, fx, fg1, fg2, fwr, fwi, fy, B_wr, B_wi, (uint32_t*)(xs + XO_TK + 256), 0u, nw);
}
```

```cpp
#include <cuda_runtime.h>
#include <cuda_bf16.h>
#include <cuda.h>
#include <stdint.h>
#include <stdio.h>

typedef __nv_bfloat16 bf16;

#define SEQ 2048
#define DM 1024
#define NH 32
#define DH 128
#define NSEG 64
#define HD (NH * DH)

#define XS_BYTES (32u << 20)
__device__ uint4 g_xs[2 * XS_BYTES / 16];
#define XO_R 0u
#define XO_PB (1u << 18)
#define XO_FL (XO_PB + 32768u)
#define XO_TK (XO_FL + 4096u)
#define XO_CQK (1u << 20)
#define XO_CV (2u << 20)
#define XO_XG (4u << 20)
#define XO_OX (16u << 20)
#define GSYNC(n)
#define PG(n)

#define DEVI __device__ __forceinline__

DEVI void die(int it) { asm volatile("st.shared.u32 [%0], %0;" ::"r"(it) : "memory"); }
DEVI uint32_t smem_u32(const void* p) { return (uint32_t)__cvta_generic_to_shared(p); }
DEVI void mbar_init(uint32_t bar, uint32_t cnt) { asm volatile("mbarrier.init.shared::cta.b64 [%0], %1;" ::"r"(bar), "r"(cnt) : "memory"); }
DEVI void mbar_expect(uint32_t bar, uint32_t bytes) { asm volatile("mbarrier.arrive.expect_tx.shared::cta.b64 _, [%0], %1;" ::"r"(bar), "r"(bytes) : "memory"); }
DEVI void mbar_arrive(uint32_t bar) { asm volatile("mbarrier.arrive.shared::cta.b64 _, [%0];" ::"r"(bar) : "memory"); }
DEVI void mbar_wait(uint32_t bar, uint32_t parity) {
    uint32_t done;
    int it = 0;
    do {
        asm volatile("{\n.reg .pred p;\nmbarrier.try_wait.parity.shared::cta.b64 p, [%1], %2;\nselp.u32 %0, 1, 0, p;\n}\n"
                     : "=r"(done) : "r"(bar), "r"(parity) : "memory");
        if (++it > (1 << 22)) die(it);
    } while (!done);
}
DEVI void tma2d(uint32_t dst, const CUtensorMap* tm, uint32_t bar, int c0, int c1) {
    asm volatile("cp.async.bulk.tensor.2d.shared::cluster.global.mbarrier::complete_tx::bytes [%0], [%1, {%3, %4}], [%2];"
                 ::"r"(dst), "l"(tm), "r"(bar), "r"(c0), "r"(c1) : "memory");
}
DEVI void tma3d(uint32_t dst, const CUtensorMap* tm, uint32_t bar, int c0, int c1, int c2) {
    asm volatile("cp.async.bulk.tensor.3d.shared::cluster.global.mbarrier::complete_tx::bytes [%0], [%1, {%3, %4, %5}], [%2];"
                 ::"r"(dst), "l"(tm), "r"(bar), "r"(c0), "r"(c1), "r"(c2) : "memory");
}
DEVI void bulk_g2s(uint32_t dst, uint32_t lo, uint32_t hi, uint32_t bytes, uint32_t bar) {
    asm volatile("{\n.reg .b64 a;\nmov.b64 a, {%1,%2};\ncp.async.bulk.shared::cluster.global.mbarrier::complete_tx::bytes [%0], [a], %3, [%4];\n}"
                 ::"r"(dst), "r"(lo), "r"(hi), "r"(bytes), "r"(bar) : "memory");
}
DEVI void bulk_s2g(uint32_t lo, uint32_t hi, uint32_t src, uint32_t bytes) {
    asm volatile("{\n.reg .b64 a;\nmov.b64 a, {%0,%1};\ncp.async.bulk.global.shared::cta.bulk_group [a], [%2], %3;\ncp.async.bulk.commit_group;\n}"
                 ::"r"(lo), "r"(hi), "r"(src), "r"(bytes) : "memory");
}
DEVI void bulk_red(uint32_t lo, uint32_t hi, uint32_t src, uint32_t bytes) {
    asm volatile("{\n.reg .b64 a;\nmov.b64 a, {%0,%1};\ncp.reduce.async.bulk.global.shared::cta.bulk_group.add.noftz.bf16 [a], [%2], %3;\ncp.async.bulk.commit_group;\n}"
                 ::"r"(lo), "r"(hi), "r"(src), "r"(bytes) : "memory");
}
DEVI bool elect() {
    uint32_t p;
    asm volatile("{\n.reg .pred P;\nelect.sync _|P, 0xFFFFFFFF;\nselp.u32 %0, 1, 0, P;\n}" : "=r"(p));
    return p != 0;
}
DEVI void ldsm4(uint32_t (&r)[4], uint32_t a) {
    asm volatile("ldmatrix.sync.aligned.m8n8.x4.shared.b16 {%0,%1,%2,%3}, [%4];" : "=r"(r[0]), "=r"(r[1]), "=r"(r[2]), "=r"(r[3]) : "r"(a) : "memory");
}
DEVI void ldsm4t(uint32_t (&r)[4], uint32_t a) {
    asm volatile("ldmatrix.sync.aligned.m8n8.x4.trans.shared.b16 {%0,%1,%2,%3}, [%4];" : "=r"(r[0]), "=r"(r[1]), "=r"(r[2]), "=r"(r[3]) : "r"(a) : "memory");
}
DEVI void ldsm2t(uint32_t (&r)[2], uint32_t a) {
    asm volatile("ldmatrix.sync.aligned.m8n8.x2.trans.shared.b16 {%0,%1}, [%2];" : "=r"(r[0]), "=r"(r[1]) : "r"(a) : "memory");
}
DEVI void ldsm2(uint32_t (&r)[2], uint32_t a) {
    asm volatile("ldmatrix.sync.aligned.m8n8.x2.shared.b16 {%0,%1}, [%2];" : "=r"(r[0]), "=r"(r[1]) : "r"(a) : "memory");
}
DEVI void stsm4t(uint32_t a, uint32_t r0, uint32_t r1, uint32_t r2, uint32_t r3) {
    asm volatile("stmatrix.sync.aligned.m8n8.x4.trans.shared.b16 [%0], {%1,%2,%3,%4};" ::"r"(a), "r"(r0), "r"(r1), "r"(r2), "r"(r3) : "memory");
}
DEVI uint32_t ldsm1(uint32_t a) {
    uint32_t r;
    asm volatile("ldmatrix.sync.aligned.m8n8.x1.shared.b16 {%0}, [%1];" : "=r"(r) : "r"(a) : "memory");
    return r;
}
DEVI void stsm4(uint32_t a, uint32_t r0, uint32_t r1, uint32_t r2, uint32_t r3) {
    asm volatile("stmatrix.sync.aligned.m8n8.x4.shared.b16 [%0], {%1,%2,%3,%4};" ::"r"(a), "r"(r0), "r"(r1), "r"(r2), "r"(r3) : "memory");
}
DEVI void stsm2(uint32_t a, uint32_t r0, uint32_t r1) {
    asm volatile("stmatrix.sync.aligned.m8n8.x2.shared.b16 [%0], {%1,%2};" ::"r"(a), "r"(r0), "r"(r1) : "memory");
}
DEVI uint32_t movm(uint32_t a) {
    uint32_t d;
    asm volatile("movmatrix.sync.aligned.m8n8.trans.b16 %0, %1;" : "=r"(d) : "r"(a));
    return d;
}
DEVI void mma16(float (&d)[4], uint32_t a0, uint32_t a1, uint32_t a2, uint32_t a3, uint32_t b0, uint32_t b1) {
    asm volatile("mma.sync.aligned.m16n8k16.row.col.f32.bf16.bf16.f32 {%0,%1,%2,%3}, {%4,%5,%6,%7}, {%8,%9}, {%0,%1,%2,%3};"
                 : "+f"(d[0]), "+f"(d[1]), "+f"(d[2]), "+f"(d[3]) : "r"(a0), "r"(a1), "r"(a2), "r"(a3), "r"(b0), "r"(b1));
}
DEVI void mma16z(float (&d)[4], uint32_t a0, uint32_t a1, uint32_t a2, uint32_t a3, uint32_t b0, uint32_t b1) {
    asm volatile("mma.sync.aligned.m16n8k16.row.col.f32.bf16.bf16.f32 {%0,%1,%2,%3}, {%4,%5,%6,%7}, {%8,%9}, {%10,%10,%10,%10};"
                 : "=f"(d[0]), "=f"(d[1]), "=f"(d[2]), "=f"(d[3]) : "r"(a0), "r"(a1), "r"(a2), "r"(a3), "r"(b0), "r"(b1), "f"(0.f));
}
DEVI void mma8(float (&d)[4], uint32_t a0, uint32_t a1, uint32_t b0) {
    asm volatile("mma.sync.aligned.m16n8k8.row.col.f32.bf16.bf16.f32 {%0,%1,%2,%3}, {%4,%5}, {%6}, {%0,%1,%2,%3};"
                 : "+f"(d[0]), "+f"(d[1]), "+f"(d[2]), "+f"(d[3]) : "r"(a0), "r"(a1), "r"(b0));
}
DEVI void mma8z(float (&d)[4], uint32_t a0, uint32_t a1, uint32_t b0) {
    asm volatile("mma.sync.aligned.m16n8k8.row.col.f32.bf16.bf16.f32 {%0,%1,%2,%3}, {%4,%5}, {%6}, {%7,%7,%7,%7};"
                 : "=f"(d[0]), "=f"(d[1]), "=f"(d[2]), "=f"(d[3]) : "r"(a0), "r"(a1), "r"(b0), "f"(0.f));
}
DEVI uint32_t pack2(float lo, float hi) {
    uint32_t r;
    asm("cvt.rn.bf16x2.f32 %0, %1, %2;" : "=r"(r) : "f"(hi), "f"(lo));
    return r;
}
DEVI uint32_t hadd2(uint32_t a, uint32_t b) {
    uint32_t r;
    asm("add.rn.bf16x2 %0, %1, %2;" : "=r"(r) : "r"(a), "r"(b));
    return r;
}
DEVI float lo_f(uint32_t x) { return __uint_as_float(x << 16); }
DEVI float hi_f(uint32_t x) { return __uint_as_float(x & 0xFFFF0000u); }
template <uint32_t OFF> DEVI uint4 ldg4(uint32_t lo, uint32_t hi) {
    uint4 v;
    asm volatile("{\n.reg .b64 a;\nmov.b64 a, {%4,%5};\nld.relaxed.gpu.global.v4.u32 {%0,%1,%2,%3}, [a+%6];\n}"
                 : "=r"(v.x), "=r"(v.y), "=r"(v.z), "=r"(v.w) : "r"(lo), "r"(hi), "n"(OFF) : "memory");
    return v;
}
template <uint32_t OFF> DEVI uint2 ldg2(uint32_t lo, uint32_t hi) {
    uint2 v;
    asm volatile("{\n.reg .b64 a;\nmov.b64 a, {%2,%3};\nld.relaxed.gpu.global.v2.u32 {%0,%1}, [a+%4];\n}"
                 : "=r"(v.x), "=r"(v.y) : "r"(lo), "r"(hi), "n"(OFF) : "memory");
    return v;
}
template <uint32_t OFF> DEVI uint32_t ldg1(uint32_t lo, uint32_t hi) {
    uint32_t v;
    asm volatile("{\n.reg .b64 a;\nmov.b64 a, {%1,%2};\nld.relaxed.gpu.global.u32 %0, [a+%3];\n}" : "=r"(v) : "r"(lo), "r"(hi), "n"(OFF) : "memory");
    return v;
}
template <uint32_t OFF> DEVI void stg1(uint32_t lo, uint32_t hi, uint32_t a) {
    asm volatile("{\n.reg .b64 a;\nmov.b64 a, {%0,%1};\nst.relaxed.gpu.global.u32 [a+%3], %2;\n}" ::"r"(lo), "r"(hi), "r"(a), "n"(OFF) : "memory");
}
template <uint32_t OFF> DEVI void stg4(uint32_t lo, uint32_t hi, uint32_t a, uint32_t b, uint32_t c, uint32_t d) {
    asm volatile("{\n.reg .b64 a;\nmov.b64 a, {%0,%1};\nst.relaxed.gpu.global.v4.u32 [a+%6], {%2,%3,%4,%5};\n}"
                 ::"r"(lo), "r"(hi), "r"(a), "r"(b), "r"(c), "r"(d), "n"(OFF) : "memory");
}
template <uint32_t OFF> DEVI void stg2(uint32_t lo, uint32_t hi, uint32_t a, uint32_t b) {
    asm volatile("{\n.reg .b64 a;\nmov.b64 a, {%0,%1};\nst.relaxed.gpu.global.v2.u32 [a+%4], {%2,%3};\n}"
                 ::"r"(lo), "r"(hi), "r"(a), "r"(b), "n"(OFF) : "memory");
}
DEVI uint32_t tagx2(uint32_t a, uint32_t b, uint32_t t) { uint32_t r; asm("lop3.b32 %0, %1, %2, %3, 0x7E;" : "=r"(r) : "r"(a), "r"(b), "r"(t)); return r; }
DEVI uint32_t tagx1(uint32_t a, uint32_t b, uint32_t t) { uint32_t r; asm("lop3.b32 %0, %1, %2, %3, 0xF6;" : "=r"(r) : "r"(a), "r"(b), "r"(t)); return r; }
DEVI uint32_t or3(uint32_t a, uint32_t b, uint32_t c) { uint32_t r; asm("lop3.b32 %0, %1, %2, %3, 0xFE;" : "=r"(r) : "r"(a), "r"(b), "r"(c)); return r; }
DEVI bool any_bad(uint32_t x) { return __any_sync(0xFFFFFFFFu, (x & 1u) != 0); }
DEVI uint32_t settag(uint32_t x, uint32_t tag) { return (x & ~1u) | tag; }
DEVI void sts32f(uint32_t a, float v) { asm volatile("st.shared.f32 [%0], %1;" ::"r"(a), "f"(v) : "memory"); }
DEVI void sts32(uint32_t a, uint32_t v) { asm volatile("st.shared.u32 [%0], %1;" ::"r"(a), "r"(v) : "memory"); }
DEVI void sts16(uint32_t a, uint32_t v) { asm volatile("st.shared.u16 [%0], %1;" ::"r"(a), "h"((unsigned short)v) : "memory"); }
DEVI void sts64(uint32_t a, uint32_t x, uint32_t y) { asm volatile("st.shared.v2.u32 [%0], {%1,%2};" ::"r"(a), "r"(x), "r"(y) : "memory"); }
DEVI void sts128(uint32_t a, uint32_t x, uint32_t y, uint32_t z, uint32_t w) {
    asm volatile("st.shared.v4.u32 [%0], {%1,%2,%3,%4};" ::"r"(a), "r"(x), "r"(y), "r"(z), "r"(w) : "memory");
}
DEVI float4 lds128f(uint32_t a) {
    float4 v;
    asm volatile("ld.shared.v4.f32 {%0,%1,%2,%3}, [%4];" : "=f"(v.x), "=f"(v.y), "=f"(v.z), "=f"(v.w) : "r"(a) : "memory");
    return v;
}
DEVI uint4 lds128(uint32_t a) {
    uint4 v;
    asm volatile("ld.shared.v4.u32 {%0,%1,%2,%3}, [%4];" : "=r"(v.x), "=r"(v.y), "=r"(v.z), "=r"(v.w) : "r"(a) : "memory");
    return v;
}
DEVI uint2 lds64(uint32_t a) {
    uint2 v;
    asm volatile("ld.shared.v2.u32 {%0,%1}, [%2];" : "=r"(v.x), "=r"(v.y) : "r"(a) : "memory");
    return v;
}
DEVI uint32_t lds32(uint32_t a) {
    uint32_t v;
    asm volatile("ld.shared.u32 %0, [%1];" : "=r"(v) : "r"(a) : "memory");
    return v;
}
DEVI float ex2(float x) { float r; asm("ex2.approx.ftz.f32 %0, %1;" : "=f"(r) : "f"(x)); return r; }
DEVI float rcp(float x) { float r; asm("rcp.approx.ftz.f32 %0, %1;" : "=f"(r) : "f"(x)); return r; }
DEVI uint32_t clk() { uint32_t c; asm volatile("mov.u32 %0, %%clock;" : "=r"(c)::"memory"); return c; }

DEVI uint64_t mkdesc(uint32_t addr, uint32_t lbo, uint32_t sbo) {
    return (uint64_t)((addr & 0x3FFFF) >> 4) | ((uint64_t)(lbo >> 4) << 16) | ((uint64_t)(sbo >> 4) << 32) | ((uint64_t)1 << 62);
}
DEVI void wg_fence() { asm volatile("wgmma.fence.sync.aligned;" ::: "memory"); }
DEVI void wg_commit() { asm volatile("wgmma.commit_group.sync.aligned;" ::: "memory"); }
template <int N> DEVI void wg_wait() { asm volatile("wgmma.wait_group.sync.aligned %0;" ::"n"(N) : "memory"); }
template <int SC>
DEVI void wg_rs32(float (&d)[16], const uint32_t (&a)[4], uint64_t db) {
    if (SC) {
        asm volatile("wgmma.mma_async.sync.aligned.m64n32k16.f32.bf16.bf16 "
                     "{%0,%1,%2,%3,%4,%5,%6,%7,%8,%9,%10,%11,%12,%13,%14,%15}, {%16,%17,%18,%19}, %20, 1, 1, 1, 0;"
                     : "+f"(d[0]), "+f"(d[1]), "+f"(d[2]), "+f"(d[3]), "+f"(d[4]), "+f"(d[5]), "+f"(d[6]), "+f"(d[7]),
                       "+f"(d[8]), "+f"(d[9]), "+f"(d[10]), "+f"(d[11]), "+f"(d[12]), "+f"(d[13]), "+f"(d[14]), "+f"(d[15])
                     : "r"(a[0]), "r"(a[1]), "r"(a[2]), "r"(a[3]), "l"(db));
    } else {
        asm volatile("wgmma.mma_async.sync.aligned.m64n32k16.f32.bf16.bf16 "
                     "{%0,%1,%2,%3,%4,%5,%6,%7,%8,%9,%10,%11,%12,%13,%14,%15}, {%16,%17,%18,%19}, %20, 0, 1, 1, 0;"
                     : "=f"(d[0]), "=f"(d[1]), "=f"(d[2]), "=f"(d[3]), "=f"(d[4]), "=f"(d[5]), "=f"(d[6]), "=f"(d[7]),
                       "=f"(d[8]), "=f"(d[9]), "=f"(d[10]), "=f"(d[11]), "=f"(d[12]), "=f"(d[13]), "=f"(d[14]), "=f"(d[15])
                     : "r"(a[0]), "r"(a[1]), "r"(a[2]), "r"(a[3]), "l"(db));
    }
}

#define NA 12
#define NPF 6
#define PF1 2
#define PF2 2
#define PF3 4
#define WPF 2
#define VPF 2
#define VORD 0x01234567
#define VSF 0
#define VMF 0
#define VC 1
#define QP 16
#define W2P 0
#define W3P 1
#define QSP 12
#define VSB 0x10F
#define QQP 3
#define CGP 8
#define C0P 9
#define C1P 9
#define PIP 10
#define K0P 2
#define KEP 4
#define KE2 0
#define VTP 0
#define CW 1
#define WV_BOX ((16 - NA) * 2048)
#define WO_BOX 16384
#define SM_WV 0
#define SM_WO (2 * WV_BOX)
#define SM_X (SM_WO + 4 * WO_BOX)
#define SM_XO (SM_X + 32768)
#define SM_MEMT (SM_XO + 12288)
#define SM_OT (SM_MEMT + 4096)
#define SM_VS (SM_OT + 2048)
#define SM_P (SM_VS + 2048)
#define SM_DN (SM_P + 1792)
#define SM_PROF (SM_P + 2048)
#define SM_ST (SM_X + 65536)
#define SM_KV SM_ST
#define SM_SP (SM_KV + 18432)
#define SM_TR (SM_ST + 32768)
#define SM_PI (SM_ST + 65536)
#define SM_BAR (SM_PI + 12288)
#define SM_TOTAL (SM_BAR + 512)
static_assert(NA == 12, "start-up chunks");
static_assert(SM_TOTAL <= 232448, "smem");
#define BAR_XA 32
#define BAR_KV 40
#define BAR_PI 48
#define BAR_RO 64
#define BAR_WF 256
#define BAR_WE 384
#define SM_ROLE (SM_BAR + 72)

#define SPIN_LIMIT (1 << 20)
#define RPOS 26
#define OPOS 2
#define ASF 0
#define KPOS 0
#define CPOS 4
#define DLY_V 350
#define NPRB 2
#define PW 4
#define ZD 0
#define FTM 2
#define XPF 1
#define WOP 2
#define WIN 2
#define EPD 1300
#define ASP 4
#define EPF 0
#define CFAR 1

template <int ID, int N> DEVI void bsync() { asm volatile("bar.sync %0, %1;" ::"n"(ID), "n"(N) : "memory"); }
template <int ID, int N> DEVI void barv() { asm volatile("bar.arrive %0, %1;" ::"n"(ID), "n"(N) : "memory"); }

#define PT(n)
#define PC(n, v)
#define PDUMP()
#define REFRESH() asm volatile("xor.b32 %0, %0, %1;" : "+r"(l16) : "r"(zero))
#define OPQ(x) asm volatile("xor.b32 %0, %0, %1;" : "+r"(x) : "r"(zero))
#define KEEP(x, a, b, c, d) asm volatile("{\n.reg .b32 t;\nlop3.b32 t, %1, %2, %3, 0x80;\nlop3.b32 t, t, %4, %5, 0x80;\nxor.b32 %0, %0, t;\n}" \
                                         : "+r"(x) : "r"(a), "r"(b), "r"(c), "r"(d), "r"(zero))
#define SF() asm volatile("pmevent 1;" ::: "memory")
#define MF() __syncwarp()
#define SB0 1024u

#define XDOFF(ks) ((((ks) >> 2) * 1024 + ((ks) & 3) * 32) >> 4)
template <int SC>
DEVI void wg_ss32t(float (&d)[16], uint64_t da, uint64_t db) {
    if (SC) {
        asm volatile("wgmma.mma_async.sync.aligned.m64n32k16.f32.bf16.bf16 "
                     "{%0,%1,%2,%3,%4,%5,%6,%7,%8,%9,%10,%11,%12,%13,%14,%15}, %16, %17, 1, 1, 1, 1, 0;"
                     : "+f"(d[0]), "+f"(d[1]), "+f"(d[2]), "+f"(d[3]), "+f"(d[4]), "+f"(d[5]), "+f"(d[6]), "+f"(d[7]),
                       "+f"(d[8]), "+f"(d[9]), "+f"(d[10]), "+f"(d[11]), "+f"(d[12]), "+f"(d[13]), "+f"(d[14]), "+f"(d[15])
                     : "l"(da), "l"(db));
    } else {
        asm volatile("wgmma.mma_async.sync.aligned.m64n32k16.f32.bf16.bf16 "
                     "{%0,%1,%2,%3,%4,%5,%6,%7,%8,%9,%10,%11,%12,%13,%14,%15}, %16, %17, 0, 1, 1, 1, 0;"
                     : "=f"(d[0]), "=f"(d[1]), "=f"(d[2]), "=f"(d[3]), "=f"(d[4]), "=f"(d[5]), "=f"(d[6]), "=f"(d[7]),
                       "=f"(d[8]), "=f"(d[9]), "=f"(d[10]), "=f"(d[11]), "=f"(d[12]), "=f"(d[13]), "=f"(d[14]), "=f"(d[15])
                     : "l"(da), "l"(db));
    }
}

DEVI void delay_until(uint32_t t0, uint32_t d) { while (clk() - t0 < d) {} }

#define VR 2
#define CW2 4
template <int I0, int I1>
DEVI void xmma(float (&xa)[16], float (&xb)[16], uint32_t w, int ps, uint32_t zero, const uint32_t (&Wq)[16][4], const uint32_t (&Wk)[16][4],
               const uint32_t (&Wv)[NA][4], const uint32_t (&wv)[16 - NA][4]) {
    const uint64_t xd = mkdesc(SB0 + SM_X, 16, 4096) + (ps & 1) * 1024, vd = mkdesc(SB0 + SM_WV, 8192, 1024);
    uint32_t vo = (w >> 2) * (WV_BOX / 16);
    if (VR ? false : VC == 0 ? I0 < 16 - NA : VC == 1 ? I0 >= 32 && I0 < 48 - NA : I1 > 32 + NA) OPQ(vo);
#pragma unroll
    for (int i = I0; i < I1; i++) {
        if (VC) {
            const int v = (i + (VC == 1 ? NA : 0)) & 15;
            if (i == 0) wg_rs32<0>(xa, Wq[0], xd);
            else if (i < 16) wg_rs32<1>(xa, Wq[i & 15], xd + XDOFF(i & 15));
            else if (i == 16) wg_rs32<0>(xb, Wk[0], xd);
            else if (i < 32) wg_rs32<1>(xb, Wk[i & 15], xd + XDOFF(i & 15));
            else if (i == 32 && v < NA) wg_rs32<0>(xa, Wv[0], xd);
            else if (VR && i == 32) wg_rs32<0>(xa, wv[0], xd + XDOFF(NA));
            else if (VR && v >= NA) wg_rs32<1>(xa, wv[v >= NA ? v - NA : 0], xd + XDOFF(v));
            else if (i == 32) wg_ss32t<0>(xa, (vd & ~0xFFFFFFFFull) | ((uint32_t)vd + vo), xd + XDOFF(NA));
            else if (v < NA) wg_rs32<1>(xa, Wv[v < NA ? v : 0], xd + XDOFF(v));
            else wg_ss32t<1>(xa, (vd & ~0xFFFFFFFFull) | ((uint32_t)vd + (v - NA) * 128 + vo), xd + XDOFF(v));
        } else
        if (i == 0) wg_ss32t<0>(xb, (vd & ~0xFFFFFFFFull) | ((uint32_t)vd + vo), xd + XDOFF(NA));
        else if (i < 16 - NA) wg_ss32t<1>(xb, (vd & ~0xFFFFFFFFull) | ((uint32_t)vd + i * 128 + vo), xd + XDOFF(NA + i));
        else if (i == 16 - NA) wg_rs32<0>(xa, Wq[0], xd);
        else if (i < 32 - NA) wg_rs32<1>(xa, Wq[(i + NA) & 15], xd + XDOFF((i + NA) & 15));
        else if (i < 32) wg_rs32<1>(xb, Wv[(i + NA) & 15], xd + XDOFF((i + NA) & 15));
        else if (i == 32) wg_rs32<0>(xa, Wk[0], xd);
        else wg_rs32<1>(xa, Wk[i & 15], xd + XDOFF(i & 15));
    }
    wg_commit();
}
#define XMMA(I0, I1) xmma<(I0), (I1)>(xa, xb, w, p ^ 1, zero, Wq, Wk, Wv, wv)
DEVI void wg_done(float (&d)[16]) {
    asm volatile("" : "+f"(d[0]), "+f"(d[1]), "+f"(d[2]), "+f"(d[3]), "+f"(d[4]), "+f"(d[5]), "+f"(d[6]), "+f"(d[7]),
                      "+f"(d[8]), "+f"(d[9]), "+f"(d[10]), "+f"(d[11]), "+f"(d[12]), "+f"(d[13]), "+f"(d[14]), "+f"(d[15]) :: "memory");
}
template <int M>
DEVI void xpack(uint32_t (&xp)[8], float (&xa)[16]) {
    wg_done(xa);
#pragma unroll
    for (int i = 0; i < 4; i++) {
        xp[2 * i] = pack2(xa[4 * i], xa[4 * i + (M < 2 ? 2 : 1)]);
        xp[2 * i + 1] = pack2(xa[4 * i + (M < 2 ? 1 : 2)], xa[4 * i + 3]);
    }
}
template <int M>
DEVI uint4 xpeer(uint32_t sb, int ps, uint32_t t16) { return lds128(sb + SM_PI - ((ps & 1) ^ 1) * 12288 + M * 4096 + t16); }
DEVI void xadd(uint32_t (&xp)[8], const uint4& pi) {
    xp[0] = hadd2(xp[0], pi.x); xp[1] = hadd2(xp[1], pi.y); xp[2] = hadd2(xp[2], pi.z); xp[3] = hadd2(xp[3], pi.w);
}
template <int M>
DEVI void xsend(const uint32_t (&xp)[8], uint32_t sb, int ps, uint32_t t16) {
    asm volatile("st.async.weak.shared::cluster.mbarrier::complete_tx::bytes.v4.b32 [%0], {%1,%2,%3,%4}, [%5];"
                 ::"r"((sb ^ 0x1000000) + SM_PI - (ps & 1) * 12288 + M * 4096 + t16), "r"(xp[4]), "r"(xp[5]), "r"(xp[6]), "r"(xp[7]),
                   "r"((sb ^ 0x1000000) + SM_BAR + BAR_PI + (ps & 1) * 8) : "memory");
}
template <int M>
DEVI void xstore(const uint32_t (&xp)[8], uint32_t sb, uint32_t sbw, int ps, uint32_t t16, uint32_t KA) {
    const uint32_t a = SM_XO + M * 2048 + (M < 2 ? (KA & 0xFF) + sbw : (t16 >> 1) + sb);
    sts64(a, xp[0], xp[1]);
    sts64(a + 6144, xp[2], xp[3]);
    xsend<M>(xp, sb, ps, t16);
}
template <int M>
DEVI void xpark(uint32_t (&xp)[8], const uint4& pi, uint32_t sb, uint32_t sbw, int ps, uint32_t t16, uint32_t KA) {
    xadd(xp, pi);
    xstore<M>(xp, sb, sbw, ps, t16, KA);
}
template <uint32_t OFF> DEVI void red2(uint32_t lo, uint32_t hi, uint32_t a, uint32_t b) {
    asm volatile("{\n.reg .b64 a;\nmov.b64 a, {%0,%1};\nred.relaxed.gpu.global.add.noftz.v2.bf16x2 [a+%4], {%2,%3};\n}"
                 ::"r"(lo), "r"(hi), "r"(a), "r"(b), "n"(OFF) : "memory");
}
template <int M, int N>
DEVI void xstart(uint32_t sb, uint32_t w, uint32_t ga, uint32_t xhi, uint32_t j, uint32_t t16, uint32_t KA, const uint32_t (&W)[N][4]) {
    float xa[16], xb[16];
    uint32_t xp[8];
    auto pass = [&](float (&d)[16], int i, int k0, int k1) {
        const uint64_t xd = mkdesc(SB0 + SM_X + (i ? i + 1 : 0) * 16384, 16, 4096), vd = mkdesc(SB0 + SM_WV, 8192, 1024) + (w >> 2) * (WV_BOX / 16);
#pragma unroll
        for (int k = k0; k < k1; k++) {
            if (k == 0) wg_rs32<0>(d, W[0], xd);
            else if (k < N) wg_rs32<1>(d, W[k < N ? k : 0], xd + XDOFF(k));
            else wg_ss32t<1>(d, vd + (k - N) * 128, xd + XDOFF(k));
        }
        wg_commit();
    };
    wg_fence();
    pass(xa, 0, 0, 16);
    pass(xb, 1, 0, ASP);
    if (M == 0) bsync<5, 288>();
    ga += M < 2 ? (KA & 0xFF) + w * 256 : t16 >> 1;
    constexpr uint32_t O = XO_XG + M * 2048, SG = 128 * 6144;
    wg_wait<1>();
    xpack<M>(xp, xa);
    red2<O>(ga, xhi, xp[0], xp[1]); red2<O + 6144>(ga, xhi, xp[2], xp[3]); red2<O + 12288>(ga, xhi, xp[4], xp[5]); red2<O + 18432>(ga, xhi, xp[6], xp[7]);
    if (M == 2) barv<3, 320>();
    wg_fence();
    pass(xb, 1, ASP, 16);
    pass(xa, 2, 0, 16);
    wg_wait<1>();
    xpack<M>(xp, xb);
    red2<O + SG>(ga, xhi, xp[0], xp[1]); red2<O + SG + 6144>(ga, xhi, xp[2], xp[3]);
    red2<O + SG + 12288>(ga, xhi, xp[4], xp[5]); red2<O + SG + 18432>(ga, xhi, xp[6], xp[7]);
    wg_wait<0>();
    xpack<M>(xp, xa);
    red2<O + 2 * SG>(ga + j * 6144, xhi, xp[0], xp[1]);
    red2<O + 2 * SG>(ga + (j ^ 1) * 6144, xhi, xp[2], xp[3]);
    xsend<M>(xp, sb, 0, t16);
}
DEVI void piwait(uint32_t sb, int p, int ps) { mbar_wait(sb + SM_BAR + BAR_PI + p * 8, ((ps + 2) >> 1) & 1); }

DEVI uint32_t par(uint32_t off) { return __popc(off & 0xB2000u) & 1; }
DEVI uint32_t probe(uint32_t lo, uint32_t hi) {
    uint32_t best = 0xFFFFFFFFu, x = 0;
    stg4<0>(lo, hi, 0, 0, 0, 0);
    stg4<16>(lo, hi, 0, 0, 0, 0);
#pragma unroll 1
    for (int r = 0; r < NPRB; r++) {
        const uint32_t t0 = clk();
        asm volatile("{\n.reg .b64 a;\nmov.b64 a, {%1,%2};\natom.relaxed.gpu.global.add.u32 %0, [a], 2;\n}" : "=r"(x) : "r"(lo), "r"(hi) : "memory");
        if (x == 0xFFFFFFFFu) die(1 << 23);
        best = min(best, clk() - t0);
    }
    return best;
}

DEVI void xload(uint32_t sb, uint32_t u, uint32_t j, int ps, const CUtensorMap* tmx) {
    if (elect()) {
        const uint32_t sg = ps + 4 - (u & 1) + (u >> 1);
        mbar_expect(sb + SM_BAR + BAR_XA, sg < NSEG ? 4096 : 0);
        if (sg < NSEG) tma3d(sb + SM_X + (ps & 1) * 16384 + u * 4096, tmx, sb + SM_BAR + BAR_XA, 0, sg * 32 + (j ^ ((u & 1) * 2 + (u >> 1))) * 8, j * 4);
    }
}
DEVI uint32_t rpage(uint32_t j, int s) { return (s & 3) * 65536 + (j & 1) * 8192 + (((s ^ (s >> 1) ^ j ^ (j >> 1)) & 1) << 12); }

#define RLOAD() { m0 = ldg4<XO_R>(a, ah); n0 = ldg4<XO_R + 16384>(a, ah); e0 = ldg1<XO_R + 32768>(e, eh); f0 = ldg1<XO_R + 33792>(e, eh); }
DEVI bool ruse(uint32_t a, const uint4& m0, const uint4& n0, uint32_t e0, uint32_t f0) {
    const uint32_t a0 = hadd2(m0.w, n0.w), b0 = hadd2(e0, f0);
    stsm4(a, hadd2(m0.x, n0.x), hadd2(m0.y, n0.y), hadd2(m0.z, n0.z), __byte_perm(a0, b0, 0x5410));
    return __any_sync(0xFFFFFFFFu, (a0 & b0 & 0x42000000u) != 0x42000000u);
}

#define GST(i) (SM_WO + (i) * 49152)
#define BAR_GF 128
#define BAR_GE (BAR_GF + 64)
#define BAR_GX (BAR_GE + 32)
#define D4(c, i) #c "f"(d[i]), #c "f"(d[i + 1]), #c "f"(d[i + 2]), #c "f"(d[i + 3])
#define D16(c, i) D4(c, i), D4(c, i + 4), D4(c, i + 8), D4(c, i + 12)
DEVI void mwait(uint32_t bar, uint32_t parity) {
    asm volatile("{\n.reg .pred p;\n.reg .b32 c;\nmbarrier.try_wait.parity.shared::cta.b64 p, [%0], %1;\n@p bra.uni D;\nmov.b32 c, 0;\n"
                 "L:\nadd.u32 c, c, 1;\nsetp.gt.u32 p, c, 4194304;\n@p st.shared.u32 [c], c;\n"
                 "mbarrier.try_wait.parity.shared::cta.b64 p, [%0], %1;\n@!p bra.uni L;\nD:\n}" ::"r"(bar), "r"(parity) : "memory");
}
DEVI void wg_ss256t(float (&d)[128], uint64_t da, uint64_t db) {
    asm volatile("wgmma.mma_async.sync.aligned.m64n256k16.f32.bf16.bf16 "
        "{%0,%1,%2,%3,%4,%5,%6,%7,%8,%9,%10,%11,%12,%13,%14,%15,%16,%17,%18,%19,%20,%21,%22,%23,%24,%25,%26,%27,%28,%29,%30,%31,%32,%33,%34,%35,%36,%37,%38,%39,%40,%41,%42,%43,%44,%45,%46,%47,%48,%49,%50,%51,%52,%53,%54,%55,%56,%57,%58,%59,%60,%61,%62,%63,%64,%65,%66,%67,%68,%69,%70,%71,%72,%73,%74,%75,%76,%77,%78,%79,%80,%81,%82,%83,%84,%85,%86,%87,%88,%89,%90,%91,%92,%93,%94,%95,%96,%97,%98,%99,%100,%101,%102,%103,%104,%105,%106,%107,%108,%109,%110,%111,%112,%113,%114,%115,%116,%117,%118,%119,%120,%121,%122,%123,%124,%125,%126,%127}, "
        "%128, %129, 1, 1, 1, 1, 1;"
        : D16(+, 0), D16(+, 16), D16(+, 32), D16(+, 48), D16(+, 64), D16(+, 80), D16(+, 96), D16(+, 112) : "l"(da), "l"(db));
}
template <int O, int KB> DEVI void g_half(float (&d)[64], uint64_t da) {
    const uint64_t db = mkdesc(SB0 + GST(KB & 3) + 16384 + O * 256, 8192, 1024);
#pragma unroll
    for (int k = 0; k < 4; k++)
        asm volatile("wgmma.mma_async.sync.aligned.m64n128k16.f32.bf16.bf16 "
            "{%0,%1,%2,%3,%4,%5,%6,%7,%8,%9,%10,%11,%12,%13,%14,%15,%16,%17,%18,%19,%20,%21,%22,%23,%24,%25,%26,%27,%28,%29,%30,%31,%32,%33,%34,%35,%36,%37,%38,%39,%40,%41,%42,%43,%44,%45,%46,%47,%48,%49,%50,%51,%52,%53,%54,%55,%56,%57,%58,%59,%60,%61,%62,%63}, "
            "%64, %65, 1, 1, 1, 1, 1;"
            : D16(+, 0), D16(+, 16), D16(+, 32), D16(+, 48) : "l"(da + (KB & 3) * 3072 + k * 16), "l"(db + k * 128));
}
DEVI void g_load(uint32_t sb, uint32_t u, uint32_t role, uint32_t kb, uint32_t xlo, uint32_t xhi, const CUtensorMap* tmb) {
    const uint32_t st = kb & 3, bar = sb + SM_BAR + BAR_GF + u * 32 + st * 8, dst = sb + GST(st), k = (role & 1) * 32 + kb;
    if (!elect()) return;
    mbar_expect(bar, u ? 8192 : 40960);
    bulk_g2s(dst + u * 8192, xlo + XO_OX + (k * 16 + (role >> 3)) * 16384 + u * 8192, xhi, 8192, bar);
    if (u == 0) {
        tma3d(dst + 16384, tmb, bar, 0, k * 64, ((role & 7) ^ 1) * 2);
        tma3d(dst + 32768, tmb, bar, 0, k * 64, (role & 7) * 2);
    }
}
DEVI void g_arrive(uint32_t a, uint32_t xhi, uint32_t n) {
    if (elect()) asm volatile("{\n.reg .b64 a;\nmov.b64 a, {%0,%1};\nred.release.gpu.global.inc.u32 [a], %2;\n}" ::"r"(a), "r"(xhi), "r"(n - 1) : "memory");
}
DEVI void g_wait(uint32_t a, uint32_t xhi) {
    int it = 0;
    uint32_t v;
    do {
        asm volatile("{\n.reg .b64 a;\nmov.b64 a, {%1,%2};\nld.acquire.gpu.global.u32 %0, [a];\n}" : "=r"(v) : "r"(a), "r"(xhi) : "memory");
        if (++it > SPIN_LIMIT) die(it);
    } while (__any_sync(0xFFFFFFFFu, v));
    asm volatile("fence.proxy.async.global;" ::: "memory");
}
#define SE 2
#define DLY_S 0
#define VX 1
#define VH 1
#define VD 1
#define SM_VP (SM_TR + 12288)
#define JV(h, j) (VH < 2 ? (j) ^ ((par((h) * 8192) ^ VH) << 1) : (j))
#define SEU 0
#define VA 0
#define VLP 0
#define VCP 1
#define SEED 0
#define VB 0
#define RCP 0
#define XLP 0
#define RE 0
#define DLY_E 300
#define DLY_T 200
#define RDW 0
#define APH 1
#define A0 0
#define A1 0
#define KEP0 1
#define VSB0 VSB
#define B3 0
#define GD 400
#define GE 3
#define GH 1
#define GS 1
#define GP 0
DEVI void g_done(float (&d)[64]) { asm volatile("" : D16(+, 0), D16(+, 16), D16(+, 32), D16(+, 48)::"memory"); }
DEVI void g_main(uint32_t sb, uint32_t w, uint32_t role, const CUtensorMap* tmy, void* out) {
    const uint32_t bar = sb + SM_BAR, t16 = threadIdx.x * 16;
    const uint64_t da = (mkdesc(SB0 + GST(0), 128, 1024) & ~((uint64_t)3 << 62)) + (w >> 2) * 512;
    float d[128];
#pragma unroll
    for (int i = 0; i < 128; i++) d[i] = 0.f;
#define GFULL(kb) { mwait(bar + BAR_GF + ((kb) & 3) * 8, ((kb) >> 2) & 1); if (w >= 4) mwait(bar + BAR_GF + 32 + ((kb) & 3) * 8, ((kb) >> 2) & 1); }
#pragma unroll 1
    for (uint32_t kb = 0; kb < (GE ? 28 : 29); kb++) {
        GFULL(kb);
        if (kb == 0 && threadIdx.x == 128) PG(4);
        if (kb == 4 && threadIdx.x == 0) PG(5);
        const uint64_t a = da + (kb & 3) * 3072, b = mkdesc(SB0 + GST(0) + 16384, 8192, 1024) + (kb & 3) * 3072;
        wg_fence();
#pragma unroll
        for (int k = 0; k < 4; k++) wg_ss256t(d, a + k * 16, b + k * 128);
        wg_commit();
        wg_wait<1>();
        if (kb > 0 && elect()) mbar_arrive(bar + BAR_GE + ((kb - 1) & 3) * 8);
    }
    if (GE) { GFULL(28); }
    else { GFULL(29); GFULL(30); GFULL(31); }
    wg_wait<0>();
    if (GE && elect()) mbar_arrive(bar + BAR_GE + 24);
    float x[64], y[64];
#pragma unroll
    for (int i = 0; i < 64; i++) asm volatile("mov.b32 %0, %1;" : "=f"(x[i]) : "f"(d[i]) : "memory");
    SF();
#pragma unroll
    for (int i = 0; i < 64; i++) asm volatile("mov.b32 %0, %1;" : "=f"(y[i]) : "f"(d[i + 64]) : "memory");
    SF();
#define GFREE() if (elect()) asm volatile("mbarrier.arrive.relaxed.cluster.shared::cluster.b64 _, [%0];" ::"r"((bar ^ 0x1000000) + BAR_GX) : "memory")
#define GSW(i) ((i) * 4096 + (GE && (i) >= 4 ? GST(0) : 0))
#define GSEND(i0) _Pragma("unroll") for (int i = (i0); i < (i0) + 4; i++) \
        asm volatile("st.async.weak.shared::cluster.mbarrier::complete_tx::bytes.v4.b32 [%0], {%1,%2,%3,%4}, [%5];" \
                     ::"r"((sb ^ 0x1000000) + GSW(i) + t16), "r"(pack2(x[8 * i], x[8 * i + 1])), "r"(pack2(x[8 * i + 2], x[8 * i + 3])), \
                       "r"(pack2(x[8 * i + 4], x[8 * i + 5])), "r"(pack2(x[8 * i + 6], x[8 * i + 7])), "r"((bar ^ 0x1000000) + BAR_GX + 8) : "memory")
    if (GE) {
        wg_fence();
        g_half<0, 28>(x, da);
        wg_commit();
        GFULL(29);
        wg_fence();
        g_half<0, 29>(x, da);
        wg_commit();
        GFULL(30);
        wg_fence();
        g_half<0, 30>(x, da);
        wg_commit();
        GFULL(31);
        wg_fence();
        g_half<0, 31>(x, da);
        wg_commit();
        g_half<64, 28>(y, da);
        if (GE == 2) g_half<64, 29>(y, da);
        wg_commit();
        wg_wait<1>();
        g_done(x);
        GFREE();
        GSEND(0);
        wg_fence();
        if (GE != 2) g_half<64, 29>(y, da);
        if (GE != 1) g_half<64, 30>(y, da);
        wg_commit();
        mwait(bar + BAR_GX, 0);
        GSEND(4);
        wg_fence();
        if (GE == 1) g_half<64, 30>(y, da);
        g_half<64, 31>(y, da);
        wg_commit();
        mwait(bar + BAR_GX + 8, 0);
        if (threadIdx.x == 0) PG(1);
#pragma unroll
        for (int i = 0; i < 8; i++) {
            const uint4 a = lds128(sb + GSW(i) + t16);
            float* e = x + 8 * i;
            e[0] = lo_f(a.x); e[1] = hi_f(a.x); e[2] = lo_f(a.y); e[3] = hi_f(a.y); e[4] = lo_f(a.z); e[5] = hi_f(a.z); e[6] = lo_f(a.w); e[7] = hi_f(a.w);
        }
        g_done(x);
        SF();
        wg_wait<0>();
        g_done(y);
        if (threadIdx.x == 0) PG(7);
    } else {
        GFREE();
        wg_fence();
        g_half<0, 29>(x, da);
        g_half<0, 30>(x, da);
        g_half<0, 31>(x, da);
        wg_commit();
        g_half<64, 29>(y, da);
        wg_commit();
        wg_wait<1>();
        g_done(x);
        mwait(bar + BAR_GX, 0);
        GSEND(0);
        wg_fence();
        g_half<64, 30>(y, da);
        wg_commit();
        GSEND(4);
        wg_fence();
        g_half<64, 31>(y, da);
        wg_commit();
        wg_wait<0>();
        g_done(y);
        if (threadIdx.x == 0) PG(7);
        mwait(bar + BAR_GX + 8, 0);
        if (threadIdx.x == 0) PG(1);
    }
    const uint32_t lane = threadIdx.x & 31, o = sb + GST(1) + w * 2048;
    char* go = (char*)out + ((role >> 3) * 128 + w * 16 + (lane >> 3)) * 4096 + (role & 7) * 256 + (lane & 7) * 16;
#pragma unroll
    for (int i = 0; i < 8; i++) {
        float* e = y + 8 * i;
        if (GE) {
#pragma unroll
            for (int n = 0; n < 8; n++) e[n] += x[8 * i + n];
        } else {
            const uint4 a = lds128(sb + i * 4096 + t16);
            e[0] += lo_f(a.x); e[1] += hi_f(a.x); e[2] += lo_f(a.y); e[3] += hi_f(a.y); e[4] += lo_f(a.z); e[5] += hi_f(a.z); e[6] += lo_f(a.w); e[7] += hi_f(a.w);
        }
        stsm4(o + (i >> 2) * 49152 + (lane & 15) * 128 + ((((i & 3) * 2 + (lane >> 4)) ^ (lane & 7)) << 4),
              pack2(e[0], e[1]), pack2(e[2], e[3]), pack2(e[4], e[5]), pack2(e[6], e[7]));
        if (i == 3 || i == 7) {
            if (GS) {
                __syncwarp();
#pragma unroll
                for (int m = 0; m < 4; m++)
                    *(uint4*)(go + m * 16384 + (i >> 2) * 128) =
                        lds128(o + (i >> 2) * 49152 + m * 512 + (lane >> 3) * 128 + (((lane & 7) ^ ((m & 1) * 4 + (lane >> 3))) << 4));
            } else {
                asm volatile("fence.proxy.async.shared::cta;" ::: "memory");
                __syncwarp();
                if (elect())
                    asm volatile("cp.async.bulk.tensor.2d.global.shared::cta.bulk_group [%0, {%2, %3}], [%1];\ncp.async.bulk.commit_group;"
                                 ::"l"(tmy), "r"(o + (i >> 2) * 49152), "r"((role & 7) * 128 + (i >> 2) * 64), "r"((role >> 3) * 128 + w * 16) : "memory");
            }
        }
    }
    if (threadIdx.x == 0) PG(6);
    if (!GS) asm volatile("cp.async.bulk.wait_group.read 0;" ::: "memory");
}

DEVI void kvload(uint32_t sb, uint32_t u, uint32_t h, uint32_t j, int sg, uint32_t xlo, uint32_t xhi) {
    const uint32_t o = u == 0 ? 0 : 2048;
    mbar_expect(sb + SM_BAR + BAR_KV, 6144 - o);
    bulk_g2s(sb + SM_KV + u * 4096 + o, xlo + XO_XG + (((sg & 7) * 32 + h) * 4 + ((j + u) & 3)) * 6144 + o, xhi, 6144 - o, sb + SM_BAR + BAR_KV);
}
DEVI void helper_step(uint32_t sb, uint32_t w, uint32_t h, uint32_t j, uint32_t& l16, uint32_t xlo, uint32_t xhi, uint32_t zero, int s,
                      const CUtensorMap* tmx, const CUtensorMap* tmb) {
    const uint32_t u = w - 8, bq = sb + SM_BAR;
    bsync<1, 384>();
    PT(0);
    PDUMP();
    PT(1);
    if (s == NSEG - 2 && u < 2) g_arrive(xlo + XO_TK + 128, xhi, 256);
    uint32_t old = 0;
#define RCLEAR(n) if (RCP == (n) && u > 0 && s + 3 < NSEG) \
        asm volatile("{\n.reg .b64 a;\nmov.b64 a, {%1,%2};\natom.relaxed.gpu.global.exch.b32 %0, [a], 0;\n}" \
                     : "=r"(old) : "r"(xlo + XO_R + rpage(j, s + 2) + (u - 1) * 16384 + h * 128 + (l16 >> 2)), "r"(xhi) : "memory");
    RCLEAR(1);
    const bool gl = u == 0 || (u == 1 && h < 30);
    if (GP == 1 && s == NSEG - 1 && gl) g_load(sb, u, h * 4 + j, 1, xlo, xhi, tmb);
    const uint32_t ctag = ((s >> 1) & 1) ^ 1;
    const uint32_t av = xlo + ((s & 1) * 32 + h) * 8192 + u * 512;
    mbar_wait(bq + BAR_XA, (s + 1) & 1);
    if (B3 == 8) barv<5, 384>();
    bsync<8, 384>();
    const uint32_t t8 = clk(), gs = xlo + XO_XG + ((((s + 3) & 7) * 32 + h) * 4 + j) * 6144;
    RCLEAR(2);
    const bool se = B3 % 8 == 0 && SE && u == SEU && s + 3 < NSEG;
    uint32_t tv = ctag ^ 1, ro = 0;
    if (se) {
        asm volatile("fence.proxy.async.shared::cta;" ::: "memory");
        if (SE == 4) delay_until(t8, DLY_E);
        if ((SE == 1 || SE == 4) && elect()) bulk_s2g(gs, xhi, sb + SM_XO, 4096);
    } else if (RE && u == 1 && s + 2 < NSEG) {
        asm volatile("fence.proxy.async.shared::cta;" ::: "memory");
        const uint32_t cb0 = (h >> 1) * 32768 + (j & 1) * 16384 + (h & 1) * 8192;
        delay_until(t8, DLY_T);
        tv = ldg1<XO_CQK>((xlo + cb0 + ((par(cb0) ^ (j >> 1) ^ CFAR ^ 1) << 12)) ^ ((s & 1) * 0x81000), xhi);
        SF();
    }
    if (B3 != 6 || u || SE == 2) delay_until(t8, DLY_V);
    if (se && SE == 2 && elect()) bulk_s2g(gs, xhi, sb + SM_XO, 4096);
    PT(4);
    int it = 0;
    uint4 d1, d2, d3;
    uint2 e1, e2, e3;
    const uint32_t ae = av - u * 512 + (u & 1) * 256;
    const uint32_t jv = JV(h, j);
#define VLOAD() { if (!VD) d1 = ldg4<XO_CV>(av + (jv ^ 1) * 2048 + l16, xhi); \
        d2 = ldg4<XO_CV>(av + (jv ^ 2) * 2048 + l16, xhi); d3 = ldg4<XO_CV>(av + (jv ^ 3) * 2048 + l16, xhi); \
        if (B3 == 6 && VX) { if (!VD) e1 = ldg2<XO_CV>(ae + (jv ^ 1) * 2048 + (l16 >> 1), xhi); \
                       e2 = ldg2<XO_CV>(ae + (jv ^ 2) * 2048 + (l16 >> 1), xhi); e3 = ldg2<XO_CV>(ae + (jv ^ 3) * 2048 + (l16 >> 1), xhi); } \
        if (VD) { d1 = lds128(sb + SM_VP + (s & 1) * 2048 + u * 512 + l16); \
                  if (B3 == 6 && VX) e1 = lds64(sb + SM_VP + (s & 1) * 2048 + (u & 1) * 256 + (l16 >> 1)); } }
#define XSEND(F, C) if (u < 2) { \
        if (F) asm volatile("fence.proxy.async.shared::cta;" ::: "memory"); \
        if ((C) && elect()) { \
            const uint32_t sg = s + 3 - u; \
            if (sg < NSEG) { \
                const uint32_t ga = xlo + XO_XG + (((sg & 7) * 32 + h) * 4 + (j ^ (2 * u))) * 6144, sa = sb + SM_XO + u * 6144; \
                if (u == 0) bulk_s2g(ga + (SE ? 4096 : 0), xhi, sa + (SE ? 4096 : 0), SE ? 2048 : 6144); \
                else bulk_red(ga + ro, xhi, sa + ro, 6144 - ro); \
            } \
        } \
    }
    if (B3 == 8) {
        bsync<3, 384>();
        if (DLY_S) delay_until(clk(), DLY_S);
        XSEND(true, true);
    } else if (B3 == 6 && u == 0) {
        const uint32_t ga = xlo + XO_XG + ((((s + 3) & 7) * 32 + h) * 4 + j) * 6144, o = SE == 1 || SE == 2 ? 4096 : 0;
        if (o) {
            asm volatile("fence.proxy.async.shared::cta;" ::: "memory");
            if (s + 3 < NSEG && elect()) bulk_s2g(ga, xhi, sb + SM_XO, o);
        }
        bsync<3, 288>();
        if (DLY_S) delay_until(clk(), DLY_S);
        asm volatile("fence.proxy.async.shared::cta;" ::: "memory");
        if (elect()) {
            if (SE == 3 && s + 3 < NSEG) bulk_s2g(ga + o, xhi, sb + SM_XO + o, 6144 - o);
            if (s + 2 < NSEG) bulk_red(xlo + XO_XG + ((((s + 2) & 7) * 32 + h) * 4 + (j ^ 2)) * 6144, xhi, sb + SM_XO + 6144, 6144);
            if (SE != 3 && s + 3 < NSEG) bulk_s2g(ga + o, xhi, sb + SM_XO + o, 6144 - o);
        }
    } else {
    if (B3 == 6) VLOAD();
    if (B3 && B3 < 6) {
        VLOAD();
        bsync<B3 == 2 ? 4 : 3, 384>();
        XSEND(true, B3 < 3 || B3 == 5 || (B3 == 4 && u == 0));
    }
    while (true) {
        if (B3 % 7 == 0) VLOAD();
        if (RE && it == 0) {
            SF();
            if (!any_bad(tv ^ ctag)) {
                if (elect()) bulk_red(xlo + XO_XG + ((((s + 2) & 7) * 32 + h) * 4 + (j ^ 2)) * 6144, xhi, sb + SM_XO + 6144, 4096);
                ro = 4096;
            }
        }
        if (se && SE == 3 && it == 0 && elect()) bulk_s2g(gs, xhi, sb + SM_XO, 4096);
        uint32_t tg = or3(tagx2(d1.x, d1.z, ctag), tagx2(d2.x, d2.z, ctag), tagx2(d3.x, d3.z, ctag));
        if (B3 == 6 && VX) tg = or3(tg, tagx2(e1.x, e2.x, ctag), e3.x ^ ctag);
        const bool bad = any_bad(tg);
        if (B3 == 6 && VX) sts64(sb + SM_VS + (u & 1) * 256 + (l16 >> 1), hadd2(hadd2(e1.x, e2.x), e3.x), hadd2(hadd2(e1.y, e2.y), e3.y));
        sts128(sb + SM_VS + u * 512 + l16, hadd2(hadd2(d1.x, d2.x), d3.x), hadd2(hadd2(d1.y, d2.y), d3.y), hadd2(hadd2(d1.z, d2.z), d3.z),
               hadd2(hadd2(d1.w, d2.w), d3.w));
        if (VA) asm volatile("{\n.reg .pred p;\nsetp.eq.u32 p, %0, 0;\n@p bar.arrive 5, 384;\n}" ::"r"((uint32_t)bad) : "memory");
        if (B3 % 7 == 0) REFRESH();
        if (!bad) break;
        if (B3 % 7) { REFRESH(); VLOAD(); }
        if (++it > SPIN_LIMIT) die(it);
    }
    PC(26, it);
    PT(5);
    if (VB) barv<11, 384>();
    else if (!VA) barv<5, B3 == 6 ? 352 : 384>();
    }
    if (B3 % 7 == 0) {
        bsync<3, 384>();
        XSEND(true, true);
    }
    if (B3 == 3 || B3 == 4) XSEND(false, B3 == 3 || u == 1);
    PT(6);
    RCLEAR(0);
    PT(7);
    bsync<7, 384>();
    if (s + 1 < NSEG && elect()) kvload(sb, u, h, j, s + 1, xlo, xhi);
    RCLEAR(3);
    if (XLP == 1) xload(sb, u, j, s + 1, tmx);
    if (u < (B3 == 6 ? 1 : 2)) {
        asm volatile("cp.async.bulk.wait_group.read 0;" ::: "memory");
        if (elect()) {
            mbar_expect(bq + BAR_PI + ((s & 1) ^ 1) * 8, 6144);
            if (B3 == 6) mbar_expect(bq + BAR_PI + ((s & 1) ^ 1) * 8, 6144);
        }
    }
    PT(8);
    if (GP && s == NSEG - 2 && gl) g_wait(xlo + XO_TK + 128, xhi);
    if (s + 1 < NSEG) bsync<10, 384>();
    if (XLP == 0) xload(sb, u, j, s + 1, tmx);
    RCLEAR(4);
    if (s == NSEG - 2 && gl) {
        if (!GP) g_wait(xlo + XO_TK + 128, xhi);
        g_load(sb, u, h * 4 + j, 0, xlo, xhi, tmb);
        if (GP == 0 || GP == 3) g_load(sb, u, h * 4 + j, 1, xlo, xhi, tmb);
    }
    asm volatile("cp.async.bulk.wait_group 0;" ::: "memory");
    if (s + 1 < NSEG) mbar_wait(bq + BAR_KV, (s + 1) & 1);
    asm volatile("lop3.b32 %0, %0, %1, %2, 0x78;" : "+r"(l16) : "r"(old), "r"(zero));
    PT(15);
}
DEVI void tickets_done(uint32_t* tk) {
    if (atomicInc(tk + 2, gridDim.x / 2 - 64) == gridDim.x / 2 - 64) { tk[0] = 0; tk[1] = 0; }
}

__global__ void __cluster_dims__(2, 1, 1) __launch_bounds__(384, 1)
chain_kernel(const __grid_constant__ CUtensorMap tmq, const __grid_constant__ CUtensorMap tmk,
             const __grid_constant__ CUtensorMap tmv, const __grid_constant__ CUtensorMap tmo,
             const __grid_constant__ CUtensorMap tmx, const __grid_constant__ CUtensorMap tmb, const __grid_constant__ CUtensorMap tmy,
             const bf16* __restrict__ mem0, const bf16* __restrict__ xg,
             uint32_t xlo, uint32_t xhi, uint32_t zero, int nseg, bf16* __restrict__ out) {
    extern __shared__ __align__(1024) uint8_t smem[];
    const uint32_t tstart = clk();
    const uint32_t rk = smem_u32(smem) & 0x1000000;
    if (rk == 0 && (threadIdx.x & 31) == 0 && threadIdx.x - 32 < 32 * PW)
        sts32(SB0 + SM_ROLE + 4 + (threadIdx.x >> 3), probe(xlo + XO_PB + (threadIdx.x & 32) * 128 + (threadIdx.x & 64) * 256 + blockIdx.x * 16, xhi));
    __syncwarp();
    if ((smem_u32(smem) & 0xFFFFFF) != SB0) die(1 << 23);
    asm volatile("griddepcontrol.launch_dependents;" ::: "memory");
    const uint32_t w = __reduce_max_sync(0xFFFFFFFFu, threadIdx.x >> 5);
    const uint32_t sb = __reduce_max_sync(0xFFFFFFFFu, smem_u32(smem));
    const uint32_t bq = sb + SM_BAR;
    uint32_t l16 = __shfl_sync(0xFFFFFFFFu, (threadIdx.x & 31) * 16, threadIdx.x & 31);
    if (threadIdx.x == 0) {
        mbar_init(bq, 1);
        for (int i = 0; i < 24; i++) mbar_init(bq + BAR_WF + i * 8, i < 16 ? 1 : 8);
        mbar_init(bq + BAR_XA, 4); mbar_init(bq + BAR_KV, 4); mbar_init(bq + BAR_PI, 2); mbar_init(bq + BAR_PI + 8, 2);
        for (int i = 0; i < 14; i++) mbar_init(bq + BAR_GF + i * 8, i < 8 || i == 13 ? 1 : 8);
        mbar_expect(bq + BAR_GX + 8, 32768);
        mbar_init(bq + BAR_RO, 1);
        mbar_expect(bq + BAR_RO, 4);
        mbar_expect(bq + BAR_PI, 6144);
        mbar_expect(bq + BAR_PI, 6144);
        asm volatile("fence.mbarrier_init.release.cluster;" ::: "memory");
        asm volatile("fence.proxy.async.shared::cta;" ::: "memory");
    }
    __syncwarp();
    asm volatile("barrier.cluster.arrive.relaxed.aligned;" ::: "memory");
    if (w == 9) {
#pragma unroll 1
        for (int e = 0; e < 12; e++) sts128(sb + SM_WO + e * 512 + l16, 0, 0, 0, 0);
    }
    if (w == 8 && blockIdx.x < 128) {
        if (XPF && elect()) {
            asm volatile("cp.async.bulk.prefetch.L2.global [%0], 3072;" ::"l"((const char*)xg + blockIdx.x * 3072) : "memory");
            asm volatile("prefetch.tensormap [%0];\nprefetch.tensormap [%1];\nprefetch.tensormap [%2];\nprefetch.tensormap [%3];\nprefetch.tensormap [%4];"
                         ::"l"(&tmq), "l"(&tmx), "l"(&tmk), "l"(&tmv), "l"(&tmo) : "memory");
        }
#pragma unroll 1
        for (int i = 0; i < EPF; i++) {
            if (i) delay_until(clk(), EPD);
            if (elect())
                asm volatile("cp.async.bulk.prefetch.tensor.3d.L2.global [%0, {0, %1, %2}];" ::"l"(&tmq), "r"((blockIdx.x & 3) * 256 + i * 64), "r"((blockIdx.x >> 2) * 2) : "memory");
        }
    }
    if (rk == 0 && w <= PW) bsync<2, 32 * PW + 32>();
    asm volatile("barrier.cluster.wait.aligned;" ::: "memory");
    if (rk == 0 && threadIdx.x == 0) {
        uint32_t t1 = lds32(sb + SM_ROLE + 8), t0 = lds32(sb + SM_ROLE + 12);
        if (PW == 4) { t1 = min(t1, lds32(sb + SM_ROLE + 16)); t0 = min(t0, lds32(sb + SM_ROLE + 20)); }
        uint32_t side = (t0 < t1 ? 0u : 1u) ^ par(XO_PB);
        uint32_t* tk = (uint32_t*)(((uint64_t)xhi << 32) | (xlo + XO_TK));
        uint32_t t = atomicAdd(tk + side, 1u);
        if (t >= 32) {
            uint2 c;
            int it = 0;
            do {
                c = ldg2<XO_TK>(xlo, xhi);
                if (++it > SPIN_LIMIT) die(it);
            } while (c.x + c.y != gridDim.x / 2);
            t += (side ? c.x : c.y) - 32;
            side ^= 1;
            if (t >= 32) tickets_done(tk);
        }
#pragma unroll
        for (uint32_t r = 0; r < 2; r++)
            asm volatile("st.async.weak.shared::cluster.mbarrier::complete_tx::bytes.b32 [%0], %1, [%2];"
                         ::"r"(sb + SM_ROLE + (r << 24)), "r"(t * 4 + side * 2 + r), "r"(bq + BAR_RO + (r << 24)) : "memory");
    }
    __syncwarp();
    mbar_wait(bq + BAR_RO, 0);
    const uint32_t role = __reduce_max_sync(0xFFFFFFFFu, lds32(sb + SM_ROLE));
    if (role >= 128) return;
    const uint32_t h = role >> 2, j = role & 3;
    if (FTM && w == 11 && elect())
#pragma unroll
        for (uint32_t c = 0; c < FTM; c++) {
            mbar_expect(bq + BAR_WF + c * 8, 16384);
            tma3d(sb + SM_ST + c * 16384, &tmq, bq + BAR_WF + c * 8, 0, j * 256 + c * 64, h * 2);
        }

    if (w >= 8) {
        asm volatile("setmaxnreg.dec.sync.aligned.u32 24;");
        const uint32_t u = w - 8;
        if (u == 3) {
#pragma unroll 1
            for (uint32_t c = FTM; c < 16; c++) {
                if (c >= WIN) mbar_wait(bq + BAR_WF + (c - WIN) * 8, 0);
                if (l16 == 0) PG(16 + c);
                if (c == 12 + WOP) bsync<2, 64>();
                if (c >= 4 && c < 12 && c != 10) mbar_wait(bq + BAR_WE + (c - 4) * 8, 0);
                if (elect()) {
                    const uint32_t b = bq + BAR_WF + c * 8;
                    mbar_expect(b, 16384);
                    if (c >= 12) tma2d(sb + SM_WO + (c - 12) * WO_BOX, &tmo, b, j * 256 + (c - 12) * 64, h * 128);
                    else tma3d(c == 10 ? sb + SM_WV : sb + SM_ST + (c & 3) * 16384, c < 4 ? &tmq : c < 8 ? &tmk : &tmv, b, 0, j * 256 + ((c ^ (c >= 10)) & 3) * 64, h * 2);
                }
            }
#pragma unroll 1
            for (uint32_t c = 16 - WIN; c < 16; c++) mbar_wait(bq + BAR_WF + c * 8, 0);
            if (l16 == 0) PG(15);
        } else if (u == 0) {
            if (elect()) {
                mbar_expect(bq, 49152);
#pragma unroll 1
                for (uint32_t i = 0; i < 12; i++)
                    tma3d(sb + SM_X + (i < 4 ? i : i + 4) * 4096, &tmx, bq, 0, i < 8 ? i * 8 : (j ^ ((0xBD98u >> (i - 8) * 4) & 15)) * 8, j * 4);
            }
#pragma unroll 1
            for (int i = 0; i < 4; i++) xload(sb, i, j, -1, &tmx);
            bsync<3, 320>();
            if (l16 == 0) PG(32);
            if (GH && j == 0 && elect()) asm volatile("{\n.reg .b64 a;\nmov.b64 a, {%0,%1};\nred.relaxed.gpu.global.inc.u32 [a+64], 4;\n}" ::"r"(xlo + XO_FL + h * 128), "r"(xhi) : "memory");
            __syncwarp();
            g_arrive(xlo + XO_FL + h * 128, xhi, 4);
            if (WOP < 4) barv<2, 64>();
            if (l16 == 0) PG(33);
            g_wait(xlo + XO_FL + h * 128, xhi);
            if (l16 == 0) PG(34);
#pragma unroll 1
            for (int i = 0; i < 4; i++)
                if (elect()) kvload(sb, i, h, j, 0, xlo, xhi);
            mbar_wait(bq + BAR_KV, 0);
            if (l16 == 0) PG(14);
        } else if (u == 1) {
            const uint32_t l = l16 >> 4, x = h * 8 + (l >> 2), d = (x & ~31u) + (l & 3) * 8 + ((x & 31) >> 2) + (x & 3) * 2 * DM;
            const unsigned short* m0 = (const unsigned short*)mem0 + j * 256;
            const uint32_t v1 = m0[d] | (((l & 3) == 3 ? 0x4200u : m0[d + DM]) << 16);
            const uint32_t v3 = h < 8 ? m0[h * 32 + 24 + (l >> 2) + ((l & 3) * 2 + 1) * DM] | 0x42000000u : 0;
#pragma unroll 1
            for (uint32_t i = 0; i < 12; i++) {
                if (i == 10) { sts32(sb + SM_WO + 6144 + l * 4, v1); sts32(sb + SM_WO + 6272 + l * 4, v3); }
                asm volatile("fence.proxy.async.shared::cta;" ::: "memory");
                __syncwarp();
                const uint32_t c = (0x21924u >> ((i - 3) * 2)) & 3;
                if (elect()) {
                    if (i < 3) bulk_s2g(xlo + XO_XG + (i * 128 + role) * 6144, xhi, sb + SM_WO, 6144);
                    else bulk_s2g(xlo + XO_R + rpage(j, i < 6 ? 0 : i < 9 ? 1 : -1) + c * 16384 + h * 128, xhi, sb + SM_WO + (i < 10 ? 0 : 6144 + c * 64), 128);
                }
            }
            asm volatile("cp.async.bulk.wait_group 0;" ::: "memory");
            if (elect()) asm volatile("{\n.reg .b64 a;\nmov.b64 a, {%0,%1};\nred.relaxed.gpu.global.inc.u32 [a], 127;\n}" ::"r"(xlo + XO_TK + 12), "r"(xhi) : "memory");
            if (l16 == 0) PG(16);
            g_wait(xlo + XO_TK + 12, xhi);
            if (l16 == 0) PG(17);
            barv<5, 288>();
            bsync<8, 320>();
            asm volatile("fence.acq_rel.gpu;" ::: "memory");
        } else {
            GSYNC(0);
            mbar_wait(bq + BAR_WE + 48, 0);
#pragma unroll 1
            for (int e = 0; e < 24; e++) sts128(sb + SM_TR + 4096 + e * 512 + l16, 0, 0, 0, 0);
            barv<3, 320>();
            bsync<8, 320>();
#pragma unroll 1
            for (int i = 0; i < 4; i++) xload(sb, i, j, 0, &tmx);
        }
#pragma unroll 1
        for (int s = 0; s < nseg; s++) helper_step(sb, w, h, j, l16, xlo, xhi, zero, s, &tmx, &tmb);
        piwait(sb, 0, nseg - 2);
        bsync<9, 384>();
        GSYNC(1);
        if (!GS && w == 11 && elect()) asm volatile("prefetch.tensormap [%0];" ::"l"(&tmy) : "memory");
        if (GH && w == 10) { g_arrive(xlo + XO_FL + h * 128 + 64, xhi, 5); PG(2); }
        if (w < 10) {
            uint32_t kb = 2, heads = 0;
            asm volatile("fence.proxy.async.shared::cta;" ::: "memory");
            if (GH) {
                if (w == 9 && h >= 30) { kb = 0; heads = 0xFFFF; }
                else delay_until(clk(), GD);
            } else if (w == 9) {
                g_arrive(xlo + XO_TK + 192, xhi, 128);
                PG(2);
                if (h >= 30) { g_wait(xlo + XO_TK + 192, xhi); kb = 0; }
                PG(3);
            } else delay_until(clk(), GD);
#pragma unroll 1
            for (; kb < 32; kb++) {
                if (kb >= 4) mbar_wait(bq + BAR_GE + (kb & 3) * 8, ((kb >> 2) & 1) ^ 1);
                if (GH && ((heads >> (kb >> 1)) & 1)) {
                    int it = 0;
                    do {
                        uint32_t v;
                        asm volatile("{\n.reg .b64 a;\nmov.b64 a, {%1,%2};\nld.acquire.gpu.global.u32 %0, [a+64];\n}"
                                     : "=r"(v) : "r"(xlo + XO_FL + (role & 1) * 2048 + (l16 & 255) * 8), "r"(xhi) : "memory");
                        heads = __ballot_sync(0xFFFFFFFFu, v != 0);
                        if (++it > SPIN_LIMIT) die(it);
                    } while ((heads >> (kb >> 1)) & 1);
                    asm volatile("fence.proxy.async.global;" ::: "memory");
                    if (kb == 0) PG(3);
                }
                g_load(sb, w - 8, role, kb, xlo, xhi, &tmb);
            }
        }
        if (role == 0 && w == 11 && elect()) tickets_done((uint32_t*)(((uint64_t)xhi << 32) | (xlo + XO_TK)));
    } else {
        asm volatile("setmaxnreg.inc.sync.aligned.u32 240;");
        uint32_t Wq[16][4], Wk[16][4], Wv[NA][4];
        uint32_t t16, KA, KB, KC, KD;
        {
            const uint32_t lane = l16 >> 4, g = lane >> 2, t = lane & 3;
            const uint32_t rw = (((lane >> 4) & 1) * 8 + (lane & 7)) * 128u;
            const uint32_t off = rw + ((((w & 3) * 2 + ((lane >> 3) & 1)) ^ (lane & 7)) << 4);
            const uint32_t offo = rw + ((((w & 1) * 4 + ((lane >> 3) & 1)) ^ (lane & 7)) << 4);
            const uint32_t r = 2 * (t & 1) + (g >> 2);
            const uint32_t mk0 = t < 2 ? 0 : (r == 0 ? 2 * g > w : j + r < 4), mk1 = t < 2 ? 0 : (r == 0 ? 2 * g + 1 > w : j + r < 4);
            t16 = __shfl_sync(0xFFFFFFFFu, w * 512 + l16, lane);
            KA = __shfl_sync(0xFFFFFFFFu, (w * 512 + t * 64 + g * 8) | ((w * 512 + (g & 1) * 256 + (g >> 1) * 64 + t * 16) << 16), lane);
            KB = __shfl_sync(0xFFFFFFFFu, ((w >> 2) * WV_BOX + off) | mk0 | (mk1 << 1) |
                                              ((w * 256 + (g >> 2) * 4096 + (g & 3) * 64 + t * 16) << 16), lane);
            KC = __shfl_sync(0xFFFFFFFFu, ((lane & 7) * 1280 + (lane >> 3) * 128 + ((w ^ (lane & 7)) << 4)) | (((t >> 1) * 16 + g * 2) << 16) | ((t * 64 + g * 8) << 24), lane);
            KD = __shfl_sync(0xFFFFFFFFu, ((w >> 1) * WO_BOX + offo) | (((lane & 7) * 208 + (lane >> 3) * 16) << 16), lane);
            if (threadIdx.x == 0) PG(8);
#define WTAKE(W, c, k0) { mbar_wait(bq + BAR_WF + (c) * 8, 0); \
                _Pragma("unroll") for (int ks = 0; ks < 4; ks++) ldsm4t(W[(k0) + ks], sb + SM_ST + ((c) & 3) * 16384 + (KB & 0xFFF0) + ks * 2048); \
                if ((c) < 8) { __syncwarp(); if (elect()) mbar_arrive(bq + BAR_WE + (c) * 8); } }
#pragma unroll
            for (int c = 0; c < 4; c++) WTAKE(Wq, c, c * 4);
            mbar_wait(bq, 0);
            if (threadIdx.x == 0) PG(9);
            xstart<0>(sb, w, xlo + h * 24576, xhi, j, t16, KA, Wq);
            if (threadIdx.x == 0) PG(10);
#pragma unroll
            for (int c = 0; c < 4; c++) WTAKE(Wk, c + 4, c * 4);
            if (threadIdx.x == 0) PG(11);
            xstart<1>(sb, w, xlo + h * 24576, xhi, j, t16, KA, Wk);
            if (threadIdx.x == 0) PG(12);
            WTAKE(Wv, 8, 0);
            WTAKE(Wv, 9, 4);
            mbar_wait(bq + BAR_WF + 80, 0);
            WTAKE(Wv, 11, 8);
            if (threadIdx.x == 0) PG(13);
            xstart<2>(sb, w, xlo + h * 24576, xhi, j, t16, KA, Wv);
            mbar_wait(bq + BAR_XA, 0);
            bsync<8, 320>();
        }
        const uint32_t ONES = 0x3F803F80u;
#define UNI(x) __reduce_max_sync(0xFFFFFFFFu, x)
        uint32_t swi = UNI((uint32_t)((uint64_t)smem >> 32));
        const uint32_t sbw = UNI(sb + w * 256), sbm = UNI(sb - w * 512), sbs = UNI(sb + w * 768), sbp = UNI(sb + w * 208);
#define OPQALL() { OPQ(t16); OPQ(KA); OPQ(KB); OPQ(KC); OPQ(KD); }
        OPQALL();
        if (SEED & 1) OPQ(Wq[0][0]);
        if (SEED & 2) OPQ(Wq[5][1]);
        if (SEED & 4) OPQ(Wk[0][0]);
        if (SEED & 8) OPQ(Wk[15][2]);
        if (SEED & 16) OPQ(Wv[0][0]);
        if (SEED & 32) OPQ(Wv[7][3]);
        const uint32_t cb0 = (h >> 1) * 32768 + (j & 1) * 16384 + (h & 1) * 8192;
        const uint32_t cb = UNI(xlo + cb0 + ((par(cb0) ^ (j >> 1) ^ CFAR) << 12)), cv = UNI(xlo + h * 8192 + JV(h, j) * 2048), h1 = UNI((h & 1) * 1024);
        const uint32_t uox = UNI(xlo + XO_OX + (h * 2 + (w >> 2)) * 262144 + j * 1024 + (w & 3) * 256 - w * 128);
        uint32_t rp = UNI(xlo + rpage(j, 0));
        float ox[4];
        float4 dn;
#define OXSTORE(s) asm volatile("{\n.reg .b64 a;\nmov.b64 a, {%0,%1};\nst.global.u32 [a], %2;\nst.global.u32 [a+128], %3;\n}" \
                                ::"r"(uox + (s) * 4096 + (t16 >> 2)), "r"(xhi), \
                                  "r"(pack2(ox[0] * dn.y, ox[1] * dn.w)), "r"(pack2(ox[2] * dn.y, ox[3] * dn.w)) : "memory")
#pragma unroll 1
        for (int s2 = 0;; s2 += 2, rp ^= 0x21000)
#pragma unroll
        for (int p = 0; p < 2; p++) {
            const int s = s2 + p;
            const uint32_t ctag = ((s2 >> 1) & 1) ^ 1;
            const uint32_t hb = cb ^ (p * 0x81000), rb = rp ^ (p * 0x11000);
            uint4 k0, k1, qq, c0, c1, c2, c3, pk;
            float va[4], vb[4];
            uint32_t qx0, qx1, ov0, ov1, wv[16 - NA][4];
            {
                float xa[16], xb[16];
                uint4 m0, n0;
                uint32_t e0, f0;
                uint32_t xp[8];
                wg_fence();
                XMMA(0, 6);
                SF();
                piwait(sb, p, s - 2);
                uint4 pi = xpeer<0>(sb, p ^ 1, t16);
                SF();
#define MR (VC ? 1 : 2)
#define MC (VC ? 2 : 1)
#define QPARK() { xpack<0>(xp, xa); xpark<0>(xp, pi, sb, sbw, p ^ 1, t16, KA); pi = xpeer<MR>(sb, p ^ 1, t16); SF(); }
                wg_fence();
                if (QP) {
                    XMMA(6, QP);
                    XMMA(QP, QP + 4);
                    wg_wait<1>();
                    SF();
                    QPARK();
                    wg_fence();
                    if (QP + 4 < RPOS) XMMA(QP + 4, RPOS);
                } else XMMA(6, RPOS);
                if (RPOS < 32) XMMA(RPOS, RPOS + 4 < 32 ? RPOS + 4 : 32);
                uint32_t a = (p ? rp : rp ^ 0x30000) + t16, e = (p ? rp : rp ^ 0x30000) + (t16 >> 2), ah = xhi, eh = xhi;
                OPQ(a); OPQ(e); OPQ(ah); OPQ(eh);
                SF();
                wg_wait<(RPOS < 32)>();
                SF();
                PT(11);
                RLOAD();
                SF();
                if (!QP) QPARK();
                if (RPOS + 4 < 32) {
                    wg_fence();
                    XMMA(RPOS + 4, 32);
                    SF();
                }
                wg_wait<0>();
                xpack<MR>(xp, xb);
                xpark<MR>(xp, pi, sb, sbw, p ^ 1, t16, KA);
                uint32_t acw, ahi, tg;
#define APREP() { OPQ(KA); if (!APH) OPQ(t16); acw = hb + (KA & 0xFFFF); ahi = xhi; tg = ctag; OPQ(acw); OPQ(ahi); OPQ(tg); }
                if (APH == 3) SF();
                if (APH) APREP();
                if (APH >= 2) OPQ(t16);
                SF();
                PT(12);
                {
                    int it = 0;
                    if (RDW) {
                        bool rb_;
#pragma unroll 1
                        do {
                            rb_ = ruse(sb + SM_MEMT + t16, m0, n0, e0, f0);
                            if (RDW == 2) MF();
                            if (RDW == 3) SF();
                            asm volatile("{\n.reg .pred p, q;\n.reg .b64 a, e;\nsetp.ne.u32 p, %15, 0;\nmov.b64 a, {%11,%12};\nmov.b64 e, {%13,%14};\n"
                                         "@p ld.relaxed.gpu.global.v4.u32 {%0,%1,%2,%3}, [a];\n@p ld.relaxed.gpu.global.v4.u32 {%4,%5,%6,%7}, [a+16384];\n"
                                         "@p ld.relaxed.gpu.global.u32 %8, [e+32768];\n@p ld.relaxed.gpu.global.u32 %9, [e+33792];\n"
                                         "add.u32 %10, %10, 1;\nsetp.gt.u32 q, %10, 1048576;\n@q st.shared.u32 [%10], %10;\n}"
                                         : "+r"(m0.x), "+r"(m0.y), "+r"(m0.z), "+r"(m0.w), "+r"(n0.x), "+r"(n0.y), "+r"(n0.z), "+r"(n0.w), "+r"(e0), "+r"(f0), "+r"(it)
                                         : "r"(a), "r"(ah), "r"(e), "r"(eh), "r"((uint32_t)rb_) : "memory");
                        } while (rb_);
                    } else
                    while (ruse(sb + SM_MEMT + t16, m0, n0, e0, f0)) {
                        RLOAD();
                        if (++it > SPIN_LIMIT) die(it);
                    }
                    PC(22, it + 1);
                }
                PT(13);
                if (APH == 1) OPQ(t16);
                if (!APH) APREP();
#define AX (p ? A1 : A0)
                float q[4], k[4];
                if (AX & 2) _Pragma("unroll") for (int i = 0; i < 4; i++) {
                    asm volatile("mov.b32 %0, %1;" : "=f"(q[i]) : "r"(zero)); asm volatile("mov.b32 %0, %1;" : "=f"(k[i]) : "r"(zero)); }
                if (APH < 2) SF();
                bsync<1, 384>();
                PT(0);
                uint32_t b[8][4];
#pragma unroll
                for (int i = 0; i < 8; i++) {
                    const int pp = i < 2 || (AX & 8) || ((AX & 16) && i >= 6) ? i : i ^ 1;
                    ldsm4t(b[pp], sbm + SM_MEMT + t16 + pp * 512);
                    if (i < 7 || (AX & 4)) MF();
                }
                if (ASF) SF();
                const uint32_t aWv = sb + SM_WV + (KB & 0xFFF0);
#define WVLD(n0, n1) _Pragma("unroll") for (int n = (n0); n < (n1) && n < 16 - NA; n++) ldsm4t(wv[n], aWv + n * 2048)
#pragma unroll
                for (int ks = 0; ks < 16; ks++) {
                    const uint32_t b0 = b[ks >> 1][(ks & 1) * 2], b1 = b[ks >> 1][(ks & 1) * 2 + 1];
                    if (AX & 1) {
                        if (ks == 0 && !(AX & 2)) {
                            mma16z(k, Wk[0][0], Wk[0][1], Wk[0][2], Wk[0][3], b0, b1);
                            mma16z(q, Wq[0][0], Wq[0][1], Wq[0][2], Wq[0][3], b0, b1);
                        } else {
                            mma16(k, Wk[ks][0], Wk[ks][1], Wk[ks][2], Wk[ks][3], b0, b1);
                            mma16(q, Wq[ks][0], Wq[ks][1], Wq[ks][2], Wq[ks][3], b0, b1);
                        }
                    } else if (ks == 0 && !(AX & 2)) {
                        mma16z(q, Wq[0][0], Wq[0][1], Wq[0][2], Wq[0][3], b0, b1);
                        mma16z(k, Wk[0][0], Wk[0][1], Wk[0][2], Wk[0][3], b0, b1);
                    } else {
                        mma16(q, Wq[ks][0], Wq[ks][1], Wq[ks][2], Wq[ks][3], b0, b1);
                        mma16(k, Wk[ks][0], Wk[ks][1], Wk[ks][2], Wk[ks][3], b0, b1);
                    }
                    if (ks == 10 && VPF) { SF(); WVLD(0, VPF); }
                }
                const uint32_t oq0 = settag(pack2(q[0], q[2]), tg), oq1 = settag(pack2(q[1], q[3]), tg);
                const uint32_t ok0 = pack2(k[0], k[2]), ok1 = pack2(k[1], k[3]);
                stg2<XO_CQK>(acw, ahi, oq0, ok0);
                stg2<XO_CQK + 256>(acw, ahi, oq1, ok1);
                SF();
                PT(1);
#define CLOADG() { c2 = ldg4<XO_CQK>((hb ^ 0x1000) + (KA >> 16), xhi); c3 = ldg4<XO_CQK>((hb ^ 0x5000) + (KA >> 16), xhi); }
#define CLOAD0() c0 = lds128(sb + SM_TR + (KA >> 16))
#define CLOAD1() c1 = lds128(sb + SM_TR + 4096 + p * 4096 + (KA >> 16))
#define CLOADS() { CLOAD0(); CLOAD1(); }
#define CSIDE(n) { if (CGP == (n)) CLOADG(); if (C0P == (n)) CLOAD0(); if (C1P == (n)) CLOAD1(); if (PIP == (n)) pk = xpeer<MC>(sb, p ^ 1, t16); \
                   if (QSP == (n)) { qx0 = (t16 & 64) ? qq.y : qq.x; qx1 = (t16 & 64) ? qq.w : qq.z; } }
#pragma unroll
                for (int rd = 0; rd < 8; rd++) {
                    const int pp = (VORD >> (28 - 4 * rd)) & 7;
                    const uint32_t* a = 2 * pp < NA ? Wv[2 * pp < NA ? 2 * pp : 0] : wv[2 * pp < NA ? 0 : 2 * pp - NA];
                    const uint32_t* c = 2 * pp < NA ? Wv[2 * pp < NA ? 2 * pp + 1 : 0] : wv[2 * pp < NA ? 0 : 2 * pp + 1 - NA];
                    if (rd == 0) {
                        mma16z(va, a[0], a[1], a[2], a[3], b[pp][0], b[pp][1]);
                        mma16z(vb, c[0], c[1], c[2], c[3], b[pp][2], b[pp][3]);
                        if (VSB & 256) SF();
                        OPQ(swi);
                        asm volatile("{\n.reg .b64 a;\nmov.b64 a, {%0,%1};\nst.v2.u32 [a], {%2,%3};\nst.v2.u32 [a+256], {%4,%5};\n}"
                                     ::"r"((KA & 0xFFF) + (sb ^ 0x1000000) + SM_TR + 4096 + p * 4096), "r"(swi), "r"(oq0), "r"(ok0), "r"(oq1), "r"(ok1) : "memory");
                        sts64(sb + SM_TR + (KA & 0xFFF), oq0, ok0);
                        sts64(sb + SM_TR + (KA & 0xFFF) + 256, oq1, ok1);
                    } else {
                        mma16(va, a[0], a[1], a[2], a[3], b[pp][0], b[pp][1]);
                        mma16(vb, c[0], c[1], c[2], c[3], b[pp][2], b[pp][3]);
                    }
                    if (rd == (p ? KEP : KEP0)) { KEEP(t16, oq0, oq1, ok0, ok1); if (KE2) KEEP(t16, acw, ahi, acw, ahi); }
                    if (((p ? VSB : VSB0) >> rd) & 1) SF();
                    if (rd == W2P) WVLD(2, 3);
                    if (rd == W3P) WVLD(3, 4);
                    if (rd == K0P) k0 = lds128(sb + SM_KV + 2048 + (KB >> 16));
                    if (rd == K0P + 1) k1 = lds128(sb + SM_KV + 10240 + (KB >> 16));
                    if (rd == QQP) qq = lds128(sbw + SM_KV + ((KA >> 16) & 0xFF));
                    CSIDE(rd);
                    if ((VSF >> rd) & 1) SF(); else if ((VMF >> rd) & 1) MF();
                }
#define VTAIL() { ov0 = pack2(va[0] + vb[0], va[1] + vb[1]); ov1 = pack2(va[2] + vb[2], va[3] + vb[3]); \
                  stg2<XO_CV>(cv + p * 262144 + (t16 >> 1), xhi, settag(ov0, ctag), ov1); \
                  if (VD) asm volatile("{\n.reg .b64 a;\nmov.b64 a, {%0,%1};\nst.v2.u32 [a], {%2,%3};\n}" \
                                     ::"r"((t16 >> 1) + (sb ^ 0x1000000) + SM_VP + p * 2048), "r"(swi), "r"(settag(ov0, ctag)), "r"(ov1) : "memory"); \
                  barv<8, 384>(); OPQ(t16); SF(); }
                if (!VTP) VTAIL();
            }
            PT(2);
            PDUMP();
            {
                const uint32_t a0 = sb + SM_KV;
                float xa[16], xb[16];
                uint32_t xp[8];
                if (CGP == 12 || QSP == 12) { CSIDE(12); SF(); }
                wg_fence();
                XMMA(32, 32 + CPOS);
                if (CGP == 13) { SF(); CSIDE(13); SF(); wg_fence(); }
                if (VR == 1) { XMMA(32 + CPOS, 36); XMMA(36, 36 + CW2); wg_wait<2>(); }
                else if (CW) { XMMA(32 + CPOS, 36 + CPOS); wg_wait<1>(); }
                SF();
                CSIDE(8);
                SF();
                if (VR == 1) { wg_wait<1>(); SF(); }
                if (VTP) VTAIL();
                CSIDE(9);
                SF();
                wg_fence();
                XMMA(VR == 1 ? 36 + CW2 : 32 + CPOS + (CW ? 4 : 0), 48);
                SF();
                uint2 u1, u2, u3;
#define ULOADG() { u2 = ldg2<XO_CV>((cv ^ 4096) + p * 262144 + (t16 >> 1), xhi); u3 = ldg2<XO_CV>((cv ^ 6144) + p * 262144 + (t16 >> 1), xhi); }
#define ULOADS() u1 = lds64(sb + SM_VP + p * 2048 + (t16 >> 1))
#define UCHECK() { int it = 0; \
                   while (__builtin_expect(any_bad(tagx1(tagx2(u2.x, u3.x, ctag), u1.x, ctag)), 0)) { OPQ(t16); ULOADG(); ULOADS(); if (++it > SPIN_LIMIT) die(it); } \
                   PC(26, it); }
                CSIDE(10);
                if (B3 == 8 && VLP == 2) ULOADG();
                SF();
                const uint32_t ka[4] = {k0.x, k0.y, k0.z, k0.w}, kb[4] = {k1.x, k1.y, k1.z, k1.w};
                const uint32_t aSp = sb + SM_SP + (KC & 0xFFFF);
                PT(3);
#define BAR3() asm volatile("{\n.reg .pred p;\nsetp.eq.u32 p, %0, 0;\n@p bar.arrive 3, %1;\n}" ::"r"((uint32_t)bad), "n"(B3 == 6 ? 288 : 384) : "memory")
#define SCORES(FIRST) { \
                    const uint32_t qA = hadd2(hadd2(c0.x, c1.x), hadd2(c2.x, c3.x)), qB = hadd2(hadd2(c0.z, c1.z), hadd2(c2.z, c3.z)); \
                    const uint32_t kA = hadd2(hadd2(c0.y, c1.y), hadd2(c2.y, c3.y)), kB = hadd2(hadd2(c0.w, c1.w), hadd2(c2.w, c3.w)); \
                    bad = any_bad(or3(tagx2(c1.x, c1.z, ctag), tagx2(c2.x, c2.z, ctag), tagx2(c3.x, c3.z, ctag))); \
                    float sa[4], sb_[4], sc[4], sd[4], se[4]; \
                    if (FIRST) { SF(); if (B3 == 8 && VLP == 3) ULOADG(); CSIDE(11); wg_wait<0>(); } \
                    mma16z(sa, ka[0], ka[1], ka[2], ka[3], qA, qB); \
                    mma16z(sb_, kb[0], kb[1], kb[2], kb[3], qA, qB); \
                    mma16z(sc, qA, qx0, qB, qx1, kA, kB); \
                    if (FIRST) { \
                        xpack<MC>(xp, xa); \
                        if (KPOS == 0) { xadd(xp, pk); xstore<MC>(xp, sb, sbw, p ^ 1, t16, KA); if (B3 >= 5) BAR3(); else if (!B3 || B3 >= 3) barv<3, 384>(); } \
                        mma16z(sd, ka[0], ka[1], ka[2], ka[3], qx0, qx1); \
                        mma16z(se, kb[0], kb[1], kb[2], kb[3], qx0, qx1); \
                    } \
                    stsm4t(aSp, pack2(sa[0], sa[1]), pack2(sa[2], sa[3]), pack2(sb_[0], sb_[1]), pack2(sb_[2], sb_[3])); \
                    stsm2(aSp + 1024, pack2(sc[0], sc[1]), pack2(sc[2], sc[3])); \
                    if (FIRST) { \
                        stsm4t(aSp + 512, pack2(sd[0], sd[1]), pack2(sd[2], sd[3]), pack2(se[0], se[1]), pack2(se[2], se[3])); \
                        if (KPOS == 0) { KEEP(KD, xp[0], xp[1], xp[2], xp[3]); KEEP(KD, xp[4], xp[5], xp[6], xp[7]); } \
                    } }
                int it = 0;
                bool bad;
                SCORES(true);
                while (__builtin_expect(bad, 0)) {
                    OPQ(KA);
                    CLOADG();
                    CLOADS();
                    SCORES(false);
                    if (B3 >= 5) BAR3();
                    if (++it > SPIN_LIMIT) die(it);
                }
                PC(25, it);
                PT(4);
                if (B3 == 8 && VLP == 0) ULOADG();
                if (B3 == 1) barv<3, 384>();
                bsync<4, B3 == 2 ? 384 : 256>();
                uint32_t wo[16][4];
                const uint32_t aWo = sb + SM_WO + (KD & 0xFFFF), aWo1 = sb + SM_WO + ((KD & 0xFFFF) ^ 32);
#define WOLD(n0, n1) _Pragma("unroll") for (int n = (n0); n < (n1) && n < 16; n++) ldsm4t(wo[n], ((n & 1) ? aWo1 : aWo) + (n >> 1) * 2048)
                const bool hi = (t16 & 32) != 0;
                const uint32_t t8 = t16 >> 1;
                uint2 v0, v1, v2, v3;
                uint32_t es;
                {
                    uint32_t am[4], ax[4], a4[2];
                    const uint32_t aSr = sbs + SM_SP + t16;
                    ldsm4t(am, aSr);
                    ldsm4t(ax, aSr + 512);
                    ldsm2t(a4, aSr + 1024);
                    MF();
                    if (B3 == 8 && VLP == 1) ULOADG();
                    if (KPOS == 1) pk = xpeer<MC>(sb, p ^ 1, t16);
                    const uint32_t se = (t16 & 128) ? 0u : ONES, so = se ^ ONES;
                    float hm[4], hx[4], h4[4];
                    mma16z(hm, am[0], am[1], am[2], am[3], se, so);
                    mma16z(hx, ax[0], ax[1], ax[2], ax[3], se, so);
                    mma8z(h4, a4[0], a4[1], ONES);
                    SF();
                    if (KPOS == 1) { xpark<MC>(xp, pk, sb, sbw, p ^ 1, t16, KA); barv<3, 384>(); }
                    v0 = lds64(a0 + 4096 + t8); v1 = lds64(a0 + 8192 + t8); v2 = lds64(a0 + 12288 + t8); v3 = lds64(a0 + 16384 + t8);
                    if (B3 == 8) ULOADS();
                    WOLD(0, PF2);
                    float s0 = hi ? hx[0] : hm[0], s1 = hi ? hx[2] : hm[2];
                    const float s2 = hi ? h4[2] : h4[0];
                    s0 = (KB & 1) ? -1.0e9f * 11.313708499f : s0;
                    s1 = (KB & 2) ? -1.0e9f * 11.313708499f : s1;
                    int mi = __float_as_int(fmaxf(fmaxf(s0, s2), s1));
                    mi ^= (mi >> 31) & 0x7FFFFFFF;
                    const int mm = __reduce_max_sync(0xFFFFFFFFu, hi ? (int)0x80000000 : mi), mx = __reduce_max_sync(0xFFFFFFFFu, hi ? mi : (int)0x80000000);
                    SF();
                    WOLD(PF2, PF3);
                    SF();
                    mi = hi ? mx : mm;
                    mi ^= (mi >> 31) & 0x7FFFFFFF;
                    const float c2_ = 0.08838834764831845f * 1.4426950408889634f;
                    const float mc = __int_as_float(mi) * c2_;
                    const float e0 = ex2(fmaf(s0, c2_, -mc)), e1 = ex2(fmaf(s1, c2_, -mc)), e2 = ex2(fmaf(s2, c2_, -mc));
                    sts32(sbp + SM_P + (KC >> 25), pack2(e0, e1));
                    sts16(sbp + SM_P + 128 + ((KC >> 16) & 0xFF), pack2(e2, e2));
                    es = __float_as_uint(fmaf(e2, 0.5f, e0 + e1) + 64.f);
                }
                const uint32_t sm = __reduce_add_sync(0xFFFFFFFFu, hi ? 0u : es), sx = __reduce_add_sync(0xFFFFFFFFu, hi ? es : 0u);
                const uint32_t aPr = sb + SM_P + (KD >> 16);
                if (B3 == 8 && VCP == 0) UCHECK();
                PT(5);
                bsync<5, VB ? 256 : B3 == 6 ? 352 : 384>();
                uint32_t pm[4], px[4], p4[2];
                ldsm4(pm, aPr);
                MF();
                uint2 vs;
                #define VGET(n) if (VB == (n)) { if (VB) bsync<11, 384>(); vs = lds64(sb + SM_VS + t8); MF(); }
                if (B3 != 8) { VGET(0); VGET(1); }
                ldsm2(p4, aPr + 128);
                MF();
                VGET(2);
                ldsm4(px, aPr + 64);
                MF();
                VGET(3);
                sts32f(sb + SM_DN + w * 8 + ((t16 >> 3) & 4), rcp(__uint_as_float((hi ? sx : sm) - 15u * 0x42800000u) - 64.f));
                MF();
                if (B3 == 8 && VCP == 2) UCHECK();
                WOLD(PF3, NPF);
                if (B3 == 8 && VCP == 1) UCHECK();
                if (B3 == 8) { ov0 = hadd2(ov0, u1.x); ov1 = hadd2(ov1, u1.y); vs.x = hadd2(u2.x, u3.x); vs.y = hadd2(u2.y, u3.y); }
                const uint32_t vm0 = hadd2(ov0, vs.x), vm1 = hadd2(ov1, vs.y);
                float oa[4], ob[4];
                mma16z(oa, v0.x, v0.y, v1.x, v1.y, pm[0], pm[1]);
                mma16z(ob, v2.x, v2.y, v3.x, v3.y, pm[2], pm[3]);
                mma8(oa, vm0, vm1, p4[0]);
                stsm2(sbw + SM_OT + (t16 & 511), pack2(oa[0] + ob[0], oa[1] + ob[1]), pack2(oa[2] + ob[2], oa[3] + ob[3]));
                PT(6);
                SF();
                bsync<6, 256>();
                mma16z(ox, v0.x, v0.y, v1.x, v1.y, px[0], px[1]);
                uint32_t b[4][4];
#define OTLD(pp) ldsm4t(b[pp], sbm + SM_OT + t16 + (pp) * 512)
                OTLD(0);
                MF();
                OTLD(1);
                barv<7, 384>();
                mma16(ox, v2.x, v2.y, v3.x, v3.y, px[2], px[3]);
                mma8(ox, vm0, vm1, p4[1]);
                if (p == 1 && s + 1 == nseg) goto done;
                SF();
                uint32_t ar, ae, ahi = xhi;
                float r[2][4];
#pragma unroll
                for (int ks = 0; ks < 8; ks++) {
                    if (ks == 0) WOLD(NPF, NPF + WPF);
                    if (ks == OPOS) { OTLD(2); MF(); }
                    if (ks == OPOS + 2) { OTLD(3); MF(); }
                    if (ks > 0) WOLD(NPF + WPF + 2 * (ks - 1), NPF + WPF + 2 * ks);
                    if (ks == 5) {
                        OPQ(t16);
                        ar = rb + h1 * 16 + t16; ae = rb + h1 + (t16 >> 2);
                        OPQ(ar); OPQ(ahi); OPQ(ae);
                        dn = lds128f(sb + SM_DN + (t16 & 48));
                    }
#pragma unroll
                    for (int mt = 0; mt < 2; mt++) {
                        const int i = ks * 2 + mt;
                        const uint32_t* a = wo[i];
                        if (i < 2) mma16z(r[mt], a[0], a[1], a[2], a[3], b[ks >> 1][2 * (ks & 1)], b[ks >> 1][2 * (ks & 1) + 1]);
                        else mma16(r[mt], a[0], a[1], a[2], a[3], b[ks >> 1][2 * (ks & 1)], b[ks >> 1][2 * (ks & 1) + 1]);
                    }
                    if (NPF + WPF + 2 * ks < 16 || ks < 5) SF();
                }
                const float r0 = dn.x, r1 = dn.z;
                asm volatile("{\n.reg .b64 a;\nmov.b64 a, {%0,%2};\nred.relaxed.gpu.global.add.noftz.v4.bf16x2 [a], {%3,%4,%5,%6};\n"
                             "mov.b64 a, {%1,%2};\nred.relaxed.gpu.global.add.noftz.bf16x2 [a+32768], %7;\n}"
                             ::"r"(ar), "r"(ae), "r"(ahi), "r"(pack2(r[0][0] * r0, r[0][1] * r1)), "r"(pack2(r[0][2] * r0, r[0][3] * r1)),
                               "r"(pack2(r[1][0] * r0, r[1][1] * r1)), "r"(pack2(r[1][2] * r0, 1.f)), "r"(pack2(r[1][3] * r1, 1.f)) : "memory");
                barv<10, 384>();
            }
            SF();
            PT(10);
            OXSTORE(s);
            OPQALL();
        }
    done:
        dn = lds128f(sb + SM_DN + (t16 & 48));
        OXSTORE(nseg - 1);
        barv<9, 384>();
        g_main(sb, w, role, &tmy, out);
        if (threadIdx.x == 0) PG(0);
    }
}

template <int SC> DEVI void wg_rs128t(float (&d)[64], const uint32_t (&a)[4], uint64_t db) {
    if (SC) asm volatile("wgmma.mma_async.sync.aligned.m64n128k16.f32.bf16.bf16 "
        "{%0,%1,%2,%3,%4,%5,%6,%7,%8,%9,%10,%11,%12,%13,%14,%15,%16,%17,%18,%19,%20,%21,%22,%23,%24,%25,%26,%27,%28,%29,%30,%31,%32,%33,%34,%35,%36,%37,%38,%39,%40,%41,%42,%43,%44,%45,%46,%47,%48,%49,%50,%51,%52,%53,%54,%55,%56,%57,%58,%59,%60,%61,%62,%63}, "
        "{%64,%65,%66,%67}, %68, 1, 1, 1, 1;"
        : D4(+, 0), D4(+, 4), D4(+, 8), D4(+, 12), D4(+, 16), D4(+, 20), D4(+, 24), D4(+, 28), D4(+, 32), D4(+, 36), D4(+, 40), D4(+, 44), D4(+, 48), D4(+, 52), D4(+, 56), D4(+, 60) : "r"(a[0]), "r"(a[1]), "r"(a[2]), "r"(a[3]), "l"(db));
    else asm volatile("wgmma.mma_async.sync.aligned.m64n128k16.f32.bf16.bf16 "
        "{%0,%1,%2,%3,%4,%5,%6,%7,%8,%9,%10,%11,%12,%13,%14,%15,%16,%17,%18,%19,%20,%21,%22,%23,%24,%25,%26,%27,%28,%29,%30,%31,%32,%33,%34,%35,%36,%37,%38,%39,%40,%41,%42,%43,%44,%45,%46,%47,%48,%49,%50,%51,%52,%53,%54,%55,%56,%57,%58,%59,%60,%61,%62,%63}, "
        "{%64,%65,%66,%67}, %68, 0, 1, 1, 1;"
        : D4(=, 0), D4(=, 4), D4(=, 8), D4(=, 12), D4(=, 16), D4(=, 20), D4(=, 24), D4(=, 28), D4(=, 32), D4(=, 36), D4(=, 40), D4(=, 44), D4(=, 48), D4(=, 52), D4(=, 56), D4(=, 60) : "r"(a[0]), "r"(a[1]), "r"(a[2]), "r"(a[3]), "l"(db));
}
template <int SC> DEVI void wg_rs64t(float (&d)[32], const uint32_t (&a)[4], uint64_t db) {
    if (SC) asm volatile("wgmma.mma_async.sync.aligned.m64n64k16.f32.bf16.bf16 "
        "{%0,%1,%2,%3,%4,%5,%6,%7,%8,%9,%10,%11,%12,%13,%14,%15,%16,%17,%18,%19,%20,%21,%22,%23,%24,%25,%26,%27,%28,%29,%30,%31}, "
        "{%32,%33,%34,%35}, %36, 1, 1, 1, 1;"
        : D4(+, 0), D4(+, 4), D4(+, 8), D4(+, 12), D4(+, 16), D4(+, 20), D4(+, 24), D4(+, 28) : "r"(a[0]), "r"(a[1]), "r"(a[2]), "r"(a[3]), "l"(db));
    else asm volatile("wgmma.mma_async.sync.aligned.m64n64k16.f32.bf16.bf16 "
        "{%0,%1,%2,%3,%4,%5,%6,%7,%8,%9,%10,%11,%12,%13,%14,%15,%16,%17,%18,%19,%20,%21,%22,%23,%24,%25,%26,%27,%28,%29,%30,%31}, "
        "{%32,%33,%34,%35}, %36, 0, 1, 1, 1;"
        : D4(=, 0), D4(=, 4), D4(=, 8), D4(=, 12), D4(=, 16), D4(=, 20), D4(=, 24), D4(=, 28) : "r"(a[0]), "r"(a[1]), "r"(a[2]), "r"(a[3]), "l"(db));
}
template <int SC> DEVI void wg_rs40(float (&d)[20], const uint32_t (&a)[4], uint64_t db) {
    if (SC) asm volatile("wgmma.mma_async.sync.aligned.m64n40k16.f32.bf16.bf16 "
        "{%0,%1,%2,%3,%4,%5,%6,%7,%8,%9,%10,%11,%12,%13,%14,%15,%16,%17,%18,%19}, "
        "{%20,%21,%22,%23}, %24, 1, 1, 1, 0;"
        : D4(+, 0), D4(+, 4), D4(+, 8), D4(+, 12), D4(+, 16) : "r"(a[0]), "r"(a[1]), "r"(a[2]), "r"(a[3]), "l"(db));
    else asm volatile("wgmma.mma_async.sync.aligned.m64n40k16.f32.bf16.bf16 "
        "{%0,%1,%2,%3,%4,%5,%6,%7,%8,%9,%10,%11,%12,%13,%14,%15,%16,%17,%18,%19}, "
        "{%20,%21,%22,%23}, %24, 0, 1, 1, 0;"
        : D4(=, 0), D4(=, 4), D4(=, 8), D4(=, 12), D4(=, 16) : "r"(a[0]), "r"(a[1]), "r"(a[2]), "r"(a[3]), "l"(db));
}
template <int SC> DEVI void wg_rs8(float (&d)[4], const uint32_t (&a)[4], uint64_t db) {
    if (SC) asm volatile("wgmma.mma_async.sync.aligned.m64n8k16.f32.bf16.bf16 "
        "{%0,%1,%2,%3}, "
        "{%4,%5,%6,%7}, %8, 1, 1, 1, 0;"
        : D4(+, 0) : "r"(a[0]), "r"(a[1]), "r"(a[2]), "r"(a[3]), "l"(db));
    else asm volatile("wgmma.mma_async.sync.aligned.m64n8k16.f32.bf16.bf16 "
        "{%0,%1,%2,%3}, "
        "{%4,%5,%6,%7}, %8, 0, 1, 1, 0;"
        : D4(=, 0) : "r"(a[0]), "r"(a[1]), "r"(a[2]), "r"(a[3]), "l"(db));
}
template <int SC> DEVI void wg_ss64a(float (&d)[32], uint64_t da, uint64_t db) {
    if (SC) asm volatile("wgmma.mma_async.sync.aligned.m64n64k16.f32.bf16.bf16 "
        "{%0,%1,%2,%3,%4,%5,%6,%7,%8,%9,%10,%11,%12,%13,%14,%15,%16,%17,%18,%19,%20,%21,%22,%23,%24,%25,%26,%27,%28,%29,%30,%31}, "
        "%32, %33, 1, 1, 1, 1, 0;"
        : D4(+, 0), D4(+, 4), D4(+, 8), D4(+, 12), D4(+, 16), D4(+, 20), D4(+, 24), D4(+, 28) : "l"(da), "l"(db));
    else asm volatile("wgmma.mma_async.sync.aligned.m64n64k16.f32.bf16.bf16 "
        "{%0,%1,%2,%3,%4,%5,%6,%7,%8,%9,%10,%11,%12,%13,%14,%15,%16,%17,%18,%19,%20,%21,%22,%23,%24,%25,%26,%27,%28,%29,%30,%31}, "
        "%32, %33, 0, 1, 1, 1, 0;"
        : D4(=, 0), D4(=, 4), D4(=, 8), D4(=, 12), D4(=, 16), D4(=, 20), D4(=, 24), D4(=, 28) : "l"(da), "l"(db));
}

#define G_ROWS 514
__device__ uint4 g_G[64 * G_ROWS * 8];
__device__ uint4 g_GN[64 * 8];
__device__ uint4 g_WN[1152];
#define FS_F2 196608
#define FS_TB (FS_F2 + 8192)
#define FS_NQ (FS_TB + 16384)
#define FS_BAR (FS_NQ + 128)
#define FS_NY (FS_NQ + 1024 + 128)
#define FS_TOTAL (FS_NQ + 3072)
#define F_THREADS 512

DEVI uint32_t cis(int j) {
    const float a = fmaf(__uint_as_float((((j + 1024) << 12) & 0x7FF000) | 0x3F800000), 6.283185307179586f, -9.42477796076938f);
    return pack2(__cosf(a), __sinf(a));
}
DEVI uint32_t cos2(int j0, int j1) {
    const float f = 6.283185307179586f / 2048.f;
    return pack2(__cosf((float)(((j0 + 1024) & 2047) - 1024) * f), __cosf((float)(((j1 + 1024) & 2047) - 1024) * f));
}
DEVI void twid(int j, float& c, float& s) {
    const float a = (float)(((j + 512) & 1023) - 512) * (6.283185307179586f / 1024.f);
    c = __cosf(a) * (1.f / 1024.f);
    s = __sinf(a) * (1.f / 1024.f);
}
template <bool B> struct Bool { static constexpr bool v = B; };
DEVI uint32_t opq(uint32_t& x, uint32_t zero) { OPQ(x); return x; }
DEVI uint32_t tidx() { uint32_t r; asm volatile("mov.u32 %0, %%tid.x;" : "=r"(r)); return r; }
DEVI void tma4d(uint32_t dst, const CUtensorMap* tm, uint32_t bar, int c0, int c1, int c2, int c3) {
    asm volatile("cp.async.bulk.tensor.4d.shared::cluster.global.mbarrier::complete_tx::bytes [%0], [%1, {%3, %4, %5, %6}], [%2];"
                 ::"r"(dst), "l"(tm), "r"(bar), "r"(c0), "r"(c1), "r"(c2), "r"(c3) : "memory");
}
DEVI void tma3s(const CUtensorMap* tm, uint32_t src, int c0, int c1, int c2) {
    asm volatile("cp.async.bulk.tensor.3d.global.shared::cta.bulk_group [%0, {%2, %3, %4}], [%1];" ::"l"(tm), "r"(src), "r"(c0), "r"(c1), "r"(c2) : "memory");
}
DEVI void tma4s(const CUtensorMap* tm, uint32_t src, int c0, int c1, int c2, int c3) {
    asm volatile("cp.async.bulk.tensor.4d.global.shared::cta.bulk_group [%0, {%2, %3, %4, %5}], [%1];"
                 ::"l"(tm), "r"(src), "r"(c0), "r"(c1), "r"(c2), "r"(c3) : "memory");
}
DEVI void bulk_commit() { asm volatile("cp.async.bulk.commit_group;" ::: "memory"); }
DEVI void fence_async() { asm volatile("fence.proxy.async;" ::: "memory"); }
DEVI void fence_smem() { asm volatile("fence.proxy.async.shared::cta;" ::: "memory"); }
DEVI void wgbar(uint32_t q) { asm volatile("bar.sync %0, 128;" ::"r"(q + 2) : "memory"); }
DEVI void grid_arrive(uint32_t* c, uint32_t n) { asm volatile("fence.proxy.async;\nred.release.gpu.global.inc.u32 [%0], %1;" ::"l"(c), "r"(n - 1) : "memory"); }
DEVI void grid_wait(uint32_t* c) {
    uint32_t v;
    int it = 0;
    do {
        asm volatile("ld.acquire.gpu.global.u32 %0, [%1];" : "=r"(v) : "l"(c) : "memory");
        if (++it > (1 << 22)) die(it);
    } while (v);
    fence_async();
}

template <bool INV, class S1, class S2>
DEVI void fft_rows(uint32_t grp, uint32_t q, const uint32_t (&F)[2][4], const float (&tc)[8], const float (&ts)[8], uint32_t so, float fx, uint32_t nq,
                   S1 sh1, S2 sh2) {
    float d[64];
    const uint64_t db = INV ? mkdesc(grp, 1024, 2048) : (mkdesc(grp, 2048, 512) ^ ((uint64_t)3 << 62));
    wg_fence();
    wg_rs128t<0>(d, F[0], db);
    wg_rs128t<1>(d, F[1], db + (INV ? 256 : 64));
    wg_commit();
    SF();
    sh1();
    float4 ny;
    if (INV) ny = lds128f(nq);
    wg_wait<0>();
    if (INV) { d[0] = fmaf(fx, ny.x, d[0]); d[16] = fmaf(fx, ny.y, d[16]); d[32] = fmaf(fx, ny.z, d[32]); d[48] = fmaf(fx, ny.w, d[48]); }
    uint32_t a[2][4][4];
    float e[2][INV ? 16 : 20];
    const uint64_t df = mkdesc(SB0 + FS_F2, 16, 1024);
#pragma unroll
    for (int s = 0; s < 2; s++) {
#pragma unroll
        for (int i = 0; i < 4; i++)
#pragma unroll
            for (int h = 0; h < 2; h++) {
                const float* x = d + (2 * s + h) * 16 + i * 4;
                a[s][i][h] = pack2(fmaf(x[2], ts[2 * i], x[0] * tc[2 * i]), fmaf(x[3], ts[2 * i + 1], x[1] * tc[2 * i + 1]));
                a[s][i][h + 2] = pack2(fmaf(-x[0], ts[2 * i], x[2] * tc[2 * i]), fmaf(-x[1], ts[2 * i + 1], x[3] * tc[2 * i + 1]));
            }
        wg_fence();
#pragma unroll
        for (int i = 0; i < 4; i++) {
            if constexpr (INV) { if (i == 0) wg_rs32<0>(e[s], a[s][i], df); else wg_rs32<1>(e[s], a[s][i], df + i * 2); }
            else { if (i == 0) wg_rs40<0>(e[s], a[s][i], df); else wg_rs40<1>(e[s], a[s][i], df + i * 2); }
        }
        wg_commit();
    }
    SF();
    sh2();
#pragma unroll
    for (int s = 0; s < 2; s++) {
        if (s == 0) wg_wait<1>(); else wg_wait<0>();
        float* x = e[s];
        if constexpr (!INV) {
            x[0] *= fx; x[1] *= fx; x[2] *= fx; x[3] *= fx;
            if (fx != 1.f) sts64(nq + s * 8, pack2(x[16], 0.f), pack2(x[18], 0.f));
        }
        const uint32_t o = grp + (INV ? so + s * 4096 : so ^ (s * 576));
#pragma unroll
        for (int b = 0; b < 2; b++)
            stsm4t(o + b * (INV ? 1024 : 4096), pack2(x[8 * b], x[8 * b + 1]), pack2(x[8 * b + 2], x[8 * b + 3]), pack2(x[8 * b + 4], x[8 * b + 5]),
                   pack2(x[8 * b + 6], x[8 * b + 7]));
    }
}

template <bool INV>
DEVI void fft_gen(uint32_t a, uint32_t n2) {
    const uint32_t tid = tidx(), x = ((tid >> 4) & 24) + (tid & 3), o = (tid & 4) * 128;
    if (INV) {
        const uint32_t r = (tid & 64) * 16 + (tid & 16) * 32 + (tid & 40) * 8 + n2;
        sts128(a + tid * 16, cis(o - r * x), cis(o - (r + 128) * x), cis(o - r * (x + 4)), cis(o - (r + 128) * (x + 4)));
    } else {
        const uint32_t r = 64 * x + n2, k = ((tid >> 2) & 24) + ((tid >> 3) & 3);
        sts128(a + tid * 16, cis(r * k + o), cis(r * (k + 4) + o), cis((r + 256) * k + o), cis((r + 256) * (k + 4) + o));
    }
}
template <bool INV, class S1>
DEVI void fft_cross(uint32_t buf, uint32_t q, uint32_t fa, uint32_t so, uint32_t nq, float (&n)[4], S1 sh1) {
    uint32_t F[4][4];
#pragma unroll
    for (int s = 0; s < 4; s++) { const uint4 v = lds128(fa + s * 2048); F[s][0] = v.x; F[s][1] = v.y; F[s][2] = v.z; F[s][3] = v.w; }
    float d[64];
    const uint64_t db = mkdesc(buf + q * 2048, 1024, 8192), dn = mkdesc(nq, 16, 1024);
    wg_fence();
#pragma unroll
    for (int s = 0; s < 4; s++) { if (s == 0) wg_rs128t<0>(d, F[s], db); else wg_rs128t<1>(d, F[s], db + s * 1024); }
#pragma unroll
    for (int s = 0; s < 4; s++) { if (s == 0) wg_rs8<0>(n, F[s], dn); else wg_rs8<1>(n, F[s], dn + s * 2); }
    wg_commit();
    SF();
    sh1();
    wg_wait<0>();
#pragma unroll
    for (int b = 0; b < 8; b++) {
        const uint32_t o = INV ? so ^ ((b >> 1) * 288 ^ (b & 1) * 32) : (so ^ ((b & 3) * 32)) + (b >> 2) * 1024;
        stsm4(buf + o, pack2(d[8 * b], d[8 * b + 1]), pack2(d[8 * b + 2], d[8 * b + 3]), pack2(d[8 * b + 4], d[8 * b + 5]), pack2(d[8 * b + 6], d[8 * b + 7]));
    }
}

template <bool ODD>
DEVI void fft_filter(uint32_t aw, const float (&e)[32], const float (&o)[32], uint32_t (&u)[4][4], uint32_t (&v)[4][4]) {
#pragma unroll
    for (int s = 0; s < 4; s++) {
        float y[2][2][4];
#pragma unroll
        for (int c = 0; c < 2; c++) {
            float f[4][2];
#pragma unroll
            for (int i = 0; i < 4; i++) {
                const uint32_t a = aw + (i * 32 + s * 8 + c) * 144, x = lds32(a);
                f[i][0] = ODD ? hi_f(x) : lo_f(x);
                f[i][1] = ODD ? lo_f(lds32(a + 4)) : hi_f(x);
            }
#pragma unroll
            for (int h = 0; h < 2; h++) {
                const int x = 8 * s + 2 * h + c;
                const float ar = e[x] + o[x], ai = e[x + 4] + o[x + 4], br = e[x] - o[x], bi = e[x + 4] - o[x + 4];
                const float yr = fmaf(-ai, f[2][h], ar * f[0][h]), yi = fmaf(ar, f[2][h], ai * f[0][h]);
                y[h][c][0] = fmaf(-bi, f[3][h], fmaf(br, f[1][h], yr));
                y[h][c][1] = fmaf(br, f[3][h], fmaf(bi, f[1][h], yi));
                y[h][c][2] = fmaf(2.f, yr, -y[h][c][0]);
                y[h][c][3] = fmaf(2.f, yi, -y[h][c][1]);
            }
        }
#pragma unroll
        for (int h = 0; h < 2; h++) {
            u[s][h] = pack2(y[h][0][0], y[h][1][0]); u[s][h + 2] = pack2(y[h][0][1], y[h][1][1]);
            v[s][h] = pack2(y[h][0][2], y[h][1][2]); v[s][h + 2] = pack2(y[h][0][3], y[h][1][3]);
        }
    }
}

__global__ void __launch_bounds__(F_THREADS, 1)
post_kernel(const __grid_constant__ CUtensorMap tmx, const __grid_constant__ CUtensorMap tmg1, const __grid_constant__ CUtensorMap tmg2,
           const __grid_constant__ CUtensorMap tmwr, const __grid_constant__ CUtensorMap tmwi, const __grid_constant__ CUtensorMap tmy,
           const bf16* __restrict__ wr, const bf16* __restrict__ wi, uint32_t* cnt, uint32_t zero, int nw) {
    extern __shared__ __align__(1024) uint8_t smem[];
    const uint32_t sb = SB0;
    if (smem_u32(smem) != sb) die(1 << 23);
    const uint32_t tid = threadIdx.x, lane = tid & 31, g = lane >> 2, t = lane & 3, j8 = lane & 7, mat = lane >> 3;
    const uint32_t wi_ = __reduce_max_sync(0xFFFFFFFFu, tid >> 5), q = wi_ >> 2, w = wi_ & 3;
    const int cta = blockIdx.x;
    const int nt = cta < 64 ? (64 - cta + nw - 1) / nw : 0;
    const uint32_t bar = sb + FS_BAR;
    if (tid == 0) {
        for (int i = 0; i < 30; i++) mbar_init(bar + i * 8, i < 3 ? 4 : i < 6 ? 16 : i >= 14 && i < 18 ? 2 : 1);
        asm volatile("fence.mbarrier_init.release.cluster;" ::: "memory");
        fence_smem();
    }
    __syncthreads();
#define FT(n)
    FT(0);
#define N2(p) (2 * ((p) & 31) + ((p) >> 5))
#define WLOAD(tk, part) { \
        const uint32_t wd_ = sb + 131072 + q * 18432 + (part) * 9216, wb_ = bar + 112 + q * 8; \
        mbar_expect(wb_, 9216); \
        if ((tk) < 256) tma3d(wd_, (part) ? &tmwi : &tmwr, wb_, ((tk) & 63) * 64, (tk) >> 6, 0); \
        else asm volatile("cp.async.bulk.shared::cluster.global.mbarrier::complete_tx::bytes [%0], [%1], 9216, [%2];" \
                          ::"r"(wd_), "l"(g_WN + (part) * 576), "r"(wb_) : "memory"); }
#define GROW(tk) ((tk) < 256 ? ((tk) >> 5) * 64 + ((tk) & 7) * 8 + (((tk) >> 3) & 3) * 2 : 512)
#define DLOAD(tk, sl) { mbar_expect(bar + 48 + (sl) * 8, 16384); tma3d(sb + (sl) * 16384, &tmg2, bar + 48 + (sl) * 8, 0, GROW(tk), 0); }
#define IO(c) if (w == 3 && (c) && elect())
#define XLOAD1(i, bb) { const uint32_t xb_ = bar + 144 + (bb) * 32 + q * 8; mbar_expect(xb_, 16384); tma4d(sb + (bb) * 65536 + q * 16384, &tmx, xb_, 0, 0, q * 8, N2(cta + (i) * nw)); }
#define GLOAD3(i, bb) { mbar_expect(bar + (bb) * 8, q ? 16384 : 16512); tma3d(sb + (bb) * 65536 + q * 16384, &tmg1, bar + (bb) * 8, 0, q * 128, cta + (i) * nw); \
        if (q == 0) asm volatile("cp.async.bulk.shared::cluster.global.mbarrier::complete_tx::bytes [%0], [%1], 128, [%2];" \
                                 ::"r"(sb + FS_NQ + (bb) * 1024), "l"(g_GN + (cta + (i) * nw) * 8), "r"(bar + (bb) * 8) : "memory"); }
    for (int i = 0; i < 3; i++) IO(i < nt) XLOAD1(i, i);
    for (uint32_t x = tid; x < 40 * 32; x += 512) {
        const uint32_t n = x >> 5, m2 = mat * 8 + t * 2, ri = g & 1;
        const uint32_t c2 = ((n >> 1) & 1) + ((n >> 3) & 1) * 2 + (n & 4) + (n >> 4) * 8;
        const uint32_t v = cos2(m2 * c2 * 64 + ((n & 1) - ri) * 512, (m2 + 1) * c2 * 64 + ((n & 1) - ri) * 512);
        sts32(sb + FS_F2 + n * 128 + ((g ^ (n & 7)) << 4) + t * 4, n < 32 ? v : n == 32 && ri == 0 ? 0xBF003F00u : 0u);
    }
    float tc[8], ts[8];
    uint32_t F[2][4];
    uint32_t c1 = 16 * (w >> 1) + 2 * g + (w & 1);
#pragma unroll
    for (int i = 0; i < 8; i++) {
        twid(c1 * (8 * (i >> 1) + 2 * t + (i & 1)), tc[i], ts[i]);
        const uint32_t m1 = (i >> 1) * 8 + 2 * t;
        F[i >> 2][i & 3] = cos2(c1 * m1 * 64 + (i & 1) * 512, c1 * (m1 + 1) * 64 + (i & 1) * 512);
    }
    {
        const uint32_t kr = (2 * (mat & 1) + (j8 & 1)) ^ ((j8 >> 2) << 1);
        const uint32_t so1 = ((mat >> 1) + 2 * (j8 >> 2)) * 1024 + kr * 128 + (((((j8 >> 1) & 1) * 4 + w) ^ kr) << 4);
        const uint32_t so2 = (2 * w + (mat & 1)) * 8192 + q * 2048 + j8 * 128 + (((mat >> 1) ^ j8) << 4);
        uint32_t so = so1 << 16 | so2;
        const float fx = (tid & 127) == 0 ? 0.5f : 1.f;
        fft_gen<false>(sb + FS_TB, N2(cta));
        fence_smem();
        bsync<1, 512>();
        FT(1);
        int b = 0, bp = 2, ph = 0;
        if (nt) mwait(bar + 144 + q * 8, 0);
        __syncwarp();
        auto step = [&](auto first, auto last, const int i) {
            const uint32_t p = cta + i * nw, bn = 3 - b - bp, tb = (i & 1) * 8192;
            const uint32_t grp = sb + b * 65536 + q * 16384, nq = sb + FS_NQ + b * 1024 + q * 32;
            auto sa = [&]() {
                if constexpr (!decltype(first)::v) {
                    fence_smem();
                    __syncwarp();
                    if (elect()) mbar_arrive(bar + 24);
                }
                IO(i > 1) {
                    mwait(bar + 32, i & 1);
                    tma3s(&tmg1, sb + bn * 65536 + q * 16384, 0, q * 128, p - 2 * nw);
                    bulk_commit();
                }
            };
            auto sb_ = [&]() { if constexpr (!decltype(first)::v) mwait(bar + 24, (i - 1) & 1); };
            if constexpr (!decltype(last)::v) fft_rows<false>(grp, q, F, tc, ts, opq(so, zero) >> 16, fx, nq, sa, sb_);
            else { sa(); __syncwarp(); sb_(); __syncwarp(); }
            if constexpr (!decltype(first)::v) {
                float n[4];
                fft_cross<false>(sb + bp * 65536, q, sb + FS_TB + 8192 - tb + (((tidx() & 127) ^ (q & 1)) << 4), opq(so, zero) & 0xFFFF, sb + FS_NQ + bp * 1024, n, [&]() {
                    fft_gen<false>(sb + FS_TB + tb, N2(p));
                    IO(i >= 2 && i + 1 < nt) {
                        asm volatile("cp.async.bulk.wait_group.read 0;" ::: "memory");
                        XLOAD1(i + 1, bn);
                    }
                });
                if (q == 0) {
                    const uint32_t x = tidx();
                    bf16* z = (bf16*)(g_G + ((p - nw) * G_ROWS + 512) * 8) + (x & 4) * 16 + ((x >> 2) & 24) + ((x >> 3) & 3);
                    asm volatile("{\n.reg .pred p;\n.reg .b16 a, b;\nsetp.eq.u32 p, %2, 0;\nmov.b32 {a, b}, %1;\n@p st.global.u16 [%0], a;\n@p st.global.u16 [%0+8], b;\n}"
                                 ::"l"(z), "r"(pack2(n[0], n[2])), "r"(x & 3) : "memory");
                }
            }
            if constexpr (!decltype(last)::v) {
                fft_rows<false>(grp + 8192, q, F, tc, ts, opq(so, zero) >> 16, fx, nq + 16, [&]() {
                    if constexpr (!decltype(first)::v) {
                        fence_smem();
                        __syncwarp();
                        if (elect()) mbar_arrive(bar + 32);
                    }
                    if ((w == 1 || w == 2) && elect())
                        asm volatile("cp.async.bulk.prefetch.L2.global [%0], 8208;" ::"l"((w == 1 ? wr : wi) + (p * 4 + q) * 4104) : "memory");
                }, [&]() { if (i + 1 < nt) mwait(bar + 144 + bn * 32 + q * 8, bn ? ph : ph ^ 1); });
                bp = b;
                if (++b == 3) { b = 0; ph ^= 1; }
            }
        };
        if (nt) {
            step(Bool<true>(), Bool<false>(), 0);
#pragma unroll 1
            for (int i = 1; i < nt; i++) step(Bool<false>(), Bool<false>(), i);
            step(Bool<false>(), Bool<true>(), nt);
        }
        for (uint32_t x = cta * 512 + tid; x < 4096; x += nw * 512)
            ((bf16*)g_WN)[(x >> 5) * 72 + (x & 16) + (x & 7) * 2 + ((x >> 3) & 1)] = (x < 2048 ? wr : wi)[(x & 2047) * 513 + 512];
        FT(2);
        fence_async();
        bsync<1, 512>();
        IO(nt) { tma3s(&tmg1, sb + bp * 65536 + q * 16384, 0, q * 128, cta + (nt - 1) * nw); bulk_commit(); }
    }
    for (uint32_t x = tid; x < 128 * 32; x += 512) {
        const uint32_t n = (x >> 5) & 63, a = x & 31, k2 = (n >> 4) * 8 + (n & 7);
        sts32(sb + FS_TB + (x >> 5) * 128 + (((a >> 2) ^ (n & 7)) << 4) + (a & 3) * 4, cis((2 * a + (x >> 11)) * k2 * 32 + (n & 8) * 64));
    }
    fence_smem();
    bsync<1, 512>();
    IO(true) {
        asm volatile("cp.async.bulk.wait_group 0;" ::: "memory");
        grid_arrive(cnt, 4 * nw);
        grid_wait(cnt);
        const int tk = cta + q * nw;
        if (tk <= 256) { DLOAD(tk, q); WLOAD(tk, 0); WLOAD(tk, 1); }
    }
    __syncwarp();
    {
        const uint32_t lo = j8 * 128 + (((2 * w + (mat & 1)) ^ j8) << 4);
        const uint32_t aw = sb + 131072 + q * 18432 + t * 288 + w * 32 + g * 4;
        const uint64_t df = mkdesc(sb + FS_TB, 16, 1024);
        const uint64_t da = mkdesc(sb + q * 16384, 16, 1024);
        const uint32_t buf = sb + 65536 + q * 16384;
        int i = 0, tk = cta + q * nw;
        if (tk <= 256) mwait(bar + 48 + q * 8, 0);
        FT(3);
#pragma unroll 1
        for (; tk <= 256; tk += 4 * nw, i++) {
            const bool more = tk + 4 * nw <= 256;
            float e[32], o[32];
            wg_fence();
#pragma unroll
            for (int s = 0; s < 4; s++) { if (s == 0) wg_ss64a<0>(e, da, df); else wg_ss64a<1>(e, da + s * 128, df + s * 2); }
#pragma unroll
            for (int s = 0; s < 4; s++) { if (s == 0) wg_ss64a<0>(o, da + 512, df + 512); else wg_ss64a<1>(o, da + 512 + s * 128, df + 512 + s * 2); }
            wg_commit();
            SF();
            if (i > 0) {
                fence_smem();
                wgbar(q);
                IO(true) { tma3s(&tmg2, buf, 0, GROW(tk - 4 * nw), 0); bulk_commit(); }
            }
            if (w == 2 && more && elect()) mbar_expect(bar + 48 + q * 8, 16384);
            const int gr = GROW(tk + 4 * nw);
            mwait(bar + 112 + q * 8, i & 1);
            wg_wait<0>();
            if (w == 2 && more && elect()) tma3d(sb + q * 16384, &tmg2, bar + 48 + q * 8, 0, gr, 0);
            uint32_t u[4][4], v[4][4];
            if (tk & 8) fft_filter<true>(aw + (tk & 48) / 4, e, o, u, v);
            else fft_filter<false>(aw + (tk & 48) / 4, e, o, u, v);
            wg_fence();
#pragma unroll
            for (int s = 0; s < 4; s++) { if (s == 0) wg_rs64t<0>(e, u[s], df); else wg_rs64t<1>(e, u[s], df + s * 128); }
#pragma unroll
            for (int s = 0; s < 4; s++) { if (s == 0) wg_rs64t<0>(o, v[s], df + 512); else wg_rs64t<1>(o, v[s], df + 512 + s * 128); }
            wg_commit();
            SF();
            IO(true) asm volatile("cp.async.bulk.wait_group.read 0;" ::: "memory");
            wgbar(q);
            if (more) {
                if ((w == 1 || w == 2) && elect()) WLOAD(tk + 4 * nw, w - 1);
                mwait(bar + 48 + q * 8, (i + 1) & 1);
            }
            wg_wait<0>();
#pragma unroll
            for (int s = 0; s < 4; s++) {
                const uint32_t a = buf + (mat >> 1) * 1024 + lo + s * 2048;
                stsm4t(a, pack2(e[8 * s], e[8 * s + 1]), pack2(e[8 * s + 2], e[8 * s + 3]), pack2(e[8 * s + 4], e[8 * s + 5]), pack2(e[8 * s + 6], e[8 * s + 7]));
                stsm4t(a + 8192, pack2(o[8 * s], o[8 * s + 1]), pack2(o[8 * s + 2], o[8 * s + 3]), pack2(o[8 * s + 4], o[8 * s + 5]), pack2(o[8 * s + 6], o[8 * s + 7]));
            }
            if (tk == 256 && w < 2) {
                uint32_t* z = (uint32_t*)g_GN + t * 32 + w * 16 + g;
#pragma unroll
                for (int s = 0; s < 16; s++) {
                    z[(s >> 1) * 128 + (s & 1) * 8] = pack2(e[2 * s], e[2 * s + 1]);
                    z[(s >> 1) * 128 + (s & 1) * 8 + 1024] = pack2(o[2 * s], o[2 * s + 1]);
                }
                fence_async();
            }
        }
        fence_smem();
        wgbar(q);
        IO(true) {
            if (i > 0) { tma3s(&tmg2, buf, 0, GROW(tk - 4 * nw), 0); bulk_commit(); }
            asm volatile("cp.async.bulk.wait_group 0;" ::: "memory");
            grid_arrive(cnt + 1, 4 * nw);
        }
    }
    FT(4);
    bsync<1, 512>();
    {
        for (uint32_t n = wi_; n < 32; n += 16) {
            const uint32_t cl = (mat >> 1) * 16 + t * 4 + (mat & 1), mh = ((n >> 3) & 1) + (n & 7) * 2 + (n & 16);
            sts32(sb + FS_F2 + n * 128 + ((g ^ (n & 7)) << 4) + t * 4, cos2(cl * mh * 64 + (g & 1) * 512, (cl + 2) * mh * 64 + (g & 1) * 512));
        }
        fence_smem();
        c1 = 8 * w + g;
#pragma unroll
        for (int i = 0; i < 8; i++) {
            twid(-c1 * (16 * (i >> 2) + 4 * t + 2 * (i & 1) + ((i >> 1) & 1)), tc[i], ts[i]);
            F[i >> 2][i & 3] = cis((i & 1) * 512 - c1 * ((i >> 1) * 4 + (t ^ (q & 1))) * 64);
        }
        const uint32_t kr = (j8 & 1) ^ ((j8 >> 2) << 1);
        const uint32_t so2 = ((w >> 1) * 4 + (j8 >> 2) * 2 + (w & 1)) * 8192 + (2 * q + (mat & 1)) * 1024 + kr * 128 + (((((j8 >> 1) & 1) * 4 + (mat >> 1)) ^ kr) << 4);
        const uint32_t so1 = (mat & 1) * 2048 + j8 * 128 + ((((mat >> 1) * 4 + w) ^ j8) << 4);
        uint32_t so = so1 << 16 | so2;
        const float fx = t ? 0.f : (g & 1) ? -1.f : 1.f;
        fft_gen<true>(sb + FS_TB, N2(cta));
        bsync<1, 512>();
        IO(true) grid_wait(cnt + 1);
        for (int i = 0; i < 3; i++) IO(i < nt) GLOAD3(i, i);
        __syncwarp();
        int b = 0, bp = 2, ph = 0;
        auto step = [&](auto first, auto last, const int i) {
            const uint32_t p = cta + i * nw, bn = 3 - b - bp, tb = (i & 1) * 8192;
            const uint32_t grp = sb + bp * 65536 + q * 16384, ny = sb + FS_NY + bp * 128 + q * 32;
            auto sb_ = [&]() { if constexpr (!decltype(last)::v) mwait(bar + b * 8, ph); };
            if constexpr (!decltype(first)::v) {
                fft_rows<true>(grp, q, F, tc, ts, opq(so, zero) >> 16, fx, ny, [&]() {
                    if (i > 1) {
                        fence_smem();
                        wgbar(q);
                        IO(true) { tma4s(&tmy, sb + bn * 65536 + q * 16384, 0, 0, q * 8, N2(p - 2 * nw)); bulk_commit(); }
                    }
                }, sb_);
            } else { sb_(); __syncwarp(); }
            if constexpr (decltype(first)::v) FT(5);
            if constexpr (!decltype(last)::v) {
                float n[4];
                fft_cross<true>(sb + b * 65536, q, sb + FS_TB + tb + (tidx() & 127) * 16, opq(so, zero) & 0xFFFF, sb + FS_NQ + b * 1024, n, [&]() {
                    fft_gen<true>(sb + FS_TB + 8192 - tb, N2(p + nw));
                    IO(i >= 2 && i + 1 < nt) {
                        asm volatile("cp.async.bulk.wait_group.read 0;" ::: "memory");
                        GLOAD3(i + 1, bn);
                    }
                });
                if (q == 0) {
                    const uint32_t x = tidx(), a = sb + FS_NY + b * 128 + (x & 64) + (x & 16) * 2 + ((x & 40) >> 1);
                    if ((x & 7) == 0) { sts32f(a, n[0]); sts32f(a + 8, n[2]); }
                }
            }
            auto sc = [&]() {
                if constexpr (!decltype(last)::v) {
                    fence_smem();
                    __syncwarp();
                    if (elect()) mbar_arrive(bar + 24);
                }
            };
            auto sd = [&]() { if constexpr (!decltype(last)::v) mwait(bar + 24, (nt + i) & 1); };
            if constexpr (!decltype(first)::v) fft_rows<true>(grp + 8192, q, F, tc, ts, opq(so, zero) >> 16, fx, ny + 16, sc, sd);
            else { sc(); __syncwarp(); sd(); __syncwarp(); }
            if constexpr (!decltype(last)::v) {
                bp = b;
                if (++b == 3) { b = 0; ph ^= 1; }
            }
        };
        if (nt) {
            step(Bool<true>(), Bool<false>(), 0);
#pragma unroll 1
            for (int i = 1; i < nt; i++) step(Bool<false>(), Bool<false>(), i);
            step(Bool<false>(), Bool<true>(), nt);
        }
        fence_smem();
        wgbar(q);
        IO(nt) { tma4s(&tmy, sb + bp * 65536 + q * 16384, 0, 0, q * 8, N2(cta + (nt - 1) * nw)); bulk_commit(); }
        FT(6);
        IO(true) asm volatile("cp.async.bulk.wait_group 0;" ::: "memory");
    }
}

typedef CUresult (*EncodeFn)(CUtensorMap*, CUtensorMapDataType, cuuint32_t, void*, const cuuint64_t*, const cuuint64_t*,
                             const cuuint32_t*, const cuuint32_t*, CUtensorMapInterleave, CUtensorMapSwizzle,
                             CUtensorMapL2promotion, CUtensorMapFloatOOBfill);

static void make_map(EncodeFn enc, CUtensorMap* m, const void* ptr, int rank, const cuuint64_t* dims, const cuuint64_t* strides,
                     const cuuint32_t* box, CUtensorMapSwizzle sw = CU_TENSOR_MAP_SWIZZLE_128B) {
    cuuint32_t es[4] = {1, 1, 1, 1};
    CUresult r = enc(m, CU_TENSOR_MAP_DATA_TYPE_BFLOAT16, rank, (void*)ptr, dims, strides, box, es, CU_TENSOR_MAP_INTERLEAVE_NONE,
                     sw, CU_TENSOR_MAP_L2_PROMOTION_L2_256B, CU_TENSOR_MAP_FLOAT_OOB_FILL_NONE);
    if (r != CUDA_SUCCESS) fprintf(stderr, "tensor map encode failed: %d\n", (int)r);
}

extern "C" void kernel_launch(void* const* d_in, const int* in_sizes, int n_in, void* d_out, int out_size) {
    const bf16* A_x = (const bf16*)d_in[0];
    const bf16* A_mem0 = (const bf16*)d_in[1];
    const bf16* A_Wq = (const bf16*)d_in[2];
    const bf16* A_Wk = (const bf16*)d_in[3];
    const bf16* A_Wv = (const bf16*)d_in[4];
    const bf16* A_Wo = (const bf16*)d_in[5];
    const bf16* B_x = (const bf16*)d_in[7];
    const bf16* B_wr = (const bf16*)d_in[8];
    const bf16* B_wi = (const bf16*)d_in[9];
    bf16* out = (bf16*)d_out;

    static EncodeFn enc = nullptr;
    static void *pxs = nullptr, *pg = nullptr;
    static int ncl = 64;
    if (!enc) {
        cudaDriverEntryPointQueryResult qr;
        void* fn = nullptr;
        cudaGetDriverEntryPoint("cuTensorMapEncodeTiled", &fn, cudaEnableDefault, &qr);
        enc = (EncodeFn)fn;
        cudaFuncSetAttribute(chain_kernel, cudaFuncAttributeMaxDynamicSharedMemorySize, SM_TOTAL);
        cudaFuncSetAttribute(post_kernel, cudaFuncAttributeMaxDynamicSharedMemorySize, FS_TOTAL);
        cudaGetSymbolAddress(&pxs, g_xs);
        cudaGetSymbolAddress(&pg, g_G);
        cudaLaunchConfig_t lc = {};
        cudaLaunchAttribute at;
        at.id = cudaLaunchAttributeClusterDimension;
        at.val.clusterDim.x = 2; at.val.clusterDim.y = 1; at.val.clusterDim.z = 1;
        lc.gridDim = dim3(132); lc.blockDim = dim3(384); lc.dynamicSmemBytes = SM_TOTAL; lc.attrs = &at; lc.numAttrs = 1;
        int nc = 0;
        if (cudaOccupancyMaxActiveClusters(&nc, chain_kernel, &lc) == cudaSuccess && nc > 64) ncl = nc < 66 ? nc : 66;
    }
    CUtensorMap tmq, tmk, tmv, tmo, tmx, tmb, tmy;
    {
        cuuint64_t d[3] = {64, DM, HD / 64}, st[2] = {HD * 2, 128};
        cuuint32_t bx[3] = {64, 64, 2};
        make_map(enc, &tmq, A_Wq, 3, d, st, bx);
        make_map(enc, &tmk, A_Wk, 3, d, st, bx);
        make_map(enc, &tmv, A_Wv, 3, d, st, bx);
    }
    {
        cuuint64_t d[2] = {DM, HD}, st[1] = {DM * 2};
        cuuint32_t bx[2] = {64, 16}, bx1[2] = {64, 128}, bx2[3] = {64, 64, 2};
        make_map(enc, &tmo, A_Wo, 2, d, st, bx1);
        cuuint64_t d2[3] = {64, HD, DM / 64}, st2[2] = {DM * 2, 128}, d3[2] = {DM, SEQ}, st3[1] = {DM * 4};
        make_map(enc, &tmb, A_Wo, 3, d2, st2, bx2);
        make_map(enc, &tmy, out, 2, d3, st3, bx);
    }
    {
        cuuint64_t d[3] = {64, SEQ, DM / 64}, st[2] = {DM * 2, 128};
        cuuint32_t bx[3] = {64, 8, 4};
        make_map(enc, &tmx, A_x, 3, d, st, bx);
    }
    CUtensorMap fx, fg1, fg2, fwr, fwi, fy;
    {
        cuuint64_t d[4] = {32, 32, 32, 64}, st[3] = {64, 64 * DM * 2, DM * 2};
        cuuint32_t bx[4] = {32, 32, 8, 1};
        make_map(enc, &fx, B_x, 4, d, st, bx, CU_TENSOR_MAP_SWIZZLE_64B);
        cuuint64_t d2[4] = {64, 16, 32, 64}, st2[3] = {128, 64 * 4096, 4096};
        cuuint32_t bx2[4] = {64, 16, 8, 1};
        make_map(enc, &fy, out + DM, 4, d2, st2, bx2);
    }
    {
        cuuint64_t d[3] = {64, G_ROWS, 64}, st[2] = {128, G_ROWS * 128};
        cuuint32_t bx[3] = {64, 128, 1}, bx2[3] = {64, 2, 64};
        make_map(enc, &fg1, pg, 3, d, st, bx);
        make_map(enc, &fg2, pg, 3, d, st, bx2);
        cuuint64_t d2[3] = {8 * 513, 4, 64}, st2[2] = {8 * 513 * 2, 32 * 513 * 2};
        cuuint32_t bx3[3] = {72, 1, 64};
        make_map(enc, &fwr, B_wr, 3, d2, st2, bx3, CU_TENSOR_MAP_SWIZZLE_NONE);
        make_map(enc, &fwi, B_wi, 3, d2, st2, bx3, CU_TENSOR_MAP_SWIZZLE_NONE);
    }
    cudaStream_t st = cudaStreamPerThread;
    const uint64_t xs = ((uint64_t)pxs + XS_BYTES - 1) & ~(uint64_t)(XS_BYTES - 1);
    chain_kernel<<<2 * ncl, 384, SM_TOTAL, st>>>(tmq, tmk, tmv, tmo, tmx, tmb, tmy, A_mem0, A_x, (uint32_t)xs, (uint32_t)(xs >> 32), 0u, NSEG, out);
    int nw = ncl == 66 ? 4 : 64;
    cudaLaunchConfig_t lc = {};
    cudaLaunchAttribute at;
    at.id = cudaLaunchAttributeProgrammaticStreamSerialization;
    at.val.programmaticStreamSerializationAllowed = 1;
    lc.gridDim = dim3(nw); lc.blockDim = dim3(F_THREADS); lc.dynamicSmemBytes = FS_TOTAL; lc.stream = st; lc.attrs = &at; lc.numAttrs = 1;
    cudaLaunchKernelEx(&lc, post_kernel, fx, fg1, fg2, fwr, fwi, fy, B_wr, B_wi, (uint32_t*)(xs + XO_TK + 256), 0u, nw);
}
```

```cpp
#include <cuda_runtime.h>
#include <cuda_bf16.h>
#include <cuda.h>
#include <stdint.h>
#include <stdio.h>

typedef __nv_bfloat16 bf16;

#define SEQ 2048
#define DM 1024
#define NH 32
#define DH 128
#define NSEG 64
#define HD (NH * DH)

#define XS_BYTES (32u << 20)
__device__ uint4 g_xs[2 * XS_BYTES / 16];
#define XO_R 0u
#define XO_PB (1u << 18)
#define XO_FL (XO_PB + 32768u)
#define XO_TK (XO_FL + 4096u)
#define XO_CQK (1u << 20)
#define XO_CV (2u << 20)
#define XO_XG (4u << 20)
#define XO_OX (16u << 20)
#define GSYNC(n)
#define PG(n)

#define DEVI __device__ __forceinline__

DEVI void die(int it) { asm volatile("st.shared.u32 [%0], %0;" ::"r"(it) : "memory"); }
DEVI uint32_t smem_u32(const void* p) { return (uint32_t)__cvta_generic_to_shared(p); }
DEVI void mbar_init(uint32_t bar, uint32_t cnt) { asm volatile("mbarrier.init.shared::cta.b64 [%0], %1;" ::"r"(bar), "r"(cnt) : "memory"); }
DEVI void mbar_expect(uint32_t bar, uint32_t bytes) { asm volatile("mbarrier.arrive.expect_tx.shared::cta.b64 _, [%0], %1;" ::"r"(bar), "r"(bytes) : "memory"); }
DEVI void mbar_arrive(uint32_t bar) { asm volatile("mbarrier.arrive.shared::cta.b64 _, [%0];" ::"r"(bar) : "memory"); }
DEVI void mbar_wait(uint32_t bar, uint32_t parity) {
    uint32_t done;
    int it = 0;
    do {
        asm volatile("{\n.reg .pred p;\nmbarrier.try_wait.parity.shared::cta.b64 p, [%1], %2;\nselp.u32 %0, 1, 0, p;\n}\n"
                     : "=r"(done) : "r"(bar), "r"(parity) : "memory");
        if (++it > (1 << 22)) die(it);
    } while (!done);
}
DEVI void tma2d(uint32_t dst, const CUtensorMap* tm, uint32_t bar, int c0, int c1) {
    asm volatile("cp.async.bulk.tensor.2d.shared::cluster.global.mbarrier::complete_tx::bytes [%0], [%1, {%3, %4}], [%2];"
                 ::"r"(dst), "l"(tm), "r"(bar), "r"(c0), "r"(c1) : "memory");
}
DEVI void tma3d(uint32_t dst, const CUtensorMap* tm, uint32_t bar, int c0, int c1, int c2) {
    asm volatile("cp.async.bulk.tensor.3d.shared::cluster.global.mbarrier::complete_tx::bytes [%0], [%1, {%3, %4, %5}], [%2];"
                 ::"r"(dst), "l"(tm), "r"(bar), "r"(c0), "r"(c1), "r"(c2) : "memory");
}
DEVI void bulk_g2s(uint32_t dst, uint32_t lo, uint32_t hi, uint32_t bytes, uint32_t bar) {
    asm volatile("{\n.reg .b64 a;\nmov.b64 a, {%1,%2};\ncp.async.bulk.shared::cluster.global.mbarrier::complete_tx::bytes [%0], [a], %3, [%4];\n}"
                 ::"r"(dst), "r"(lo), "r"(hi), "r"(bytes), "r"(bar) : "memory");
}
DEVI void bulk_s2g(uint32_t lo, uint32_t hi, uint32_t src, uint32_t bytes) {
    asm volatile("{\n.reg .b64 a;\nmov.b64 a, {%0,%1};\ncp.async.bulk.global.shared::cta.bulk_group [a], [%2], %3;\ncp.async.bulk.commit_group;\n}"
                 ::"r"(lo), "r"(hi), "r"(src), "r"(bytes) : "memory");
}
DEVI void bulk_red(uint32_t lo, uint32_t hi, uint32_t src, uint32_t bytes) {
    asm volatile("{\n.reg .b64 a;\nmov.b64 a, {%0,%1};\ncp.reduce.async.bulk.global.shared::cta.bulk_group.add.noftz.bf16 [a], [%2], %3;\ncp.async.bulk.commit_group;\n}"
                 ::"r"(lo), "r"(hi), "r"(src), "r"(bytes) : "memory");
}
DEVI bool elect() {
    uint32_t p;
    asm volatile("{\n.reg .pred P;\nelect.sync _|P, 0xFFFFFFFF;\nselp.u32 %0, 1, 0, P;\n}" : "=r"(p));
    return p != 0;
}
DEVI void ldsm4(uint32_t (&r)[4], uint32_t a) {
    asm volatile("ldmatrix.sync.aligned.m8n8.x4.shared.b16 {%0,%1,%2,%3}, [%4];" : "=r"(r[0]), "=r"(r[1]), "=r"(r[2]), "=r"(r[3]) : "r"(a) : "memory");
}
DEVI void ldsm4t(uint32_t (&r)[4], uint32_t a) {
    asm volatile("ldmatrix.sync.aligned.m8n8.x4.trans.shared.b16 {%0,%1,%2,%3}, [%4];" : "=r"(r[0]), "=r"(r[1]), "=r"(r[2]), "=r"(r[3]) : "r"(a) : "memory");
}
DEVI void ldsm2t(uint32_t (&r)[2], uint32_t a) {
    asm volatile("ldmatrix.sync.aligned.m8n8.x2.trans.shared.b16 {%0,%1}, [%2];" : "=r"(r[0]), "=r"(r[1]) : "r"(a) : "memory");
}
DEVI void ldsm2(uint32_t (&r)[2], uint32_t a) {
    asm volatile("ldmatrix.sync.aligned.m8n8.x2.shared.b16 {%0,%1}, [%2];" : "=r"(r[0]), "=r"(r[1]) : "r"(a) : "memory");
}
DEVI void stsm4t(uint32_t a, uint32_t r0, uint32_t r1, uint32_t r2, uint32_t r3) {
    asm volatile("stmatrix.sync.aligned.m8n8.x4.trans.shared.b16 [%0], {%1,%2,%3,%4};" ::"r"(a), "r"(r0), "r"(r1), "r"(r2), "r"(r3) : "memory");
}
DEVI uint32_t ldsm1(uint32_t a) {
    uint32_t r;
    asm volatile("ldmatrix.sync.aligned.m8n8.x1.shared.b16 {%0}, [%1];" : "=r"(r) : "r"(a) : "memory");
    return r;
}
DEVI void stsm4(uint32_t a, uint32_t r0, uint32_t r1, uint32_t r2, uint32_t r3) {
    asm volatile("stmatrix.sync.aligned.m8n8.x4.shared.b16 [%0], {%1,%2,%3,%4};" ::"r"(a), "r"(r0), "r"(r1), "r"(r2), "r"(r3) : "memory");
}
DEVI void stsm2(uint32_t a, uint32_t r0, uint32_t r1) {
    asm volatile("stmatrix.sync.aligned.m8n8.x2.shared.b16 [%0], {%1,%2};" ::"r"(a), "r"(r0), "r"(r1) : "memory");
}
DEVI uint32_t movm(uint32_t a) {
    uint32_t d;
    asm volatile("movmatrix.sync.aligned.m8n8.trans.b16 %0, %1;" : "=r"(d) : "r"(a));
    return d;
}
DEVI void mma16(float (&d)[4], uint32_t a0, uint32_t a1, uint32_t a2, uint32_t a3, uint32_t b0, uint32_t b1) {
    asm volatile("mma.sync.aligned.m16n8k16.row.col.f32.bf16.bf16.f32 {%0,%1,%2,%3}, {%4,%5,%6,%7}, {%8,%9}, {%0,%1,%2,%3};"
                 : "+f"(d[0]), "+f"(d[1]), "+f"(d[2]), "+f"(d[3]) : "r"(a0), "r"(a1), "r"(a2), "r"(a3), "r"(b0), "r"(b1));
}
DEVI void mma16z(float (&d)[4], uint32_t a0, uint32_t a1, uint32_t a2, uint32_t a3, uint32_t b0, uint32_t b1) {
    asm volatile("mma.sync.aligned.m16n8k16.row.col.f32.bf16.bf16.f32 {%0,%1,%2,%3}, {%4,%5,%6,%7}, {%8,%9}, {%10,%10,%10,%10};"
                 : "=f"(d[0]), "=f"(d[1]), "=f"(d[2]), "=f"(d[3]) : "r"(a0), "r"(a1), "r"(a2), "r"(a3), "r"(b0), "r"(b1), "f"(0.f));
}
DEVI void mma8(float (&d)[4], uint32_t a0, uint32_t a1, uint32_t b0) {
    asm volatile("mma.sync.aligned.m16n8k8.row.col.f32.bf16.bf16.f32 {%0,%1,%2,%3}, {%4,%5}, {%6}, {%0,%1,%2,%3};"
                 : "+f"(d[0]), "+f"(d[1]), "+f"(d[2]), "+f"(d[3]) : "r"(a0), "r"(a1), "r"(b0));
}
DEVI void mma8z(float (&d)[4], uint32_t a0, uint32_t a1, uint32_t b0) {
    asm volatile("mma.sync.aligned.m16n8k8.row.col.f32.bf16.bf16.f32 {%0,%1,%2,%3}, {%4,%5}, {%6}, {%7,%7,%7,%7};"
                 : "=f"(d[0]), "=f"(d[1]), "=f"(d[2]), "=f"(d[3]) : "r"(a0), "r"(a1), "r"(b0), "f"(0.f));
}
DEVI uint32_t pack2(float lo, float hi) {
    uint32_t r;
    asm("cvt.rn.bf16x2.f32 %0, %1, %2;" : "=r"(r) : "f"(hi), "f"(lo));
    return r;
}
DEVI uint32_t hadd2(uint32_t a, uint32_t b) {
    uint32_t r;
    asm("add.rn.bf16x2 %0, %1, %2;" : "=r"(r) : "r"(a), "r"(b));
    return r;
}
DEVI float lo_f(uint32_t x) { return __uint_as_float(x << 16); }
DEVI float hi_f(uint32_t x) { return __uint_as_float(x & 0xFFFF0000u); }
template <uint32_t OFF> DEVI uint4 ldg4(uint32_t lo, uint32_t hi) {
    uint4 v;
    asm volatile("{\n.reg .b64 a;\nmov.b64 a, {%4,%5};\nld.relaxed.gpu.global.v4.u32 {%0,%1,%2,%3}, [a+%6];\n}"
                 : "=r"(v.x), "=r"(v.y), "=r"(v.z), "=r"(v.w) : "r"(lo), "r"(hi), "n"(OFF) : "memory");
    return v;
}
template <uint32_t OFF> DEVI uint2 ldg2(uint32_t lo, uint32_t hi) {
    uint2 v;
    asm volatile("{\n.reg .b64 a;\nmov.b64 a, {%2,%3};\nld.relaxed.gpu.global.v2.u32 {%0,%1}, [a+%4];\n}"
                 : "=r"(v.x), "=r"(v.y) : "r"(lo), "r"(hi), "n"(OFF) : "memory");
    return v;
}
template <uint32_t OFF> DEVI uint32_t ldg1(uint32_t lo, uint32_t hi) {
    uint32_t v;
    asm volatile("{\n.reg .b64 a;\nmov.b64 a, {%1,%2};\nld.relaxed.gpu.global.u32 %0, [a+%3];\n}" : "=r"(v) : "r"(lo), "r"(hi), "n"(OFF) : "memory");
    return v;
}
template <uint32_t OFF> DEVI void stg1(uint32_t lo, uint32_t hi, uint32_t a) {
    asm volatile("{\n.reg .b64 a;\nmov.b64 a, {%0,%1};\nst.relaxed.gpu.global.u32 [a+%3], %2;\n}" ::"r"(lo), "r"(hi), "r"(a), "n"(OFF) : "memory");
}
template <uint32_t OFF> DEVI void stg4(uint32_t lo, uint32_t hi, uint32_t a, uint32_t b, uint32_t c, uint32_t d) {
    asm volatile("{\n.reg .b64 a;\nmov.b64 a, {%0,%1};\nst.relaxed.gpu.global.v4.u32 [a+%6], {%2,%3,%4,%5};\n}"
                 ::"r"(lo), "r"(hi), "r"(a), "r"(b), "r"(c), "r"(d), "n"(OFF) : "memory");
}
template <uint32_t OFF> DEVI void stg2(uint32_t lo, uint32_t hi, uint32_t a, uint32_t b) {
    asm volatile("{\n.reg .b64 a;\nmov.b64 a, {%0,%1};\nst.relaxed.gpu.global.v2.u32 [a+%4], {%2,%3};\n}"
                 ::"r"(lo), "r"(hi), "r"(a), "r"(b), "n"(OFF) : "memory");
}
DEVI uint32_t tagx2(uint32_t a, uint32_t b, uint32_t t) { uint32_t r; asm("lop3.b32 %0, %1, %2, %3, 0x7E;" : "=r"(r) : "r"(a), "r"(b), "r"(t)); return r; }
DEVI uint32_t tagx1(uint32_t a, uint32_t b, uint32_t t) { uint32_t r; asm("lop3.b32 %0, %1, %2, %3, 0xF6;" : "=r"(r) : "r"(a), "r"(b), "r"(t)); return r; }
DEVI uint32_t or3(uint32_t a, uint32_t b, uint32_t c) { uint32_t r; asm("lop3.b32 %0, %1, %2, %3, 0xFE;" : "=r"(r) : "r"(a), "r"(b), "r"(c)); return r; }
DEVI bool any_bad(uint32_t x) { return __any_sync(0xFFFFFFFFu, (x & 1u) != 0); }
DEVI uint32_t settag(uint32_t x, uint32_t tag) { return (x & ~1u) | tag; }
DEVI void sts32f(uint32_t a, float v) { asm volatile("st.shared.f32 [%0], %1;" ::"r"(a), "f"(v) : "memory"); }
DEVI void sts32(uint32_t a, uint32_t v) { asm volatile("st.shared.u32 [%0], %1;" ::"r"(a), "r"(v) : "memory"); }
DEVI void sts16(uint32_t a, uint32_t v) { asm volatile("st.shared.u16 [%0], %1;" ::"r"(a), "h"((unsigned short)v) : "memory"); }
DEVI void sts64(uint32_t a, uint32_t x, uint32_t y) { asm volatile("st.shared.v2.u32 [%0], {%1,%2};" ::"r"(a), "r"(x), "r"(y) : "memory"); }
DEVI void sts128(uint32_t a, uint32_t x, uint32_t y, uint32_t z, uint32_t w) {
    asm volatile("st.shared.v4.u32 [%0], {%1,%2,%3,%4};" ::"r"(a), "r"(x), "r"(y), "r"(z), "r"(w) : "memory");
}
DEVI float4 lds128f(uint32_t a) {
    float4 v;
    asm volatile("ld.shared.v4.f32 {%0,%1,%2,%3}, [%4];" : "=f"(v.x), "=f"(v.y), "=f"(v.z), "=f"(v.w) : "r"(a) : "memory");
    return v;
}
DEVI uint4 lds128(uint32_t a) {
    uint4 v;
    asm volatile("ld.shared.v4.u32 {%0,%1,%2,%3}, [%4];" : "=r"(v.x), "=r"(v.y), "=r"(v.z), "=r"(v.w) : "r"(a) : "memory");
    return v;
}
DEVI uint2 lds64(uint32_t a) {
    uint2 v;
    asm volatile("ld.shared.v2.u32 {%0,%1}, [%2];" : "=r"(v.x), "=r"(v.y) : "r"(a) : "memory");
    return v;
}
DEVI uint32_t lds32(uint32_t a) {
    uint32_t v;
    asm volatile("ld.shared.u32 %0, [%1];" : "=r"(v) : "r"(a) : "memory");
    return v;
}
DEVI float ex2(float x) { float r; asm("ex2.approx.ftz.f32 %0, %1;" : "=f"(r) : "f"(x)); return r; }
DEVI float rcp(float x) { float r; asm("rcp.approx.ftz.f32 %0, %1;" : "=f"(r) : "f"(x)); return r; }
DEVI uint32_t clk() { uint32_t c; asm volatile("mov.u32 %0, %%clock;" : "=r"(c)::"memory"); return c; }

DEVI uint64_t mkdesc(uint32_t addr, uint32_t lbo, uint32_t sbo) {
    return (uint64_t)((addr & 0x3FFFF) >> 4) | ((uint64_t)(lbo >> 4) << 16) | ((uint64_t)(sbo >> 4) << 32) | ((uint64_t)1 << 62);
}
DEVI void wg_fence() { asm volatile("wgmma.fence.sync.aligned;" ::: "memory"); }
DEVI void wg_commit() { asm volatile("wgmma.commit_group.sync.aligned;" ::: "memory"); }
template <int N> DEVI void wg_wait() { asm volatile("wgmma.wait_group.sync.aligned %0;" ::"n"(N) : "memory"); }
template <int SC>
DEVI void wg_rs32(float (&d)[16], const uint32_t (&a)[4], uint64_t db) {
    if (SC) {
        asm volatile("wgmma.mma_async.sync.aligned.m64n32k16.f32.bf16.bf16 "
                     "{%0,%1,%2,%3,%4,%5,%6,%7,%8,%9,%10,%11,%12,%13,%14,%15}, {%16,%17,%18,%19}, %20, 1, 1, 1, 0;"
                     : "+f"(d[0]), "+f"(d[1]), "+f"(d[2]), "+f"(d[3]), "+f"(d[4]), "+f"(d[5]), "+f"(d[6]), "+f"(d[7]),
                       "+f"(d[8]), "+f"(d[9]), "+f"(d[10]), "+f"(d[11]), "+f"(d[12]), "+f"(d[13]), "+f"(d[14]), "+f"(d[15])
                     : "r"(a[0]), "r"(a[1]), "r"(a[2]), "r"(a[3]), "l"(db));
    } else {
        asm volatile("wgmma.mma_async.sync.aligned.m64n32k16.f32.bf16.bf16 "
                     "{%0,%1,%2,%3,%4,%5,%6,%7,%8,%9,%10,%11,%12,%13,%14,%15}, {%16,%17,%18,%19}, %20, 0, 1, 1, 0;"
                     : "=f"(d[0]), "=f"(d[1]), "=f"(d[2]), "=f"(d[3]), "=f"(d[4]), "=f"(d[5]), "=f"(d[6]), "=f"(d[7]),
                       "=f"(d[8]), "=f"(d[9]), "=f"(d[10]), "=f"(d[11]), "=f"(d[12]), "=f"(d[13]), "=f"(d[14]), "=f"(d[15])
                     : "r"(a[0]), "r"(a[1]), "r"(a[2]), "r"(a[3]), "l"(db));
    }
}

#define NA 12
#define NPF 6
#define PF1 2
#define PF2 1
#define PF3 4
#define WPF 2
#define VPF 2
#define VORD 0x01234567
#define VSF 0
#define VMF 0
#define VC 1
#define QP 16
#define W2P 0
#define W3P 1
#define QSP 10
#define VSB 0x105
#define QQP 3
#define CGP 8
#define C0P 9
#define C1P 9
#define PIP 10
#define K0P 2
#define KEP 1
#define KE2 0
#define VTP 0
#define CW 1
#define WV_BOX ((16 - NA) * 2048)
#define WO_BOX 16384
#define SM_WV 0
#define SM_WO (2 * WV_BOX)
#define SM_X (SM_WO + 4 * WO_BOX)
#define SM_XO (SM_X + 32768)
#define SM_MEMT (SM_XO + 12288)
#define SM_OT (SM_MEMT + 4096)
#define SM_VS (SM_OT + 2048)
#define SM_P (SM_VS + 2048)
#define SM_DN (SM_P + 1792)
#define SM_PROF (SM_P + 2048)
#define SM_ST (SM_X + 65536)
#define SM_KV SM_ST
#define SM_SP (SM_KV + 18432)
#define SM_TR (SM_ST + 32768)
#define SM_PI (SM_ST + 65536)
#define SM_BAR (SM_PI + 12288)
#define SM_TOTAL (SM_BAR + 512)
static_assert(NA == 12, "start-up chunks");
static_assert(SM_TOTAL <= 232448, "smem");
#define BAR_XA 32
#define BAR_KV 40
#define BAR_PI 48
#define BAR_RO 64
#define BAR_WF 256
#define BAR_WE 384
#define SM_ROLE (SM_BAR + 72)

#define SPIN_LIMIT (1 << 20)
#define RPOS 26
#define OPOS 3
#define ASF 0
#define KPOS 0
#define CPOS 5
#define DLY_V 260
#define NPRB 2
#define PW 4
#define ZD 0
#define FTM 2
#define XPF 1
#define WOP 2
#define WIN 2
#define EPD 1300
#define ASP 4
#define EPF 0
#define CFAR 1

template <int ID, int N> DEVI void bsync() { asm volatile("bar.sync %0, %1;" ::"n"(ID), "n"(N) : "memory"); }
template <int ID, int N> DEVI void barv() { asm volatile("bar.arrive %0, %1;" ::"n"(ID), "n"(N) : "memory"); }

#define PT(n)
#define PC(n, v)
#define PDUMP()
#define REFRESH() asm volatile("xor.b32 %0, %0, %1;" : "+r"(l16) : "r"(zero))
#define OPQ(x) asm volatile("xor.b32 %0, %0, %1;" : "+r"(x) : "r"(zero))
#define KEEP(x, a, b, c, d) asm volatile("{\n.reg .b32 t;\nlop3.b32 t, %1, %2, %3, 0x80;\nlop3.b32 t, t, %4, %5, 0x80;\nxor.b32 %0, %0, t;\n}" \
                                         : "+r"(x) : "r"(a), "r"(b), "r"(c), "r"(d), "r"(zero))
#define SF() asm volatile("pmevent 1;" ::: "memory")
#define MF() __syncwarp()
#define SB0 1024u

#define XDOFF(ks) ((((ks) >> 2) * 1024 + ((ks) & 3) * 32) >> 4)
template <int SC>
DEVI void wg_ss32t(float (&d)[16], uint64_t da, uint64_t db) {
    if (SC) {
        asm volatile("wgmma.mma_async.sync.aligned.m64n32k16.f32.bf16.bf16 "
                     "{%0,%1,%2,%3,%4,%5,%6,%7,%8,%9,%10,%11,%12,%13,%14,%15}, %16, %17, 1, 1, 1, 1, 0;"
                     : "+f"(d[0]), "+f"(d[1]), "+f"(d[2]), "+f"(d[3]), "+f"(d[4]), "+f"(d[5]), "+f"(d[6]), "+f"(d[7]),
                       "+f"(d[8]), "+f"(d[9]), "+f"(d[10]), "+f"(d[11]), "+f"(d[12]), "+f"(d[13]), "+f"(d[14]), "+f"(d[15])
                     : "l"(da), "l"(db));
    } else {
        asm volatile("wgmma.mma_async.sync.aligned.m64n32k16.f32.bf16.bf16 "
                     "{%0,%1,%2,%3,%4,%5,%6,%7,%8,%9,%10,%11,%12,%13,%14,%15}, %16, %17, 0, 1, 1, 1, 0;"
                     : "=f"(d[0]), "=f"(d[1]), "=f"(d[2]), "=f"(d[3]), "=f"(d[4]), "=f"(d[5]), "=f"(d[6]), "=f"(d[7]),
                       "=f"(d[8]), "=f"(d[9]), "=f"(d[10]), "=f"(d[11]), "=f"(d[12]), "=f"(d[13]), "=f"(d[14]), "=f"(d[15])
                     : "l"(da), "l"(db));
    }
}

DEVI void delay_until(uint32_t t0, uint32_t d) { while (clk() - t0 < d) {} }

#define VR 2
#define CW2 4
template <int I0, int I1>
DEVI void xmma(float (&xa)[16], float (&xb)[16], uint32_t w, int ps, uint32_t zero, const uint32_t (&Wq)[16][4], const uint32_t (&Wk)[16][4],
               const uint32_t (&Wv)[NA][4], const uint32_t (&wv)[16 - NA][4]) {
    const uint64_t xd = mkdesc(SB0 + SM_X, 16, 4096) + (ps & 1) * 1024, vd = mkdesc(SB0 + SM_WV, 8192, 1024);
    uint32_t vo = (w >> 2) * (WV_BOX / 16);
    if (VR ? false : VC == 0 ? I0 < 16 - NA : VC == 1 ? I0 >= 32 && I0 < 48 - NA : I1 > 32 + NA) OPQ(vo);
#pragma unroll
    for (int i = I0; i < I1; i++) {
        if (VC) {
            const int v = (i + (VC == 1 ? NA : 0)) & 15;
            if (i == 0) wg_rs32<0>(xa, Wq[0], xd);
            else if (i < 16) wg_rs32<1>(xa, Wq[i & 15], xd + XDOFF(i & 15));
            else if (i == 16) wg_rs32<0>(xb, Wk[0], xd);
            else if (i < 32) wg_rs32<1>(xb, Wk[i & 15], xd + XDOFF(i & 15));
            else if (i == 32 && v < NA) wg_rs32<0>(xa, Wv[0], xd);
            else if (VR && i == 32) wg_rs32<0>(xa, wv[0], xd + XDOFF(NA));
            else if (VR && v >= NA) wg_rs32<1>(xa, wv[v >= NA ? v - NA : 0], xd + XDOFF(v));
            else if (i == 32) wg_ss32t<0>(xa, (vd & ~0xFFFFFFFFull) | ((uint32_t)vd + vo), xd + XDOFF(NA));
            else if (v < NA) wg_rs32<1>(xa, Wv[v < NA ? v : 0], xd + XDOFF(v));
            else wg_ss32t<1>(xa, (vd & ~0xFFFFFFFFull) | ((uint32_t)vd + (v - NA) * 128 + vo), xd + XDOFF(v));
        } else
        if (i == 0) wg_ss32t<0>(xb, (vd & ~0xFFFFFFFFull) | ((uint32_t)vd + vo), xd + XDOFF(NA));
        else if (i < 16 - NA) wg_ss32t<1>(xb, (vd & ~0xFFFFFFFFull) | ((uint32_t)vd + i * 128 + vo), xd + XDOFF(NA + i));
        else if (i == 16 - NA) wg_rs32<0>(xa, Wq[0], xd);
        else if (i < 32 - NA) wg_rs32<1>(xa, Wq[(i + NA) & 15], xd + XDOFF((i + NA) & 15));
        else if (i < 32) wg_rs32<1>(xb, Wv[(i + NA) & 15], xd + XDOFF((i + NA) & 15));
        else if (i == 32) wg_rs32<0>(xa, Wk[0], xd);
        else wg_rs32<1>(xa, Wk[i & 15], xd + XDOFF(i & 15));
    }
    wg_commit();
}
#define XMMA(I0, I1) xmma<(I0), (I1)>(xa, xb, w, p ^ 1, zero, Wq, Wk, Wv, wv)
DEVI void wg_done(float (&d)[16]) {
    asm volatile("" : "+f"(d[0]), "+f"(d[1]), "+f"(d[2]), "+f"(d[3]), "+f"(d[4]), "+f"(d[5]), "+f"(d[6]), "+f"(d[7]),
                      "+f"(d[8]), "+f"(d[9]), "+f"(d[10]), "+f"(d[11]), "+f"(d[12]), "+f"(d[13]), "+f"(d[14]), "+f"(d[15]) :: "memory");
}
template <int M>
DEVI void xpack(uint32_t (&xp)[8], float (&xa)[16]) {
    wg_done(xa);
#pragma unroll
    for (int i = 0; i < 4; i++) {
        xp[2 * i] = pack2(xa[4 * i], xa[4 * i + (M < 2 ? 2 : 1)]);
        xp[2 * i + 1] = pack2(xa[4 * i + (M < 2 ? 1 : 2)], xa[4 * i + 3]);
    }
}
template <int M>
DEVI uint4 xpeer(uint32_t sb, int ps, uint32_t t16) { return lds128(sb + SM_PI - ((ps & 1) ^ 1) * 12288 + M * 4096 + t16); }
DEVI void xadd(uint32_t (&xp)[8], const uint4& pi) {
    xp[0] = hadd2(xp[0], pi.x); xp[1] = hadd2(xp[1], pi.y); xp[2] = hadd2(xp[2], pi.z); xp[3] = hadd2(xp[3], pi.w);
}
template <int M>
DEVI void xsend(const uint32_t (&xp)[8], uint32_t sb, int ps, uint32_t t16) {
    asm volatile("st.async.weak.shared::cluster.mbarrier::complete_tx::bytes.v4.b32 [%0], {%1,%2,%3,%4}, [%5];"
                 ::"r"((sb ^ 0x1000000) + SM_PI - (ps & 1) * 12288 + M * 4096 + t16), "r"(xp[4]), "r"(xp[5]), "r"(xp[6]), "r"(xp[7]),
                   "r"((sb ^ 0x1000000) + SM_BAR + BAR_PI + (ps & 1) * 8) : "memory");
}
template <int M>
DEVI void xstore(const uint32_t (&xp)[8], uint32_t sb, uint32_t sbw, int ps, uint32_t t16, uint32_t KA) {
    const uint32_t a = SM_XO + M * 2048 + (M < 2 ? (KA & 0xFF) + sbw : (t16 >> 1) + sb);
    sts64(a, xp[0], xp[1]);
    sts64(a + 6144, xp[2], xp[3]);
    xsend<M>(xp, sb, ps, t16);
}
template <int M>
DEVI void xpark(uint32_t (&xp)[8], const uint4& pi, uint32_t sb, uint32_t sbw, int ps, uint32_t t16, uint32_t KA) {
    xadd(xp, pi);
    xstore<M>(xp, sb, sbw, ps, t16, KA);
}
template <uint32_t OFF> DEVI void red2(uint32_t lo, uint32_t hi, uint32_t a, uint32_t b) {
    asm volatile("{\n.reg .b64 a;\nmov.b64 a, {%0,%1};\nred.relaxed.gpu.global.add.noftz.v2.bf16x2 [a+%4], {%2,%3};\n}"
                 ::"r"(lo), "r"(hi), "r"(a), "r"(b), "n"(OFF) : "memory");
}
template <int M, int N>
DEVI void xstart(uint32_t sb, uint32_t w, uint32_t ga, uint32_t xhi, uint32_t j, uint32_t t16, uint32_t KA, const uint32_t (&W)[N][4]) {
    float xa[16], xb[16];
    uint32_t xp[8];
    auto pass = [&](float (&d)[16], int i, int k0, int k1) {
        const uint64_t xd = mkdesc(SB0 + SM_X + (i ? i + 1 : 0) * 16384, 16, 4096), vd = mkdesc(SB0 + SM_WV, 8192, 1024) + (w >> 2) * (WV_BOX / 16);
#pragma unroll
        for (int k = k0; k < k1; k++) {
            if (k == 0) wg_rs32<0>(d, W[0], xd);
            else if (k < N) wg_rs32<1>(d, W[k < N ? k : 0], xd + XDOFF(k));
            else wg_ss32t<1>(d, vd + (k - N) * 128, xd + XDOFF(k));
        }
        wg_commit();
    };
    wg_fence();
    pass(xa, 0, 0, 16);
    pass(xb, 1, 0, ASP);
    if (M == 0) bsync<5, 288>();
    ga += M < 2 ? (KA & 0xFF) + w * 256 : t16 >> 1;
    constexpr uint32_t O = XO_XG + M * 2048, SG = 128 * 6144;
    wg_wait<1>();
    xpack<M>(xp, xa);
    red2<O>(ga, xhi, xp[0], xp[1]); red2<O + 6144>(ga, xhi, xp[2], xp[3]); red2<O + 12288>(ga, xhi, xp[4], xp[5]); red2<O + 18432>(ga, xhi, xp[6], xp[7]);
    if (M == 2) barv<3, 320>();
    wg_fence();
    pass(xb, 1, ASP, 16);
    pass(xa, 2, 0, 16);
    wg_wait<1>();
    xpack<M>(xp, xb);
    red2<O + SG>(ga, xhi, xp[0], xp[1]); red2<O + SG + 6144>(ga, xhi, xp[2], xp[3]);
    red2<O + SG + 12288>(ga, xhi, xp[4], xp[5]); red2<O + SG + 18432>(ga, xhi, xp[6], xp[7]);
    wg_wait<0>();
    xpack<M>(xp, xa);
    red2<O + 2 * SG>(ga + j * 6144, xhi, xp[0], xp[1]);
    red2<O + 2 * SG>(ga + (j ^ 1) * 6144, xhi, xp[2], xp[3]);
    xsend<M>(xp, sb, 0, t16);
}
DEVI void piwait(uint32_t sb, int p, int ps) { mbar_wait(sb + SM_BAR + BAR_PI + p * 8, ((ps + 2) >> 1) & 1); }

DEVI uint32_t par(uint32_t off) { return __popc(off & 0xB2000u) & 1; }
DEVI uint32_t probe(uint32_t lo, uint32_t hi) {
    uint32_t best = 0xFFFFFFFFu, x = 0;
    stg4<0>(lo, hi, 0, 0, 0, 0);
    stg4<16>(lo, hi, 0, 0, 0, 0);
#pragma unroll 1
    for (int r = 0; r < NPRB; r++) {
        const uint32_t t0 = clk();
        asm volatile("{\n.reg .b64 a;\nmov.b64 a, {%1,%2};\natom.relaxed.gpu.global.add.u32 %0, [a], 2;\n}" : "=r"(x) : "r"(lo), "r"(hi) : "memory");
        if (x == 0xFFFFFFFFu) die(1 << 23);
        best = min(best, clk() - t0);
    }
    return best;
}

DEVI void xload(uint32_t sb, uint32_t u, uint32_t j, int ps, const CUtensorMap* tmx) {
    if (elect()) {
        const uint32_t sg = ps + 4 - (u & 1) + (u >> 1);
        mbar_expect(sb + SM_BAR + BAR_XA, sg < NSEG ? 4096 : 0);
        if (sg < NSEG) tma3d(sb + SM_X + (ps & 1) * 16384 + u * 4096, tmx, sb + SM_BAR + BAR_XA, 0, sg * 32 + (j ^ ((u & 1) * 2 + (u >> 1))) * 8, j * 4);
    }
}
DEVI uint32_t rpage(uint32_t j, int s) { return (s & 3) * 65536 + (j & 1) * 8192 + (((s ^ (s >> 1) ^ j ^ (j >> 1)) & 1) << 12); }

#define RLOAD() { m0 = ldg4<XO_R>(a, ah); n0 = ldg4<XO_R + 16384>(a, ah); e0 = ldg1<XO_R + 32768>(e, eh); f0 = ldg1<XO_R + 33792>(e, eh); }
DEVI bool ruse(uint32_t a, const uint4& m0, const uint4& n0, uint32_t e0, uint32_t f0) {
    const uint32_t a0 = hadd2(m0.w, n0.w), b0 = hadd2(e0, f0);
    stsm4(a, hadd2(m0.x, n0.x), hadd2(m0.y, n0.y), hadd2(m0.z, n0.z), __byte_perm(a0, b0, 0x5410));
    return __any_sync(0xFFFFFFFFu, (a0 & b0 & 0x42000000u) != 0x42000000u);
}

#define GST(i) (SM_WO + (i) * 49152)
#define BAR_GF 128
#define BAR_GE (BAR_GF + 64)
#define BAR_GX (BAR_GE + 32)
#define D4(c, i) #c "f"(d[i]), #c "f"(d[i + 1]), #c "f"(d[i + 2]), #c "f"(d[i + 3])
#define D16(c, i) D4(c, i), D4(c, i + 4), D4(c, i + 8), D4(c, i + 12)
DEVI void mwait(uint32_t bar, uint32_t parity) {
    asm volatile("{\n.reg .pred p;\n.reg .b32 c;\nmbarrier.try_wait.parity.shared::cta.b64 p, [%0], %1;\n@p bra.uni D;\nmov.b32 c, 0;\n"
                 "L:\nadd.u32 c, c, 1;\nsetp.gt.u32 p, c, 4194304;\n@p st.shared.u32 [c], c;\n"
                 "mbarrier.try_wait.parity.shared::cta.b64 p, [%0], %1;\n@!p bra.uni L;\nD:\n}" ::"r"(bar), "r"(parity) : "memory");
}
DEVI void wg_ss256t(float (&d)[128], uint64_t da, uint64_t db) {
    asm volatile("wgmma.mma_async.sync.aligned.m64n256k16.f32.bf16.bf16 "
        "{%0,%1,%2,%3,%4,%5,%6,%7,%8,%9,%10,%11,%12,%13,%14,%15,%16,%17,%18,%19,%20,%21,%22,%23,%24,%25,%26,%27,%28,%29,%30,%31,%32,%33,%34,%35,%36,%37,%38,%39,%40,%41,%42,%43,%44,%45,%46,%47,%48,%49,%50,%51,%52,%53,%54,%55,%56,%57,%58,%59,%60,%61,%62,%63,%64,%65,%66,%67,%68,%69,%70,%71,%72,%73,%74,%75,%76,%77,%78,%79,%80,%81,%82,%83,%84,%85,%86,%87,%88,%89,%90,%91,%92,%93,%94,%95,%96,%97,%98,%99,%100,%101,%102,%103,%104,%105,%106,%107,%108,%109,%110,%111,%112,%113,%114,%115,%116,%117,%118,%119,%120,%121,%122,%123,%124,%125,%126,%127}, "
        "%128, %129, 1, 1, 1, 1, 1;"
        : D16(+, 0), D16(+, 16), D16(+, 32), D16(+, 48), D16(+, 64), D16(+, 80), D16(+, 96), D16(+, 112) : "l"(da), "l"(db));
}
template <int O, int KB> DEVI void g_half(float (&d)[64], uint64_t da) {
    const uint64_t db = mkdesc(SB0 + GST(KB & 3) + 16384 + O * 256, 8192, 1024);
#pragma unroll
    for (int k = 0; k < 4; k++)
        asm volatile("wgmma.mma_async.sync.aligned.m64n128k16.f32.bf16.bf16 "
            "{%0,%1,%2,%3,%4,%5,%6,%7,%8,%9,%10,%11,%12,%13,%14,%15,%16,%17,%18,%19,%20,%21,%22,%23,%24,%25,%26,%27,%28,%29,%30,%31,%32,%33,%34,%35,%36,%37,%38,%39,%40,%41,%42,%43,%44,%45,%46,%47,%48,%49,%50,%51,%52,%53,%54,%55,%56,%57,%58,%59,%60,%61,%62,%63}, "
            "%64, %65, 1, 1, 1, 1, 1;"
            : D16(+, 0), D16(+, 16), D16(+, 32), D16(+, 48) : "l"(da + (KB & 3) * 3072 + k * 16), "l"(db + k * 128));
}
DEVI void g_load(uint32_t sb, uint32_t u, uint32_t role, uint32_t kb, uint32_t xlo, uint32_t xhi, const CUtensorMap* tmb) {
    const uint32_t st = kb & 3, bar = sb + SM_BAR + BAR_GF + u * 32 + st * 8, dst = sb + GST(st), k = (role & 1) * 32 + kb;
    if (!elect()) return;
    mbar_expect(bar, u ? 8192 : 40960);
    bulk_g2s(dst + u * 8192, xlo + XO_OX + (k * 16 + (role >> 3)) * 16384 + u * 8192, xhi, 8192, bar);
    if (u == 0) {
        tma3d(dst + 16384, tmb, bar, 0, k * 64, ((role & 7) ^ 1) * 2);
        tma3d(dst + 32768, tmb, bar, 0, k * 64, (role & 7) * 2);
    }
}
DEVI void g_arrive(uint32_t a, uint32_t xhi, uint32_t n) {
    if (elect()) asm volatile("{\n.reg .b64 a;\nmov.b64 a, {%0,%1};\nred.release.gpu.global.inc.u32 [a], %2;\n}" ::"r"(a), "r"(xhi), "r"(n - 1) : "memory");
}
DEVI void g_wait(uint32_t a, uint32_t xhi) {
    int it = 0;
    uint32_t v;
    do {
        asm volatile("{\n.reg .b64 a;\nmov.b64 a, {%1,%2};\nld.acquire.gpu.global.u32 %0, [a];\n}" : "=r"(v) : "r"(a), "r"(xhi) : "memory");
        if (++it > SPIN_LIMIT) die(it);
    } while (__any_sync(0xFFFFFFFFu, v));
    asm volatile("fence.proxy.async.global;" ::: "memory");
}
#define SE 2
#define DLY_S 0
#define VX 1
#define VH 1
#define VD 1
#define SM_VP (SM_TR + 12288)
#define JV(h, j) (VH < 2 ? (j) ^ ((par((h) * 8192) ^ VH) << 1) : (j))
#define SEU 0
#define VA 0
#define VLP 0
#define VCP 1
#define SEED 0
#define VB 0
#define RCP 0
#define XLP 0
#define RE 0
#define DLY_E 300
#define DLY_T 200
#define RDW 0
#define APH 1
#define A0 0
#define A1 0
#define DNP 0
#define WLP 0
#define KEP0 1
#define VSB0 VSB
#define B3 0
#define GD 400
#define GE 3
#define GH 1
#define GS 1
#define GP 0
DEVI void g_done(float (&d)[64]) { asm volatile("" : D16(+, 0), D16(+, 16), D16(+, 32), D16(+, 48)::"memory"); }
DEVI void g_main(uint32_t sb, uint32_t w, uint32_t role, const CUtensorMap* tmy, void* out) {
    const uint32_t bar = sb + SM_BAR, t16 = threadIdx.x * 16;
    const uint64_t da = (mkdesc(SB0 + GST(0), 128, 1024) & ~((uint64_t)3 << 62)) + (w >> 2) * 512;
    float d[128];
#pragma unroll
    for (int i = 0; i < 128; i++) d[i] = 0.f;
#define GFULL(kb) { mwait(bar + BAR_GF + ((kb) & 3) * 8, ((kb) >> 2) & 1); if (w >= 4) mwait(bar + BAR_GF + 32 + ((kb) & 3) * 8, ((kb) >> 2) & 1); }
#pragma unroll 1
    for (uint32_t kb = 0; kb < (GE ? 28 : 29); kb++) {
        GFULL(kb);
        if (kb == 0 && threadIdx.x == 128) PG(4);
        if (kb == 4 && threadIdx.x == 0) PG(5);
        const uint64_t a = da + (kb & 3) * 3072, b = mkdesc(SB0 + GST(0) + 16384, 8192, 1024) + (kb & 3) * 3072;
        wg_fence();
#pragma unroll
        for (int k = 0; k < 4; k++) wg_ss256t(d, a + k * 16, b + k * 128);
        wg_commit();
        wg_wait<1>();
        if (kb > 0 && elect()) mbar_arrive(bar + BAR_GE + ((kb - 1) & 3) * 8);
    }
    if (GE) { GFULL(28); }
    else { GFULL(29); GFULL(30); GFULL(31); }
    wg_wait<0>();
    if (GE && elect()) mbar_arrive(bar + BAR_GE + 24);
    float x[64], y[64];
#pragma unroll
    for (int i = 0; i < 64; i++) asm volatile("mov.b32 %0, %1;" : "=f"(x[i]) : "f"(d[i]) : "memory");
    SF();
#pragma unroll
    for (int i = 0; i < 64; i++) asm volatile("mov.b32 %0, %1;" : "=f"(y[i]) : "f"(d[i + 64]) : "memory");
    SF();
#define GFREE() if (elect()) asm volatile("mbarrier.arrive.relaxed.cluster.shared::cluster.b64 _, [%0];" ::"r"((bar ^ 0x1000000) + BAR_GX) : "memory")
#define GSW(i) ((i) * 4096 + (GE && (i) >= 4 ? GST(0) : 0))
#define GSEND(i0) _Pragma("unroll") for (int i = (i0); i < (i0) + 4; i++) \
        asm volatile("st.async.weak.shared::cluster.mbarrier::complete_tx::bytes.v4.b32 [%0], {%1,%2,%3,%4}, [%5];" \
                     ::"r"((sb ^ 0x1000000) + GSW(i) + t16), "r"(pack2(x[8 * i], x[8 * i + 1])), "r"(pack2(x[8 * i + 2], x[8 * i + 3])), \
                       "r"(pack2(x[8 * i + 4], x[8 * i + 5])), "r"(pack2(x[8 * i + 6], x[8 * i + 7])), "r"((bar ^ 0x1000000) + BAR_GX + 8) : "memory")
    if (GE) {
        wg_fence();
        g_half<0, 28>(x, da);
        wg_commit();
        GFULL(29);
        wg_fence();
        g_half<0, 29>(x, da);
        wg_commit();
        GFULL(30);
        wg_fence();
        g_half<0, 30>(x, da);
        wg_commit();
        GFULL(31);
        wg_fence();
        g_half<0, 31>(x, da);
        wg_commit();
        g_half<64, 28>(y, da);
        if (GE == 2) g_half<64, 29>(y, da);
        wg_commit();
        wg_wait<1>();
        g_done(x);
        GFREE();
        GSEND(0);
        wg_fence();
        if (GE != 2) g_half<64, 29>(y, da);
        if (GE != 1) g_half<64, 30>(y, da);
        wg_commit();
        mwait(bar + BAR_GX, 0);
        GSEND(4);
        wg_fence();
        if (GE == 1) g_half<64, 30>(y, da);
        g_half<64, 31>(y, da);
        wg_commit();
        mwait(bar + BAR_GX + 8, 0);
        if (threadIdx.x == 0) PG(1);
#pragma unroll
        for (int i = 0; i < 8; i++) {
            const uint4 a = lds128(sb + GSW(i) + t16);
            float* e = x + 8 * i;
            e[0] = lo_f(a.x); e[1] = hi_f(a.x); e[2] = lo_f(a.y); e[3] = hi_f(a.y); e[4] = lo_f(a.z); e[5] = hi_f(a.z); e[6] = lo_f(a.w); e[7] = hi_f(a.w);
        }
        g_done(x);
        SF();
        wg_wait<0>();
        g_done(y);
        if (threadIdx.x == 0) PG(7);
    } else {
        GFREE();
        wg_fence();
        g_half<0, 29>(x, da);
        g_half<0, 30>(x, da);
        g_half<0, 31>(x, da);
        wg_commit();
        g_half<64, 29>(y, da);
        wg_commit();
        wg_wait<1>();
        g_done(x);
        mwait(bar + BAR_GX, 0);
        GSEND(0);
        wg_fence();
        g_half<64, 30>(y, da);
        wg_commit();
        GSEND(4);
        wg_fence();
        g_half<64, 31>(y, da);
        wg_commit();
        wg_wait<0>();
        g_done(y);
        if (threadIdx.x == 0) PG(7);
        mwait(bar + BAR_GX + 8, 0);
        if (threadIdx.x == 0) PG(1);
    }
    const uint32_t lane = threadIdx.x & 31, o = sb + GST(1) + w * 2048;
    char* go = (char*)out + ((role >> 3) * 128 + w * 16 + (lane >> 3)) * 4096 + (role & 7) * 256 + (lane & 7) * 16;
#pragma unroll
    for (int i = 0; i < 8; i++) {
        float* e = y + 8 * i;
        if (GE) {
#pragma unroll
            for (int n = 0; n < 8; n++) e[n] += x[8 * i + n];
        } else {
            const uint4 a = lds128(sb + i * 4096 + t16);
            e[0] += lo_f(a.x); e[1] += hi_f(a.x); e[2] += lo_f(a.y); e[3] += hi_f(a.y); e[4] += lo_f(a.z); e[5] += hi_f(a.z); e[6] += lo_f(a.w); e[7] += hi_f(a.w);
        }
        stsm4(o + (i >> 2) * 49152 + (lane & 15) * 128 + ((((i & 3) * 2 + (lane >> 4)) ^ (lane & 7)) << 4),
              pack2(e[0], e[1]), pack2(e[2], e[3]), pack2(e[4], e[5]), pack2(e[6], e[7]));
        if (i == 3 || i == 7) {
            if (GS) {
                __syncwarp();
#pragma unroll
                for (int m = 0; m < 4; m++)
                    *(uint4*)(go + m * 16384 + (i >> 2) * 128) =
                        lds128(o + (i >> 2) * 49152 + m * 512 + (lane >> 3) * 128 + (((lane & 7) ^ ((m & 1) * 4 + (lane >> 3))) << 4));
            } else {
                asm volatile("fence.proxy.async.shared::cta;" ::: "memory");
                __syncwarp();
                if (elect())
                    asm volatile("cp.async.bulk.tensor.2d.global.shared::cta.bulk_group [%0, {%2, %3}], [%1];\ncp.async.bulk.commit_group;"
                                 ::"l"(tmy), "r"(o + (i >> 2) * 49152), "r"((role & 7) * 128 + (i >> 2) * 64), "r"((role >> 3) * 128 + w * 16) : "memory");
            }
        }
    }
    if (threadIdx.x == 0) PG(6);
    if (!GS) asm volatile("cp.async.bulk.wait_group.read 0;" ::: "memory");
}

DEVI void kvload(uint32_t sb, uint32_t u, uint32_t h, uint32_t j, int sg, uint32_t xlo, uint32_t xhi) {
    const uint32_t o = u == 0 ? 0 : 2048;
    mbar_expect(sb + SM_BAR + BAR_KV, 6144 - o);
    bulk_g2s(sb + SM_KV + u * 4096 + o, xlo + XO_XG + (((sg & 7) * 32 + h) * 4 + ((j + u) & 3)) * 6144 + o, xhi, 6144 - o, sb + SM_BAR + BAR_KV);
}
DEVI void helper_step(uint32_t sb, uint32_t w, uint32_t h, uint32_t j, uint32_t& l16, uint32_t xlo, uint32_t xhi, uint32_t zero, int s,
                      const CUtensorMap* tmx, const CUtensorMap* tmb) {
    const uint32_t u = w - 8, bq = sb + SM_BAR;
    bsync<1, 384>();
    PT(0);
    PDUMP();
    PT(1);
    if (s == NSEG - 2 && u < 2) g_arrive(xlo + XO_TK + 128, xhi, 256);
    uint32_t old = 0;
#define RCLEAR(n) if (RCP == (n) && u > 0 && s + 3 < NSEG) \
        asm volatile("{\n.reg .b64 a;\nmov.b64 a, {%1,%2};\natom.relaxed.gpu.global.exch.b32 %0, [a], 0;\n}" \
                     : "=r"(old) : "r"(xlo + XO_R + rpage(j, s + 2) + (u - 1) * 16384 + h * 128 + (l16 >> 2)), "r"(xhi) : "memory");
    RCLEAR(1);
    const bool gl = u == 0 || (u == 1 && h < 30);
    if (GP == 1 && s == NSEG - 1 && gl) g_load(sb, u, h * 4 + j, 1, xlo, xhi, tmb);
    const uint32_t ctag = ((s >> 1) & 1) ^ 1;
    const uint32_t av = xlo + ((s & 1) * 32 + h) * 8192 + u * 512;
    mbar_wait(bq + BAR_XA, (s + 1) & 1);
    if (B3 == 8) barv<5, 384>();
    bsync<8, 384>();
    const uint32_t t8 = clk(), gs = xlo + XO_XG + ((((s + 3) & 7) * 32 + h) * 4 + j) * 6144;
    RCLEAR(2);
    const bool se = B3 % 8 == 0 && SE && u == SEU && s + 3 < NSEG;
    uint32_t tv = ctag ^ 1, ro = 0;
    if (se) {
        asm volatile("fence.proxy.async.shared::cta;" ::: "memory");
        if (SE == 4) delay_until(t8, DLY_E);
        if ((SE == 1 || SE == 4) && elect()) bulk_s2g(gs, xhi, sb + SM_XO, 4096);
    } else if (RE && u == 1 && s + 2 < NSEG) {
        asm volatile("fence.proxy.async.shared::cta;" ::: "memory");
        const uint32_t cb0 = (h >> 1) * 32768 + (j & 1) * 16384 + (h & 1) * 8192;
        delay_until(t8, DLY_T);
        tv = ldg1<XO_CQK>((xlo + cb0 + ((par(cb0) ^ (j >> 1) ^ CFAR ^ 1) << 12)) ^ ((s & 1) * 0x81000), xhi);
        SF();
    }
    if (B3 != 6 || u || SE == 2) delay_until(t8, DLY_V);
    if (se && SE == 2 && elect()) bulk_s2g(gs, xhi, sb + SM_XO, 4096);
    PT(4);
    int it = 0;
    uint4 d1, d2, d3;
    uint2 e1, e2, e3;
    const uint32_t ae = av - u * 512 + (u & 1) * 256;
    const uint32_t jv = JV(h, j);
#define VLOAD() { if (!VD) d1 = ldg4<XO_CV>(av + (jv ^ 1) * 2048 + l16, xhi); \
        d2 = ldg4<XO_CV>(av + (jv ^ 2) * 2048 + l16, xhi); d3 = ldg4<XO_CV>(av + (jv ^ 3) * 2048 + l16, xhi); \
        if (B3 == 6 && VX) { if (!VD) e1 = ldg2<XO_CV>(ae + (jv ^ 1) * 2048 + (l16 >> 1), xhi); \
                       e2 = ldg2<XO_CV>(ae + (jv ^ 2) * 2048 + (l16 >> 1), xhi); e3 = ldg2<XO_CV>(ae + (jv ^ 3) * 2048 + (l16 >> 1), xhi); } \
        if (VD) { d1 = lds128(sb + SM_VP + (s & 1) * 2048 + u * 512 + l16); \
                  if (B3 == 6 && VX) e1 = lds64(sb + SM_VP + (s & 1) * 2048 + (u & 1) * 256 + (l16 >> 1)); } }
#define XSEND(F, C) if (u < 2) { \
        if (F) asm volatile("fence.proxy.async.shared::cta;" ::: "memory"); \
        if ((C) && elect()) { \
            const uint32_t sg = s + 3 - u; \
            if (sg < NSEG) { \
                const uint32_t ga = xlo + XO_XG + (((sg & 7) * 32 + h) * 4 + (j ^ (2 * u))) * 6144, sa = sb + SM_XO + u * 6144; \
                if (u == 0) bulk_s2g(ga + (SE ? 4096 : 0), xhi, sa + (SE ? 4096 : 0), SE ? 2048 : 6144); \
                else bulk_red(ga + ro, xhi, sa + ro, 6144 - ro); \
            } \
        } \
    }
    if (B3 == 8) {
        bsync<3, 384>();
        if (DLY_S) delay_until(clk(), DLY_S);
        XSEND(true, true);
    } else if (B3 == 6 && u == 0) {
        const uint32_t ga = xlo + XO_XG + ((((s + 3) & 7) * 32 + h) * 4 + j) * 6144, o = SE == 1 || SE == 2 ? 4096 : 0;
        if (o) {
            asm volatile("fence.proxy.async.shared::cta;" ::: "memory");
            if (s + 3 < NSEG && elect()) bulk_s2g(ga, xhi, sb + SM_XO, o);
        }
        bsync<3, 288>();
        if (DLY_S) delay_until(clk(), DLY_S);
        asm volatile("fence.proxy.async.shared::cta;" ::: "memory");
        if (elect()) {
            if (SE == 3 && s + 3 < NSEG) bulk_s2g(ga + o, xhi, sb + SM_XO + o, 6144 - o);
            if (s + 2 < NSEG) bulk_red(xlo + XO_XG + ((((s + 2) & 7) * 32 + h) * 4 + (j ^ 2)) * 6144, xhi, sb + SM_XO + 6144, 6144);
            if (SE != 3 && s + 3 < NSEG) bulk_s2g(ga + o, xhi, sb + SM_XO + o, 6144 - o);
        }
    } else {
    if (B3 == 6) VLOAD();
    if (B3 && B3 < 6) {
        VLOAD();
        bsync<B3 == 2 ? 4 : 3, 384>();
        XSEND(true, B3 < 3 || B3 == 5 || (B3 == 4 && u == 0));
    }
    while (true) {
        if (B3 % 7 == 0) VLOAD();
        if (RE && it == 0) {
            SF();
            if (!any_bad(tv ^ ctag)) {
                if (elect()) bulk_red(xlo + XO_XG + ((((s + 2) & 7) * 32 + h) * 4 + (j ^ 2)) * 6144, xhi, sb + SM_XO + 6144, 4096);
                ro = 4096;
            }
        }
        if (se && SE == 3 && it == 0 && elect()) bulk_s2g(gs, xhi, sb + SM_XO, 4096);
        uint32_t tg = or3(tagx2(d1.x, d1.z, ctag), tagx2(d2.x, d2.z, ctag), tagx2(d3.x, d3.z, ctag));
        if (B3 == 6 && VX) tg = or3(tg, tagx2(e1.x, e2.x, ctag), e3.x ^ ctag);
        const bool bad = any_bad(tg);
        if (B3 == 6 && VX) sts64(sb + SM_VS + (u & 1) * 256 + (l16 >> 1), hadd2(hadd2(e1.x, e2.x), e3.x), hadd2(hadd2(e1.y, e2.y), e3.y));
        sts128(sb + SM_VS + u * 512 + l16, hadd2(hadd2(d1.x, d2.x), d3.x), hadd2(hadd2(d1.y, d2.y), d3.y), hadd2(hadd2(d1.z, d2.z), d3.z),
               hadd2(hadd2(d1.w, d2.w), d3.w));
        if (VA) asm volatile("{\n.reg .pred p;\nsetp.eq.u32 p, %0, 0;\n@p bar.arrive 5, 384;\n}" ::"r"((uint32_t)bad) : "memory");
        if (B3 % 7 == 0) REFRESH();
        if (!bad) break;
        if (B3 % 7) { REFRESH(); VLOAD(); }
        if (++it > SPIN_LIMIT) die(it);
    }
    PC(26, it);
    PT(5);
    if (VB) barv<11, 384>();
    else if (!VA) barv<5, B3 == 6 ? 352 : 384>();
    }
    if (B3 % 7 == 0) {
        bsync<3, 384>();
        XSEND(true, true);
    }
    if (B3 == 3 || B3 == 4) XSEND(false, B3 == 3 || u == 1);
    PT(6);
    RCLEAR(0);
    PT(7);
    bsync<7, 384>();
    if (s + 1 < NSEG && elect()) kvload(sb, u, h, j, s + 1, xlo, xhi);
    RCLEAR(3);
    if (XLP == 1) xload(sb, u, j, s + 1, tmx);
    if (u < (B3 == 6 ? 1 : 2)) {
        asm volatile("cp.async.bulk.wait_group.read 0;" ::: "memory");
        if (elect()) {
            mbar_expect(bq + BAR_PI + ((s & 1) ^ 1) * 8, 6144);
            if (B3 == 6) mbar_expect(bq + BAR_PI + ((s & 1) ^ 1) * 8, 6144);
        }
    }
    PT(8);
    if (GP && s == NSEG - 2 && gl) g_wait(xlo + XO_TK + 128, xhi);
    if (s + 1 < NSEG) bsync<10, 384>();
    if (XLP == 0) xload(sb, u, j, s + 1, tmx);
    RCLEAR(4);
    if (s == NSEG - 2 && gl) {
        if (!GP) g_wait(xlo + XO_TK + 128, xhi);
        g_load(sb, u, h * 4 + j, 0, xlo, xhi, tmb);
        if (GP == 0 || GP == 3) g_load(sb, u, h * 4 + j, 1, xlo, xhi, tmb);
    }
    asm volatile("cp.async.bulk.wait_group 0;" ::: "memory");
    if (s + 1 < NSEG) mbar_wait(bq + BAR_KV, (s + 1) & 1);
    asm volatile("lop3.b32 %0, %0, %1, %2, 0x78;" : "+r"(l16) : "r"(old), "r"(zero));
    PT(15);
}
DEVI void tickets_done(uint32_t* tk) {
    if (atomicInc(tk + 2, gridDim.x / 2 - 64) == gridDim.x / 2 - 64) { tk[0] = 0; tk[1] = 0; }
}

__global__ void __cluster_dims__(2, 1, 1) __launch_bounds__(384, 1)
chain_kernel(const __grid_constant__ CUtensorMap tmq, const __grid_constant__ CUtensorMap tmk,
             const __grid_constant__ CUtensorMap tmv, const __grid_constant__ CUtensorMap tmo,
             const __grid_constant__ CUtensorMap tmx, const __grid_constant__ CUtensorMap tmb, const __grid_constant__ CUtensorMap tmy,
             const bf16* __restrict__ mem0, const bf16* __restrict__ xg,
             uint32_t xlo, uint32_t xhi, uint32_t zero, int nseg, bf16* __restrict__ out) {
    extern __shared__ __align__(1024) uint8_t smem[];
    const uint32_t tstart = clk();
    const uint32_t rk = smem_u32(smem) & 0x1000000;
    if (rk == 0 && (threadIdx.x & 31) == 0 && threadIdx.x - 32 < 32 * PW)
        sts32(SB0 + SM_ROLE + 4 + (threadIdx.x >> 3), probe(xlo + XO_PB + (threadIdx.x & 32) * 128 + (threadIdx.x & 64) * 256 + blockIdx.x * 16, xhi));
    __syncwarp();
    if ((smem_u32(smem) & 0xFFFFFF) != SB0) die(1 << 23);
    asm volatile("griddepcontrol.launch_dependents;" ::: "memory");
    const uint32_t w = __reduce_max_sync(0xFFFFFFFFu, threadIdx.x >> 5);
    const uint32_t sb = __reduce_max_sync(0xFFFFFFFFu, smem_u32(smem));
    const uint32_t bq = sb + SM_BAR;
    uint32_t l16 = __shfl_sync(0xFFFFFFFFu, (threadIdx.x & 31) * 16, threadIdx.x & 31);
    if (threadIdx.x == 0) {
        mbar_init(bq, 1);
        for (int i = 0; i < 24; i++) mbar_init(bq + BAR_WF + i * 8, i < 16 ? 1 : 8);
        mbar_init(bq + BAR_XA, 4); mbar_init(bq + BAR_KV, 4); mbar_init(bq + BAR_PI, 2); mbar_init(bq + BAR_PI + 8, 2);
        for (int i = 0; i < 14; i++) mbar_init(bq + BAR_GF + i * 8, i < 8 || i == 13 ? 1 : 8);
        mbar_expect(bq + BAR_GX + 8, 32768);
        mbar_init(bq + BAR_RO, 1);
        mbar_expect(bq + BAR_RO, 4);
        mbar_expect(bq + BAR_PI, 6144);
        mbar_expect(bq + BAR_PI, 6144);
        asm volatile("fence.mbarrier_init.release.cluster;" ::: "memory");
        asm volatile("fence.proxy.async.shared::cta;" ::: "memory");
    }
    __syncwarp();
    asm volatile("barrier.cluster.arrive.relaxed.aligned;" ::: "memory");
    if (w == 9) {
#pragma unroll 1
        for (int e = 0; e < 12; e++) sts128(sb + SM_WO + e * 512 + l16, 0, 0, 0, 0);
    }
    if (w == 8 && blockIdx.x < 128) {
        if (XPF && elect()) {
            asm volatile("cp.async.bulk.prefetch.L2.global [%0], 3072;" ::"l"((const char*)xg + blockIdx.x * 3072) : "memory");
            asm volatile("prefetch.tensormap [%0];\nprefetch.tensormap [%1];\nprefetch.tensormap [%2];\nprefetch.tensormap [%3];\nprefetch.tensormap [%4];"
                         ::"l"(&tmq), "l"(&tmx), "l"(&tmk), "l"(&tmv), "l"(&tmo) : "memory");
        }
#pragma unroll 1
        for (int i = 0; i < EPF; i++) {
            if (i) delay_until(clk(), EPD);
            if (elect())
                asm volatile("cp.async.bulk.prefetch.tensor.3d.L2.global [%0, {0, %1, %2}];" ::"l"(&tmq), "r"((blockIdx.x & 3) * 256 + i * 64), "r"((blockIdx.x >> 2) * 2) : "memory");
        }
    }
    if (rk == 0 && w <= PW) bsync<2, 32 * PW + 32>();
    asm volatile("barrier.cluster.wait.aligned;" ::: "memory");
    if (rk == 0 && threadIdx.x == 0) {
        uint32_t t1 = lds32(sb + SM_ROLE + 8), t0 = lds32(sb + SM_ROLE + 12);
        if (PW == 4) { t1 = min(t1, lds32(sb + SM_ROLE + 16)); t0 = min(t0, lds32(sb + SM_ROLE + 20)); }
        uint32_t side = (t0 < t1 ? 0u : 1u) ^ par(XO_PB);
        uint32_t* tk = (uint32_t*)(((uint64_t)xhi << 32) | (xlo + XO_TK));
        uint32_t t = atomicAdd(tk + side, 1u);
        if (t >= 32) {
            uint2 c;
            int it = 0;
            do {
                c = ldg2<XO_TK>(xlo, xhi);
                if (++it > SPIN_LIMIT) die(it);
            } while (c.x + c.y != gridDim.x / 2);
            t += (side ? c.x : c.y) - 32;
            side ^= 1;
            if (t >= 32) tickets_done(tk);
        }
#pragma unroll
        for (uint32_t r = 0; r < 2; r++)
            asm volatile("st.async.weak.shared::cluster.mbarrier::complete_tx::bytes.b32 [%0], %1, [%2];"
                         ::"r"(sb + SM_ROLE + (r << 24)), "r"(t * 4 + side * 2 + r), "r"(bq + BAR_RO + (r << 24)) : "memory");
    }
    __syncwarp();
    mbar_wait(bq + BAR_RO, 0);
    const uint32_t role = __reduce_max_sync(0xFFFFFFFFu, lds32(sb + SM_ROLE));
    if (role >= 128) return;
    const uint32_t h = role >> 2, j = role & 3;
    if (FTM && w == 11 && elect())
#pragma unroll
        for (uint32_t c = 0; c < FTM; c++) {
            mbar_expect(bq + BAR_WF + c * 8, 16384);
            tma3d(sb + SM_ST + c * 16384, &tmq, bq + BAR_WF + c * 8, 0, j * 256 + c * 64, h * 2);
        }

    if (w >= 8) {
        asm volatile("setmaxnreg.dec.sync.aligned.u32 24;");
        const uint32_t u = w - 8;
        if (u == 3) {
#pragma unroll 1
            for (uint32_t c = FTM; c < 16; c++) {
                if (c >= WIN) mbar_wait(bq + BAR_WF + (c - WIN) * 8, 0);
                if (l16 == 0) PG(16 + c);
                if (c == 12 + WOP) bsync<2, 64>();
                if (c >= 4 && c < 12 && c != 10) mbar_wait(bq + BAR_WE + (c - 4) * 8, 0);
                if (elect()) {
                    const uint32_t b = bq + BAR_WF + c * 8;
                    mbar_expect(b, 16384);
                    if (c >= 12) tma2d(sb + SM_WO + (c - 12) * WO_BOX, &tmo, b, j * 256 + (c - 12) * 64, h * 128);
                    else tma3d(c == 10 ? sb + SM_WV : sb + SM_ST + (c & 3) * 16384, c < 4 ? &tmq : c < 8 ? &tmk : &tmv, b, 0, j * 256 + ((c ^ (c >= 10)) & 3) * 64, h * 2);
                }
            }
#pragma unroll 1
            for (uint32_t c = 16 - WIN; c < 16; c++) mbar_wait(bq + BAR_WF + c * 8, 0);
            if (l16 == 0) PG(15);
        } else if (u == 0) {
            if (elect()) {
                mbar_expect(bq, 49152);
#pragma unroll 1
                for (uint32_t i = 0; i < 12; i++)
                    tma3d(sb + SM_X + (i < 4 ? i : i + 4) * 4096, &tmx, bq, 0, i < 8 ? i * 8 : (j ^ ((0xBD98u >> (i - 8) * 4) & 15)) * 8, j * 4);
            }
#pragma unroll 1
            for (int i = 0; i < 4; i++) xload(sb, i, j, -1, &tmx);
            bsync<3, 320>();
            if (l16 == 0) PG(32);
            if (GH && j == 0 && elect()) asm volatile("{\n.reg .b64 a;\nmov.b64 a, {%0,%1};\nred.relaxed.gpu.global.inc.u32 [a+64], 4;\n}" ::"r"(xlo + XO_FL + h * 128), "r"(xhi) : "memory");
            __syncwarp();
            g_arrive(xlo + XO_FL + h * 128, xhi, 4);
            if (WOP < 4) barv<2, 64>();
            if (l16 == 0) PG(33);
            g_wait(xlo + XO_FL + h * 128, xhi);
            if (l16 == 0) PG(34);
#pragma unroll 1
            for (int i = 0; i < 4; i++)
                if (elect()) kvload(sb, i, h, j, 0, xlo, xhi);
            mbar_wait(bq + BAR_KV, 0);
            if (l16 == 0) PG(14);
        } else if (u == 1) {
            const uint32_t l = l16 >> 4, x = h * 8 + (l >> 2), d = (x & ~31u) + (l & 3) * 8 + ((x & 31) >> 2) + (x & 3) * 2 * DM;
            const unsigned short* m0 = (const unsigned short*)mem0 + j * 256;
            const uint32_t v1 = m0[d] | (((l & 3) == 3 ? 0x4200u : m0[d + DM]) << 16);
            const uint32_t v3 = h < 8 ? m0[h * 32 + 24 + (l >> 2) + ((l & 3) * 2 + 1) * DM] | 0x42000000u : 0;
#pragma unroll 1
            for (uint32_t i = 0; i < 12; i++) {
                if (i == 10) { sts32(sb + SM_WO + 6144 + l * 4, v1); sts32(sb + SM_WO + 6272 + l * 4, v3); }
                asm volatile("fence.proxy.async.shared::cta;" ::: "memory");
                __syncwarp();
                const uint32_t c = (0x21924u >> ((i - 3) * 2)) & 3;
                if (elect()) {
                    if (i < 3) bulk_s2g(xlo + XO_XG + (i * 128 + role) * 6144, xhi, sb + SM_WO, 6144);
                    else bulk_s2g(xlo + XO_R + rpage(j, i < 6 ? 0 : i < 9 ? 1 : -1) + c * 16384 + h * 128, xhi, sb + SM_WO + (i < 10 ? 0 : 6144 + c * 64), 128);
                }
            }
            asm volatile("cp.async.bulk.wait_group 0;" ::: "memory");
            if (elect()) asm volatile("{\n.reg .b64 a;\nmov.b64 a, {%0,%1};\nred.relaxed.gpu.global.inc.u32 [a], 127;\n}" ::"r"(xlo + XO_TK + 12), "r"(xhi) : "memory");
            if (l16 == 0) PG(16);
            g_wait(xlo + XO_TK + 12, xhi);
            if (l16 == 0) PG(17);
            barv<5, 288>();
            bsync<8, 320>();
            asm volatile("fence.acq_rel.gpu;" ::: "memory");
        } else {
            GSYNC(0);
            mbar_wait(bq + BAR_WE + 48, 0);
#pragma unroll 1
            for (int e = 0; e < 24; e++) sts128(sb + SM_TR + 4096 + e * 512 + l16, 0, 0, 0, 0);
            barv<3, 320>();
            bsync<8, 320>();
#pragma unroll 1
            for (int i = 0; i < 4; i++) xload(sb, i, j, 0, &tmx);
        }
#pragma unroll 1
        for (int s = 0; s < nseg; s++) helper_step(sb, w, h, j, l16, xlo, xhi, zero, s, &tmx, &tmb);
        piwait(sb, 0, nseg - 2);
        bsync<9, 384>();
        GSYNC(1);
        if (!GS && w == 11 && elect()) asm volatile("prefetch.tensormap [%0];" ::"l"(&tmy) : "memory");
        if (GH && w == 10) { g_arrive(xlo + XO_FL + h * 128 + 64, xhi, 5); PG(2); }
        if (w < 10) {
            uint32_t kb = 2, heads = 0;
            asm volatile("fence.proxy.async.shared::cta;" ::: "memory");
            if (GH) {
                if (w == 9 && h >= 30) { kb = 0; heads = 0xFFFF; }
                else delay_until(clk(), GD);
            } else if (w == 9) {
                g_arrive(xlo + XO_TK + 192, xhi, 128);
                PG(2);
                if (h >= 30) { g_wait(xlo + XO_TK + 192, xhi); kb = 0; }
                PG(3);
            } else delay_until(clk(), GD);
#pragma unroll 1
            for (; kb < 32; kb++) {
                if (kb >= 4) mbar_wait(bq + BAR_GE + (kb & 3) * 8, ((kb >> 2) & 1) ^ 1);
                if (GH && ((heads >> (kb >> 1)) & 1)) {
                    int it = 0;
                    do {
                        uint32_t v;
                        asm volatile("{\n.reg .b64 a;\nmov.b64 a, {%1,%2};\nld.acquire.gpu.global.u32 %0, [a+64];\n}"
                                     : "=r"(v) : "r"(xlo + XO_FL + (role & 1) * 2048 + (l16 & 255) * 8), "r"(xhi) : "memory");
                        heads = __ballot_sync(0xFFFFFFFFu, v != 0);
                        if (++it > SPIN_LIMIT) die(it);
                    } while ((heads >> (kb >> 1)) & 1);
                    asm volatile("fence.proxy.async.global;" ::: "memory");
                    if (kb == 0) PG(3);
                }
                g_load(sb, w - 8, role, kb, xlo, xhi, &tmb);
            }
        }
        if (role == 0 && w == 11 && elect()) tickets_done((uint32_t*)(((uint64_t)xhi << 32) | (xlo + XO_TK)));
    } else {
        asm volatile("setmaxnreg.inc.sync.aligned.u32 240;");
        uint32_t Wq[16][4], Wk[16][4], Wv[NA][4];
        uint32_t t16, KA, KB, KC, KD;
        {
            const uint32_t lane = l16 >> 4, g = lane >> 2, t = lane & 3;
            const uint32_t rw = (((lane >> 4) & 1) * 8 + (lane & 7)) * 128u;
            const uint32_t off = rw + ((((w & 3) * 2 + ((lane >> 3) & 1)) ^ (lane & 7)) << 4);
            const uint32_t offo = rw + ((((w & 1) * 4 + ((lane >> 3) & 1)) ^ (lane & 7)) << 4);
            const uint32_t r = 2 * (t & 1) + (g >> 2);
            const uint32_t mk0 = t < 2 ? 0 : (r == 0 ? 2 * g > w : j + r < 4), mk1 = t < 2 ? 0 : (r == 0 ? 2 * g + 1 > w : j + r < 4);
            t16 = __shfl_sync(0xFFFFFFFFu, w * 512 + l16, lane);
            KA = __shfl_sync(0xFFFFFFFFu, (w * 512 + t * 64 + g * 8) | ((w * 512 + (g & 1) * 256 + (g >> 1) * 64 + t * 16) << 16), lane);
            KB = __shfl_sync(0xFFFFFFFFu, ((w >> 2) * WV_BOX + off) | mk0 | (mk1 << 1) |
                                              ((w * 256 + (g >> 2) * 4096 + (g & 3) * 64 + t * 16) << 16), lane);
            KC = __shfl_sync(0xFFFFFFFFu, ((lane & 7) * 1280 + (lane >> 3) * 128 + ((w ^ (lane & 7)) << 4)) | (((t >> 1) * 16 + g * 2) << 16) | ((t * 64 + g * 8) << 24), lane);
            KD = __shfl_sync(0xFFFFFFFFu, ((w >> 1) * WO_BOX + offo) | (((lane & 7) * 208 + (lane >> 3) * 16) << 16), lane);
            if (threadIdx.x == 0) PG(8);
#define WTAKE(W, c, k0) { mbar_wait(bq + BAR_WF + (c) * 8, 0); \
                _Pragma("unroll") for (int ks = 0; ks < 4; ks++) ldsm4t(W[(k0) + ks], sb + SM_ST + ((c) & 3) * 16384 + (KB & 0xFFF0) + ks * 2048); \
                if ((c) < 8) { __syncwarp(); if (elect()) mbar_arrive(bq + BAR_WE + (c) * 8); } }
#pragma unroll
            for (int c = 0; c < 4; c++) WTAKE(Wq, c, c * 4);
            mbar_wait(bq, 0);
            if (threadIdx.x == 0) PG(9);
            xstart<0>(sb, w, xlo + h * 24576, xhi, j, t16, KA, Wq);
            if (threadIdx.x == 0) PG(10);
#pragma unroll
            for (int c = 0; c < 4; c++) WTAKE(Wk, c + 4, c * 4);
            if (threadIdx.x == 0) PG(11);
            xstart<1>(sb, w, xlo + h * 24576, xhi, j, t16, KA, Wk);
            if (threadIdx.x == 0) PG(12);
            WTAKE(Wv, 8, 0);
            WTAKE(Wv, 9, 4);
            mbar_wait(bq + BAR_WF + 80, 0);
            WTAKE(Wv, 11, 8);
            if (threadIdx.x == 0) PG(13);
            xstart<2>(sb, w, xlo + h * 24576, xhi, j, t16, KA, Wv);
            mbar_wait(bq + BAR_XA, 0);
            bsync<8, 320>();
        }
        const uint32_t ONES = 0x3F803F80u;
#define UNI(x) __reduce_max_sync(0xFFFFFFFFu, x)
        uint32_t swi = UNI((uint32_t)((uint64_t)smem >> 32));
        const uint32_t sbw = UNI(sb + w * 256), sbm = UNI(sb - w * 512), sbs = UNI(sb + w * 768), sbp = UNI(sb + w * 208);
#define OPQALL() { OPQ(t16); OPQ(KA); OPQ(KB); OPQ(KC); OPQ(KD); }
        OPQALL();
        if (SEED & 1) OPQ(Wq[0][0]);
        if (SEED & 2) OPQ(Wq[5][1]);
        if (SEED & 4) OPQ(Wk[0][0]);
        if (SEED & 8) OPQ(Wk[15][2]);
        if (SEED & 16) OPQ(Wv[0][0]);
        if (SEED & 32) OPQ(Wv[7][3]);
        const uint32_t cb0 = (h >> 1) * 32768 + (j & 1) * 16384 + (h & 1) * 8192;
        const uint32_t cb = UNI(xlo + cb0 + ((par(cb0) ^ (j >> 1) ^ CFAR) << 12)), cv = UNI(xlo + h * 8192 + JV(h, j) * 2048), h1 = UNI((h & 1) * 1024);
        const uint32_t uox = UNI(xlo + XO_OX + (h * 2 + (w >> 2)) * 262144 + j * 1024 + (w & 3) * 256 - w * 128);
        uint32_t rp = UNI(xlo + rpage(j, 0));
        float ox[4];
        float4 dn;
#define OXSTORE(s) asm volatile("{\n.reg .b64 a;\nmov.b64 a, {%0,%1};\nst.global.u32 [a], %2;\nst.global.u32 [a+128], %3;\n}" \
                                ::"r"(uox + (s) * 4096 + (t16 >> 2)), "r"(xhi), \
                                  "r"(pack2(ox[0] * dn.y, ox[1] * dn.w)), "r"(pack2(ox[2] * dn.y, ox[3] * dn.w)) : "memory")
#pragma unroll 1
        for (int s2 = 0;; s2 += 2, rp ^= 0x21000)
#pragma unroll
        for (int p = 0; p < 2; p++) {
            const int s = s2 + p;
            const uint32_t ctag = ((s2 >> 1) & 1) ^ 1;
            const uint32_t hb = cb ^ (p * 0x81000), rb = rp ^ (p * 0x11000);
            uint4 k0, k1, qq, c0, c1, c2, c3, pk;
            float va[4], vb[4];
            uint32_t qx0, qx1, ov0, ov1, wv[16 - NA][4];
            {
                float xa[16], xb[16];
                uint4 m0, n0;
                uint32_t e0, f0;
                uint32_t xp[8];
                wg_fence();
                XMMA(0, 6);
                SF();
                piwait(sb, p, s - 2);
                uint4 pi = xpeer<0>(sb, p ^ 1, t16);
                SF();
#define MR (VC ? 1 : 2)
#define MC (VC ? 2 : 1)
#define QPARK() { xpack<0>(xp, xa); xpark<0>(xp, pi, sb, sbw, p ^ 1, t16, KA); pi = xpeer<MR>(sb, p ^ 1, t16); SF(); }
                wg_fence();
                if (QP) {
                    XMMA(6, QP);
                    XMMA(QP, QP + 4);
                    wg_wait<1>();
                    SF();
                    QPARK();
                    wg_fence();
                    if (QP + 4 < RPOS) XMMA(QP + 4, RPOS);
                } else XMMA(6, RPOS);
                if (RPOS < 32) XMMA(RPOS, RPOS + 4 < 32 ? RPOS + 4 : 32);
                uint32_t a = (p ? rp : rp ^ 0x30000) + t16, e = (p ? rp : rp ^ 0x30000) + (t16 >> 2), ah = xhi, eh = xhi;
                OPQ(a); OPQ(e); OPQ(ah); OPQ(eh);
                SF();
                wg_wait<(RPOS < 32)>();
                SF();
                PT(11);
                RLOAD();
                SF();
                if (!QP) QPARK();
                if (RPOS + 4 < 32) {
                    wg_fence();
                    XMMA(RPOS + 4, 32);
                    SF();
                }
                wg_wait<0>();
                xpack<MR>(xp, xb);
                xpark<MR>(xp, pi, sb, sbw, p ^ 1, t16, KA);
                uint32_t acw, ahi, tg;
#define APREP() { OPQ(KA); if (!APH) OPQ(t16); acw = hb + (KA & 0xFFFF); ahi = xhi; tg = ctag; OPQ(acw); OPQ(ahi); OPQ(tg); }
                if (APH == 3) SF();
                if (APH) APREP();
                if (APH >= 2) OPQ(t16);
                SF();
                PT(12);
                {
                    int it = 0;
                    if (RDW) {
                        bool rb_;
#pragma unroll 1
                        do {
                            rb_ = ruse(sb + SM_MEMT + t16, m0, n0, e0, f0);
                            if (RDW == 2) MF();
                            if (RDW == 3) SF();
                            asm volatile("{\n.reg .pred p, q;\n.reg .b64 a, e;\nsetp.ne.u32 p, %15, 0;\nmov.b64 a, {%11,%12};\nmov.b64 e, {%13,%14};\n"
                                         "@p ld.relaxed.gpu.global.v4.u32 {%0,%1,%2,%3}, [a];\n@p ld.relaxed.gpu.global.v4.u32 {%4,%5,%6,%7}, [a+16384];\n"
                                         "@p ld.relaxed.gpu.global.u32 %8, [e+32768];\n@p ld.relaxed.gpu.global.u32 %9, [e+33792];\n"
                                         "add.u32 %10, %10, 1;\nsetp.gt.u32 q, %10, 1048576;\n@q st.shared.u32 [%10], %10;\n}"
                                         : "+r"(m0.x), "+r"(m0.y), "+r"(m0.z), "+r"(m0.w), "+r"(n0.x), "+r"(n0.y), "+r"(n0.z), "+r"(n0.w), "+r"(e0), "+r"(f0), "+r"(it)
                                         : "r"(a), "r"(ah), "r"(e), "r"(eh), "r"((uint32_t)rb_) : "memory");
                        } while (rb_);
                    } else
                    while (ruse(sb + SM_MEMT + t16, m0, n0, e0, f0)) {
                        RLOAD();
                        if (++it > SPIN_LIMIT) die(it);
                    }
                    PC(22, it + 1);
                }
                PT(13);
                if (APH == 1) OPQ(t16);
                if (!APH) APREP();
#define AX (p ? A1 : A0)
                float q[4], k[4];
                if (AX & 2) _Pragma("unroll") for (int i = 0; i < 4; i++) {
                    asm volatile("mov.b32 %0, %1;" : "=f"(q[i]) : "r"(zero)); asm volatile("mov.b32 %0, %1;" : "=f"(k[i]) : "r"(zero)); }
                if (APH < 2) SF();
                bsync<1, 384>();
                PT(0);
                uint32_t b[8][4];
#pragma unroll
                for (int i = 0; i < 8; i++) {
                    const int pp = i < 2 || (AX & 8) || ((AX & 16) && i >= 6) ? i : i ^ 1;
                    ldsm4t(b[pp], sbm + SM_MEMT + t16 + pp * 512);
                    if (i < 7 || (AX & 4)) MF();
                }
                if (ASF) SF();
                const uint32_t aWv = sb + SM_WV + (KB & 0xFFF0);
#define WVLD(n0, n1) _Pragma("unroll") for (int n = (n0); n < (n1) && n < 16 - NA; n++) ldsm4t(wv[n], aWv + n * 2048)
#pragma unroll
                for (int ks = 0; ks < 16; ks++) {
                    const uint32_t b0 = b[ks >> 1][(ks & 1) * 2], b1 = b[ks >> 1][(ks & 1) * 2 + 1];
                    if (AX & 1) {
                        if (ks == 0 && !(AX & 2)) {
                            mma16z(k, Wk[0][0], Wk[0][1], Wk[0][2], Wk[0][3], b0, b1);
                            mma16z(q, Wq[0][0], Wq[0][1], Wq[0][2], Wq[0][3], b0, b1);
                        } else {
                            mma16(k, Wk[ks][0], Wk[ks][1], Wk[ks][2], Wk[ks][3], b0, b1);
                            mma16(q, Wq[ks][0], Wq[ks][1], Wq[ks][2], Wq[ks][3], b0, b1);
                        }
                    } else if (ks == 0 && !(AX & 2)) {
                        mma16z(q, Wq[0][0], Wq[0][1], Wq[0][2], Wq[0][3], b0, b1);
                        mma16z(k, Wk[0][0], Wk[0][1], Wk[0][2], Wk[0][3], b0, b1);
                    } else {
                        mma16(q, Wq[ks][0], Wq[ks][1], Wq[ks][2], Wq[ks][3], b0, b1);
                        mma16(k, Wk[ks][0], Wk[ks][1], Wk[ks][2], Wk[ks][3], b0, b1);
                    }
                    if (ks == 10 && VPF) { SF(); WVLD(0, VPF); }
                }
                const uint32_t oq0 = settag(pack2(q[0], q[2]), tg), oq1 = settag(pack2(q[1], q[3]), tg);
                const uint32_t ok0 = pack2(k[0], k[2]), ok1 = pack2(k[1], k[3]);
                stg2<XO_CQK>(acw, ahi, oq0, ok0);
                stg2<XO_CQK + 256>(acw, ahi, oq1, ok1);
                SF();
                PT(1);
#define CLOADG() { c2 = ldg4<XO_CQK>((hb ^ 0x1000) + (KA >> 16), xhi); c3 = ldg4<XO_CQK>((hb ^ 0x5000) + (KA >> 16), xhi); }
#define CLOAD0() c0 = lds128(sb + SM_TR + (KA >> 16))
#define CLOAD1() c1 = lds128(sb + SM_TR + 4096 + p * 4096 + (KA >> 16))
#define CLOADS() { CLOAD0(); CLOAD1(); }
#define CSIDE(n) { if (CGP == (n)) CLOADG(); if (C0P == (n)) CLOAD0(); if (C1P == (n)) CLOAD1(); if (PIP == (n)) pk = xpeer<MC>(sb, p ^ 1, t16); \
                   if (QSP == (n)) { qx0 = (t16 & 64) ? qq.y : qq.x; qx1 = (t16 & 64) ? qq.w : qq.z; } }
#pragma unroll
                for (int rd = 0; rd < 8; rd++) {
                    const int pp = (VORD >> (28 - 4 * rd)) & 7;
                    const uint32_t* a = 2 * pp < NA ? Wv[2 * pp < NA ? 2 * pp : 0] : wv[2 * pp < NA ? 0 : 2 * pp - NA];
                    const uint32_t* c = 2 * pp < NA ? Wv[2 * pp < NA ? 2 * pp + 1 : 0] : wv[2 * pp < NA ? 0 : 2 * pp + 1 - NA];
                    if (rd == 0) {
                        mma16z(va, a[0], a[1], a[2], a[3], b[pp][0], b[pp][1]);
                        mma16z(vb, c[0], c[1], c[2], c[3], b[pp][2], b[pp][3]);
                        if (VSB & 256) SF();
                        OPQ(swi);
                        asm volatile("{\n.reg .b64 a;\nmov.b64 a, {%0,%1};\nst.v2.u32 [a], {%2,%3};\nst.v2.u32 [a+256], {%4,%5};\n}"
                                     ::"r"((KA & 0xFFF) + (sb ^ 0x1000000) + SM_TR + 4096 + p * 4096), "r"(swi), "r"(oq0), "r"(ok0), "r"(oq1), "r"(ok1) : "memory");
                        sts64(sb + SM_TR + (KA & 0xFFF), oq0, ok0);
                        sts64(sb + SM_TR + (KA & 0xFFF) + 256, oq1, ok1);
                    } else {
                        mma16(va, a[0], a[1], a[2], a[3], b[pp][0], b[pp][1]);
                        mma16(vb, c[0], c[1], c[2], c[3], b[pp][2], b[pp][3]);
                    }
                    if (rd == (p ? KEP : KEP0)) { KEEP(t16, oq0, oq1, ok0, ok1); if (KE2) KEEP(t16, acw, ahi, acw, ahi); }
                    if (((p ? VSB : VSB0) >> rd) & 1) SF();
                    if (rd == W2P) WVLD(2, 3);
                    if (rd == W3P) WVLD(3, 4);
                    if (rd == K0P) k0 = lds128(sb + SM_KV + 2048 + (KB >> 16));
                    if (rd == K0P + 1) k1 = lds128(sb + SM_KV + 10240 + (KB >> 16));
                    if (rd == QQP) qq = lds128(sbw + SM_KV + ((KA >> 16) & 0xFF));
                    CSIDE(rd);
                    if ((VSF >> rd) & 1) SF(); else if ((VMF >> rd) & 1) MF();
                }
#define VTAIL() { ov0 = pack2(va[0] + vb[0], va[1] + vb[1]); ov1 = pack2(va[2] + vb[2], va[3] + vb[3]); \
                  stg2<XO_CV>(cv + p * 262144 + (t16 >> 1), xhi, settag(ov0, ctag), ov1); \
                  if (VD) asm volatile("{\n.reg .b64 a;\nmov.b64 a, {%0,%1};\nst.v2.u32 [a], {%2,%3};\n}" \
                                     ::"r"((t16 >> 1) + (sb ^ 0x1000000) + SM_VP + p * 2048), "r"(swi), "r"(settag(ov0, ctag)), "r"(ov1) : "memory"); \
                  barv<8, 384>(); OPQ(t16); SF(); }
                if (!VTP) VTAIL();
            }
            PT(2);
            PDUMP();
            {
                const uint32_t a0 = sb + SM_KV;
                float xa[16], xb[16];
                uint32_t xp[8];
                if (CGP == 12 || QSP == 12) { CSIDE(12); SF(); }
                wg_fence();
                XMMA(32, 32 + CPOS);
                if (CGP == 13) { SF(); CSIDE(13); SF(); wg_fence(); }
                if (VR == 1) { XMMA(32 + CPOS, 36); XMMA(36, 36 + CW2); wg_wait<2>(); }
                else if (CW) { XMMA(32 + CPOS, 36 + CPOS); wg_wait<1>(); }
                SF();
                CSIDE(8);
                SF();
                if (VR == 1) { wg_wait<1>(); SF(); }
                if (VTP) VTAIL();
                CSIDE(9);
                SF();
                wg_fence();
                XMMA(VR == 1 ? 36 + CW2 : 32 + CPOS + (CW ? 4 : 0), 48);
                SF();
                uint2 u1, u2, u3;
#define ULOADG() { u2 = ldg2<XO_CV>((cv ^ 4096) + p * 262144 + (t16 >> 1), xhi); u3 = ldg2<XO_CV>((cv ^ 6144) + p * 262144 + (t16 >> 1), xhi); }
#define ULOADS() u1 = lds64(sb + SM_VP + p * 2048 + (t16 >> 1))
#define UCHECK() { int it = 0; \
                   while (__builtin_expect(any_bad(tagx1(tagx2(u2.x, u3.x, ctag), u1.x, ctag)), 0)) { OPQ(t16); ULOADG(); ULOADS(); if (++it > SPIN_LIMIT) die(it); } \
                   PC(26, it); }
                CSIDE(10);
                if (B3 == 8 && VLP == 2) ULOADG();
                SF();
                const uint32_t ka[4] = {k0.x, k0.y, k0.z, k0.w}, kb[4] = {k1.x, k1.y, k1.z, k1.w};
                const uint32_t aSp = sb + SM_SP + (KC & 0xFFFF);
                PT(3);
#define BAR3() asm volatile("{\n.reg .pred p;\nsetp.eq.u32 p, %0, 0;\n@p bar.arrive 3, %1;\n}" ::"r"((uint32_t)bad), "n"(B3 == 6 ? 288 : 384) : "memory")
#define SCORES(FIRST) { \
                    const uint32_t qA = hadd2(hadd2(c0.x, c1.x), hadd2(c2.x, c3.x)), qB = hadd2(hadd2(c0.z, c1.z), hadd2(c2.z, c3.z)); \
                    const uint32_t kA = hadd2(hadd2(c0.y, c1.y), hadd2(c2.y, c3.y)), kB = hadd2(hadd2(c0.w, c1.w), hadd2(c2.w, c3.w)); \
                    bad = any_bad(or3(tagx2(c1.x, c1.z, ctag), tagx2(c2.x, c2.z, ctag), tagx2(c3.x, c3.z, ctag))); \
                    float sa[4], sb_[4], sc[4], sd[4], se[4]; \
                    if (FIRST) { SF(); if (B3 == 8 && VLP == 3) ULOADG(); CSIDE(11); wg_wait<0>(); } \
                    mma16z(sa, ka[0], ka[1], ka[2], ka[3], qA, qB); \
                    mma16z(sb_, kb[0], kb[1], kb[2], kb[3], qA, qB); \
                    mma16z(sc, qA, qx0, qB, qx1, kA, kB); \
                    if (FIRST) { \
                        xpack<MC>(xp, xa); \
                        if (KPOS == 0) { xadd(xp, pk); xstore<MC>(xp, sb, sbw, p ^ 1, t16, KA); if (B3 >= 5) BAR3(); else if (!B3 || B3 >= 3) barv<3, 384>(); } \
                        mma16z(sd, ka[0], ka[1], ka[2], ka[3], qx0, qx1); \
                        mma16z(se, kb[0], kb[1], kb[2], kb[3], qx0, qx1); \
                    } \
                    stsm4t(aSp, pack2(sa[0], sa[1]), pack2(sa[2], sa[3]), pack2(sb_[0], sb_[1]), pack2(sb_[2], sb_[3])); \
                    stsm2(aSp + 1024, pack2(sc[0], sc[1]), pack2(sc[2], sc[3])); \
                    if (FIRST) { \
                        stsm4t(aSp + 512, pack2(sd[0], sd[1]), pack2(sd[2], sd[3]), pack2(se[0], se[1]), pack2(se[2], se[3])); \
                        if (KPOS == 0) { KEEP(KD, xp[0], xp[1], xp[2], xp[3]); KEEP(KD, xp[4], xp[5], xp[6], xp[7]); } \
                    } }
                int it = 0;
                bool bad;
                SCORES(true);
                while (__builtin_expect(bad, 0)) {
                    OPQ(KA);
                    CLOADG();
                    CLOADS();
                    SCORES(false);
                    if (B3 >= 5) BAR3();
                    if (++it > SPIN_LIMIT) die(it);
                }
                PC(25, it);
                PT(4);
                if (B3 == 8 && VLP == 0) ULOADG();
                if (B3 == 1) barv<3, 384>();
                bsync<4, B3 == 2 ? 384 : 256>();
                uint32_t wo[16][4];
                const uint32_t aWo = sb + SM_WO + (KD & 0xFFFF), aWo1 = sb + SM_WO + ((KD & 0xFFFF) ^ 32);
#define WOLD(n0, n1) _Pragma("unroll") for (int n = (n0); n < (n1) && n < 16; n++) ldsm4t(wo[n], ((n & 1) ? aWo1 : aWo) + (n >> 1) * 2048)
                const bool hi = (t16 & 32) != 0;
                const uint32_t t8 = t16 >> 1;
                uint2 v0, v1, v2, v3;
                uint32_t es;
                {
                    uint32_t am[4], ax[4], a4[2];
                    const uint32_t aSr = sbs + SM_SP + t16;
                    ldsm4t(am, aSr);
                    ldsm4t(ax, aSr + 512);
                    ldsm2t(a4, aSr + 1024);
                    MF();
                    if (B3 == 8 && VLP == 1) ULOADG();
                    if (KPOS == 1) pk = xpeer<MC>(sb, p ^ 1, t16);
                    const uint32_t se = (t16 & 128) ? 0u : ONES, so = se ^ ONES;
                    float hm[4], hx[4], h4[4];
                    mma16z(hm, am[0], am[1], am[2], am[3], se, so);
                    mma16z(hx, ax[0], ax[1], ax[2], ax[3], se, so);
                    mma8z(h4, a4[0], a4[1], ONES);
                    SF();
                    if (KPOS == 1) { xpark<MC>(xp, pk, sb, sbw, p ^ 1, t16, KA); barv<3, 384>(); }
                    v0 = lds64(a0 + 4096 + t8); v1 = lds64(a0 + 8192 + t8); v2 = lds64(a0 + 12288 + t8); v3 = lds64(a0 + 16384 + t8);
                    if (B3 == 8) ULOADS();
                    WOLD(0, PF2);
                    float s0 = hi ? hx[0] : hm[0], s1 = hi ? hx[2] : hm[2];
                    const float s2 = hi ? h4[2] : h4[0];
                    s0 = (KB & 1) ? -1.0e9f * 11.313708499f : s0;
                    s1 = (KB & 2) ? -1.0e9f * 11.313708499f : s1;
                    int mi = __float_as_int(fmaxf(fmaxf(s0, s2), s1));
                    mi ^= (mi >> 31) & 0x7FFFFFFF;
                    const int mm = __reduce_max_sync(0xFFFFFFFFu, hi ? (int)0x80000000 : mi), mx = __reduce_max_sync(0xFFFFFFFFu, hi ? mi : (int)0x80000000);
                    SF();
                    WOLD(PF2, PF3);
                    SF();
                    mi = hi ? mx : mm;
                    mi ^= (mi >> 31) & 0x7FFFFFFF;
                    const float c2_ = 0.08838834764831845f * 1.4426950408889634f;
                    const float mc = __int_as_float(mi) * c2_;
                    const float e0 = ex2(fmaf(s0, c2_, -mc)), e1 = ex2(fmaf(s1, c2_, -mc)), e2 = ex2(fmaf(s2, c2_, -mc));
                    sts32(sbp + SM_P + (KC >> 25), pack2(e0, e1));
                    sts16(sbp + SM_P + 128 + ((KC >> 16) & 0xFF), pack2(e2, e2));
                    es = __float_as_uint(fmaf(e2, 0.5f, e0 + e1) + 64.f);
                }
                const uint32_t sm = __reduce_add_sync(0xFFFFFFFFu, hi ? 0u : es), sx = __reduce_add_sync(0xFFFFFFFFu, hi ? es : 0u);
                const uint32_t aPr = sb + SM_P + (KD >> 16);
                if (B3 == 8 && VCP == 0) UCHECK();
                PT(5);
                bsync<5, VB ? 256 : B3 == 6 ? 352 : 384>();
                uint32_t pm[4], px[4], p4[2];
                ldsm4(pm, aPr);
                MF();
                uint2 vs;
                #define VGET(n) if (VB == (n)) { if (VB) bsync<11, 384>(); vs = lds64(sb + SM_VS + t8); MF(); }
                if (B3 != 8) { VGET(0); VGET(1); }
                ldsm2(p4, aPr + 128);
                MF();
                VGET(2);
                ldsm4(px, aPr + 64);
                MF();
                VGET(3);
#define DNST(n) if (DNP == (n)) { sts32f(sb + SM_DN + w * 8 + ((t16 >> 3) & 4), rcp(__uint_as_float((hi ? sx : sm) - 15u * 0x42800000u) - 64.f)); MF(); }
                DNST(0);
                if (B3 == 8 && VCP == 2) UCHECK();
                if (WLP == 0) { WOLD(PF3, NPF); }
                if (DNP == 1) MF();
                DNST(1);
                if (B3 == 8 && VCP == 1) UCHECK();
                if (B3 == 8) { ov0 = hadd2(ov0, u1.x); ov1 = hadd2(ov1, u1.y); vs.x = hadd2(u2.x, u3.x); vs.y = hadd2(u2.y, u3.y); }
                const uint32_t vm0 = hadd2(ov0, vs.x), vm1 = hadd2(ov1, vs.y);
                float oa[4], ob[4];
                mma16z(oa, v0.x, v0.y, v1.x, v1.y, pm[0], pm[1]);
                mma16z(ob, v2.x, v2.y, v3.x, v3.y, pm[2], pm[3]);
                mma8(oa, vm0, vm1, p4[0]);
                stsm2(sbw + SM_OT + (t16 & 511), pack2(oa[0] + ob[0], oa[1] + ob[1]), pack2(oa[2] + ob[2], oa[3] + ob[3]));
                if (DNP == 2) MF();
                DNST(2);
                PT(6);
                SF();
                bsync<6, 256>();
                mma16z(ox, v0.x, v0.y, v1.x, v1.y, px[0], px[1]);
                uint32_t b[4][4];
#define OTLD(pp) ldsm4t(b[pp], sbm + SM_OT + t16 + (pp) * 512)
                OTLD(0);
                MF();
                OTLD(1);
                if (WLP == 1) { MF(); WOLD(PF3, NPF); }
                barv<7, 384>();
                mma16(ox, v2.x, v2.y, v3.x, v3.y, px[2], px[3]);
                mma8(ox, vm0, vm1, p4[1]);
                if (p == 1 && s + 1 == nseg) goto done;
                SF();
                uint32_t ar, ae, ahi = xhi;
                float r[2][4];
#pragma unroll
                for (int ks = 0; ks < 8; ks++) {
                    if (ks == 0) WOLD(NPF, NPF + WPF);
                    if (ks == OPOS) { OTLD(2); MF(); }
                    if (ks == OPOS + 2) { OTLD(3); MF(); }
                    if (ks > 0) WOLD(NPF + WPF + 2 * (ks - 1), NPF + WPF + 2 * ks);
                    if (ks == 5) {
                        OPQ(t16);
                        ar = rb + h1 * 16 + t16; ae = rb + h1 + (t16 >> 2);
                        OPQ(ar); OPQ(ahi); OPQ(ae);
                        dn = lds128f(sb + SM_DN + (t16 & 48));
                    }
#pragma unroll
                    for (int mt = 0; mt < 2; mt++) {
                        const int i = ks * 2 + mt;
                        const uint32_t* a = wo[i];
                        if (i < 2) mma16z(r[mt], a[0], a[1], a[2], a[3], b[ks >> 1][2 * (ks & 1)], b[ks >> 1][2 * (ks & 1) + 1]);
                        else mma16(r[mt], a[0], a[1], a[2], a[3], b[ks >> 1][2 * (ks & 1)], b[ks >> 1][2 * (ks & 1) + 1]);
                    }
                    if (NPF + WPF + 2 * ks < 16 || ks < 5) SF();
                }
                const float r0 = dn.x, r1 = dn.z;
                asm volatile("{\n.reg .b64 a;\nmov.b64 a, {%0,%2};\nred.relaxed.gpu.global.add.noftz.v4.bf16x2 [a], {%3,%4,%5,%6};\n"
                             "mov.b64 a, {%1,%2};\nred.relaxed.gpu.global.add.noftz.bf16x2 [a+32768], %7;\n}"
                             ::"r"(ar), "r"(ae), "r"(ahi), "r"(pack2(r[0][0] * r0, r[0][1] * r1)), "r"(pack2(r[0][2] * r0, r[0][3] * r1)),
                               "r"(pack2(r[1][0] * r0, r[1][1] * r1)), "r"(pack2(r[1][2] * r0, 1.f)), "r"(pack2(r[1][3] * r1, 1.f)) : "memory");
                barv<10, 384>();
            }
            SF();
            PT(10);
            OXSTORE(s);
            OPQALL();
        }
    done:
        dn = lds128f(sb + SM_DN + (t16 & 48));
        OXSTORE(nseg - 1);
        barv<9, 384>();
        g_main(sb, w, role, &tmy, out);
        if (threadIdx.x == 0) PG(0);
    }
}

template <int SC> DEVI void wg_rs128t(float (&d)[64], const uint32_t (&a)[4], uint64_t db) {
    if (SC) asm volatile("wgmma.mma_async.sync.aligned.m64n128k16.f32.bf16.bf16 "
        "{%0,%1,%2,%3,%4,%5,%6,%7,%8,%9,%10,%11,%12,%13,%14,%15,%16,%17,%18,%19,%20,%21,%22,%23,%24,%25,%26,%27,%28,%29,%30,%31,%32,%33,%34,%35,%36,%37,%38,%39,%40,%41,%42,%43,%44,%45,%46,%47,%48,%49,%50,%51,%52,%53,%54,%55,%56,%57,%58,%59,%60,%61,%62,%63}, "
        "{%64,%65,%66,%67}, %68, 1, 1, 1, 1;"
        : D4(+, 0), D4(+, 4), D4(+, 8), D4(+, 12), D4(+, 16), D4(+, 20), D4(+, 24), D4(+, 28), D4(+, 32), D4(+, 36), D4(+, 40), D4(+, 44), D4(+, 48), D4(+, 52), D4(+, 56), D4(+, 60) : "r"(a[0]), "r"(a[1]), "r"(a[2]), "r"(a[3]), "l"(db));
    else asm volatile("wgmma.mma_async.sync.aligned.m64n128k16.f32.bf16.bf16 "
        "{%0,%1,%2,%3,%4,%5,%6,%7,%8,%9,%10,%11,%12,%13,%14,%15,%16,%17,%18,%19,%20,%21,%22,%23,%24,%25,%26,%27,%28,%29,%30,%31,%32,%33,%34,%35,%36,%37,%38,%39,%40,%41,%42,%43,%44,%45,%46,%47,%48,%49,%50,%51,%52,%53,%54,%55,%56,%57,%58,%59,%60,%61,%62,%63}, "
        "{%64,%65,%66,%67}, %68, 0, 1, 1, 1;"
        : D4(=, 0), D4(=, 4), D4(=, 8), D4(=, 12), D4(=, 16), D4(=, 20), D4(=, 24), D4(=, 28), D4(=, 32), D4(=, 36), D4(=, 40), D4(=, 44), D4(=, 48), D4(=, 52), D4(=, 56), D4(=, 60) : "r"(a[0]), "r"(a[1]), "r"(a[2]), "r"(a[3]), "l"(db));
}
template <int SC> DEVI void wg_rs64t(float (&d)[32], const uint32_t (&a)[4], uint64_t db) {
    if (SC) asm volatile("wgmma.mma_async.sync.aligned.m64n64k16.f32.bf16.bf16 "
        "{%0,%1,%2,%3,%4,%5,%6,%7,%8,%9,%10,%11,%12,%13,%14,%15,%16,%17,%18,%19,%20,%21,%22,%23,%24,%25,%26,%27,%28,%29,%30,%31}, "
        "{%32,%33,%34,%35}, %36, 1, 1, 1, 1;"
        : D4(+, 0), D4(+, 4), D4(+, 8), D4(+, 12), D4(+, 16), D4(+, 20), D4(+, 24), D4(+, 28) : "r"(a[0]), "r"(a[1]), "r"(a[2]), "r"(a[3]), "l"(db));
    else asm volatile("wgmma.mma_async.sync.aligned.m64n64k16.f32.bf16.bf16 "
        "{%0,%1,%2,%3,%4,%5,%6,%7,%8,%9,%10,%11,%12,%13,%14,%15,%16,%17,%18,%19,%20,%21,%22,%23,%24,%25,%26,%27,%28,%29,%30,%31}, "
        "{%32,%33,%34,%35}, %36, 0, 1, 1, 1;"
        : D4(=, 0), D4(=, 4), D4(=, 8), D4(=, 12), D4(=, 16), D4(=, 20), D4(=, 24), D4(=, 28) : "r"(a[0]), "r"(a[1]), "r"(a[2]), "r"(a[3]), "l"(db));
}
template <int SC> DEVI void wg_rs40(float (&d)[20], const uint32_t (&a)[4], uint64_t db) {
    if (SC) asm volatile("wgmma.mma_async.sync.aligned.m64n40k16.f32.bf16.bf16 "
        "{%0,%1,%2,%3,%4,%5,%6,%7,%8,%9,%10,%11,%12,%13,%14,%15,%16,%17,%18,%19}, "
        "{%20,%21,%22,%23}, %24, 1, 1, 1, 0;"
        : D4(+, 0), D4(+, 4), D4(+, 8), D4(+, 12), D4(+, 16) : "r"(a[0]), "r"(a[1]), "r"(a[2]), "r"(a[3]), "l"(db));
    else asm volatile("wgmma.mma_async.sync.aligned.m64n40k16.f32.bf16.bf16 "
        "{%0,%1,%2,%3,%4,%5,%6,%7,%8,%9,%10,%11,%12,%13,%14,%15,%16,%17,%18,%19}, "
        "{%20,%21,%22,%23}, %24, 0, 1, 1, 0;"
        : D4(=, 0), D4(=, 4), D4(=, 8), D4(=, 12), D4(=, 16) : "r"(a[0]), "r"(a[1]), "r"(a[2]), "r"(a[3]), "l"(db));
}
template <int SC> DEVI void wg_rs8(float (&d)[4], const uint32_t (&a)[4], uint64_t db) {
    if (SC) asm volatile("wgmma.mma_async.sync.aligned.m64n8k16.f32.bf16.bf16 "
        "{%0,%1,%2,%3}, "
        "{%4,%5,%6,%7}, %8, 1, 1, 1, 0;"
        : D4(+, 0) : "r"(a[0]), "r"(a[1]), "r"(a[2]), "r"(a[3]), "l"(db));
    else asm volatile("wgmma.mma_async.sync.aligned.m64n8k16.f32.bf16.bf16 "
        "{%0,%1,%2,%3}, "
        "{%4,%5,%6,%7}, %8, 0, 1, 1, 0;"
        : D4(=, 0) : "r"(a[0]), "r"(a[1]), "r"(a[2]), "r"(a[3]), "l"(db));
}
template <int SC> DEVI void wg_ss64a(float (&d)[32], uint64_t da, uint64_t db) {
    if (SC) asm volatile("wgmma.mma_async.sync.aligned.m64n64k16.f32.bf16.bf16 "
        "{%0,%1,%2,%3,%4,%5,%6,%7,%8,%9,%10,%11,%12,%13,%14,%15,%16,%17,%18,%19,%20,%21,%22,%23,%24,%25,%26,%27,%28,%29,%30,%31}, "
        "%32, %33, 1, 1, 1, 1, 0;"
        : D4(+, 0), D4(+, 4), D4(+, 8), D4(+, 12), D4(+, 16), D4(+, 20), D4(+, 24), D4(+, 28) : "l"(da), "l"(db));
    else asm volatile("wgmma.mma_async.sync.aligned.m64n64k16.f32.bf16.bf16 "
        "{%0,%1,%2,%3,%4,%5,%6,%7,%8,%9,%10,%11,%12,%13,%14,%15,%16,%17,%18,%19,%20,%21,%22,%23,%24,%25,%26,%27,%28,%29,%30,%31}, "
        "%32, %33, 0, 1, 1, 1, 0;"
        : D4(=, 0), D4(=, 4), D4(=, 8), D4(=, 12), D4(=, 16), D4(=, 20), D4(=, 24), D4(=, 28) : "l"(da), "l"(db));
}

#define G_ROWS 514
__device__ uint4 g_G[64 * G_ROWS * 8];
__device__ uint4 g_GN[64 * 8];
__device__ uint4 g_WN[1152];
#define FS_F2 196608
#define FS_TB (FS_F2 + 8192)
#define FS_NQ (FS_TB + 16384)
#define FS_BAR (FS_NQ + 128)
#define FS_NY (FS_NQ + 1024 + 128)
#define FS_TOTAL (FS_NQ + 3072)
#define F_THREADS 512

DEVI uint32_t cis(int j) {
    const float a = fmaf(__uint_as_float((((j + 1024) << 12) & 0x7FF000) | 0x3F800000), 6.283185307179586f, -9.42477796076938f);
    return pack2(__cosf(a), __sinf(a));
}
DEVI uint32_t cos2(int j0, int j1) {
    const float f = 6.283185307179586f / 2048.f;
    return pack2(__cosf((float)(((j0 + 1024) & 2047) - 1024) * f), __cosf((float)(((j1 + 1024) & 2047) - 1024) * f));
}
DEVI void twid(int j, float& c, float& s) {
    const float a = (float)(((j + 512) & 1023) - 512) * (6.283185307179586f / 1024.f);
    c = __cosf(a) * (1.f / 1024.f);
    s = __sinf(a) * (1.f / 1024.f);
}
template <bool B> struct Bool { static constexpr bool v = B; };
DEVI uint32_t opq(uint32_t& x, uint32_t zero) { OPQ(x); return x; }
DEVI uint32_t tidx() { uint32_t r; asm volatile("mov.u32 %0, %%tid.x;" : "=r"(r)); return r; }
DEVI void tma4d(uint32_t dst, const CUtensorMap* tm, uint32_t bar, int c0, int c1, int c2, int c3) {
    asm volatile("cp.async.bulk.tensor.4d.shared::cluster.global.mbarrier::complete_tx::bytes [%0], [%1, {%3, %4, %5, %6}], [%2];"
                 ::"r"(dst), "l"(tm), "r"(bar), "r"(c0), "r"(c1), "r"(c2), "r"(c3) : "memory");
}
DEVI void tma3s(const CUtensorMap* tm, uint32_t src, int c0, int c1, int c2) {
    asm volatile("cp.async.bulk.tensor.3d.global.shared::cta.bulk_group [%0, {%2, %3, %4}], [%1];" ::"l"(tm), "r"(src), "r"(c0), "r"(c1), "r"(c2) : "memory");
}
DEVI void tma4s(const CUtensorMap* tm, uint32_t src, int c0, int c1, int c2, int c3) {
    asm volatile("cp.async.bulk.tensor.4d.global.shared::cta.bulk_group [%0, {%2, %3, %4, %5}], [%1];"
                 ::"l"(tm), "r"(src), "r"(c0), "r"(c1), "r"(c2), "r"(c3) : "memory");
}
DEVI void bulk_commit() { asm volatile("cp.async.bulk.commit_group;" ::: "memory"); }
DEVI void fence_async() { asm volatile("fence.proxy.async;" ::: "memory"); }
DEVI void fence_smem() { asm volatile("fence.proxy.async.shared::cta;" ::: "memory"); }
DEVI void wgbar(uint32_t q) { asm volatile("bar.sync %0, 128;" ::"r"(q + 2) : "memory"); }
DEVI void grid_arrive(uint32_t* c, uint32_t n) { asm volatile("fence.proxy.async;\nred.release.gpu.global.inc.u32 [%0], %1;" ::"l"(c), "r"(n - 1) : "memory"); }
DEVI void grid_wait(uint32_t* c) {
    uint32_t v;
    int it = 0;
    do {
        asm volatile("ld.acquire.gpu.global.u32 %0, [%1];" : "=r"(v) : "l"(c) : "memory");
        if (++it > (1 << 22)) die(it);
    } while (v);
    fence_async();
}

template <bool INV, class S1, class S2>
DEVI void fft_rows(uint32_t grp, uint32_t q, const uint32_t (&F)[2][4], const float (&tc)[8], const float (&ts)[8], uint32_t so, float fx, uint32_t nq,
                   S1 sh1, S2 sh2) {
    float d[64];
    const uint64_t db = INV ? mkdesc(grp, 1024, 2048) : (mkdesc(grp, 2048, 512) ^ ((uint64_t)3 << 62));
    wg_fence();
    wg_rs128t<0>(d, F[0], db);
    wg_rs128t<1>(d, F[1], db + (INV ? 256 : 64));
    wg_commit();
    SF();
    sh1();
    float4 ny;
    if (INV) ny = lds128f(nq);
    wg_wait<0>();
    if (INV) { d[0] = fmaf(fx, ny.x, d[0]); d[16] = fmaf(fx, ny.y, d[16]); d[32] = fmaf(fx, ny.z, d[32]); d[48] = fmaf(fx, ny.w, d[48]); }
    uint32_t a[2][4][4];
    float e[2][INV ? 16 : 20];
    const uint64_t df = mkdesc(SB0 + FS_F2, 16, 1024);
#pragma unroll
    for (int s = 0; s < 2; s++) {
#pragma unroll
        for (int i = 0; i < 4; i++)
#pragma unroll
            for (int h = 0; h < 2; h++) {
                const float* x = d + (2 * s + h) * 16 + i * 4;
                a[s][i][h] = pack2(fmaf(x[2], ts[2 * i], x[0] * tc[2 * i]), fmaf(x[3], ts[2 * i + 1], x[1] * tc[2 * i + 1]));
                a[s][i][h + 2] = pack2(fmaf(-x[0], ts[2 * i], x[2] * tc[2 * i]), fmaf(-x[1], ts[2 * i + 1], x[3] * tc[2 * i + 1]));
            }
        wg_fence();
#pragma unroll
        for (int i = 0; i < 4; i++) {
            if constexpr (INV) { if (i == 0) wg_rs32<0>(e[s], a[s][i], df); else wg_rs32<1>(e[s], a[s][i], df + i * 2); }
            else { if (i == 0) wg_rs40<0>(e[s], a[s][i], df); else wg_rs40<1>(e[s], a[s][i], df + i * 2); }
        }
        wg_commit();
    }
    SF();
    sh2();
#pragma unroll
    for (int s = 0; s < 2; s++) {
        if (s == 0) wg_wait<1>(); else wg_wait<0>();
        float* x = e[s];
        if constexpr (!INV) {
            x[0] *= fx; x[1] *= fx; x[2] *= fx; x[3] *= fx;
            if (fx != 1.f) sts64(nq + s * 8, pack2(x[16], 0.f), pack2(x[18], 0.f));
        }
        const uint32_t o = grp + (INV ? so + s * 4096 : so ^ (s * 576));
#pragma unroll
        for (int b = 0; b < 2; b++)
            stsm4t(o + b * (INV ? 1024 : 4096), pack2(x[8 * b], x[8 * b + 1]), pack2(x[8 * b + 2], x[8 * b + 3]), pack2(x[8 * b + 4], x[8 * b + 5]),
                   pack2(x[8 * b + 6], x[8 * b + 7]));
    }
}

template <bool INV>
DEVI void fft_gen(uint32_t a, uint32_t n2) {
    const uint32_t tid = tidx(), x = ((tid >> 4) & 24) + (tid & 3), o = (tid & 4) * 128;
    if (INV) {
        const uint32_t r = (tid & 64) * 16 + (tid & 16) * 32 + (tid & 40) * 8 + n2;
        sts128(a + tid * 16, cis(o - r * x), cis(o - (r + 128) * x), cis(o - r * (x + 4)), cis(o - (r + 128) * (x + 4)));
    } else {
        const uint32_t r = 64 * x + n2, k = ((tid >> 2) & 24) + ((tid >> 3) & 3);
        sts128(a + tid * 16, cis(r * k + o), cis(r * (k + 4) + o), cis((r + 256) * k + o), cis((r + 256) * (k + 4) + o));
    }
}
template <bool INV, class S1>
DEVI void fft_cross(uint32_t buf, uint32_t q, uint32_t fa, uint32_t so, uint32_t nq, float (&n)[4], S1 sh1) {
    uint32_t F[4][4];
#pragma unroll
    for (int s = 0; s < 4; s++) { const uint4 v = lds128(fa + s * 2048); F[s][0] = v.x; F[s][1] = v.y; F[s][2] = v.z; F[s][3] = v.w; }
    float d[64];
    const uint64_t db = mkdesc(buf + q * 2048, 1024, 8192), dn = mkdesc(nq, 16, 1024);
    wg_fence();
#pragma unroll
    for (int s = 0; s < 4; s++) { if (s == 0) wg_rs128t<0>(d, F[s], db); else wg_rs128t<1>(d, F[s], db + s * 1024); }
#pragma unroll
    for (int s = 0; s < 4; s++) { if (s == 0) wg_rs8<0>(n, F[s], dn); else wg_rs8<1>(n, F[s], dn + s * 2); }
    wg_commit();
    SF();
    sh1();
    wg_wait<0>();
#pragma unroll
    for (int b = 0; b < 8; b++) {
        const uint32_t o = INV ? so ^ ((b >> 1) * 288 ^ (b & 1) * 32) : (so ^ ((b & 3) * 32)) + (b >> 2) * 1024;
        stsm4(buf + o, pack2(d[8 * b], d[8 * b + 1]), pack2(d[8 * b + 2], d[8 * b + 3]), pack2(d[8 * b + 4], d[8 * b + 5]), pack2(d[8 * b + 6], d[8 * b + 7]));
    }
}

template <bool ODD>
DEVI void fft_filter(uint32_t aw, const float (&e)[32], const float (&o)[32], uint32_t (&u)[4][4], uint32_t (&v)[4][4]) {
#pragma unroll
    for (int s = 0; s < 4; s++) {
        float y[2][2][4];
#pragma unroll
        for (int c = 0; c < 2; c++) {
            float f[4][2];
#pragma unroll
            for (int i = 0; i < 4; i++) {
                const uint32_t a = aw + (i * 32 + s * 8 + c) * 144, x = lds32(a);
                f[i][0] = ODD ? hi_f(x) : lo_f(x);
                f[i][1] = ODD ? lo_f(lds32(a + 4)) : hi_f(x);
            }
#pragma unroll
            for (int h = 0; h < 2; h++) {
                const int x = 8 * s + 2 * h + c;
                const float ar = e[x] + o[x], ai = e[x + 4] + o[x + 4], br = e[x] - o[x], bi = e[x + 4] - o[x + 4];
                const float yr = fmaf(-ai, f[2][h], ar * f[0][h]), yi = fmaf(ar, f[2][h], ai * f[0][h]);
                y[h][c][0] = fmaf(-bi, f[3][h], fmaf(br, f[1][h], yr));
                y[h][c][1] = fmaf(br, f[3][h], fmaf(bi, f[1][h], yi));
                y[h][c][2] = fmaf(2.f, yr, -y[h][c][0]);
                y[h][c][3] = fmaf(2.f, yi, -y[h][c][1]);
            }
        }
#pragma unroll
        for (int h = 0; h < 2; h++) {
            u[s][h] = pack2(y[h][0][0], y[h][1][0]); u[s][h + 2] = pack2(y[h][0][1], y[h][1][1]);
            v[s][h] = pack2(y[h][0][2], y[h][1][2]); v[s][h + 2] = pack2(y[h][0][3], y[h][1][3]);
        }
    }
}

__global__ void __launch_bounds__(F_THREADS, 1)
post_kernel(const __grid_constant__ CUtensorMap tmx, const __grid_constant__ CUtensorMap tmg1, const __grid_constant__ CUtensorMap tmg2,
           const __grid_constant__ CUtensorMap tmwr, const __grid_constant__ CUtensorMap tmwi, const __grid_constant__ CUtensorMap tmy,
           const bf16* __restrict__ wr, const bf16* __restrict__ wi, uint32_t* cnt, uint32_t zero, int nw) {
    extern __shared__ __align__(1024) uint8_t smem[];
    const uint32_t sb = SB0;
    if (smem_u32(smem) != sb) die(1 << 23);
    const uint32_t tid = threadIdx.x, lane = tid & 31, g = lane >> 2, t = lane & 3, j8 = lane & 7, mat = lane >> 3;
    const uint32_t wi_ = __reduce_max_sync(0xFFFFFFFFu, tid >> 5), q = wi_ >> 2, w = wi_ & 3;
    const int cta = blockIdx.x;
    const int nt = cta < 64 ? (64 - cta + nw - 1) / nw : 0;
    const uint32_t bar = sb + FS_BAR;
    if (tid == 0) {
        for (int i = 0; i < 30; i++) mbar_init(bar + i * 8, i < 3 ? 4 : i < 6 ? 16 : i >= 14 && i < 18 ? 2 : 1);
        asm volatile("fence.mbarrier_init.release.cluster;" ::: "memory");
        fence_smem();
    }
    __syncthreads();
#define FT(n)
    FT(0);
#define N2(p) (2 * ((p) & 31) + ((p) >> 5))
#define WLOAD(tk, part) { \
        const uint32_t wd_ = sb + 131072 + q * 18432 + (part) * 9216, wb_ = bar + 112 + q * 8; \
        mbar_expect(wb_, 9216); \
        if ((tk) < 256) tma3d(wd_, (part) ? &tmwi : &tmwr, wb_, ((tk) & 63) * 64, (tk) >> 6, 0); \
        else asm volatile("cp.async.bulk.shared::cluster.global.mbarrier::complete_tx::bytes [%0], [%1], 9216, [%2];" \
                          ::"r"(wd_), "l"(g_WN + (part) * 576), "r"(wb_) : "memory"); }
#define GROW(tk) ((tk) < 256 ? ((tk) >> 5) * 64 + ((tk) & 7) * 8 + (((tk) >> 3) & 3) * 2 : 512)
#define DLOAD(tk, sl) { mbar_expect(bar + 48 + (sl) * 8, 16384); tma3d(sb + (sl) * 16384, &tmg2, bar + 48 + (sl) * 8, 0, GROW(tk), 0); }
#define IO(c) if (w == 3 && (c) && elect())
#define XLOAD1(i, bb) { const uint32_t xb_ = bar + 144 + (bb) * 32 + q * 8; mbar_expect(xb_, 16384); tma4d(sb + (bb) * 65536 + q * 16384, &tmx, xb_, 0, 0, q * 8, N2(cta + (i) * nw)); }
#define GLOAD3(i, bb) { mbar_expect(bar + (bb) * 8, q ? 16384 : 16512); tma3d(sb + (bb) * 65536 + q * 16384, &tmg1, bar + (bb) * 8, 0, q * 128, cta + (i) * nw); \
        if (q == 0) asm volatile("cp.async.bulk.shared::cluster.global.mbarrier::complete_tx::bytes [%0], [%1], 128, [%2];" \
                                 ::"r"(sb + FS_NQ + (bb) * 1024), "l"(g_GN + (cta + (i) * nw) * 8), "r"(bar + (bb) * 8) : "memory"); }
    for (int i = 0; i < 3; i++) IO(i < nt) XLOAD1(i, i);
    for (uint32_t x = tid; x < 40 * 32; x += 512) {
        const uint32_t n = x >> 5, m2 = mat * 8 + t * 2, ri = g & 1;
        const uint32_t c2 = ((n >> 1) & 1) + ((n >> 3) & 1) * 2 + (n & 4) + (n >> 4) * 8;
        const uint32_t v = cos2(m2 * c2 * 64 + ((n & 1) - ri) * 512, (m2 + 1) * c2 * 64 + ((n & 1) - ri) * 512);
        sts32(sb + FS_F2 + n * 128 + ((g ^ (n & 7)) << 4) + t * 4, n < 32 ? v : n == 32 && ri == 0 ? 0xBF003F00u : 0u);
    }
    float tc[8], ts[8];
    uint32_t F[2][4];
    uint32_t c1 = 16 * (w >> 1) + 2 * g + (w & 1);
#pragma unroll
    for (int i = 0; i < 8; i++) {
        twid(c1 * (8 * (i >> 1) + 2 * t + (i & 1)), tc[i], ts[i]);
        const uint32_t m1 = (i >> 1) * 8 + 2 * t;
        F[i >> 2][i & 3] = cos2(c1 * m1 * 64 + (i & 1) * 512, c1 * (m1 + 1) * 64 + (i & 1) * 512);
    }
    {
        const uint32_t kr = (2 * (mat & 1) + (j8 & 1)) ^ ((j8 >> 2) << 1);
        const uint32_t so1 = ((mat >> 1) + 2 * (j8 >> 2)) * 1024 + kr * 128 + (((((j8 >> 1) & 1) * 4 + w) ^ kr) << 4);
        const uint32_t so2 = (2 * w + (mat & 1)) * 8192 + q * 2048 + j8 * 128 + (((mat >> 1) ^ j8) << 4);
        uint32_t so = so1 << 16 | so2;
        const float fx = (tid & 127) == 0 ? 0.5f : 1.f;
        fft_gen<false>(sb + FS_TB, N2(cta));
        fence_smem();
        bsync<1, 512>();
        FT(1);
        int b = 0, bp = 2, ph = 0;
        if (nt) mwait(bar + 144 + q * 8, 0);
        __syncwarp();
        auto step = [&](auto first, auto last, const int i) {
            const uint32_t p = cta + i * nw, bn = 3 - b - bp, tb = (i & 1) * 8192;
            const uint32_t grp = sb + b * 65536 + q * 16384, nq = sb + FS_NQ + b * 1024 + q * 32;
            auto sa = [&]() {
                if constexpr (!decltype(first)::v) {
                    fence_smem();
                    __syncwarp();
                    if (elect()) mbar_arrive(bar + 24);
                }
                IO(i > 1) {
                    mwait(bar + 32, i & 1);
                    tma3s(&tmg1, sb + bn * 65536 + q * 16384, 0, q * 128, p - 2 * nw);
                    bulk_commit();
                }
            };
            auto sb_ = [&]() { if constexpr (!decltype(first)::v) mwait(bar + 24, (i - 1) & 1); };
            if constexpr (!decltype(last)::v) fft_rows<false>(grp, q, F, tc, ts, opq(so, zero) >> 16, fx, nq, sa, sb_);
            else { sa(); __syncwarp(); sb_(); __syncwarp(); }
            if constexpr (!decltype(first)::v) {
                float n[4];
                fft_cross<false>(sb + bp * 65536, q, sb + FS_TB + 8192 - tb + (((tidx() & 127) ^ (q & 1)) << 4), opq(so, zero) & 0xFFFF, sb + FS_NQ + bp * 1024, n, [&]() {
                    fft_gen<false>(sb + FS_TB + tb, N2(p));
                    IO(i >= 2 && i + 1 < nt) {
                        asm volatile("cp.async.bulk.wait_group.read 0;" ::: "memory");
                        XLOAD1(i + 1, bn);
                    }
                });
                if (q == 0) {
                    const uint32_t x = tidx();
                    bf16* z = (bf16*)(g_G + ((p - nw) * G_ROWS + 512) * 8) + (x & 4) * 16 + ((x >> 2) & 24) + ((x >> 3) & 3);
                    asm volatile("{\n.reg .pred p;\n.reg .b16 a, b;\nsetp.eq.u32 p, %2, 0;\nmov.b32 {a, b}, %1;\n@p st.global.u16 [%0], a;\n@p st.global.u16 [%0+8], b;\n}"
                                 ::"l"(z), "r"(pack2(n[0], n[2])), "r"(x & 3) : "memory");
                }
            }
            if constexpr (!decltype(last)::v) {
                fft_rows<false>(grp + 8192, q, F, tc, ts, opq(so, zero) >> 16, fx, nq + 16, [&]() {
                    if constexpr (!decltype(first)::v) {
                        fence_smem();
                        __syncwarp();
                        if (elect()) mbar_arrive(bar + 32);
                    }
                    if ((w == 1 || w == 2) && elect())
                        asm volatile("cp.async.bulk.prefetch.L2.global [%0], 8208;" ::"l"((w == 1 ? wr : wi) + (p * 4 + q) * 4104) : "memory");
                }, [&]() { if (i + 1 < nt) mwait(bar + 144 + bn * 32 + q * 8, bn ? ph : ph ^ 1); });
                bp = b;
                if (++b == 3) { b = 0; ph ^= 1; }
            }
        };
        if (nt) {
            step(Bool<true>(), Bool<false>(), 0);
#pragma unroll 1
            for (int i = 1; i < nt; i++) step(Bool<false>(), Bool<false>(), i);
            step(Bool<false>(), Bool<true>(), nt);
        }
        for (uint32_t x = cta * 512 + tid; x < 4096; x += nw * 512)
            ((bf16*)g_WN)[(x >> 5) * 72 + (x & 16) + (x & 7) * 2 + ((x >> 3) & 1)] = (x < 2048 ? wr : wi)[(x & 2047) * 513 + 512];
        FT(2);
        fence_async();
        bsync<1, 512>();
        IO(nt) { tma3s(&tmg1, sb + bp * 65536 + q * 16384, 0, q * 128, cta + (nt - 1) * nw); bulk_commit(); }
    }
    for (uint32_t x = tid; x < 128 * 32; x += 512) {
        const uint32_t n = (x >> 5) & 63, a = x & 31, k2 = (n >> 4) * 8 + (n & 7);
        sts32(sb + FS_TB + (x >> 5) * 128 + (((a >> 2) ^ (n & 7)) << 4) + (a & 3) * 4, cis((2 * a + (x >> 11)) * k2 * 32 + (n & 8) * 64));
    }
    fence_smem();
    bsync<1, 512>();
    IO(true) {
        asm volatile("cp.async.bulk.wait_group 0;" ::: "memory");
        grid_arrive(cnt, 4 * nw);
        grid_wait(cnt);
        const int tk = cta + q * nw;
        if (tk <= 256) { DLOAD(tk, q); WLOAD(tk, 0); WLOAD(tk, 1); }
    }
    __syncwarp();
    {
        const uint32_t lo = j8 * 128 + (((2 * w + (mat & 1)) ^ j8) << 4);
        const uint32_t aw = sb + 131072 + q * 18432 + t * 288 + w * 32 + g * 4;
        const uint64_t df = mkdesc(sb + FS_TB, 16, 1024);
        const uint64_t da = mkdesc(sb + q * 16384, 16, 1024);
        const uint32_t buf = sb + 65536 + q * 16384;
        int i = 0, tk = cta + q * nw;
        if (tk <= 256) mwait(bar + 48 + q * 8, 0);
        FT(3);
#pragma unroll 1
        for (; tk <= 256; tk += 4 * nw, i++) {
            const bool more = tk + 4 * nw <= 256;
            float e[32], o[32];
            wg_fence();
#pragma unroll
            for (int s = 0; s < 4; s++) { if (s == 0) wg_ss64a<0>(e, da, df); else wg_ss64a<1>(e, da + s * 128, df + s * 2); }
#pragma unroll
            for (int s = 0; s < 4; s++) { if (s == 0) wg_ss64a<0>(o, da + 512, df + 512); else wg_ss64a<1>(o, da + 512 + s * 128, df + 512 + s * 2); }
            wg_commit();
            SF();
            if (i > 0) {
                fence_smem();
                wgbar(q);
                IO(true) { tma3s(&tmg2, buf, 0, GROW(tk - 4 * nw), 0); bulk_commit(); }
            }
            if (w == 2 && more && elect()) mbar_expect(bar + 48 + q * 8, 16384);
            const int gr = GROW(tk + 4 * nw);
            mwait(bar + 112 + q * 8, i & 1);
            wg_wait<0>();
            if (w == 2 && more && elect()) tma3d(sb + q * 16384, &tmg2, bar + 48 + q * 8, 0, gr, 0);
            uint32_t u[4][4], v[4][4];
            if (tk & 8) fft_filter<true>(aw + (tk & 48) / 4, e, o, u, v);
            else fft_filter<false>(aw + (tk & 48) / 4, e, o, u, v);
            wg_fence();
#pragma unroll
            for (int s = 0; s < 4; s++) { if (s == 0) wg_rs64t<0>(e, u[s], df); else wg_rs64t<1>(e, u[s], df + s * 128); }
#pragma unroll
            for (int s = 0; s < 4; s++) { if (s == 0) wg_rs64t<0>(o, v[s], df + 512); else wg_rs64t<1>(o, v[s], df + 512 + s * 128); }
            wg_commit();
            SF();
            IO(true) asm volatile("cp.async.bulk.wait_group.read 0;" ::: "memory");
            wgbar(q);
            if (more) {
                if ((w == 1 || w == 2) && elect()) WLOAD(tk + 4 * nw, w - 1);
                mwait(bar + 48 + q * 8, (i + 1) & 1);
            }
            wg_wait<0>();
#pragma unroll
            for (int s = 0; s < 4; s++) {
                const uint32_t a = buf + (mat >> 1) * 1024 + lo + s * 2048;
                stsm4t(a, pack2(e[8 * s], e[8 * s + 1]), pack2(e[8 * s + 2], e[8 * s + 3]), pack2(e[8 * s + 4], e[8 * s + 5]), pack2(e[8 * s + 6], e[8 * s + 7]));
                stsm4t(a + 8192, pack2(o[8 * s], o[8 * s + 1]), pack2(o[8 * s + 2], o[8 * s + 3]), pack2(o[8 * s + 4], o[8 * s + 5]), pack2(o[8 * s + 6], o[8 * s + 7]));
            }
            if (tk == 256 && w < 2) {
                uint32_t* z = (uint32_t*)g_GN + t * 32 + w * 16 + g;
#pragma unroll
                for (int s = 0; s < 16; s++) {
                    z[(s >> 1) * 128 + (s & 1) * 8] = pack2(e[2 * s], e[2 * s + 1]);
                    z[(s >> 1) * 128 + (s & 1) * 8 + 1024] = pack2(o[2 * s], o[2 * s + 1]);
                }
                fence_async();
            }
        }
        fence_smem();
        wgbar(q);
        IO(true) {
            if (i > 0) { tma3s(&tmg2, buf, 0, GROW(tk - 4 * nw), 0); bulk_commit(); }
            asm volatile("cp.async.bulk.wait_group 0;" ::: "memory");
            grid_arrive(cnt + 1, 4 * nw);
        }
    }
    FT(4);
    bsync<1, 512>();
    {
        for (uint32_t n = wi_; n < 32; n += 16) {
            const uint32_t cl = (mat >> 1) * 16 + t * 4 + (mat & 1), mh = ((n >> 3) & 1) + (n & 7) * 2 + (n & 16);
            sts32(sb + FS_F2 + n * 128 + ((g ^ (n & 7)) << 4) + t * 4, cos2(cl * mh * 64 + (g & 1) * 512, (cl + 2) * mh * 64 + (g & 1) * 512));
        }
        fence_smem();
        c1 = 8 * w + g;
#pragma unroll
        for (int i = 0; i < 8; i++) {
            twid(-c1 * (16 * (i >> 2) + 4 * t + 2 * (i & 1) + ((i >> 1) & 1)), tc[i], ts[i]);
            F[i >> 2][i & 3] = cis((i & 1) * 512 - c1 * ((i >> 1) * 4 + (t ^ (q & 1))) * 64);
        }
        const uint32_t kr = (j8 & 1) ^ ((j8 >> 2) << 1);
        const uint32_t so2 = ((w >> 1) * 4 + (j8 >> 2) * 2 + (w & 1)) * 8192 + (2 * q + (mat & 1)) * 1024 + kr * 128 + (((((j8 >> 1) & 1) * 4 + (mat >> 1)) ^ kr) << 4);
        const uint32_t so1 = (mat & 1) * 2048 + j8 * 128 + ((((mat >> 1) * 4 + w) ^ j8) << 4);
        uint32_t so = so1 << 16 | so2;
        const float fx = t ? 0.f : (g & 1) ? -1.f : 1.f;
        fft_gen<true>(sb + FS_TB, N2(cta));
        bsync<1, 512>();
        IO(true) grid_wait(cnt + 1);
        for (int i = 0; i < 3; i++) IO(i < nt) GLOAD3(i, i);
        __syncwarp();
        int b = 0, bp = 2, ph = 0;
        auto step = [&](auto first, auto last, const int i) {
            const uint32_t p = cta + i * nw, bn = 3 - b - bp, tb = (i & 1) * 8192;
            const uint32_t grp = sb + bp * 65536 + q * 16384, ny = sb + FS_NY + bp * 128 + q * 32;
            auto sb_ = [&]() { if constexpr (!decltype(last)::v) mwait(bar + b * 8, ph); };
            if constexpr (!decltype(first)::v) {
                fft_rows<true>(grp, q, F, tc, ts, opq(so, zero) >> 16, fx, ny, [&]() {
                    if (i > 1) {
                        fence_smem();
                        wgbar(q);
                        IO(true) { tma4s(&tmy, sb + bn * 65536 + q * 16384, 0, 0, q * 8, N2(p - 2 * nw)); bulk_commit(); }
                    }
                }, sb_);
            } else { sb_(); __syncwarp(); }
            if constexpr (decltype(first)::v) FT(5);
            if constexpr (!decltype(last)::v) {
                float n[4];
                fft_cross<true>(sb + b * 65536, q, sb + FS_TB + tb + (tidx() & 127) * 16, opq(so, zero) & 0xFFFF, sb + FS_NQ + b * 1024, n, [&]() {
                    fft_gen<true>(sb + FS_TB + 8192 - tb, N2(p + nw));
                    IO(i >= 2 && i + 1 < nt) {
                        asm volatile("cp.async.bulk.wait_group.read 0;" ::: "memory");
                        GLOAD3(i + 1, bn);
                    }
                });
                if (q == 0) {
                    const uint32_t x = tidx(), a = sb + FS_NY + b * 128 + (x & 64) + (x & 16) * 2 + ((x & 40) >> 1);
                    if ((x & 7) == 0) { sts32f(a, n[0]); sts32f(a + 8, n[2]); }
                }
            }
            auto sc = [&]() {
                if constexpr (!decltype(last)::v) {
                    fence_smem();
                    __syncwarp();
                    if (elect()) mbar_arrive(bar + 24);
                }
            };
            auto sd = [&]() { if constexpr (!decltype(last)::v) mwait(bar + 24, (nt + i) & 1); };
            if constexpr (!decltype(first)::v) fft_rows<true>(grp + 8192, q, F, tc, ts, opq(so, zero) >> 16, fx, ny + 16, sc, sd);
            else { sc(); __syncwarp(); sd(); __syncwarp(); }
            if constexpr (!decltype(last)::v) {
                bp = b;
                if (++b == 3) { b = 0; ph ^= 1; }
            }
        };
        if (nt) {
            step(Bool<true>(), Bool<false>(), 0);
#pragma unroll 1
            for (int i = 1; i < nt; i++) step(Bool<false>(), Bool<false>(), i);
            step(Bool<false>(), Bool<true>(), nt);
        }
        fence_smem();
        wgbar(q);
        IO(nt) { tma4s(&tmy, sb + bp * 65536 + q * 16384, 0, 0, q * 8, N2(cta + (nt - 1) * nw)); bulk_commit(); }
        FT(6);
        IO(true) asm volatile("cp.async.bulk.wait_group 0;" ::: "memory");
    }
}

typedef CUresult (*EncodeFn)(CUtensorMap*, CUtensorMapDataType, cuuint32_t, void*, const cuuint64_t*, const cuuint64_t*,
                             const cuuint32_t*, const cuuint32_t*, CUtensorMapInterleave, CUtensorMapSwizzle,
                             CUtensorMapL2promotion, CUtensorMapFloatOOBfill);

static void make_map(EncodeFn enc, CUtensorMap* m, const void* ptr, int rank, const cuuint64_t* dims, const cuuint64_t* strides,
                     const cuuint32_t* box, CUtensorMapSwizzle sw = CU_TENSOR_MAP_SWIZZLE_128B) {
    cuuint32_t es[4] = {1, 1, 1, 1};
    CUresult r = enc(m, CU_TENSOR_MAP_DATA_TYPE_BFLOAT16, rank, (void*)ptr, dims, strides, box, es, CU_TENSOR_MAP_INTERLEAVE_NONE,
                     sw, CU_TENSOR_MAP_L2_PROMOTION_L2_256B, CU_TENSOR_MAP_FLOAT_OOB_FILL_NONE);
    if (r != CUDA_SUCCESS) fprintf(stderr, "tensor map encode failed: %d\n", (int)r);
}

extern "C" void kernel_launch(void* const* d_in, const int* in_sizes, int n_in, void* d_out, int out_size) {
    const bf16* A_x = (const bf16*)d_in[0];
    const bf16* A_mem0 = (const bf16*)d_in[1];
    const bf16* A_Wq = (const bf16*)d_in[2];
    const bf16* A_Wk = (const bf16*)d_in[3];
    const bf16* A_Wv = (const bf16*)d_in[4];
    const bf16* A_Wo = (const bf16*)d_in[5];
    const bf16* B_x = (const bf16*)d_in[7];
    const bf16* B_wr = (const bf16*)d_in[8];
    const bf16* B_wi = (const bf16*)d_in[9];
    bf16* out = (bf16*)d_out;

    static EncodeFn enc = nullptr;
    static void *pxs = nullptr, *pg = nullptr;
    static int ncl = 64;
    if (!enc) {
        cudaDriverEntryPointQueryResult qr;
        void* fn = nullptr;
        cudaGetDriverEntryPoint("cuTensorMapEncodeTiled", &fn, cudaEnableDefault, &qr);
        enc = (EncodeFn)fn;
        cudaFuncSetAttribute(chain_kernel, cudaFuncAttributeMaxDynamicSharedMemorySize, SM_TOTAL);
        cudaFuncSetAttribute(post_kernel, cudaFuncAttributeMaxDynamicSharedMemorySize, FS_TOTAL);
        cudaGetSymbolAddress(&pxs, g_xs);
        cudaGetSymbolAddress(&pg, g_G);
        cudaLaunchConfig_t lc = {};
        cudaLaunchAttribute at;
        at.id = cudaLaunchAttributeClusterDimension;
        at.val.clusterDim.x = 2; at.val.clusterDim.y = 1; at.val.clusterDim.z = 1;
        lc.gridDim = dim3(132); lc.blockDim = dim3(384); lc.dynamicSmemBytes = SM_TOTAL; lc.attrs = &at; lc.numAttrs = 1;
        int nc = 0;
        if (cudaOccupancyMaxActiveClusters(&nc, chain_kernel, &lc) == cudaSuccess && nc > 64) ncl = nc < 66 ? nc : 66;
    }
    CUtensorMap tmq, tmk, tmv, tmo, tmx, tmb, tmy;
    {
        cuuint64_t d[3] = {64, DM, HD / 64}, st[2] = {HD * 2, 128};
        cuuint32_t bx[3] = {64, 64, 2};
        make_map(enc, &tmq, A_Wq, 3, d, st, bx);
        make_map(enc, &tmk, A_Wk, 3, d, st, bx);
        make_map(enc, &tmv, A_Wv, 3, d, st, bx);
    }
    {
        cuuint64_t d[2] = {DM, HD}, st[1] = {DM * 2};
        cuuint32_t bx[2] = {64, 16}, bx1[2] = {64, 128}, bx2[3] = {64, 64, 2};
        make_map(enc, &tmo, A_Wo, 2, d, st, bx1);
        cuuint64_t d2[3] = {64, HD, DM / 64}, st2[2] = {DM * 2, 128}, d3[2] = {DM, SEQ}, st3[1] = {DM * 4};
        make_map(enc, &tmb, A_Wo, 3, d2, st2, bx2);
        make_map(enc, &tmy, out, 2, d3, st3, bx);
    }
    {
        cuuint64_t d[3] = {64, SEQ, DM / 64}, st[2] = {DM * 2, 128};
        cuuint32_t bx[3] = {64, 8, 4};
        make_map(enc, &tmx, A_x, 3, d, st, bx);
    }
    CUtensorMap fx, fg1, fg2, fwr, fwi, fy;
    {
        cuuint64_t d[4] = {32, 32, 32, 64}, st[3] = {64, 64 * DM * 2, DM * 2};
        cuuint32_t bx[4] = {32, 32, 8, 1};
        make_map(enc, &fx, B_x, 4, d, st, bx, CU_TENSOR_MAP_SWIZZLE_64B);
        cuuint64_t d2[4] = {64, 16, 32, 64}, st2[3] = {128, 64 * 4096, 4096};
        cuuint32_t bx2[4] = {64, 16, 8, 1};
        make_map(enc, &fy, out + DM, 4, d2, st2, bx2);
    }
    {
        cuuint64_t d[3] = {64, G_ROWS, 64}, st[2] = {128, G_ROWS * 128};
        cuuint32_t bx[3] = {64, 128, 1}, bx2[3] = {64, 2, 64};
        make_map(enc, &fg1, pg, 3, d, st, bx);
        make_map(enc, &fg2, pg, 3, d, st, bx2);
        cuuint64_t d2[3] = {8 * 513, 4, 64}, st2[2] = {8 * 513 * 2, 32 * 513 * 2};
        cuuint32_t bx3[3] = {72, 1, 64};
        make_map(enc, &fwr, B_wr, 3, d2, st2, bx3, CU_TENSOR_MAP_SWIZZLE_NONE);
        make_map(enc, &fwi, B_wi, 3, d2, st2, bx3, CU_TENSOR_MAP_SWIZZLE_NONE);
    }
    cudaStream_t st = cudaStreamPerThread;
    const uint64_t xs = ((uint64_t)pxs + XS_BYTES - 1) & ~(uint64_t)(XS_BYTES - 1);
    chain_kernel<<<2 * ncl, 384, SM_TOTAL, st>>>(tmq, tmk, tmv, tmo, tmx, tmb, tmy, A_mem0, A_x, (uint32_t)xs, (uint32_t)(xs >> 32), 0u, NSEG, out);
    int nw = ncl == 66 ? 4 : 64;
    cudaLaunchConfig_t lc = {};
    cudaLaunchAttribute at;
    at.id = cudaLaunchAttributeProgrammaticStreamSerialization;
    at.val.programmaticStreamSerializationAllowed = 1;
    lc.gridDim = dim3(nw); lc.blockDim = dim3(F_THREADS); lc.dynamicSmemBytes = FS_TOTAL; lc.stream = st; lc.attrs = &at; lc.numAttrs = 1;
    cudaLaunchKernelEx(&lc, post_kernel, fx, fg1, fg2, fwr, fwi, fy, B_wr, B_wi, (uint32_t*)(xs + XO_TK + 256), 0u, nw);
}
```

```cpp
#include <cuda_runtime.h>
#include <cuda_bf16.h>
#include <cuda.h>
#include <stdint.h>
#include <stdio.h>

typedef __nv_bfloat16 bf16;

#define SEQ 2048
#define DM 1024
#define NH 32
#define DH 128
#define NSEG 64
#define HD (NH * DH)

#define XS_BYTES (32u << 20)
__device__ uint4 g_xs[2 * XS_BYTES / 16];
#define XO_R 0u
#define XO_PB (1u << 18)
#define XO_FL (XO_PB + 32768u)
#define XO_TK (XO_FL + 4096u)
#define XO_CQK (1u << 20)
#define XO_CV (2u << 20)
#define XO_XG (4u << 20)
#define XO_OX (16u << 20)
#define GSYNC(n)
#define PG(n)

#define DEVI __device__ __forceinline__

DEVI void die(int it) { asm volatile("st.shared.u32 [%0], %0;" ::"r"(it) : "memory"); }
DEVI uint32_t smem_u32(const void* p) { return (uint32_t)__cvta_generic_to_shared(p); }
DEVI void mbar_init(uint32_t bar, uint32_t cnt) { asm volatile("mbarrier.init.shared::cta.b64 [%0], %1;" ::"r"(bar), "r"(cnt) : "memory"); }
DEVI void mbar_expect(uint32_t bar, uint32_t bytes) { asm volatile("mbarrier.arrive.expect_tx.shared::cta.b64 _, [%0], %1;" ::"r"(bar), "r"(bytes) : "memory"); }
DEVI void mbar_arrive(uint32_t bar) { asm volatile("mbarrier.arrive.shared::cta.b64 _, [%0];" ::"r"(bar) : "memory"); }
DEVI void mbar_wait(uint32_t bar, uint32_t parity) {
    uint32_t done;
    int it = 0;
    do {
        asm volatile("{\n.reg .pred p;\nmbarrier.try_wait.parity.shared::cta.b64 p, [%1], %2;\nselp.u32 %0, 1, 0, p;\n}\n"
                     : "=r"(done) : "r"(bar), "r"(parity) : "memory");
        if (++it > (1 << 22)) die(it);
    } while (!done);
}
DEVI void tma2d(uint32_t dst, const CUtensorMap* tm, uint32_t bar, int c0, int c1) {
    asm volatile("cp.async.bulk.tensor.2d.shared::cluster.global.mbarrier::complete_tx::bytes [%0], [%1, {%3, %4}], [%2];"
                 ::"r"(dst), "l"(tm), "r"(bar), "r"(c0), "r"(c1) : "memory");
}
DEVI void tma3d(uint32_t dst, const CUtensorMap* tm, uint32_t bar, int c0, int c1, int c2) {
    asm volatile("cp.async.bulk.tensor.3d.shared::cluster.global.mbarrier::complete_tx::bytes [%0], [%1, {%3, %4, %5}], [%2];"
                 ::"r"(dst), "l"(tm), "r"(bar), "r"(c0), "r"(c1), "r"(c2) : "memory");
}
DEVI void bulk_g2s(uint32_t dst, uint32_t lo, uint32_t hi, uint32_t bytes, uint32_t bar) {
    asm volatile("{\n.reg .b64 a;\nmov.b64 a, {%1,%2};\ncp.async.bulk.shared::cluster.global.mbarrier::complete_tx::bytes [%0], [a], %3, [%4];\n}"
                 ::"r"(dst), "r"(lo), "r"(hi), "r"(bytes), "r"(bar) : "memory");
}
DEVI void bulk_s2g(uint32_t lo, uint32_t hi, uint32_t src, uint32_t bytes) {
    asm volatile("{\n.reg .b64 a;\nmov.b64 a, {%0,%1};\ncp.async.bulk.global.shared::cta.bulk_group [a], [%2], %3;\ncp.async.bulk.commit_group;\n}"
                 ::"r"(lo), "r"(hi), "r"(src), "r"(bytes) : "memory");
}
DEVI void bulk_red(uint32_t lo, uint32_t hi, uint32_t src, uint32_t bytes) {
    asm volatile("{\n.reg .b64 a;\nmov.b64 a, {%0,%1};\ncp.reduce.async.bulk.global.shared::cta.bulk_group.add.noftz.bf16 [a], [%2], %3;\ncp.async.bulk.commit_group;\n}"
                 ::"r"(lo), "r"(hi), "r"(src), "r"(bytes) : "memory");
}
DEVI bool elect() {
    uint32_t p;
    asm volatile("{\n.reg .pred P;\nelect.sync _|P, 0xFFFFFFFF;\nselp.u32 %0, 1, 0, P;\n}" : "=r"(p));
    return p != 0;
}
DEVI void ldsm4(uint32_t (&r)[4], uint32_t a) {
    asm volatile("ldmatrix.sync.aligned.m8n8.x4.shared.b16 {%0,%1,%2,%3}, [%4];" : "=r"(r[0]), "=r"(r[1]), "=r"(r[2]), "=r"(r[3]) : "r"(a) : "memory");
}
DEVI void ldsm4t(uint32_t (&r)[4], uint32_t a) {
    asm volatile("ldmatrix.sync.aligned.m8n8.x4.trans.shared.b16 {%0,%1,%2,%3}, [%4];" : "=r"(r[0]), "=r"(r[1]), "=r"(r[2]), "=r"(r[3]) : "r"(a) : "memory");
}
DEVI void ldsm2t(uint32_t (&r)[2], uint32_t a) {
    asm volatile("ldmatrix.sync.aligned.m8n8.x2.trans.shared.b16 {%0,%1}, [%2];" : "=r"(r[0]), "=r"(r[1]) : "r"(a) : "memory");
}
DEVI void ldsm2(uint32_t (&r)[2], uint32_t a) {
    asm volatile("ldmatrix.sync.aligned.m8n8.x2.shared.b16 {%0,%1}, [%2];" : "=r"(r[0]), "=r"(r[1]) : "r"(a) : "memory");
}
DEVI void stsm4t(uint32_t a, uint32_t r0, uint32_t r1, uint32_t r2, uint32_t r3) {
    asm volatile("stmatrix.sync.aligned.m8n8.x4.trans.shared.b16 [%0], {%1,%2,%3,%4};" ::"r"(a), "r"(r0), "r"(r1), "r"(r2), "r"(r3) : "memory");
}
DEVI uint32_t ldsm1(uint32_t a) {
    uint32_t r;
    asm volatile("ldmatrix.sync.aligned.m8n8.x1.shared.b16 {%0}, [%1];" : "=r"(r) : "r"(a) : "memory");
    return r;
}
DEVI void stsm4(uint32_t a, uint32_t r0, uint32_t r1, uint32_t r2, uint32_t r3) {
    asm volatile("stmatrix.sync.aligned.m8n8.x4.shared.b16 [%0], {%1,%2,%3,%4};" ::"r"(a), "r"(r0), "r"(r1), "r"(r2), "r"(r3) : "memory");
}
DEVI void stsm2(uint32_t a, uint32_t r0, uint32_t r1) {
    asm volatile("stmatrix.sync.aligned.m8n8.x2.shared.b16 [%0], {%1,%2};" ::"r"(a), "r"(r0), "r"(r1) : "memory");
}
DEVI uint32_t movm(uint32_t a) {
    uint32_t d;
    asm volatile("movmatrix.sync.aligned.m8n8.trans.b16 %0, %1;" : "=r"(d) : "r"(a));
    return d;
}
DEVI void mma16(float (&d)[4], uint32_t a0, uint32_t a1, uint32_t a2, uint32_t a3, uint32_t b0, uint32_t b1) {
    asm volatile("mma.sync.aligned.m16n8k16.row.col.f32.bf16.bf16.f32 {%0,%1,%2,%3}, {%4,%5,%6,%7}, {%8,%9}, {%0,%1,%2,%3};"
                 : "+f"(d[0]), "+f"(d[1]), "+f"(d[2]), "+f"(d[3]) : "r"(a0), "r"(a1), "r"(a2), "r"(a3), "r"(b0), "r"(b1));
}
DEVI void mma16z(float (&d)[4], uint32_t a0, uint32_t a1, uint32_t a2, uint32_t a3, uint32_t b0, uint32_t b1) {
    asm volatile("mma.sync.aligned.m16n8k16.row.col.f32.bf16.bf16.f32 {%0,%1,%2,%3}, {%4,%5,%6,%7}, {%8,%9}, {%10,%10,%10,%10};"
                 : "=f"(d[0]), "=f"(d[1]), "=f"(d[2]), "=f"(d[3]) : "r"(a0), "r"(a1), "r"(a2), "r"(a3), "r"(b0), "r"(b1), "f"(0.f));
}
DEVI void mma8(float (&d)[4], uint32_t a0, uint32_t a1, uint32_t b0) {
    asm volatile("mma.sync.aligned.m16n8k8.row.col.f32.bf16.bf16.f32 {%0,%1,%2,%3}, {%4,%5}, {%6}, {%0,%1,%2,%3};"
                 : "+f"(d[0]), "+f"(d[1]), "+f"(d[2]), "+f"(d[3]) : "r"(a0), "r"(a1), "r"(b0));
}
DEVI void mma8z(float (&d)[4], uint32_t a0, uint32_t a1, uint32_t b0) {
    asm volatile("mma.sync.aligned.m16n8k8.row.col.f32.bf16.bf16.f32 {%0,%1,%2,%3}, {%4,%5}, {%6}, {%7,%7,%7,%7};"
                 : "=f"(d[0]), "=f"(d[1]), "=f"(d[2]), "=f"(d[3]) : "r"(a0), "r"(a1), "r"(b0), "f"(0.f));
}
DEVI uint32_t pack2(float lo, float hi) {
    uint32_t r;
    asm("cvt.rn.bf16x2.f32 %0, %1, %2;" : "=r"(r) : "f"(hi), "f"(lo));
    return r;
}
DEVI uint32_t hadd2(uint32_t a, uint32_t b) {
    uint32_t r;
    asm("add.rn.bf16x2 %0, %1, %2;" : "=r"(r) : "r"(a), "r"(b));
    return r;
}
DEVI float lo_f(uint32_t x) { return __uint_as_float(x << 16); }
DEVI float hi_f(uint32_t x) { return __uint_as_float(x & 0xFFFF0000u); }
template <uint32_t OFF> DEVI uint4 ldg4(uint32_t lo, uint32_t hi) {
    uint4 v;
    asm volatile("{\n.reg .b64 a;\nmov.b64 a, {%4,%5};\nld.relaxed.gpu.global.v4.u32 {%0,%1,%2,%3}, [a+%6];\n}"
                 : "=r"(v.x), "=r"(v.y), "=r"(v.z), "=r"(v.w) : "r"(lo), "r"(hi), "n"(OFF) : "memory");
    return v;
}
template <uint32_t OFF> DEVI uint2 ldg2(uint32_t lo, uint32_t hi) {
    uint2 v;
    asm volatile("{\n.reg .b64 a;\nmov.b64 a, {%2,%3};\nld.relaxed.gpu.global.v2.u32 {%0,%1}, [a+%4];\n}"
                 : "=r"(v.x), "=r"(v.y) : "r"(lo), "r"(hi), "n"(OFF) : "memory");
    return v;
}
template <uint32_t OFF> DEVI uint32_t ldg1(uint32_t lo, uint32_t hi) {
    uint32_t v;
    asm volatile("{\n.reg .b64 a;\nmov.b64 a, {%1,%2};\nld.relaxed.gpu.global.u32 %0, [a+%3];\n}" : "=r"(v) : "r"(lo), "r"(hi), "n"(OFF) : "memory");
    return v;
}
template <uint32_t OFF> DEVI void stg1(uint32_t lo, uint32_t hi, uint32_t a) {
    asm volatile("{\n.reg .b64 a;\nmov.b64 a, {%0,%1};\nst.relaxed.gpu.global.u32 [a+%3], %2;\n}" ::"r"(lo), "r"(hi), "r"(a), "n"(OFF) : "memory");
}
template <uint32_t OFF> DEVI void stg4(uint32_t lo, uint32_t hi, uint32_t a, uint32_t b, uint32_t c, uint32_t d) {
    asm volatile("{\n.reg .b64 a;\nmov.b64 a, {%0,%1};\nst.relaxed.gpu.global.v4.u32 [a+%6], {%2,%3,%4,%5};\n}"
                 ::"r"(lo), "r"(hi), "r"(a), "r"(b), "r"(c), "r"(d), "n"(OFF) : "memory");
}
template <uint32_t OFF> DEVI void stg2(uint32_t lo, uint32_t hi, uint32_t a, uint32_t b) {
    asm volatile("{\n.reg .b64 a;\nmov.b64 a, {%0,%1};\nst.relaxed.gpu.global.v2.u32 [a+%4], {%2,%3};\n}"
                 ::"r"(lo), "r"(hi), "r"(a), "r"(b), "n"(OFF) : "memory");
}
DEVI uint32_t tagx2(uint32_t a, uint32_t b, uint32_t t) { uint32_t r; asm("lop3.b32 %0, %1, %2, %3, 0x7E;" : "=r"(r) : "r"(a), "r"(b), "r"(t)); return r; }
DEVI uint32_t tagx1(uint32_t a, uint32_t b, uint32_t t) { uint32_t r; asm("lop3.b32 %0, %1, %2, %3, 0xF6;" : "=r"(r) : "r"(a), "r"(b), "r"(t)); return r; }
DEVI uint32_t or3(uint32_t a, uint32_t b, uint32_t c) { uint32_t r; asm("lop3.b32 %0, %1, %2, %3, 0xFE;" : "=r"(r) : "r"(a), "r"(b), "r"(c)); return r; }
DEVI bool any_bad(uint32_t x) { return __any_sync(0xFFFFFFFFu, (x & 1u) != 0); }
DEVI uint32_t settag(uint32_t x, uint32_t tag) { return (x & ~1u) | tag; }
DEVI void sts32f(uint32_t a, float v) { asm volatile("st.shared.f32 [%0], %1;" ::"r"(a), "f"(v) : "memory"); }
DEVI void sts32(uint32_t a, uint32_t v) { asm volatile("st.shared.u32 [%0], %1;" ::"r"(a), "r"(v) : "memory"); }
DEVI void sts16(uint32_t a, uint32_t v) { asm volatile("st.shared.u16 [%0], %1;" ::"r"(a), "h"((unsigned short)v) : "memory"); }
DEVI void sts64(uint32_t a, uint32_t x, uint32_t y) { asm volatile("st.shared.v2.u32 [%0], {%1,%2};" ::"r"(a), "r"(x), "r"(y) : "memory"); }
DEVI void sts128(uint32_t a, uint32_t x, uint32_t y, uint32_t z, uint32_t w) {
    asm volatile("st.shared.v4.u32 [%0], {%1,%2,%3,%4};" ::"r"(a), "r"(x), "r"(y), "r"(z), "r"(w) : "memory");
}
DEVI float4 lds128f(uint32_t a) {
    float4 v;
    asm volatile("ld.shared.v4.f32 {%0,%1,%2,%3}, [%4];" : "=f"(v.x), "=f"(v.y), "=f"(v.z), "=f"(v.w) : "r"(a) : "memory");
    return v;
}
DEVI uint4 lds128(uint32_t a) {
    uint4 v;
    asm volatile("ld.shared.v4.u32 {%0,%1,%2,%3}, [%4];" : "=r"(v.x), "=r"(v.y), "=r"(v.z), "=r"(v.w) : "r"(a) : "memory");
    return v;
}
DEVI uint2 lds64(uint32_t a) {
    uint2 v;
    asm volatile("ld.shared.v2.u32 {%0,%1}, [%2];" : "=r"(v.x), "=r"(v.y) : "r"(a) : "memory");
    return v;
}
DEVI uint32_t lds32(uint32_t a) {
    uint32_t v;
    asm volatile("ld.shared.u32 %0, [%1];" : "=r"(v) : "r"(a) : "memory");
    return v;
}
DEVI float ex2(float x) { float r; asm("ex2.approx.ftz.f32 %0, %1;" : "=f"(r) : "f"(x)); return r; }
DEVI float rcp(float x) { float r; asm("rcp.approx.ftz.f32 %0, %1;" : "=f"(r) : "f"(x)); return r; }
DEVI uint32_t clk() { uint32_t c; asm volatile("mov.u32 %0, %%clock;" : "=r"(c)::"memory"); return c; }

DEVI uint64_t mkdesc(uint32_t addr, uint32_t lbo, uint32_t sbo) {
    return (uint64_t)((addr & 0x3FFFF) >> 4) | ((uint64_t)(lbo >> 4) << 16) | ((uint64_t)(sbo >> 4) << 32) | ((uint64_t)1 << 62);
}
DEVI void wg_fence() { asm volatile("wgmma.fence.sync.aligned;" ::: "memory"); }
DEVI void wg_commit() { asm volatile("wgmma.commit_group.sync.aligned;" ::: "memory"); }
template <int N> DEVI void wg_wait() { asm volatile("wgmma.wait_group.sync.aligned %0;" ::"n"(N) : "memory"); }
template <int SC>
DEVI void wg_rs32(float (&d)[16], const uint32_t (&a)[4], uint64_t db) {
    if (SC) {
        asm volatile("wgmma.mma_async.sync.aligned.m64n32k16.f32.bf16.bf16 "
                     "{%0,%1,%2,%3,%4,%5,%6,%7,%8,%9,%10,%11,%12,%13,%14,%15}, {%16,%17,%18,%19}, %20, 1, 1, 1, 0;"
                     : "+f"(d[0]), "+f"(d[1]), "+f"(d[2]), "+f"(d[3]), "+f"(d[4]), "+f"(d[5]), "+f"(d[6]), "+f"(d[7]),
                       "+f"(d[8]), "+f"(d[9]), "+f"(d[10]), "+f"(d[11]), "+f"(d[12]), "+f"(d[13]), "+f"(d[14]), "+f"(d[15])
                     : "r"(a[0]), "r"(a[1]), "r"(a[2]), "r"(a[3]), "l"(db));
    } else {
        asm volatile("wgmma.mma_async.sync.aligned.m64n32k16.f32.bf16.bf16 "
                     "{%0,%1,%2,%3,%4,%5,%6,%7,%8,%9,%10,%11,%12,%13,%14,%15}, {%16,%17,%18,%19}, %20, 0, 1, 1, 0;"
                     : "=f"(d[0]), "=f"(d[1]), "=f"(d[2]), "=f"(d[3]), "=f"(d[4]), "=f"(d[5]), "=f"(d[6]), "=f"(d[7]),
                       "=f"(d[8]), "=f"(d[9]), "=f"(d[10]), "=f"(d[11]), "=f"(d[12]), "=f"(d[13]), "=f"(d[14]), "=f"(d[15])
                     : "r"(a[0]), "r"(a[1]), "r"(a[2]), "r"(a[3]), "l"(db));
    }
}

#define NA 12
#define NPF 6
#define PF1 2
#define PF2 1
#define PF3 4
#define WPF 2
#define VPF 2
#define VORD 0x01234567
#define VSF 0
#define VMF 0
#define VC 1
#define QP 16
#define W2P 0
#define W3P 1
#define QSP 10
#define VSB 0x105
#define QQP 3
#define CGP 8
#define C0P 9
#define C1P 9
#define PIP 10
#define K0P 2
#define KEP 1
#define KE2 0
#define VTP 0
#define CW 1
#define WV_BOX ((16 - NA) * 2048)
#define WO_BOX 16384
#define SM_WV 0
#define SM_WO (2 * WV_BOX)
#define SM_X (SM_WO + 4 * WO_BOX)
#define SM_XO (SM_X + 32768)
#define SM_MEMT (SM_XO + 12288)
#define SM_OT (SM_MEMT + 4096)
#define SM_VS (SM_OT + 2048)
#define SM_P (SM_VS + 2048)
#define SM_DN (SM_P + 1792)
#define SM_PROF (SM_P + 2048)
#define SM_ST (SM_X + 65536)
#define SM_KV SM_ST
#define SM_SP (SM_KV + 18432)
#define SM_TR (SM_ST + 32768)
#define SM_PI (SM_ST + 65536)
#define SM_BAR (SM_PI + 12288)
#define SM_TOTAL (SM_BAR + 512)
static_assert(NA == 12, "start-up chunks");
static_assert(SM_TOTAL <= 232448, "smem");
#define BAR_XA 32
#define BAR_KV 40
#define BAR_PI 48
#define BAR_RO 64
#define BAR_WF 256
#define BAR_WE 384
#define SM_ROLE (SM_BAR + 72)

#define SPIN_LIMIT (1 << 20)
#define RPOS 26
#define OPOS 3
#define ASF 0
#define KPOS 0
#define CPOS 5
#define DLY_V 260
#define NPRB 2
#define PW 4
#define ZD 0
#define FTM 2
#define XPF 1
#define WOP 2
#define WIN 2
#define EPD 1300
#define ASP 4
#define EPF 0
#define CFAR 1

template <int ID, int N> DEVI void bsync() { asm volatile("bar.sync %0, %1;" ::"n"(ID), "n"(N) : "memory"); }
template <int ID, int N> DEVI void barv() { asm volatile("bar.arrive %0, %1;" ::"n"(ID), "n"(N) : "memory"); }

#define PT(n)
#define PC(n, v)
#define PDUMP()
#define REFRESH() asm volatile("xor.b32 %0, %0, %1;" : "+r"(l16) : "r"(zero))
#define OPQ(x) asm volatile("xor.b32 %0, %0, %1;" : "+r"(x) : "r"(zero))
#define KEEP(x, a, b, c, d) asm volatile("{\n.reg .b32 t;\nlop3.b32 t, %1, %2, %3, 0x80;\nlop3.b32 t, t, %4, %5, 0x80;\nxor.b32 %0, %0, t;\n}" \
                                         : "+r"(x) : "r"(a), "r"(b), "r"(c), "r"(d), "r"(zero))
#define SF() asm volatile("pmevent 1;" ::: "memory")
#define MF() __syncwarp()
#define SB0 1024u

#define XDOFF(ks) ((((ks) >> 2) * 1024 + ((ks) & 3) * 32) >> 4)
template <int SC>
DEVI void wg_ss32t(float (&d)[16], uint64_t da, uint64_t db) {
    if (SC) {
        asm volatile("wgmma.mma_async.sync.aligned.m64n32k16.f32.bf16.bf16 "
                     "{%0,%1,%2,%3,%4,%5,%6,%7,%8,%9,%10,%11,%12,%13,%14,%15}, %16, %17, 1, 1, 1, 1, 0;"
                     : "+f"(d[0]), "+f"(d[1]), "+f"(d[2]), "+f"(d[3]), "+f"(d[4]), "+f"(d[5]), "+f"(d[6]), "+f"(d[7]),
                       "+f"(d[8]), "+f"(d[9]), "+f"(d[10]), "+f"(d[11]), "+f"(d[12]), "+f"(d[13]), "+f"(d[14]), "+f"(d[15])
                     : "l"(da), "l"(db));
    } else {
        asm volatile("wgmma.mma_async.sync.aligned.m64n32k16.f32.bf16.bf16 "
                     "{%0,%1,%2,%3,%4,%5,%6,%7,%8,%9,%10,%11,%12,%13,%14,%15}, %16, %17, 0, 1, 1, 1, 0;"
                     : "=f"(d[0]), "=f"(d[1]), "=f"(d[2]), "=f"(d[3]), "=f"(d[4]), "=f"(d[5]), "=f"(d[6]), "=f"(d[7]),
                       "=f"(d[8]), "=f"(d[9]), "=f"(d[10]), "=f"(d[11]), "=f"(d[12]), "=f"(d[13]), "=f"(d[14]), "=f"(d[15])
                     : "l"(da), "l"(db));
    }
}

DEVI void delay_until(uint32_t t0, uint32_t d) { while (clk() - t0 < d) {} }

#define VR 2
#define CW2 4
template <int I0, int I1>
DEVI void xmma(float (&xa)[16], float (&xb)[16], uint32_t w, int ps, uint32_t zero, const uint32_t (&Wq)[16][4], const uint32_t (&Wk)[16][4],
               const uint32_t (&Wv)[NA][4], const uint32_t (&wv)[16 - NA][4]) {
    const uint64_t xd = mkdesc(SB0 + SM_X, 16, 4096) + (ps & 1) * 1024, vd = mkdesc(SB0 + SM_WV, 8192, 1024);
    uint32_t vo = (w >> 2) * (WV_BOX / 16);
    if (VR ? false : VC == 0 ? I0 < 16 - NA : VC == 1 ? I0 >= 32 && I0 < 48 - NA : I1 > 32 + NA) OPQ(vo);
#pragma unroll
    for (int i = I0; i < I1; i++) {
        if (VC) {
            const int v = (i + (VC == 1 ? NA : 0)) & 15;
            if (i == 0) wg_rs32<0>(xa, Wq[0], xd);
            else if (i < 16) wg_rs32<1>(xa, Wq[i & 15], xd + XDOFF(i & 15));
            else if (i == 16) wg_rs32<0>(xb, Wk[0], xd);
            else if (i < 32) wg_rs32<1>(xb, Wk[i & 15], xd + XDOFF(i & 15));
            else if (i == 32 && v < NA) wg_rs32<0>(xa, Wv[0], xd);
            else if (VR && i == 32) wg_rs32<0>(xa, wv[0], xd + XDOFF(NA));
            else if (VR && v >= NA) wg_rs32<1>(xa, wv[v >= NA ? v - NA : 0], xd + XDOFF(v));
            else if (i == 32) wg_ss32t<0>(xa, (vd & ~0xFFFFFFFFull) | ((uint32_t)vd + vo), xd + XDOFF(NA));
            else if (v < NA) wg_rs32<1>(xa, Wv[v < NA ? v : 0], xd + XDOFF(v));
            else wg_ss32t<1>(xa, (vd & ~0xFFFFFFFFull) | ((uint32_t)vd + (v - NA) * 128 + vo), xd + XDOFF(v));
        } else
        if (i == 0) wg_ss32t<0>(xb, (vd & ~0xFFFFFFFFull) | ((uint32_t)vd + vo), xd + XDOFF(NA));
        else if (i < 16 - NA) wg_ss32t<1>(xb, (vd & ~0xFFFFFFFFull) | ((uint32_t)vd + i * 128 + vo), xd + XDOFF(NA + i));
        else if (i == 16 - NA) wg_rs32<0>(xa, Wq[0], xd);
        else if (i < 32 - NA) wg_rs32<1>(xa, Wq[(i + NA) & 15], xd + XDOFF((i + NA) & 15));
        else if (i < 32) wg_rs32<1>(xb, Wv[(i + NA) & 15], xd + XDOFF((i + NA) & 15));
        else if (i == 32) wg_rs32<0>(xa, Wk[0], xd);
        else wg_rs32<1>(xa, Wk[i & 15], xd + XDOFF(i & 15));
    }
    wg_commit();
}
#define XMMA(I0, I1) xmma<(I0), (I1)>(xa, xb, w, p ^ 1, zero, Wq, Wk, Wv, wv)
DEVI void wg_done(float (&d)[16]) {
    asm volatile("" : "+f"(d[0]), "+f"(d[1]), "+f"(d[2]), "+f"(d[3]), "+f"(d[4]), "+f"(d[5]), "+f"(d[6]), "+f"(d[7]),
                      "+f"(d[8]), "+f"(d[9]), "+f"(d[10]), "+f"(d[11]), "+f"(d[12]), "+f"(d[13]), "+f"(d[14]), "+f"(d[15]) :: "memory");
}
template <int M>
DEVI void xpack(uint32_t (&xp)[8], float (&xa)[16]) {
    wg_done(xa);
#pragma unroll
    for (int i = 0; i < 4; i++) {
        xp[2 * i] = pack2(xa[4 * i], xa[4 * i + (M < 2 ? 2 : 1)]);
        xp[2 * i + 1] = pack2(xa[4 * i + (M < 2 ? 1 : 2)], xa[4 * i + 3]);
    }
}
template <int M>
DEVI uint4 xpeer(uint32_t sb, int ps, uint32_t t16) { return lds128(sb + SM_PI - ((ps & 1) ^ 1) * 12288 + M * 4096 + t16); }
DEVI void xadd(uint32_t (&xp)[8], const uint4& pi) {
    xp[0] = hadd2(xp[0], pi.x); xp[1] = hadd2(xp[1], pi.y); xp[2] = hadd2(xp[2], pi.z); xp[3] = hadd2(xp[3], pi.w);
}
template <int M>
DEVI void xsend(const uint32_t (&xp)[8], uint32_t sb, int ps, uint32_t t16) {
    asm volatile("st.async.weak.shared::cluster.mbarrier::complete_tx::bytes.v4.b32 [%0], {%1,%2,%3,%4}, [%5];"
                 ::"r"((sb ^ 0x1000000) + SM_PI - (ps & 1) * 12288 + M * 4096 + t16), "r"(xp[4]), "r"(xp[5]), "r"(xp[6]), "r"(xp[7]),
                   "r"((sb ^ 0x1000000) + SM_BAR + BAR_PI + (ps & 1) * 8) : "memory");
}
template <int M>
DEVI void xstore(const uint32_t (&xp)[8], uint32_t sb, uint32_t sbw, int ps, uint32_t t16, uint32_t KA) {
    const uint32_t a = SM_XO + M * 2048 + (M < 2 ? (KA & 0xFF) + sbw : (t16 >> 1) + sb);
    sts64(a, xp[0], xp[1]);
    sts64(a + 6144, xp[2], xp[3]);
    xsend<M>(xp, sb, ps, t16);
}
template <int M>
DEVI void xpark(uint32_t (&xp)[8], const uint4& pi, uint32_t sb, uint32_t sbw, int ps, uint32_t t16, uint32_t KA) {
    xadd(xp, pi);
    xstore<M>(xp, sb, sbw, ps, t16, KA);
}
template <uint32_t OFF> DEVI void red2(uint32_t lo, uint32_t hi, uint32_t a, uint32_t b) {
    asm volatile("{\n.reg .b64 a;\nmov.b64 a, {%0,%1};\nred.relaxed.gpu.global.add.noftz.v2.bf16x2 [a+%4], {%2,%3};\n}"
                 ::"r"(lo), "r"(hi), "r"(a), "r"(b), "n"(OFF) : "memory");
}
template <int M, int N>
DEVI void xstart(uint32_t sb, uint32_t w, uint32_t ga, uint32_t xhi, uint32_t j, uint32_t t16, uint32_t KA, const uint32_t (&W)[N][4]) {
    float xa[16], xb[16];
    uint32_t xp[8];
    auto pass = [&](float (&d)[16], int i, int k0, int k1) {
        const uint64_t xd = mkdesc(SB0 + SM_X + (i ? i + 1 : 0) * 16384, 16, 4096), vd = mkdesc(SB0 + SM_WV, 8192, 1024) + (w >> 2) * (WV_BOX / 16);
#pragma unroll
        for (int k = k0; k < k1; k++) {
            if (k == 0) wg_rs32<0>(d, W[0], xd);
            else if (k < N) wg_rs32<1>(d, W[k < N ? k : 0], xd + XDOFF(k));
            else wg_ss32t<1>(d, vd + (k - N) * 128, xd + XDOFF(k));
        }
        wg_commit();
    };
    wg_fence();
    pass(xa, 0, 0, 16);
    pass(xb, 1, 0, ASP);
    if (M == 0) bsync<5, 288>();
    ga += M < 2 ? (KA & 0xFF) + w * 256 : t16 >> 1;
    constexpr uint32_t O = XO_XG + M * 2048, SG = 128 * 6144;
    wg_wait<1>();
    xpack<M>(xp, xa);
    red2<O>(ga, xhi, xp[0], xp[1]); red2<O + 6144>(ga, xhi, xp[2], xp[3]); red2<O + 12288>(ga, xhi, xp[4], xp[5]); red2<O + 18432>(ga, xhi, xp[6], xp[7]);
    if (M == 2) barv<3, 320>();
    wg_fence();
    pass(xb, 1, ASP, 16);
    pass(xa, 2, 0, 16);
    wg_wait<1>();
    xpack<M>(xp, xb);
    red2<O + SG>(ga, xhi, xp[0], xp[1]); red2<O + SG + 6144>(ga, xhi, xp[2], xp[3]);
    red2<O + SG + 12288>(ga, xhi, xp[4], xp[5]); red2<O + SG + 18432>(ga, xhi, xp[6], xp[7]);
    wg_wait<0>();
    xpack<M>(xp, xa);
    red2<O + 2 * SG>(ga + j * 6144, xhi, xp[0], xp[1]);
    red2<O + 2 * SG>(ga + (j ^ 1) * 6144, xhi, xp[2], xp[3]);
    xsend<M>(xp, sb, 0, t16);
}
DEVI void piwait(uint32_t sb, int p, int ps) { mbar_wait(sb + SM_BAR + BAR_PI + p * 8, ((ps + 2) >> 1) & 1); }

DEVI uint32_t par(uint32_t off) { return __popc(off & 0xB2000u) & 1; }
DEVI uint32_t probe(uint32_t lo, uint32_t hi) {
    uint32_t best = 0xFFFFFFFFu, x = 0;
    stg4<0>(lo, hi, 0, 0, 0, 0);
    stg4<16>(lo, hi, 0, 0, 0, 0);
#pragma unroll 1
    for (int r = 0; r < NPRB; r++) {
        const uint32_t t0 = clk();
        asm volatile("{\n.reg .b64 a;\nmov.b64 a, {%1,%2};\natom.relaxed.gpu.global.add.u32 %0, [a], 2;\n}" : "=r"(x) : "r"(lo), "r"(hi) : "memory");
        if (x == 0xFFFFFFFFu) die(1 << 23);
        best = min(best, clk() - t0);
    }
    return best;
}

DEVI void xload(uint32_t sb, uint32_t u, uint32_t j, int ps, const CUtensorMap* tmx) {
    if (elect()) {
        const uint32_t sg = ps + 4 - (u & 1) + (u >> 1);
        mbar_expect(sb + SM_BAR + BAR_XA, sg < NSEG ? 4096 : 0);
        if (sg < NSEG) tma3d(sb + SM_X + (ps & 1) * 16384 + u * 4096, tmx, sb + SM_BAR + BAR_XA, 0, sg * 32 + (j ^ ((u & 1) * 2 + (u >> 1))) * 8, j * 4);
    }
}
DEVI uint32_t rpage(uint32_t j, int s) { return (s & 3) * 65536 + (j & 1) * 8192 + (((s ^ (s >> 1) ^ j ^ (j >> 1)) & 1) << 12); }

#define RLOAD() { m0 = ldg4<XO_R>(a, ah); n0 = ldg4<XO_R + 16384>(a, ah); e0 = ldg1<XO_R + 32768>(e, eh); f0 = ldg1<XO_R + 33792>(e, eh); }
DEVI bool ruse(uint32_t a, const uint4& m0, const uint4& n0, uint32_t e0, uint32_t f0) {
    const uint32_t a0 = hadd2(m0.w, n0.w), b0 = hadd2(e0, f0);
    stsm4(a, hadd2(m0.x, n0.x), hadd2(m0.y, n0.y), hadd2(m0.z, n0.z), __byte_perm(a0, b0, 0x5410));
    return __any_sync(0xFFFFFFFFu, (a0 & b0 & 0x42000000u) != 0x42000000u);
}

#define GST(i) (SM_WO + (i) * 49152)
#define BAR_GF 128
#define BAR_GE (BAR_GF + 64)
#define BAR_GX (BAR_GE + 32)
#define D4(c, i) #c "f"(d[i]), #c "f"(d[i + 1]), #c "f"(d[i + 2]), #c "f"(d[i + 3])
#define D16(c, i) D4(c, i), D4(c, i + 4), D4(c, i + 8), D4(c, i + 12)
DEVI void mwait(uint32_t bar, uint32_t parity) {
    asm volatile("{\n.reg .pred p;\n.reg .b32 c;\nmbarrier.try_wait.parity.shared::cta.b64 p, [%0], %1;\n@p bra.uni D;\nmov.b32 c, 0;\n"
                 "L:\nadd.u32 c, c, 1;\nsetp.gt.u32 p, c, 4194304;\n@p st.shared.u32 [c], c;\n"
                 "mbarrier.try_wait.parity.shared::cta.b64 p, [%0], %1;\n@!p bra.uni L;\nD:\n}" ::"r"(bar), "r"(parity) : "memory");
}
DEVI void wg_ss256t(float (&d)[128], uint64_t da, uint64_t db) {
    asm volatile("wgmma.mma_async.sync.aligned.m64n256k16.f32.bf16.bf16 "
        "{%0,%1,%2,%3,%4,%5,%6,%7,%8,%9,%10,%11,%12,%13,%14,%15,%16,%17,%18,%19,%20,%21,%22,%23,%24,%25,%26,%27,%28,%29,%30,%31,%32,%33,%34,%35,%36,%37,%38,%39,%40,%41,%42,%43,%44,%45,%46,%47,%48,%49,%50,%51,%52,%53,%54,%55,%56,%57,%58,%59,%60,%61,%62,%63,%64,%65,%66,%67,%68,%69,%70,%71,%72,%73,%74,%75,%76,%77,%78,%79,%80,%81,%82,%83,%84,%85,%86,%87,%88,%89,%90,%91,%92,%93,%94,%95,%96,%97,%98,%99,%100,%101,%102,%103,%104,%105,%106,%107,%108,%109,%110,%111,%112,%113,%114,%115,%116,%117,%118,%119,%120,%121,%122,%123,%124,%125,%126,%127}, "
        "%128, %129, 1, 1, 1, 1, 1;"
        : D16(+, 0), D16(+, 16), D16(+, 32), D16(+, 48), D16(+, 64), D16(+, 80), D16(+, 96), D16(+, 112) : "l"(da), "l"(db));
}
template <int O, int KB> DEVI void g_half(float (&d)[64], uint64_t da) {
    const uint64_t db = mkdesc(SB0 + GST(KB & 3) + 16384 + O * 256, 8192, 1024);
#pragma unroll
    for (int k = 0; k < 4; k++)
        asm volatile("wgmma.mma_async.sync.aligned.m64n128k16.f32.bf16.bf16 "
            "{%0,%1,%2,%3,%4,%5,%6,%7,%8,%9,%10,%11,%12,%13,%14,%15,%16,%17,%18,%19,%20,%21,%22,%23,%24,%25,%26,%27,%28,%29,%30,%31,%32,%33,%34,%35,%36,%37,%38,%39,%40,%41,%42,%43,%44,%45,%46,%47,%48,%49,%50,%51,%52,%53,%54,%55,%56,%57,%58,%59,%60,%61,%62,%63}, "
            "%64, %65, 1, 1, 1, 1, 1;"
            : D16(+, 0), D16(+, 16), D16(+, 32), D16(+, 48) : "l"(da + (KB & 3) * 3072 + k * 16), "l"(db + k * 128));
}
DEVI void g_load(uint32_t sb, uint32_t u, uint32_t role, uint32_t kb, uint32_t xlo, uint32_t xhi, const CUtensorMap* tmb) {
    const uint32_t st = kb & 3, bar = sb + SM_BAR + BAR_GF + u * 32 + st * 8, dst = sb + GST(st), k = (role & 1) * 32 + kb;
    if (!elect()) return;
    mbar_expect(bar, u ? 8192 : 40960);
    bulk_g2s(dst + u * 8192, xlo + XO_OX + (k * 16 + (role >> 3)) * 16384 + u * 8192, xhi, 8192, bar);
    if (u == 0) {
        tma3d(dst + 16384, tmb, bar, 0, k * 64, ((role & 7) ^ 1) * 2);
        tma3d(dst + 32768, tmb, bar, 0, k * 64, (role & 7) * 2);
    }
}
DEVI void g_arrive(uint32_t a, uint32_t xhi, uint32_t n) {
    if (elect()) asm volatile("{\n.reg .b64 a;\nmov.b64 a, {%0,%1};\nred.release.gpu.global.inc.u32 [a], %2;\n}" ::"r"(a), "r"(xhi), "r"(n - 1) : "memory");
}
DEVI void g_wait(uint32_t a, uint32_t xhi) {
    int it = 0;
    uint32_t v;
    do {
        asm volatile("{\n.reg .b64 a;\nmov.b64 a, {%1,%2};\nld.acquire.gpu.global.u32 %0, [a];\n}" : "=r"(v) : "r"(a), "r"(xhi) : "memory");
        if (++it > SPIN_LIMIT) die(it);
    } while (__any_sync(0xFFFFFFFFu, v));
    asm volatile("fence.proxy.async.global;" ::: "memory");
}
#define SE 2
#define DLY_S 0
#define VX 1
#define VH 1
#define VD 1
#define SM_VP (SM_TR + 12288)
#define JV(h, j) (VH < 2 ? (j) ^ ((par((h) * 8192) ^ VH) << 1) : (j))
#define SEU 0
#define VA 0
#define VLP 0
#define VCP 1
#define SEED 0
#define VB 0
#define RCP 0
#define XLP 0
#define RE 0
#define DLY_E 300
#define DLY_T 200
#define RDW 0
#define APH 1
#define A0 0
#define A1 0
#define DNP 0
#define WLP 0
#define LDP 0
#define FDL 0
#define KEP0 1
#define VSB0 VSB
#define B3 0
#define GD 400
#define GE 3
#define GH 1
#define GS 1
#define GP 0
DEVI void g_done(float (&d)[64]) { asm volatile("" : D16(+, 0), D16(+, 16), D16(+, 32), D16(+, 48)::"memory"); }
DEVI void g_main(uint32_t sb, uint32_t w, uint32_t role, const CUtensorMap* tmy, void* out) {
    const uint32_t bar = sb + SM_BAR, t16 = threadIdx.x * 16;
    const uint64_t da = (mkdesc(SB0 + GST(0), 128, 1024) & ~((uint64_t)3 << 62)) + (w >> 2) * 512;
    float d[128];
#pragma unroll
    for (int i = 0; i < 128; i++) d[i] = 0.f;
#define GFULL(kb) { mwait(bar + BAR_GF + ((kb) & 3) * 8, ((kb) >> 2) & 1); if (w >= 4) mwait(bar + BAR_GF + 32 + ((kb) & 3) * 8, ((kb) >> 2) & 1); }
#pragma unroll 1
    for (uint32_t kb = 0; kb < (GE ? 28 : 29); kb++) {
        GFULL(kb);
        if (kb == 0 && threadIdx.x == 128) PG(4);
        if (kb == 4 && threadIdx.x == 0) PG(5);
        const uint64_t a = da + (kb & 3) * 3072, b = mkdesc(SB0 + GST(0) + 16384, 8192, 1024) + (kb & 3) * 3072;
        wg_fence();
#pragma unroll
        for (int k = 0; k < 4; k++) wg_ss256t(d, a + k * 16, b + k * 128);
        wg_commit();
        wg_wait<1>();
        if (kb > 0 && elect()) mbar_arrive(bar + BAR_GE + ((kb - 1) & 3) * 8);
    }
    if (GE) { GFULL(28); }
    else { GFULL(29); GFULL(30); GFULL(31); }
    wg_wait<0>();
    if (GE && elect()) mbar_arrive(bar + BAR_GE + 24);
    float x[64], y[64];
#pragma unroll
    for (int i = 0; i < 64; i++) asm volatile("mov.b32 %0, %1;" : "=f"(x[i]) : "f"(d[i]) : "memory");
    SF();
#pragma unroll
    for (int i = 0; i < 64; i++) asm volatile("mov.b32 %0, %1;" : "=f"(y[i]) : "f"(d[i + 64]) : "memory");
    SF();
#define GFREE() if (elect()) asm volatile("mbarrier.arrive.relaxed.cluster.shared::cluster.b64 _, [%0];" ::"r"((bar ^ 0x1000000) + BAR_GX) : "memory")
#define GSW(i) ((i) * 4096 + (GE && (i) >= 4 ? GST(0) : 0))
#define GSEND(i0) _Pragma("unroll") for (int i = (i0); i < (i0) + 4; i++) \
        asm volatile("st.async.weak.shared::cluster.mbarrier::complete_tx::bytes.v4.b32 [%0], {%1,%2,%3,%4}, [%5];" \
                     ::"r"((sb ^ 0x1000000) + GSW(i) + t16), "r"(pack2(x[8 * i], x[8 * i + 1])), "r"(pack2(x[8 * i + 2], x[8 * i + 3])), \
                       "r"(pack2(x[8 * i + 4], x[8 * i + 5])), "r"(pack2(x[8 * i + 6], x[8 * i + 7])), "r"((bar ^ 0x1000000) + BAR_GX + 8) : "memory")
    if (GE) {
        wg_fence();
        g_half<0, 28>(x, da);
        wg_commit();
        GFULL(29);
        wg_fence();
        g_half<0, 29>(x, da);
        wg_commit();
        GFULL(30);
        wg_fence();
        g_half<0, 30>(x, da);
        wg_commit();
        GFULL(31);
        wg_fence();
        g_half<0, 31>(x, da);
        wg_commit();
        g_half<64, 28>(y, da);
        if (GE == 2) g_half<64, 29>(y, da);
        wg_commit();
        wg_wait<1>();
        g_done(x);
        GFREE();
        GSEND(0);
        wg_fence();
        if (GE != 2) g_half<64, 29>(y, da);
        if (GE != 1) g_half<64, 30>(y, da);
        wg_commit();
        mwait(bar + BAR_GX, 0);
        GSEND(4);
        wg_fence();
        if (GE == 1) g_half<64, 30>(y, da);
        g_half<64, 31>(y, da);
        wg_commit();
        mwait(bar + BAR_GX + 8, 0);
        if (threadIdx.x == 0) PG(1);
#pragma unroll
        for (int i = 0; i < 8; i++) {
            const uint4 a = lds128(sb + GSW(i) + t16);
            float* e = x + 8 * i;
            e[0] = lo_f(a.x); e[1] = hi_f(a.x); e[2] = lo_f(a.y); e[3] = hi_f(a.y); e[4] = lo_f(a.z); e[5] = hi_f(a.z); e[6] = lo_f(a.w); e[7] = hi_f(a.w);
        }
        g_done(x);
        SF();
        wg_wait<0>();
        g_done(y);
        if (threadIdx.x == 0) PG(7);
    } else {
        GFREE();
        wg_fence();
        g_half<0, 29>(x, da);
        g_half<0, 30>(x, da);
        g_half<0, 31>(x, da);
        wg_commit();
        g_half<64, 29>(y, da);
        wg_commit();
        wg_wait<1>();
        g_done(x);
        mwait(bar + BAR_GX, 0);
        GSEND(0);
        wg_fence();
        g_half<64, 30>(y, da);
        wg_commit();
        GSEND(4);
        wg_fence();
        g_half<64, 31>(y, da);
        wg_commit();
        wg_wait<0>();
        g_done(y);
        if (threadIdx.x == 0) PG(7);
        mwait(bar + BAR_GX + 8, 0);
        if (threadIdx.x == 0) PG(1);
    }
    const uint32_t lane = threadIdx.x & 31, o = sb + GST(1) + w * 2048;
    char* go = (char*)out + ((role >> 3) * 128 + w * 16 + (lane >> 3)) * 4096 + (role & 7) * 256 + (lane & 7) * 16;
#pragma unroll
    for (int i = 0; i < 8; i++) {
        float* e = y + 8 * i;
        if (GE) {
#pragma unroll
            for (int n = 0; n < 8; n++) e[n] += x[8 * i + n];
        } else {
            const uint4 a = lds128(sb + i * 4096 + t16);
            e[0] += lo_f(a.x); e[1] += hi_f(a.x); e[2] += lo_f(a.y); e[3] += hi_f(a.y); e[4] += lo_f(a.z); e[5] += hi_f(a.z); e[6] += lo_f(a.w); e[7] += hi_f(a.w);
        }
        stsm4(o + (i >> 2) * 49152 + (lane & 15) * 128 + ((((i & 3) * 2 + (lane >> 4)) ^ (lane & 7)) << 4),
              pack2(e[0], e[1]), pack2(e[2], e[3]), pack2(e[4], e[5]), pack2(e[6], e[7]));
        if (i == 3 || i == 7) {
            if (GS) {
                __syncwarp();
#pragma unroll
                for (int m = 0; m < 4; m++)
                    *(uint4*)(go + m * 16384 + (i >> 2) * 128) =
                        lds128(o + (i >> 2) * 49152 + m * 512 + (lane >> 3) * 128 + (((lane & 7) ^ ((m & 1) * 4 + (lane >> 3))) << 4));
            } else {
                asm volatile("fence.proxy.async.shared::cta;" ::: "memory");
                __syncwarp();
                if (elect())
                    asm volatile("cp.async.bulk.tensor.2d.global.shared::cta.bulk_group [%0, {%2, %3}], [%1];\ncp.async.bulk.commit_group;"
                                 ::"l"(tmy), "r"(o + (i >> 2) * 49152), "r"((role & 7) * 128 + (i >> 2) * 64), "r"((role >> 3) * 128 + w * 16) : "memory");
            }
        }
    }
    if (threadIdx.x == 0) PG(6);
    if (!GS) asm volatile("cp.async.bulk.wait_group.read 0;" ::: "memory");
}

DEVI void kvload(uint32_t sb, uint32_t u, uint32_t h, uint32_t j, int sg, uint32_t xlo, uint32_t xhi) {
    const uint32_t o = u == 0 ? 0 : 2048;
    mbar_expect(sb + SM_BAR + BAR_KV, 6144 - o);
    bulk_g2s(sb + SM_KV + u * 4096 + o, xlo + XO_XG + (((sg & 7) * 32 + h) * 4 + ((j + u) & 3)) * 6144 + o, xhi, 6144 - o, sb + SM_BAR + BAR_KV);
}
DEVI void helper_step(uint32_t sb, uint32_t w, uint32_t h, uint32_t j, uint32_t& l16, uint32_t xlo, uint32_t xhi, uint32_t zero, int s,
                      const CUtensorMap* tmx, const CUtensorMap* tmb) {
    const uint32_t u = w - 8, bq = sb + SM_BAR;
    bsync<1, 384>();
    PT(0);
    PDUMP();
    PT(1);
    if (s == NSEG - 2 && u < 2) g_arrive(xlo + XO_TK + 128, xhi, 256);
    uint32_t old = 0;
#define RCLEAR(n) if (RCP == (n) && u > 0 && s + 3 < NSEG) \
        asm volatile("{\n.reg .b64 a;\nmov.b64 a, {%1,%2};\natom.relaxed.gpu.global.exch.b32 %0, [a], 0;\n}" \
                     : "=r"(old) : "r"(xlo + XO_R + rpage(j, s + 2) + (u - 1) * 16384 + h * 128 + (l16 >> 2)), "r"(xhi) : "memory");
    RCLEAR(1);
    const bool gl = u == 0 || (u == 1 && h < 30);
    if (GP == 1 && s == NSEG - 1 && gl) g_load(sb, u, h * 4 + j, 1, xlo, xhi, tmb);
    const uint32_t ctag = ((s >> 1) & 1) ^ 1;
    const uint32_t av = xlo + ((s & 1) * 32 + h) * 8192 + u * 512;
    mbar_wait(bq + BAR_XA, (s + 1) & 1);
    if (B3 == 8) barv<5, 384>();
    bsync<8, 384>();
    const uint32_t t8 = clk(), gs = xlo + XO_XG + ((((s + 3) & 7) * 32 + h) * 4 + j) * 6144;
    RCLEAR(2);
    const bool se = B3 % 8 == 0 && SE && u == SEU && s + 3 < NSEG;
    uint32_t tv = ctag ^ 1, ro = 0;
    if (se) {
        asm volatile("fence.proxy.async.shared::cta;" ::: "memory");
        if (SE == 4) delay_until(t8, DLY_E);
        if ((SE == 1 || SE == 4) && elect()) bulk_s2g(gs, xhi, sb + SM_XO, 4096);
    } else if (RE && u == 1 && s + 2 < NSEG) {
        asm volatile("fence.proxy.async.shared::cta;" ::: "memory");
        const uint32_t cb0 = (h >> 1) * 32768 + (j & 1) * 16384 + (h & 1) * 8192;
        delay_until(t8, DLY_T);
        tv = ldg1<XO_CQK>((xlo + cb0 + ((par(cb0) ^ (j >> 1) ^ CFAR ^ 1) << 12)) ^ ((s & 1) * 0x81000), xhi);
        SF();
    }
    if (B3 != 6 || u || SE == 2) delay_until(t8, DLY_V);
    if (se && SE == 2 && elect()) bulk_s2g(gs, xhi, sb + SM_XO, 4096);
    PT(4);
    int it = 0;
    uint4 d1, d2, d3;
    uint2 e1, e2, e3;
    const uint32_t ae = av - u * 512 + (u & 1) * 256;
    const uint32_t jv = JV(h, j);
#define VLOAD() { if (!VD) d1 = ldg4<XO_CV>(av + (jv ^ 1) * 2048 + l16, xhi); \
        d2 = ldg4<XO_CV>(av + (jv ^ 2) * 2048 + l16, xhi); d3 = ldg4<XO_CV>(av + (jv ^ 3) * 2048 + l16, xhi); \
        if (B3 == 6 && VX) { if (!VD) e1 = ldg2<XO_CV>(ae + (jv ^ 1) * 2048 + (l16 >> 1), xhi); \
                       e2 = ldg2<XO_CV>(ae + (jv ^ 2) * 2048 + (l16 >> 1), xhi); e3 = ldg2<XO_CV>(ae + (jv ^ 3) * 2048 + (l16 >> 1), xhi); } \
        if (VD) { d1 = lds128(sb + SM_VP + (s & 1) * 2048 + u * 512 + l16); \
                  if (B3 == 6 && VX) e1 = lds64(sb + SM_VP + (s & 1) * 2048 + (u & 1) * 256 + (l16 >> 1)); } }
#define XSEND(F, C) if (u < 2) { \
        if (F) asm volatile("fence.proxy.async.shared::cta;" ::: "memory"); \
        if ((C) && elect()) { \
            const uint32_t sg = s + 3 - u; \
            if (sg < NSEG) { \
                const uint32_t ga = xlo + XO_XG + (((sg & 7) * 32 + h) * 4 + (j ^ (2 * u))) * 6144, sa = sb + SM_XO + u * 6144; \
                if (u == 0) bulk_s2g(ga + (SE ? 4096 : 0), xhi, sa + (SE ? 4096 : 0), SE ? 2048 : 6144); \
                else bulk_red(ga + ro, xhi, sa + ro, 6144 - ro); \
            } \
        } \
    }
    if (B3 == 8) {
        bsync<3, 384>();
        if (DLY_S) delay_until(clk(), DLY_S);
        XSEND(true, true);
    } else if (B3 == 6 && u == 0) {
        const uint32_t ga = xlo + XO_XG + ((((s + 3) & 7) * 32 + h) * 4 + j) * 6144, o = SE == 1 || SE == 2 ? 4096 : 0;
        if (o) {
            asm volatile("fence.proxy.async.shared::cta;" ::: "memory");
            if (s + 3 < NSEG && elect()) bulk_s2g(ga, xhi, sb + SM_XO, o);
        }
        bsync<3, 288>();
        if (DLY_S) delay_until(clk(), DLY_S);
        asm volatile("fence.proxy.async.shared::cta;" ::: "memory");
        if (elect()) {
            if (SE == 3 && s + 3 < NSEG) bulk_s2g(ga + o, xhi, sb + SM_XO + o, 6144 - o);
            if (s + 2 < NSEG) bulk_red(xlo + XO_XG + ((((s + 2) & 7) * 32 + h) * 4 + (j ^ 2)) * 6144, xhi, sb + SM_XO + 6144, 6144);
            if (SE != 3 && s + 3 < NSEG) bulk_s2g(ga + o, xhi, sb + SM_XO + o, 6144 - o);
        }
    } else {
    if (B3 == 6) VLOAD();
    if (B3 && B3 < 6) {
        VLOAD();
        bsync<B3 == 2 ? 4 : 3, 384>();
        XSEND(true, B3 < 3 || B3 == 5 || (B3 == 4 && u == 0));
    }
    while (true) {
        if (B3 % 7 == 0) VLOAD();
        if (RE && it == 0) {
            SF();
            if (!any_bad(tv ^ ctag)) {
                if (elect()) bulk_red(xlo + XO_XG + ((((s + 2) & 7) * 32 + h) * 4 + (j ^ 2)) * 6144, xhi, sb + SM_XO + 6144, 4096);
                ro = 4096;
            }
        }
        if (se && SE == 3 && it == 0 && elect()) bulk_s2g(gs, xhi, sb + SM_XO, 4096);
        uint32_t tg = or3(tagx2(d1.x, d1.z, ctag), tagx2(d2.x, d2.z, ctag), tagx2(d3.x, d3.z, ctag));
        if (B3 == 6 && VX) tg = or3(tg, tagx2(e1.x, e2.x, ctag), e3.x ^ ctag);
        const bool bad = any_bad(tg);
        if (B3 == 6 && VX) sts64(sb + SM_VS + (u & 1) * 256 + (l16 >> 1), hadd2(hadd2(e1.x, e2.x), e3.x), hadd2(hadd2(e1.y, e2.y), e3.y));
        sts128(sb + SM_VS + u * 512 + l16, hadd2(hadd2(d1.x, d2.x), d3.x), hadd2(hadd2(d1.y, d2.y), d3.y), hadd2(hadd2(d1.z, d2.z), d3.z),
               hadd2(hadd2(d1.w, d2.w), d3.w));
        if (VA) asm volatile("{\n.reg .pred p;\nsetp.eq.u32 p, %0, 0;\n@p bar.arrive 5, 384;\n}" ::"r"((uint32_t)bad) : "memory");
        if (B3 % 7 == 0) REFRESH();
        if (!bad) break;
        if (B3 % 7) { REFRESH(); VLOAD(); }
        if (++it > SPIN_LIMIT) die(it);
    }
    PC(26, it);
    PT(5);
    if (VB) barv<11, 384>();
    else if (!VA) barv<5, B3 == 6 ? 352 : 384>();
    }
    if (B3 % 7 == 0) {
        bsync<3, 384>();
        XSEND(true, true);
    }
    if (B3 == 3 || B3 == 4) XSEND(false, B3 == 3 || u == 1);
    PT(6);
    RCLEAR(0);
    PT(7);
    bsync<7, 384>();
    if (s + 1 < NSEG && elect()) kvload(sb, u, h, j, s + 1, xlo, xhi);
    RCLEAR(3);
    if (XLP == 1) xload(sb, u, j, s + 1, tmx);
    if (u < (B3 == 6 ? 1 : 2)) {
        asm volatile("cp.async.bulk.wait_group.read 0;" ::: "memory");
        if (elect()) {
            mbar_expect(bq + BAR_PI + ((s & 1) ^ 1) * 8, 6144);
            if (B3 == 6) mbar_expect(bq + BAR_PI + ((s & 1) ^ 1) * 8, 6144);
        }
    }
    PT(8);
    if (GP && s == NSEG - 2 && gl) g_wait(xlo + XO_TK + 128, xhi);
    if (s + 1 < NSEG) bsync<10, 384>();
    if (XLP == 0) xload(sb, u, j, s + 1, tmx);
    RCLEAR(4);
    if (s == NSEG - 2 && gl) {
        if (!GP) g_wait(xlo + XO_TK + 128, xhi);
        g_load(sb, u, h * 4 + j, 0, xlo, xhi, tmb);
        if (GP == 0 || GP == 3) g_load(sb, u, h * 4 + j, 1, xlo, xhi, tmb);
    }
    asm volatile("cp.async.bulk.wait_group 0;" ::: "memory");
    if (s + 1 < NSEG) mbar_wait(bq + BAR_KV, (s + 1) & 1);
    asm volatile("lop3.b32 %0, %0, %1, %2, 0x78;" : "+r"(l16) : "r"(old), "r"(zero));
    PT(15);
}
DEVI void tickets_done(uint32_t* tk) {
    if (atomicInc(tk + 2, gridDim.x / 2 - 64) == gridDim.x / 2 - 64) { tk[0] = 0; tk[1] = 0; }
}

__global__ void __cluster_dims__(2, 1, 1) __launch_bounds__(384, 1)
chain_kernel(const __grid_constant__ CUtensorMap tmq, const __grid_constant__ CUtensorMap tmk,
             const __grid_constant__ CUtensorMap tmv, const __grid_constant__ CUtensorMap tmo,
             const __grid_constant__ CUtensorMap tmx, const __grid_constant__ CUtensorMap tmb, const __grid_constant__ CUtensorMap tmy,
             const bf16* __restrict__ mem0, const bf16* __restrict__ xg,
             uint32_t xlo, uint32_t xhi, uint32_t zero, int nseg, bf16* __restrict__ out) {
    extern __shared__ __align__(1024) uint8_t smem[];
    const uint32_t tstart = clk();
    const uint32_t rk = smem_u32(smem) & 0x1000000;
    if (rk == 0 && (threadIdx.x & 31) == 0 && threadIdx.x - 32 < 32 * PW)
        sts32(SB0 + SM_ROLE + 4 + (threadIdx.x >> 3), probe(xlo + XO_PB + (threadIdx.x & 32) * 128 + (threadIdx.x & 64) * 256 + blockIdx.x * 16, xhi));
    __syncwarp();
    if ((smem_u32(smem) & 0xFFFFFF) != SB0) die(1 << 23);
    if (!LDP) asm volatile("griddepcontrol.launch_dependents;" ::: "memory");
    const uint32_t w = __reduce_max_sync(0xFFFFFFFFu, threadIdx.x >> 5);
    const uint32_t sb = __reduce_max_sync(0xFFFFFFFFu, smem_u32(smem));
    const uint32_t bq = sb + SM_BAR;
    uint32_t l16 = __shfl_sync(0xFFFFFFFFu, (threadIdx.x & 31) * 16, threadIdx.x & 31);
    if (threadIdx.x == 0) {
        mbar_init(bq, 1);
        for (int i = 0; i < 24; i++) mbar_init(bq + BAR_WF + i * 8, i < 16 ? 1 : 8);
        mbar_init(bq + BAR_XA, 4); mbar_init(bq + BAR_KV, 4); mbar_init(bq + BAR_PI, 2); mbar_init(bq + BAR_PI + 8, 2);
        for (int i = 0; i < 14; i++) mbar_init(bq + BAR_GF + i * 8, i < 8 || i == 13 ? 1 : 8);
        mbar_expect(bq + BAR_GX + 8, 32768);
        mbar_init(bq + BAR_RO, 1);
        mbar_expect(bq + BAR_RO, 4);
        mbar_expect(bq + BAR_PI, 6144);
        mbar_expect(bq + BAR_PI, 6144);
        asm volatile("fence.mbarrier_init.release.cluster;" ::: "memory");
        asm volatile("fence.proxy.async.shared::cta;" ::: "memory");
    }
    __syncwarp();
    asm volatile("barrier.cluster.arrive.relaxed.aligned;" ::: "memory");
    if (w == 9) {
#pragma unroll 1
        for (int e = 0; e < 12; e++) sts128(sb + SM_WO + e * 512 + l16, 0, 0, 0, 0);
    }
    if (w == 8 && blockIdx.x < 128) {
        if (XPF && elect()) {
            asm volatile("cp.async.bulk.prefetch.L2.global [%0], 3072;" ::"l"((const char*)xg + blockIdx.x * 3072) : "memory");
            asm volatile("prefetch.tensormap [%0];\nprefetch.tensormap [%1];\nprefetch.tensormap [%2];\nprefetch.tensormap [%3];\nprefetch.tensormap [%4];"
                         ::"l"(&tmq), "l"(&tmx), "l"(&tmk), "l"(&tmv), "l"(&tmo) : "memory");
        }
#pragma unroll 1
        for (int i = 0; i < EPF; i++) {
            if (i) delay_until(clk(), EPD);
            if (elect())
                asm volatile("cp.async.bulk.prefetch.tensor.3d.L2.global [%0, {0, %1, %2}];" ::"l"(&tmq), "r"((blockIdx.x & 3) * 256 + i * 64), "r"((blockIdx.x >> 2) * 2) : "memory");
        }
    }
    if (rk == 0 && w <= PW) bsync<2, 32 * PW + 32>();
    asm volatile("barrier.cluster.wait.aligned;" ::: "memory");
    if (rk == 0 && threadIdx.x == 0) {
        uint32_t t1 = lds32(sb + SM_ROLE + 8), t0 = lds32(sb + SM_ROLE + 12);
        if (PW == 4) { t1 = min(t1, lds32(sb + SM_ROLE + 16)); t0 = min(t0, lds32(sb + SM_ROLE + 20)); }
        uint32_t side = (t0 < t1 ? 0u : 1u) ^ par(XO_PB);
        uint32_t* tk = (uint32_t*)(((uint64_t)xhi << 32) | (xlo + XO_TK));
        uint32_t t = atomicAdd(tk + side, 1u);
        if (t >= 32) {
            uint2 c;
            int it = 0;
            do {
                c = ldg2<XO_TK>(xlo, xhi);
                if (++it > SPIN_LIMIT) die(it);
            } while (c.x + c.y != gridDim.x / 2);
            t += (side ? c.x : c.y) - 32;
            side ^= 1;
            if (t >= 32) tickets_done(tk);
        }
#pragma unroll
        for (uint32_t r = 0; r < 2; r++)
            asm volatile("st.async.weak.shared::cluster.mbarrier::complete_tx::bytes.b32 [%0], %1, [%2];"
                         ::"r"(sb + SM_ROLE + (r << 24)), "r"(t * 4 + side * 2 + r), "r"(bq + BAR_RO + (r << 24)) : "memory");
    }
    __syncwarp();
    mbar_wait(bq + BAR_RO, 0);
    const uint32_t role = __reduce_max_sync(0xFFFFFFFFu, lds32(sb + SM_ROLE));
    if (role >= 128) return;
    const uint32_t h = role >> 2, j = role & 3;
    if (FTM && w == 11 && elect())
#pragma unroll
        for (uint32_t c = 0; c < FTM; c++) {
            mbar_expect(bq + BAR_WF + c * 8, 16384);
            tma3d(sb + SM_ST + c * 16384, &tmq, bq + BAR_WF + c * 8, 0, j * 256 + c * 64, h * 2);
        }

    if (w >= 8) {
        asm volatile("setmaxnreg.dec.sync.aligned.u32 24;");
        const uint32_t u = w - 8;
        if (u == 3) {
#pragma unroll 1
            for (uint32_t c = FTM; c < 16; c++) {
                if (c >= WIN) mbar_wait(bq + BAR_WF + (c - WIN) * 8, 0);
                if (l16 == 0) PG(16 + c);
                if (c == 12 + WOP) bsync<2, 64>();
                if (c >= 4 && c < 12 && c != 10) mbar_wait(bq + BAR_WE + (c - 4) * 8, 0);
                if (elect()) {
                    const uint32_t b = bq + BAR_WF + c * 8;
                    mbar_expect(b, 16384);
                    if (c >= 12) tma2d(sb + SM_WO + (c - 12) * WO_BOX, &tmo, b, j * 256 + (c - 12) * 64, h * 128);
                    else tma3d(c == 10 ? sb + SM_WV : sb + SM_ST + (c & 3) * 16384, c < 4 ? &tmq : c < 8 ? &tmk : &tmv, b, 0, j * 256 + ((c ^ (c >= 10)) & 3) * 64, h * 2);
                }
            }
#pragma unroll 1
            for (uint32_t c = 16 - WIN; c < 16; c++) mbar_wait(bq + BAR_WF + c * 8, 0);
            if (l16 == 0) PG(15);
        } else if (u == 0) {
            if (elect()) {
                mbar_expect(bq, 49152);
#pragma unroll 1
                for (uint32_t i = 0; i < 12; i++)
                    tma3d(sb + SM_X + (i < 4 ? i : i + 4) * 4096, &tmx, bq, 0, i < 8 ? i * 8 : (j ^ ((0xBD98u >> (i - 8) * 4) & 15)) * 8, j * 4);
            }
#pragma unroll 1
            for (int i = 0; i < 4; i++) xload(sb, i, j, -1, &tmx);
            bsync<3, 320>();
            if (l16 == 0) PG(32);
            if (GH && j == 0 && elect()) asm volatile("{\n.reg .b64 a;\nmov.b64 a, {%0,%1};\nred.relaxed.gpu.global.inc.u32 [a+64], 4;\n}" ::"r"(xlo + XO_FL + h * 128), "r"(xhi) : "memory");
            __syncwarp();
            g_arrive(xlo + XO_FL + h * 128, xhi, 4);
            if (WOP < 4) barv<2, 64>();
            if (l16 == 0) PG(33);
            g_wait(xlo + XO_FL + h * 128, xhi);
            if (l16 == 0) PG(34);
#pragma unroll 1
            for (int i = 0; i < 4; i++)
                if (elect()) kvload(sb, i, h, j, 0, xlo, xhi);
            mbar_wait(bq + BAR_KV, 0);
            if (l16 == 0) PG(14);
        } else if (u == 1) {
            const uint32_t l = l16 >> 4, x = h * 8 + (l >> 2), d = (x & ~31u) + (l & 3) * 8 + ((x & 31) >> 2) + (x & 3) * 2 * DM;
            const unsigned short* m0 = (const unsigned short*)mem0 + j * 256;
            const uint32_t v1 = m0[d] | (((l & 3) == 3 ? 0x4200u : m0[d + DM]) << 16);
            const uint32_t v3 = h < 8 ? m0[h * 32 + 24 + (l >> 2) + ((l & 3) * 2 + 1) * DM] | 0x42000000u : 0;
#pragma unroll 1
            for (uint32_t i = 0; i < 12; i++) {
                if (i == 10) { sts32(sb + SM_WO + 6144 + l * 4, v1); sts32(sb + SM_WO + 6272 + l * 4, v3); }
                asm volatile("fence.proxy.async.shared::cta;" ::: "memory");
                __syncwarp();
                const uint32_t c = (0x21924u >> ((i - 3) * 2)) & 3;
                if (elect()) {
                    if (i < 3) bulk_s2g(xlo + XO_XG + (i * 128 + role) * 6144, xhi, sb + SM_WO, 6144);
                    else bulk_s2g(xlo + XO_R + rpage(j, i < 6 ? 0 : i < 9 ? 1 : -1) + c * 16384 + h * 128, xhi, sb + SM_WO + (i < 10 ? 0 : 6144 + c * 64), 128);
                }
            }
            asm volatile("cp.async.bulk.wait_group 0;" ::: "memory");
            if (elect()) asm volatile("{\n.reg .b64 a;\nmov.b64 a, {%0,%1};\nred.relaxed.gpu.global.inc.u32 [a], 127;\n}" ::"r"(xlo + XO_TK + 12), "r"(xhi) : "memory");
            if (l16 == 0) PG(16);
            g_wait(xlo + XO_TK + 12, xhi);
            if (l16 == 0) PG(17);
            barv<5, 288>();
            bsync<8, 320>();
            asm volatile("fence.acq_rel.gpu;" ::: "memory");
        } else {
            GSYNC(0);
            mbar_wait(bq + BAR_WE + 48, 0);
#pragma unroll 1
            for (int e = 0; e < 24; e++) sts128(sb + SM_TR + 4096 + e * 512 + l16, 0, 0, 0, 0);
            barv<3, 320>();
            bsync<8, 320>();
#pragma unroll 1
            for (int i = 0; i < 4; i++) xload(sb, i, j, 0, &tmx);
        }
        if (LDP) asm volatile("griddepcontrol.launch_dependents;" ::: "memory");
#pragma unroll 1
        for (int s = 0; s < nseg; s++) helper_step(sb, w, h, j, l16, xlo, xhi, zero, s, &tmx, &tmb);
        piwait(sb, 0, nseg - 2);
        bsync<9, 384>();
        GSYNC(1);
        if (!GS && w == 11 && elect()) asm volatile("prefetch.tensormap [%0];" ::"l"(&tmy) : "memory");
        if (GH && w == 10) { g_arrive(xlo + XO_FL + h * 128 + 64, xhi, 5); PG(2); }
        if (w < 10) {
            uint32_t kb = 2, heads = 0;
            asm volatile("fence.proxy.async.shared::cta;" ::: "memory");
            if (GH) {
                if (w == 9 && h >= 30) { kb = 0; heads = 0xFFFF; }
                else delay_until(clk(), GD);
            } else if (w == 9) {
                g_arrive(xlo + XO_TK + 192, xhi, 128);
                PG(2);
                if (h >= 30) { g_wait(xlo + XO_TK + 192, xhi); kb = 0; }
                PG(3);
            } else delay_until(clk(), GD);
#pragma unroll 1
            for (; kb < 32; kb++) {
                if (kb >= 4) mbar_wait(bq + BAR_GE + (kb & 3) * 8, ((kb >> 2) & 1) ^ 1);
                if (GH && ((heads >> (kb >> 1)) & 1)) {
                    int it = 0;
                    do {
                        uint32_t v;
                        asm volatile("{\n.reg .b64 a;\nmov.b64 a, {%1,%2};\nld.acquire.gpu.global.u32 %0, [a+64];\n}"
                                     : "=r"(v) : "r"(xlo + XO_FL + (role & 1) * 2048 + (l16 & 255) * 8), "r"(xhi) : "memory");
                        heads = __ballot_sync(0xFFFFFFFFu, v != 0);
                        if (++it > SPIN_LIMIT) die(it);
                    } while ((heads >> (kb >> 1)) & 1);
                    asm volatile("fence.proxy.async.global;" ::: "memory");
                    if (kb == 0) PG(3);
                }
                g_load(sb, w - 8, role, kb, xlo, xhi, &tmb);
            }
        }
        if (role == 0 && w == 11 && elect()) tickets_done((uint32_t*)(((uint64_t)xhi << 32) | (xlo + XO_TK)));
    } else {
        asm volatile("setmaxnreg.inc.sync.aligned.u32 240;");
        uint32_t Wq[16][4], Wk[16][4], Wv[NA][4];
        uint32_t t16, KA, KB, KC, KD;
        {
            const uint32_t lane = l16 >> 4, g = lane >> 2, t = lane & 3;
            const uint32_t rw = (((lane >> 4) & 1) * 8 + (lane & 7)) * 128u;
            const uint32_t off = rw + ((((w & 3) * 2 + ((lane >> 3) & 1)) ^ (lane & 7)) << 4);
            const uint32_t offo = rw + ((((w & 1) * 4 + ((lane >> 3) & 1)) ^ (lane & 7)) << 4);
            const uint32_t r = 2 * (t & 1) + (g >> 2);
            const uint32_t mk0 = t < 2 ? 0 : (r == 0 ? 2 * g > w : j + r < 4), mk1 = t < 2 ? 0 : (r == 0 ? 2 * g + 1 > w : j + r < 4);
            t16 = __shfl_sync(0xFFFFFFFFu, w * 512 + l16, lane);
            KA = __shfl_sync(0xFFFFFFFFu, (w * 512 + t * 64 + g * 8) | ((w * 512 + (g & 1) * 256 + (g >> 1) * 64 + t * 16) << 16), lane);
            KB = __shfl_sync(0xFFFFFFFFu, ((w >> 2) * WV_BOX + off) | mk0 | (mk1 << 1) |
                                              ((w * 256 + (g >> 2) * 4096 + (g & 3) * 64 + t * 16) << 16), lane);
            KC = __shfl_sync(0xFFFFFFFFu, ((lane & 7) * 1280 + (lane >> 3) * 128 + ((w ^ (lane & 7)) << 4)) | (((t >> 1) * 16 + g * 2) << 16) | ((t * 64 + g * 8) << 24), lane);
            KD = __shfl_sync(0xFFFFFFFFu, ((w >> 1) * WO_BOX + offo) | (((lane & 7) * 208 + (lane >> 3) * 16) << 16), lane);
            if (threadIdx.x == 0) PG(8);
#define WTAKE(W, c, k0) { mbar_wait(bq + BAR_WF + (c) * 8, 0); \
                _Pragma("unroll") for (int ks = 0; ks < 4; ks++) ldsm4t(W[(k0) + ks], sb + SM_ST + ((c) & 3) * 16384 + (KB & 0xFFF0) + ks * 2048); \
                if ((c) < 8) { __syncwarp(); if (elect()) mbar_arrive(bq + BAR_WE + (c) * 8); } }
#pragma unroll
            for (int c = 0; c < 4; c++) WTAKE(Wq, c, c * 4);
            mbar_wait(bq, 0);
            if (threadIdx.x == 0) PG(9);
            xstart<0>(sb, w, xlo + h * 24576, xhi, j, t16, KA, Wq);
            if (threadIdx.x == 0) PG(10);
#pragma unroll
            for (int c = 0; c < 4; c++) WTAKE(Wk, c + 4, c * 4);
            if (threadIdx.x == 0) PG(11);
            xstart<1>(sb, w, xlo + h * 24576, xhi, j, t16, KA, Wk);
            if (threadIdx.x == 0) PG(12);
            WTAKE(Wv, 8, 0);
            WTAKE(Wv, 9, 4);
            mbar_wait(bq + BAR_WF + 80, 0);
            WTAKE(Wv, 11, 8);
            if (threadIdx.x == 0) PG(13);
            xstart<2>(sb, w, xlo + h * 24576, xhi, j, t16, KA, Wv);
            mbar_wait(bq + BAR_XA, 0);
            bsync<8, 320>();
        }
        const uint32_t ONES = 0x3F803F80u;
#define UNI(x) __reduce_max_sync(0xFFFFFFFFu, x)
        uint32_t swi = UNI((uint32_t)((uint64_t)smem >> 32));
        const uint32_t sbw = UNI(sb + w * 256), sbm = UNI(sb - w * 512), sbs = UNI(sb + w * 768), sbp = UNI(sb + w * 208);
#define OPQALL() { OPQ(t16); OPQ(KA); OPQ(KB); OPQ(KC); OPQ(KD); }
        OPQALL();
        if (SEED & 1) OPQ(Wq[0][0]);
        if (SEED & 2) OPQ(Wq[5][1]);
        if (SEED & 4) OPQ(Wk[0][0]);
        if (SEED & 8) OPQ(Wk[15][2]);
        if (SEED & 16) OPQ(Wv[0][0]);
        if (SEED & 32) OPQ(Wv[7][3]);
        const uint32_t cb0 = (h >> 1) * 32768 + (j & 1) * 16384 + (h & 1) * 8192;
        const uint32_t cb = UNI(xlo + cb0 + ((par(cb0) ^ (j >> 1) ^ CFAR) << 12)), cv = UNI(xlo + h * 8192 + JV(h, j) * 2048), h1 = UNI((h & 1) * 1024);
        const uint32_t uox = UNI(xlo + XO_OX + (h * 2 + (w >> 2)) * 262144 + j * 1024 + (w & 3) * 256 - w * 128);
        uint32_t rp = UNI(xlo + rpage(j, 0));
        float ox[4];
        float4 dn;
#define OXSTORE(s) asm volatile("{\n.reg .b64 a;\nmov.b64 a, {%0,%1};\nst.global.u32 [a], %2;\nst.global.u32 [a+128], %3;\n}" \
                                ::"r"(uox + (s) * 4096 + (t16 >> 2)), "r"(xhi), \
                                  "r"(pack2(ox[0] * dn.y, ox[1] * dn.w)), "r"(pack2(ox[2] * dn.y, ox[3] * dn.w)) : "memory")
#pragma unroll 1
        for (int s2 = 0;; s2 += 2, rp ^= 0x21000)
#pragma unroll
        for (int p = 0; p < 2; p++) {
            const int s = s2 + p;
            const uint32_t ctag = ((s2 >> 1) & 1) ^ 1;
            const uint32_t hb = cb ^ (p * 0x81000), rb = rp ^ (p * 0x11000);
            uint4 k0, k1, qq, c0, c1, c2, c3, pk;
            float va[4], vb[4];
            uint32_t qx0, qx1, ov0, ov1, wv[16 - NA][4];
            {
                float xa[16], xb[16];
                uint4 m0, n0;
                uint32_t e0, f0;
                uint32_t xp[8];
                wg_fence();
                XMMA(0, 6);
                SF();
                piwait(sb, p, s - 2);
                uint4 pi = xpeer<0>(sb, p ^ 1, t16);
                SF();
#define MR (VC ? 1 : 2)
#define MC (VC ? 2 : 1)
#define QPARK() { xpack<0>(xp, xa); xpark<0>(xp, pi, sb, sbw, p ^ 1, t16, KA); pi = xpeer<MR>(sb, p ^ 1, t16); SF(); }
                wg_fence();
                if (QP) {
                    XMMA(6, QP);
                    XMMA(QP, QP + 4);
                    wg_wait<1>();
                    SF();
                    QPARK();
                    wg_fence();
                    if (QP + 4 < RPOS) XMMA(QP + 4, RPOS);
                } else XMMA(6, RPOS);
                if (RPOS < 32) XMMA(RPOS, RPOS + 4 < 32 ? RPOS + 4 : 32);
                uint32_t a = (p ? rp : rp ^ 0x30000) + t16, e = (p ? rp : rp ^ 0x30000) + (t16 >> 2), ah = xhi, eh = xhi;
                OPQ(a); OPQ(e); OPQ(ah); OPQ(eh);
                SF();
                wg_wait<(RPOS < 32)>();
                SF();
                PT(11);
                RLOAD();
                SF();
                if (!QP) QPARK();
                if (RPOS + 4 < 32) {
                    wg_fence();
                    XMMA(RPOS + 4, 32);
                    SF();
                }
                wg_wait<0>();
                xpack<MR>(xp, xb);
                xpark<MR>(xp, pi, sb, sbw, p ^ 1, t16, KA);
                uint32_t acw, ahi, tg;
#define APREP() { OPQ(KA); if (!APH) OPQ(t16); acw = hb + (KA & 0xFFFF); ahi = xhi; tg = ctag; OPQ(acw); OPQ(ahi); OPQ(tg); }
                if (APH == 3) SF();
                if (APH) APREP();
                if (APH >= 2) OPQ(t16);
                SF();
                PT(12);
                {
                    int it = 0;
                    if (RDW) {
                        bool rb_;
#pragma unroll 1
                        do {
                            rb_ = ruse(sb + SM_MEMT + t16, m0, n0, e0, f0);
                            if (RDW == 2) MF();
                            if (RDW == 3) SF();
                            asm volatile("{\n.reg .pred p, q;\n.reg .b64 a, e;\nsetp.ne.u32 p, %15, 0;\nmov.b64 a, {%11,%12};\nmov.b64 e, {%13,%14};\n"
                                         "@p ld.relaxed.gpu.global.v4.u32 {%0,%1,%2,%3}, [a];\n@p ld.relaxed.gpu.global.v4.u32 {%4,%5,%6,%7}, [a+16384];\n"
                                         "@p ld.relaxed.gpu.global.u32 %8, [e+32768];\n@p ld.relaxed.gpu.global.u32 %9, [e+33792];\n"
                                         "add.u32 %10, %10, 1;\nsetp.gt.u32 q, %10, 1048576;\n@q st.shared.u32 [%10], %10;\n}"
                                         : "+r"(m0.x), "+r"(m0.y), "+r"(m0.z), "+r"(m0.w), "+r"(n0.x), "+r"(n0.y), "+r"(n0.z), "+r"(n0.w), "+r"(e0), "+r"(f0), "+r"(it)
                                         : "r"(a), "r"(ah), "r"(e), "r"(eh), "r"((uint32_t)rb_) : "memory");
                        } while (rb_);
                    } else
                    while (ruse(sb + SM_MEMT + t16, m0, n0, e0, f0)) {
                        RLOAD();
                        if (++it > SPIN_LIMIT) die(it);
                    }
                    PC(22, it + 1);
                }
                PT(13);
                if (APH == 1) OPQ(t16);
                if (!APH) APREP();
#define AX (p ? A1 : A0)
                float q[4], k[4];
                if (AX & 2) _Pragma("unroll") for (int i = 0; i < 4; i++) {
                    asm volatile("mov.b32 %0, %1;" : "=f"(q[i]) : "r"(zero)); asm volatile("mov.b32 %0, %1;" : "=f"(k[i]) : "r"(zero)); }
                if (APH < 2) SF();
                bsync<1, 384>();
                PT(0);
                uint32_t b[8][4];
#pragma unroll
                for (int i = 0; i < 8; i++) {
                    const int pp = i < 2 || (AX & 8) || ((AX & 16) && i >= 6) ? i : i ^ 1;
                    ldsm4t(b[pp], sbm + SM_MEMT + t16 + pp * 512);
                    if (i < 7 || (AX & 4)) MF();
                }
                if (ASF) SF();
                const uint32_t aWv = sb + SM_WV + (KB & 0xFFF0);
#define WVLD(n0, n1) _Pragma("unroll") for (int n = (n0); n < (n1) && n < 16 - NA; n++) ldsm4t(wv[n], aWv + n * 2048)
#pragma unroll
                for (int ks = 0; ks < 16; ks++) {
                    const uint32_t b0 = b[ks >> 1][(ks & 1) * 2], b1 = b[ks >> 1][(ks & 1) * 2 + 1];
                    if (AX & 1) {
                        if (ks == 0 && !(AX & 2)) {
                            mma16z(k, Wk[0][0], Wk[0][1], Wk[0][2], Wk[0][3], b0, b1);
                            mma16z(q, Wq[0][0], Wq[0][1], Wq[0][2], Wq[0][3], b0, b1);
                        } else {
                            mma16(k, Wk[ks][0], Wk[ks][1], Wk[ks][2], Wk[ks][3], b0, b1);
                            mma16(q, Wq[ks][0], Wq[ks][1], Wq[ks][2], Wq[ks][3], b0, b1);
                        }
                    } else if (ks == 0 && !(AX & 2)) {
                        mma16z(q, Wq[0][0], Wq[0][1], Wq[0][2], Wq[0][3], b0, b1);
                        mma16z(k, Wk[0][0], Wk[0][1], Wk[0][2], Wk[0][3], b0, b1);
                    } else {
                        mma16(q, Wq[ks][0], Wq[ks][1], Wq[ks][2], Wq[ks][3], b0, b1);
                        mma16(k, Wk[ks][0], Wk[ks][1], Wk[ks][2], Wk[ks][3], b0, b1);
                    }
                    if (ks == 10 && VPF) { SF(); WVLD(0, VPF); }
                }
                const uint32_t oq0 = settag(pack2(q[0], q[2]), tg), oq1 = settag(pack2(q[1], q[3]), tg);
                const uint32_t ok0 = pack2(k[0], k[2]), ok1 = pack2(k[1], k[3]);
                stg2<XO_CQK>(acw, ahi, oq0, ok0);
                stg2<XO_CQK + 256>(acw, ahi, oq1, ok1);
                SF();
                PT(1);
#define CLOADG() { c2 = ldg4<XO_CQK>((hb ^ 0x1000) + (KA >> 16), xhi); c3 = ldg4<XO_CQK>((hb ^ 0x5000) + (KA >> 16), xhi); }
#define CLOAD0() c0 = lds128(sb + SM_TR + (KA >> 16))
#define CLOAD1() c1 = lds128(sb + SM_TR + 4096 + p * 4096 + (KA >> 16))
#define CLOADS() { CLOAD0(); CLOAD1(); }
#define CSIDE(n) { if (CGP == (n)) CLOADG(); if (C0P == (n)) CLOAD0(); if (C1P == (n)) CLOAD1(); if (PIP == (n)) pk = xpeer<MC>(sb, p ^ 1, t16); \
                   if (QSP == (n)) { qx0 = (t16 & 64) ? qq.y : qq.x; qx1 = (t16 & 64) ? qq.w : qq.z; } }
#pragma unroll
                for (int rd = 0; rd < 8; rd++) {
                    const int pp = (VORD >> (28 - 4 * rd)) & 7;
                    const uint32_t* a = 2 * pp < NA ? Wv[2 * pp < NA ? 2 * pp : 0] : wv[2 * pp < NA ? 0 : 2 * pp - NA];
                    const uint32_t* c = 2 * pp < NA ? Wv[2 * pp < NA ? 2 * pp + 1 : 0] : wv[2 * pp < NA ? 0 : 2 * pp + 1 - NA];
                    if (rd == 0) {
                        mma16z(va, a[0], a[1], a[2], a[3], b[pp][0], b[pp][1]);
                        mma16z(vb, c[0], c[1], c[2], c[3], b[pp][2], b[pp][3]);
                        if (VSB & 256) SF();
                        OPQ(swi);
                        asm volatile("{\n.reg .b64 a;\nmov.b64 a, {%0,%1};\nst.v2.u32 [a], {%2,%3};\nst.v2.u32 [a+256], {%4,%5};\n}"
                                     ::"r"((KA & 0xFFF) + (sb ^ 0x1000000) + SM_TR + 4096 + p * 4096), "r"(swi), "r"(oq0), "r"(ok0), "r"(oq1), "r"(ok1) : "memory");
                        sts64(sb + SM_TR + (KA & 0xFFF), oq0, ok0);
                        sts64(sb + SM_TR + (KA & 0xFFF) + 256, oq1, ok1);
                    } else {
                        mma16(va, a[0], a[1], a[2], a[3], b[pp][0], b[pp][1]);
                        mma16(vb, c[0], c[1], c[2], c[3], b[pp][2], b[pp][3]);
                    }
                    if (rd == (p ? KEP : KEP0)) { KEEP(t16, oq0, oq1, ok0, ok1); if (KE2) KEEP(t16, acw, ahi, acw, ahi); }
                    if (((p ? VSB : VSB0) >> rd) & 1) SF();
                    if (rd == W2P) WVLD(2, 3);
                    if (rd == W3P) WVLD(3, 4);
                    if (rd == K0P) k0 = lds128(sb + SM_KV + 2048 + (KB >> 16));
                    if (rd == K0P + 1) k1 = lds128(sb + SM_KV + 10240 + (KB >> 16));
                    if (rd == QQP) qq = lds128(sbw + SM_KV + ((KA >> 16) & 0xFF));
                    CSIDE(rd);
                    if ((VSF >> rd) & 1) SF(); else if ((VMF >> rd) & 1) MF();
                }
#define VTAIL() { ov0 = pack2(va[0] + vb[0], va[1] + vb[1]); ov1 = pack2(va[2] + vb[2], va[3] + vb[3]); \
                  stg2<XO_CV>(cv + p * 262144 + (t16 >> 1), xhi, settag(ov0, ctag), ov1); \
                  if (VD) asm volatile("{\n.reg .b64 a;\nmov.b64 a, {%0,%1};\nst.v2.u32 [a], {%2,%3};\n}" \
                                     ::"r"((t16 >> 1) + (sb ^ 0x1000000) + SM_VP + p * 2048), "r"(swi), "r"(settag(ov0, ctag)), "r"(ov1) : "memory"); \
                  barv<8, 384>(); OPQ(t16); SF(); }
                if (!VTP) VTAIL();
            }
            PT(2);
            PDUMP();
            {
                const uint32_t a0 = sb + SM_KV;
                float xa[16], xb[16];
                uint32_t xp[8];
                if (CGP == 12 || QSP == 12) { CSIDE(12); SF(); }
                wg_fence();
                XMMA(32, 32 + CPOS);
                if (CGP == 13) { SF(); CSIDE(13); SF(); wg_fence(); }
                if (VR == 1) { XMMA(32 + CPOS, 36); XMMA(36, 36 + CW2); wg_wait<2>(); }
                else if (CW) { XMMA(32 + CPOS, 36 + CPOS); wg_wait<1>(); }
                SF();
                CSIDE(8);
                SF();
                if (VR == 1) { wg_wait<1>(); SF(); }
                if (VTP) VTAIL();
                CSIDE(9);
                SF();
                wg_fence();
                XMMA(VR == 1 ? 36 + CW2 : 32 + CPOS + (CW ? 4 : 0), 48);
                SF();
                uint2 u1, u2, u3;
#define ULOADG() { u2 = ldg2<XO_CV>((cv ^ 4096) + p * 262144 + (t16 >> 1), xhi); u3 = ldg2<XO_CV>((cv ^ 6144) + p * 262144 + (t16 >> 1), xhi); }
#define ULOADS() u1 = lds64(sb + SM_VP + p * 2048 + (t16 >> 1))
#define UCHECK() { int it = 0; \
                   while (__builtin_expect(any_bad(tagx1(tagx2(u2.x, u3.x, ctag), u1.x, ctag)), 0)) { OPQ(t16); ULOADG(); ULOADS(); if (++it > SPIN_LIMIT) die(it); } \
                   PC(26, it); }
                CSIDE(10);
                if (B3 == 8 && VLP == 2) ULOADG();
                SF();
                const uint32_t ka[4] = {k0.x, k0.y, k0.z, k0.w}, kb[4] = {k1.x, k1.y, k1.z, k1.w};
                const uint32_t aSp = sb + SM_SP + (KC & 0xFFFF);
                PT(3);
#define BAR3() asm volatile("{\n.reg .pred p;\nsetp.eq.u32 p, %0, 0;\n@p bar.arrive 3, %1;\n}" ::"r"((uint32_t)bad), "n"(B3 == 6 ? 288 : 384) : "memory")
#define SCORES(FIRST) { \
                    const uint32_t qA = hadd2(hadd2(c0.x, c1.x), hadd2(c2.x, c3.x)), qB = hadd2(hadd2(c0.z, c1.z), hadd2(c2.z, c3.z)); \
                    const uint32_t kA = hadd2(hadd2(c0.y, c1.y), hadd2(c2.y, c3.y)), kB = hadd2(hadd2(c0.w, c1.w), hadd2(c2.w, c3.w)); \
                    bad = any_bad(or3(tagx2(c1.x, c1.z, ctag), tagx2(c2.x, c2.z, ctag), tagx2(c3.x, c3.z, ctag))); \
                    float sa[4], sb_[4], sc[4], sd[4], se[4]; \
                    if (FIRST) { SF(); if (B3 == 8 && VLP == 3) ULOADG(); CSIDE(11); wg_wait<0>(); } \
                    mma16z(sa, ka[0], ka[1], ka[2], ka[3], qA, qB); \
                    mma16z(sb_, kb[0], kb[1], kb[2], kb[3], qA, qB); \
                    mma16z(sc, qA, qx0, qB, qx1, kA, kB); \
                    if (FIRST) { \
                        xpack<MC>(xp, xa); \
                        if (KPOS == 0) { xadd(xp, pk); xstore<MC>(xp, sb, sbw, p ^ 1, t16, KA); if (B3 >= 5) BAR3(); else if (!B3 || B3 >= 3) barv<3, 384>(); } \
                        mma16z(sd, ka[0], ka[1], ka[2], ka[3], qx0, qx1); \
                        mma16z(se, kb[0], kb[1], kb[2], kb[3], qx0, qx1); \
                    } \
                    stsm4t(aSp, pack2(sa[0], sa[1]), pack2(sa[2], sa[3]), pack2(sb_[0], sb_[1]), pack2(sb_[2], sb_[3])); \
                    stsm2(aSp + 1024, pack2(sc[0], sc[1]), pack2(sc[2], sc[3])); \
                    if (FIRST) { \
                        stsm4t(aSp + 512, pack2(sd[0], sd[1]), pack2(sd[2], sd[3]), pack2(se[0], se[1]), pack2(se[2], se[3])); \
                        if (KPOS == 0) { KEEP(KD, xp[0], xp[1], xp[2], xp[3]); KEEP(KD, xp[4], xp[5], xp[6], xp[7]); } \
                    } }
                int it = 0;
                bool bad;
                SCORES(true);
                while (__builtin_expect(bad, 0)) {
                    OPQ(KA);
                    CLOADG();
                    CLOADS();
                    SCORES(false);
                    if (B3 >= 5) BAR3();
                    if (++it > SPIN_LIMIT) die(it);
                }
                PC(25, it);
                PT(4);
                if (B3 == 8 && VLP == 0) ULOADG();
                if (B3 == 1) barv<3, 384>();
                bsync<4, B3 == 2 ? 384 : 256>();
                uint32_t wo[16][4];
                const uint32_t aWo = sb + SM_WO + (KD & 0xFFFF), aWo1 = sb + SM_WO + ((KD & 0xFFFF) ^ 32);
#define WOLD(n0, n1) _Pragma("unroll") for (int n = (n0); n < (n1) && n < 16; n++) ldsm4t(wo[n], ((n & 1) ? aWo1 : aWo) + (n >> 1) * 2048)
                const bool hi = (t16 & 32) != 0;
                const uint32_t t8 = t16 >> 1;
                uint2 v0, v1, v2, v3;
                uint32_t es;
                {
                    uint32_t am[4], ax[4], a4[2];
                    const uint32_t aSr = sbs + SM_SP + t16;
                    ldsm4t(am, aSr);
                    ldsm4t(ax, aSr + 512);
                    ldsm2t(a4, aSr + 1024);
                    MF();
                    if (B3 == 8 && VLP == 1) ULOADG();
                    if (KPOS == 1) pk = xpeer<MC>(sb, p ^ 1, t16);
                    const uint32_t se = (t16 & 128) ? 0u : ONES, so = se ^ ONES;
                    float hm[4], hx[4], h4[4];
                    mma16z(hm, am[0], am[1], am[2], am[3], se, so);
                    mma16z(hx, ax[0], ax[1], ax[2], ax[3], se, so);
                    mma8z(h4, a4[0], a4[1], ONES);
                    SF();
                    if (KPOS == 1) { xpark<MC>(xp, pk, sb, sbw, p ^ 1, t16, KA); barv<3, 384>(); }
                    v0 = lds64(a0 + 4096 + t8); v1 = lds64(a0 + 8192 + t8); v2 = lds64(a0 + 12288 + t8); v3 = lds64(a0 + 16384 + t8);
                    if (B3 == 8) ULOADS();
                    WOLD(0, PF2);
                    float s0 = hi ? hx[0] : hm[0], s1 = hi ? hx[2] : hm[2];
                    const float s2 = hi ? h4[2] : h4[0];
                    s0 = (KB & 1) ? -1.0e9f * 11.313708499f : s0;
                    s1 = (KB & 2) ? -1.0e9f * 11.313708499f : s1;
                    int mi = __float_as_int(fmaxf(fmaxf(s0, s2), s1));
                    mi ^= (mi >> 31) & 0x7FFFFFFF;
                    const int mm = __reduce_max_sync(0xFFFFFFFFu, hi ? (int)0x80000000 : mi), mx = __reduce_max_sync(0xFFFFFFFFu, hi ? mi : (int)0x80000000);
                    SF();
                    WOLD(PF2, PF3);
                    SF();
                    mi = hi ? mx : mm;
                    mi ^= (mi >> 31) & 0x7FFFFFFF;
                    const float c2_ = 0.08838834764831845f * 1.4426950408889634f;
                    const float mc = __int_as_float(mi) * c2_;
                    const float e0 = ex2(fmaf(s0, c2_, -mc)), e1 = ex2(fmaf(s1, c2_, -mc)), e2 = ex2(fmaf(s2, c2_, -mc));
                    sts32(sbp + SM_P + (KC >> 25), pack2(e0, e1));
                    sts16(sbp + SM_P + 128 + ((KC >> 16) & 0xFF), pack2(e2, e2));
                    es = __float_as_uint(fmaf(e2, 0.5f, e0 + e1) + 64.f);
                }
                const uint32_t sm = __reduce_add_sync(0xFFFFFFFFu, hi ? 0u : es), sx = __reduce_add_sync(0xFFFFFFFFu, hi ? es : 0u);
                const uint32_t aPr = sb + SM_P + (KD >> 16);
                if (B3 == 8 && VCP == 0) UCHECK();
                PT(5);
                bsync<5, VB ? 256 : B3 == 6 ? 352 : 384>();
                uint32_t pm[4], px[4], p4[2];
                ldsm4(pm, aPr);
                MF();
                uint2 vs;
                #define VGET(n) if (VB == (n)) { if (VB) bsync<11, 384>(); vs = lds64(sb + SM_VS + t8); MF(); }
                if (B3 != 8) { VGET(0); VGET(1); }
                ldsm2(p4, aPr + 128);
                MF();
                VGET(2);
                ldsm4(px, aPr + 64);
                MF();
                VGET(3);
#define DNST(n) if (DNP == (n)) { sts32f(sb + SM_DN + w * 8 + ((t16 >> 3) & 4), rcp(__uint_as_float((hi ? sx : sm) - 15u * 0x42800000u) - 64.f)); MF(); }
                DNST(0);
                if (B3 == 8 && VCP == 2) UCHECK();
                if (WLP == 0) { WOLD(PF3, NPF); }
                if (DNP == 1) MF();
                DNST(1);
                if (B3 == 8 && VCP == 1) UCHECK();
                if (B3 == 8) { ov0 = hadd2(ov0, u1.x); ov1 = hadd2(ov1, u1.y); vs.x = hadd2(u2.x, u3.x); vs.y = hadd2(u2.y, u3.y); }
                const uint32_t vm0 = hadd2(ov0, vs.x), vm1 = hadd2(ov1, vs.y);
                float oa[4], ob[4];
                mma16z(oa, v0.x, v0.y, v1.x, v1.y, pm[0], pm[1]);
                mma16z(ob, v2.x, v2.y, v3.x, v3.y, pm[2], pm[3]);
                mma8(oa, vm0, vm1, p4[0]);
                stsm2(sbw + SM_OT + (t16 & 511), pack2(oa[0] + ob[0], oa[1] + ob[1]), pack2(oa[2] + ob[2], oa[3] + ob[3]));
                if (DNP == 2) MF();
                DNST(2);
                PT(6);
                SF();
                bsync<6, 256>();
                mma16z(ox, v0.x, v0.y, v1.x, v1.y, px[0], px[1]);
                uint32_t b[4][4];
#define OTLD(pp) ldsm4t(b[pp], sbm + SM_OT + t16 + (pp) * 512)
                OTLD(0);
                MF();
                OTLD(1);
                if (WLP == 1) { MF(); WOLD(PF3, NPF); }
                barv<7, 384>();
                mma16(ox, v2.x, v2.y, v3.x, v3.y, px[2], px[3]);
                mma8(ox, vm0, vm1, p4[1]);
                if (p == 1 && s + 1 == nseg) goto done;
                SF();
                uint32_t ar, ae, ahi = xhi;
                float r[2][4];
#pragma unroll
                for (int ks = 0; ks < 8; ks++) {
                    if (ks == 0) WOLD(NPF, NPF + WPF);
                    if (ks == OPOS) { OTLD(2); MF(); }
                    if (ks == OPOS + 2) { OTLD(3); MF(); }
                    if (ks > 0) WOLD(NPF + WPF + 2 * (ks - 1), NPF + WPF + 2 * ks);
                    if (ks == 5) {
                        OPQ(t16);
                        ar = rb + h1 * 16 + t16; ae = rb + h1 + (t16 >> 2);
                        OPQ(ar); OPQ(ahi); OPQ(ae);
                        dn = lds128f(sb + SM_DN + (t16 & 48));
                    }
#pragma unroll
                    for (int mt = 0; mt < 2; mt++) {
                        const int i = ks * 2 + mt;
                        const uint32_t* a = wo[i];
                        if (i < 2) mma16z(r[mt], a[0], a[1], a[2], a[3], b[ks >> 1][2 * (ks & 1)], b[ks >> 1][2 * (ks & 1) + 1]);
                        else mma16(r[mt], a[0], a[1], a[2], a[3], b[ks >> 1][2 * (ks & 1)], b[ks >> 1][2 * (ks & 1) + 1]);
                    }
                    if (NPF + WPF + 2 * ks < 16 || ks < 5) SF();
                }
                const float r0 = dn.x, r1 = dn.z;
                asm volatile("{\n.reg .b64 a;\nmov.b64 a, {%0,%2};\nred.relaxed.gpu.global.add.noftz.v4.bf16x2 [a], {%3,%4,%5,%6};\n"
                             "mov.b64 a, {%1,%2};\nred.relaxed.gpu.global.add.noftz.bf16x2 [a+32768], %7;\n}"
                             ::"r"(ar), "r"(ae), "r"(ahi), "r"(pack2(r[0][0] * r0, r[0][1] * r1)), "r"(pack2(r[0][2] * r0, r[0][3] * r1)),
                               "r"(pack2(r[1][0] * r0, r[1][1] * r1)), "r"(pack2(r[1][2] * r0, 1.f)), "r"(pack2(r[1][3] * r1, 1.f)) : "memory");
                barv<10, 384>();
            }
            SF();
            PT(10);
            OXSTORE(s);
            OPQALL();
        }
    done:
        dn = lds128f(sb + SM_DN + (t16 & 48));
        OXSTORE(nseg - 1);
        barv<9, 384>();
        g_main(sb, w, role, &tmy, out);
        if (threadIdx.x == 0) PG(0);
    }
}

template <int SC> DEVI void wg_rs128t(float (&d)[64], const uint32_t (&a)[4], uint64_t db) {
    if (SC) asm volatile("wgmma.mma_async.sync.aligned.m64n128k16.f32.bf16.bf16 "
        "{%0,%1,%2,%3,%4,%5,%6,%7,%8,%9,%10,%11,%12,%13,%14,%15,%16,%17,%18,%19,%20,%21,%22,%23,%24,%25,%26,%27,%28,%29,%30,%31,%32,%33,%34,%35,%36,%37,%38,%39,%40,%41,%42,%43,%44,%45,%46,%47,%48,%49,%50,%51,%52,%53,%54,%55,%56,%57,%58,%59,%60,%61,%62,%63}, "
        "{%64,%65,%66,%67}, %68, 1, 1, 1, 1;"
        : D4(+, 0), D4(+, 4), D4(+, 8), D4(+, 12), D4(+, 16), D4(+, 20), D4(+, 24), D4(+, 28), D4(+, 32), D4(+, 36), D4(+, 40), D4(+, 44), D4(+, 48), D4(+, 52), D4(+, 56), D4(+, 60) : "r"(a[0]), "r"(a[1]), "r"(a[2]), "r"(a[3]), "l"(db));
    else asm volatile("wgmma.mma_async.sync.aligned.m64n128k16.f32.bf16.bf16 "
        "{%0,%1,%2,%3,%4,%5,%6,%7,%8,%9,%10,%11,%12,%13,%14,%15,%16,%17,%18,%19,%20,%21,%22,%23,%24,%25,%26,%27,%28,%29,%30,%31,%32,%33,%34,%35,%36,%37,%38,%39,%40,%41,%42,%43,%44,%45,%46,%47,%48,%49,%50,%51,%52,%53,%54,%55,%56,%57,%58,%59,%60,%61,%62,%63}, "
        "{%64,%65,%66,%67}, %68, 0, 1, 1, 1;"
        : D4(=, 0), D4(=, 4), D4(=, 8), D4(=, 12), D4(=, 16), D4(=, 20), D4(=, 24), D4(=, 28), D4(=, 32), D4(=, 36), D4(=, 40), D4(=, 44), D4(=, 48), D4(=, 52), D4(=, 56), D4(=, 60) : "r"(a[0]), "r"(a[1]), "r"(a[2]), "r"(a[3]), "l"(db));
}
template <int SC> DEVI void wg_rs64t(float (&d)[32], const uint32_t (&a)[4], uint64_t db) {
    if (SC) asm volatile("wgmma.mma_async.sync.aligned.m64n64k16.f32.bf16.bf16 "
        "{%0,%1,%2,%3,%4,%5,%6,%7,%8,%9,%10,%11,%12,%13,%14,%15,%16,%17,%18,%19,%20,%21,%22,%23,%24,%25,%26,%27,%28,%29,%30,%31}, "
        "{%32,%33,%34,%35}, %36, 1, 1, 1, 1;"
        : D4(+, 0), D4(+, 4), D4(+, 8), D4(+, 12), D4(+, 16), D4(+, 20), D4(+, 24), D4(+, 28) : "r"(a[0]), "r"(a[1]), "r"(a[2]), "r"(a[3]), "l"(db));
    else asm volatile("wgmma.mma_async.sync.aligned.m64n64k16.f32.bf16.bf16 "
        "{%0,%1,%2,%3,%4,%5,%6,%7,%8,%9,%10,%11,%12,%13,%14,%15,%16,%17,%18,%19,%20,%21,%22,%23,%24,%25,%26,%27,%28,%29,%30,%31}, "
        "{%32,%33,%34,%35}, %36, 0, 1, 1, 1;"
        : D4(=, 0), D4(=, 4), D4(=, 8), D4(=, 12), D4(=, 16), D4(=, 20), D4(=, 24), D4(=, 28) : "r"(a[0]), "r"(a[1]), "r"(a[2]), "r"(a[3]), "l"(db));
}
template <int SC> DEVI void wg_rs40(float (&d)[20], const uint32_t (&a)[4], uint64_t db) {
    if (SC) asm volatile("wgmma.mma_async.sync.aligned.m64n40k16.f32.bf16.bf16 "
        "{%0,%1,%2,%3,%4,%5,%6,%7,%8,%9,%10,%11,%12,%13,%14,%15,%16,%17,%18,%19}, "
        "{%20,%21,%22,%23}, %24, 1, 1, 1, 0;"
        : D4(+, 0), D4(+, 4), D4(+, 8), D4(+, 12), D4(+, 16) : "r"(a[0]), "r"(a[1]), "r"(a[2]), "r"(a[3]), "l"(db));
    else asm volatile("wgmma.mma_async.sync.aligned.m64n40k16.f32.bf16.bf16 "
        "{%0,%1,%2,%3,%4,%5,%6,%7,%8,%9,%10,%11,%12,%13,%14,%15,%16,%17,%18,%19}, "
        "{%20,%21,%22,%23}, %24, 0, 1, 1, 0;"
        : D4(=, 0), D4(=, 4), D4(=, 8), D4(=, 12), D4(=, 16) : "r"(a[0]), "r"(a[1]), "r"(a[2]), "r"(a[3]), "l"(db));
}
template <int SC> DEVI void wg_rs8(float (&d)[4], const uint32_t (&a)[4], uint64_t db) {
    if (SC) asm volatile("wgmma.mma_async.sync.aligned.m64n8k16.f32.bf16.bf16 "
        "{%0,%1,%2,%3}, "
        "{%4,%5,%6,%7}, %8, 1, 1, 1, 0;"
        : D4(+, 0) : "r"(a[0]), "r"(a[1]), "r"(a[2]), "r"(a[3]), "l"(db));
    else asm volatile("wgmma.mma_async.sync.aligned.m64n8k16.f32.bf16.bf16 "
        "{%0,%1,%2,%3}, "
        "{%4,%5,%6,%7}, %8, 0, 1, 1, 0;"
        : D4(=, 0) : "r"(a[0]), "r"(a[1]), "r"(a[2]), "r"(a[3]), "l"(db));
}
template <int SC> DEVI void wg_ss64a(float (&d)[32], uint64_t da, uint64_t db) {
    if (SC) asm volatile("wgmma.mma_async.sync.aligned.m64n64k16.f32.bf16.bf16 "
        "{%0,%1,%2,%3,%4,%5,%6,%7,%8,%9,%10,%11,%12,%13,%14,%15,%16,%17,%18,%19,%20,%21,%22,%23,%24,%25,%26,%27,%28,%29,%30,%31}, "
        "%32, %33, 1, 1, 1, 1, 0;"
        : D4(+, 0), D4(+, 4), D4(+, 8), D4(+, 12), D4(+, 16), D4(+, 20), D4(+, 24), D4(+, 28) : "l"(da), "l"(db));
    else asm volatile("wgmma.mma_async.sync.aligned.m64n64k16.f32.bf16.bf16 "
        "{%0,%1,%2,%3,%4,%5,%6,%7,%8,%9,%10,%11,%12,%13,%14,%15,%16,%17,%18,%19,%20,%21,%22,%23,%24,%25,%26,%27,%28,%29,%30,%31}, "
        "%32, %33, 0, 1, 1, 1, 0;"
        : D4(=, 0), D4(=, 4), D4(=, 8), D4(=, 12), D4(=, 16), D4(=, 20), D4(=, 24), D4(=, 28) : "l"(da), "l"(db));
}

#define G_ROWS 514
__device__ uint4 g_G[64 * G_ROWS * 8];
__device__ uint4 g_GN[64 * 8];
__device__ uint4 g_WN[1152];
#define FS_F2 196608
#define FS_TB (FS_F2 + 8192)
#define FS_NQ (FS_TB + 16384)
#define FS_BAR (FS_NQ + 128)
#define FS_NY (FS_NQ + 1024 + 128)
#define FS_TOTAL (FS_NQ + 3072)
#define F_THREADS 512

DEVI uint32_t cis(int j) {
    const float a = fmaf(__uint_as_float((((j + 1024) << 12) & 0x7FF000) | 0x3F800000), 6.283185307179586f, -9.42477796076938f);
    return pack2(__cosf(a), __sinf(a));
}
DEVI uint32_t cos2(int j0, int j1) {
    const float f = 6.283185307179586f / 2048.f;
    return pack2(__cosf((float)(((j0 + 1024) & 2047) - 1024) * f), __cosf((float)(((j1 + 1024) & 2047) - 1024) * f));
}
DEVI void twid(int j, float& c, float& s) {
    const float a = (float)(((j + 512) & 1023) - 512) * (6.283185307179586f / 1024.f);
    c = __cosf(a) * (1.f / 1024.f);
    s = __sinf(a) * (1.f / 1024.f);
}
template <bool B> struct Bool { static constexpr bool v = B; };
DEVI uint32_t opq(uint32_t& x, uint32_t zero) { OPQ(x); return x; }
DEVI uint32_t tidx() { uint32_t r; asm volatile("mov.u32 %0, %%tid.x;" : "=r"(r)); return r; }
DEVI void tma4d(uint32_t dst, const CUtensorMap* tm, uint32_t bar, int c0, int c1, int c2, int c3) {
    asm volatile("cp.async.bulk.tensor.4d.shared::cluster.global.mbarrier::complete_tx::bytes [%0], [%1, {%3, %4, %5, %6}], [%2];"
                 ::"r"(dst), "l"(tm), "r"(bar), "r"(c0), "r"(c1), "r"(c2), "r"(c3) : "memory");
}
DEVI void tma3s(const CUtensorMap* tm, uint32_t src, int c0, int c1, int c2) {
    asm volatile("cp.async.bulk.tensor.3d.global.shared::cta.bulk_group [%0, {%2, %3, %4}], [%1];" ::"l"(tm), "r"(src), "r"(c0), "r"(c1), "r"(c2) : "memory");
}
DEVI void tma4s(const CUtensorMap* tm, uint32_t src, int c0, int c1, int c2, int c3) {
    asm volatile("cp.async.bulk.tensor.4d.global.shared::cta.bulk_group [%0, {%2, %3, %4, %5}], [%1];"
                 ::"l"(tm), "r"(src), "r"(c0), "r"(c1), "r"(c2), "r"(c3) : "memory");
}
DEVI void bulk_commit() { asm volatile("cp.async.bulk.commit_group;" ::: "memory"); }
DEVI void fence_async() { asm volatile("fence.proxy.async;" ::: "memory"); }
DEVI void fence_smem() { asm volatile("fence.proxy.async.shared::cta;" ::: "memory"); }
DEVI void wgbar(uint32_t q) { asm volatile("bar.sync %0, 128;" ::"r"(q + 2) : "memory"); }
DEVI void grid_arrive(uint32_t* c, uint32_t n) { asm volatile("fence.proxy.async;\nred.release.gpu.global.inc.u32 [%0], %1;" ::"l"(c), "r"(n - 1) : "memory"); }
DEVI void grid_wait(uint32_t* c) {
    uint32_t v;
    int it = 0;
    do {
        asm volatile("ld.acquire.gpu.global.u32 %0, [%1];" : "=r"(v) : "l"(c) : "memory");
        if (++it > (1 << 22)) die(it);
    } while (v);
    fence_async();
}

template <bool INV, class S1, class S2>
DEVI void fft_rows(uint32_t grp, uint32_t q, const uint32_t (&F)[2][4], const float (&tc)[8], const float (&ts)[8], uint32_t so, float fx, uint32_t nq,
                   S1 sh1, S2 sh2) {
    float d[64];
    const uint64_t db = INV ? mkdesc(grp, 1024, 2048) : (mkdesc(grp, 2048, 512) ^ ((uint64_t)3 << 62));
    wg_fence();
    wg_rs128t<0>(d, F[0], db);
    wg_rs128t<1>(d, F[1], db + (INV ? 256 : 64));
    wg_commit();
    SF();
    sh1();
    float4 ny;
    if (INV) ny = lds128f(nq);
    wg_wait<0>();
    if (INV) { d[0] = fmaf(fx, ny.x, d[0]); d[16] = fmaf(fx, ny.y, d[16]); d[32] = fmaf(fx, ny.z, d[32]); d[48] = fmaf(fx, ny.w, d[48]); }
    uint32_t a[2][4][4];
    float e[2][INV ? 16 : 20];
    const uint64_t df = mkdesc(SB0 + FS_F2, 16, 1024);
#pragma unroll
    for (int s = 0; s < 2; s++) {
#pragma unroll
        for (int i = 0; i < 4; i++)
#pragma unroll
            for (int h = 0; h < 2; h++) {
                const float* x = d + (2 * s + h) * 16 + i * 4;
                a[s][i][h] = pack2(fmaf(x[2], ts[2 * i], x[0] * tc[2 * i]), fmaf(x[3], ts[2 * i + 1], x[1] * tc[2 * i + 1]));
                a[s][i][h + 2] = pack2(fmaf(-x[0], ts[2 * i], x[2] * tc[2 * i]), fmaf(-x[1], ts[2 * i + 1], x[3] * tc[2 * i + 1]));
            }
        wg_fence();
#pragma unroll
        for (int i = 0; i < 4; i++) {
            if constexpr (INV) { if (i == 0) wg_rs32<0>(e[s], a[s][i], df); else wg_rs32<1>(e[s], a[s][i], df + i * 2); }
            else { if (i == 0) wg_rs40<0>(e[s], a[s][i], df); else wg_rs40<1>(e[s], a[s][i], df + i * 2); }
        }
        wg_commit();
    }
    SF();
    sh2();
#pragma unroll
    for (int s = 0; s < 2; s++) {
        if (s == 0) wg_wait<1>(); else wg_wait<0>();
        float* x = e[s];
        if constexpr (!INV) {
            x[0] *= fx; x[1] *= fx; x[2] *= fx; x[3] *= fx;
            if (fx != 1.f) sts64(nq + s * 8, pack2(x[16], 0.f), pack2(x[18], 0.f));
        }
        const uint32_t o = grp + (INV ? so + s * 4096 : so ^ (s * 576));
#pragma unroll
        for (int b = 0; b < 2; b++)
            stsm4t(o + b * (INV ? 1024 : 4096), pack2(x[8 * b], x[8 * b + 1]), pack2(x[8 * b + 2], x[8 * b + 3]), pack2(x[8 * b + 4], x[8 * b + 5]),
                   pack2(x[8 * b + 6], x[8 * b + 7]));
    }
}

template <bool INV>
DEVI void fft_gen(uint32_t a, uint32_t n2) {
    const uint32_t tid = tidx(), x = ((tid >> 4) & 24) + (tid & 3), o = (tid & 4) * 128;
    if (INV) {
        const uint32_t r = (tid & 64) * 16 + (tid & 16) * 32 + (tid & 40) * 8 + n2;
        sts128(a + tid * 16, cis(o - r * x), cis(o - (r + 128) * x), cis(o - r * (x + 4)), cis(o - (r + 128) * (x + 4)));
    } else {
        const uint32_t r = 64 * x + n2, k = ((tid >> 2) & 24) + ((tid >> 3) & 3);
        sts128(a + tid * 16, cis(r * k + o), cis(r * (k + 4) + o), cis((r + 256) * k + o), cis((r + 256) * (k + 4) + o));
    }
}
template <bool INV, class S1>
DEVI void fft_cross(uint32_t buf, uint32_t q, uint32_t fa, uint32_t so, uint32_t nq, float (&n)[4], S1 sh1) {
    uint32_t F[4][4];
#pragma unroll
    for (int s = 0; s < 4; s++) { const uint4 v = lds128(fa + s * 2048); F[s][0] = v.x; F[s][1] = v.y; F[s][2] = v.z; F[s][3] = v.w; }
    float d[64];
    const uint64_t db = mkdesc(buf + q * 2048, 1024, 8192), dn = mkdesc(nq, 16, 1024);
    wg_fence();
#pragma unroll
    for (int s = 0; s < 4; s++) { if (s == 0) wg_rs128t<0>(d, F[s], db); else wg_rs128t<1>(d, F[s], db + s * 1024); }
#pragma unroll
    for (int s = 0; s < 4; s++) { if (s == 0) wg_rs8<0>(n, F[s], dn); else wg_rs8<1>(n, F[s], dn + s * 2); }
    wg_commit();
    SF();
    sh1();
    wg_wait<0>();
#pragma unroll
    for (int b = 0; b < 8; b++) {
        const uint32_t o = INV ? so ^ ((b >> 1) * 288 ^ (b & 1) * 32) : (so ^ ((b & 3) * 32)) + (b >> 2) * 1024;
        stsm4(buf + o, pack2(d[8 * b], d[8 * b + 1]), pack2(d[8 * b + 2], d[8 * b + 3]), pack2(d[8 * b + 4], d[8 * b + 5]), pack2(d[8 * b + 6], d[8 * b + 7]));
    }
}

template <bool ODD>
DEVI void fft_filter(uint32_t aw, const float (&e)[32], const float (&o)[32], uint32_t (&u)[4][4], uint32_t (&v)[4][4]) {
#pragma unroll
    for (int s = 0; s < 4; s++) {
        float y[2][2][4];
#pragma unroll
        for (int c = 0; c < 2; c++) {
            float f[4][2];
#pragma unroll
            for (int i = 0; i < 4; i++) {
                const uint32_t a = aw + (i * 32 + s * 8 + c) * 144, x = lds32(a);
                f[i][0] = ODD ? hi_f(x) : lo_f(x);
                f[i][1] = ODD ? lo_f(lds32(a + 4)) : hi_f(x);
            }
#pragma unroll
            for (int h = 0; h < 2; h++) {
                const int x = 8 * s + 2 * h + c;
                const float ar = e[x] + o[x], ai = e[x + 4] + o[x + 4], br = e[x] - o[x], bi = e[x + 4] - o[x + 4];
                const float yr = fmaf(-ai, f[2][h], ar * f[0][h]), yi = fmaf(ar, f[2][h], ai * f[0][h]);
                y[h][c][0] = fmaf(-bi, f[3][h], fmaf(br, f[1][h], yr));
                y[h][c][1] = fmaf(br, f[3][h], fmaf(bi, f[1][h], yi));
                y[h][c][2] = fmaf(2.f, yr, -y[h][c][0]);
                y[h][c][3] = fmaf(2.f, yi, -y[h][c][1]);
            }
        }
#pragma unroll
        for (int h = 0; h < 2; h++) {
            u[s][h] = pack2(y[h][0][0], y[h][1][0]); u[s][h + 2] = pack2(y[h][0][1], y[h][1][1]);
            v[s][h] = pack2(y[h][0][2], y[h][1][2]); v[s][h + 2] = pack2(y[h][0][3], y[h][1][3]);
        }
    }
}

__global__ void __launch_bounds__(F_THREADS, 1)
post_kernel(const __grid_constant__ CUtensorMap tmx, const __grid_constant__ CUtensorMap tmg1, const __grid_constant__ CUtensorMap tmg2,
           const __grid_constant__ CUtensorMap tmwr, const __grid_constant__ CUtensorMap tmwi, const __grid_constant__ CUtensorMap tmy,
           const bf16* __restrict__ wr, const bf16* __restrict__ wi, uint32_t* cnt, uint32_t zero, int nw) {
    extern __shared__ __align__(1024) uint8_t smem[];
    const uint32_t sb = SB0;
    if (smem_u32(smem) != sb) die(1 << 23);
    if (FDL) delay_until(clk(), FDL);
    const uint32_t tid = threadIdx.x, lane = tid & 31, g = lane >> 2, t = lane & 3, j8 = lane & 7, mat = lane >> 3;
    const uint32_t wi_ = __reduce_max_sync(0xFFFFFFFFu, tid >> 5), q = wi_ >> 2, w = wi_ & 3;
    const int cta = blockIdx.x;
    const int nt = cta < 64 ? (64 - cta + nw - 1) / nw : 0;
    const uint32_t bar = sb + FS_BAR;
    if (tid == 0) {
        for (int i = 0; i < 30; i++) mbar_init(bar + i * 8, i < 3 ? 4 : i < 6 ? 16 : i >= 14 && i < 18 ? 2 : 1);
        asm volatile("fence.mbarrier_init.release.cluster;" ::: "memory");
        fence_smem();
    }
    __syncthreads();
#define FT(n)
    FT(0);
#define N2(p) (2 * ((p) & 31) + ((p) >> 5))
#define WLOAD(tk, part) { \
        const uint32_t wd_ = sb + 131072 + q * 18432 + (part) * 9216, wb_ = bar + 112 + q * 8; \
        mbar_expect(wb_, 9216); \
        if ((tk) < 256) tma3d(wd_, (part) ? &tmwi : &tmwr, wb_, ((tk) & 63) * 64, (tk) >> 6, 0); \
        else asm volatile("cp.async.bulk.shared::cluster.global.mbarrier::complete_tx::bytes [%0], [%1], 9216, [%2];" \
                          ::"r"(wd_), "l"(g_WN + (part) * 576), "r"(wb_) : "memory"); }
#define GROW(tk) ((tk) < 256 ? ((tk) >> 5) * 64 + ((tk) & 7) * 8 + (((tk) >> 3) & 3) * 2 : 512)
#define DLOAD(tk, sl) { mbar_expect(bar + 48 + (sl) * 8, 16384); tma3d(sb + (sl) * 16384, &tmg2, bar + 48 + (sl) * 8, 0, GROW(tk), 0); }
#define IO(c) if (w == 3 && (c) && elect())
#define XLOAD1(i, bb) { const uint32_t xb_ = bar + 144 + (bb) * 32 + q * 8; mbar_expect(xb_, 16384); tma4d(sb + (bb) * 65536 + q * 16384, &tmx, xb_, 0, 0, q * 8, N2(cta + (i) * nw)); }
#define GLOAD3(i, bb) { mbar_expect(bar + (bb) * 8, q ? 16384 : 16512); tma3d(sb + (bb) * 65536 + q * 16384, &tmg1, bar + (bb) * 8, 0, q * 128, cta + (i) * nw); \
        if (q == 0) asm volatile("cp.async.bulk.shared::cluster.global.mbarrier::complete_tx::bytes [%0], [%1], 128, [%2];" \
                                 ::"r"(sb + FS_NQ + (bb) * 1024), "l"(g_GN + (cta + (i) * nw) * 8), "r"(bar + (bb) * 8) : "memory"); }
    for (int i = 0; i < 3; i++) IO(i < nt) XLOAD1(i, i);
    for (uint32_t x = tid; x < 40 * 32; x += 512) {
        const uint32_t n = x >> 5, m2 = mat * 8 + t * 2, ri = g & 1;
        const uint32_t c2 = ((n >> 1) & 1) + ((n >> 3) & 1) * 2 + (n & 4) + (n >> 4) * 8;
        const uint32_t v = cos2(m2 * c2 * 64 + ((n & 1) - ri) * 512, (m2 + 1) * c2 * 64 + ((n & 1) - ri) * 512);
        sts32(sb + FS_F2 + n * 128 + ((g ^ (n & 7)) << 4) + t * 4, n < 32 ? v : n == 32 && ri == 0 ? 0xBF003F00u : 0u);
    }
    float tc[8], ts[8];
    uint32_t F[2][4];
    uint32_t c1 = 16 * (w >> 1) + 2 * g + (w & 1);
#pragma unroll
    for (int i = 0; i < 8; i++) {
        twid(c1 * (8 * (i >> 1) + 2 * t + (i & 1)), tc[i], ts[i]);
        const uint32_t m1 = (i >> 1) * 8 + 2 * t;
        F[i >> 2][i & 3] = cos2(c1 * m1 * 64 + (i & 1) * 512, c1 * (m1 + 1) * 64 + (i & 1) * 512);
    }
    {
        const uint32_t kr = (2 * (mat & 1) + (j8 & 1)) ^ ((j8 >> 2) << 1);
        const uint32_t so1 = ((mat >> 1) + 2 * (j8 >> 2)) * 1024 + kr * 128 + (((((j8 >> 1) & 1) * 4 + w) ^ kr) << 4);
        const uint32_t so2 = (2 * w + (mat & 1)) * 8192 + q * 2048 + j8 * 128 + (((mat >> 1) ^ j8) << 4);
        uint32_t so = so1 << 16 | so2;
        const float fx = (tid & 127) == 0 ? 0.5f : 1.f;
        fft_gen<false>(sb + FS_TB, N2(cta));
        fence_smem();
        bsync<1, 512>();
        FT(1);
        int b = 0, bp = 2, ph = 0;
        if (nt) mwait(bar + 144 + q * 8, 0);
        __syncwarp();
        auto step = [&](auto first, auto last, const int i) {
            const uint32_t p = cta + i * nw, bn = 3 - b - bp, tb = (i & 1) * 8192;
            const uint32_t grp = sb + b * 65536 + q * 16384, nq = sb + FS_NQ + b * 1024 + q * 32;
            auto sa = [&]() {
                if constexpr (!decltype(first)::v) {
                    fence_smem();
                    __syncwarp();
                    if (elect()) mbar_arrive(bar + 24);
                }
                IO(i > 1) {
                    mwait(bar + 32, i & 1);
                    tma3s(&tmg1, sb + bn * 65536 + q * 16384, 0, q * 128, p - 2 * nw);
                    bulk_commit();
                }
            };
            auto sb_ = [&]() { if constexpr (!decltype(first)::v) mwait(bar + 24, (i - 1) & 1); };
            if constexpr (!decltype(last)::v) fft_rows<false>(grp, q, F, tc, ts, opq(so, zero) >> 16, fx, nq, sa, sb_);
            else { sa(); __syncwarp(); sb_(); __syncwarp(); }
            if constexpr (!decltype(first)::v) {
                float n[4];
                fft_cross<false>(sb + bp * 65536, q, sb + FS_TB + 8192 - tb + (((tidx() & 127) ^ (q & 1)) << 4), opq(so, zero) & 0xFFFF, sb + FS_NQ + bp * 1024, n, [&]() {
                    fft_gen<false>(sb + FS_TB + tb, N2(p));
                    IO(i >= 2 && i + 1 < nt) {
                        asm volatile("cp.async.bulk.wait_group.read 0;" ::: "memory");
                        XLOAD1(i + 1, bn);
                    }
                });
                if (q == 0) {
                    const uint32_t x = tidx();
                    bf16* z = (bf16*)(g_G + ((p - nw) * G_ROWS + 512) * 8) + (x & 4) * 16 + ((x >> 2) & 24) + ((x >> 3) & 3);
                    asm volatile("{\n.reg .pred p;\n.reg .b16 a, b;\nsetp.eq.u32 p, %2, 0;\nmov.b32 {a, b}, %1;\n@p st.global.u16 [%0], a;\n@p st.global.u16 [%0+8], b;\n}"
                                 ::"l"(z), "r"(pack2(n[0], n[2])), "r"(x & 3) : "memory");
                }
            }
            if constexpr (!decltype(last)::v) {
                fft_rows<false>(grp + 8192, q, F, tc, ts, opq(so, zero) >> 16, fx, nq + 16, [&]() {
                    if constexpr (!decltype(first)::v) {
                        fence_smem();
                        __syncwarp();
                        if (elect()) mbar_arrive(bar + 32);
                    }
                    if ((w == 1 || w == 2) && elect())
                        asm volatile("cp.async.bulk.prefetch.L2.global [%0], 8208;" ::"l"((w == 1 ? wr : wi) + (p * 4 + q) * 4104) : "memory");
                }, [&]() { if (i + 1 < nt) mwait(bar + 144 + bn * 32 + q * 8, bn ? ph : ph ^ 1); });
                bp = b;
                if (++b == 3) { b = 0; ph ^= 1; }
            }
        };
        if (nt) {
            step(Bool<true>(), Bool<false>(), 0);
#pragma unroll 1
            for (int i = 1; i < nt; i++) step(Bool<false>(), Bool<false>(), i);
            step(Bool<false>(), Bool<true>(), nt);
        }
        for (uint32_t x = cta * 512 + tid; x < 4096; x += nw * 512)
            ((bf16*)g_WN)[(x >> 5) * 72 + (x & 16) + (x & 7) * 2 + ((x >> 3) & 1)] = (x < 2048 ? wr : wi)[(x & 2047) * 513 + 512];
        FT(2);
        fence_async();
        bsync<1, 512>();
        IO(nt) { tma3s(&tmg1, sb + bp * 65536 + q * 16384, 0, q * 128, cta + (nt - 1) * nw); bulk_commit(); }
    }
    for (uint32_t x = tid; x < 128 * 32; x += 512) {
        const uint32_t n = (x >> 5) & 63, a = x & 31, k2 = (n >> 4) * 8 + (n & 7);
        sts32(sb + FS_TB + (x >> 5) * 128 + (((a >> 2) ^ (n & 7)) << 4) + (a & 3) * 4, cis((2 * a + (x >> 11)) * k2 * 32 + (n & 8) * 64));
    }
    fence_smem();
    bsync<1, 512>();
    IO(true) {
        asm volatile("cp.async.bulk.wait_group 0;" ::: "memory");
        grid_arrive(cnt, 4 * nw);
        grid_wait(cnt);
        const int tk = cta + q * nw;
        if (tk <= 256) { DLOAD(tk, q); WLOAD(tk, 0); WLOAD(tk, 1); }
    }
    __syncwarp();
    {
        const uint32_t lo = j8 * 128 + (((2 * w + (mat & 1)) ^ j8) << 4);
        const uint32_t aw = sb + 131072 + q * 18432 + t * 288 + w * 32 + g * 4;
        const uint64_t df = mkdesc(sb + FS_TB, 16, 1024);
        const uint64_t da = mkdesc(sb + q * 16384, 16, 1024);
        const uint32_t buf = sb + 65536 + q * 16384;
        int i = 0, tk = cta + q * nw;
        if (tk <= 256) mwait(bar + 48 + q * 8, 0);
        FT(3);
#pragma unroll 1
        for (; tk <= 256; tk += 4 * nw, i++) {
            const bool more = tk + 4 * nw <= 256;
            float e[32], o[32];
            wg_fence();
#pragma unroll
            for (int s = 0; s < 4; s++) { if (s == 0) wg_ss64a<0>(e, da, df); else wg_ss64a<1>(e, da + s * 128, df + s * 2); }
#pragma unroll
            for (int s = 0; s < 4; s++) { if (s == 0) wg_ss64a<0>(o, da + 512, df + 512); else wg_ss64a<1>(o, da + 512 + s * 128, df + 512 + s * 2); }
            wg_commit();
            SF();
            if (i > 0) {
                fence_smem();
                wgbar(q);
                IO(true) { tma3s(&tmg2, buf, 0, GROW(tk - 4 * nw), 0); bulk_commit(); }
            }
            if (w == 2 && more && elect()) mbar_expect(bar + 48 + q * 8, 16384);
            const int gr = GROW(tk + 4 * nw);
            mwait(bar + 112 + q * 8, i & 1);
            wg_wait<0>();
            if (w == 2 && more && elect()) tma3d(sb + q * 16384, &tmg2, bar + 48 + q * 8, 0, gr, 0);
            uint32_t u[4][4], v[4][4];
            if (tk & 8) fft_filter<true>(aw + (tk & 48) / 4, e, o, u, v);
            else fft_filter<false>(aw + (tk & 48) / 4, e, o, u, v);
            wg_fence();
#pragma unroll
            for (int s = 0; s < 4; s++) { if (s == 0) wg_rs64t<0>(e, u[s], df); else wg_rs64t<1>(e, u[s], df + s * 128); }
#pragma unroll
            for (int s = 0; s < 4; s++) { if (s == 0) wg_rs64t<0>(o, v[s], df + 512); else wg_rs64t<1>(o, v[s], df + 512 + s * 128); }
            wg_commit();
            SF();
            IO(true) asm volatile("cp.async.bulk.wait_group.read 0;" ::: "memory");
            wgbar(q);
            if (more) {
                if ((w == 1 || w == 2) && elect()) WLOAD(tk + 4 * nw, w - 1);
                mwait(bar + 48 + q * 8, (i + 1) & 1);
            }
            wg_wait<0>();
#pragma unroll
            for (int s = 0; s < 4; s++) {
                const uint32_t a = buf + (mat >> 1) * 1024 + lo + s * 2048;
                stsm4t(a, pack2(e[8 * s], e[8 * s + 1]), pack2(e[8 * s + 2], e[8 * s + 3]), pack2(e[8 * s + 4], e[8 * s + 5]), pack2(e[8 * s + 6], e[8 * s + 7]));
                stsm4t(a + 8192, pack2(o[8 * s], o[8 * s + 1]), pack2(o[8 * s + 2], o[8 * s + 3]), pack2(o[8 * s + 4], o[8 * s + 5]), pack2(o[8 * s + 6], o[8 * s + 7]));
            }
            if (tk == 256 && w < 2) {
                uint32_t* z = (uint32_t*)g_GN + t * 32 + w * 16 + g;
#pragma unroll
                for (int s = 0; s < 16; s++) {
                    z[(s >> 1) * 128 + (s & 1) * 8] = pack2(e[2 * s], e[2 * s + 1]);
                    z[(s >> 1) * 128 + (s & 1) * 8 + 1024] = pack2(o[2 * s], o[2 * s + 1]);
                }
                fence_async();
            }
        }
        fence_smem();
        wgbar(q);
        IO(true) {
            if (i > 0) { tma3s(&tmg2, buf, 0, GROW(tk - 4 * nw), 0); bulk_commit(); }
            asm volatile("cp.async.bulk.wait_group 0;" ::: "memory");
            grid_arrive(cnt + 1, 4 * nw);
        }
    }
    FT(4);
    bsync<1, 512>();
    {
        for (uint32_t n = wi_; n < 32; n += 16) {
            const uint32_t cl = (mat >> 1) * 16 + t * 4 + (mat & 1), mh = ((n >> 3) & 1) + (n & 7) * 2 + (n & 16);
            sts32(sb + FS_F2 + n * 128 + ((g ^ (n & 7)) << 4) + t * 4, cos2(cl * mh * 64 + (g & 1) * 512, (cl + 2) * mh * 64 + (g & 1) * 512));
        }
        fence_smem();
        c1 = 8 * w + g;
#pragma unroll
        for (int i = 0; i < 8; i++) {
            twid(-c1 * (16 * (i >> 2) + 4 * t + 2 * (i & 1) + ((i >> 1) & 1)), tc[i], ts[i]);
            F[i >> 2][i & 3] = cis((i & 1) * 512 - c1 * ((i >> 1) * 4 + (t ^ (q & 1))) * 64);
        }
        const uint32_t kr = (j8 & 1) ^ ((j8 >> 2) << 1);
        const uint32_t so2 = ((w >> 1) * 4 + (j8 >> 2) * 2 + (w & 1)) * 8192 + (2 * q + (mat & 1)) * 1024 + kr * 128 + (((((j8 >> 1) & 1) * 4 + (mat >> 1)) ^ kr) << 4);
        const uint32_t so1 = (mat & 1) * 2048 + j8 * 128 + ((((mat >> 1) * 4 + w) ^ j8) << 4);
        uint32_t so = so1 << 16 | so2;
        const float fx = t ? 0.f : (g & 1) ? -1.f : 1.f;
        fft_gen<true>(sb + FS_TB, N2(cta));
        bsync<1, 512>();
        IO(true) grid_wait(cnt + 1);
        for (int i = 0; i < 3; i++) IO(i < nt) GLOAD3(i, i);
        __syncwarp();
        int b = 0, bp = 2, ph = 0;
        auto step = [&](auto first, auto last, const int i) {
            const uint32_t p = cta + i * nw, bn = 3 - b - bp, tb = (i & 1) * 8192;
            const uint32_t grp = sb + bp * 65536 + q * 16384, ny = sb + FS_NY + bp * 128 + q * 32;
            auto sb_ = [&]() { if constexpr (!decltype(last)::v) mwait(bar + b * 8, ph); };
            if constexpr (!decltype(first)::v) {
                fft_rows<true>(grp, q, F, tc, ts, opq(so, zero) >> 16, fx, ny, [&]() {
                    if (i > 1) {
                        fence_smem();
                        wgbar(q);
                        IO(true) { tma4s(&tmy, sb + bn * 65536 + q * 16384, 0, 0, q * 8, N2(p - 2 * nw)); bulk_commit(); }
                    }
                }, sb_);
            } else { sb_(); __syncwarp(); }
            if constexpr (decltype(first)::v) FT(5);
            if constexpr (!decltype(last)::v) {
                float n[4];
                fft_cross<true>(sb + b * 65536, q, sb + FS_TB + tb + (tidx() & 127) * 16, opq(so, zero) & 0xFFFF, sb + FS_NQ + b * 1024, n, [&]() {
                    fft_gen<true>(sb + FS_TB + 8192 - tb, N2(p + nw));
                    IO(i >= 2 && i + 1 < nt) {
                        asm volatile("cp.async.bulk.wait_group.read 0;" ::: "memory");
                        GLOAD3(i + 1, bn);
                    }
                });
                if (q == 0) {
                    const uint32_t x = tidx(), a = sb + FS_NY + b * 128 + (x & 64) + (x & 16) * 2 + ((x & 40) >> 1);
                    if ((x & 7) == 0) { sts32f(a, n[0]); sts32f(a + 8, n[2]); }
                }
            }
            auto sc = [&]() {
                if constexpr (!decltype(last)::v) {
                    fence_smem();
                    __syncwarp();
                    if (elect()) mbar_arrive(bar + 24);
                }
            };
            auto sd = [&]() { if constexpr (!decltype(last)::v) mwait(bar + 24, (nt + i) & 1); };
            if constexpr (!decltype(first)::v) fft_rows<true>(grp + 8192, q, F, tc, ts, opq(so, zero) >> 16, fx, ny + 16, sc, sd);
            else { sc(); __syncwarp(); sd(); __syncwarp(); }
            if constexpr (!decltype(last)::v) {
                bp = b;
                if (++b == 3) { b = 0; ph ^= 1; }
            }
        };
        if (nt) {
            step(Bool<true>(), Bool<false>(), 0);
#pragma unroll 1
            for (int i = 1; i < nt; i++) step(Bool<false>(), Bool<false>(), i);
            step(Bool<false>(), Bool<true>(), nt);
        }
        fence_smem();
        wgbar(q);
        IO(nt) { tma4s(&tmy, sb + bp * 65536 + q * 16384, 0, 0, q * 8, N2(cta + (nt - 1) * nw)); bulk_commit(); }
        FT(6);
        IO(true) asm volatile("cp.async.bulk.wait_group 0;" ::: "memory");
    }
}

typedef CUresult (*EncodeFn)(CUtensorMap*, CUtensorMapDataType, cuuint32_t, void*, const cuuint64_t*, const cuuint64_t*,
                             const cuuint32_t*, const cuuint32_t*, CUtensorMapInterleave, CUtensorMapSwizzle,
                             CUtensorMapL2promotion, CUtensorMapFloatOOBfill);

static void make_map(EncodeFn enc, CUtensorMap* m, const void* ptr, int rank, const cuuint64_t* dims, const cuuint64_t* strides,
                     const cuuint32_t* box, CUtensorMapSwizzle sw = CU_TENSOR_MAP_SWIZZLE_128B) {
    cuuint32_t es[4] = {1, 1, 1, 1};
    CUresult r = enc(m, CU_TENSOR_MAP_DATA_TYPE_BFLOAT16, rank, (void*)ptr, dims, strides, box, es, CU_TENSOR_MAP_INTERLEAVE_NONE,
                     sw, CU_TENSOR_MAP_L2_PROMOTION_L2_256B, CU_TENSOR_MAP_FLOAT_OOB_FILL_NONE);
    if (r != CUDA_SUCCESS) fprintf(stderr, "tensor map encode failed: %d\n", (int)r);
}

extern "C" void kernel_launch(void* const* d_in, const int* in_sizes, int n_in, void* d_out, int out_size) {
    const bf16* A_x = (const bf16*)d_in[0];
    const bf16* A_mem0 = (const bf16*)d_in[1];
    const bf16* A_Wq = (const bf16*)d_in[2];
    const bf16* A_Wk = (const bf16*)d_in[3];
    const bf16* A_Wv = (const bf16*)d_in[4];
    const bf16* A_Wo = (const bf16*)d_in[5];
    const bf16* B_x = (const bf16*)d_in[7];
    const bf16* B_wr = (const bf16*)d_in[8];
    const bf16* B_wi = (const bf16*)d_in[9];
    bf16* out = (bf16*)d_out;

    static EncodeFn enc = nullptr;
    static void *pxs = nullptr, *pg = nullptr;
    static int ncl = 64;
    if (!enc) {
        cudaDriverEntryPointQueryResult qr;
        void* fn = nullptr;
        cudaGetDriverEntryPoint("cuTensorMapEncodeTiled", &fn, cudaEnableDefault, &qr);
        enc = (EncodeFn)fn;
        cudaFuncSetAttribute(chain_kernel, cudaFuncAttributeMaxDynamicSharedMemorySize, SM_TOTAL);
        cudaFuncSetAttribute(post_kernel, cudaFuncAttributeMaxDynamicSharedMemorySize, FS_TOTAL);
        cudaGetSymbolAddress(&pxs, g_xs);
        cudaGetSymbolAddress(&pg, g_G);
        cudaLaunchConfig_t lc = {};
        cudaLaunchAttribute at;
        at.id = cudaLaunchAttributeClusterDimension;
        at.val.clusterDim.x = 2; at.val.clusterDim.y = 1; at.val.clusterDim.z = 1;
        lc.gridDim = dim3(132); lc.blockDim = dim3(384); lc.dynamicSmemBytes = SM_TOTAL; lc.attrs = &at; lc.numAttrs = 1;
        int nc = 0;
        if (cudaOccupancyMaxActiveClusters(&nc, chain_kernel, &lc) == cudaSuccess && nc > 64) ncl = nc < 66 ? nc : 66;
    }
    CUtensorMap tmq, tmk, tmv, tmo, tmx, tmb, tmy;
    {
        cuuint64_t d[3] = {64, DM, HD / 64}, st[2] = {HD * 2, 128};
        cuuint32_t bx[3] = {64, 64, 2};
        make_map(enc, &tmq, A_Wq, 3, d, st, bx);
        make_map(enc, &tmk, A_Wk, 3, d, st, bx);
        make_map(enc, &tmv, A_Wv, 3, d, st, bx);
    }
    {
        cuuint64_t d[2] = {DM, HD}, st[1] = {DM * 2};
        cuuint32_t bx[2] = {64, 16}, bx1[2] = {64, 128}, bx2[3] = {64, 64, 2};
        make_map(enc, &tmo, A_Wo, 2, d, st, bx1);
        cuuint64_t d2[3] = {64, HD, DM / 64}, st2[2] = {DM * 2, 128}, d3[2] = {DM, SEQ}, st3[1] = {DM * 4};
        make_map(enc, &tmb, A_Wo, 3, d2, st2, bx2);
        make_map(enc, &tmy, out, 2, d3, st3, bx);
    }
    {
        cuuint64_t d[3] = {64, SEQ, DM / 64}, st[2] = {DM * 2, 128};
        cuuint32_t bx[3] = {64, 8, 4};
        make_map(enc, &tmx, A_x, 3, d, st, bx);
    }
    CUtensorMap fx, fg1, fg2, fwr, fwi, fy;
    {
        cuuint64_t d[4] = {32, 32, 32, 64}, st[3] = {64, 64 * DM * 2, DM * 2};
        cuuint32_t bx[4] = {32, 32, 8, 1};
        make_map(enc, &fx, B_x, 4, d, st, bx, CU_TENSOR_MAP_SWIZZLE_64B);
        cuuint64_t d2[4] = {64, 16, 32, 64}, st2[3] = {128, 64 * 4096, 4096};
        cuuint32_t bx2[4] = {64, 16, 8, 1};
        make_map(enc, &fy, out + DM, 4, d2, st2, bx2);
    }
    {
        cuuint64_t d[3] = {64, G_ROWS, 64}, st[2] = {128, G_ROWS * 128};
        cuuint32_t bx[3] = {64, 128, 1}, bx2[3] = {64, 2, 64};
        make_map(enc, &fg1, pg, 3, d, st, bx);
        make_map(enc, &fg2, pg, 3, d, st, bx2);
        cuuint64_t d2[3] = {8 * 513, 4, 64}, st2[2] = {8 * 513 * 2, 32 * 513 * 2};
        cuuint32_t bx3[3] = {72, 1, 64};
        make_map(enc, &fwr, B_wr, 3, d2, st2, bx3, CU_TENSOR_MAP_SWIZZLE_NONE);
        make_map(enc, &fwi, B_wi, 3, d2, st2, bx3, CU_TENSOR_MAP_SWIZZLE_NONE);
    }
    cudaStream_t st = cudaStreamPerThread;
    const uint64_t xs = ((uint64_t)pxs + XS_BYTES - 1) & ~(uint64_t)(XS_BYTES - 1);
    chain_kernel<<<2 * ncl, 384, SM_TOTAL, st>>>(tmq, tmk, tmv, tmo, tmx, tmb, tmy, A_mem0, A_x, (uint32_t)xs, (uint32_t)(xs >> 32), 0u, NSEG, out);
    int nw = ncl == 66 ? 4 : 64;
    cudaLaunchConfig_t lc = {};
    cudaLaunchAttribute at;
    at.id = cudaLaunchAttributeProgrammaticStreamSerialization;
    at.val.programmaticStreamSerializationAllowed = 1;
    lc.gridDim = dim3(nw); lc.blockDim = dim3(F_THREADS); lc.dynamicSmemBytes = FS_TOTAL; lc.stream = st; lc.attrs = &at; lc.numAttrs = 1;
    cudaLaunchKernelEx(&lc, post_kernel, fx, fg1, fg2, fwr, fwi, fy, B_wr, B_wi, (uint32_t*)(xs + XO_TK + 256), 0u, nw);
}
```

```cpp
#include <cuda_runtime.h>
#include <cuda_bf16.h>
#include <cuda.h>
#include <stdint.h>
#include <stdio.h>

typedef __nv_bfloat16 bf16;

#define SEQ 2048
#define DM 1024
#define NH 32
#define DH 128
#define NSEG 64
#define HD (NH * DH)

#define XS_BYTES (32u << 20)
__device__ uint4 g_xs[2 * XS_BYTES / 16];
#define XO_R 0u
#define XO_PB (1u << 18)
#define XO_FL (XO_PB + 32768u)
#define XO_TK (XO_FL + 4096u)
#define XO_CQK (1u << 20)
#define XO_CV (2u << 20)
#define XO_XG (4u << 20)
#define XO_OX (16u << 20)
#define GSYNC(n)
#define PG(n)

#define DEVI __device__ __forceinline__

DEVI void die(int it) { asm volatile("st.shared.u32 [%0], %0;" ::"r"(it) : "memory"); }
DEVI uint32_t smem_u32(const void* p) { return (uint32_t)__cvta_generic_to_shared(p); }
DEVI void mbar_init(uint32_t bar, uint32_t cnt) { asm volatile("mbarrier.init.shared::cta.b64 [%0], %1;" ::"r"(bar), "r"(cnt) : "memory"); }
DEVI void mbar_expect(uint32_t bar, uint32_t bytes) { asm volatile("mbarrier.arrive.expect_tx.shared::cta.b64 _, [%0], %1;" ::"r"(bar), "r"(bytes) : "memory"); }
DEVI void mbar_arrive(uint32_t bar) { asm volatile("mbarrier.arrive.shared::cta.b64 _, [%0];" ::"r"(bar) : "memory"); }
DEVI void mbar_wait(uint32_t bar, uint32_t parity) {
    uint32_t done;
    int it = 0;
    do {
        asm volatile("{\n.reg .pred p;\nmbarrier.try_wait.parity.shared::cta.b64 p, [%1], %2;\nselp.u32 %0, 1, 0, p;\n}\n"
                     : "=r"(done) : "r"(bar), "r"(parity) : "memory");
        if (++it > (1 << 22)) die(it);
    } while (!done);
}
DEVI void tma2d(uint32_t dst, const CUtensorMap* tm, uint32_t bar, int c0, int c1) {
    asm volatile("cp.async.bulk.tensor.2d.shared::cluster.global.mbarrier::complete_tx::bytes [%0], [%1, {%3, %4}], [%2];"
                 ::"r"(dst), "l"(tm), "r"(bar), "r"(c0), "r"(c1) : "memory");
}
DEVI void tma3d(uint32_t dst, const CUtensorMap* tm, uint32_t bar, int c0, int c1, int c2) {
    asm volatile("cp.async.bulk.tensor.3d.shared::cluster.global.mbarrier::complete_tx::bytes [%0], [%1, {%3, %4, %5}], [%2];"
                 ::"r"(dst), "l"(tm), "r"(bar), "r"(c0), "r"(c1), "r"(c2) : "memory");
}
DEVI void bulk_g2s(uint32_t dst, uint32_t lo, uint32_t hi, uint32_t bytes, uint32_t bar) {
    asm volatile("{\n.reg .b64 a;\nmov.b64 a, {%1,%2};\ncp.async.bulk.shared::cluster.global.mbarrier::complete_tx::bytes [%0], [a], %3, [%4];\n}"
                 ::"r"(dst), "r"(lo), "r"(hi), "r"(bytes), "r"(bar) : "memory");
}
DEVI void bulk_s2g(uint32_t lo, uint32_t hi, uint32_t src, uint32_t bytes) {
    asm volatile("{\n.reg .b64 a;\nmov.b64 a, {%0,%1};\ncp.async.bulk.global.shared::cta.bulk_group [a], [%2], %3;\ncp.async.bulk.commit_group;\n}"
                 ::"r"(lo), "r"(hi), "r"(src), "r"(bytes) : "memory");
}
DEVI void bulk_red(uint32_t lo, uint32_t hi, uint32_t src, uint32_t bytes) {
    asm volatile("{\n.reg .b64 a;\nmov.b64 a, {%0,%1};\ncp.reduce.async.bulk.global.shared::cta.bulk_group.add.noftz.bf16 [a], [%2], %3;\ncp.async.bulk.commit_group;\n}"
                 ::"r"(lo), "r"(hi), "r"(src), "r"(bytes) : "memory");
}
DEVI bool elect() {
    uint32_t p;
    asm volatile("{\n.reg .pred P;\nelect.sync _|P, 0xFFFFFFFF;\nselp.u32 %0, 1, 0, P;\n}" : "=r"(p));
    return p != 0;
}
DEVI void ldsm4(uint32_t (&r)[4], uint32_t a) {
    asm volatile("ldmatrix.sync.aligned.m8n8.x4.shared.b16 {%0,%1,%2,%3}, [%4];" : "=r"(r[0]), "=r"(r[1]), "=r"(r[2]), "=r"(r[3]) : "r"(a) : "memory");
}
DEVI void ldsm4t(uint32_t (&r)[4], uint32_t a) {
    asm volatile("ldmatrix.sync.aligned.m8n8.x4.trans.shared.b16 {%0,%1,%2,%3}, [%4];" : "=r"(r[0]), "=r"(r[1]), "=r"(r[2]), "=r"(r[3]) : "r"(a) : "memory");
}
DEVI void ldsm2t(uint32_t (&r)[2], uint32_t a) {
    asm volatile("ldmatrix.sync.aligned.m8n8.x2.trans.shared.b16 {%0,%1}, [%2];" : "=r"(r[0]), "=r"(r[1]) : "r"(a) : "memory");
}
DEVI void ldsm2(uint32_t (&r)[2], uint32_t a) {
    asm volatile("ldmatrix.sync.aligned.m8n8.x2.shared.b16 {%0,%1}, [%2];" : "=r"(r[0]), "=r"(r[1]) : "r"(a) : "memory");
}
DEVI void stsm4t(uint32_t a, uint32_t r0, uint32_t r1, uint32_t r2, uint32_t r3) {
    asm volatile("stmatrix.sync.aligned.m8n8.x4.trans.shared.b16 [%0], {%1,%2,%3,%4};" ::"r"(a), "r"(r0), "r"(r1), "r"(r2), "r"(r3) : "memory");
}
DEVI uint32_t ldsm1(uint32_t a) {
    uint32_t r;
    asm volatile("ldmatrix.sync.aligned.m8n8.x1.shared.b16 {%0}, [%1];" : "=r"(r) : "r"(a) : "memory");
    return r;
}
DEVI void stsm4(uint32_t a, uint32_t r0, uint32_t r1, uint32_t r2, uint32_t r3) {
    asm volatile("stmatrix.sync.aligned.m8n8.x4.shared.b16 [%0], {%1,%2,%3,%4};" ::"r"(a), "r"(r0), "r"(r1), "r"(r2), "r"(r3) : "memory");
}
DEVI void stsm2(uint32_t a, uint32_t r0, uint32_t r1) {
    asm volatile("stmatrix.sync.aligned.m8n8.x2.shared.b16 [%0], {%1,%2};" ::"r"(a), "r"(r0), "r"(r1) : "memory");
}
DEVI uint32_t movm(uint32_t a) {
    uint32_t d;
    asm volatile("movmatrix.sync.aligned.m8n8.trans.b16 %0, %1;" : "=r"(d) : "r"(a));
    return d;
}
DEVI void mma16(float (&d)[4], uint32_t a0, uint32_t a1, uint32_t a2, uint32_t a3, uint32_t b0, uint32_t b1) {
    asm volatile("mma.sync.aligned.m16n8k16.row.col.f32.bf16.bf16.f32 {%0,%1,%2,%3}, {%4,%5,%6,%7}, {%8,%9}, {%0,%1,%2,%3};"
                 : "+f"(d[0]), "+f"(d[1]), "+f"(d[2]), "+f"(d[3]) : "r"(a0), "r"(a1), "r"(a2), "r"(a3), "r"(b0), "r"(b1));
}
DEVI void mma16z(float (&d)[4], uint32_t a0, uint32_t a1, uint32_t a2, uint32_t a3, uint32_t b0, uint32_t b1) {
    asm volatile("mma.sync.aligned.m16n8k16.row.col.f32.bf16.bf16.f32 {%0,%1,%2,%3}, {%4,%5,%6,%7}, {%8,%9}, {%10,%10,%10,%10};"
                 : "=f"(d[0]), "=f"(d[1]), "=f"(d[2]), "=f"(d[3]) : "r"(a0), "r"(a1), "r"(a2), "r"(a3), "r"(b0), "r"(b1), "f"(0.f));
}
DEVI void mma8(float (&d)[4], uint32_t a0, uint32_t a1, uint32_t b0) {
    asm volatile("mma.sync.aligned.m16n8k8.row.col.f32.bf16.bf16.f32 {%0,%1,%2,%3}, {%4,%5}, {%6}, {%0,%1,%2,%3};"
                 : "+f"(d[0]), "+f"(d[1]), "+f"(d[2]), "+f"(d[3]) : "r"(a0), "r"(a1), "r"(b0));
}
DEVI void mma8z(float (&d)[4], uint32_t a0, uint32_t a1, uint32_t b0) {
    asm volatile("mma.sync.aligned.m16n8k8.row.col.f32.bf16.bf16.f32 {%0,%1,%2,%3}, {%4,%5}, {%6}, {%7,%7,%7,%7};"
                 : "=f"(d[0]), "=f"(d[1]), "=f"(d[2]), "=f"(d[3]) : "r"(a0), "r"(a1), "r"(b0), "f"(0.f));
}
DEVI uint32_t pack2(float lo, float hi) {
    uint32_t r;
    asm("cvt.rn.bf16x2.f32 %0, %1, %2;" : "=r"(r) : "f"(hi), "f"(lo));
    return r;
}
DEVI uint32_t hadd2(uint32_t a, uint32_t b) {
    uint32_t r;
    asm("add.rn.bf16x2 %0, %1, %2;" : "=r"(r) : "r"(a), "r"(b));
    return r;
}
DEVI float lo_f(uint32_t x) { return __uint_as_float(x << 16); }
DEVI float hi_f(uint32_t x) { return __uint_as_float(x & 0xFFFF0000u); }
template <uint32_t OFF> DEVI uint4 ldg4(uint32_t lo, uint32_t hi) {
    uint4 v;
    asm volatile("{\n.reg .b64 a;\nmov.b64 a, {%4,%5};\nld.relaxed.gpu.global.v4.u32 {%0,%1,%2,%3}, [a+%6];\n}"
                 : "=r"(v.x), "=r"(v.y), "=r"(v.z), "=r"(v.w) : "r"(lo), "r"(hi), "n"(OFF) : "memory");
    return v;
}
template <uint32_t OFF> DEVI uint2 ldg2(uint32_t lo, uint32_t hi) {
    uint2 v;
    asm volatile("{\n.reg .b64 a;\nmov.b64 a, {%2,%3};\nld.relaxed.gpu.global.v2.u32 {%0,%1}, [a+%4];\n}"
                 : "=r"(v.x), "=r"(v.y) : "r"(lo), "r"(hi), "n"(OFF) : "memory");
    return v;
}
template <uint32_t OFF> DEVI uint32_t ldg1(uint32_t lo, uint32_t hi) {
    uint32_t v;
    asm volatile("{\n.reg .b64 a;\nmov.b64 a, {%1,%2};\nld.relaxed.gpu.global.u32 %0, [a+%3];\n}" : "=r"(v) : "r"(lo), "r"(hi), "n"(OFF) : "memory");
    return v;
}
template <uint32_t OFF> DEVI void stg1(uint32_t lo, uint32_t hi, uint32_t a) {
    asm volatile("{\n.reg .b64 a;\nmov.b64 a, {%0,%1};\nst.relaxed.gpu.global.u32 [a+%3], %2;\n}" ::"r"(lo), "r"(hi), "r"(a), "n"(OFF) : "memory");
}
template <uint32_t OFF> DEVI void stg4(uint32_t lo, uint32_t hi, uint32_t a, uint32_t b, uint32_t c, uint32_t d) {
    asm volatile("{\n.reg .b64 a;\nmov.b64 a, {%0,%1};\nst.relaxed.gpu.global.v4.u32 [a+%6], {%2,%3,%4,%5};\n}"
                 ::"r"(lo), "r"(hi), "r"(a), "r"(b), "r"(c), "r"(d), "n"(OFF) : "memory");
}
template <uint32_t OFF> DEVI void stg2(uint32_t lo, uint32_t hi, uint32_t a, uint32_t b) {
    asm volatile("{\n.reg .b64 a;\nmov.b64 a, {%0,%1};\nst.relaxed.gpu.global.v2.u32 [a+%4], {%2,%3};\n}"
                 ::"r"(lo), "r"(hi), "r"(a), "r"(b), "n"(OFF) : "memory");
}
DEVI uint32_t tagx2(uint32_t a, uint32_t b, uint32_t t) { uint32_t r; asm("lop3.b32 %0, %1, %2, %3, 0x7E;" : "=r"(r) : "r"(a), "r"(b), "r"(t)); return r; }
DEVI uint32_t tagx1(uint32_t a, uint32_t b, uint32_t t) { uint32_t r; asm("lop3.b32 %0, %1, %2, %3, 0xF6;" : "=r"(r) : "r"(a), "r"(b), "r"(t)); return r; }
DEVI uint32_t or3(uint32_t a, uint32_t b, uint32_t c) { uint32_t r; asm("lop3.b32 %0, %1, %2, %3, 0xFE;" : "=r"(r) : "r"(a), "r"(b), "r"(c)); return r; }
DEVI bool any_bad(uint32_t x) { return __any_sync(0xFFFFFFFFu, (x & 1u) != 0); }
DEVI uint32_t settag(uint32_t x, uint32_t tag) { return (x & ~1u) | tag; }
DEVI void sts32f(uint32_t a, float v) { asm volatile("st.shared.f32 [%0], %1;" ::"r"(a), "f"(v) : "memory"); }
DEVI void sts32(uint32_t a, uint32_t v) { asm volatile("st.shared.u32 [%0], %1;" ::"r"(a), "r"(v) : "memory"); }
DEVI void sts16(uint32_t a, uint32_t v) { asm volatile("st.shared.u16 [%0], %1;" ::"r"(a), "h"((unsigned short)v) : "memory"); }
DEVI void sts64(uint32_t a, uint32_t x, uint32_t y) { asm volatile("st.shared.v2.u32 [%0], {%1,%2};" ::"r"(a), "r"(x), "r"(y) : "memory"); }
DEVI void sts128(uint32_t a, uint32_t x, uint32_t y, uint32_t z, uint32_t w) {
    asm volatile("st.shared.v4.u32 [%0], {%1,%2,%3,%4};" ::"r"(a), "r"(x), "r"(y), "r"(z), "r"(w) : "memory");
}
DEVI float4 lds128f(uint32_t a) {
    float4 v;
    asm volatile("ld.shared.v4.f32 {%0,%1,%2,%3}, [%4];" : "=f"(v.x), "=f"(v.y), "=f"(v.z), "=f"(v.w) : "r"(a) : "memory");
    return v;
}
DEVI uint4 lds128(uint32_t a) {
    uint4 v;
    asm volatile("ld.shared.v4.u32 {%0,%1,%2,%3}, [%4];" : "=r"(v.x), "=r"(v.y), "=r"(v.z), "=r"(v.w) : "r"(a) : "memory");
    return v;
}
DEVI uint2 lds64(uint32_t a) {
    uint2 v;
    asm volatile("ld.shared.v2.u32 {%0,%1}, [%2];" : "=r"(v.x), "=r"(v.y) : "r"(a) : "memory");
    return v;
}
DEVI uint32_t lds32(uint32_t a) {
    uint32_t v;
    asm volatile("ld.shared.u32 %0, [%1];" : "=r"(v) : "r"(a) : "memory");
    return v;
}
DEVI float ex2(float x) { float r; asm("ex2.approx.ftz.f32 %0, %1;" : "=f"(r) : "f"(x)); return r; }
DEVI float rcp(float x) { float r; asm("rcp.approx.ftz.f32 %0, %1;" : "=f"(r) : "f"(x)); return r; }
DEVI uint32_t clk() { uint32_t c; asm volatile("mov.u32 %0, %%clock;" : "=r"(c)::"memory"); return c; }

DEVI uint64_t mkdesc(uint32_t addr, uint32_t lbo, uint32_t sbo) {
    return (uint64_t)((addr & 0x3FFFF) >> 4) | ((uint64_t)(lbo >> 4) << 16) | ((uint64_t)(sbo >> 4) << 32) | ((uint64_t)1 << 62);
}
DEVI void wg_fence() { asm volatile("wgmma.fence.sync.aligned;" ::: "memory"); }
DEVI void wg_commit() { asm volatile("wgmma.commit_group.sync.aligned;" ::: "memory"); }
template <int N> DEVI void wg_wait() { asm volatile("wgmma.wait_group.sync.aligned %0;" ::"n"(N) : "memory"); }
template <int SC>
DEVI void wg_rs32(float (&d)[16], const uint32_t (&a)[4], uint64_t db) {
    if (SC) {
        asm volatile("wgmma.mma_async.sync.aligned.m64n32k16.f32.bf16.bf16 "
                     "{%0,%1,%2,%3,%4,%5,%6,%7,%8,%9,%10,%11,%12,%13,%14,%15}, {%16,%17,%18,%19}, %20, 1, 1, 1, 0;"
                     : "+f"(d[0]), "+f"(d[1]), "+f"(d[2]), "+f"(d[3]), "+f"(d[4]), "+f"(d[5]), "+f"(d[6]), "+f"(d[7]),
                       "+f"(d[8]), "+f"(d[9]), "+f"(d[10]), "+f"(d[11]), "+f"(d[12]), "+f"(d[13]), "+f"(d[14]), "+f"(d[15])
                     : "r"(a[0]), "r"(a[1]), "r"(a[2]), "r"(a[3]), "l"(db));
    } else {
        asm volatile("wgmma.mma_async.sync.aligned.m64n32k16.f32.bf16.bf16 "
                     "{%0,%1,%2,%3,%4,%5,%6,%7,%8,%9,%10,%11,%12,%13,%14,%15}, {%16,%17,%18,%19}, %20, 0, 1, 1, 0;"
                     : "=f"(d[0]), "=f"(d[1]), "=f"(d[2]), "=f"(d[3]), "=f"(d[4]), "=f"(d[5]), "=f"(d[6]), "=f"(d[7]),
                       "=f"(d[8]), "=f"(d[9]), "=f"(d[10]), "=f"(d[11]), "=f"(d[12]), "=f"(d[13]), "=f"(d[14]), "=f"(d[15])
                     : "r"(a[0]), "r"(a[1]), "r"(a[2]), "r"(a[3]), "l"(db));
    }
}

#define NA 12
#define NPF 6
#define PF1 2
#define PF2 1
#define PF3 4
#define WPF 2
#define VPF 2
#define VORD 0x01234567
#define VSF 0
#define VMF 0
#define VC 1
#define QP 16
#define W2P 0
#define W3P 1
#define QSP 10
#define VSB 0x105
#define QQP 3
#define CGP 8
#define C0P 9
#define C1P 9
#define PIP 10
#define K0P 2
#define KEP 1
#define KE2 0
#define VTP 0
#define CW 1
#define WV_BOX ((16 - NA) * 2048)
#define WO_BOX 16384
#define SM_WV 0
#define SM_WO (2 * WV_BOX)
#define SM_X (SM_WO + 4 * WO_BOX)
#define SM_XO (SM_X + 32768)
#define SM_MEMT (SM_XO + 12288)
#define SM_OT (SM_MEMT + 4096)
#define SM_VS (SM_OT + 2048)
#define SM_P (SM_VS + 2048)
#define SM_DN (SM_P + 1792)
#define SM_PROF (SM_P + 2048)
#define SM_ST (SM_X + 65536)
#define SM_KV SM_ST
#define SM_SP (SM_KV + 18432)
#define SM_TR (SM_ST + 32768)
#define SM_PI (SM_ST + 65536)
#define SM_BAR (SM_PI + 12288)
#define SM_TOTAL (SM_BAR + 512)
static_assert(NA == 12, "start-up chunks");
static_assert(SM_TOTAL <= 232448, "smem");
#define BAR_XA 32
#define BAR_KV 40
#define BAR_PI 48
#define BAR_RO 64
#define BAR_WF 256
#define BAR_WE 384
#define SM_ROLE (SM_BAR + 72)

#define SPIN_LIMIT (1 << 20)
#define RPOS 26
#define OPOS 3
#define ASF 0
#define KPOS 0
#define CPOS 5
#define DLY_V 260
#define NPRB 2
#define PW 4
#define ZD 0
#define FTM 2
#define XPF 1
#define WOP 2
#define WIN 2
#define EPD 1300
#define ASP 4
#define EPF 0
#define CFAR 1

template <int ID, int N> DEVI void bsync() { asm volatile("bar.sync %0, %1;" ::"n"(ID), "n"(N) : "memory"); }
template <int ID, int N> DEVI void barv() { asm volatile("bar.arrive %0, %1;" ::"n"(ID), "n"(N) : "memory"); }

#define PT(n)
#define PC(n, v)
#define PDUMP()
#define REFRESH() asm volatile("xor.b32 %0, %0, %1;" : "+r"(l16) : "r"(zero))
#define OPQ(x) asm volatile("xor.b32 %0, %0, %1;" : "+r"(x) : "r"(zero))
#define KEEP(x, a, b, c, d) asm volatile("{\n.reg .b32 t;\nlop3.b32 t, %1, %2, %3, 0x80;\nlop3.b32 t, t, %4, %5, 0x80;\nxor.b32 %0, %0, t;\n}" \
                                         : "+r"(x) : "r"(a), "r"(b), "r"(c), "r"(d), "r"(zero))
#define SF() asm volatile("pmevent 1;" ::: "memory")
#define MF() __syncwarp()
#define SB0 1024u

#define XDOFF(ks) ((((ks) >> 2) * 1024 + ((ks) & 3) * 32) >> 4)
template <int SC>
DEVI void wg_ss32t(float (&d)[16], uint64_t da, uint64_t db) {
    if (SC) {
        asm volatile("wgmma.mma_async.sync.aligned.m64n32k16.f32.bf16.bf16 "
                     "{%0,%1,%2,%3,%4,%5,%6,%7,%8,%9,%10,%11,%12,%13,%14,%15}, %16, %17, 1, 1, 1, 1, 0;"
                     : "+f"(d[0]), "+f"(d[1]), "+f"(d[2]), "+f"(d[3]), "+f"(d[4]), "+f"(d[5]), "+f"(d[6]), "+f"(d[7]),
                       "+f"(d[8]), "+f"(d[9]), "+f"(d[10]), "+f"(d[11]), "+f"(d[12]), "+f"(d[13]), "+f"(d[14]), "+f"(d[15])
                     : "l"(da), "l"(db));
    } else {
        asm volatile("wgmma.mma_async.sync.aligned.m64n32k16.f32.bf16.bf16 "
                     "{%0,%1,%2,%3,%4,%5,%6,%7,%8,%9,%10,%11,%12,%13,%14,%15}, %16, %17, 0, 1, 1, 1, 0;"
                     : "=f"(d[0]), "=f"(d[1]), "=f"(d[2]), "=f"(d[3]), "=f"(d[4]), "=f"(d[5]), "=f"(d[6]), "=f"(d[7]),
                       "=f"(d[8]), "=f"(d[9]), "=f"(d[10]), "=f"(d[11]), "=f"(d[12]), "=f"(d[13]), "=f"(d[14]), "=f"(d[15])
                     : "l"(da), "l"(db));
    }
}

DEVI void delay_until(uint32_t t0, uint32_t d) { while (clk() - t0 < d) {} }

#define VR 2
#define CW2 4
template <int I0, int I1>
DEVI void xmma(float (&xa)[16], float (&xb)[16], uint32_t w, int ps, uint32_t zero, const uint32_t (&Wq)[16][4], const uint32_t (&Wk)[16][4],
               const uint32_t (&Wv)[NA][4], const uint32_t (&wv)[16 - NA][4]) {
    const uint64_t xd = mkdesc(SB0 + SM_X, 16, 4096) + (ps & 1) * 1024, vd = mkdesc(SB0 + SM_WV, 8192, 1024);
    uint32_t vo = (w >> 2) * (WV_BOX / 16);
    if (VR ? false : VC == 0 ? I0 < 16 - NA : VC == 1 ? I0 >= 32 && I0 < 48 - NA : I1 > 32 + NA) OPQ(vo);
#pragma unroll
    for (int i = I0; i < I1; i++) {
        if (VC) {
            const int v = (i + (VC == 1 ? NA : 0)) & 15;
            if (i == 0) wg_rs32<0>(xa, Wq[0], xd);
            else if (i < 16) wg_rs32<1>(xa, Wq[i & 15], xd + XDOFF(i & 15));
            else if (i == 16) wg_rs32<0>(xb, Wk[0], xd);
            else if (i < 32) wg_rs32<1>(xb, Wk[i & 15], xd + XDOFF(i & 15));
            else if (i == 32 && v < NA) wg_rs32<0>(xa, Wv[0], xd);
            else if (VR && i == 32) wg_rs32<0>(xa, wv[0], xd + XDOFF(NA));
            else if (VR && v >= NA) wg_rs32<1>(xa, wv[v >= NA ? v - NA : 0], xd + XDOFF(v));
            else if (i == 32) wg_ss32t<0>(xa, (vd & ~0xFFFFFFFFull) | ((uint32_t)vd + vo), xd + XDOFF(NA));
            else if (v < NA) wg_rs32<1>(xa, Wv[v < NA ? v : 0], xd + XDOFF(v));
            else wg_ss32t<1>(xa, (vd & ~0xFFFFFFFFull) | ((uint32_t)vd + (v - NA) * 128 + vo), xd + XDOFF(v));
        } else
        if (i == 0) wg_ss32t<0>(xb, (vd & ~0xFFFFFFFFull) | ((uint32_t)vd + vo), xd + XDOFF(NA));
        else if (i < 16 - NA) wg_ss32t<1>(xb, (vd & ~0xFFFFFFFFull) | ((uint32_t)vd + i * 128 + vo), xd + XDOFF(NA + i));
        else if (i == 16 - NA) wg_rs32<0>(xa, Wq[0], xd);
        else if (i < 32 - NA) wg_rs32<1>(xa, Wq[(i + NA) & 15], xd + XDOFF((i + NA) & 15));
        else if (i < 32) wg_rs32<1>(xb, Wv[(i + NA) & 15], xd + XDOFF((i + NA) & 15));
        else if (i == 32) wg_rs32<0>(xa, Wk[0], xd);
        else wg_rs32<1>(xa, Wk[i & 15], xd + XDOFF(i & 15));
    }
    wg_commit();
}
#define XMMA(I0, I1) xmma<(I0), (I1)>(xa, xb, w, p ^ 1, zero, Wq, Wk, Wv, wv)
DEVI void wg_done(float (&d)[16]) {
    asm volatile("" : "+f"(d[0]), "+f"(d[1]), "+f"(d[2]), "+f"(d[3]), "+f"(d[4]), "+f"(d[5]), "+f"(d[6]), "+f"(d[7]),
                      "+f"(d[8]), "+f"(d[9]), "+f"(d[10]), "+f"(d[11]), "+f"(d[12]), "+f"(d[13]), "+f"(d[14]), "+f"(d[15]) :: "memory");
}
template <int M>
DEVI void xpack(uint32_t (&xp)[8], float (&xa)[16]) {
    wg_done(xa);
#pragma unroll
    for (int i = 0; i < 4; i++) {
        xp[2 * i] = pack2(xa[4 * i], xa[4 * i + (M < 2 ? 2 : 1)]);
        xp[2 * i + 1] = pack2(xa[4 * i + (M < 2 ? 1 : 2)], xa[4 * i + 3]);
    }
}
template <int M>
DEVI uint4 xpeer(uint32_t sb, int ps, uint32_t t16) { return lds128(sb + SM_PI - ((ps & 1) ^ 1) * 12288 + M * 4096 + t16); }
DEVI void xadd(uint32_t (&xp)[8], const uint4& pi) {
    xp[0] = hadd2(xp[0], pi.x); xp[1] = hadd2(xp[1], pi.y); xp[2] = hadd2(xp[2], pi.z); xp[3] = hadd2(xp[3], pi.w);
}
template <int M>
DEVI void xsend(const uint32_t (&xp)[8], uint32_t sb, int ps, uint32_t t16) {
    asm volatile("st.async.weak.shared::cluster.mbarrier::complete_tx::bytes.v4.b32 [%0], {%1,%2,%3,%4}, [%5];"
                 ::"r"((sb ^ 0x1000000) + SM_PI - (ps & 1) * 12288 + M * 4096 + t16), "r"(xp[4]), "r"(xp[5]), "r"(xp[6]), "r"(xp[7]),
                   "r"((sb ^ 0x1000000) + SM_BAR + BAR_PI + (ps & 1) * 8) : "memory");
}
template <int M>
DEVI void xstore(const uint32_t (&xp)[8], uint32_t sb, uint32_t sbw, int ps, uint32_t t16, uint32_t KA) {
    const uint32_t a = SM_XO + M * 2048 + (M < 2 ? (KA & 0xFF) + sbw : (t16 >> 1) + sb);
    sts64(a, xp[0], xp[1]);
    sts64(a + 6144, xp[2], xp[3]);
    xsend<M>(xp, sb, ps, t16);
}
template <int M>
DEVI void xpark(uint32_t (&xp)[8], const uint4& pi, uint32_t sb, uint32_t sbw, int ps, uint32_t t16, uint32_t KA) {
    xadd(xp, pi);
    xstore<M>(xp, sb, sbw, ps, t16, KA);
}
template <uint32_t OFF> DEVI void red2(uint32_t lo, uint32_t hi, uint32_t a, uint32_t b) {
    asm volatile("{\n.reg .b64 a;\nmov.b64 a, {%0,%1};\nred.relaxed.gpu.global.add.noftz.v2.bf16x2 [a+%4], {%2,%3};\n}"
                 ::"r"(lo), "r"(hi), "r"(a), "r"(b), "n"(OFF) : "memory");
}
template <int M, int N>
DEVI void xstart(uint32_t sb, uint32_t w, uint32_t ga, uint32_t xhi, uint32_t j, uint32_t t16, uint32_t KA, const uint32_t (&W)[N][4]) {
    float xa[16], xb[16];
    uint32_t xp[8];
    auto pass = [&](float (&d)[16], int i, int k0, int k1) {
        const uint64_t xd = mkdesc(SB0 + SM_X + (i ? i + 1 : 0) * 16384, 16, 4096), vd = mkdesc(SB0 + SM_WV, 8192, 1024) + (w >> 2) * (WV_BOX / 16);
#pragma unroll
        for (int k = k0; k < k1; k++) {
            if (k == 0) wg_rs32<0>(d, W[0], xd);
            else if (k < N) wg_rs32<1>(d, W[k < N ? k : 0], xd + XDOFF(k));
            else wg_ss32t<1>(d, vd + (k - N) * 128, xd + XDOFF(k));
        }
        wg_commit();
    };
    wg_fence();
    pass(xa, 0, 0, 16);
    pass(xb, 1, 0, ASP);
    if (M == 0) bsync<5, 288>();
    ga += M < 2 ? (KA & 0xFF) + w * 256 : t16 >> 1;
    constexpr uint32_t O = XO_XG + M * 2048, SG = 128 * 6144;
    wg_wait<1>();
    xpack<M>(xp, xa);
    red2<O>(ga, xhi, xp[0], xp[1]); red2<O + 6144>(ga, xhi, xp[2], xp[3]); red2<O + 12288>(ga, xhi, xp[4], xp[5]); red2<O + 18432>(ga, xhi, xp[6], xp[7]);
    if (M == 2) barv<3, 320>();
    wg_fence();
    pass(xb, 1, ASP, 16);
    pass(xa, 2, 0, 16);
    wg_wait<1>();
    xpack<M>(xp, xb);
    red2<O + SG>(ga, xhi, xp[0], xp[1]); red2<O + SG + 6144>(ga, xhi, xp[2], xp[3]);
    red2<O + SG + 12288>(ga, xhi, xp[4], xp[5]); red2<O + SG + 18432>(ga, xhi, xp[6], xp[7]);
    wg_wait<0>();
    xpack<M>(xp, xa);
    red2<O + 2 * SG>(ga + j * 6144, xhi, xp[0], xp[1]);
    red2<O + 2 * SG>(ga + (j ^ 1) * 6144, xhi, xp[2], xp[3]);
    xsend<M>(xp, sb, 0, t16);
}
DEVI void piwait(uint32_t sb, int p, int ps) { mbar_wait(sb + SM_BAR + BAR_PI + p * 8, ((ps + 2) >> 1) & 1); }

DEVI uint32_t par(uint32_t off) { return __popc(off & 0xB2000u) & 1; }
DEVI uint32_t probe(uint32_t lo, uint32_t hi) {
    uint32_t best = 0xFFFFFFFFu, x = 0;
    stg4<0>(lo, hi, 0, 0, 0, 0);
    stg4<16>(lo, hi, 0, 0, 0, 0);
#pragma unroll 1
    for (int r = 0; r < NPRB; r++) {
        const uint32_t t0 = clk();
        asm volatile("{\n.reg .b64 a;\nmov.b64 a, {%1,%2};\natom.relaxed.gpu.global.add.u32 %0, [a], 2;\n}" : "=r"(x) : "r"(lo), "r"(hi) : "memory");
        if (x == 0xFFFFFFFFu) die(1 << 23);
        best = min(best, clk() - t0);
    }
    return best;
}

DEVI void xload(uint32_t sb, uint32_t u, uint32_t j, int ps, const CUtensorMap* tmx) {
    if (elect()) {
        const uint32_t sg = ps + 4 - (u & 1) + (u >> 1);
        mbar_expect(sb + SM_BAR + BAR_XA, sg < NSEG ? 4096 : 0);
        if (sg < NSEG) tma3d(sb + SM_X + (ps & 1) * 16384 + u * 4096, tmx, sb + SM_BAR + BAR_XA, 0, sg * 32 + (j ^ ((u & 1) * 2 + (u >> 1))) * 8, j * 4);
    }
}
DEVI uint32_t rpage(uint32_t j, int s) { return (s & 3) * 65536 + (j & 1) * 8192 + (((s ^ (s >> 1) ^ j ^ (j >> 1)) & 1) << 12); }

#define RLOAD() { m0 = ldg4<XO_R>(a, ah); n0 = ldg4<XO_R + 16384>(a, ah); e0 = ldg1<XO_R + 32768>(e, eh); f0 = ldg1<XO_R + 33792>(e, eh); }
DEVI bool ruse(uint32_t a, const uint4& m0, const uint4& n0, uint32_t e0, uint32_t f0) {
    const uint32_t a0 = hadd2(m0.w, n0.w), b0 = hadd2(e0, f0);
    stsm4(a, hadd2(m0.x, n0.x), hadd2(m0.y, n0.y), hadd2(m0.z, n0.z), __byte_perm(a0, b0, 0x5410));
    return __any_sync(0xFFFFFFFFu, (a0 & b0 & 0x42000000u) != 0x42000000u);
}

#define GST(i) (SM_WO + (i) * 49152)
#define BAR_GF 128
#define BAR_GE (BAR_GF + 64)
#define BAR_GX (BAR_GE + 32)
#define D4(c, i) #c "f"(d[i]), #c "f"(d[i + 1]), #c "f"(d[i + 2]), #c "f"(d[i + 3])
#define D16(c, i) D4(c, i), D4(c, i + 4), D4(c, i + 8), D4(c, i + 12)
DEVI void mwait(uint32_t bar, uint32_t parity) {
    asm volatile("{\n.reg .pred p;\n.reg .b32 c;\nmbarrier.try_wait.parity.shared::cta.b64 p, [%0], %1;\n@p bra.uni D;\nmov.b32 c, 0;\n"
                 "L:\nadd.u32 c, c, 1;\nsetp.gt.u32 p, c, 4194304;\n@p st.shared.u32 [c], c;\n"
                 "mbarrier.try_wait.parity.shared::cta.b64 p, [%0], %1;\n@!p bra.uni L;\nD:\n}" ::"r"(bar), "r"(parity) : "memory");
}
DEVI void wg_ss256t(float (&d)[128], uint64_t da, uint64_t db) {
    asm volatile("wgmma.mma_async.sync.aligned.m64n256k16.f32.bf16.bf16 "
        "{%0,%1,%2,%3,%4,%5,%6,%7,%8,%9,%10,%11,%12,%13,%14,%15,%16,%17,%18,%19,%20,%21,%22,%23,%24,%25,%26,%27,%28,%29,%30,%31,%32,%33,%34,%35,%36,%37,%38,%39,%40,%41,%42,%43,%44,%45,%46,%47,%48,%49,%50,%51,%52,%53,%54,%55,%56,%57,%58,%59,%60,%61,%62,%63,%64,%65,%66,%67,%68,%69,%70,%71,%72,%73,%74,%75,%76,%77,%78,%79,%80,%81,%82,%83,%84,%85,%86,%87,%88,%89,%90,%91,%92,%93,%94,%95,%96,%97,%98,%99,%100,%101,%102,%103,%104,%105,%106,%107,%108,%109,%110,%111,%112,%113,%114,%115,%116,%117,%118,%119,%120,%121,%122,%123,%124,%125,%126,%127}, "
        "%128, %129, 1, 1, 1, 1, 1;"
        : D16(+, 0), D16(+, 16), D16(+, 32), D16(+, 48), D16(+, 64), D16(+, 80), D16(+, 96), D16(+, 112) : "l"(da), "l"(db));
}
template <int O, int KB> DEVI void g_half(float (&d)[64], uint64_t da) {
    const uint64_t db = mkdesc(SB0 + GST(KB & 3) + 16384 + O * 256, 8192, 1024);
#pragma unroll
    for (int k = 0; k < 4; k++)
        asm volatile("wgmma.mma_async.sync.aligned.m64n128k16.f32.bf16.bf16 "
            "{%0,%1,%2,%3,%4,%5,%6,%7,%8,%9,%10,%11,%12,%13,%14,%15,%16,%17,%18,%19,%20,%21,%22,%23,%24,%25,%26,%27,%28,%29,%30,%31,%32,%33,%34,%35,%36,%37,%38,%39,%40,%41,%42,%43,%44,%45,%46,%47,%48,%49,%50,%51,%52,%53,%54,%55,%56,%57,%58,%59,%60,%61,%62,%63}, "
            "%64, %65, 1, 1, 1, 1, 1;"
            : D16(+, 0), D16(+, 16), D16(+, 32), D16(+, 48) : "l"(da + (KB & 3) * 3072 + k * 16), "l"(db + k * 128));
}
DEVI void g_load(uint32_t sb, uint32_t u, uint32_t role, uint32_t kb, uint32_t xlo, uint32_t xhi, const CUtensorMap* tmb) {
    const uint32_t st = kb & 3, bar = sb + SM_BAR + BAR_GF + u * 32 + st * 8, dst = sb + GST(st), k = (role & 1) * 32 + kb;
    if (!elect()) return;
    mbar_expect(bar, u ? 8192 : 40960);
    bulk_g2s(dst + u * 8192, xlo + XO_OX + (k * 16 + (role >> 3)) * 16384 + u * 8192, xhi, 8192, bar);
    if (u == 0) {
        tma3d(dst + 16384, tmb, bar, 0, k * 64, ((role & 7) ^ 1) * 2);
        tma3d(dst + 32768, tmb, bar, 0, k * 64, (role & 7) * 2);
    }
}
DEVI void g_arrive(uint32_t a, uint32_t xhi, uint32_t n) {
    if (elect()) asm volatile("{\n.reg .b64 a;\nmov.b64 a, {%0,%1};\nred.release.gpu.global.inc.u32 [a], %2;\n}" ::"r"(a), "r"(xhi), "r"(n - 1) : "memory");
}
DEVI void g_wait(uint32_t a, uint32_t xhi) {
    int it = 0;
    uint32_t v;
    do {
        asm volatile("{\n.reg .b64 a;\nmov.b64 a, {%1,%2};\nld.acquire.gpu.global.u32 %0, [a];\n}" : "=r"(v) : "r"(a), "r"(xhi) : "memory");
        if (++it > SPIN_LIMIT) die(it);
    } while (__any_sync(0xFFFFFFFFu, v));
    asm volatile("fence.proxy.async.global;" ::: "memory");
}
#define SE 2
#define DLY_S 0
#define VX 1
#define VH 1
#define VD 1
#define SM_VP (SM_TR + 12288)
#define JV(h, j) (VH < 2 ? (j) ^ ((par((h) * 8192) ^ VH) << 1) : (j))
#define SEU 0
#define VA 0
#define VLP 0
#define VCP 1
#define SEED 0
#define VB 0
#define RCP 0
#define XLP 0
#define RE 0
#define DLY_E 300
#define DLY_T 200
#define RDW 0
#define APH 1
#define A0 0
#define A1 0
#define DNP 0
#define WLP 0
#define LDP 0
#define FDL 0
#define OSF 0x0F
#define OAP 5
#define VKS 10
#define XM0 12
#define QW 4
#define RW 4
#define KEP0 1
#define VSB0 VSB
#define B3 0
#define GD 400
#define GE 3
#define GH 1
#define GS 1
#define GP 0
DEVI void g_done(float (&d)[64]) { asm volatile("" : D16(+, 0), D16(+, 16), D16(+, 32), D16(+, 48)::"memory"); }
DEVI void g_main(uint32_t sb, uint32_t w, uint32_t role, const CUtensorMap* tmy, void* out) {
    const uint32_t bar = sb + SM_BAR, t16 = threadIdx.x * 16;
    const uint64_t da = (mkdesc(SB0 + GST(0), 128, 1024) & ~((uint64_t)3 << 62)) + (w >> 2) * 512;
    float d[128];
#pragma unroll
    for (int i = 0; i < 128; i++) d[i] = 0.f;
#define GFULL(kb) { mwait(bar + BAR_GF + ((kb) & 3) * 8, ((kb) >> 2) & 1); if (w >= 4) mwait(bar + BAR_GF + 32 + ((kb) & 3) * 8, ((kb) >> 2) & 1); }
#pragma unroll 1
    for (uint32_t kb = 0; kb < (GE ? 28 : 29); kb++) {
        GFULL(kb);
        if (kb == 0 && threadIdx.x == 128) PG(4);
        if (kb == 4 && threadIdx.x == 0) PG(5);
        const uint64_t a = da + (kb & 3) * 3072, b = mkdesc(SB0 + GST(0) + 16384, 8192, 1024) + (kb & 3) * 3072;
        wg_fence();
#pragma unroll
        for (int k = 0; k < 4; k++) wg_ss256t(d, a + k * 16, b + k * 128);
        wg_commit();
        wg_wait<1>();
        if (kb > 0 && elect()) mbar_arrive(bar + BAR_GE + ((kb - 1) & 3) * 8);
    }
    if (GE) { GFULL(28); }
    else { GFULL(29); GFULL(30); GFULL(31); }
    wg_wait<0>();
    if (GE && elect()) mbar_arrive(bar + BAR_GE + 24);
    float x[64], y[64];
#pragma unroll
    for (int i = 0; i < 64; i++) asm volatile("mov.b32 %0, %1;" : "=f"(x[i]) : "f"(d[i]) : "memory");
    SF();
#pragma unroll
    for (int i = 0; i < 64; i++) asm volatile("mov.b32 %0, %1;" : "=f"(y[i]) : "f"(d[i + 64]) : "memory");
    SF();
#define GFREE() if (elect()) asm volatile("mbarrier.arrive.relaxed.cluster.shared::cluster.b64 _, [%0];" ::"r"((bar ^ 0x1000000) + BAR_GX) : "memory")
#define GSW(i) ((i) * 4096 + (GE && (i) >= 4 ? GST(0) : 0))
#define GSEND(i0) _Pragma("unroll") for (int i = (i0); i < (i0) + 4; i++) \
        asm volatile("st.async.weak.shared::cluster.mbarrier::complete_tx::bytes.v4.b32 [%0], {%1,%2,%3,%4}, [%5];" \
                     ::"r"((sb ^ 0x1000000) + GSW(i) + t16), "r"(pack2(x[8 * i], x[8 * i + 1])), "r"(pack2(x[8 * i + 2], x[8 * i + 3])), \
                       "r"(pack2(x[8 * i + 4], x[8 * i + 5])), "r"(pack2(x[8 * i + 6], x[8 * i + 7])), "r"((bar ^ 0x1000000) + BAR_GX + 8) : "memory")
    if (GE) {
        wg_fence();
        g_half<0, 28>(x, da);
        wg_commit();
        GFULL(29);
        wg_fence();
        g_half<0, 29>(x, da);
        wg_commit();
        GFULL(30);
        wg_fence();
        g_half<0, 30>(x, da);
        wg_commit();
        GFULL(31);
        wg_fence();
        g_half<0, 31>(x, da);
        wg_commit();
        g_half<64, 28>(y, da);
        if (GE == 2) g_half<64, 29>(y, da);
        wg_commit();
        wg_wait<1>();
        g_done(x);
        GFREE();
        GSEND(0);
        wg_fence();
        if (GE != 2) g_half<64, 29>(y, da);
        if (GE != 1) g_half<64, 30>(y, da);
        wg_commit();
        mwait(bar + BAR_GX, 0);
        GSEND(4);
        wg_fence();
        if (GE == 1) g_half<64, 30>(y, da);
        g_half<64, 31>(y, da);
        wg_commit();
        mwait(bar + BAR_GX + 8, 0);
        if (threadIdx.x == 0) PG(1);
#pragma unroll
        for (int i = 0; i < 8; i++) {
            const uint4 a = lds128(sb + GSW(i) + t16);
            float* e = x + 8 * i;
            e[0] = lo_f(a.x); e[1] = hi_f(a.x); e[2] = lo_f(a.y); e[3] = hi_f(a.y); e[4] = lo_f(a.z); e[5] = hi_f(a.z); e[6] = lo_f(a.w); e[7] = hi_f(a.w);
        }
        g_done(x);
        SF();
        wg_wait<0>();
        g_done(y);
        if (threadIdx.x == 0) PG(7);
    } else {
        GFREE();
        wg_fence();
        g_half<0, 29>(x, da);
        g_half<0, 30>(x, da);
        g_half<0, 31>(x, da);
        wg_commit();
        g_half<64, 29>(y, da);
        wg_commit();
        wg_wait<1>();
        g_done(x);
        mwait(bar + BAR_GX, 0);
        GSEND(0);
        wg_fence();
        g_half<64, 30>(y, da);
        wg_commit();
        GSEND(4);
        wg_fence();
        g_half<64, 31>(y, da);
        wg_commit();
        wg_wait<0>();
        g_done(y);
        if (threadIdx.x == 0) PG(7);
        mwait(bar + BAR_GX + 8, 0);
        if (threadIdx.x == 0) PG(1);
    }
    const uint32_t lane = threadIdx.x & 31, o = sb + GST(1) + w * 2048;
    char* go = (char*)out + ((role >> 3) * 128 + w * 16 + (lane >> 3)) * 4096 + (role & 7) * 256 + (lane & 7) * 16;
#pragma unroll
    for (int i = 0; i < 8; i++) {
        float* e = y + 8 * i;
        if (GE) {
#pragma unroll
            for (int n = 0; n < 8; n++) e[n] += x[8 * i + n];
        } else {
            const uint4 a = lds128(sb + i * 4096 + t16);
            e[0] += lo_f(a.x); e[1] += hi_f(a.x); e[2] += lo_f(a.y); e[3] += hi_f(a.y); e[4] += lo_f(a.z); e[5] += hi_f(a.z); e[6] += lo_f(a.w); e[7] += hi_f(a.w);
        }
        stsm4(o + (i >> 2) * 49152 + (lane & 15) * 128 + ((((i & 3) * 2 + (lane >> 4)) ^ (lane & 7)) << 4),
              pack2(e[0], e[1]), pack2(e[2], e[3]), pack2(e[4], e[5]), pack2(e[6], e[7]));
        if (i == 3 || i == 7) {
            if (GS) {
                __syncwarp();
#pragma unroll
                for (int m = 0; m < 4; m++)
                    *(uint4*)(go + m * 16384 + (i >> 2) * 128) =
                        lds128(o + (i >> 2) * 49152 + m * 512 + (lane >> 3) * 128 + (((lane & 7) ^ ((m & 1) * 4 + (lane >> 3))) << 4));
            } else {
                asm volatile("fence.proxy.async.shared::cta;" ::: "memory");
                __syncwarp();
                if (elect())
                    asm volatile("cp.async.bulk.tensor.2d.global.shared::cta.bulk_group [%0, {%2, %3}], [%1];\ncp.async.bulk.commit_group;"
                                 ::"l"(tmy), "r"(o + (i >> 2) * 49152), "r"((role & 7) * 128 + (i >> 2) * 64), "r"((role >> 3) * 128 + w * 16) : "memory");
            }
        }
    }
    if (threadIdx.x == 0) PG(6);
    if (!GS) asm volatile("cp.async.bulk.wait_group.read 0;" ::: "memory");
}

DEVI void kvload(uint32_t sb, uint32_t u, uint32_t h, uint32_t j, int sg, uint32_t xlo, uint32_t xhi) {
    const uint32_t o = u == 0 ? 0 : 2048;
    mbar_expect(sb + SM_BAR + BAR_KV, 6144 - o);
    bulk_g2s(sb + SM_KV + u * 4096 + o, xlo + XO_XG + (((sg & 7) * 32 + h) * 4 + ((j + u) & 3)) * 6144 + o, xhi, 6144 - o, sb + SM_BAR + BAR_KV);
}
DEVI void helper_step(uint32_t sb, uint32_t w, uint32_t h, uint32_t j, uint32_t& l16, uint32_t xlo, uint32_t xhi, uint32_t zero, int s,
                      const CUtensorMap* tmx, const CUtensorMap* tmb) {
    const uint32_t u = w - 8, bq = sb + SM_BAR;
    bsync<1, 384>();
    PT(0);
    PDUMP();
    PT(1);
    if (s == NSEG - 2 && u < 2) g_arrive(xlo + XO_TK + 128, xhi, 256);
    uint32_t old = 0;
#define RCLEAR(n) if (RCP == (n) && u > 0 && s + 3 < NSEG) \
        asm volatile("{\n.reg .b64 a;\nmov.b64 a, {%1,%2};\natom.relaxed.gpu.global.exch.b32 %0, [a], 0;\n}" \
                     : "=r"(old) : "r"(xlo + XO_R + rpage(j, s + 2) + (u - 1) * 16384 + h * 128 + (l16 >> 2)), "r"(xhi) : "memory");
    RCLEAR(1);
    const bool gl = u == 0 || (u == 1 && h < 30);
    if (GP == 1 && s == NSEG - 1 && gl) g_load(sb, u, h * 4 + j, 1, xlo, xhi, tmb);
    const uint32_t ctag = ((s >> 1) & 1) ^ 1;
    const uint32_t av = xlo + ((s & 1) * 32 + h) * 8192 + u * 512;
    mbar_wait(bq + BAR_XA, (s + 1) & 1);
    if (B3 == 8) barv<5, 384>();
    bsync<8, 384>();
    const uint32_t t8 = clk(), gs = xlo + XO_XG + ((((s + 3) & 7) * 32 + h) * 4 + j) * 6144;
    RCLEAR(2);
    const bool se = B3 % 8 == 0 && SE && u == SEU && s + 3 < NSEG;
    uint32_t tv = ctag ^ 1, ro = 0;
    if (se) {
        asm volatile("fence.proxy.async.shared::cta;" ::: "memory");
        if (SE == 4) delay_until(t8, DLY_E);
        if ((SE == 1 || SE == 4) && elect()) bulk_s2g(gs, xhi, sb + SM_XO, 4096);
    } else if (RE && u == 1 && s + 2 < NSEG) {
        asm volatile("fence.proxy.async.shared::cta;" ::: "memory");
        const uint32_t cb0 = (h >> 1) * 32768 + (j & 1) * 16384 + (h & 1) * 8192;
        delay_until(t8, DLY_T);
        tv = ldg1<XO_CQK>((xlo + cb0 + ((par(cb0) ^ (j >> 1) ^ CFAR ^ 1) << 12)) ^ ((s & 1) * 0x81000), xhi);
        SF();
    }
    if (B3 != 6 || u || SE == 2) delay_until(t8, DLY_V);
    if (se && SE == 2 && elect()) bulk_s2g(gs, xhi, sb + SM_XO, 4096);
    PT(4);
    int it = 0;
    uint4 d1, d2, d3;
    uint2 e1, e2, e3;
    const uint32_t ae = av - u * 512 + (u & 1) * 256;
    const uint32_t jv = JV(h, j);
#define VLOAD() { if (!VD) d1 = ldg4<XO_CV>(av + (jv ^ 1) * 2048 + l16, xhi); \
        d2 = ldg4<XO_CV>(av + (jv ^ 2) * 2048 + l16, xhi); d3 = ldg4<XO_CV>(av + (jv ^ 3) * 2048 + l16, xhi); \
        if (B3 == 6 && VX) { if (!VD) e1 = ldg2<XO_CV>(ae + (jv ^ 1) * 2048 + (l16 >> 1), xhi); \
                       e2 = ldg2<XO_CV>(ae + (jv ^ 2) * 2048 + (l16 >> 1), xhi); e3 = ldg2<XO_CV>(ae + (jv ^ 3) * 2048 + (l16 >> 1), xhi); } \
        if (VD) { d1 = lds128(sb + SM_VP + (s & 1) * 2048 + u * 512 + l16); \
                  if (B3 == 6 && VX) e1 = lds64(sb + SM_VP + (s & 1) * 2048 + (u & 1) * 256 + (l16 >> 1)); } }
#define XSEND(F, C) if (u < 2) { \
        if (F) asm volatile("fence.proxy.async.shared::cta;" ::: "memory"); \
        if ((C) && elect()) { \
            const uint32_t sg = s + 3 - u; \
            if (sg < NSEG) { \
                const uint32_t ga = xlo + XO_XG + (((sg & 7) * 32 + h) * 4 + (j ^ (2 * u))) * 6144, sa = sb + SM_XO + u * 6144; \
                if (u == 0) bulk_s2g(ga + (SE ? 4096 : 0), xhi, sa + (SE ? 4096 : 0), SE ? 2048 : 6144); \
                else bulk_red(ga + ro, xhi, sa + ro, 6144 - ro); \
            } \
        } \
    }
    if (B3 == 8) {
        bsync<3, 384>();
        if (DLY_S) delay_until(clk(), DLY_S);
        XSEND(true, true);
    } else if (B3 == 6 && u == 0) {
        const uint32_t ga = xlo + XO_XG + ((((s + 3) & 7) * 32 + h) * 4 + j) * 6144, o = SE == 1 || SE == 2 ? 4096 : 0;
        if (o) {
            asm volatile("fence.proxy.async.shared::cta;" ::: "memory");
            if (s + 3 < NSEG && elect()) bulk_s2g(ga, xhi, sb + SM_XO, o);
        }
        bsync<3, 288>();
        if (DLY_S) delay_until(clk(), DLY_S);
        asm volatile("fence.proxy.async.shared::cta;" ::: "memory");
        if (elect()) {
            if (SE == 3 && s + 3 < NSEG) bulk_s2g(ga + o, xhi, sb + SM_XO + o, 6144 - o);
            if (s + 2 < NSEG) bulk_red(xlo + XO_XG + ((((s + 2) & 7) * 32 + h) * 4 + (j ^ 2)) * 6144, xhi, sb + SM_XO + 6144, 6144);
            if (SE != 3 && s + 3 < NSEG) bulk_s2g(ga + o, xhi, sb + SM_XO + o, 6144 - o);
        }
    } else {
    if (B3 == 6) VLOAD();
    if (B3 && B3 < 6) {
        VLOAD();
        bsync<B3 == 2 ? 4 : 3, 384>();
        XSEND(true, B3 < 3 || B3 == 5 || (B3 == 4 && u == 0));
    }
    while (true) {
        if (B3 % 7 == 0) VLOAD();
        if (RE && it == 0) {
            SF();
            if (!any_bad(tv ^ ctag)) {
                if (elect()) bulk_red(xlo + XO_XG + ((((s + 2) & 7) * 32 + h) * 4 + (j ^ 2)) * 6144, xhi, sb + SM_XO + 6144, 4096);
                ro = 4096;
            }
        }
        if (se && SE == 3 && it == 0 && elect()) bulk_s2g(gs, xhi, sb + SM_XO, 4096);
        uint32_t tg = or3(tagx2(d1.x, d1.z, ctag), tagx2(d2.x, d2.z, ctag), tagx2(d3.x, d3.z, ctag));
        if (B3 == 6 && VX) tg = or3(tg, tagx2(e1.x, e2.x, ctag), e3.x ^ ctag);
        const bool bad = any_bad(tg);
        if (B3 == 6 && VX) sts64(sb + SM_VS + (u & 1) * 256 + (l16 >> 1), hadd2(hadd2(e1.x, e2.x), e3.x), hadd2(hadd2(e1.y, e2.y), e3.y));
        sts128(sb + SM_VS + u * 512 + l16, hadd2(hadd2(d1.x, d2.x), d3.x), hadd2(hadd2(d1.y, d2.y), d3.y), hadd2(hadd2(d1.z, d2.z), d3.z),
               hadd2(hadd2(d1.w, d2.w), d3.w));
        if (VA) asm volatile("{\n.reg .pred p;\nsetp.eq.u32 p, %0, 0;\n@p bar.arrive 5, 384;\n}" ::"r"((uint32_t)bad) : "memory");
        if (B3 % 7 == 0) REFRESH();
        if (!bad) break;
        if (B3 % 7) { REFRESH(); VLOAD(); }
        if (++it > SPIN_LIMIT) die(it);
    }
    PC(26, it);
    PT(5);
    if (VB) barv<11, 384>();
    else if (!VA) barv<5, B3 == 6 ? 352 : 384>();
    }
    if (B3 % 7 == 0) {
        bsync<3, 384>();
        XSEND(true, true);
    }
    if (B3 == 3 || B3 == 4) XSEND(false, B3 == 3 || u == 1);
    PT(6);
    RCLEAR(0);
    PT(7);
    bsync<7, 384>();
    if (s + 1 < NSEG && elect()) kvload(sb, u, h, j, s + 1, xlo, xhi);
    RCLEAR(3);
    if (XLP == 1) xload(sb, u, j, s + 1, tmx);
    if (u < (B3 == 6 ? 1 : 2)) {
        asm volatile("cp.async.bulk.wait_group.read 0;" ::: "memory");
        if (elect()) {
            mbar_expect(bq + BAR_PI + ((s & 1) ^ 1) * 8, 6144);
            if (B3 == 6) mbar_expect(bq + BAR_PI + ((s & 1) ^ 1) * 8, 6144);
        }
    }
    PT(8);
    if (GP && s == NSEG - 2 && gl) g_wait(xlo + XO_TK + 128, xhi);
    if (s + 1 < NSEG) bsync<10, 384>();
    if (XLP == 0) xload(sb, u, j, s + 1, tmx);
    RCLEAR(4);
    if (s == NSEG - 2 && gl) {
        if (!GP) g_wait(xlo + XO_TK + 128, xhi);
        g_load(sb, u, h * 4 + j, 0, xlo, xhi, tmb);
        if (GP == 0 || GP == 3) g_load(sb, u, h * 4 + j, 1, xlo, xhi, tmb);
    }
    asm volatile("cp.async.bulk.wait_group 0;" ::: "memory");
    if (s + 1 < NSEG) mbar_wait(bq + BAR_KV, (s + 1) & 1);
    asm volatile("lop3.b32 %0, %0, %1, %2, 0x78;" : "+r"(l16) : "r"(old), "r"(zero));
    PT(15);
}
DEVI void tickets_done(uint32_t* tk) {
    if (atomicInc(tk + 2, gridDim.x / 2 - 64) == gridDim.x / 2 - 64) { tk[0] = 0; tk[1] = 0; }
}

__global__ void __cluster_dims__(2, 1, 1) __launch_bounds__(384, 1)
chain_kernel(const __grid_constant__ CUtensorMap tmq, const __grid_constant__ CUtensorMap tmk,
             const __grid_constant__ CUtensorMap tmv, const __grid_constant__ CUtensorMap tmo,
             const __grid_constant__ CUtensorMap tmx, const __grid_constant__ CUtensorMap tmb, const __grid_constant__ CUtensorMap tmy,
             const bf16* __restrict__ mem0, const bf16* __restrict__ xg,
             uint32_t xlo, uint32_t xhi, uint32_t zero, int nseg, bf16* __restrict__ out) {
    extern __shared__ __align__(1024) uint8_t smem[];
    const uint32_t tstart = clk();
    const uint32_t rk = smem_u32(smem) & 0x1000000;
    if (rk == 0 && (threadIdx.x & 31) == 0 && threadIdx.x - 32 < 32 * PW)
        sts32(SB0 + SM_ROLE + 4 + (threadIdx.x >> 3), probe(xlo + XO_PB + (threadIdx.x & 32) * 128 + (threadIdx.x & 64) * 256 + blockIdx.x * 16, xhi));
    __syncwarp();
    if ((smem_u32(smem) & 0xFFFFFF) != SB0) die(1 << 23);
    if (!LDP) asm volatile("griddepcontrol.launch_dependents;" ::: "memory");
    const uint32_t w = __reduce_max_sync(0xFFFFFFFFu, threadIdx.x >> 5);
    const uint32_t sb = __reduce_max_sync(0xFFFFFFFFu, smem_u32(smem));
    const uint32_t bq = sb + SM_BAR;
    uint32_t l16 = __shfl_sync(0xFFFFFFFFu, (threadIdx.x & 31) * 16, threadIdx.x & 31);
    if (threadIdx.x == 0) {
        mbar_init(bq, 1);
        for (int i = 0; i < 24; i++) mbar_init(bq + BAR_WF + i * 8, i < 16 ? 1 : 8);
        mbar_init(bq + BAR_XA, 4); mbar_init(bq + BAR_KV, 4); mbar_init(bq + BAR_PI, 2); mbar_init(bq + BAR_PI + 8, 2);
        for (int i = 0; i < 14; i++) mbar_init(bq + BAR_GF + i * 8, i < 8 || i == 13 ? 1 : 8);
        mbar_expect(bq + BAR_GX + 8, 32768);
        mbar_init(bq + BAR_RO, 1);
        mbar_expect(bq + BAR_RO, 4);
        mbar_expect(bq + BAR_PI, 6144);
        mbar_expect(bq + BAR_PI, 6144);
        asm volatile("fence.mbarrier_init.release.cluster;" ::: "memory");
        asm volatile("fence.proxy.async.shared::cta;" ::: "memory");
    }
    __syncwarp();
    asm volatile("barrier.cluster.arrive.relaxed.aligned;" ::: "memory");
    if (w == 9) {
#pragma unroll 1
        for (int e = 0; e < 12; e++) sts128(sb + SM_WO + e * 512 + l16, 0, 0, 0, 0);
    }
    if (w == 8 && blockIdx.x < 128) {
        if (XPF && elect()) {
            asm volatile("cp.async.bulk.prefetch.L2.global [%0], 3072;" ::"l"((const char*)xg + blockIdx.x * 3072) : "memory");
            asm volatile("prefetch.tensormap [%0];\nprefetch.tensormap [%1];\nprefetch.tensormap [%2];\nprefetch.tensormap [%3];\nprefetch.tensormap [%4];"
                         ::"l"(&tmq), "l"(&tmx), "l"(&tmk), "l"(&tmv), "l"(&tmo) : "memory");
        }
#pragma unroll 1
        for (int i = 0; i < EPF; i++) {
            if (i) delay_until(clk(), EPD);
            if (elect())
                asm volatile("cp.async.bulk.prefetch.tensor.3d.L2.global [%0, {0, %1, %2}];" ::"l"(&tmq), "r"((blockIdx.x & 3) * 256 + i * 64), "r"((blockIdx.x >> 2) * 2) : "memory");
        }
    }
    if (rk == 0 && w <= PW) bsync<2, 32 * PW + 32>();
    asm volatile("barrier.cluster.wait.aligned;" ::: "memory");
    if (rk == 0 && threadIdx.x == 0) {
        uint32_t t1 = lds32(sb + SM_ROLE + 8), t0 = lds32(sb + SM_ROLE + 12);
        if (PW == 4) { t1 = min(t1, lds32(sb + SM_ROLE + 16)); t0 = min(t0, lds32(sb + SM_ROLE + 20)); }
        uint32_t side = (t0 < t1 ? 0u : 1u) ^ par(XO_PB);
        uint32_t* tk = (uint32_t*)(((uint64_t)xhi << 32) | (xlo + XO_TK));
        uint32_t t = atomicAdd(tk + side, 1u);
        if (t >= 32) {
            uint2 c;
            int it = 0;
            do {
                c = ldg2<XO_TK>(xlo, xhi);
                if (++it > SPIN_LIMIT) die(it);
            } while (c.x + c.y != gridDim.x / 2);
            t += (side ? c.x : c.y) - 32;
            side ^= 1;
            if (t >= 32) tickets_done(tk);
        }
#pragma unroll
        for (uint32_t r = 0; r < 2; r++)
            asm volatile("st.async.weak.shared::cluster.mbarrier::complete_tx::bytes.b32 [%0], %1, [%2];"
                         ::"r"(sb + SM_ROLE + (r << 24)), "r"(t * 4 + side * 2 + r), "r"(bq + BAR_RO + (r << 24)) : "memory");
    }
    __syncwarp();
    mbar_wait(bq + BAR_RO, 0);
    const uint32_t role = __reduce_max_sync(0xFFFFFFFFu, lds32(sb + SM_ROLE));
    if (role >= 128) return;
    const uint32_t h = role >> 2, j = role & 3;
    if (FTM && w == 11 && elect())
#pragma unroll
        for (uint32_t c = 0; c < FTM; c++) {
            mbar_expect(bq + BAR_WF + c * 8, 16384);
            tma3d(sb + SM_ST + c * 16384, &tmq, bq + BAR_WF + c * 8, 0, j * 256 + c * 64, h * 2);
        }

    if (w >= 8) {
        asm volatile("setmaxnreg.dec.sync.aligned.u32 24;");
        const uint32_t u = w - 8;
        if (u == 3) {
#pragma unroll 1
            for (uint32_t c = FTM; c < 16; c++) {
                if (c >= WIN) mbar_wait(bq + BAR_WF + (c - WIN) * 8, 0);
                if (l16 == 0) PG(16 + c);
                if (c == 12 + WOP) bsync<2, 64>();
                if (c >= 4 && c < 12 && c != 10) mbar_wait(bq + BAR_WE + (c - 4) * 8, 0);
                if (elect()) {
                    const uint32_t b = bq + BAR_WF + c * 8;
                    mbar_expect(b, 16384);
                    if (c >= 12) tma2d(sb + SM_WO + (c - 12) * WO_BOX, &tmo, b, j * 256 + (c - 12) * 64, h * 128);
                    else tma3d(c == 10 ? sb + SM_WV : sb + SM_ST + (c & 3) * 16384, c < 4 ? &tmq : c < 8 ? &tmk : &tmv, b, 0, j * 256 + ((c ^ (c >= 10)) & 3) * 64, h * 2);
                }
            }
#pragma unroll 1
            for (uint32_t c = 16 - WIN; c < 16; c++) mbar_wait(bq + BAR_WF + c * 8, 0);
            if (l16 == 0) PG(15);
        } else if (u == 0) {
            if (elect()) {
                mbar_expect(bq, 49152);
#pragma unroll 1
                for (uint32_t i = 0; i < 12; i++)
                    tma3d(sb + SM_X + (i < 4 ? i : i + 4) * 4096, &tmx, bq, 0, i < 8 ? i * 8 : (j ^ ((0xBD98u >> (i - 8) * 4) & 15)) * 8, j * 4);
            }
#pragma unroll 1
            for (int i = 0; i < 4; i++) xload(sb, i, j, -1, &tmx);
            bsync<3, 320>();
            if (l16 == 0) PG(32);
            if (GH && j == 0 && elect()) asm volatile("{\n.reg .b64 a;\nmov.b64 a, {%0,%1};\nred.relaxed.gpu.global.inc.u32 [a+64], 4;\n}" ::"r"(xlo + XO_FL + h * 128), "r"(xhi) : "memory");
            __syncwarp();
            g_arrive(xlo + XO_FL + h * 128, xhi, 4);
            if (WOP < 4) barv<2, 64>();
            if (l16 == 0) PG(33);
            g_wait(xlo + XO_FL + h * 128, xhi);
            if (l16 == 0) PG(34);
#pragma unroll 1
            for (int i = 0; i < 4; i++)
                if (elect()) kvload(sb, i, h, j, 0, xlo, xhi);
            mbar_wait(bq + BAR_KV, 0);
            if (l16 == 0) PG(14);
        } else if (u == 1) {
            const uint32_t l = l16 >> 4, x = h * 8 + (l >> 2), d = (x & ~31u) + (l & 3) * 8 + ((x & 31) >> 2) + (x & 3) * 2 * DM;
            const unsigned short* m0 = (const unsigned short*)mem0 + j * 256;
            const uint32_t v1 = m0[d] | (((l & 3) == 3 ? 0x4200u : m0[d + DM]) << 16);
            const uint32_t v3 = h < 8 ? m0[h * 32 + 24 + (l >> 2) + ((l & 3) * 2 + 1) * DM] | 0x42000000u : 0;
#pragma unroll 1
            for (uint32_t i = 0; i < 12; i++) {
                if (i == 10) { sts32(sb + SM_WO + 6144 + l * 4, v1); sts32(sb + SM_WO + 6272 + l * 4, v3); }
                asm volatile("fence.proxy.async.shared::cta;" ::: "memory");
                __syncwarp();
                const uint32_t c = (0x21924u >> ((i - 3) * 2)) & 3;
                if (elect()) {
                    if (i < 3) bulk_s2g(xlo + XO_XG + (i * 128 + role) * 6144, xhi, sb + SM_WO, 6144);
                    else bulk_s2g(xlo + XO_R + rpage(j, i < 6 ? 0 : i < 9 ? 1 : -1) + c * 16384 + h * 128, xhi, sb + SM_WO + (i < 10 ? 0 : 6144 + c * 64), 128);
                }
            }
            asm volatile("cp.async.bulk.wait_group 0;" ::: "memory");
            if (elect()) asm volatile("{\n.reg .b64 a;\nmov.b64 a, {%0,%1};\nred.relaxed.gpu.global.inc.u32 [a], 127;\n}" ::"r"(xlo + XO_TK + 12), "r"(xhi) : "memory");
            if (l16 == 0) PG(16);
            g_wait(xlo + XO_TK + 12, xhi);
            if (l16 == 0) PG(17);
            barv<5, 288>();
            bsync<8, 320>();
            asm volatile("fence.acq_rel.gpu;" ::: "memory");
        } else {
            GSYNC(0);
            mbar_wait(bq + BAR_WE + 48, 0);
#pragma unroll 1
            for (int e = 0; e < 24; e++) sts128(sb + SM_TR + 4096 + e * 512 + l16, 0, 0, 0, 0);
            barv<3, 320>();
            bsync<8, 320>();
#pragma unroll 1
            for (int i = 0; i < 4; i++) xload(sb, i, j, 0, &tmx);
        }
        if (LDP) asm volatile("griddepcontrol.launch_dependents;" ::: "memory");
#pragma unroll 1
        for (int s = 0; s < nseg; s++) helper_step(sb, w, h, j, l16, xlo, xhi, zero, s, &tmx, &tmb);
        piwait(sb, 0, nseg - 2);
        bsync<9, 384>();
        GSYNC(1);
        if (!GS && w == 11 && elect()) asm volatile("prefetch.tensormap [%0];" ::"l"(&tmy) : "memory");
        if (GH && w == 10) { g_arrive(xlo + XO_FL + h * 128 + 64, xhi, 5); PG(2); }
        if (w < 10) {
            uint32_t kb = 2, heads = 0;
            asm volatile("fence.proxy.async.shared::cta;" ::: "memory");
            if (GH) {
                if (w == 9 && h >= 30) { kb = 0; heads = 0xFFFF; }
                else delay_until(clk(), GD);
            } else if (w == 9) {
                g_arrive(xlo + XO_TK + 192, xhi, 128);
                PG(2);
                if (h >= 30) { g_wait(xlo + XO_TK + 192, xhi); kb = 0; }
                PG(3);
            } else delay_until(clk(), GD);
#pragma unroll 1
            for (; kb < 32; kb++) {
                if (kb >= 4) mbar_wait(bq + BAR_GE + (kb & 3) * 8, ((kb >> 2) & 1) ^ 1);
                if (GH && ((heads >> (kb >> 1)) & 1)) {
                    int it = 0;
                    do {
                        uint32_t v;
                        asm volatile("{\n.reg .b64 a;\nmov.b64 a, {%1,%2};\nld.acquire.gpu.global.u32 %0, [a+64];\n}"
                                     : "=r"(v) : "r"(xlo + XO_FL + (role & 1) * 2048 + (l16 & 255) * 8), "r"(xhi) : "memory");
                        heads = __ballot_sync(0xFFFFFFFFu, v != 0);
                        if (++it > SPIN_LIMIT) die(it);
                    } while ((heads >> (kb >> 1)) & 1);
                    asm volatile("fence.proxy.async.global;" ::: "memory");
                    if (kb == 0) PG(3);
                }
                g_load(sb, w - 8, role, kb, xlo, xhi, &tmb);
            }
        }
        if (role == 0 && w == 11 && elect()) tickets_done((uint32_t*)(((uint64_t)xhi << 32) | (xlo + XO_TK)));
    } else {
        asm volatile("setmaxnreg.inc.sync.aligned.u32 240;");
        uint32_t Wq[16][4], Wk[16][4], Wv[NA][4];
        uint32_t t16, KA, KB, KC, KD;
        {
            const uint32_t lane = l16 >> 4, g = lane >> 2, t = lane & 3;
            const uint32_t rw = (((lane >> 4) & 1) * 8 + (lane & 7)) * 128u;
            const uint32_t off = rw + ((((w & 3) * 2 + ((lane >> 3) & 1)) ^ (lane & 7)) << 4);
            const uint32_t offo = rw + ((((w & 1) * 4 + ((lane >> 3) & 1)) ^ (lane & 7)) << 4);
            const uint32_t r = 2 * (t & 1) + (g >> 2);
            const uint32_t mk0 = t < 2 ? 0 : (r == 0 ? 2 * g > w : j + r < 4), mk1 = t < 2 ? 0 : (r == 0 ? 2 * g + 1 > w : j + r < 4);
            t16 = __shfl_sync(0xFFFFFFFFu, w * 512 + l16, lane);
            KA = __shfl_sync(0xFFFFFFFFu, (w * 512 + t * 64 + g * 8) | ((w * 512 + (g & 1) * 256 + (g >> 1) * 64 + t * 16) << 16), lane);
            KB = __shfl_sync(0xFFFFFFFFu, ((w >> 2) * WV_BOX + off) | mk0 | (mk1 << 1) |
                                              ((w * 256 + (g >> 2) * 4096 + (g & 3) * 64 + t * 16) << 16), lane);
            KC = __shfl_sync(0xFFFFFFFFu, ((lane & 7) * 1280 + (lane >> 3) * 128 + ((w ^ (lane & 7)) << 4)) | (((t >> 1) * 16 + g * 2) << 16) | ((t * 64 + g * 8) << 24), lane);
            KD = __shfl_sync(0xFFFFFFFFu, ((w >> 1) * WO_BOX + offo) | (((lane & 7) * 208 + (lane >> 3) * 16) << 16), lane);
            if (threadIdx.x == 0) PG(8);
#define WTAKE(W, c, k0) { mbar_wait(bq + BAR_WF + (c) * 8, 0); \
                _Pragma("unroll") for (int ks = 0; ks < 4; ks++) ldsm4t(W[(k0) + ks], sb + SM_ST + ((c) & 3) * 16384 + (KB & 0xFFF0) + ks * 2048); \
                if ((c) < 8) { __syncwarp(); if (elect()) mbar_arrive(bq + BAR_WE + (c) * 8); } }
#pragma unroll
            for (int c = 0; c < 4; c++) WTAKE(Wq, c, c * 4);
            mbar_wait(bq, 0);
            if (threadIdx.x == 0) PG(9);
            xstart<0>(sb, w, xlo + h * 24576, xhi, j, t16, KA, Wq);
            if (threadIdx.x == 0) PG(10);
#pragma unroll
            for (int c = 0; c < 4; c++) WTAKE(Wk, c + 4, c * 4);
            if (threadIdx.x == 0) PG(11);
            xstart<1>(sb, w, xlo + h * 24576, xhi, j, t16, KA, Wk);
            if (threadIdx.x == 0) PG(12);
            WTAKE(Wv, 8, 0);
            WTAKE(Wv, 9, 4);
            mbar_wait(bq + BAR_WF + 80, 0);
            WTAKE(Wv, 11, 8);
            if (threadIdx.x == 0) PG(13);
            xstart<2>(sb, w, xlo + h * 24576, xhi, j, t16, KA, Wv);
            mbar_wait(bq + BAR_XA, 0);
            bsync<8, 320>();
        }
        const uint32_t ONES = 0x3F803F80u;
#define UNI(x) __reduce_max_sync(0xFFFFFFFFu, x)
        uint32_t swi = UNI((uint32_t)((uint64_t)smem >> 32));
        const uint32_t sbw = UNI(sb + w * 256), sbm = UNI(sb - w * 512), sbs = UNI(sb + w * 768), sbp = UNI(sb + w * 208);
#define OPQALL() { OPQ(t16); OPQ(KA); OPQ(KB); OPQ(KC); OPQ(KD); }
        OPQALL();
        if (SEED & 1) OPQ(Wq[0][0]);
        if (SEED & 2) OPQ(Wq[5][1]);
        if (SEED & 4) OPQ(Wk[0][0]);
        if (SEED & 8) OPQ(Wk[15][2]);
        if (SEED & 16) OPQ(Wv[0][0]);
        if (SEED & 32) OPQ(Wv[7][3]);
        const uint32_t cb0 = (h >> 1) * 32768 + (j & 1) * 16384 + (h & 1) * 8192;
        const uint32_t cb = UNI(xlo + cb0 + ((par(cb0) ^ (j >> 1) ^ CFAR) << 12)), cv = UNI(xlo + h * 8192 + JV(h, j) * 2048), h1 = UNI((h & 1) * 1024);
        const uint32_t uox = UNI(xlo + XO_OX + (h * 2 + (w >> 2)) * 262144 + j * 1024 + (w & 3) * 256 - w * 128);
        uint32_t rp = UNI(xlo + rpage(j, 0));
        float ox[4];
        float4 dn;
#define OXSTORE(s) asm volatile("{\n.reg .b64 a;\nmov.b64 a, {%0,%1};\nst.global.u32 [a], %2;\nst.global.u32 [a+128], %3;\n}" \
                                ::"r"(uox + (s) * 4096 + (t16 >> 2)), "r"(xhi), \
                                  "r"(pack2(ox[0] * dn.y, ox[1] * dn.w)), "r"(pack2(ox[2] * dn.y, ox[3] * dn.w)) : "memory")
#pragma unroll 1
        for (int s2 = 0;; s2 += 2, rp ^= 0x21000)
#pragma unroll
        for (int p = 0; p < 2; p++) {
            const int s = s2 + p;
            const uint32_t ctag = ((s2 >> 1) & 1) ^ 1;
            const uint32_t hb = cb ^ (p * 0x81000), rb = rp ^ (p * 0x11000);
            uint4 k0, k1, qq, c0, c1, c2, c3, pk;
            float va[4], vb[4];
            uint32_t qx0, qx1, ov0, ov1, wv[16 - NA][4];
            {
                float xa[16], xb[16];
                uint4 m0, n0;
                uint32_t e0, f0;
                uint32_t xp[8];
                wg_fence();
                XMMA(0, XM0);
                SF();
                piwait(sb, p, s - 2);
                uint4 pi = xpeer<0>(sb, p ^ 1, t16);
                SF();
#define MR (VC ? 1 : 2)
#define MC (VC ? 2 : 1)
#define QPARK() { xpack<0>(xp, xa); xpark<0>(xp, pi, sb, sbw, p ^ 1, t16, KA); pi = xpeer<MR>(sb, p ^ 1, t16); SF(); }
                wg_fence();
                if (QP) {
                    XMMA(XM0, QP);
                    XMMA(QP, QP + QW);
                    wg_wait<1>();
                    SF();
                    QPARK();
                    wg_fence();
                    if (QP + QW < RPOS) XMMA(QP + QW, RPOS);
                } else XMMA(6, RPOS);
                if (RPOS < 32) XMMA(RPOS, RPOS + RW < 32 ? RPOS + RW : 32);
                uint32_t a = (p ? rp : rp ^ 0x30000) + t16, e = (p ? rp : rp ^ 0x30000) + (t16 >> 2), ah = xhi, eh = xhi;
                OPQ(a); OPQ(e); OPQ(ah); OPQ(eh);
                SF();
                wg_wait<(RPOS < 32)>();
                SF();
                PT(11);
                RLOAD();
                SF();
                if (!QP) QPARK();
                if (RPOS + RW < 32) {
                    wg_fence();
                    XMMA(RPOS + RW < 32 ? RPOS + RW : 31, 32);
                    SF();
                }
                wg_wait<0>();
                xpack<MR>(xp, xb);
                xpark<MR>(xp, pi, sb, sbw, p ^ 1, t16, KA);
                uint32_t acw, ahi, tg;
#define APREP() { OPQ(KA); if (!APH) OPQ(t16); acw = hb + (KA & 0xFFFF); ahi = xhi; tg = ctag; OPQ(acw); OPQ(ahi); OPQ(tg); }
                if (APH == 3) SF();
                if (APH) APREP();
                if (APH >= 2) OPQ(t16);
                SF();
                PT(12);
                {
                    int it = 0;
                    if (RDW) {
                        bool rb_;
#pragma unroll 1
                        do {
                            rb_ = ruse(sb + SM_MEMT + t16, m0, n0, e0, f0);
                            if (RDW == 2) MF();
                            if (RDW == 3) SF();
                            asm volatile("{\n.reg .pred p, q;\n.reg .b64 a, e;\nsetp.ne.u32 p, %15, 0;\nmov.b64 a, {%11,%12};\nmov.b64 e, {%13,%14};\n"
                                         "@p ld.relaxed.gpu.global.v4.u32 {%0,%1,%2,%3}, [a];\n@p ld.relaxed.gpu.global.v4.u32 {%4,%5,%6,%7}, [a+16384];\n"
                                         "@p ld.relaxed.gpu.global.u32 %8, [e+32768];\n@p ld.relaxed.gpu.global.u32 %9, [e+33792];\n"
                                         "add.u32 %10, %10, 1;\nsetp.gt.u32 q, %10, 1048576;\n@q st.shared.u32 [%10], %10;\n}"
                                         : "+r"(m0.x), "+r"(m0.y), "+r"(m0.z), "+r"(m0.w), "+r"(n0.x), "+r"(n0.y), "+r"(n0.z), "+r"(n0.w), "+r"(e0), "+r"(f0), "+r"(it)
                                         : "r"(a), "r"(ah), "r"(e), "r"(eh), "r"((uint32_t)rb_) : "memory");
                        } while (rb_);
                    } else
                    while (ruse(sb + SM_MEMT + t16, m0, n0, e0, f0)) {
                        RLOAD();
                        if (++it > SPIN_LIMIT) die(it);
                    }
                    PC(22, it + 1);
                }
                PT(13);
                if (APH == 1) OPQ(t16);
                if (!APH) APREP();
#define AX (p ? A1 : A0)
                float q[4], k[4];
                if (AX & 2) _Pragma("unroll") for (int i = 0; i < 4; i++) {
                    asm volatile("mov.b32 %0, %1;" : "=f"(q[i]) : "r"(zero)); asm volatile("mov.b32 %0, %1;" : "=f"(k[i]) : "r"(zero)); }
                if (APH < 2) SF();
                bsync<1, 384>();
                PT(0);
                uint32_t b[8][4];
#pragma unroll
                for (int i = 0; i < 8; i++) {
                    const int pp = i < 2 || (AX & 8) || ((AX & 16) && i >= 6) ? i : i ^ 1;
                    ldsm4t(b[pp], sbm + SM_MEMT + t16 + pp * 512);
                    if (i < 7 || (AX & 4)) MF();
                }
                if (ASF) SF();
                const uint32_t aWv = sb + SM_WV + (KB & 0xFFF0);
#define WVLD(n0, n1) _Pragma("unroll") for (int n = (n0); n < (n1) && n < 16 - NA; n++) ldsm4t(wv[n], aWv + n * 2048)
#pragma unroll
                for (int ks = 0; ks < 16; ks++) {
                    const uint32_t b0 = b[ks >> 1][(ks & 1) * 2], b1 = b[ks >> 1][(ks & 1) * 2 + 1];
                    if (AX & 1) {
                        if (ks == 0 && !(AX & 2)) {
                            mma16z(k, Wk[0][0], Wk[0][1], Wk[0][2], Wk[0][3], b0, b1);
                            mma16z(q, Wq[0][0], Wq[0][1], Wq[0][2], Wq[0][3], b0, b1);
                        } else {
                            mma16(k, Wk[ks][0], Wk[ks][1], Wk[ks][2], Wk[ks][3], b0, b1);
                            mma16(q, Wq[ks][0], Wq[ks][1], Wq[ks][2], Wq[ks][3], b0, b1);
                        }
                    } else if (ks == 0 && !(AX & 2)) {
                        mma16z(q, Wq[0][0], Wq[0][1], Wq[0][2], Wq[0][3], b0, b1);
                        mma16z(k, Wk[0][0], Wk[0][1], Wk[0][2], Wk[0][3], b0, b1);
                    } else {
                        mma16(q, Wq[ks][0], Wq[ks][1], Wq[ks][2], Wq[ks][3], b0, b1);
                        mma16(k, Wk[ks][0], Wk[ks][1], Wk[ks][2], Wk[ks][3], b0, b1);
                    }
                    if (ks == (VKS & 15) && VPF) { if (VKS < 16) SF(); WVLD(0, VPF); }
                }
                const uint32_t oq0 = settag(pack2(q[0], q[2]), tg), oq1 = settag(pack2(q[1], q[3]), tg);
                const uint32_t ok0 = pack2(k[0], k[2]), ok1 = pack2(k[1], k[3]);
                stg2<XO_CQK>(acw, ahi, oq0, ok0);
                stg2<XO_CQK + 256>(acw, ahi, oq1, ok1);
                SF();
                PT(1);
#define CLOADG() { c2 = ldg4<XO_CQK>((hb ^ 0x1000) + (KA >> 16), xhi); c3 = ldg4<XO_CQK>((hb ^ 0x5000) + (KA >> 16), xhi); }
#define CLOAD0() c0 = lds128(sb + SM_TR + (KA >> 16))
#define CLOAD1() c1 = lds128(sb + SM_TR + 4096 + p * 4096 + (KA >> 16))
#define CLOADS() { CLOAD0(); CLOAD1(); }
#define CSIDE(n) { if (CGP == (n)) CLOADG(); if (C0P == (n)) CLOAD0(); if (C1P == (n)) CLOAD1(); if (PIP == (n)) pk = xpeer<MC>(sb, p ^ 1, t16); \
                   if (QSP == (n)) { qx0 = (t16 & 64) ? qq.y : qq.x; qx1 = (t16 & 64) ? qq.w : qq.z; } }
#pragma unroll
                for (int rd = 0; rd < 8; rd++) {
                    const int pp = (VORD >> (28 - 4 * rd)) & 7;
                    const uint32_t* a = 2 * pp < NA ? Wv[2 * pp < NA ? 2 * pp : 0] : wv[2 * pp < NA ? 0 : 2 * pp - NA];
                    const uint32_t* c = 2 * pp < NA ? Wv[2 * pp < NA ? 2 * pp + 1 : 0] : wv[2 * pp < NA ? 0 : 2 * pp + 1 - NA];
                    if (rd == 0) {
                        mma16z(va, a[0], a[1], a[2], a[3], b[pp][0], b[pp][1]);
                        mma16z(vb, c[0], c[1], c[2], c[3], b[pp][2], b[pp][3]);
                        if (VSB & 256) SF();
                        OPQ(swi);
                        asm volatile("{\n.reg .b64 a;\nmov.b64 a, {%0,%1};\nst.v2.u32 [a], {%2,%3};\nst.v2.u32 [a+256], {%4,%5};\n}"
                                     ::"r"((KA & 0xFFF) + (sb ^ 0x1000000) + SM_TR + 4096 + p * 4096), "r"(swi), "r"(oq0), "r"(ok0), "r"(oq1), "r"(ok1) : "memory");
                        sts64(sb + SM_TR + (KA & 0xFFF), oq0, ok0);
                        sts64(sb + SM_TR + (KA & 0xFFF) + 256, oq1, ok1);
                    } else {
                        mma16(va, a[0], a[1], a[2], a[3], b[pp][0], b[pp][1]);
                        mma16(vb, c[0], c[1], c[2], c[3], b[pp][2], b[pp][3]);
                    }
                    if (rd == (p ? KEP : KEP0)) { KEEP(t16, oq0, oq1, ok0, ok1); if (KE2) KEEP(t16, acw, ahi, acw, ahi); }
                    if (((p ? VSB : VSB0) >> rd) & 1) SF();
                    if (rd == W2P) WVLD(2, 3);
                    if (rd == W3P) WVLD(3, 4);
                    if (rd == K0P) k0 = lds128(sb + SM_KV + 2048 + (KB >> 16));
                    if (rd == K0P + 1) k1 = lds128(sb + SM_KV + 10240 + (KB >> 16));
                    if (rd == QQP) qq = lds128(sbw + SM_KV + ((KA >> 16) & 0xFF));
                    CSIDE(rd);
                    if ((VSF >> rd) & 1) SF(); else if ((VMF >> rd) & 1) MF();
                }
#define VTAIL() { ov0 = pack2(va[0] + vb[0], va[1] + vb[1]); ov1 = pack2(va[2] + vb[2], va[3] + vb[3]); \
                  stg2<XO_CV>(cv + p * 262144 + (t16 >> 1), xhi, settag(ov0, ctag), ov1); \
                  if (VD) asm volatile("{\n.reg .b64 a;\nmov.b64 a, {%0,%1};\nst.v2.u32 [a], {%2,%3};\n}" \
                                     ::"r"((t16 >> 1) + (sb ^ 0x1000000) + SM_VP + p * 2048), "r"(swi), "r"(settag(ov0, ctag)), "r"(ov1) : "memory"); \
                  barv<8, 384>(); OPQ(t16); SF(); }
                if (!VTP) VTAIL();
            }
            PT(2);
            PDUMP();
            {
                const uint32_t a0 = sb + SM_KV;
                float xa[16], xb[16];
                uint32_t xp[8];
                if (CGP == 12 || QSP == 12) { CSIDE(12); SF(); }
                wg_fence();
                XMMA(32, 32 + CPOS);
                if (CGP == 13) { SF(); CSIDE(13); SF(); wg_fence(); }
                if (VR == 1) { XMMA(32 + CPOS, 36); XMMA(36, 36 + CW2); wg_wait<2>(); }
                else if (CW) { XMMA(32 + CPOS, 36 + CPOS); wg_wait<1>(); }
                SF();
                CSIDE(8);
                SF();
                if (VR == 1) { wg_wait<1>(); SF(); }
                if (VTP) VTAIL();
                CSIDE(9);
                SF();
                wg_fence();
                XMMA(VR == 1 ? 36 + CW2 : 32 + CPOS + (CW ? 4 : 0), 48);
                SF();
                uint2 u1, u2, u3;
#define ULOADG() { u2 = ldg2<XO_CV>((cv ^ 4096) + p * 262144 + (t16 >> 1), xhi); u3 = ldg2<XO_CV>((cv ^ 6144) + p * 262144 + (t16 >> 1), xhi); }
#define ULOADS() u1 = lds64(sb + SM_VP + p * 2048 + (t16 >> 1))
#define UCHECK() { int it = 0; \
                   while (__builtin_expect(any_bad(tagx1(tagx2(u2.x, u3.x, ctag), u1.x, ctag)), 0)) { OPQ(t16); ULOADG(); ULOADS(); if (++it > SPIN_LIMIT) die(it); } \
                   PC(26, it); }
                CSIDE(10);
                if (B3 == 8 && VLP == 2) ULOADG();
                SF();
                const uint32_t ka[4] = {k0.x, k0.y, k0.z, k0.w}, kb[4] = {k1.x, k1.y, k1.z, k1.w};
                const uint32_t aSp = sb + SM_SP + (KC & 0xFFFF);
                PT(3);
#define BAR3() asm volatile("{\n.reg .pred p;\nsetp.eq.u32 p, %0, 0;\n@p bar.arrive 3, %1;\n}" ::"r"((uint32_t)bad), "n"(B3 == 6 ? 288 : 384) : "memory")
#define SCORES(FIRST) { \
                    const uint32_t qA = hadd2(hadd2(c0.x, c1.x), hadd2(c2.x, c3.x)), qB = hadd2(hadd2(c0.z, c1.z), hadd2(c2.z, c3.z)); \
                    const uint32_t kA = hadd2(hadd2(c0.y, c1.y), hadd2(c2.y, c3.y)), kB = hadd2(hadd2(c0.w, c1.w), hadd2(c2.w, c3.w)); \
                    bad = any_bad(or3(tagx2(c1.x, c1.z, ctag), tagx2(c2.x, c2.z, ctag), tagx2(c3.x, c3.z, ctag))); \
                    float sa[4], sb_[4], sc[4], sd[4], se[4]; \
                    if (FIRST) { SF(); if (B3 == 8 && VLP == 3) ULOADG(); CSIDE(11); wg_wait<0>(); } \
                    mma16z(sa, ka[0], ka[1], ka[2], ka[3], qA, qB); \
                    mma16z(sb_, kb[0], kb[1], kb[2], kb[3], qA, qB); \
                    mma16z(sc, qA, qx0, qB, qx1, kA, kB); \
                    if (FIRST) { \
                        xpack<MC>(xp, xa); \
                        if (KPOS == 0) { xadd(xp, pk); xstore<MC>(xp, sb, sbw, p ^ 1, t16, KA); if (B3 >= 5) BAR3(); else if (!B3 || B3 >= 3) barv<3, 384>(); } \
                        mma16z(sd, ka[0], ka[1], ka[2], ka[3], qx0, qx1); \
                        mma16z(se, kb[0], kb[1], kb[2], kb[3], qx0, qx1); \
                    } \
                    stsm4t(aSp, pack2(sa[0], sa[1]), pack2(sa[2], sa[3]), pack2(sb_[0], sb_[1]), pack2(sb_[2], sb_[3])); \
                    stsm2(aSp + 1024, pack2(sc[0], sc[1]), pack2(sc[2], sc[3])); \
                    if (FIRST) { \
                        stsm4t(aSp + 512, pack2(sd[0], sd[1]), pack2(sd[2], sd[3]), pack2(se[0], se[1]), pack2(se[2], se[3])); \
                        if (KPOS == 0) { KEEP(KD, xp[0], xp[1], xp[2], xp[3]); KEEP(KD, xp[4], xp[5], xp[6], xp[7]); } \
                    } }
                int it = 0;
                bool bad;
                SCORES(true);
                while (__builtin_expect(bad, 0)) {
                    OPQ(KA);
                    CLOADG();
                    CLOADS();
                    SCORES(false);
                    if (B3 >= 5) BAR3();
                    if (++it > SPIN_LIMIT) die(it);
                }
                PC(25, it);
                PT(4);
                if (B3 == 8 && VLP == 0) ULOADG();
                if (B3 == 1) barv<3, 384>();
                bsync<4, B3 == 2 ? 384 : 256>();
                uint32_t wo[16][4];
                const uint32_t aWo = sb + SM_WO + (KD & 0xFFFF), aWo1 = sb + SM_WO + ((KD & 0xFFFF) ^ 32);
#define WOLD(n0, n1) _Pragma("unroll") for (int n = (n0); n < (n1) && n < 16; n++) ldsm4t(wo[n], ((n & 1) ? aWo1 : aWo) + (n >> 1) * 2048)
                const bool hi = (t16 & 32) != 0;
                const uint32_t t8 = t16 >> 1;
                uint2 v0, v1, v2, v3;
                uint32_t es;
                {
                    uint32_t am[4], ax[4], a4[2];
                    const uint32_t aSr = sbs + SM_SP + t16;
                    ldsm4t(am, aSr);
                    ldsm4t(ax, aSr + 512);
                    ldsm2t(a4, aSr + 1024);
                    MF();
                    if (B3 == 8 && VLP == 1) ULOADG();
                    if (KPOS == 1) pk = xpeer<MC>(sb, p ^ 1, t16);
                    const uint32_t se = (t16 & 128) ? 0u : ONES, so = se ^ ONES;
                    float hm[4], hx[4], h4[4];
                    mma16z(hm, am[0], am[1], am[2], am[3], se, so);
                    mma16z(hx, ax[0], ax[1], ax[2], ax[3], se, so);
                    mma8z(h4, a4[0], a4[1], ONES);
                    SF();
                    if (KPOS == 1) { xpark<MC>(xp, pk, sb, sbw, p ^ 1, t16, KA); barv<3, 384>(); }
                    v0 = lds64(a0 + 4096 + t8); v1 = lds64(a0 + 8192 + t8); v2 = lds64(a0 + 12288 + t8); v3 = lds64(a0 + 16384 + t8);
                    if (B3 == 8) ULOADS();
                    WOLD(0, PF2);
                    float s0 = hi ? hx[0] : hm[0], s1 = hi ? hx[2] : hm[2];
                    const float s2 = hi ? h4[2] : h4[0];
                    s0 = (KB & 1) ? -1.0e9f * 11.313708499f : s0;
                    s1 = (KB & 2) ? -1.0e9f * 11.313708499f : s1;
                    int mi = __float_as_int(fmaxf(fmaxf(s0, s2), s1));
                    mi ^= (mi >> 31) & 0x7FFFFFFF;
                    const int mm = __reduce_max_sync(0xFFFFFFFFu, hi ? (int)0x80000000 : mi), mx = __reduce_max_sync(0xFFFFFFFFu, hi ? mi : (int)0x80000000);
                    SF();
                    WOLD(PF2, PF3);
                    SF();
                    mi = hi ? mx : mm;
                    mi ^= (mi >> 31) & 0x7FFFFFFF;
                    const float c2_ = 0.08838834764831845f * 1.4426950408889634f;
                    const float mc = __int_as_float(mi) * c2_;
                    const float e0 = ex2(fmaf(s0, c2_, -mc)), e1 = ex2(fmaf(s1, c2_, -mc)), e2 = ex2(fmaf(s2, c2_, -mc));
                    sts32(sbp + SM_P + (KC >> 25), pack2(e0, e1));
                    sts16(sbp + SM_P + 128 + ((KC >> 16) & 0xFF), pack2(e2, e2));
                    es = __float_as_uint(fmaf(e2, 0.5f, e0 + e1) + 64.f);
                }
                const uint32_t sm = __reduce_add_sync(0xFFFFFFFFu, hi ? 0u : es), sx = __reduce_add_sync(0xFFFFFFFFu, hi ? es : 0u);
                const uint32_t aPr = sb + SM_P + (KD >> 16);
                if (B3 == 8 && VCP == 0) UCHECK();
                PT(5);
                bsync<5, VB ? 256 : B3 == 6 ? 352 : 384>();
                uint32_t pm[4], px[4], p4[2];
                ldsm4(pm, aPr);
                MF();
                uint2 vs;
                #define VGET(n) if (VB == (n)) { if (VB) bsync<11, 384>(); vs = lds64(sb + SM_VS + t8); MF(); }
                if (B3 != 8) { VGET(0); VGET(1); }
                ldsm2(p4, aPr + 128);
                MF();
                VGET(2);
                ldsm4(px, aPr + 64);
                MF();
                VGET(3);
#define DNST(n) if (DNP == (n)) { sts32f(sb + SM_DN + w * 8 + ((t16 >> 3) & 4), rcp(__uint_as_float((hi ? sx : sm) - 15u * 0x42800000u) - 64.f)); MF(); }
                DNST(0);
                if (B3 == 8 && VCP == 2) UCHECK();
                if (WLP == 0) { WOLD(PF3, NPF); }
                if (DNP == 1) MF();
                DNST(1);
                if (B3 == 8 && VCP == 1) UCHECK();
                if (B3 == 8) { ov0 = hadd2(ov0, u1.x); ov1 = hadd2(ov1, u1.y); vs.x = hadd2(u2.x, u3.x); vs.y = hadd2(u2.y, u3.y); }
                const uint32_t vm0 = hadd2(ov0, vs.x), vm1 = hadd2(ov1, vs.y);
                float oa[4], ob[4];
                mma16z(oa, v0.x, v0.y, v1.x, v1.y, pm[0], pm[1]);
                mma16z(ob, v2.x, v2.y, v3.x, v3.y, pm[2], pm[3]);
                mma8(oa, vm0, vm1, p4[0]);
                stsm2(sbw + SM_OT + (t16 & 511), pack2(oa[0] + ob[0], oa[1] + ob[1]), pack2(oa[2] + ob[2], oa[3] + ob[3]));
                if (DNP == 2) MF();
                DNST(2);
                PT(6);
                SF();
                bsync<6, 256>();
                mma16z(ox, v0.x, v0.y, v1.x, v1.y, px[0], px[1]);
                uint32_t b[4][4];
#define OTLD(pp) ldsm4t(b[pp], sbm + SM_OT + t16 + (pp) * 512)
                OTLD(0);
                MF();
                OTLD(1);
                if (WLP == 1) { MF(); WOLD(PF3, NPF); }
                barv<7, 384>();
                mma16(ox, v2.x, v2.y, v3.x, v3.y, px[2], px[3]);
                mma8(ox, vm0, vm1, p4[1]);
                if (p == 1 && s + 1 == nseg) goto done;
                SF();
                uint32_t ar, ae, ahi = xhi;
                float r[2][4];
#pragma unroll
                for (int ks = 0; ks < 8; ks++) {
                    if (ks == 0) WOLD(NPF, NPF + WPF);
                    if (ks == OPOS) { OTLD(2); MF(); }
                    if (ks == OPOS + 2) { OTLD(3); MF(); }
                    if (ks > 0) WOLD(NPF + WPF + 2 * (ks - 1), NPF + WPF + 2 * ks);
                    if (ks == OAP) {
                        OPQ(t16);
                        ar = rb + h1 * 16 + t16; ae = rb + h1 + (t16 >> 2);
                        OPQ(ar); OPQ(ahi); OPQ(ae);
                        dn = lds128f(sb + SM_DN + (t16 & 48));
                    }
#pragma unroll
                    for (int mt = 0; mt < 2; mt++) {
                        const int i = ks * 2 + mt;
                        const uint32_t* a = wo[i];
                        if (i < 2) mma16z(r[mt], a[0], a[1], a[2], a[3], b[ks >> 1][2 * (ks & 1)], b[ks >> 1][2 * (ks & 1) + 1]);
                        else mma16(r[mt], a[0], a[1], a[2], a[3], b[ks >> 1][2 * (ks & 1)], b[ks >> 1][2 * (ks & 1) + 1]);
                    }
                    if ((OSF >> ks) & 1) SF();
                }
                const float r0 = dn.x, r1 = dn.z;
                asm volatile("{\n.reg .b64 a;\nmov.b64 a, {%0,%2};\nred.relaxed.gpu.global.add.noftz.v4.bf16x2 [a], {%3,%4,%5,%6};\n"
                             "mov.b64 a, {%1,%2};\nred.relaxed.gpu.global.add.noftz.bf16x2 [a+32768], %7;\n}"
                             ::"r"(ar), "r"(ae), "r"(ahi), "r"(pack2(r[0][0] * r0, r[0][1] * r1)), "r"(pack2(r[0][2] * r0, r[0][3] * r1)),
                               "r"(pack2(r[1][0] * r0, r[1][1] * r1)), "r"(pack2(r[1][2] * r0, 1.f)), "r"(pack2(r[1][3] * r1, 1.f)) : "memory");
                barv<10, 384>();
            }
            SF();
            PT(10);
            OXSTORE(s);
            OPQALL();
        }
    done:
        dn = lds128f(sb + SM_DN + (t16 & 48));
        OXSTORE(nseg - 1);
        barv<9, 384>();
        g_main(sb, w, role, &tmy, out);
        if (threadIdx.x == 0) PG(0);
    }
}

template <int SC> DEVI void wg_rs128t(float (&d)[64], const uint32_t (&a)[4], uint64_t db) {
    if (SC) asm volatile("wgmma.mma_async.sync.aligned.m64n128k16.f32.bf16.bf16 "
        "{%0,%1,%2,%3,%4,%5,%6,%7,%8,%9,%10,%11,%12,%13,%14,%15,%16,%17,%18,%19,%20,%21,%22,%23,%24,%25,%26,%27,%28,%29,%30,%31,%32,%33,%34,%35,%36,%37,%38,%39,%40,%41,%42,%43,%44,%45,%46,%47,%48,%49,%50,%51,%52,%53,%54,%55,%56,%57,%58,%59,%60,%61,%62,%63}, "
        "{%64,%65,%66,%67}, %68, 1, 1, 1, 1;"
        : D4(+, 0), D4(+, 4), D4(+, 8), D4(+, 12), D4(+, 16), D4(+, 20), D4(+, 24), D4(+, 28), D4(+, 32), D4(+, 36), D4(+, 40), D4(+, 44), D4(+, 48), D4(+, 52), D4(+, 56), D4(+, 60) : "r"(a[0]), "r"(a[1]), "r"(a[2]), "r"(a[3]), "l"(db));
    else asm volatile("wgmma.mma_async.sync.aligned.m64n128k16.f32.bf16.bf16 "
        "{%0,%1,%2,%3,%4,%5,%6,%7,%8,%9,%10,%11,%12,%13,%14,%15,%16,%17,%18,%19,%20,%21,%22,%23,%24,%25,%26,%27,%28,%29,%30,%31,%32,%33,%34,%35,%36,%37,%38,%39,%40,%41,%42,%43,%44,%45,%46,%47,%48,%49,%50,%51,%52,%53,%54,%55,%56,%57,%58,%59,%60,%61,%62,%63}, "
        "{%64,%65,%66,%67}, %68, 0, 1, 1, 1;"
        : D4(=, 0), D4(=, 4), D4(=, 8), D4(=, 12), D4(=, 16), D4(=, 20), D4(=, 24), D4(=, 28), D4(=, 32), D4(=, 36), D4(=, 40), D4(=, 44), D4(=, 48), D4(=, 52), D4(=, 56), D4(=, 60) : "r"(a[0]), "r"(a[1]), "r"(a[2]), "r"(a[3]), "l"(db));
}
template <int SC> DEVI void wg_rs64t(float (&d)[32], const uint32_t (&a)[4], uint64_t db) {
    if (SC) asm volatile("wgmma.mma_async.sync.aligned.m64n64k16.f32.bf16.bf16 "
        "{%0,%1,%2,%3,%4,%5,%6,%7,%8,%9,%10,%11,%12,%13,%14,%15,%16,%17,%18,%19,%20,%21,%22,%23,%24,%25,%26,%27,%28,%29,%30,%31}, "
        "{%32,%33,%34,%35}, %36, 1, 1, 1, 1;"
        : D4(+, 0), D4(+, 4), D4(+, 8), D4(+, 12), D4(+, 16), D4(+, 20), D4(+, 24), D4(+, 28) : "r"(a[0]), "r"(a[1]), "r"(a[2]), "r"(a[3]), "l"(db));
    else asm volatile("wgmma.mma_async.sync.aligned.m64n64k16.f32.bf16.bf16 "
        "{%0,%1,%2,%3,%4,%5,%6,%7,%8,%9,%10,%11,%12,%13,%14,%15,%16,%17,%18,%19,%20,%21,%22,%23,%24,%25,%26,%27,%28,%29,%30,%31}, "
        "{%32,%33,%34,%35}, %36, 0, 1, 1, 1;"
        : D4(=, 0), D4(=, 4), D4(=, 8), D4(=, 12), D4(=, 16), D4(=, 20), D4(=, 24), D4(=, 28) : "r"(a[0]), "r"(a[1]), "r"(a[2]), "r"(a[3]), "l"(db));
}
template <int SC> DEVI void wg_rs40(float (&d)[20], const uint32_t (&a)[4], uint64_t db) {
    if (SC) asm volatile("wgmma.mma_async.sync.aligned.m64n40k16.f32.bf16.bf16 "
        "{%0,%1,%2,%3,%4,%5,%6,%7,%8,%9,%10,%11,%12,%13,%14,%15,%16,%17,%18,%19}, "
        "{%20,%21,%22,%23}, %24, 1, 1, 1, 0;"
        : D4(+, 0), D4(+, 4), D4(+, 8), D4(+, 12), D4(+, 16) : "r"(a[0]), "r"(a[1]), "r"(a[2]), "r"(a[3]), "l"(db));
    else asm volatile("wgmma.mma_async.sync.aligned.m64n40k16.f32.bf16.bf16 "
        "{%0,%1,%2,%3,%4,%5,%6,%7,%8,%9,%10,%11,%12,%13,%14,%15,%16,%17,%18,%19}, "
        "{%20,%21,%22,%23}, %24, 0, 1, 1, 0;"
        : D4(=, 0), D4(=, 4), D4(=, 8), D4(=, 12), D4(=, 16) : "r"(a[0]), "r"(a[1]), "r"(a[2]), "r"(a[3]), "l"(db));
}
template <int SC> DEVI void wg_rs8(float (&d)[4], const uint32_t (&a)[4], uint64_t db) {
    if (SC) asm volatile("wgmma.mma_async.sync.aligned.m64n8k16.f32.bf16.bf16 "
        "{%0,%1,%2,%3}, "
        "{%4,%5,%6,%7}, %8, 1, 1, 1, 0;"
        : D4(+, 0) : "r"(a[0]), "r"(a[1]), "r"(a[2]), "r"(a[3]), "l"(db));
    else asm volatile("wgmma.mma_async.sync.aligned.m64n8k16.f32.bf16.bf16 "
        "{%0,%1,%2,%3}, "
        "{%4,%5,%6,%7}, %8, 0, 1, 1, 0;"
        : D4(=, 0) : "r"(a[0]), "r"(a[1]), "r"(a[2]), "r"(a[3]), "l"(db));
}
template <int SC> DEVI void wg_ss64a(float (&d)[32], uint64_t da, uint64_t db) {
    if (SC) asm volatile("wgmma.mma_async.sync.aligned.m64n64k16.f32.bf16.bf16 "
        "{%0,%1,%2,%3,%4,%5,%6,%7,%8,%9,%10,%11,%12,%13,%14,%15,%16,%17,%18,%19,%20,%21,%22,%23,%24,%25,%26,%27,%28,%29,%30,%31}, "
        "%32, %33, 1, 1, 1, 1, 0;"
        : D4(+, 0), D4(+, 4), D4(+, 8), D4(+, 12), D4(+, 16), D4(+, 20), D4(+, 24), D4(+, 28) : "l"(da), "l"(db));
    else asm volatile("wgmma.mma_async.sync.aligned.m64n64k16.f32.bf16.bf16 "
        "{%0,%1,%2,%3,%4,%5,%6,%7,%8,%9,%10,%11,%12,%13,%14,%15,%16,%17,%18,%19,%20,%21,%22,%23,%24,%25,%26,%27,%28,%29,%30,%31}, "
        "%32, %33, 0, 1, 1, 1, 0;"
        : D4(=, 0), D4(=, 4), D4(=, 8), D4(=, 12), D4(=, 16), D4(=, 20), D4(=, 24), D4(=, 28) : "l"(da), "l"(db));
}

#define G_ROWS 514
__device__ uint4 g_G[64 * G_ROWS * 8];
__device__ uint4 g_GN[64 * 8];
__device__ uint4 g_WN[1152];
#define FS_F2 196608
#define FS_TB (FS_F2 + 8192)
#define FS_NQ (FS_TB + 16384)
#define FS_BAR (FS_NQ + 128)
#define FS_NY (FS_NQ + 1024 + 128)
#define FS_TOTAL (FS_NQ + 3072)
#define F_THREADS 512

DEVI uint32_t cis(int j) {
    const float a = fmaf(__uint_as_float((((j + 1024) << 12) & 0x7FF000) | 0x3F800000), 6.283185307179586f, -9.42477796076938f);
    return pack2(__cosf(a), __sinf(a));
}
DEVI uint32_t cos2(int j0, int j1) {
    const float f = 6.283185307179586f / 2048.f;
    return pack2(__cosf((float)(((j0 + 1024) & 2047) - 1024) * f), __cosf((float)(((j1 + 1024) & 2047) - 1024) * f));
}
DEVI void twid(int j, float& c, float& s) {
    const float a = (float)(((j + 512) & 1023) - 512) * (6.283185307179586f / 1024.f);
    c = __cosf(a) * (1.f / 1024.f);
    s = __sinf(a) * (1.f / 1024.f);
}
template <bool B> struct Bool { static constexpr bool v = B; };
DEVI uint32_t opq(uint32_t& x, uint32_t zero) { OPQ(x); return x; }
DEVI uint32_t tidx() { uint32_t r; asm volatile("mov.u32 %0, %%tid.x;" : "=r"(r)); return r; }
DEVI void tma4d(uint32_t dst, const CUtensorMap* tm, uint32_t bar, int c0, int c1, int c2, int c3) {
    asm volatile("cp.async.bulk.tensor.4d.shared::cluster.global.mbarrier::complete_tx::bytes [%0], [%1, {%3, %4, %5, %6}], [%2];"
                 ::"r"(dst), "l"(tm), "r"(bar), "r"(c0), "r"(c1), "r"(c2), "r"(c3) : "memory");
}
DEVI void tma3s(const CUtensorMap* tm, uint32_t src, int c0, int c1, int c2) {
    asm volatile("cp.async.bulk.tensor.3d.global.shared::cta.bulk_group [%0, {%2, %3, %4}], [%1];" ::"l"(tm), "r"(src), "r"(c0), "r"(c1), "r"(c2) : "memory");
}
DEVI void tma4s(const CUtensorMap* tm, uint32_t src, int c0, int c1, int c2, int c3) {
    asm volatile("cp.async.bulk.tensor.4d.global.shared::cta.bulk_group [%0, {%2, %3, %4, %5}], [%1];"
                 ::"l"(tm), "r"(src), "r"(c0), "r"(c1), "r"(c2), "r"(c3) : "memory");
}
DEVI void bulk_commit() { asm volatile("cp.async.bulk.commit_group;" ::: "memory"); }
DEVI void fence_async() { asm volatile("fence.proxy.async;" ::: "memory"); }
DEVI void fence_smem() { asm volatile("fence.proxy.async.shared::cta;" ::: "memory"); }
DEVI void wgbar(uint32_t q) { asm volatile("bar.sync %0, 128;" ::"r"(q + 2) : "memory"); }
DEVI void grid_arrive(uint32_t* c, uint32_t n) { asm volatile("fence.proxy.async;\nred.release.gpu.global.inc.u32 [%0], %1;" ::"l"(c), "r"(n - 1) : "memory"); }
DEVI void grid_wait(uint32_t* c) {
    uint32_t v;
    int it = 0;
    do {
        asm volatile("ld.acquire.gpu.global.u32 %0, [%1];" : "=r"(v) : "l"(c) : "memory");
        if (++it > (1 << 22)) die(it);
    } while (v);
    fence_async();
}

template <bool INV, class S1, class S2>
DEVI void fft_rows(uint32_t grp, uint32_t q, const uint32_t (&F)[2][4], const float (&tc)[8], const float (&ts)[8], uint32_t so, float fx, uint32_t nq,
                   S1 sh1, S2 sh2) {
    float d[64];
    const uint64_t db = INV ? mkdesc(grp, 1024, 2048) : (mkdesc(grp, 2048, 512) ^ ((uint64_t)3 << 62));
    wg_fence();
    wg_rs128t<0>(d, F[0], db);
    wg_rs128t<1>(d, F[1], db + (INV ? 256 : 64));
    wg_commit();
    SF();
    sh1();
    float4 ny;
    if (INV) ny = lds128f(nq);
    wg_wait<0>();
    if (INV) { d[0] = fmaf(fx, ny.x, d[0]); d[16] = fmaf(fx, ny.y, d[16]); d[32] = fmaf(fx, ny.z, d[32]); d[48] = fmaf(fx, ny.w, d[48]); }
    uint32_t a[2][4][4];
    float e[2][INV ? 16 : 20];
    const uint64_t df = mkdesc(SB0 + FS_F2, 16, 1024);
#pragma unroll
    for (int s = 0; s < 2; s++) {
#pragma unroll
        for (int i = 0; i < 4; i++)
#pragma unroll
            for (int h = 0; h < 2; h++) {
                const float* x = d + (2 * s + h) * 16 + i * 4;
                a[s][i][h] = pack2(fmaf(x[2], ts[2 * i], x[0] * tc[2 * i]), fmaf(x[3], ts[2 * i + 1], x[1] * tc[2 * i + 1]));
                a[s][i][h + 2] = pack2(fmaf(-x[0], ts[2 * i], x[2] * tc[2 * i]), fmaf(-x[1], ts[2 * i + 1], x[3] * tc[2 * i + 1]));
            }
        wg_fence();
#pragma unroll
        for (int i = 0; i < 4; i++) {
            if constexpr (INV) { if (i == 0) wg_rs32<0>(e[s], a[s][i], df); else wg_rs32<1>(e[s], a[s][i], df + i * 2); }
            else { if (i == 0) wg_rs40<0>(e[s], a[s][i], df); else wg_rs40<1>(e[s], a[s][i], df + i * 2); }
        }
        wg_commit();
    }
    SF();
    sh2();
#pragma unroll
    for (int s = 0; s < 2; s++) {
        if (s == 0) wg_wait<1>(); else wg_wait<0>();
        float* x = e[s];
        if constexpr (!INV) {
            x[0] *= fx; x[1] *= fx; x[2] *= fx; x[3] *= fx;
            if (fx != 1.f) sts64(nq + s * 8, pack2(x[16], 0.f), pack2(x[18], 0.f));
        }
        const uint32_t o = grp + (INV ? so + s * 4096 : so ^ (s * 576));
#pragma unroll
        for (int b = 0; b < 2; b++)
            stsm4t(o + b * (INV ? 1024 : 4096), pack2(x[8 * b], x[8 * b + 1]), pack2(x[8 * b + 2], x[8 * b + 3]), pack2(x[8 * b + 4], x[8 * b + 5]),
                   pack2(x[8 * b + 6], x[8 * b + 7]));
    }
}

template <bool INV>
DEVI void fft_gen(uint32_t a, uint32_t n2) {
    const uint32_t tid = tidx(), x = ((tid >> 4) & 24) + (tid & 3), o = (tid & 4) * 128;
    if (INV) {
        const uint32_t r = (tid & 64) * 16 + (tid & 16) * 32 + (tid & 40) * 8 + n2;
        sts128(a + tid * 16, cis(o - r * x), cis(o - (r + 128) * x), cis(o - r * (x + 4)), cis(o - (r + 128) * (x + 4)));
    } else {
        const uint32_t r = 64 * x + n2, k = ((tid >> 2) & 24) + ((tid >> 3) & 3);
        sts128(a + tid * 16, cis(r * k + o), cis(r * (k + 4) + o), cis((r + 256) * k + o), cis((r + 256) * (k + 4) + o));
    }
}
template <bool INV, class S1>
DEVI void fft_cross(uint32_t buf, uint32_t q, uint32_t fa, uint32_t so, uint32_t nq, float (&n)[4], S1 sh1) {
    uint32_t F[4][4];
#pragma unroll
    for (int s = 0; s < 4; s++) { const uint4 v = lds128(fa + s * 2048); F[s][0] = v.x; F[s][1] = v.y; F[s][2] = v.z; F[s][3] = v.w; }
    float d[64];
    const uint64_t db = mkdesc(buf + q * 2048, 1024, 8192), dn = mkdesc(nq, 16, 1024);
    wg_fence();
#pragma unroll
    for (int s = 0; s < 4; s++) { if (s == 0) wg_rs128t<0>(d, F[s], db); else wg_rs128t<1>(d, F[s], db + s * 1024); }
#pragma unroll
    for (int s = 0; s < 4; s++) { if (s == 0) wg_rs8<0>(n, F[s], dn); else wg_rs8<1>(n, F[s], dn + s * 2); }
    wg_commit();
    SF();
    sh1();
    wg_wait<0>();
#pragma unroll
    for (int b = 0; b < 8; b++) {
        const uint32_t o = INV ? so ^ ((b >> 1) * 288 ^ (b & 1) * 32) : (so ^ ((b & 3) * 32)) + (b >> 2) * 1024;
        stsm4(buf + o, pack2(d[8 * b], d[8 * b + 1]), pack2(d[8 * b + 2], d[8 * b + 3]), pack2(d[8 * b + 4], d[8 * b + 5]), pack2(d[8 * b + 6], d[8 * b + 7]));
    }
}

template <bool ODD>
DEVI void fft_filter(uint32_t aw, const float (&e)[32], const float (&o)[32], uint32_t (&u)[4][4], uint32_t (&v)[4][4]) {
#pragma unroll
    for (int s = 0; s < 4; s++) {
        float y[2][2][4];
#pragma unroll
        for (int c = 0; c < 2; c++) {
            float f[4][2];
#pragma unroll
            for (int i = 0; i < 4; i++) {
                const uint32_t a = aw + (i * 32 + s * 8 + c) * 144, x = lds32(a);
                f[i][0] = ODD ? hi_f(x) : lo_f(x);
                f[i][1] = ODD ? lo_f(lds32(a + 4)) : hi_f(x);
            }
#pragma unroll
            for (int h = 0; h < 2; h++) {
                const int x = 8 * s + 2 * h + c;
                const float ar = e[x] + o[x], ai = e[x + 4] + o[x + 4], br = e[x] - o[x], bi = e[x + 4] - o[x + 4];
                const float yr = fmaf(-ai, f[2][h], ar * f[0][h]), yi = fmaf(ar, f[2][h], ai * f[0][h]);
                y[h][c][0] = fmaf(-bi, f[3][h], fmaf(br, f[1][h], yr));
                y[h][c][1] = fmaf(br, f[3][h], fmaf(bi, f[1][h], yi));
                y[h][c][2] = fmaf(2.f, yr, -y[h][c][0]);
                y[h][c][3] = fmaf(2.f, yi, -y[h][c][1]);
            }
        }
#pragma unroll
        for (int h = 0; h < 2; h++) {
            u[s][h] = pack2(y[h][0][0], y[h][1][0]); u[s][h + 2] = pack2(y[h][0][1], y[h][1][1]);
            v[s][h] = pack2(y[h][0][2], y[h][1][2]); v[s][h + 2] = pack2(y[h][0][3], y[h][1][3]);
        }
    }
}

__global__ void __launch_bounds__(F_THREADS, 1)
post_kernel(const __grid_constant__ CUtensorMap tmx, const __grid_constant__ CUtensorMap tmg1, const __grid_constant__ CUtensorMap tmg2,
           const __grid_constant__ CUtensorMap tmwr, const __grid_constant__ CUtensorMap tmwi, const __grid_constant__ CUtensorMap tmy,
           const bf16* __restrict__ wr, const bf16* __restrict__ wi, uint32_t* cnt, uint32_t zero, int nw) {
    extern __shared__ __align__(1024) uint8_t smem[];
    const uint32_t sb = SB0;
    if (smem_u32(smem) != sb) die(1 << 23);
    if (FDL) delay_until(clk(), FDL);
    const uint32_t tid = threadIdx.x, lane = tid & 31, g = lane >> 2, t = lane & 3, j8 = lane & 7, mat = lane >> 3;
    const uint32_t wi_ = __reduce_max_sync(0xFFFFFFFFu, tid >> 5), q = wi_ >> 2, w = wi_ & 3;
    const int cta = blockIdx.x;
    const int nt = cta < 64 ? (64 - cta + nw - 1) / nw : 0;
    const uint32_t bar = sb + FS_BAR;
    if (tid == 0) {
        for (int i = 0; i < 30; i++) mbar_init(bar + i * 8, i < 3 ? 4 : i < 6 ? 16 : i >= 14 && i < 18 ? 2 : 1);
        asm volatile("fence.mbarrier_init.release.cluster;" ::: "memory");
        fence_smem();
    }
    __syncthreads();
#define FT(n)
    FT(0);
#define N2(p) (2 * ((p) & 31) + ((p) >> 5))
#define WLOAD(tk, part) { \
        const uint32_t wd_ = sb + 131072 + q * 18432 + (part) * 9216, wb_ = bar + 112 + q * 8; \
        mbar_expect(wb_, 9216); \
        if ((tk) < 256) tma3d(wd_, (part) ? &tmwi : &tmwr, wb_, ((tk) & 63) * 64, (tk) >> 6, 0); \
        else asm volatile("cp.async.bulk.shared::cluster.global.mbarrier::complete_tx::bytes [%0], [%1], 9216, [%2];" \
                          ::"r"(wd_), "l"(g_WN + (part) * 576), "r"(wb_) : "memory"); }
#define GROW(tk) ((tk) < 256 ? ((tk) >> 5) * 64 + ((tk) & 7) * 8 + (((tk) >> 3) & 3) * 2 : 512)
#define DLOAD(tk, sl) { mbar_expect(bar + 48 + (sl) * 8, 16384); tma3d(sb + (sl) * 16384, &tmg2, bar + 48 + (sl) * 8, 0, GROW(tk), 0); }
#define IO(c) if (w == 3 && (c) && elect())
#define XLOAD1(i, bb) { const uint32_t xb_ = bar + 144 + (bb) * 32 + q * 8; mbar_expect(xb_, 16384); tma4d(sb + (bb) * 65536 + q * 16384, &tmx, xb_, 0, 0, q * 8, N2(cta + (i) * nw)); }
#define GLOAD3(i, bb) { mbar_expect(bar + (bb) * 8, q ? 16384 : 16512); tma3d(sb + (bb) * 65536 + q * 16384, &tmg1, bar + (bb) * 8, 0, q * 128, cta + (i) * nw); \
        if (q == 0) asm volatile("cp.async.bulk.shared::cluster.global.mbarrier::complete_tx::bytes [%0], [%1], 128, [%2];" \
                                 ::"r"(sb + FS_NQ + (bb) * 1024), "l"(g_GN + (cta + (i) * nw) * 8), "r"(bar + (bb) * 8) : "memory"); }
    for (int i = 0; i < 3; i++) IO(i < nt) XLOAD1(i, i);
    for (uint32_t x = tid; x < 40 * 32; x += 512) {
        const uint32_t n = x >> 5, m2 = mat * 8 + t * 2, ri = g & 1;
        const uint32_t c2 = ((n >> 1) & 1) + ((n >> 3) & 1) * 2 + (n & 4) + (n >> 4) * 8;
        const uint32_t v = cos2(m2 * c2 * 64 + ((n & 1) - ri) * 512, (m2 + 1) * c2 * 64 + ((n & 1) - ri) * 512);
        sts32(sb + FS_F2 + n * 128 + ((g ^ (n & 7)) << 4) + t * 4, n < 32 ? v : n == 32 && ri == 0 ? 0xBF003F00u : 0u);
    }
    float tc[8], ts[8];
    uint32_t F[2][4];
    uint32_t c1 = 16 * (w >> 1) + 2 * g + (w & 1);
#pragma unroll
    for (int i = 0; i < 8; i++) {
        twid(c1 * (8 * (i >> 1) + 2 * t + (i & 1)), tc[i], ts[i]);
        const uint32_t m1 = (i >> 1) * 8 + 2 * t;
        F[i >> 2][i & 3] = cos2(c1 * m1 * 64 + (i & 1) * 512, c1 * (m1 + 1) * 64 + (i & 1) * 512);
    }
    {
        const uint32_t kr = (2 * (mat & 1) + (j8 & 1)) ^ ((j8 >> 2) << 1);
        const uint32_t so1 = ((mat >> 1) + 2 * (j8 >> 2)) * 1024 + kr * 128 + (((((j8 >> 1) & 1) * 4 + w) ^ kr) << 4);
        const uint32_t so2 = (2 * w + (mat & 1)) * 8192 + q * 2048 + j8 * 128 + (((mat >> 1) ^ j8) << 4);
        uint32_t so = so1 << 16 | so2;
        const float fx = (tid & 127) == 0 ? 0.5f : 1.f;
        fft_gen<false>(sb + FS_TB, N2(cta));
        fence_smem();
        bsync<1, 512>();
        FT(1);
        int b = 0, bp = 2, ph = 0;
        if (nt) mwait(bar + 144 + q * 8, 0);
        __syncwarp();
        auto step = [&](auto first, auto last, const int i) {
            const uint32_t p = cta + i * nw, bn = 3 - b - bp, tb = (i & 1) * 8192;
            const uint32_t grp = sb + b * 65536 + q * 16384, nq = sb + FS_NQ + b * 1024 + q * 32;
            auto sa = [&]() {
                if constexpr (!decltype(first)::v) {
                    fence_smem();
                    __syncwarp();
                    if (elect()) mbar_arrive(bar + 24);
                }
                IO(i > 1) {
                    mwait(bar + 32, i & 1);
                    tma3s(&tmg1, sb + bn * 65536 + q * 16384, 0, q * 128, p - 2 * nw);
                    bulk_commit();
                }
            };
            auto sb_ = [&]() { if constexpr (!decltype(first)::v) mwait(bar + 24, (i - 1) & 1); };
            if constexpr (!decltype(last)::v) fft_rows<false>(grp, q, F, tc, ts, opq(so, zero) >> 16, fx, nq, sa, sb_);
            else { sa(); __syncwarp(); sb_(); __syncwarp(); }
            if constexpr (!decltype(first)::v) {
                float n[4];
                fft_cross<false>(sb + bp * 65536, q, sb + FS_TB + 8192 - tb + (((tidx() & 127) ^ (q & 1)) << 4), opq(so, zero) & 0xFFFF, sb + FS_NQ + bp * 1024, n, [&]() {
                    fft_gen<false>(sb + FS_TB + tb, N2(p));
                    IO(i >= 2 && i + 1 < nt) {
                        asm volatile("cp.async.bulk.wait_group.read 0;" ::: "memory");
                        XLOAD1(i + 1, bn);
                    }
                });
                if (q == 0) {
                    const uint32_t x = tidx();
                    bf16* z = (bf16*)(g_G + ((p - nw) * G_ROWS + 512) * 8) + (x & 4) * 16 + ((x >> 2) & 24) + ((x >> 3) & 3);
                    asm volatile("{\n.reg .pred p;\n.reg .b16 a, b;\nsetp.eq.u32 p, %2, 0;\nmov.b32 {a, b}, %1;\n@p st.global.u16 [%0], a;\n@p st.global.u16 [%0+8], b;\n}"
                                 ::"l"(z), "r"(pack2(n[0], n[2])), "r"(x & 3) : "memory");
                }
            }
            if constexpr (!decltype(last)::v) {
                fft_rows<false>(grp + 8192, q, F, tc, ts, opq(so, zero) >> 16, fx, nq + 16, [&]() {
                    if constexpr (!decltype(first)::v) {
                        fence_smem();
                        __syncwarp();
                        if (elect()) mbar_arrive(bar + 32);
                    }
                    if ((w == 1 || w == 2) && elect())
                        asm volatile("cp.async.bulk.prefetch.L2.global [%0], 8208;" ::"l"((w == 1 ? wr : wi) + (p * 4 + q) * 4104) : "memory");
                }, [&]() { if (i + 1 < nt) mwait(bar + 144 + bn * 32 + q * 8, bn ? ph : ph ^ 1); });
                bp = b;
                if (++b == 3) { b = 0; ph ^= 1; }
            }
        };
        if (nt) {
            step(Bool<true>(), Bool<false>(), 0);
#pragma unroll 1
            for (int i = 1; i < nt; i++) step(Bool<false>(), Bool<false>(), i);
            step(Bool<false>(), Bool<true>(), nt);
        }
        for (uint32_t x = cta * 512 + tid; x < 4096; x += nw * 512)
            ((bf16*)g_WN)[(x >> 5) * 72 + (x & 16) + (x & 7) * 2 + ((x >> 3) & 1)] = (x < 2048 ? wr : wi)[(x & 2047) * 513 + 512];
        FT(2);
        fence_async();
        bsync<1, 512>();
        IO(nt) { tma3s(&tmg1, sb + bp * 65536 + q * 16384, 0, q * 128, cta + (nt - 1) * nw); bulk_commit(); }
    }
    for (uint32_t x = tid; x < 128 * 32; x += 512) {
        const uint32_t n = (x >> 5) & 63, a = x & 31, k2 = (n >> 4) * 8 + (n & 7);
        sts32(sb + FS_TB + (x >> 5) * 128 + (((a >> 2) ^ (n & 7)) << 4) + (a & 3) * 4, cis((2 * a + (x >> 11)) * k2 * 32 + (n & 8) * 64));
    }
    fence_smem();
    bsync<1, 512>();
    IO(true) {
        asm volatile("cp.async.bulk.wait_group 0;" ::: "memory");
        grid_arrive(cnt, 4 * nw);
        grid_wait(cnt);
        const int tk = cta + q * nw;
        if (tk <= 256) { DLOAD(tk, q); WLOAD(tk, 0); WLOAD(tk, 1); }
    }
    __syncwarp();
    {
        const uint32_t lo = j8 * 128 + (((2 * w + (mat & 1)) ^ j8) << 4);
        const uint32_t aw = sb + 131072 + q * 18432 + t * 288 + w * 32 + g * 4;
        const uint64_t df = mkdesc(sb + FS_TB, 16, 1024);
        const uint64_t da = mkdesc(sb + q * 16384, 16, 1024);
        const uint32_t buf = sb + 65536 + q * 16384;
        int i = 0, tk = cta + q * nw;
        if (tk <= 256) mwait(bar + 48 + q * 8, 0);
        FT(3);
#pragma unroll 1
        for (; tk <= 256; tk += 4 * nw, i++) {
            const bool more = tk + 4 * nw <= 256;
            float e[32], o[32];
            wg_fence();
#pragma unroll
            for (int s = 0; s < 4; s++) { if (s == 0) wg_ss64a<0>(e, da, df); else wg_ss64a<1>(e, da + s * 128, df + s * 2); }
#pragma unroll
            for (int s = 0; s < 4; s++) { if (s == 0) wg_ss64a<0>(o, da + 512, df + 512); else wg_ss64a<1>(o, da + 512 + s * 128, df + 512 + s * 2); }
            wg_commit();
            SF();
            if (i > 0) {
                fence_smem();
                wgbar(q);
                IO(true) { tma3s(&tmg2, buf, 0, GROW(tk - 4 * nw), 0); bulk_commit(); }
            }
            if (w == 2 && more && elect()) mbar_expect(bar + 48 + q * 8, 16384);
            const int gr = GROW(tk + 4 * nw);
            mwait(bar + 112 + q * 8, i & 1);
            wg_wait<0>();
            if (w == 2 && more && elect()) tma3d(sb + q * 16384, &tmg2, bar + 48 + q * 8, 0, gr, 0);
            uint32_t u[4][4], v[4][4];
            if (tk & 8) fft_filter<true>(aw + (tk & 48) / 4, e, o, u, v);
            else fft_filter<false>(aw + (tk & 48) / 4, e, o, u, v);
            wg_fence();
#pragma unroll
            for (int s = 0; s < 4; s++) { if (s == 0) wg_rs64t<0>(e, u[s], df); else wg_rs64t<1>(e, u[s], df + s * 128); }
#pragma unroll
            for (int s = 0; s < 4; s++) { if (s == 0) wg_rs64t<0>(o, v[s], df + 512); else wg_rs64t<1>(o, v[s], df + 512 + s * 128); }
            wg_commit();
            SF();
            IO(true) asm volatile("cp.async.bulk.wait_group.read 0;" ::: "memory");
            wgbar(q);
            if (more) {
                if ((w == 1 || w == 2) && elect()) WLOAD(tk + 4 * nw, w - 1);
                mwait(bar + 48 + q * 8, (i + 1) & 1);
            }
            wg_wait<0>();
#pragma unroll
            for (int s = 0; s < 4; s++) {
                const uint32_t a = buf + (mat >> 1) * 1024 + lo + s * 2048;
                stsm4t(a, pack2(e[8 * s], e[8 * s + 1]), pack2(e[8 * s + 2], e[8 * s + 3]), pack2(e[8 * s + 4], e[8 * s + 5]), pack2(e[8 * s + 6], e[8 * s + 7]));
                stsm4t(a + 8192, pack2(o[8 * s], o[8 * s + 1]), pack2(o[8 * s + 2], o[8 * s + 3]), pack2(o[8 * s + 4], o[8 * s + 5]), pack2(o[8 * s + 6], o[8 * s + 7]));
            }
            if (tk == 256 && w < 2) {
                uint32_t* z = (uint32_t*)g_GN + t * 32 + w * 16 + g;
#pragma unroll
                for (int s = 0; s < 16; s++) {
                    z[(s >> 1) * 128 + (s & 1) * 8] = pack2(e[2 * s], e[2 * s + 1]);
                    z[(s >> 1) * 128 + (s & 1) * 8 + 1024] = pack2(o[2 * s], o[2 * s + 1]);
                }
                fence_async();
            }
        }
        fence_smem();
        wgbar(q);
        IO(true) {
            if (i > 0) { tma3s(&tmg2, buf, 0, GROW(tk - 4 * nw), 0); bulk_commit(); }
            asm volatile("cp.async.bulk.wait_group 0;" ::: "memory");
            grid_arrive(cnt + 1, 4 * nw);
        }
    }
    FT(4);
    bsync<1, 512>();
    {
        for (uint32_t n = wi_; n < 32; n += 16) {
            const uint32_t cl = (mat >> 1) * 16 + t * 4 + (mat & 1), mh = ((n >> 3) & 1) + (n & 7) * 2 + (n & 16);
            sts32(sb + FS_F2 + n * 128 + ((g ^ (n & 7)) << 4) + t * 4, cos2(cl * mh * 64 + (g & 1) * 512, (cl + 2) * mh * 64 + (g & 1) * 512));
        }
        fence_smem();
        c1 = 8 * w + g;
#pragma unroll
        for (int i = 0; i < 8; i++) {
            twid(-c1 * (16 * (i >> 2) + 4 * t + 2 * (i & 1) + ((i >> 1) & 1)), tc[i], ts[i]);
            F[i >> 2][i & 3] = cis((i & 1) * 512 - c1 * ((i >> 1) * 4 + (t ^ (q & 1))) * 64);
        }
        const uint32_t kr = (j8 & 1) ^ ((j8 >> 2) << 1);
        const uint32_t so2 = ((w >> 1) * 4 + (j8 >> 2) * 2 + (w & 1)) * 8192 + (2 * q + (mat & 1)) * 1024 + kr * 128 + (((((j8 >> 1) & 1) * 4 + (mat >> 1)) ^ kr) << 4);
        const uint32_t so1 = (mat & 1) * 2048 + j8 * 128 + ((((mat >> 1) * 4 + w) ^ j8) << 4);
        uint32_t so = so1 << 16 | so2;
        const float fx = t ? 0.f : (g & 1) ? -1.f : 1.f;
        fft_gen<true>(sb + FS_TB, N2(cta));
        bsync<1, 512>();
        IO(true) grid_wait(cnt + 1);
        for (int i = 0; i < 3; i++) IO(i < nt) GLOAD3(i, i);
        __syncwarp();
        int b = 0, bp = 2, ph = 0;
        auto step = [&](auto first, auto last, const int i) {
            const uint32_t p = cta + i * nw, bn = 3 - b - bp, tb = (i & 1) * 8192;
            const uint32_t grp = sb + bp * 65536 + q * 16384, ny = sb + FS_NY + bp * 128 + q * 32;
            auto sb_ = [&]() { if constexpr (!decltype(last)::v) mwait(bar + b * 8, ph); };
            if constexpr (!decltype(first)::v) {
                fft_rows<true>(grp, q, F, tc, ts, opq(so, zero) >> 16, fx, ny, [&]() {
                    if (i > 1) {
                        fence_smem();
                        wgbar(q);
                        IO(true) { tma4s(&tmy, sb + bn * 65536 + q * 16384, 0, 0, q * 8, N2(p - 2 * nw)); bulk_commit(); }
                    }
                }, sb_);
            } else { sb_(); __syncwarp(); }
            if constexpr (decltype(first)::v) FT(5);
            if constexpr (!decltype(last)::v) {
                float n[4];
                fft_cross<true>(sb + b * 65536, q, sb + FS_TB + tb + (tidx() & 127) * 16, opq(so, zero) & 0xFFFF, sb + FS_NQ + b * 1024, n, [&]() {
                    fft_gen<true>(sb + FS_TB + 8192 - tb, N2(p + nw));
                    IO(i >= 2 && i + 1 < nt) {
                        asm volatile("cp.async.bulk.wait_group.read 0;" ::: "memory");
                        GLOAD3(i + 1, bn);
                    }
                });
                if (q == 0) {
                    const uint32_t x = tidx(), a = sb + FS_NY + b * 128 + (x & 64) + (x & 16) * 2 + ((x & 40) >> 1);
                    if ((x & 7) == 0) { sts32f(a, n[0]); sts32f(a + 8, n[2]); }
                }
            }
            auto sc = [&]() {
                if constexpr (!decltype(last)::v) {
                    fence_smem();
                    __syncwarp();
                    if (elect()) mbar_arrive(bar + 24);
                }
            };
            auto sd = [&]() { if constexpr (!decltype(last)::v) mwait(bar + 24, (nt + i) & 1); };
            if constexpr (!decltype(first)::v) fft_rows<true>(grp + 8192, q, F, tc, ts, opq(so, zero) >> 16, fx, ny + 16, sc, sd);
            else { sc(); __syncwarp(); sd(); __syncwarp(); }
            if constexpr (!decltype(last)::v) {
                bp = b;
                if (++b == 3) { b = 0; ph ^= 1; }
            }
        };
        if (nt) {
            step(Bool<true>(), Bool<false>(), 0);
#pragma unroll 1
            for (int i = 1; i < nt; i++) step(Bool<false>(), Bool<false>(), i);
            step(Bool<false>(), Bool<true>(), nt);
        }
        fence_smem();
        wgbar(q);
        IO(nt) { tma4s(&tmy, sb + bp * 65536 + q * 16384, 0, 0, q * 8, N2(cta + (nt - 1) * nw)); bulk_commit(); }
        FT(6);
        IO(true) asm volatile("cp.async.bulk.wait_group 0;" ::: "memory");
    }
}

typedef CUresult (*EncodeFn)(CUtensorMap*, CUtensorMapDataType, cuuint32_t, void*, const cuuint64_t*, const cuuint64_t*,
                             const cuuint32_t*, const cuuint32_t*, CUtensorMapInterleave, CUtensorMapSwizzle,
                             CUtensorMapL2promotion, CUtensorMapFloatOOBfill);

static void make_map(EncodeFn enc, CUtensorMap* m, const void* ptr, int rank, const cuuint64_t* dims, const cuuint64_t* strides,
                     const cuuint32_t* box, CUtensorMapSwizzle sw = CU_TENSOR_MAP_SWIZZLE_128B) {
    cuuint32_t es[4] = {1, 1, 1, 1};
    CUresult r = enc(m, CU_TENSOR_MAP_DATA_TYPE_BFLOAT16, rank, (void*)ptr, dims, strides, box, es, CU_TENSOR_MAP_INTERLEAVE_NONE,
                     sw, CU_TENSOR_MAP_L2_PROMOTION_L2_256B, CU_TENSOR_MAP_FLOAT_OOB_FILL_NONE);
    if (r != CUDA_SUCCESS) fprintf(stderr, "tensor map encode failed: %d\n", (int)r);
}

extern "C" void kernel_launch(void* const* d_in, const int* in_sizes, int n_in, void* d_out, int out_size) {
    const bf16* A_x = (const bf16*)d_in[0];
    const bf16* A_mem0 = (const bf16*)d_in[1];
    const bf16* A_Wq = (const bf16*)d_in[2];
    const bf16* A_Wk = (const bf16*)d_in[3];
    const bf16* A_Wv = (const bf16*)d_in[4];
    const bf16* A_Wo = (const bf16*)d_in[5];
    const bf16* B_x = (const bf16*)d_in[7];
    const bf16* B_wr = (const bf16*)d_in[8];
    const bf16* B_wi = (const bf16*)d_in[9];
    bf16* out = (bf16*)d_out;

    static EncodeFn enc = nullptr;
    static void *pxs = nullptr, *pg = nullptr;
    static int ncl = 64;
    if (!enc) {
        cudaDriverEntryPointQueryResult qr;
        void* fn = nullptr;
        cudaGetDriverEntryPoint("cuTensorMapEncodeTiled", &fn, cudaEnableDefault, &qr);
        enc = (EncodeFn)fn;
        cudaFuncSetAttribute(chain_kernel, cudaFuncAttributeMaxDynamicSharedMemorySize, SM_TOTAL);
        cudaFuncSetAttribute(post_kernel, cudaFuncAttributeMaxDynamicSharedMemorySize, FS_TOTAL);
        cudaGetSymbolAddress(&pxs, g_xs);
        cudaGetSymbolAddress(&pg, g_G);
        cudaLaunchConfig_t lc = {};
        cudaLaunchAttribute at;
        at.id = cudaLaunchAttributeClusterDimension;
        at.val.clusterDim.x = 2; at.val.clusterDim.y = 1; at.val.clusterDim.z = 1;
        lc.gridDim = dim3(132); lc.blockDim = dim3(384); lc.dynamicSmemBytes = SM_TOTAL; lc.attrs = &at; lc.numAttrs = 1;
        int nc = 0;
        if (cudaOccupancyMaxActiveClusters(&nc, chain_kernel, &lc) == cudaSuccess && nc > 64) ncl = nc < 66 ? nc : 66;
    }
    CUtensorMap tmq, tmk, tmv, tmo, tmx, tmb, tmy;
    {
        cuuint64_t d[3] = {64, DM, HD / 64}, st[2] = {HD * 2, 128};
        cuuint32_t bx[3] = {64, 64, 2};
        make_map(enc, &tmq, A_Wq, 3, d, st, bx);
        make_map(enc, &tmk, A_Wk, 3, d, st, bx);
        make_map(enc, &tmv, A_Wv, 3, d, st, bx);
    }
    {
        cuuint64_t d[2] = {DM, HD}, st[1] = {DM * 2};
        cuuint32_t bx[2] = {64, 16}, bx1[2] = {64, 128}, bx2[3] = {64, 64, 2};
        make_map(enc, &tmo, A_Wo, 2, d, st, bx1);
        cuuint64_t d2[3] = {64, HD, DM / 64}, st2[2] = {DM * 2, 128}, d3[2] = {DM, SEQ}, st3[1] = {DM * 4};
        make_map(enc, &tmb, A_Wo, 3, d2, st2, bx2);
        make_map(enc, &tmy, out, 2, d3, st3, bx);
    }
    {
        cuuint64_t d[3] = {64, SEQ, DM / 64}, st[2] = {DM * 2, 128};
        cuuint32_t bx[3] = {64, 8, 4};
        make_map(enc, &tmx, A_x, 3, d, st, bx);
    }
    CUtensorMap fx, fg1, fg2, fwr, fwi, fy;
    {
        cuuint64_t d[4] = {32, 32, 32, 64}, st[3] = {64, 64 * DM * 2, DM * 2};
        cuuint32_t bx[4] = {32, 32, 8, 1};
        make_map(enc, &fx, B_x, 4, d, st, bx, CU_TENSOR_MAP_SWIZZLE_64B);
        cuuint64_t d2[4] = {64, 16, 32, 64}, st2[3] = {128, 64 * 4096, 4096};
        cuuint32_t bx2[4] = {64, 16, 8, 1};
        make_map(enc, &fy, out + DM, 4, d2, st2, bx2);
    }
    {
        cuuint64_t d[3] = {64, G_ROWS, 64}, st[2] = {128, G_ROWS * 128};
        cuuint32_t bx[3] = {64, 128, 1}, bx2[3] = {64, 2, 64};
        make_map(enc, &fg1, pg, 3, d, st, bx);
        make_map(enc, &fg2, pg, 3, d, st, bx2);
        cuuint64_t d2[3] = {8 * 513, 4, 64}, st2[2] = {8 * 513 * 2, 32 * 513 * 2};
        cuuint32_t bx3[3] = {72, 1, 64};
        make_map(enc, &fwr, B_wr, 3, d2, st2, bx3, CU_TENSOR_MAP_SWIZZLE_NONE);
        make_map(enc, &fwi, B_wi, 3, d2, st2, bx3, CU_TENSOR_MAP_SWIZZLE_NONE);
    }
    cudaStream_t st = cudaStreamPerThread;
    const uint64_t xs = ((uint64_t)pxs + XS_BYTES - 1) & ~(uint64_t)(XS_BYTES - 1);
    chain_kernel<<<2 * ncl, 384, SM_TOTAL, st>>>(tmq, tmk, tmv, tmo, tmx, tmb, tmy, A_mem0, A_x, (uint32_t)xs, (uint32_t)(xs >> 32), 0u, NSEG, out);
    int nw = ncl == 66 ? 4 : 64;
    cudaLaunchConfig_t lc = {};
    cudaLaunchAttribute at;
    at.id = cudaLaunchAttributeProgrammaticStreamSerialization;
    at.val.programmaticStreamSerializationAllowed = 1;
    lc.gridDim = dim3(nw); lc.blockDim = dim3(F_THREADS); lc.dynamicSmemBytes = FS_TOTAL; lc.stream = st; lc.attrs = &at; lc.numAttrs = 1;
    cudaLaunchKernelEx(&lc, post_kernel, fx, fg1, fg2, fwr, fwi, fy, B_wr, B_wi, (uint32_t*)(xs + XO_TK + 256), 0u, nw);
}
```
